```python
import torch

def _softmax(x, axis=-1):
    return torch.softmax(x, dim=axis)

def _gelu(x):
    return torch.nn.functional.gelu(x, approximate='tanh')

def _silu(x):
    return torch.nn.functional.silu(x)

def _sigmoid(x):
    return torch.sigmoid(x)

def _layernorm(x, axis=-1, eps=1e-05):
    m = x.mean(dim=axis, keepdim=True)
    v = x.var(dim=axis, keepdim=True, unbiased=False)
    return (x - m) / torch.sqrt(v + eps)

def _scatter_add(tgt, idx, src, axis=0):
    return tgt.clone().index_add_(axis, idx, src)

def _segment_sum(src, seg, n):
    out = torch.zeros((n,) + src.shape[1:], dtype=src.dtype)
    return out.index_add_(0, seg, src)

def _pad(x, pw):
    flat = tuple((v for pair in reversed(pw) for v in pair))
    return torch.nn.functional.pad(x, flat)
kernel_name = 'adaLN_cond__sliding_local_dilated__glu_gated_glu__prompt'

def setup_inputs():

    _w = lambda a: (lambda t: t.to(torch.bfloat16) if t.is_floating_point() else t)(torch.as_tensor(a))

    def _A_setup():
        B, S, D = (1, 2048, 1024)
        return {'x': _w((lambda *s: torch.randn(*s, dtype=torch.bfloat16) * 0.05)(B, S, D)), 'wqkv': _w((lambda *s: torch.randn(*s, dtype=torch.bfloat16) * 0.05)(D, 3 * D)), 'wo': _w((lambda *s: torch.randn(*s, dtype=torch.bfloat16) * 0.05)(D, D))}
    _A_in = _A_setup()

    def _B_setup():
        B, S, D, F = (1, 2048, 1024, 3584)
        return {'x': _w((lambda *s: torch.randn(*s, dtype=torch.bfloat16) * 0.05)(B, S, D)), 'w_gate': _w((lambda *s: torch.randn(*s, dtype=torch.bfloat16) * 0.05)(D, F)), 'w_up': _w((lambda *s: torch.randn(*s, dtype=torch.bfloat16) * 0.05)(D, F)), 'w_down': _w((lambda *s: torch.randn(*s, dtype=torch.bfloat16) * 0.05)(F, D))}
    _B_in = _B_setup()
    return {'A_x': _A_in['x'], 'A_wqkv': _A_in['wqkv'], 'A_wo': _A_in['wo'], 'B_x': _B_in['x'], 'B_w_gate': _B_in['w_gate'], 'B_w_up': _B_in['w_up'], 'B_w_down': _B_in['w_down'], 'c': _w((lambda *s: torch.randn(*s, dtype=torch.bfloat16) * 0.1)(1, 1024) * 8.0), 'w_mod': _w((lambda *s: torch.randn(*s, dtype=torch.bfloat16) * 0.1)(1024, 6 * 1024) * 1024 ** (-0.5) * 8.0)}

def reference(A_x, A_wqkv, A_wo, B_x, B_w_gate, B_w_up, B_w_down, c, w_mod):

    def _A_ref(x, wqkv, wo):
        B, S, D = x.shape
        H = 32
        Dh = D // H
        W, dil = (8, 2)
        qkv = (lambda x, *d: x.permute(*d))((x @ wqkv).reshape(B, S, 3, H, Dh), 2, 0, 3, 1, 4)
        q, k, v = (qkv[0], qkv[1], qkv[2])
        scale = Dh ** (-0.5)
        pos = torch.arange(S)
        off = torch.arange(W) * dil
        idx = pos[:, None] - off[None, :]
        mask = idx >= 0
        idx_c = torch.where(mask, idx, 0).reshape(-1)
        kg = k[:, :, idx_c, :].reshape(B, H, S, W, Dh)
        vg = v[:, :, idx_c, :].reshape(B, H, S, W, Dh)
        logits = torch.einsum('bhsd,bhswd->bhsw', q, kg) * scale
        logits = torch.where(mask[None, None, :, :], logits, -1000000000.0)
        attn = _softmax(logits, axis=-1)
        o = torch.einsum('bhsw,bhswd->bhsd', attn, vg)
        return (lambda x, *d: x.permute(*d))(o, 0, 2, 1, 3).reshape(B, S, D) @ wo

    def _B_ref(x, w_gate, w_up, w_down):
        g = torch.einsum('bsd,df->bsf', x, w_gate)
        u = torch.einsum('bsd,df->bsf', x, w_up)
        h = _sigmoid(g) * u
        return torch.einsum('bsf,fd->bsd', h, w_down)
    x = A_x
    mod = (_silu(c) @ w_mod).reshape(c.shape[0], 6, 1, -1)
    sa, ca, ga, sb, cb, gb = (mod[:, 0].clone(), mod[:, 1].clone(), mod[:, 2].clone(), mod[:, 3].clone(), mod[:, 4].clone(), mod[:, 5].clone())
    h = _layernorm(x, axis=-1) * (1 + ca) + sa
    x = x + ga * _A_ref(h, A_wqkv, A_wo)
    h = _layernorm(x, axis=-1) * (1 + cb) + sb
    x = x + gb * _B_ref(h, B_w_gate, B_w_up, B_w_down)
    return x
```

```cpp
#include <cuda_runtime.h>
#include <cuda_bf16.h>
#include <cuda.h>
#include <stdint.h>
#include <stddef.h>

#define LAG 3
#define LAGS 3
#define LAGW 3
#define LAGD 3
#define LAGQ 4
#define SIGAT 1
#define MIDW 8
#define PFWO 14
#define FLAGRED 1
#define FS 1
#define GFENCE 0
#define AGO 7
#define AGW 6
#define LAGSIG 1
#define ONEP 1
#define KDEBUG 0

namespace {

constexpr int S_ = 2048, D_ = 1024, F_ = 3584;
constexpr int NCTA = 132;
constexpr int NSLOT = 6;
constexpr uint32_t SLOT = 32768;
constexpr uint32_t OFF_STG = NSLOT * SLOT;
constexpr uint32_t OFF_BAR = OFF_STG + 32768;
constexpr uint32_t OFF_PAR = OFF_BAR + 512;
constexpr uint32_t OFF_TAB = OFF_PAR + 768;
constexpr uint32_t OFF_TL = OFF_PAR + 2048;
constexpr uint32_t SMEM_BYTES = OFF_TL + (KDEBUG ? 512 : 0);
constexpr uint32_t P3_SLOT1 = (32 + 16 + 32) % NSLOT, P3_SLOT0 = (P3_SLOT1 + 1) % NSLOT;

constexpr int ST_H1 = 1, ST_O = 2, ST_H2 = 3, ST_H = 4, FL_DONE = 16 * 32 * FS, FL_LN2 = FL_DONE + 1;

struct Maps {
    CUtensorMap h1h, h1s, o, h2h, h2l, h2s, hb, wqkv, wo, wg, wu, wd, wmod, wm8, x, x1, out;
};

struct Mail {
    uint32_t flags[16 * 32 * FS + 32];
    uint2 mod[6 * D_ / 2];
    uint4 mod1[8 * 512];
    uint4 st1[8 * S_];
    uint32_t par2[D_];
    uint4 halo[128 * 512];
};
struct Ptrs { const __nv_bfloat16* c; Mail* mail; };

__device__ __align__(128) Mail g_mail;
__device__ __align__(128) __nv_bfloat16 g_h1[S_ * D_];
__device__ __align__(128) __nv_bfloat16 g_o[S_ * D_];
__device__ __align__(128) __nv_bfloat16 g_hb[S_ * F_];
#define TL(i) do {} while (0)
#define TC(i) do {} while (0)
#define TS(g, which) do {} while (0)

#define PS(i) do {} while (0)
__device__ __forceinline__ uint32_t smem_u32(const void* p) { return (uint32_t)__cvta_generic_to_shared(p); }
__device__ __forceinline__ void mbar_init(uint32_t bar, uint32_t cnt) { asm volatile("mbarrier.init.shared::cta.b64 [%0], %1;" :: "r"(bar), "r"(cnt) : "memory"); }
__device__ __forceinline__ void mbar_expect_tx(uint32_t bar, uint32_t bytes) { asm volatile("mbarrier.arrive.expect_tx.shared::cta.b64 _, [%0], %1;" :: "r"(bar), "r"(bytes) : "memory"); }
__device__ __forceinline__ void mbar_arrive(uint32_t bar) { asm volatile("mbarrier.arrive.shared::cta.b64 _, [%0];" :: "r"(bar) : "memory"); }
__device__ __forceinline__ void mbar_arrive_cta(uint32_t bar, uint32_t cta) {
    asm volatile("{\n.reg .b32 r;\nmapa.shared::cluster.u32 r, %0, %1;\nmbarrier.arrive.shared::cluster.b64 _, [r];\n}" :: "r"(bar), "r"(cta) : "memory");
}
__device__ __forceinline__ void mbar_wait(uint32_t bar, uint32_t parity) {
    asm volatile("{\n.reg .pred p;\n.reg .u32 n;\nmov.u32 n, 0;\n"
        "W_LOOP:\nmbarrier.try_wait.parity.shared::cta.b64 p, [%0], %1;\n@p bra W_DONE;\n"
        "add.u32 n, n, 1;\nsetp.lt.u32 p, n, 0x400000;\n@p bra W_LOOP;\ntrap;\nW_DONE:\n}" :: "r"(bar), "r"(parity) : "memory");
}
__device__ __forceinline__ void mbar_wait2(uint32_t b0, uint32_t b1, uint32_t parity) {
    asm volatile("{\n.reg .pred p, q;\n.reg .u32 n;\nmov.u32 n, 0;\n"
        "W_LOOP:\nmbarrier.try_wait.parity.shared::cta.b64 p, [%0], %2;\nmbarrier.try_wait.parity.shared::cta.b64 q, [%1], %2;\nand.pred p, p, q;\n@p bra W_DONE;\n"
        "add.u32 n, n, 1;\nsetp.lt.u32 p, n, 0x400000;\n@p bra W_LOOP;\ntrap;\nW_DONE:\n}" :: "r"(b0), "r"(b1), "r"(parity) : "memory");
}
__device__ __forceinline__ bool mbar_test(uint32_t bar, uint32_t parity) {
    uint32_t r; asm volatile("{\n.reg .pred p;\nmbarrier.test_wait.parity.shared::cta.b64 p, [%1], %2;\nselp.u32 %0, 1, 0, p;\n}" : "=r"(r) : "r"(bar), "r"(parity) : "memory"); return r;
}
__device__ __forceinline__ bool mbar_test2(uint32_t b0, uint32_t b1, uint32_t parity) {
    uint32_t r;
    asm volatile("{\n.reg .pred p, q;\nmbarrier.test_wait.parity.shared::cta.b64 p, [%1], %3;\nmbarrier.test_wait.parity.shared::cta.b64 q, [%2], %3;\n"
        "and.pred p, p, q;\nselp.u32 %0, 1, 0, p;\n}" : "=r"(r) : "r"(b0), "r"(b1), "r"(parity) : "memory");
    return r;
}
__device__ __forceinline__ void tma_load3(uint32_t dst, const CUtensorMap* m, int c0, int c1, uint32_t bar) {
    asm volatile("cp.async.bulk.tensor.3d.shared::cluster.global.mbarrier::complete_tx::bytes [%0], [%1, {%3, %4, %5}], [%2];"
        :: "r"(dst), "l"(m), "r"(bar), "r"(c0), "r"(c1), "r"(0) : "memory");
}
__device__ __forceinline__ void tma_store3(const CUtensorMap* m, int c0, int c1, uint32_t src) {
    asm volatile("cp.async.bulk.tensor.3d.global.shared::cta.bulk_group [%0, {%2, %3, %4}], [%1];" :: "l"(m), "r"(src), "r"(c0), "r"(c1), "r"(0) : "memory");
}
__device__ __forceinline__ void tma_load(uint32_t dst, const CUtensorMap* m, int c0, int c1, uint32_t bar) {
    asm volatile("cp.async.bulk.tensor.2d.shared::cluster.global.mbarrier::complete_tx::bytes [%0], [%1, {%3, %4}], [%2];"
        :: "r"(dst), "l"(m), "r"(bar), "r"(c0), "r"(c1) : "memory");
}
__device__ __forceinline__ void tma_load_mc(uint32_t dst, const CUtensorMap* m, int c0, int c1, uint32_t bar) {
    asm volatile("cp.async.bulk.tensor.2d.shared::cluster.global.mbarrier::complete_tx::bytes.multicast::cluster.L2::cache_hint [%0], [%1, {%3, %4}], [%2], %5, %6;"
        :: "r"(dst), "l"(m), "r"(bar), "r"(c0), "r"(c1), "h"((uint16_t)3), "l"(0x12F0000000000000ull) : "memory");
}
__device__ __forceinline__ void tma_prefetch(const CUtensorMap* m, int c0, int c1) {
    asm volatile("cp.async.bulk.prefetch.tensor.2d.L2.global [%0, {%1, %2}];" :: "l"(m), "r"(c0), "r"(c1) : "memory");
}
__device__ __forceinline__ void tma_store(const CUtensorMap* m, int c0, int c1, uint32_t src) {
    asm volatile("cp.async.bulk.tensor.2d.global.shared::cta.bulk_group [%0, {%2, %3}], [%1];" :: "l"(m), "r"(src), "r"(c0), "r"(c1) : "memory");
}
__device__ __forceinline__ void bulk_commit() { asm volatile("cp.async.bulk.commit_group;" ::: "memory"); }
__device__ __forceinline__ void bulk_wait_read() { asm volatile("cp.async.bulk.wait_group.read 0;" ::: "memory"); }
__device__ __forceinline__ void bulk_wait_all() { asm volatile("cp.async.bulk.wait_group 0;" ::: "memory"); }
__device__ __forceinline__ void fence_async_smem() { asm volatile("fence.proxy.async.shared::cta;" ::: "memory"); }
__device__ __forceinline__ void fence_async_global() { if (GFENCE) asm volatile("fence.proxy.async.global;" ::: "memory"); }
__device__ __forceinline__ void prefetch_map(const CUtensorMap* m) { asm volatile("prefetch.tensormap [%0];" :: "l"(m) : "memory"); }
__device__ __forceinline__ void wg_fence() { asm volatile("wgmma.fence.sync.aligned;" ::: "memory"); }
__device__ __forceinline__ void wg_commit() { asm volatile("wgmma.commit_group.sync.aligned;" ::: "memory"); }
template <int N> __device__ __forceinline__ void wg_wait() { asm volatile("wgmma.wait_group.sync.aligned %0;" :: "n"(N) : "memory"); }
__device__ __forceinline__ void bar_sync(int id, int n) { asm volatile("bar.sync %0, %1;" :: "r"(id), "r"(n) : "memory"); }
__device__ __forceinline__ void bar_arrive(int id, int n) { asm volatile("bar.arrive %0, %1;" :: "r"(id), "r"(n) : "memory"); }
__device__ __forceinline__ void flag_add(uint32_t* f) { asm volatile("red.relaxed.gpu.global.add.u32 [%0], 1;" :: "l"(f) : "memory"); }
__device__ __forceinline__ void flag_set(uint32_t* f, uint32_t v) { asm volatile("red.relaxed.gpu.global.max.u32 [%0], %1;" :: "l"(f), "r"(v) : "memory"); }
__device__ __forceinline__ uint32_t flag_get(const uint32_t* f) { uint32_t v; asm volatile("ld.relaxed.gpu.global.u32 %0, [%1];" : "=r"(v) : "l"(f) : "memory"); return v; }
__device__ __forceinline__ uint32_t d16(uint32_t addr) { return (addr & 0x3FFFF) >> 4; }
__device__ __forceinline__ uint64_t mk_desc(uint32_t a16, uint32_t off, uint32_t lbo, uint32_t sbo, uint32_t swz) {
    const uint32_t lo = a16 + (off >> 4) + ((lbo >> 4) << 16), hi = (sbo >> 4) | (swz << 30);
    return ((uint64_t)hi << 32) | lo;
}
__device__ __forceinline__ uint32_t pack2(float lo, float hi) {
    uint32_t r; asm("cvt.rn.bf16x2.f32 %0, %1, %2;" : "=r"(r) : "f"(hi), "f"(lo)); return r;
}
__device__ __forceinline__ uint32_t hfma2_bf16(uint32_t a, uint32_t b, uint32_t c) {
    uint32_t r; asm("fma.rn.bf16x2 %0, %1, %2, %3;" : "=r"(r) : "r"(a), "r"(b), "r"(c)); return r;
}
__device__ __forceinline__ float bf_lo(uint32_t v) { return __uint_as_float(v << 16); }
__device__ __forceinline__ float bf_hi(uint32_t v) { return __uint_as_float(v & 0xFFFF0000u); }
__device__ __forceinline__ float bf_round(float x) { return __bfloat162float(__float2bfloat16_rn(x)); }
__device__ __forceinline__ void stsm4(uint32_t addr, uint32_t r0, uint32_t r1, uint32_t r2, uint32_t r3) {
    asm volatile("stmatrix.sync.aligned.m8n8.x4.shared.b16 [%0], {%1, %2, %3, %4};" :: "r"(addr), "r"(r0), "r"(r1), "r"(r2), "r"(r3) : "memory");
}
__device__ __forceinline__ void stsm4t(uint32_t addr, uint32_t r0, uint32_t r1, uint32_t r2, uint32_t r3) {
    asm volatile("stmatrix.sync.aligned.m8n8.x4.trans.shared.b16 [%0], {%1, %2, %3, %4};" :: "r"(addr), "r"(r0), "r"(r1), "r"(r2), "r"(r3) : "memory");
}
__device__ __forceinline__ uint32_t movm(uint32_t a) { uint32_t d; asm volatile("movmatrix.sync.aligned.m8n8.trans.b16 %0, %1;" : "=r"(d) : "r"(a)); return d; }
__device__ __forceinline__ void ldsm4(uint32_t addr, uint32_t& r0, uint32_t& r1, uint32_t& r2, uint32_t& r3) {
    asm volatile("ldmatrix.sync.aligned.m8n8.x4.shared.b16 {%0, %1, %2, %3}, [%4];" : "=r"(r0), "=r"(r1), "=r"(r2), "=r"(r3) : "r"(addr) : "memory");
}
__device__ __forceinline__ void ldsm4t(uint32_t addr, uint32_t& r0, uint32_t& r1, uint32_t& r2, uint32_t& r3) {
    asm volatile("ldmatrix.sync.aligned.m8n8.x4.trans.shared.b16 {%0, %1, %2, %3}, [%4];" : "=r"(r0), "=r"(r1), "=r"(r2), "=r"(r3) : "r"(addr) : "memory");
}
__device__ __forceinline__ void mma16816(float (&c)[4], uint32_t a0, uint32_t a1, uint32_t a2, uint32_t a3, uint32_t b0, uint32_t b1) {
    asm("mma.sync.aligned.m16n8k16.row.col.f32.bf16.bf16.f32 {%0, %1, %2, %3}, {%4, %5, %6, %7}, {%8, %9}, {%0, %1, %2, %3};"
        : "+f"(c[0]), "+f"(c[1]), "+f"(c[2]), "+f"(c[3]) : "r"(a0), "r"(a1), "r"(a2), "r"(a3), "r"(b0), "r"(b1));
}
__device__ __forceinline__ float rcp(float x) { float r; asm("rcp.approx.ftz.f32 %0, %1;" : "=f"(r) : "f"(x)); return r; }
__device__ __forceinline__ float ex2(float x) { float r; asm("ex2.approx.ftz.f32 %0, %1;" : "=f"(r) : "f"(x)); return r; }
__device__ __forceinline__ float glu_half(float gh, float uh) {
    float t; asm("tanh.approx.f32 %0, %1;" : "=f"(t) : "f"(gh)); return fmaf(t, uh, uh);
}
__device__ __forceinline__ float silu_(float x) { return __fdividef(x, 1.f + __expf(-x)); }
__device__ __forceinline__ void st_pkt(void* p, uint32_t a, uint32_t b) {
    asm volatile("{\n.reg .b64 t;\nmov.b64 t, {%1, %2};\nst.relaxed.gpu.global.b64 [%0], t;\n}" :: "l"(p), "r"(a), "r"(b) : "memory");
}
__device__ __forceinline__ uint4 ld_pkt2(const void* p) {
    uint4 v; asm volatile("{\n.reg .b64 t, u;\nld.relaxed.gpu.global.v2.b64 {t, u}, [%4];\nmov.b64 {%0, %1}, t;\nmov.b64 {%2, %3}, u;\n}"
        : "=r"(v.x), "=r"(v.y), "=r"(v.z), "=r"(v.w) : "l"(p) : "memory"); return v;
}
__device__ __forceinline__ void st_pkt16(void* p, uint32_t a, uint32_t b, uint32_t c, uint32_t d) {
    asm volatile("{\n.reg .b64 t, u;\n.reg .b128 w;\nmov.b64 t, {%1, %2};\nmov.b64 u, {%3, %4};\nmov.b128 w, {t, u};\nst.relaxed.gpu.global.b128 [%0], w;\n}"
        :: "l"(p), "r"(a), "r"(b), "r"(c), "r"(d) : "memory");
}
__device__ __forceinline__ uint4 ld_pkt16(const void* p) {
    uint4 v; asm volatile("{\n.reg .b64 t, u;\n.reg .b128 w;\nld.relaxed.gpu.global.b128 w, [%4];\nmov.b128 {t, u}, w;\nmov.b64 {%0, %1}, t;\nmov.b64 {%2, %3}, u;\n}"
        : "=r"(v.x), "=r"(v.y), "=r"(v.z), "=r"(v.w) : "l"(p) : "memory"); return v;
}
#define SPIN_GUARD(n) do { if (++(n) > (1u << 22)) asm volatile("trap;"); } while (0)
__device__ __forceinline__ uint4 lds128(uint32_t a) { uint4 v; asm volatile("ld.shared.v4.u32 {%0, %1, %2, %3}, [%4];" : "=r"(v.x), "=r"(v.y), "=r"(v.z), "=r"(v.w) : "r"(a) : "memory"); return v; }
__device__ __forceinline__ void sts128(uint32_t a, uint32_t x, uint32_t y, uint32_t z, uint32_t w) { asm volatile("st.shared.v4.u32 [%0], {%1, %2, %3, %4};" :: "r"(a), "r"(x), "r"(y), "r"(z), "r"(w) : "memory"); }
__device__ __forceinline__ uint32_t lds32(uint32_t a) { uint32_t v; asm volatile("ld.shared.u32 %0, [%1];" : "=r"(v) : "r"(a) : "memory"); return v; }
__device__ __forceinline__ void sts32(uint32_t a, uint32_t v) { asm volatile("st.shared.u32 [%0], %1;" :: "r"(a), "r"(v) : "memory"); }
__device__ __forceinline__ bool elect_one() {
    uint32_t p; asm volatile("{\n.reg .pred q;\nelect.sync _|q, 0xffffffff;\nselp.u32 %0, 1, 0, q;\n}" : "=r"(p)); return p;
}
__device__ __forceinline__ void cluster_arrive() { asm volatile("barrier.cluster.arrive.relaxed.aligned;" ::: "memory"); }
__device__ __forceinline__ void cluster_wait() { asm volatile("barrier.cluster.wait.aligned;" ::: "memory"); }

__device__ __forceinline__ void wgmma_n128_z(float (&d)[64], uint64_t da, uint64_t db) {
    asm volatile("{\n.reg .pred p;\nsetp.ne.b32 p, 0, 0;\n"
        "wgmma.mma_async.sync.aligned.m64n128k16.f32.bf16.bf16 {"
        "%0, %1, %2, %3, %4, %5, %6, %7, %8, %9, %10, %11, %12, %13, %14, %15, "
        "%16, %17, %18, %19, %20, %21, %22, %23, %24, %25, %26, %27, %28, %29, %30, %31, "
        "%32, %33, %34, %35, %36, %37, %38, %39, %40, %41, %42, %43, %44, %45, %46, %47, "
        "%48, %49, %50, %51, %52, %53, %54, %55, %56, %57, %58, %59, %60, %61, %62, %63"
        "}, %64, %65, p, 1, 1, 0, 1;\n}\n"
        : "=f"(d[0]), "=f"(d[1]), "=f"(d[2]), "=f"(d[3]), "=f"(d[4]), "=f"(d[5]), "=f"(d[6]), "=f"(d[7]),
          "=f"(d[8]), "=f"(d[9]), "=f"(d[10]), "=f"(d[11]), "=f"(d[12]), "=f"(d[13]), "=f"(d[14]), "=f"(d[15]),
          "=f"(d[16]), "=f"(d[17]), "=f"(d[18]), "=f"(d[19]), "=f"(d[20]), "=f"(d[21]), "=f"(d[22]), "=f"(d[23]),
          "=f"(d[24]), "=f"(d[25]), "=f"(d[26]), "=f"(d[27]), "=f"(d[28]), "=f"(d[29]), "=f"(d[30]), "=f"(d[31]),
          "=f"(d[32]), "=f"(d[33]), "=f"(d[34]), "=f"(d[35]), "=f"(d[36]), "=f"(d[37]), "=f"(d[38]), "=f"(d[39]),
          "=f"(d[40]), "=f"(d[41]), "=f"(d[42]), "=f"(d[43]), "=f"(d[44]), "=f"(d[45]), "=f"(d[46]), "=f"(d[47]),
          "=f"(d[48]), "=f"(d[49]), "=f"(d[50]), "=f"(d[51]), "=f"(d[52]), "=f"(d[53]), "=f"(d[54]), "=f"(d[55]),
          "=f"(d[56]), "=f"(d[57]), "=f"(d[58]), "=f"(d[59]), "=f"(d[60]), "=f"(d[61]), "=f"(d[62]), "=f"(d[63])
        : "l"(da), "l"(db));
}
__device__ __forceinline__ void wgmma_n128(float (&d)[64], uint64_t da, uint64_t db) {
    asm volatile("{\n.reg .pred p;\nsetp.eq.b32 p, 0, 0;\n"
        "wgmma.mma_async.sync.aligned.m64n128k16.f32.bf16.bf16 {"
        "%0, %1, %2, %3, %4, %5, %6, %7, %8, %9, %10, %11, %12, %13, %14, %15, "
        "%16, %17, %18, %19, %20, %21, %22, %23, %24, %25, %26, %27, %28, %29, %30, %31, "
        "%32, %33, %34, %35, %36, %37, %38, %39, %40, %41, %42, %43, %44, %45, %46, %47, "
        "%48, %49, %50, %51, %52, %53, %54, %55, %56, %57, %58, %59, %60, %61, %62, %63"
        "}, %64, %65, p, 1, 1, 0, 1;\n}\n"
        : "+f"(d[0]), "+f"(d[1]), "+f"(d[2]), "+f"(d[3]), "+f"(d[4]), "+f"(d[5]), "+f"(d[6]), "+f"(d[7]),
          "+f"(d[8]), "+f"(d[9]), "+f"(d[10]), "+f"(d[11]), "+f"(d[12]), "+f"(d[13]), "+f"(d[14]), "+f"(d[15]),
          "+f"(d[16]), "+f"(d[17]), "+f"(d[18]), "+f"(d[19]), "+f"(d[20]), "+f"(d[21]), "+f"(d[22]), "+f"(d[23]),
          "+f"(d[24]), "+f"(d[25]), "+f"(d[26]), "+f"(d[27]), "+f"(d[28]), "+f"(d[29]), "+f"(d[30]), "+f"(d[31]),
          "+f"(d[32]), "+f"(d[33]), "+f"(d[34]), "+f"(d[35]), "+f"(d[36]), "+f"(d[37]), "+f"(d[38]), "+f"(d[39]),
          "+f"(d[40]), "+f"(d[41]), "+f"(d[42]), "+f"(d[43]), "+f"(d[44]), "+f"(d[45]), "+f"(d[46]), "+f"(d[47]),
          "+f"(d[48]), "+f"(d[49]), "+f"(d[50]), "+f"(d[51]), "+f"(d[52]), "+f"(d[53]), "+f"(d[54]), "+f"(d[55]),
          "+f"(d[56]), "+f"(d[57]), "+f"(d[58]), "+f"(d[59]), "+f"(d[60]), "+f"(d[61]), "+f"(d[62]), "+f"(d[63])
        : "l"(da), "l"(db));
}
__device__ __forceinline__ void wgmma_n256_z(float (&d)[128], uint64_t da, uint64_t db) {
    asm volatile("{\n.reg .pred p;\nsetp.ne.b32 p, 0, 0;\n"
        "wgmma.mma_async.sync.aligned.m64n256k16.f32.bf16.bf16 {"
        "%0, %1, %2, %3, %4, %5, %6, %7, %8, %9, %10, %11, %12, %13, %14, %15, "
        "%16, %17, %18, %19, %20, %21, %22, %23, %24, %25, %26, %27, %28, %29, %30, %31, "
        "%32, %33, %34, %35, %36, %37, %38, %39, %40, %41, %42, %43, %44, %45, %46, %47, "
        "%48, %49, %50, %51, %52, %53, %54, %55, %56, %57, %58, %59, %60, %61, %62, %63, "
        "%64, %65, %66, %67, %68, %69, %70, %71, %72, %73, %74, %75, %76, %77, %78, %79, "
        "%80, %81, %82, %83, %84, %85, %86, %87, %88, %89, %90, %91, %92, %93, %94, %95, "
        "%96, %97, %98, %99, %100, %101, %102, %103, %104, %105, %106, %107, %108, %109, %110, %111, "
        "%112, %113, %114, %115, %116, %117, %118, %119, %120, %121, %122, %123, %124, %125, %126, %127"
        "}, %128, %129, p, 1, 1, 0, 1;\n}\n"
        : "=f"(d[0]), "=f"(d[1]), "=f"(d[2]), "=f"(d[3]), "=f"(d[4]), "=f"(d[5]), "=f"(d[6]), "=f"(d[7]),
          "=f"(d[8]), "=f"(d[9]), "=f"(d[10]), "=f"(d[11]), "=f"(d[12]), "=f"(d[13]), "=f"(d[14]), "=f"(d[15]),
          "=f"(d[16]), "=f"(d[17]), "=f"(d[18]), "=f"(d[19]), "=f"(d[20]), "=f"(d[21]), "=f"(d[22]), "=f"(d[23]),
          "=f"(d[24]), "=f"(d[25]), "=f"(d[26]), "=f"(d[27]), "=f"(d[28]), "=f"(d[29]), "=f"(d[30]), "=f"(d[31]),
          "=f"(d[32]), "=f"(d[33]), "=f"(d[34]), "=f"(d[35]), "=f"(d[36]), "=f"(d[37]), "=f"(d[38]), "=f"(d[39]),
          "=f"(d[40]), "=f"(d[41]), "=f"(d[42]), "=f"(d[43]), "=f"(d[44]), "=f"(d[45]), "=f"(d[46]), "=f"(d[47]),
          "=f"(d[48]), "=f"(d[49]), "=f"(d[50]), "=f"(d[51]), "=f"(d[52]), "=f"(d[53]), "=f"(d[54]), "=f"(d[55]),
          "=f"(d[56]), "=f"(d[57]), "=f"(d[58]), "=f"(d[59]), "=f"(d[60]), "=f"(d[61]), "=f"(d[62]), "=f"(d[63]),
          "=f"(d[64]), "=f"(d[65]), "=f"(d[66]), "=f"(d[67]), "=f"(d[68]), "=f"(d[69]), "=f"(d[70]), "=f"(d[71]),
          "=f"(d[72]), "=f"(d[73]), "=f"(d[74]), "=f"(d[75]), "=f"(d[76]), "=f"(d[77]), "=f"(d[78]), "=f"(d[79]),
          "=f"(d[80]), "=f"(d[81]), "=f"(d[82]), "=f"(d[83]), "=f"(d[84]), "=f"(d[85]), "=f"(d[86]), "=f"(d[87]),
          "=f"(d[88]), "=f"(d[89]), "=f"(d[90]), "=f"(d[91]), "=f"(d[92]), "=f"(d[93]), "=f"(d[94]), "=f"(d[95]),
          "=f"(d[96]), "=f"(d[97]), "=f"(d[98]), "=f"(d[99]), "=f"(d[100]), "=f"(d[101]), "=f"(d[102]), "=f"(d[103]),
          "=f"(d[104]), "=f"(d[105]), "=f"(d[106]), "=f"(d[107]), "=f"(d[108]), "=f"(d[109]), "=f"(d[110]), "=f"(d[111]),
          "=f"(d[112]), "=f"(d[113]), "=f"(d[114]), "=f"(d[115]), "=f"(d[116]), "=f"(d[117]), "=f"(d[118]), "=f"(d[119]),
          "=f"(d[120]), "=f"(d[121]), "=f"(d[122]), "=f"(d[123]), "=f"(d[124]), "=f"(d[125]), "=f"(d[126]), "=f"(d[127])
        : "l"(da), "l"(db));
}
__device__ __forceinline__ void wgmma_n256(float (&d)[128], uint64_t da, uint64_t db) {
    asm volatile("{\n.reg .pred p;\nsetp.eq.b32 p, 0, 0;\n"
        "wgmma.mma_async.sync.aligned.m64n256k16.f32.bf16.bf16 {"
        "%0, %1, %2, %3, %4, %5, %6, %7, %8, %9, %10, %11, %12, %13, %14, %15, "
        "%16, %17, %18, %19, %20, %21, %22, %23, %24, %25, %26, %27, %28, %29, %30, %31, "
        "%32, %33, %34, %35, %36, %37, %38, %39, %40, %41, %42, %43, %44, %45, %46, %47, "
        "%48, %49, %50, %51, %52, %53, %54, %55, %56, %57, %58, %59, %60, %61, %62, %63, "
        "%64, %65, %66, %67, %68, %69, %70, %71, %72, %73, %74, %75, %76, %77, %78, %79, "
        "%80, %81, %82, %83, %84, %85, %86, %87, %88, %89, %90, %91, %92, %93, %94, %95, "
        "%96, %97, %98, %99, %100, %101, %102, %103, %104, %105, %106, %107, %108, %109, %110, %111, "
        "%112, %113, %114, %115, %116, %117, %118, %119, %120, %121, %122, %123, %124, %125, %126, %127"
        "}, %128, %129, p, 1, 1, 0, 1;\n}\n"
        : "+f"(d[0]), "+f"(d[1]), "+f"(d[2]), "+f"(d[3]), "+f"(d[4]), "+f"(d[5]), "+f"(d[6]), "+f"(d[7]),
          "+f"(d[8]), "+f"(d[9]), "+f"(d[10]), "+f"(d[11]), "+f"(d[12]), "+f"(d[13]), "+f"(d[14]), "+f"(d[15]),
          "+f"(d[16]), "+f"(d[17]), "+f"(d[18]), "+f"(d[19]), "+f"(d[20]), "+f"(d[21]), "+f"(d[22]), "+f"(d[23]),
          "+f"(d[24]), "+f"(d[25]), "+f"(d[26]), "+f"(d[27]), "+f"(d[28]), "+f"(d[29]), "+f"(d[30]), "+f"(d[31]),
          "+f"(d[32]), "+f"(d[33]), "+f"(d[34]), "+f"(d[35]), "+f"(d[36]), "+f"(d[37]), "+f"(d[38]), "+f"(d[39]),
          "+f"(d[40]), "+f"(d[41]), "+f"(d[42]), "+f"(d[43]), "+f"(d[44]), "+f"(d[45]), "+f"(d[46]), "+f"(d[47]),
          "+f"(d[48]), "+f"(d[49]), "+f"(d[50]), "+f"(d[51]), "+f"(d[52]), "+f"(d[53]), "+f"(d[54]), "+f"(d[55]),
          "+f"(d[56]), "+f"(d[57]), "+f"(d[58]), "+f"(d[59]), "+f"(d[60]), "+f"(d[61]), "+f"(d[62]), "+f"(d[63]),
          "+f"(d[64]), "+f"(d[65]), "+f"(d[66]), "+f"(d[67]), "+f"(d[68]), "+f"(d[69]), "+f"(d[70]), "+f"(d[71]),
          "+f"(d[72]), "+f"(d[73]), "+f"(d[74]), "+f"(d[75]), "+f"(d[76]), "+f"(d[77]), "+f"(d[78]), "+f"(d[79]),
          "+f"(d[80]), "+f"(d[81]), "+f"(d[82]), "+f"(d[83]), "+f"(d[84]), "+f"(d[85]), "+f"(d[86]), "+f"(d[87]),
          "+f"(d[88]), "+f"(d[89]), "+f"(d[90]), "+f"(d[91]), "+f"(d[92]), "+f"(d[93]), "+f"(d[94]), "+f"(d[95]),
          "+f"(d[96]), "+f"(d[97]), "+f"(d[98]), "+f"(d[99]), "+f"(d[100]), "+f"(d[101]), "+f"(d[102]), "+f"(d[103]),
          "+f"(d[104]), "+f"(d[105]), "+f"(d[106]), "+f"(d[107]), "+f"(d[108]), "+f"(d[109]), "+f"(d[110]), "+f"(d[111]),
          "+f"(d[112]), "+f"(d[113]), "+f"(d[114]), "+f"(d[115]), "+f"(d[116]), "+f"(d[117]), "+f"(d[118]), "+f"(d[119]),
          "+f"(d[120]), "+f"(d[121]), "+f"(d[122]), "+f"(d[123]), "+f"(d[124]), "+f"(d[125]), "+f"(d[126]), "+f"(d[127])
        : "l"(da), "l"(db));
}

struct Idx {
    uint32_t lane, warp, w4, q4, g8, prow, pan;
    __device__ __forceinline__ Idx() {
        uint32_t t; asm volatile("mov.u32 %0, %%tid.x;" : "=r"(t));
        lane = t & 31; warp = t >> 5; w4 = warp & 3; q4 = lane & 3; g8 = lane >> 2;
        prow = w4 * 16 + ((lane >> 3) & 1) * 8 + (lane & 7);
        pan = prow * 128 + (((lane >> 4) ^ (lane & 7)) << 4);
    }
};
#define IDX() const Idx ix; const uint32_t lane = ix.lane, warp = ix.warp, w4 = ix.w4, q4 = ix.q4, g8 = ix.g8, prow = ix.prow, pan_addr = ix.pan; \
    (void)lane; (void)warp; (void)w4; (void)q4; (void)g8; (void)prow; (void)pan_addr;

__device__ __forceinline__ int kof(int t, int sh, int j) {
    const int q = (t >> sh) - 1;
    return ((q < 0 ? j : q + (q >= j)) << 7) + ((t & ((1 << sh) - 1)) << (7 - sh));
}
__device__ __forceinline__ int kdown(int g) {
    return g < 24 ? (g / 3 * 4 + g) * 64 : (((g - 24) & 15) / 2 * 7 + 3 + ((g - 24) >> 4) * 2 + (g & 1)) * 64;
}
#define SCHED_FENCE() asm volatile("{\n.reg .pred p;\nsetp.ne.u32 p, %0, 0xffffffff;\n@p bra.uni S_SKIP;\ntrap;\nS_SKIP:\n}" :: "r"(sb))

struct Ring {
    uint32_t slot, par;
    __device__ __forceinline__ void next() { if (++slot == NSLOT) { slot = 0; par ^= 1; } }
    __device__ __forceinline__ void skip(uint32_t n) { slot += n; if (slot >= NSLOT) { slot -= NSLOT; par ^= 1; } }
};
__device__ __forceinline__ uint32_t BAR_FULL(uint32_t sb, uint32_t s) { return sb + OFF_BAR + 8 * s; }
constexpr uint32_t AF_REL = 48;
__device__ __forceinline__ uint32_t BAR_EMPTY(uint32_t sb, uint32_t s) { return sb + OFF_BAR + 96 + 8 * s; }
__device__ __forceinline__ uint32_t BAR_SFULL(uint32_t sb, uint32_t i) { return sb + OFF_BAR + 152 + 8 * i; }
__device__ __forceinline__ uint32_t BAR_SREADY(uint32_t sb, uint32_t i) { return sb + OFF_BAR + 184 + 8 * i; }
__device__ __forceinline__ uint32_t BAR_ONE(uint32_t sb, uint32_t i) { return sb + OFF_BAR + 216 + 8 * i; }
enum { EV_WIN, EV_WIN1, EV_WIN2, EV_WIN3, EV_P0, EV_GA, EV_GB, EV_LN2, EV_LAG0, EV_LAG1, EV_LAG2, EV_LAG3, EV_LAG4, EV_LAG5, EV_OWN, EV_OWN1, EV_P3, EV_P31, EV_KV, EV_GO, EV_PAR, EV_AGO, EV_AGO1, EV_AGO2, EV_H0, EV_H1, EV_H2, EV_COUNT };
constexpr int NB_TAIL = 4;

struct Rel {
    uint32_t base; bool sig;
    __device__ __forceinline__ Rel(uint32_t sb, uint32_t tw) {
        uint32_t a; asm("mapa.shared::cluster.u32 %0, %1, %2;" : "=r"(a) : "r"(BAR_EMPTY(sb, 0)), "r"((tw >> 5) & 1));
        base = __shfl_sync(0xffffffffu, a, 0); sig = (tw & ~32u) == 0;
    }
    __device__ __forceinline__ void operator()(uint32_t slot) const {
        if (sig) asm volatile("mbarrier.arrive.shared::cluster.b64 _, [%0];" :: "r"(base + 8 * slot) : "memory");
    }
};
struct LnRow { float rs0, nm0, rs1, nm1; };
struct Pipe {
    Rel rel; uint32_t p1, p2;
    __device__ __forceinline__ Pipe(uint32_t sb, uint32_t tw, uint32_t first) : rel(sb, tw), p1(first), p2(NSLOT) {}
    template <bool TWO> __device__ __forceinline__ void acquire(uint32_t sb, uint32_t wg, const Ring& r) {
        const uint32_t b0 = BAR_FULL(sb, r.slot), b1 = b0 + (wg ? 0 : AF_REL);
        const bool ready = TWO ? mbar_test2(b0, b1, r.par) : mbar_test(b0, r.par);
        wg_wait<1>();
        rel(p2);
        if (!ready) { if (TWO) mbar_wait2(b0, b1, r.par); else mbar_wait(b0, r.par); }
    }
    __device__ __forceinline__ void issued(uint32_t slot) { p2 = p1; p1 = slot; }
    __device__ __forceinline__ void drain1() { wg_wait<1>(); rel(p2); p2 = NSLOT; }
    __device__ __forceinline__ void drain0() { wg_wait<0>(); rel(p1); p1 = NSLOT; }
};
template <bool WITH128, bool FIRST>
__device__ __forceinline__ void step32(float (&a256)[128], float (&a128)[64], uint32_t sb, uint32_t wg, uint32_t slot, int own) {
    const uint32_t st = d16(sb) + slot * (SLOT >> 4);
    const uint32_t alo = own >= 0 ? d16(sb) + OFF_STG / 16 + wg * 1024 + (own >> 1) * 512 + (own & 1) * 4 : st + wg * 256;
    const uint32_t ahi = own >= 0 ? (1024 >> 4) | (1u << 30) : (512 >> 4) | (2u << 30);
    wg_fence();
#pragma unroll
    for (int k = 0; k < 2; ++k) {
        const uint64_t da = ((uint64_t)ahi << 32) | (alo + k * 2 + 0x10000);
        const uint64_t d0 = mk_desc(st, 8192 + k * 2048, 4096, 1024, 1), d1 = mk_desc(st, 24576 + k * 2048, 4096, 1024, 1);
        if (FIRST && k == 0) { wgmma_n256_z(a256, da, d0); if (WITH128) wgmma_n128_z(a128, da, d1); }
        else { wgmma_n256(a256, da, d0); if (WITH128) wgmma_n128(a128, da, d1); }
    }
    wg_commit();
}
template <bool WITH128, int LG, class Tail>
__device__ __forceinline__ void mainloop32(float (&a256)[128], float (&a128)[64], uint32_t sb, uint32_t wg, uint32_t tw, Ring& r, uint32_t lag_ev, int g0, Tail tail) {
    mbar_wait(BAR_FULL(sb, r.slot), r.par);
    step32<WITH128, true>(a256, a128, sb, wg, r.slot, WITH128 ? 0 : -1);
    TS(g0, 0);
    Pipe pp(sb, tw, r.slot);
    r.next();
    const int hold = wg ? 32 : 32 - LG;
#pragma unroll 1
    for (int it = 1; it < 32; ++it) {
        if (it == hold) { pp.drain1(); pp.drain0(); mbar_wait(BAR_ONE(sb, lag_ev), 0); }
        pp.acquire<WITH128>(sb, wg, r);
        step32<WITH128, false>(a256, a128, sb, wg, r.slot, WITH128 && it < 4 ? it : -1);
        pp.issued(r.slot);
        TS(g0 + it, 0);
        r.next();
    }
    if (LAGSIG == 2 && wg == 1 && tw == 0) mbar_arrive(BAR_ONE(sb, lag_ev));
    pp.drain1();
    if (LAGSIG == 1 && wg == 1 && tw == 0) mbar_arrive(BAR_ONE(sb, lag_ev));
    tail();
    pp.drain0();
    TS(g0 + 31, 1);
}
template <bool FIRST>
__device__ __forceinline__ void step64(float (&acc)[64], uint32_t sb, uint32_t wg, uint32_t slot, int own) {
    const uint32_t sbb = d16(sb) + slot * (SLOT >> 4), sa = own >= 0 ? d16(sb) + OFF_STG / 16 + wg * 1024 + own * 512 : sbb + wg * 512;
    wg_fence();
#pragma unroll
    for (int k = 0; k < 4; ++k) {
        const uint64_t da = mk_desc(sa, k * 32, 16, 1024, 1), db = mk_desc(sbb, 16384 + k * 2048, 8192, 1024, 1);
        if (FIRST && k == 0) wgmma_n128_z(acc, da, db); else wgmma_n128(acc, da, db);
    }
    wg_commit();
}
template <bool OWN, int NST, int LG, int MID, class Mid>
__device__ __forceinline__ void mainloop64(float (&acc)[64], uint32_t sb, uint32_t wg, uint32_t tw, Ring& r, Mid mid) {
    constexpr int G0 = OWN ? 32 : 144; (void)G0;
    const uint32_t lag_bar = BAR_ONE(sb, OWN ? EV_LAG4 : EV_LAG5);
    mbar_wait(BAR_FULL(sb, r.slot), r.par);
    step64<true>(acc, sb, wg, r.slot, OWN ? 0 : -1);
    TS(G0, 0);
    Pipe pp(sb, tw, r.slot);
    r.next();
    if (OWN) {
        mbar_wait(BAR_FULL(sb, r.slot), r.par);
        step64<false>(acc, sb, wg, r.slot, 1);
        TS(G0 + 1, 0);
        pp.drain0();
        TS(G0 + 1, 1);
        pp.rel(r.slot);
        if (tw == 0) mbar_arrive(BAR_ONE(sb, EV_OWN + wg));
        r.next();
    }
    int it = OWN ? 2 : 1;
    auto run = [&](int end) {
#pragma unroll 1
        do {
            pp.acquire<OWN>(sb, wg, r);
            step64<false>(acc, sb, wg, r.slot, -1);
            pp.issued(r.slot);
            TS(G0 + it, 0);
            r.next();
        } while (++it < end);
    };
    run(wg ? MID : NST - LG);
    mid();
    if (wg == 0) { pp.drain1(); pp.drain0(); mbar_wait(lag_bar, 0); }
    run(NST);
    if (LAGSIG == 2 && wg == 1 && tw == 0) mbar_arrive(lag_bar);
    pp.drain1();
    if (LAGSIG == 1 && wg == 1 && tw == 0) mbar_arrive(lag_bar);
    pp.drain0();
    TS(G0 + NST - 1, 1);
}

struct RowAcc {
    float sm[4] = {0.f, 0.f, 0.f, 0.f}, g0[4] = {0.f, 0.f, 0.f, 0.f}, g1[4] = {0.f, 0.f, 0.f, 0.f};
    __device__ __forceinline__ void add(uint32_t a0, uint32_t a1, uint32_t a2, uint32_t a3) {
        mma16816(sm, a0, a1, a2, a3, 0x3F803F80u, 0x3F803F80u);
        mma16816(g0, a0, a1, a2, a3, a0, a2);
        mma16816(g1, a0, a1, a2, a3, a1, a3);
    }
    __device__ __forceinline__ void publish(uint4* dst, uint32_t q4, uint32_t g8, uint32_t ep) const {
        if (q4 == (g8 >> 1)) {
            st_pkt16(dst, 0, __float_as_uint(sm[0]), __float_as_uint((g8 & 1) ? g0[1] : g0[0]), ep);
            st_pkt16(dst + 8, 0, __float_as_uint(sm[2]), __float_as_uint((g8 & 1) ? g1[3] : g1[2]), ep);
        }
    }
};
__device__ __forceinline__ LnRow merge_stats(const uint4* src, uint32_t stride, uint32_t q4, uint32_t ep, uint32_t sb, uint32_t sig) {
    uint4 t[4];
    uint32_t n = 0;
    while (true) {
#pragma unroll
        for (int i = 0; i < 4; ++i) t[i] = ld_pkt16(src + (q4 * 2 + (i >> 1)) * stride + (i & 1) * 8);
        if (n == SIGAT && sig) mbar_arrive(sig);
        const bool ok_ = __all_sync(0xffffffffu, t[0].w == ep && t[1].w == ep && t[2].w == ep && t[3].w == ep);
        if (ok_) break;
        SPIN_GUARD(n);
    }
    if (n < SIGAT && sig) mbar_arrive(sig);
    float v[4];
#pragma unroll
    for (int h = 0; h < 2; ++h) { v[h] = __uint_as_float(t[h].y) + __uint_as_float(t[2 + h].y); v[2 + h] = __uint_as_float(t[h].z) + __uint_as_float(t[2 + h].z); }
#pragma unroll
    for (int o = 1; o < 4; o <<= 1)
#pragma unroll
        for (int i = 0; i < 4; ++i) v[i] += __shfl_xor_sync(0xffffffffu, v[i], o);
    const float m0 = v[0] * (1.f / D_), m1 = v[1] * (1.f / D_);
    const float r0 = rsqrtf(fmaxf(fmaf(-m0, m0, v[2] * (1.f / D_)), 0.f) + 1e-5f), r1 = rsqrtf(fmaxf(fmaf(-m1, m1, v[3] * (1.f / D_)), 0.f) + 1e-5f);
    return LnRow{r0, -m0 * r0, r1, -m1 * r1};
}
struct Stg {
    uint32_t b, par;
    __device__ __forceinline__ uint32_t acquire2(uint32_t sb, uint32_t wg) {
        mbar_wait(BAR_SREADY(sb, wg * 2), par & 1);
        mbar_wait(BAR_SREADY(sb, wg * 2 + 1), (par >> 1) & 1);
        par ^= 3;
        return sb + OFF_STG + wg * 16384;
    }
    __device__ __forceinline__ void publish(uint32_t sb, uint32_t wg, uint32_t lane) {
        fence_async_smem();
        __syncwarp();
        if (lane == 0) mbar_arrive(BAR_SFULL(sb, wg * 2 + b));
        b ^= 1;
    }
};

struct LnPar {
    uint4 p[8];
    __device__ __forceinline__ void load(uint32_t sb, uint32_t q4) {
#pragma unroll
        for (int i = 0; i < 8; ++i) p[i] = lds128(sb + OFF_PAR + i * 64 + q4 * 16);
    }
};
__device__ __forceinline__ void ln_norm(uint32_t (&xn)[32], const float (&x)[64], const LnRow& n) {
#pragma unroll
    for (int e = 0; e < 32; ++e) {
        const float rs = (e & 1) ? n.rs1 : n.rs0, nm = (e & 1) ? n.nm1 : n.nm0;
        xn[e] = pack2(fmaf(x[2 * e], rs, nm), fmaf(x[2 * e + 1], rs, nm));
    }
}
__device__ __forceinline__ void ln_emit(const uint32_t (&xr)[32], const LnPar& lp, uint32_t sb, uint32_t wg, const Idx& ix) {
#pragma unroll
    for (int i = 0; i < 8; ++i)
        stsm4(sb + OFF_STG + wg * 16384 + (i >> 2) * 8192 + (ix.pan ^ ((i & 3) << 5)), hfma2_bf16(xr[4 * i], lp.p[i].z, lp.p[i].x), hfma2_bf16(xr[4 * i + 1], lp.p[i].z, lp.p[i].x),
              hfma2_bf16(xr[4 * i + 2], lp.p[i].w, lp.p[i].y), hfma2_bf16(xr[4 * i + 3], lp.p[i].w, lp.p[i].y));
    fence_async_smem();
    __syncwarp();
    if (ix.lane < 2) mbar_arrive(BAR_SFULL(sb, wg * 2 + ix.lane));
    bar_sync(1 + wg, 128);
}
__device__ __forceinline__ void fetch_halo(uint4* src, bool first, uint32_t sb, uint32_t W, uint32_t lane) {
    mbar_wait(BAR_ONE(sb, EV_KV), 0);
    mbar_wait2(BAR_SREADY(sb, 0), BAR_SREADY(sb, 1), 1);
    uint4 hv[8];
    uint32_t n = 0;
    while (true) {
        bool ok = true;
#pragma unroll
        for (int i = 0; i < 8; ++i) { hv[i] = first ? make_uint4(0, 0, 0, 0) : ld_pkt16(src + i * 32); ok = ok && hv[i].x != 0; }
        if (first || __all_sync(0xffffffffu, ok)) break;
        SPIN_GUARD(n);
    }
#pragma unroll
    for (int i = 0; i < 8; ++i) stsm4(sb + OFF_STG + W * 2048 + (i >> 2) * 8192 + (i & 3) * 512 + lane * 16, hv[i].x, hv[i].y, hv[i].z, hv[i].w);
    bar_arrive(NB_TAIL + W, 64);
    if (!first) {
#pragma unroll
        for (int i = 0; i < 8; ++i) src[i * 32] = make_uint4(0, 0, 0, 0);
    }
}

template <int OFF, int LEN>
__device__ __forceinline__ void glu_panel(const float (&a)[LEN], uint32_t buf, uint32_t bar) {
    IDX();
    uint32_t r[16];
#pragma unroll
    for (int i = 0; i < 16; ++i) r[i] = pack2(glu_half(a[OFF + 2 * i], a[OFF + 2 * i + 32]), glu_half(a[OFF + 2 * i + 1], a[OFF + 2 * i + 33]));
#pragma unroll
    for (int jn = 0; jn < 8; jn += 2) stsm4(buf + (pan_addr ^ (jn << 4)), r[jn * 2], r[jn * 2 + 1], r[jn * 2 + 2], r[jn * 2 + 3]);
    fence_async_smem();
    __syncwarp();
    if (lane == 0) mbar_arrive(bar);
}

__global__ void __launch_bounds__(384, 1)
fused_block_kernel(const __grid_constant__ Ptrs pt, const __grid_constant__ Maps mp) {
    uint32_t* const g_flags = pt.mail->flags;
    uint2* const g_mod = pt.mail->mod;
    uint4* const g_st1 = pt.mail->st1;
    uint32_t* const g_par2 = pt.mail->par2;
    uint4* const g_halo = pt.mail->halo;
    const __nv_bfloat16* __restrict__ cvec = pt.c;
    if (threadIdx.x == 224) { prefetch_map(&mp.wm8); prefetch_map(&mp.x); }
    extern __shared__ __align__(1024) uint8_t smem[];
    const uint32_t sb = smem_u32(smem);
    const uint32_t tid = threadIdx.x, tw = tid & 127, lane = tid & 31;
    const uint32_t warp = __shfl_sync(0xffffffffu, tid >> 5, 0), wg = warp >> 2;
    uint32_t rank; asm("mov.u32 %0, %%cluster_ctarank;" : "=r"(rank));
    rank = __shfl_sync(0xffffffffu, rank, 0);
    uint32_t ep;
#define LOAD_EP() asm volatile("ld.relaxed.gpu.global.u32 %0, [%1];" : "=r"(ep) : "l"(&g_flags[FL_DONE]) : "memory")
    uint32_t smid; asm volatile("mov.u32 %0, %%smid;" : "=r"(smid));
    const int c = __shfl_sync(0xffffffffu, smid >> 1, 0);
    int grp, j;
    if (c < 32) { grp = c & 7; j = c >> 3; }
    else if (c < 60) { grp = 1 + (c - 32) % 7; j = 4 + (c - 32) / 7; }
    else if (c < 62) { grp = -1; j = (c - 60) * 2 + rank; }
    else { grp = 0; j = c - 58; }
    const bool aux = grp < 0;
    const int m = grp * 2 + rank;
    uint4* const g_st2 = g_halo + (m > 0 ? (m - 1) * 8 * 512 : 128);

    bool cluster_arrive_early = false;
    if (wg < 2) {
      asm volatile("setmaxnreg.inc.sync.aligned.u32 224;");
      if (tid == 0) TL(58);
      LOAD_EP();
      cluster_arrive();
      if (aux) {
        if (wg == 0) {
            const uint4 cv = *(const uint4*)(cvec + tw * 8);
            sts128(sb + OFF_STG + (tw >> 3) * 1024 + (tw & 7) * 16, pack2(silu_(bf_lo(cv.x)), silu_(bf_hi(cv.x))), pack2(silu_(bf_lo(cv.y)), silu_(bf_hi(cv.y))),
                   pack2(silu_(bf_lo(cv.z)), silu_(bf_hi(cv.z))), pack2(silu_(bf_lo(cv.w)), silu_(bf_hi(cv.w))));
            fence_async_smem();
        }
        cluster_wait();
        ep = __shfl_sync(0xffffffffu, ep, 0) / NCTA + 1;
        if (wg == 0) {
            if (tw == 0) {
                uint32_t n = 0;
                while (ld_pkt16(pt.mail->mod1 + 256).z != ep) { SPIN_GUARD(n); __nanosleep(200); }
                mbar_arrive(BAR_ONE(sb, EV_GO));
            }
            bar_sync(1, 128);
            Ring r{0, 0};
#pragma unroll 1
            for (int p = 0; p < 4; ++p) {
                float acc[128];
#pragma unroll
                for (int i = 0; i < 128; ++i) acc[i] = 0.f;
                uint32_t prev = 0;
#pragma unroll 1
                for (int kc = 0; kc < 16; ++kc) {
                    mbar_wait(BAR_FULL(sb, r.slot), r.par);
                    wg_fence();
#pragma unroll
                    for (int k = 0; k < 4; ++k)
                        wgmma_n256(acc, mk_desc(d16(sb) + kc * 64, OFF_STG + k * 32, 16, 0, 1), mk_desc(d16(sb) + r.slot * (SLOT >> 4), k * 2048, 8192, 1024, 1));
                    wg_commit();
                    wg_wait<1>();
                    if (kc > 0 && tw == 0) mbar_arrive(BAR_EMPTY(sb, prev));
                    prev = r.slot;
                    r.next();
                }
                wg_wait<0>();
                if (tw == 0) mbar_arrive(BAR_EMPTY(sb, prev));
                if (tw < 4) {
#pragma unroll
                    for (int jn = 0; jn < 32; ++jn) sts32(sb + OFF_TAB + (jn * 4 + tw) * 4, pack2(acc[jn * 4], acc[jn * 4 + 1]));
                }
                bar_sync(1, 128);
                const int vec = 2 + p, blk = p * 4 + j;
                const uint32_t val = lds32(sb + OFF_TAB + tw * 4);
                if (vec == 2 || vec == 5) st_pkt(g_mod + (8 + blk) * 128 + tw, val, ep);
                else {
                    const float one = vec == 4 ? 1.f : 0.f;
                    g_par2[((blk & 3) * 16 + (tw >> 3)) * 16 + (tw & 3) * 4 + (vec - 3) * 2 + ((tw >> 2) & 1)] =
                        pack2(0.5f * bf_round(one + bf_lo(val)), 0.5f * bf_round(one + bf_hi(val)));
                }
                bar_sync(1, 128);
                if (tw == 0) {
                    if (vec == 3 || vec == 4) asm volatile("red.release.gpu.global.add.u32 [%0], 1;" :: "l"(&g_flags[FL_LN2]) : "memory");
                    TL(1 + p);
                }
            }
        }
      } else {
        Ring r{0, 0};
        Stg stg{0, 0};
        {
            IDX();
            const int cid = m * 8 + j;
            const uint4 cv = *(const uint4*)(cvec + (tid >> 1) * 8);
            const uint32_t cu[4] = {cv.x, cv.y, cv.z, cv.w};
            float sv[8];
#pragma unroll
            for (int i = 0; i < 8; ++i) sv[i] = bf_round(silu_((i & 1) ? bf_hi(cu[i >> 1]) : bf_lo(cu[i >> 1])));
            cluster_wait();
            ep = __shfl_sync(0xffffffffu, ep, 0) / NCTA + 1;
            uint32_t xr[32];
            const uint32_t buf0 = stg.acquire2(sb, wg);
            if (tid == 0) TL(24);
            RowAcc ra;
#pragma unroll
            for (int i = 0; i < 8; ++i) {
                ldsm4(buf0 + (i >> 2) * 8192 + (pan_addr ^ ((i & 3) << 5)), xr[4 * i], xr[4 * i + 1], xr[4 * i + 2], xr[4 * i + 3]);
                ra.add(xr[4 * i], xr[4 * i + 1], xr[4 * i + 2], xr[4 * i + 3]);
            }
            uint4* const st1 = g_st1 + m * 128 + wg * 64 + w4 * 16 + g8;
            ra.publish(st1 + j * S_, q4, g8, ep);
            if (tid == 0) TL(26);
            float pa[8];
#pragma unroll
            for (int e = 0; e < 8; ++e) pa[e] = 0.f;
#pragma unroll
            for (int i = 0; i < 8; ++i) {
                if (!(i & 1)) mbar_wait(BAR_ONE(sb, EV_WIN + (i >> 1)), 0);
                if (i == 6 && tid == 0) TL(25);
                const uint4 wv = lds128(sb + 5 * SLOT + i * 4096 + tid * 16);
                const uint32_t u[4] = {wv.x, wv.y, wv.z, wv.w};
#pragma unroll
                for (int e = 0; e < 4; ++e) { pa[2 * e] = fmaf(sv[i], bf_lo(u[e]), pa[2 * e]); pa[2 * e + 1] = fmaf(sv[i], bf_hi(u[e]), pa[2 * e + 1]); }
            }
#pragma unroll
            for (int h = 4; h >= 1; h >>= 1) {
                const bool up = lane & (h * 4);
#pragma unroll
                for (int e = 0; e < h; ++e) pa[e] = (up ? pa[e + h] : pa[e]) + __shfl_xor_sync(0xffffffffu, up ? pa[e] : pa[e + h], h * 4);
            }
            pa[0] += __shfl_xor_sync(0xffffffffu, pa[0], 2);
            if (lane < 2) mbar_arrive_cta(BAR_ONE(sb, EV_P0), lane);
            if (!(lane & 2)) sts32(sb + OFF_TAB + (warp * 16 + (lane >> 3) * 4 + (lane & 1) * 2 + ((lane >> 2) & 1)) * 4, __float_as_uint(pa[0]));
            bar_sync(3, 256);
            if (tid < 32) {
                const uint4 t = lds128(sb + OFF_TAB + lane * 16);
                float a[4] = {__uint_as_float(t.x), __uint_as_float(t.y), __uint_as_float(t.z), __uint_as_float(t.w)};
#pragma unroll
                for (int o = 4; o < 32; o <<= 1)
#pragma unroll
                    for (int e = 0; e < 4; ++e) a[e] += __shfl_xor_sync(0xffffffffu, a[e], o);
                const float add = cid >= 64 ? 1.f : 0.f;
                st_pkt16(pt.mail->mod1 + g8 * 512 + cid * 4 + q4, pack2(bf_round(a[0]) + add, bf_round(a[1]) + add), pack2(bf_round(a[2]) + add, bf_round(a[3]) + add), ep, 0);
                if (tid == 0) TL(3);
            }
            const LnRow n1 = merge_stats(st1, S_, q4, ep, sb, 0);
            if (tid == 0) TL(48);
            float xf[64];
#pragma unroll
            for (int e = 0; e < 32; ++e) { xf[2 * e] = bf_lo(xr[e]); xf[2 * e + 1] = bf_hi(xr[e]); }
            ln_norm(xr, xf, n1);
            mbar_wait(BAR_ONE(sb, EV_PAR), 0);
            LnPar lp; lp.load(sb, q4);
            ln_emit(xr, lp, sb, wg, ix);
            if (tid == 0) { TL(8); TC(103); }
        }
        {
            float kv[128], qa[64];
            mainloop32<true, LAGQ>(kv, qa, sb, wg, tw, r, EV_LAG0, 0, [&] { stg.acquire2(sb, wg); mbar_wait2(BAR_SREADY(sb, 2), BAR_SREADY(sb, 3), 1); });
            if (tid == 0) { TL(4); TC(104); }
            if (tid == 128) TL(50);
            IDX();
            uint32_t k1[16], k2[16], v1[16], v2[16], qf[32];
#pragma unroll
            for (int i = 0; i < 8; ++i) qf[i] = pack2(qa[2 * i], qa[2 * i + 1]);
#pragma unroll
            for (int t = 0; t < 16; ++t) k2[t] = pack2(kv[4 * t + 2], kv[4 * t + 3]);
#pragma unroll
            for (int t = 0; t < 16; ++t) v2[t] = pack2(kv[64 + 4 * t + 2], kv[64 + 4 * t + 3]);
            const uint32_t nxt = warp + ((warp & 1) ? 3 : 1);
            if (nxt < 8) {
                const uint32_t dst = sb + OFF_STG + (nxt >> 2) * 16384 + (nxt & 3) * 2048 + lane * 16;
#pragma unroll
                for (int h = 0; h < 4; ++h) stsm4(dst + h * 512, k2[4 * h], k2[4 * h + 1], k2[4 * h + 2], k2[4 * h + 3]);
#pragma unroll
                for (int h = 0; h < 4; ++h) stsm4(dst + 8192 + h * 512, v2[4 * h], v2[4 * h + 1], v2[4 * h + 2], v2[4 * h + 3]);
                bar_arrive(NB_TAIL + nxt, 64);
            } else if (m < 15) {
                uint4* dst = g_halo + (m * 8 + j) * 512 + (w4 >> 1) * 256 + lane;
#pragma unroll
                for (int h = 0; h < 4; ++h) { if (!k2[4 * h]) k2[4 * h] = 0x8000u; if (!v2[4 * h]) v2[4 * h] = 0x8000u; }
#pragma unroll
                for (int h = 0; h < 4; ++h) st_pkt16(dst + h * 32, k2[4 * h], k2[4 * h + 1], k2[4 * h + 2], k2[4 * h + 3]);
#pragma unroll
                for (int h = 0; h < 4; ++h) st_pkt16(dst + 128 + h * 32, v2[4 * h], v2[4 * h + 1], v2[4 * h + 2], v2[4 * h + 3]);
            }
#pragma unroll
            for (int t = 0; t < 16; ++t) { k1[t] = pack2(kv[4 * t], kv[4 * t + 1]); v1[t] = pack2(kv[64 + 4 * t], kv[64 + 4 * t + 1]); }
#pragma unroll
            for (int i = 8; i < 32; ++i) qf[i] = pack2(qa[2 * i], qa[2 * i + 1]);
#pragma unroll
            for (int t = 0; t < 16; ++t) { v1[t] = movm(v1[t]); v2[t] = movm(v2[t]); }
            if (tid == 0) TL(33);
            SCHED_FENCE();
            float s[4][3][4];
            auto qk = [&](float (&c)[4], int h, const uint32_t* k) {
                c[0] = c[1] = c[2] = c[3] = 0.f;
                mma16816(c, qf[h * 8], qf[h * 8 + 1], qf[h * 8 + 2], qf[h * 8 + 3], k[0], k[1]);
                mma16816(c, qf[h * 8 + 4], qf[h * 8 + 5], qf[h * 8 + 6], qf[h * 8 + 7], k[2], k[3]);
            };
#pragma unroll
            for (int h = 0; h < 4; ++h) { qk(s[h][1], h, k1 + 4 * h); qk(s[h][2], h, k2 + 4 * h); }
            bar_sync(NB_TAIL + warp, 64);
            if (tid == 0) TL(5);
            uint32_t k0[16], v0[16];
            const uint32_t mine = sb + OFF_STG + wg * 16384 + w4 * 2048;
#pragma unroll
            for (int h = 0; h < 4; ++h) ldsm4(mine + lane * 16 + h * 512, k0[4 * h], k0[4 * h + 1], k0[4 * h + 2], k0[4 * h + 3]);
#pragma unroll
            for (int h = 0; h < 4; ++h) ldsm4t(mine + lane * 16 + 8192 + h * 512, v0[4 * h], v0[4 * h + 1], v0[4 * h + 2], v0[4 * h + 3]);
#pragma unroll
            for (int h = 0; h < 4; ++h) qk(s[h][0], h, k0 + 4 * h);
            const bool lo0 = q4 * 2 > g8, lo1 = q4 * 2 + 1 > g8;
            const bool nopast = m == 0 && (warp & 5) == 0;
            const uint32_t lomask = (lo0 ? 0xFFFFu : 0u) | (lo1 ? 0xFFFF0000u : 0u);
            const float sl2 = 0.17677669529663687f * 1.4426950408889634f;
            float e0[8], e1[8], mx[8], sum[8], tt[8];
#pragma unroll
            for (int u = 0; u < 8; ++u) {
                const int h = u >> 1, hf = u & 1;
                e0[u] = lo0 ? ((hf == 0 && nopast) ? -INFINITY : s[h][hf][hf * 2]) : s[h][hf + 1][hf * 2];
                e1[u] = lo1 ? ((hf == 0 && nopast) ? -INFINITY : s[h][hf][hf * 2 + 1]) : s[h][hf + 1][hf * 2 + 1];
                mx[u] = fmaxf(e0[u], e1[u]);
                tt[u] = __shfl_xor_sync(0xffffffffu, mx[u], 1);
            }
            SCHED_FENCE();
#pragma unroll
            for (int u = 0; u < 8; ++u) { mx[u] = fmaxf(mx[u], tt[u]); tt[u] = __shfl_xor_sync(0xffffffffu, mx[u], 2); }
            SCHED_FENCE();
#pragma unroll
            for (int u = 0; u < 8; ++u) {
                const float c = -fmaxf(mx[u], tt[u]) * sl2;
                e0[u] = ex2(fmaf(e0[u], sl2, c)); e1[u] = ex2(fmaf(e1[u], sl2, c));
            }
            SCHED_FENCE();
#pragma unroll
            for (int u = 0; u < 8; ++u) { sum[u] = e0[u] + e1[u]; tt[u] = __shfl_xor_sync(0xffffffffu, sum[u], 1); }
            SCHED_FENCE();
#pragma unroll
            for (int u = 0; u < 8; ++u) { sum[u] += tt[u]; tt[u] = __shfl_xor_sync(0xffffffffu, sum[u], 2); }
            SCHED_FENCE();
#pragma unroll
            for (int u = 0; u < 8; ++u) sum[u] = rcp(sum[u] + tt[u]);
            SCHED_FENCE();
            float o[8][2][4];
#pragma unroll
            for (int u = 0; u < 8; ++u) {
                const int h = u >> 1;
                const uint32_t p = pack2(e0[u] * sum[u], e1[u] * sum[u]);
                const uint32_t* va = ((u & 1) ? v1 : v0) + 4 * h;
                const uint32_t* vb = ((u & 1) ? v2 : v1) + 4 * h;
#pragma unroll
                for (int d = 0; d < 2; ++d) {
                    o[u][d][0] = o[u][d][1] = o[u][d][2] = o[u][d][3] = 0.f;
                    mma16816(o[u][d], va[2 * d], va[2 * d + 1], vb[2 * d], vb[2 * d + 1], p & lomask, p & ~lomask);
                }
            }
            SCHED_FENCE();
            const uint32_t orow = mine + (lane & 7) * 128 + (((lane >> 3) ^ (lane & 7)) << 4);
#pragma unroll
            for (int u = 0; u < 8; ++u)
                stsm4t((orow ^ (((u >> 1) & 1) << 6)) + (u >> 2) * 8192 + (u & 1) * 1024, pack2(o[u][0][0], o[u][0][1]), pack2(o[u][0][2], o[u][0][3]),
                       pack2(o[u][1][0], o[u][1][1]), pack2(o[u][1][2], o[u][1][3]));
            fence_async_smem();
            __syncwarp();
            if (lane < 2) mbar_arrive(BAR_SFULL(sb, wg * 2 + lane));
            if (tid == 32) TL(41);
            bar_sync(1 + wg, 128);
            if (tid == 0) { TL(6); TC(106); }
            if (tid == 128) TL(44);
        }
        {
            float acc[64];
            uint32_t xr[32], gt[16];
            const uint32_t buf0 = sb + OFF_STG + wg * 16384;
            mainloop64<true, 16, LAGW, MIDW>(acc, sb, wg, tw, r, [&] {
                IDX();
                mbar_wait(BAR_ONE(sb, EV_GA), 0);
                stg.acquire2(sb, wg);
#pragma unroll
                for (int i = 0; i < 8; ++i) ldsm4(buf0 + (i >> 2) * 8192 + (pan_addr ^ ((i & 3) << 5)), xr[4 * i], xr[4 * i + 1], xr[4 * i + 2], xr[4 * i + 3]);
#pragma unroll
                for (int cg = 0; cg < 16; ++cg) gt[cg] = lds32(sb + OFF_TAB + cg * 16 + q4 * 4);
            });
            if (tid == 0) { TL(7); TC(107); }
            if (tid == 128) TL(42);
            IDX();
            float sm[4] = {0.f, 0.f, 0.f, 0.f}, sq[4] = {0.f, 0.f, 0.f, 0.f};
#pragma unroll
            for (int e = 0; e < 64; ++e) {
                acc[e] = fmaf((e & 1) ? bf_hi(gt[e >> 2]) : bf_lo(gt[e >> 2]), acc[e], (e & 1) ? bf_hi(xr[e >> 1]) : bf_lo(xr[e >> 1]));
                sm[e & 3] += acc[e]; sq[e & 3] = fmaf(acc[e], acc[e], sq[e & 3]);
            }
            {
                const float s0 = sm[0] + sm[1], s1 = sm[2] + sm[3], q0 = sq[0] + sq[1], q1 = sq[2] + sq[3];
                const bool od = lane & 1;
                float sv = (od ? s1 : s0) + __shfl_xor_sync(0xffffffffu, od ? s0 : s1, 1), qv = (od ? q1 : q0) + __shfl_xor_sync(0xffffffffu, od ? q0 : q1, 1);
                sv += __shfl_xor_sync(0xffffffffu, sv, 2); qv += __shfl_xor_sync(0xffffffffu, qv, 2);
                if (q4 < 2) st_pkt16(g_st2 + j * 512 + wg * 64 + w4 * 16 + g8 + q4 * 8, 0, __float_as_uint(sv), __float_as_uint(qv), ep);
            }
            if (tid == 0) TL(9);
            if (tid == 128) TL(34);
#pragma unroll
            for (int i = 0; i < 8; ++i)
                stsm4(buf0 + (i >> 2) * 8192 + (pan_addr ^ ((i & 3) << 5)), pack2(acc[8 * i], acc[8 * i + 1]), pack2(acc[8 * i + 2], acc[8 * i + 3]),
                      pack2(acc[8 * i + 4], acc[8 * i + 5]), pack2(acc[8 * i + 6], acc[8 * i + 7]));
            fence_async_smem();
            __syncwarp();
            mbar_wait(BAR_ONE(sb, EV_LN2), 0);
            LnPar lp; lp.load(sb, q4);
            if (tid == 0) TL(35);
            const LnRow n2 = merge_stats(g_st2 + wg * 64 + w4 * 16 + g8, 512, q4, ep, sb, lane < 2 ? BAR_SFULL(sb, wg * 2 + lane) : 0);
            if (tid == 0) TL(49);
            if (tid == 128) TL(45);
            ln_norm(xr, acc, n2);
            stg.acquire2(sb, wg);
            ln_emit(xr, lp, sb, wg, ix);
            if (tid == 0) { TL(36); TC(109); }
            if (tid == 128) TL(43);
        }
        {
            float a256[128], a128[64];
            mainloop32<true, LAG>(a256, a128, sb, wg, tw, r, EV_LAG1, 48, [&] {
                stg.acquire2(sb, wg);
                Ring q = r; if (!wg) q.next();
                mbar_wait(BAR_EMPTY(sb, q.slot), q.par ^ 1);
            });
            if (tid == 0) { TL(10); TC(110); }
            if (tid == 128) TL(51);
            glu_panel<0>(a256, sb + OFF_STG + wg * 16384, BAR_SFULL(sb, wg * 2));
            glu_panel<64>(a256, sb + OFF_STG + wg * 16384 + 8192, BAR_SFULL(sb, wg * 2 + 1));
            glu_panel<0>(a128, sb + (wg ? P3_SLOT1 : P3_SLOT0) * SLOT + 24576, BAR_ONE(sb, EV_P3 + wg));
            if (tid == 0) { TL(11); TC(111); }
            if (tid == 128) TL(52);
#pragma unroll 1
            for (int p = 0; p < 2; ++p) {
                float b256[128];
                mainloop32<false, LAGS>(b256, a128, sb, wg, tw, r, EV_LAG2 + p, 80 + 32 * p, [&] { stg.acquire2(sb, wg); });
                if (tid == 0) { TL(29 + 2 * p); TC(114 + 2 * p); }
                if (tid == 128) TL(53 + 2 * p);
                glu_panel<0>(b256, sb + OFF_STG + wg * 16384, BAR_SFULL(sb, wg * 2));
                glu_panel<64>(b256, sb + OFF_STG + wg * 16384 + 8192, BAR_SFULL(sb, wg * 2 + 1));
                if (tid == 0) { TL(30 + 2 * p); TC(115 + 2 * p); }
                if (tid == 128) TL(54 + 2 * p);
            }
            if (tid == 0) { TL(12); TC(112); }
        }
        {
            float acc[64];
            uint32_t xr[32], gt[16];
            const uint32_t buf0 = sb + OFF_STG + wg * 16384;
            mainloop64<false, 56, LAGD, 40>(acc, sb, wg, tw, r, [&] {
                IDX();
                mbar_wait(BAR_ONE(sb, EV_GB), 0);
                stg.acquire2(sb, wg);
#pragma unroll
                for (int i = 0; i < 8; ++i) ldsm4(buf0 + (i >> 2) * 8192 + (pan_addr ^ ((i & 3) << 5)), xr[4 * i], xr[4 * i + 1], xr[4 * i + 2], xr[4 * i + 3]);
#pragma unroll
                for (int cg = 0; cg < 16; ++cg) gt[cg] = lds32(sb + OFF_TAB + 256 + cg * 16 + q4 * 4);
            });
            cluster_arrive();
            if (tid == 0) { TL(13); TC(113); }
            if (tid == 128) TL(57);
            IDX();
#pragma unroll
            for (int p = 0; p < 2; ++p) {
#pragma unroll
                for (int e = 16 * p; e < 16 * p + 16; ++e)
                    xr[e] = pack2(fmaf(bf_lo(gt[e >> 1]), acc[2 * e], bf_lo(xr[e])), fmaf(bf_hi(gt[e >> 1]), acc[2 * e + 1], bf_hi(xr[e])));
#pragma unroll
                for (int i = 4 * p; i < 4 * p + 4; ++i) stsm4(buf0 + p * 8192 + (pan_addr ^ ((i & 3) << 5)), xr[4 * i], xr[4 * i + 1], xr[4 * i + 2], xr[4 * i + 3]);
                stg.publish(sb, wg, lane);
            }
            if (tid == 0) TL(14);
        }
      }
    } else {
        asm volatile("setmaxnreg.dec.sync.aligned.u32 56;");
        if (elect_one()) {
            if (warp == 8) {
#pragma unroll
                for (int i = 0; i < 4; ++i) {
                    mbar_init(BAR_ONE(sb, EV_WIN + i), 1);
                    if (!aux) {
                        mbar_expect_tx(BAR_ONE(sb, EV_WIN + i), 8192);
                        tma_load(sb + 5 * SLOT + i * 8192, &mp.wm8, 2 * i * 6144 + (m * 8 + j) * 16, 0, BAR_ONE(sb, EV_WIN + i));
                        tma_load(sb + 5 * SLOT + i * 8192 + 4096, &mp.wm8, (2 * i + 1) * 6144 + (m * 8 + j) * 16, 0, BAR_ONE(sb, EV_WIN + i));
                    }
                }
                prefetch_map(&mp.wqkv); prefetch_map(&mp.wmod);
#pragma unroll
                for (int i = 0; i < NSLOT; ++i) mbar_init(BAR_FULL(sb, i), 1);
                mbar_init(BAR_EMPTY(sb, NSLOT), 1);
            } else if (warp < 11) {
#pragma unroll
                for (int i = 0; i < 2; ++i) {
                    const uint32_t pn = (warp - 9) * 2 + i;
                    mbar_init(BAR_SREADY(sb, pn), 1);
                    if (!aux) {
                        mbar_expect_tx(BAR_SREADY(sb, pn), 8192);
                        tma_load3(sb + OFF_STG + pn * 8192, &mp.x, j * 128 + i * 64, m * 64 + (warp - 9) * 32, BAR_SREADY(sb, pn));
                    }
                    mbar_init(BAR_SFULL(sb, pn), 4);
                }
#pragma unroll
                for (int i = 0; i < 3; ++i) { mbar_init(BAR_EMPTY(sb, (warp - 9) * 3 + i), aux ? 1 : 4); mbar_init(BAR_FULL(sb, (warp - 9) * 3 + i) + AF_REL, 1); }
            } else {
#pragma unroll
                for (int i = EV_P0; i < EV_COUNT; ++i) mbar_init(BAR_ONE(sb, i), i == EV_P0 ? 16 : (i == EV_P3 || i == EV_P31) ? 4 : 1);
            }
            asm volatile("fence.mbarrier_init.release.cluster;" ::: "memory");
        }
        __syncwarp();
        LOAD_EP();
        cluster_arrive();
        cluster_wait();
        ep = __shfl_sync(0xffffffffu, ep, 0) / NCTA + 1;
        if (warp == 8) {
            const bool el = elect_one();
            Ring r{0, 1};
            if (aux) {
                mbar_wait(BAR_ONE(sb, EV_GO), 0);
#pragma unroll 1
                for (int it = 0; it < 64; ++it) {
                    const int col = 2048 + (it >> 4) * 1024 + j * 256;
                    mbar_wait(BAR_EMPTY(sb, r.slot), r.par);
                    const uint32_t st = sb + r.slot * SLOT, fb = BAR_FULL(sb, r.slot);
                    if (el) {
                        mbar_expect_tx(fb, 32768);
#pragma unroll
                        for (int b = 0; b < 4; ++b) tma_load(st + b * 8192, &mp.wmod, col + b * 64, (it & 15) * 64, fb);
                    }
                    r.next();
                }
            } else {
#pragma unroll 1
                for (int it = 0; it < 32; ++it) {
                    const int cb = j * 128 + rank * 64, k0 = kof(it, 2, j);
                    if (it == 2) mbar_wait(BAR_ONE(sb, EV_PAR), 0);
                    if (it == 5) mbar_wait(BAR_ONE(sb, EV_P0), 0);
                    if ((AGO & 1) && it == 6) mbar_wait(BAR_ONE(sb, EV_AGO), 0);
                    mbar_wait(BAR_EMPTY(sb, r.slot), r.par);
                    const uint32_t st = sb + r.slot * SLOT, fb = BAR_FULL(sb, r.slot);
                    if (el) {
                        mbar_expect_tx(fb, it < 4 ? 24576 : 28672);
                        tma_load_mc(st + 8192 + rank * 4096, &mp.wqkv, 1024 + cb, k0, fb);
                        tma_load_mc(st + 16384 + rank * 4096, &mp.wqkv, 2048 + cb, k0, fb);
                        tma_load_mc(st + 24576 + rank * 4096, &mp.wqkv, cb, k0, fb);
                        if (it < 4) mbar_arrive(fb + AF_REL);
                        if (it == PFWO + (m >> 1)) { tma_prefetch(&mp.wo, j * 128, m * 64); tma_prefetch(&mp.wo, j * 128 + 64, m * 64); }
                    }
                    r.next();
                }
                if (el) mbar_arrive(BAR_ONE(sb, EV_KV));
#pragma unroll 1
                for (int it = 0; it < 16; ++it) {
                    if ((AGO & 2) && it == 6) mbar_wait(BAR_ONE(sb, EV_AGO1), 0);
                    mbar_wait(BAR_EMPTY(sb, r.slot), r.par);
                    const uint32_t st = sb + r.slot * SLOT, fb = BAR_FULL(sb, r.slot);
                    if (el) {
                        mbar_expect_tx(fb, it < 2 ? 16384 : 24576);
                        tma_load_mc(st + 16384 + rank * 8192, &mp.wo, j * 128 + rank * 64, kof(it, 1, j), fb);
                        if (it < 2) mbar_arrive(fb + AF_REL);
                        if (it == 6) { prefetch_map(&mp.wg); prefetch_map(&mp.wu); }
                    }
                    r.next();
                }
                const CUtensorMap* wm = rank ? &mp.wu : &mp.wg;
#pragma unroll 1
                for (int g = 0; g < 96; ++g) {
                    if ((AGO & 4) && g == 6) mbar_wait(BAR_ONE(sb, EV_AGO2), 0);
                    const int p = g >> 5, cb = j * 448 + (p == 0 ? 0 : 64 + p * 128), k0 = p == 0 ? kof(g, 2, j) : (g & 31) * 32;
                    mbar_wait(BAR_EMPTY(sb, r.slot), r.par);
                    const uint32_t st = sb + r.slot * SLOT, fb = BAR_FULL(sb, r.slot);
                    if (el) {
                        mbar_expect_tx(fb, (g < 4 || p > 0) ? 24576 : 28672);
                        tma_load_mc(st + 8192 + rank * 4096, wm, cb, k0, fb);
                        tma_load_mc(st + 16384 + rank * 4096, wm, cb + 64, k0, fb);
                        if (p == 0) tma_load_mc(st + 24576 + rank * 4096, wm, cb + 128, k0, fb);
                        else if (ONEP) tma_load(st, &mp.h2l, k0, m * 128, fb);
                        if (g < 4) mbar_arrive(fb + AF_REL);
                        if (g == 90) prefetch_map(&mp.wd);
                    }
                    r.next();
                }
#pragma unroll 1
                for (int g = 0; g < 56; ++g) {
                    if (ONEP && (g == 0 || g == 24 || g == 40)) mbar_wait(BAR_ONE(sb, EV_H0 + (g >> 4)), 0);
                    const int k0 = kdown(g);
                    mbar_wait(BAR_EMPTY(sb, r.slot), r.par);
                    const uint32_t st = sb + r.slot * SLOT, fb = BAR_FULL(sb, r.slot);
                    if (el) {
                        mbar_expect_tx(fb, 32768);
                        tma_load_mc(st + 16384 + rank * 8192, &mp.wd, j * 128 + rank * 64, k0, fb);
                        if (ONEP) { tma_load(st, &mp.hb, k0, m * 128, fb); tma_load(st + 8192, &mp.hb, k0, m * 128 + 64, fb); }
                    }
                    r.next();
                }
            }
        } else if (aux) {
        } else if (warp == 11) {
            const bool el = elect_one();
            const int row0 = m * 128;
            const uint32_t* const fl = g_flags + (m * 32 + (lane & 16) + (kof(lane & 15, 1, j) >> 6)) * FS;
            if (el) { prefetch_map(&mp.h1h); prefetch_map(&mp.h2h); prefetch_map(&mp.h2l); }
            {
                const uint4* pk = pt.mail->mod1 + grp * 512 + j * 32 + lane;
                uint4 a, b; uint32_t n = 0;
                while (true) {
                    a = ld_pkt16(pk); b = ld_pkt16(pk + 256);
                    if (__all_sync(0xffffffffu, a.z == ep && b.z == ep)) break;
                    SPIN_GUARD(n);
                }
                sts128(sb + OFF_PAR + lane * 16, a.x, a.y, b.x, b.y);
                __syncwarp();
                if (lane == 0) { mbar_arrive(BAR_ONE(sb, EV_PAR)); TL(46); }
            }
            mbar_wait(BAR_ONE(sb, EV_P0), 0);
            Ring r{0, 1};
#pragma unroll 1
            for (int ph = 0; ph < 3; ++ph) {
                const int sh = ph == 1 ? 1 : 2, nst = 8 << sh;
                const uint32_t half = 16384 >> sh;
                const CUtensorMap* tm = ph == 0 ? &mp.h1h : ph == 1 ? &mp.o : &mp.h2h;
                if (ph == 1) fetch_halo(g_halo + ((m - 1) * 8 + j) * 512 + 256 + lane, m == 0, sb, 2, lane);
                const uint32_t target = ep * 8 + ST_H1 + ph;
                int a0 = 1 << sh, a1 = a0, fr = a0;
                r.skip(fr);
                uint32_t s0 = r.slot, s1 = r.slot, have = 0, n = 0;
                int k0 = j ? 0 : 128, k1 = k0;
#pragma unroll 1
                for (; fr < NSLOT; ++fr) { mbar_wait(BAR_EMPTY(sb, r.slot), r.par); r.next(); }
                uint32_t v = flag_get(fl);
                auto load = [&](int& a, uint32_t& sl, int& k, uint32_t w) {
                    const uint32_t fb = BAR_FULL(sb, sl) + (w ? 0 : AF_REL);
                    if (el) { if (!w) mbar_expect_tx(fb, half); tma_load(sb + sl * SLOT + w * half, tm, k, row0 + w * 64, fb); }
                    if (a == NSLOT - 1 && w == ((AGW >> ph) & 1) && el) mbar_arrive(BAR_ONE(sb, EV_AGO + ph));
                    ++a; if (++sl == NSLOT) sl = 0;
                    k += 128 >> sh; if (k == j * 128) k += 128;
                };
                do {
                    PS(0);
                    if (fr < 2 * NSLOT && mbar_test(BAR_EMPTY(sb, r.slot), r.par)) { ++fr; r.next(); }
                    SPIN_GUARD(n);
                    PS(1);
                    const bool ok = (int32_t)(v - target) >= 0;
                    v = flag_get(fl);
                    have = __ballot_sync(0xffffffffu, ok);
                    PS(2);
#pragma unroll 1
                    while (a1 < fr && (have & (0x10000u << (a1 >> (sh - 1))))) {
                        if (a1 == (1 << sh)) TL(16 + ph);
                        load(a1, s1, k1, 1);
                    }
                    PS(3);
#pragma unroll 1
                    while (a0 < fr && (have & (1u << (a0 >> (sh - 1))))) load(a0, s0, k0, 0);
                    PS(4);
                } while (have != 0xffffffffu);
#pragma unroll 1
                while (a0 < nst) {
                    mbar_wait(BAR_EMPTY(sb, r.slot), r.par);
                    r.next();
                    load(a1, s1, k1, 1); load(a0, s0, k0, 0);
                }
            }
#pragma unroll 1
            for (int p = 0; p < 3; ++p) {
                uint32_t n = 0;
                while (!__all_sync(0xffffffffu, (int32_t)(flag_get(fl) - (ep * 8 + ST_H + p)) >= 0)) { SPIN_GUARD(n); __nanosleep(500); }
                if (el) mbar_arrive(BAR_ONE(sb, EV_H0 + p));
            }
        } else {
            const uint32_t w = warp - 9;
            const int row0 = m * 128 + w * 64;
            const uint32_t stg = sb + OFF_STG + w * 16384;
            uint32_t* const fl = g_flags + (m * 32 + w * 16 + 2 * j) * FS;
            uint32_t b = 0, par = 0;
            const bool el = elect_one();
            auto store = [&](const CUtensorMap* tm, int col, bool nat = false) {
                mbar_wait(BAR_SFULL(sb, w * 2 + b), (par >> b) & 1);
                par ^= 1u << b;
                if (el) {
                    if (nat) tma_store3(tm, col, row0 >> 1, stg + b * 8192); else tma_store(tm, col, row0, stg + b * 8192);
                    bulk_commit();
                }
                b ^= 1;
            };
            auto load2 = [&](const CUtensorMap* tm, bool nat) {
                if (el) {
#pragma unroll
                    for (uint32_t i = 0; i < 2; ++i) {
                        mbar_expect_tx(BAR_SREADY(sb, w * 2 + i), 8192);
                        if (nat) tma_load3(stg + i * 8192, tm, j * 128 + i * 64, row0 >> 1, BAR_SREADY(sb, w * 2 + i));
                        else tma_load(stg + i * 8192, tm, j * 128 + i * 64, row0, BAR_SREADY(sb, w * 2 + i));
                    }
                }
            };
            auto send2 = [&](const CUtensorMap* tm, int step) {
                store(tm, j * 128); store(tm, j * 128 + 64);
                if (el) {
                    asm volatile("cp.async.bulk.wait_group 1;" ::: "memory"); flag_set(fl, ep * 8 + step);
                    bulk_wait_all(); flag_set(fl + FS, ep * 8 + step);
                }
            };
            auto free2 = [&]() { if (el) { mbar_arrive(BAR_SREADY(sb, w * 2)); mbar_arrive(BAR_SREADY(sb, w * 2 + 1)); } };
            auto gate = [&](int vec, int ev) {
                uint4 v; uint32_t n = 0;
                while (true) {
                    v = ld_pkt2(g_mod + vec * 512 + j * 64 + lane * 2);
                    if (__all_sync(0xffffffffu, v.y == ep && v.w == ep)) break;
                    SPIN_GUARD(n); __nanosleep(300);
                }
                asm volatile("st.shared.v2.u32 [%0], {%1, %2};" :: "r"(sb + OFF_TAB + (ev - EV_GA) * 256 + lane * 8), "r"(v.x), "r"(v.z) : "memory");
                __syncwarp();
                if (lane == 0) mbar_arrive(BAR_ONE(sb, ev));
            };
            if (el) { prefetch_map(&mp.h1s); prefetch_map(&mp.o); prefetch_map(&mp.x1); prefetch_map(&mp.h2s); prefetch_map(&mp.hb); prefetch_map(&mp.out); prefetch_map(&mp.wo); }
            send2(&mp.h1s, ST_H1);
            if (w == 0) TL(47);
            free2();
            if (w == 0) fetch_halo(g_halo + ((m - 1) * 8 + j) * 512 + lane, m == 0, sb, 0, lane);
            else { mbar_wait(BAR_SFULL(sb, 0), 0); gate(2, EV_GA); }
            send2(&mp.o, ST_O);
            if (w == 0) TL(40); else TL(38);
            mbar_wait(BAR_ONE(sb, EV_OWN + w), 0);
            load2(&mp.x, true);
            if (w == 1) {
                uint32_t n = 0;
                while ((int32_t)(flag_get(g_flags + FL_LN2) - ep * 8) < 0) { SPIN_GUARD(n); __nanosleep(200); }
                const uint4 v = __ldcg((const uint4*)(g_par2 + j * 128) + lane);
                sts128(sb + OFF_PAR + lane * 16, v.x, v.y, v.z, v.w);
                __syncwarp();
                if (lane == 0) mbar_arrive(BAR_ONE(sb, EV_LN2));
            }
            store(&mp.x1, j * 128); store(&mp.x1, j * 128 + 64);
            if (el) bulk_wait_read();
            free2();
            send2(&mp.h2s, ST_H2);
            if (w == 0) TL(37);
            free2();
            if (w == 1) gate(5, EV_GB);
#pragma unroll 1
            for (int p = 0; p < 3; ++p) {
                const int col = j * 448 + (p ? 64 + p * 128 : 0);
                store(&mp.hb, col); store(&mp.hb, col + 64);
                if (p == 0) {
                    mbar_wait(BAR_ONE(sb, EV_P3 + w), 0);
                    if (el) { tma_store(&mp.hb, col + 128, row0, sb + (w ? P3_SLOT1 : P3_SLOT0) * SLOT + 24576); bulk_commit(); }
                }
                if (el) { bulk_wait_all(); flag_set(fl, ep * 8 + ST_H + p); flag_set(fl + FS, ep * 8 + ST_H + p); }
                if (p < 2) free2();
            }
            load2(&mp.x1, false);
            cluster_arrive_early = true;
            cluster_arrive();
            store(&mp.out, j * 128, true); store(&mp.out, j * 128 + 64, true);
            if (el) bulk_wait_read();
        }
        __syncwarp();
    }
    if (aux || (wg == 2 && !cluster_arrive_early)) cluster_arrive();
    cluster_wait();
    if (tid == 0) {
        TL(15);
        flag_add(pt.mail->flags + FL_DONE);
    }
}

typedef CUresult (*EncodeFn)(CUtensorMap*, CUtensorMapDataType, cuuint32_t, void*, const cuuint64_t*, const cuuint64_t*, const cuuint32_t*,
                             const cuuint32_t*, CUtensorMapInterleave, CUtensorMapSwizzle, CUtensorMapL2promotion, CUtensorMapFloatOOBfill);

void make_map(EncodeFn fn, CUtensorMap* m, const void* ptr, uint64_t rows, uint64_t cols, uint32_t brows, uint32_t bcols) {
    cuuint64_t dims[2] = {cols, rows}, strides[1] = {cols * 2};
    cuuint32_t box[2] = {bcols, brows}, es[2] = {1, 1};
    fn(m, CU_TENSOR_MAP_DATA_TYPE_BFLOAT16, 2, (void*)ptr, dims, strides, box, es, CU_TENSOR_MAP_INTERLEAVE_NONE,
       bcols == 64 ? CU_TENSOR_MAP_SWIZZLE_128B : bcols == 32 ? CU_TENSOR_MAP_SWIZZLE_64B : CU_TENSOR_MAP_SWIZZLE_NONE, CU_TENSOR_MAP_L2_PROMOTION_L2_256B, CU_TENSOR_MAP_FLOAT_OOB_FILL_NONE);
}

void make_map3(EncodeFn fn, CUtensorMap* m, const void* ptr) {
    cuuint64_t dims[3] = {D_, S_ / 2, 2}, strides[2] = {4 * D_, 2 * D_};
    cuuint32_t box[3] = {64, 32, 2}, es[3] = {1, 1, 1};
    fn(m, CU_TENSOR_MAP_DATA_TYPE_BFLOAT16, 3, (void*)ptr, dims, strides, box, es, CU_TENSOR_MAP_INTERLEAVE_NONE,
       CU_TENSOR_MAP_SWIZZLE_128B, CU_TENSOR_MAP_L2_PROMOTION_L2_256B, CU_TENSOR_MAP_FLOAT_OOB_FILL_NONE);
}

}

extern "C" void kernel_launch(void* const* d_in, const int* in_sizes, int n_in, void* d_out, int out_size) {
    (void)in_sizes; (void)n_in; (void)out_size;
    void* fnp = nullptr;
    cudaDriverEntryPointQueryResult qr;
    cudaGetDriverEntryPoint("cuTensorMapEncodeTiled", &fnp, cudaEnableDefault, &qr);
    EncodeFn fn = (EncodeFn)fnp;
    void *h1, *o, *x1, *h2, *hb, *mail;
    cudaGetSymbolAddress(&h1, g_h1);
    cudaGetSymbolAddress(&mail, g_mail);
    cudaGetSymbolAddress(&o, g_o);
    cudaGetSymbolAddress(&hb, g_hb);
    x1 = h1; h2 = o;
    Maps mp;
    make_map(fn, &mp.h1h, h1, S_, D_, 64, 32);
    make_map(fn, &mp.h2h, h2, S_, D_, 64, 32);
    make_map(fn, &mp.h1s, h1, S_, D_, 64, 64);
    make_map(fn, &mp.o, o, S_, D_, 64, 64);
    make_map(fn, &mp.h2l, h2, S_, D_, 128, 32);
    make_map(fn, &mp.h2s, h2, S_, D_, 64, 64);
    make_map(fn, &mp.hb, hb, S_, F_, 64, 64);
    make_map(fn, &mp.wqkv, d_in[1], D_, 3 * D_, 32, 64);
    make_map(fn, &mp.wo, d_in[2], D_, D_, 64, 64);
    make_map(fn, &mp.wg, d_in[4], D_, F_, 32, 64);
    make_map(fn, &mp.wu, d_in[5], D_, F_, 32, 64);
    make_map(fn, &mp.wd, d_in[6], F_, D_, 64, 64);
    make_map(fn, &mp.wmod, d_in[8], D_, 6 * D_, 64, 64);
    make_map(fn, &mp.wm8, d_in[8], D_ / 8, 8 * 6 * D_, 128, 16);
    make_map3(fn, &mp.x, d_in[0]);
    make_map(fn, &mp.x1, x1, S_, D_, 64, 64);
    make_map3(fn, &mp.out, d_out);
    cudaFuncSetAttribute(fused_block_kernel, cudaFuncAttributeMaxDynamicSharedMemorySize, SMEM_BYTES);
    cudaLaunchConfig_t cfg = {};
    cfg.gridDim = dim3(NCTA); cfg.blockDim = dim3(384); cfg.dynamicSmemBytes = SMEM_BYTES; cfg.stream = cudaStreamPerThread;
    cudaLaunchAttribute at[1];
    at[0].id = cudaLaunchAttributeClusterDimension; at[0].val.clusterDim.x = 2; at[0].val.clusterDim.y = 1; at[0].val.clusterDim.z = 1;
    cfg.attrs = at; cfg.numAttrs = 1;
    const Ptrs pt{(const __nv_bfloat16*)d_in[7], (Mail*)mail};
    cudaLaunchKernelEx(&cfg, fused_block_kernel, pt, mp);
}
```

```cpp
#include <cuda_runtime.h>
#include <cuda_bf16.h>
#include <cuda.h>
#include <stdint.h>
#include <stddef.h>

#define LAG 3
#define LAGS 3
#define LAGW 3
#define LAGD 3
#define LAGQ 4
#define MIDW 8
#define PFWO 14
#define FLAGRED 1
#define FS 1
#define GFENCE 0
#define AGO 7
#define AGW 6
#define LAGSIG 1
#define ONEP 1
#define SIGW 1
#define SIGD 1
#define CSW 0
#define FENCES 1
#define LWAIT 2
#define RESET 1
#define BW0 0
#define BWEV EV_WIN
#define GODLY 0
#define BW1 3
#define KDEBUG 0

namespace {

constexpr int S_ = 2048, D_ = 1024, F_ = 3584;
constexpr int NCTA = 132;
constexpr int NSLOT = 6;
constexpr uint32_t SLOT = 32768;
constexpr uint32_t OFF_STG = NSLOT * SLOT;
constexpr uint32_t OFF_BAR = OFF_STG + 32768;
constexpr uint32_t OFF_PAR = OFF_BAR + 512;
constexpr uint32_t OFF_TAB = OFF_PAR + 768;
constexpr uint32_t OFF_TL = OFF_PAR + 2048;
constexpr uint32_t SMEM_BYTES = OFF_TL + (KDEBUG ? 512 : 0);
constexpr uint32_t P3_SLOT1 = (32 + 16 + 32) % NSLOT, P3_SLOT0 = (P3_SLOT1 + 1) % NSLOT;

constexpr uint32_t X1_SLOT = (32 + 16) % NSLOT;
static_assert(X1_SLOT + 3 < NSLOT && LAGW <= 4, "x1 parking");
constexpr int ST_H1 = 1, ST_O = 2, ST_H2 = 3, ST_H = 4, FL_DONE = 0, FL_LN2 = 1, FL_PROG = 32;

struct Maps {
    CUtensorMap h1h, h1s, o, h2h, h2l, h2s, hb, wqkv, wo, wg, wu, wd, wmod, wm8, x, x1, out;
};

struct Mail {
    uint32_t flags[16 * 32 * FS + 32];
    uint2 mod[6 * D_ / 2];
    uint4 mod1[8 * 512];
    uint4 st1[8 * S_];
    uint32_t par2[D_];
    uint4 halo[128 * 512];
};
struct Ptrs { const __nv_bfloat16* c; Mail* mail; };

__device__ __align__(128) Mail g_mail;
__device__ __align__(128) __nv_bfloat16 g_h1[S_ * D_];
__device__ __align__(128) __nv_bfloat16 g_o[S_ * D_];
__device__ __align__(128) __nv_bfloat16 g_hb[S_ * F_];
#define TL(i) do {} while (0)
#define TC(i) do {} while (0)
#define TS(g, which) do {} while (0)
#define CS(i) do {} while (0)

#define PS(i) do {} while (0)
__device__ __forceinline__ uint32_t smem_u32(const void* p) { return (uint32_t)__cvta_generic_to_shared(p); }
__device__ __forceinline__ void mbar_init(uint32_t bar, uint32_t cnt) { asm volatile("mbarrier.init.shared::cta.b64 [%0], %1;" :: "r"(bar), "r"(cnt) : "memory"); }
__device__ __forceinline__ void mbar_expect_tx(uint32_t bar, uint32_t bytes) { asm volatile("mbarrier.arrive.expect_tx.shared::cta.b64 _, [%0], %1;" :: "r"(bar), "r"(bytes) : "memory"); }
__device__ __forceinline__ void mbar_arrive(uint32_t bar) { asm volatile("mbarrier.arrive.shared::cta.b64 _, [%0];" :: "r"(bar) : "memory"); }
__device__ __forceinline__ void mbar_arrive_cta(uint32_t bar, uint32_t cta) {
    asm volatile("{\n.reg .b32 r;\nmapa.shared::cluster.u32 r, %0, %1;\nmbarrier.arrive.shared::cluster.b64 _, [r];\n}" :: "r"(bar), "r"(cta) : "memory");
}
__device__ __forceinline__ void mbar_wait(uint32_t bar, uint32_t parity) {
    asm volatile("{\n.reg .pred p;\n.reg .u32 n;\nmov.u32 n, 0;\n"
        "W_LOOP:\nmbarrier.try_wait.parity.shared::cta.b64 p, [%0], %1;\n@p bra W_DONE;\n"
        "add.u32 n, n, 1;\nsetp.lt.u32 p, n, 0x400000;\n@p bra W_LOOP;\ntrap;\nW_DONE:\n}" :: "r"(bar), "r"(parity) : "memory");
}
__device__ __forceinline__ void mbar_wait2(uint32_t b0, uint32_t b1, uint32_t parity) {
    asm volatile("{\n.reg .pred p, q;\n.reg .u32 n;\nmov.u32 n, 0;\n"
        "W_LOOP:\nmbarrier.try_wait.parity.shared::cta.b64 p, [%0], %2;\nmbarrier.try_wait.parity.shared::cta.b64 q, [%1], %2;\nand.pred p, p, q;\n@p bra W_DONE;\n"
        "add.u32 n, n, 1;\nsetp.lt.u32 p, n, 0x400000;\n@p bra W_LOOP;\ntrap;\nW_DONE:\n}" :: "r"(b0), "r"(b1), "r"(parity) : "memory");
}
__device__ __forceinline__ bool mbar_test(uint32_t bar, uint32_t parity) {
    uint32_t r; asm volatile("{\n.reg .pred p;\nmbarrier.test_wait.parity.shared::cta.b64 p, [%1], %2;\nselp.u32 %0, 1, 0, p;\n}" : "=r"(r) : "r"(bar), "r"(parity) : "memory"); return r;
}
__device__ __forceinline__ bool mbar_test2(uint32_t b0, uint32_t b1, uint32_t parity) {
    uint32_t r;
    asm volatile("{\n.reg .pred p, q;\nmbarrier.test_wait.parity.shared::cta.b64 p, [%1], %3;\nmbarrier.test_wait.parity.shared::cta.b64 q, [%2], %3;\n"
        "and.pred p, p, q;\nselp.u32 %0, 1, 0, p;\n}" : "=r"(r) : "r"(b0), "r"(b1), "r"(parity) : "memory");
    return r;
}
__device__ __forceinline__ void tma_load3(uint32_t dst, const CUtensorMap* m, int c0, int c1, uint32_t bar) {
    asm volatile("cp.async.bulk.tensor.3d.shared::cluster.global.mbarrier::complete_tx::bytes [%0], [%1, {%3, %4, %5}], [%2];"
        :: "r"(dst), "l"(m), "r"(bar), "r"(c0), "r"(c1), "r"(0) : "memory");
}
__device__ __forceinline__ void tma_store3(const CUtensorMap* m, int c0, int c1, uint32_t src) {
    asm volatile("cp.async.bulk.tensor.3d.global.shared::cta.bulk_group [%0, {%2, %3, %4}], [%1];" :: "l"(m), "r"(src), "r"(c0), "r"(c1), "r"(0) : "memory");
}
__device__ __forceinline__ void tma_load(uint32_t dst, const CUtensorMap* m, int c0, int c1, uint32_t bar) {
    asm volatile("cp.async.bulk.tensor.2d.shared::cluster.global.mbarrier::complete_tx::bytes [%0], [%1, {%3, %4}], [%2];"
        :: "r"(dst), "l"(m), "r"(bar), "r"(c0), "r"(c1) : "memory");
}
__device__ __forceinline__ void tma_load_mc(uint32_t dst, const CUtensorMap* m, int c0, int c1, uint32_t bar) {
    asm volatile("cp.async.bulk.tensor.2d.shared::cluster.global.mbarrier::complete_tx::bytes.multicast::cluster.L2::cache_hint [%0], [%1, {%3, %4}], [%2], %5, %6;"
        :: "r"(dst), "l"(m), "r"(bar), "r"(c0), "r"(c1), "h"((uint16_t)3), "l"(0x12F0000000000000ull) : "memory");
}
__device__ __forceinline__ void tma_prefetch(const CUtensorMap* m, int c0, int c1) {
    asm volatile("cp.async.bulk.prefetch.tensor.2d.L2.global [%0, {%1, %2}];" :: "l"(m), "r"(c0), "r"(c1) : "memory");
}
__device__ __forceinline__ void tma_store(const CUtensorMap* m, int c0, int c1, uint32_t src) {
    asm volatile("cp.async.bulk.tensor.2d.global.shared::cta.bulk_group [%0, {%2, %3}], [%1];" :: "l"(m), "r"(src), "r"(c0), "r"(c1) : "memory");
}
__device__ __forceinline__ void bulk_commit() { asm volatile("cp.async.bulk.commit_group;" ::: "memory"); }
__device__ __forceinline__ void bulk_wait_read() { asm volatile("cp.async.bulk.wait_group.read 0;" ::: "memory"); }
__device__ __forceinline__ void bulk_wait_all() { asm volatile("cp.async.bulk.wait_group 0;" ::: "memory"); }
__device__ __forceinline__ void fence_async_smem() { asm volatile("fence.proxy.async.shared::cta;" ::: "memory"); }
__device__ __forceinline__ void fence_async_global() { if (GFENCE) asm volatile("fence.proxy.async.global;" ::: "memory"); }
__device__ __forceinline__ void prefetch_map(const CUtensorMap* m) { asm volatile("prefetch.tensormap [%0];" :: "l"(m) : "memory"); }
__device__ __forceinline__ void wg_fence() { asm volatile("wgmma.fence.sync.aligned;" ::: "memory"); }
__device__ __forceinline__ void wg_commit() { asm volatile("wgmma.commit_group.sync.aligned;" ::: "memory"); }
template <int N> __device__ __forceinline__ void wg_wait() { asm volatile("wgmma.wait_group.sync.aligned %0;" :: "n"(N) : "memory"); }
__device__ __forceinline__ void bar_sync(int id, int n) { asm volatile("bar.sync %0, %1;" :: "r"(id), "r"(n) : "memory"); }
__device__ __forceinline__ void bar_arrive(int id, int n) { asm volatile("bar.arrive %0, %1;" :: "r"(id), "r"(n) : "memory"); }
__device__ __forceinline__ void flag_add(uint32_t* f) { asm volatile("red.relaxed.gpu.global.add.u32 [%0], 1;" :: "l"(f) : "memory"); }
__device__ __forceinline__ void flag_set(uint32_t* f, uint32_t v) { asm volatile("red.relaxed.gpu.global.max.u32 [%0], %1;" :: "l"(f), "r"(v) : "memory"); }
__device__ __forceinline__ uint32_t flag_get(const uint32_t* f) { uint32_t v; asm volatile("ld.relaxed.gpu.global.u32 %0, [%1];" : "=r"(v) : "l"(f) : "memory"); return v; }
__device__ __forceinline__ uint32_t d16(uint32_t addr) { return (addr & 0x3FFFF) >> 4; }
__device__ __forceinline__ uint64_t mk_desc(uint32_t a16, uint32_t off, uint32_t lbo, uint32_t sbo, uint32_t swz) {
    const uint32_t lo = a16 + (off >> 4) + ((lbo >> 4) << 16), hi = (sbo >> 4) | (swz << 30);
    return ((uint64_t)hi << 32) | lo;
}
__device__ __forceinline__ uint32_t pack2(float lo, float hi) {
    uint32_t r; asm("cvt.rn.bf16x2.f32 %0, %1, %2;" : "=r"(r) : "f"(hi), "f"(lo)); return r;
}
__device__ __forceinline__ uint32_t hfma2_bf16(uint32_t a, uint32_t b, uint32_t c) {
    uint32_t r; asm("fma.rn.bf16x2 %0, %1, %2, %3;" : "=r"(r) : "r"(a), "r"(b), "r"(c)); return r;
}
__device__ __forceinline__ float bf_lo(uint32_t v) { return __uint_as_float(v << 16); }
__device__ __forceinline__ float bf_hi(uint32_t v) { return __uint_as_float(v & 0xFFFF0000u); }
__device__ __forceinline__ void unpack2(uint32_t v, float& lo, float& hi) {
    asm volatile("shl.b32 %0, %2, 16;\nand.b32 %1, %2, 0xffff0000;" : "=f"(lo), "=f"(hi) : "r"(v));
}
__device__ __forceinline__ float bf_round(float x) { return __bfloat162float(__float2bfloat16_rn(x)); }
__device__ __forceinline__ void stsm4(uint32_t addr, uint32_t r0, uint32_t r1, uint32_t r2, uint32_t r3) {
    asm volatile("stmatrix.sync.aligned.m8n8.x4.shared.b16 [%0], {%1, %2, %3, %4};" :: "r"(addr), "r"(r0), "r"(r1), "r"(r2), "r"(r3) : "memory");
}
__device__ __forceinline__ void stsm4t(uint32_t addr, uint32_t r0, uint32_t r1, uint32_t r2, uint32_t r3) {
    asm volatile("stmatrix.sync.aligned.m8n8.x4.trans.shared.b16 [%0], {%1, %2, %3, %4};" :: "r"(addr), "r"(r0), "r"(r1), "r"(r2), "r"(r3) : "memory");
}
__device__ __forceinline__ uint32_t movm(uint32_t a) { uint32_t d; asm volatile("movmatrix.sync.aligned.m8n8.trans.b16 %0, %1;" : "=r"(d) : "r"(a)); return d; }
__device__ __forceinline__ void ldsm4(uint32_t addr, uint32_t& r0, uint32_t& r1, uint32_t& r2, uint32_t& r3) {
    asm volatile("ldmatrix.sync.aligned.m8n8.x4.shared.b16 {%0, %1, %2, %3}, [%4];" : "=r"(r0), "=r"(r1), "=r"(r2), "=r"(r3) : "r"(addr) : "memory");
}
__device__ __forceinline__ void ldsm4t(uint32_t addr, uint32_t& r0, uint32_t& r1, uint32_t& r2, uint32_t& r3) {
    asm volatile("ldmatrix.sync.aligned.m8n8.x4.trans.shared.b16 {%0, %1, %2, %3}, [%4];" : "=r"(r0), "=r"(r1), "=r"(r2), "=r"(r3) : "r"(addr) : "memory");
}
__device__ __forceinline__ void mma16816(float (&c)[4], uint32_t a0, uint32_t a1, uint32_t a2, uint32_t a3, uint32_t b0, uint32_t b1) {
    asm("mma.sync.aligned.m16n8k16.row.col.f32.bf16.bf16.f32 {%0, %1, %2, %3}, {%4, %5, %6, %7}, {%8, %9}, {%0, %1, %2, %3};"
        : "+f"(c[0]), "+f"(c[1]), "+f"(c[2]), "+f"(c[3]) : "r"(a0), "r"(a1), "r"(a2), "r"(a3), "r"(b0), "r"(b1));
}
__device__ __forceinline__ float rcp(float x) { float r; asm("rcp.approx.ftz.f32 %0, %1;" : "=f"(r) : "f"(x)); return r; }
__device__ __forceinline__ float ex2(float x) { float r; asm("ex2.approx.ftz.f32 %0, %1;" : "=f"(r) : "f"(x)); return r; }
__device__ __forceinline__ float glu_half(float gh, float uh) {
    float t; asm("tanh.approx.f32 %0, %1;" : "=f"(t) : "f"(gh)); return fmaf(t, uh, uh);
}
__device__ __forceinline__ float silu_(float x) { return __fdividef(x, 1.f + __expf(-x)); }
__device__ __forceinline__ void st_pkt(void* p, uint32_t a, uint32_t b) {
    asm volatile("{\n.reg .b64 t;\nmov.b64 t, {%1, %2};\nst.relaxed.gpu.global.b64 [%0], t;\n}" :: "l"(p), "r"(a), "r"(b) : "memory");
}
__device__ __forceinline__ uint4 ld_pkt2(const void* p) {
    uint4 v; asm volatile("{\n.reg .b64 t, u;\nld.relaxed.gpu.global.v2.b64 {t, u}, [%4];\nmov.b64 {%0, %1}, t;\nmov.b64 {%2, %3}, u;\n}"
        : "=r"(v.x), "=r"(v.y), "=r"(v.z), "=r"(v.w) : "l"(p) : "memory"); return v;
}
__device__ __forceinline__ void st_pkt16(void* p, uint32_t a, uint32_t b, uint32_t c, uint32_t d) {
    asm volatile("{\n.reg .b64 t, u;\n.reg .b128 w;\nmov.b64 t, {%1, %2};\nmov.b64 u, {%3, %4};\nmov.b128 w, {t, u};\nst.relaxed.gpu.global.b128 [%0], w;\n}"
        :: "l"(p), "r"(a), "r"(b), "r"(c), "r"(d) : "memory");
}
__device__ __forceinline__ uint4 ld_pkt16(const void* p) {
    uint4 v; asm volatile("{\n.reg .b64 t, u;\n.reg .b128 w;\nld.relaxed.gpu.global.b128 w, [%4];\nmov.b128 {t, u}, w;\nmov.b64 {%0, %1}, t;\nmov.b64 {%2, %3}, u;\n}"
        : "=r"(v.x), "=r"(v.y), "=r"(v.z), "=r"(v.w) : "l"(p) : "memory"); return v;
}
#define SPIN_GUARD(n) do { if (++(n) > (1u << 22)) asm volatile("trap;"); } while (0)
__device__ __forceinline__ uint4 lds128(uint32_t a) { uint4 v; asm volatile("ld.shared.v4.u32 {%0, %1, %2, %3}, [%4];" : "=r"(v.x), "=r"(v.y), "=r"(v.z), "=r"(v.w) : "r"(a) : "memory"); return v; }
__device__ __forceinline__ void sts128(uint32_t a, uint32_t x, uint32_t y, uint32_t z, uint32_t w) { asm volatile("st.shared.v4.u32 [%0], {%1, %2, %3, %4};" :: "r"(a), "r"(x), "r"(y), "r"(z), "r"(w) : "memory"); }
__device__ __forceinline__ uint32_t lds32(uint32_t a) { uint32_t v; asm volatile("ld.shared.u32 %0, [%1];" : "=r"(v) : "r"(a) : "memory"); return v; }
__device__ __forceinline__ void sts32(uint32_t a, uint32_t v) { asm volatile("st.shared.u32 [%0], %1;" :: "r"(a), "r"(v) : "memory"); }
__device__ __forceinline__ bool elect_one() {
    uint32_t p; asm volatile("{\n.reg .pred q;\nelect.sync _|q, 0xffffffff;\nselp.u32 %0, 1, 0, q;\n}" : "=r"(p)); return p;
}
__device__ __forceinline__ void cluster_arrive() { asm volatile("barrier.cluster.arrive.relaxed.aligned;" ::: "memory"); }
__device__ __forceinline__ void cluster_wait() { asm volatile("barrier.cluster.wait.aligned;" ::: "memory"); }

__device__ __forceinline__ void wgmma_n128_z(float (&d)[64], uint64_t da, uint64_t db) {
    asm volatile("{\n.reg .pred p;\nsetp.ne.b32 p, 0, 0;\n"
        "wgmma.mma_async.sync.aligned.m64n128k16.f32.bf16.bf16 {"
        "%0, %1, %2, %3, %4, %5, %6, %7, %8, %9, %10, %11, %12, %13, %14, %15, "
        "%16, %17, %18, %19, %20, %21, %22, %23, %24, %25, %26, %27, %28, %29, %30, %31, "
        "%32, %33, %34, %35, %36, %37, %38, %39, %40, %41, %42, %43, %44, %45, %46, %47, "
        "%48, %49, %50, %51, %52, %53, %54, %55, %56, %57, %58, %59, %60, %61, %62, %63"
        "}, %64, %65, p, 1, 1, 0, 1;\n}\n"
        : "=f"(d[0]), "=f"(d[1]), "=f"(d[2]), "=f"(d[3]), "=f"(d[4]), "=f"(d[5]), "=f"(d[6]), "=f"(d[7]),
          "=f"(d[8]), "=f"(d[9]), "=f"(d[10]), "=f"(d[11]), "=f"(d[12]), "=f"(d[13]), "=f"(d[14]), "=f"(d[15]),
          "=f"(d[16]), "=f"(d[17]), "=f"(d[18]), "=f"(d[19]), "=f"(d[20]), "=f"(d[21]), "=f"(d[22]), "=f"(d[23]),
          "=f"(d[24]), "=f"(d[25]), "=f"(d[26]), "=f"(d[27]), "=f"(d[28]), "=f"(d[29]), "=f"(d[30]), "=f"(d[31]),
          "=f"(d[32]), "=f"(d[33]), "=f"(d[34]), "=f"(d[35]), "=f"(d[36]), "=f"(d[37]), "=f"(d[38]), "=f"(d[39]),
          "=f"(d[40]), "=f"(d[41]), "=f"(d[42]), "=f"(d[43]), "=f"(d[44]), "=f"(d[45]), "=f"(d[46]), "=f"(d[47]),
          "=f"(d[48]), "=f"(d[49]), "=f"(d[50]), "=f"(d[51]), "=f"(d[52]), "=f"(d[53]), "=f"(d[54]), "=f"(d[55]),
          "=f"(d[56]), "=f"(d[57]), "=f"(d[58]), "=f"(d[59]), "=f"(d[60]), "=f"(d[61]), "=f"(d[62]), "=f"(d[63])
        : "l"(da), "l"(db));
}
__device__ __forceinline__ void wgmma_n128(float (&d)[64], uint64_t da, uint64_t db) {
    asm volatile("{\n.reg .pred p;\nsetp.eq.b32 p, 0, 0;\n"
        "wgmma.mma_async.sync.aligned.m64n128k16.f32.bf16.bf16 {"
        "%0, %1, %2, %3, %4, %5, %6, %7, %8, %9, %10, %11, %12, %13, %14, %15, "
        "%16, %17, %18, %19, %20, %21, %22, %23, %24, %25, %26, %27, %28, %29, %30, %31, "
        "%32, %33, %34, %35, %36, %37, %38, %39, %40, %41, %42, %43, %44, %45, %46, %47, "
        "%48, %49, %50, %51, %52, %53, %54, %55, %56, %57, %58, %59, %60, %61, %62, %63"
        "}, %64, %65, p, 1, 1, 0, 1;\n}\n"
        : "+f"(d[0]), "+f"(d[1]), "+f"(d[2]), "+f"(d[3]), "+f"(d[4]), "+f"(d[5]), "+f"(d[6]), "+f"(d[7]),
          "+f"(d[8]), "+f"(d[9]), "+f"(d[10]), "+f"(d[11]), "+f"(d[12]), "+f"(d[13]), "+f"(d[14]), "+f"(d[15]),
          "+f"(d[16]), "+f"(d[17]), "+f"(d[18]), "+f"(d[19]), "+f"(d[20]), "+f"(d[21]), "+f"(d[22]), "+f"(d[23]),
          "+f"(d[24]), "+f"(d[25]), "+f"(d[26]), "+f"(d[27]), "+f"(d[28]), "+f"(d[29]), "+f"(d[30]), "+f"(d[31]),
          "+f"(d[32]), "+f"(d[33]), "+f"(d[34]), "+f"(d[35]), "+f"(d[36]), "+f"(d[37]), "+f"(d[38]), "+f"(d[39]),
          "+f"(d[40]), "+f"(d[41]), "+f"(d[42]), "+f"(d[43]), "+f"(d[44]), "+f"(d[45]), "+f"(d[46]), "+f"(d[47]),
          "+f"(d[48]), "+f"(d[49]), "+f"(d[50]), "+f"(d[51]), "+f"(d[52]), "+f"(d[53]), "+f"(d[54]), "+f"(d[55]),
          "+f"(d[56]), "+f"(d[57]), "+f"(d[58]), "+f"(d[59]), "+f"(d[60]), "+f"(d[61]), "+f"(d[62]), "+f"(d[63])
        : "l"(da), "l"(db));
}
__device__ __forceinline__ void wgmma_n256_z(float (&d)[128], uint64_t da, uint64_t db) {
    asm volatile("{\n.reg .pred p;\nsetp.ne.b32 p, 0, 0;\n"
        "wgmma.mma_async.sync.aligned.m64n256k16.f32.bf16.bf16 {"
        "%0, %1, %2, %3, %4, %5, %6, %7, %8, %9, %10, %11, %12, %13, %14, %15, "
        "%16, %17, %18, %19, %20, %21, %22, %23, %24, %25, %26, %27, %28, %29, %30, %31, "
        "%32, %33, %34, %35, %36, %37, %38, %39, %40, %41, %42, %43, %44, %45, %46, %47, "
        "%48, %49, %50, %51, %52, %53, %54, %55, %56, %57, %58, %59, %60, %61, %62, %63, "
        "%64, %65, %66, %67, %68, %69, %70, %71, %72, %73, %74, %75, %76, %77, %78, %79, "
        "%80, %81, %82, %83, %84, %85, %86, %87, %88, %89, %90, %91, %92, %93, %94, %95, "
        "%96, %97, %98, %99, %100, %101, %102, %103, %104, %105, %106, %107, %108, %109, %110, %111, "
        "%112, %113, %114, %115, %116, %117, %118, %119, %120, %121, %122, %123, %124, %125, %126, %127"
        "}, %128, %129, p, 1, 1, 0, 1;\n}\n"
        : "=f"(d[0]), "=f"(d[1]), "=f"(d[2]), "=f"(d[3]), "=f"(d[4]), "=f"(d[5]), "=f"(d[6]), "=f"(d[7]),
          "=f"(d[8]), "=f"(d[9]), "=f"(d[10]), "=f"(d[11]), "=f"(d[12]), "=f"(d[13]), "=f"(d[14]), "=f"(d[15]),
          "=f"(d[16]), "=f"(d[17]), "=f"(d[18]), "=f"(d[19]), "=f"(d[20]), "=f"(d[21]), "=f"(d[22]), "=f"(d[23]),
          "=f"(d[24]), "=f"(d[25]), "=f"(d[26]), "=f"(d[27]), "=f"(d[28]), "=f"(d[29]), "=f"(d[30]), "=f"(d[31]),
          "=f"(d[32]), "=f"(d[33]), "=f"(d[34]), "=f"(d[35]), "=f"(d[36]), "=f"(d[37]), "=f"(d[38]), "=f"(d[39]),
          "=f"(d[40]), "=f"(d[41]), "=f"(d[42]), "=f"(d[43]), "=f"(d[44]), "=f"(d[45]), "=f"(d[46]), "=f"(d[47]),
          "=f"(d[48]), "=f"(d[49]), "=f"(d[50]), "=f"(d[51]), "=f"(d[52]), "=f"(d[53]), "=f"(d[54]), "=f"(d[55]),
          "=f"(d[56]), "=f"(d[57]), "=f"(d[58]), "=f"(d[59]), "=f"(d[60]), "=f"(d[61]), "=f"(d[62]), "=f"(d[63]),
          "=f"(d[64]), "=f"(d[65]), "=f"(d[66]), "=f"(d[67]), "=f"(d[68]), "=f"(d[69]), "=f"(d[70]), "=f"(d[71]),
          "=f"(d[72]), "=f"(d[73]), "=f"(d[74]), "=f"(d[75]), "=f"(d[76]), "=f"(d[77]), "=f"(d[78]), "=f"(d[79]),
          "=f"(d[80]), "=f"(d[81]), "=f"(d[82]), "=f"(d[83]), "=f"(d[84]), "=f"(d[85]), "=f"(d[86]), "=f"(d[87]),
          "=f"(d[88]), "=f"(d[89]), "=f"(d[90]), "=f"(d[91]), "=f"(d[92]), "=f"(d[93]), "=f"(d[94]), "=f"(d[95]),
          "=f"(d[96]), "=f"(d[97]), "=f"(d[98]), "=f"(d[99]), "=f"(d[100]), "=f"(d[101]), "=f"(d[102]), "=f"(d[103]),
          "=f"(d[104]), "=f"(d[105]), "=f"(d[106]), "=f"(d[107]), "=f"(d[108]), "=f"(d[109]), "=f"(d[110]), "=f"(d[111]),
          "=f"(d[112]), "=f"(d[113]), "=f"(d[114]), "=f"(d[115]), "=f"(d[116]), "=f"(d[117]), "=f"(d[118]), "=f"(d[119]),
          "=f"(d[120]), "=f"(d[121]), "=f"(d[122]), "=f"(d[123]), "=f"(d[124]), "=f"(d[125]), "=f"(d[126]), "=f"(d[127])
        : "l"(da), "l"(db));
}
__device__ __forceinline__ void wgmma_n256(float (&d)[128], uint64_t da, uint64_t db) {
    asm volatile("{\n.reg .pred p;\nsetp.eq.b32 p, 0, 0;\n"
        "wgmma.mma_async.sync.aligned.m64n256k16.f32.bf16.bf16 {"
        "%0, %1, %2, %3, %4, %5, %6, %7, %8, %9, %10, %11, %12, %13, %14, %15, "
        "%16, %17, %18, %19, %20, %21, %22, %23, %24, %25, %26, %27, %28, %29, %30, %31, "
        "%32, %33, %34, %35, %36, %37, %38, %39, %40, %41, %42, %43, %44, %45, %46, %47, "
        "%48, %49, %50, %51, %52, %53, %54, %55, %56, %57, %58, %59, %60, %61, %62, %63, "
        "%64, %65, %66, %67, %68, %69, %70, %71, %72, %73, %74, %75, %76, %77, %78, %79, "
        "%80, %81, %82, %83, %84, %85, %86, %87, %88, %89, %90, %91, %92, %93, %94, %95, "
        "%96, %97, %98, %99, %100, %101, %102, %103, %104, %105, %106, %107, %108, %109, %110, %111, "
        "%112, %113, %114, %115, %116, %117, %118, %119, %120, %121, %122, %123, %124, %125, %126, %127"
        "}, %128, %129, p, 1, 1, 0, 1;\n}\n"
        : "+f"(d[0]), "+f"(d[1]), "+f"(d[2]), "+f"(d[3]), "+f"(d[4]), "+f"(d[5]), "+f"(d[6]), "+f"(d[7]),
          "+f"(d[8]), "+f"(d[9]), "+f"(d[10]), "+f"(d[11]), "+f"(d[12]), "+f"(d[13]), "+f"(d[14]), "+f"(d[15]),
          "+f"(d[16]), "+f"(d[17]), "+f"(d[18]), "+f"(d[19]), "+f"(d[20]), "+f"(d[21]), "+f"(d[22]), "+f"(d[23]),
          "+f"(d[24]), "+f"(d[25]), "+f"(d[26]), "+f"(d[27]), "+f"(d[28]), "+f"(d[29]), "+f"(d[30]), "+f"(d[31]),
          "+f"(d[32]), "+f"(d[33]), "+f"(d[34]), "+f"(d[35]), "+f"(d[36]), "+f"(d[37]), "+f"(d[38]), "+f"(d[39]),
          "+f"(d[40]), "+f"(d[41]), "+f"(d[42]), "+f"(d[43]), "+f"(d[44]), "+f"(d[45]), "+f"(d[46]), "+f"(d[47]),
          "+f"(d[48]), "+f"(d[49]), "+f"(d[50]), "+f"(d[51]), "+f"(d[52]), "+f"(d[53]), "+f"(d[54]), "+f"(d[55]),
          "+f"(d[56]), "+f"(d[57]), "+f"(d[58]), "+f"(d[59]), "+f"(d[60]), "+f"(d[61]), "+f"(d[62]), "+f"(d[63]),
          "+f"(d[64]), "+f"(d[65]), "+f"(d[66]), "+f"(d[67]), "+f"(d[68]), "+f"(d[69]), "+f"(d[70]), "+f"(d[71]),
          "+f"(d[72]), "+f"(d[73]), "+f"(d[74]), "+f"(d[75]), "+f"(d[76]), "+f"(d[77]), "+f"(d[78]), "+f"(d[79]),
          "+f"(d[80]), "+f"(d[81]), "+f"(d[82]), "+f"(d[83]), "+f"(d[84]), "+f"(d[85]), "+f"(d[86]), "+f"(d[87]),
          "+f"(d[88]), "+f"(d[89]), "+f"(d[90]), "+f"(d[91]), "+f"(d[92]), "+f"(d[93]), "+f"(d[94]), "+f"(d[95]),
          "+f"(d[96]), "+f"(d[97]), "+f"(d[98]), "+f"(d[99]), "+f"(d[100]), "+f"(d[101]), "+f"(d[102]), "+f"(d[103]),
          "+f"(d[104]), "+f"(d[105]), "+f"(d[106]), "+f"(d[107]), "+f"(d[108]), "+f"(d[109]), "+f"(d[110]), "+f"(d[111]),
          "+f"(d[112]), "+f"(d[113]), "+f"(d[114]), "+f"(d[115]), "+f"(d[116]), "+f"(d[117]), "+f"(d[118]), "+f"(d[119]),
          "+f"(d[120]), "+f"(d[121]), "+f"(d[122]), "+f"(d[123]), "+f"(d[124]), "+f"(d[125]), "+f"(d[126]), "+f"(d[127])
        : "l"(da), "l"(db));
}

struct Idx {
    uint32_t lane, warp, w4, q4, g8, prow, pan;
    __device__ __forceinline__ Idx() {
        uint32_t t; asm volatile("mov.u32 %0, %%tid.x;" : "=r"(t));
        lane = t & 31; warp = t >> 5; w4 = warp & 3; q4 = lane & 3; g8 = lane >> 2;
        prow = w4 * 16 + ((lane >> 3) & 1) * 8 + (lane & 7);
        pan = prow * 128 + (((lane >> 4) ^ (lane & 7)) << 4);
    }
};
#define IDX() const Idx ix; const uint32_t lane = ix.lane, warp = ix.warp, w4 = ix.w4, q4 = ix.q4, g8 = ix.g8, prow = ix.prow, pan_addr = ix.pan; \
    (void)lane; (void)warp; (void)w4; (void)q4; (void)g8; (void)prow; (void)pan_addr;

__device__ __forceinline__ int kof(int t, int sh, int j) {
    const int q = (t >> sh) - 1;
    return ((q < 0 ? j : q + (q >= j)) << 7) + ((t & ((1 << sh) - 1)) << (7 - sh));
}
__device__ __forceinline__ int kdown(int g) {
    return g < 24 ? (g / 3 * 4 + g) * 64 : (((g - 24) & 15) / 2 * 7 + 3 + ((g - 24) >> 4) * 2 + (g & 1)) * 64;
}
#define SCHED_FENCE(k) do { if ((FENCES >> (k)) & 1) asm volatile("{\n.reg .pred p;\nsetp.ne.u32 p, %0, %1;\n@p bra.uni S_SKIP;\ntrap;\nS_SKIP:\n}" :: "r"(sb), "n"(0xffffff00u + (k))); } while (0)

struct Ring {
    uint32_t slot, par;
    __device__ __forceinline__ void next() { if (++slot == NSLOT) { slot = 0; par ^= 1; } }
    __device__ __forceinline__ void skip(uint32_t n) { slot += n; if (slot >= NSLOT) { slot -= NSLOT; par ^= 1; } }
};
__device__ __forceinline__ uint32_t BAR_FULL(uint32_t sb, uint32_t s) { return sb + OFF_BAR + 8 * s; }
constexpr uint32_t AF_REL = 48;
__device__ __forceinline__ uint32_t BAR_EMPTY(uint32_t sb, uint32_t s) { return sb + OFF_BAR + 96 + 8 * s; }
__device__ __forceinline__ uint32_t BAR_SFULL(uint32_t sb, uint32_t i) { return sb + OFF_BAR + 152 + 8 * i; }
__device__ __forceinline__ uint32_t BAR_SREADY(uint32_t sb, uint32_t i) { return sb + OFF_BAR + 184 + 8 * i; }
__device__ __forceinline__ uint32_t BAR_ONE(uint32_t sb, uint32_t i) { return sb + OFF_BAR + 216 + 8 * i; }
enum { EV_WIN, EV_WIN1, EV_WIN2, EV_WIN3, EV_P0, EV_GA, EV_GB, EV_LN2, EV_LAG0, EV_LAG1, EV_LAG2, EV_LAG3, EV_LAG4, EV_LAG5, EV_OWN, EV_OWN1, EV_P3, EV_P31, EV_KV, EV_GO, EV_PAR, EV_AGO, EV_AGO1, EV_AGO2, EV_H0, EV_H1, EV_H2, EV_X1, EV_X11, EV_X1S, EV_X1S1, EV_COUNT };
constexpr int NB_TAIL = 4;

struct Rel {
    uint32_t base; bool sig;
    __device__ __forceinline__ Rel(uint32_t sb, uint32_t tw) {
        uint32_t a; asm("mapa.shared::cluster.u32 %0, %1, %2;" : "=r"(a) : "r"(BAR_EMPTY(sb, 0)), "r"((tw >> 5) & 1));
        base = __shfl_sync(0xffffffffu, a, 0); sig = (tw & ~32u) == 0;
    }
    __device__ __forceinline__ void operator()(uint32_t slot) const {
        if (sig) asm volatile("mbarrier.arrive.shared::cluster.b64 _, [%0];" :: "r"(base + 8 * slot) : "memory");
    }
};
struct LnRow { float rs0, nm0, rs1, nm1; };
struct Pipe {
    Rel rel; uint32_t p1, p2;
    __device__ __forceinline__ Pipe(uint32_t sb, uint32_t tw, uint32_t first) : rel(sb, tw), p1(first), p2(NSLOT) {}
    template <bool TWO> __device__ __forceinline__ void acquire(uint32_t sb, uint32_t wg, const Ring& r) {
        const uint32_t b0 = BAR_FULL(sb, r.slot), b1 = b0 + (wg ? 0 : AF_REL);
        const bool ready = TWO ? mbar_test2(b0, b1, r.par) : mbar_test(b0, r.par);
        wg_wait<1>();
        rel(p2);
        if (!ready) { if (TWO) mbar_wait2(b0, b1, r.par); else mbar_wait(b0, r.par); }
    }
    __device__ __forceinline__ void issued(uint32_t slot) { p2 = p1; p1 = slot; }
    __device__ __forceinline__ void drain1() { wg_wait<1>(); rel(p2); p2 = NSLOT; }
    __device__ __forceinline__ void drain0() { wg_wait<0>(); rel(p1); p1 = NSLOT; }
    template <bool TWO, int LG, int PRE, class Step> __device__ __forceinline__ void hold(uint32_t sb, Ring& r, uint32_t lag_bar, Step step) {
        drain1(); drain0();
        Ring q = r;
        auto landed = [&] { if (TWO) mbar_wait2(BAR_FULL(sb, q.slot), BAR_FULL(sb, q.slot) + AF_REL, q.par); else mbar_wait(BAR_FULL(sb, q.slot), q.par); q.next(); };
#pragma unroll 1
        for (int i = 0; i < PRE; ++i) landed();
        mbar_wait(lag_bar, 0);
#pragma unroll 1
        for (int i = 0; i < LG; ++i) {
            if (PRE < LG && i >= PRE) landed();
            step(r.slot);
            wg_wait<2>(); rel(p2); p2 = p1; p1 = r.slot;
            if (++r.slot == NSLOT) r.slot = 0;
        }
        r.par = q.par;
    }
};
template <bool WITH128, bool FIRST>
__device__ __forceinline__ void step32(float (&a256)[128], float (&a128)[64], uint32_t sb, uint32_t wg, uint32_t slot, int own) {
    const uint32_t st = d16(sb) + slot * (SLOT >> 4);
    const uint32_t alo = own >= 0 ? d16(sb) + OFF_STG / 16 + wg * 1024 + (own >> 1) * 512 + (own & 1) * 4 : st + wg * 256;
    const uint32_t ahi = own >= 0 ? (1024 >> 4) | (1u << 30) : (512 >> 4) | (2u << 30);
    wg_fence();
#pragma unroll
    for (int k = 0; k < 2; ++k) {
        const uint64_t da = ((uint64_t)ahi << 32) | (alo + k * 2 + 0x10000);
        const uint64_t d0 = mk_desc(st, 8192 + k * 2048, 4096, 1024, 1), d1 = mk_desc(st, 24576 + k * 2048, 4096, 1024, 1);
        if (FIRST && k == 0) { wgmma_n256_z(a256, da, d0); if (WITH128) wgmma_n128_z(a128, da, d1); }
        else { wgmma_n256(a256, da, d0); if (WITH128) wgmma_n128(a128, da, d1); }
    }
    wg_commit();
}
template <bool WITH128, int LG, class Tail>
__device__ __forceinline__ void mainloop32(float (&a256)[128], float (&a128)[64], uint32_t sb, uint32_t wg, uint32_t tw, Ring& r, uint32_t lag_ev, int g0, Tail tail) {
    mbar_wait(BAR_FULL(sb, r.slot), r.par);
    step32<WITH128, true>(a256, a128, sb, wg, r.slot, WITH128 ? 0 : -1);
    TS(g0, 0);
    Pipe pp(sb, tw, r.slot);
    r.next();
    const int end = wg ? 32 : 32 - LG;
#pragma unroll 1
    for (int it = 1; it < end; ++it) {
        pp.acquire<WITH128>(sb, wg, r);
        step32<WITH128, false>(a256, a128, sb, wg, r.slot, WITH128 && it < 4 ? it : -1);
        pp.issued(r.slot);
        TS(g0 + it, 0);
        r.next();
    }
    if (wg == 0) pp.hold<WITH128, LG, LG>(sb, r, BAR_ONE(sb, lag_ev), [&](uint32_t slot) { step32<WITH128, false>(a256, a128, sb, 0, slot, -1); });
    if (LAGSIG == 2 && wg == 1 && tw == 0) mbar_arrive(BAR_ONE(sb, lag_ev));
    pp.drain1();
    if (LAGSIG == 1 && wg == 1 && tw == 0) mbar_arrive(BAR_ONE(sb, lag_ev));
    tail();
    pp.drain0();
    TS(g0 + 31, 1);
}
template <bool FIRST>
__device__ __forceinline__ void step64(float (&acc)[64], uint32_t sb, uint32_t wg, uint32_t slot, int own) {
    const uint32_t sbb = d16(sb) + slot * (SLOT >> 4), sa = own >= 0 ? d16(sb) + OFF_STG / 16 + wg * 1024 + own * 512 : sbb + wg * 512;
    wg_fence();
#pragma unroll
    for (int k = 0; k < 4; ++k) {
        const uint64_t da = mk_desc(sa, k * 32, 16, 1024, 1), db = mk_desc(sbb, 16384 + k * 2048, 8192, 1024, 1);
        if (FIRST && k == 0) wgmma_n128_z(acc, da, db); else wgmma_n128(acc, da, db);
    }
    wg_commit();
}
template <bool OWN, int NST, int LG, int MID, class Mid>
__device__ __forceinline__ void mainloop64(float (&acc)[64], uint32_t sb, uint32_t wg, uint32_t tw, Ring& r, Mid mid) {
    constexpr int G0 = OWN ? 32 : 144, SG = OWN ? SIGW : SIGD; (void)G0;
    const uint32_t lag_bar = BAR_ONE(sb, OWN ? EV_LAG4 : EV_LAG5);
    mbar_wait(BAR_FULL(sb, r.slot), r.par);
    step64<true>(acc, sb, wg, r.slot, OWN ? 0 : -1);
    TS(G0, 0);
    Pipe pp(sb, tw, r.slot);
    r.next();
    if (OWN) {
        mbar_wait(BAR_FULL(sb, r.slot), r.par);
        step64<false>(acc, sb, wg, r.slot, 1);
        TS(G0 + 1, 0);
        pp.drain0();
        TS(G0 + 1, 1);
        pp.rel(r.slot);
        if (tw == 0) mbar_arrive(BAR_ONE(sb, EV_OWN + wg));
        r.next();
    }
    int it = OWN ? 2 : 1;
    auto run = [&](int end) {
#pragma unroll 1
        do {
            if (SG > 2 && it == NST + 2 - SG && tw == 0) mbar_arrive(lag_bar);
            pp.acquire<OWN>(sb, wg, r);
            step64<false>(acc, sb, wg, r.slot, -1);
            pp.issued(r.slot);
            TS(G0 + it, 0);
            r.next();
        } while (++it < end);
    };
    run(wg ? MID : NST - LG);
    mid();
    if (wg) run(NST);
    else pp.hold<OWN, LG, (SG > 2 ? 2 : LG)>(sb, r, lag_bar, [&](uint32_t slot) { step64<false>(acc, sb, 0, slot, -1); });
    if (SG == 2 && wg == 1 && tw == 0) mbar_arrive(lag_bar);
    pp.drain1();
    if (SG == 1 && wg == 1 && tw == 0) mbar_arrive(lag_bar);
    pp.drain0();
    TS(G0 + NST - 1, 1);
}

struct RowAcc {
    float sm[4] = {0.f, 0.f, 0.f, 0.f}, sq[4] = {0.f, 0.f, 0.f, 0.f};
    __device__ __forceinline__ void add(int e, float x) { sm[e & 3] += x; sq[e & 3] = fmaf(x, x, sq[e & 3]); }
    __device__ __forceinline__ void publish(uint4* dst, uint32_t q4, uint32_t ep) const {
        const float s0 = sm[0] + sm[1], s1 = sm[2] + sm[3], q0 = sq[0] + sq[1], q1 = sq[2] + sq[3];
        const bool od = q4 & 1;
        float sv = (od ? s1 : s0) + __shfl_xor_sync(0xffffffffu, od ? s0 : s1, 1), qv = (od ? q1 : q0) + __shfl_xor_sync(0xffffffffu, od ? q0 : q1, 1);
        sv += __shfl_xor_sync(0xffffffffu, sv, 2); qv += __shfl_xor_sync(0xffffffffu, qv, 2);
        if (q4 < 2) st_pkt16(dst + q4 * 8, 0, __float_as_uint(sv), __float_as_uint(qv), ep);
    }
};
__device__ __forceinline__ LnRow merge_stats(const uint4* src, uint32_t stride, uint32_t q4, uint32_t ep, uint32_t sb, uint32_t sig) {
    uint4 t[4];
    uint32_t n = 0;
    while (true) {
#pragma unroll
        for (int i = 0; i < 4; ++i) t[i] = ld_pkt16(src + (q4 * 2 + (i >> 1)) * stride + (i & 1) * 8);
        if (sig) { mbar_arrive(sig); sig = 0; }
        const bool ok_ = __all_sync(0xffffffffu, t[0].w == ep && t[1].w == ep && t[2].w == ep && t[3].w == ep);
        if (stride == 512 && n < 4) CS(14 + n);
        if (ok_) break;
        SPIN_GUARD(n);
    }
    float v[4];
#pragma unroll
    for (int h = 0; h < 2; ++h) { v[h] = __uint_as_float(t[h].y) + __uint_as_float(t[2 + h].y); v[2 + h] = __uint_as_float(t[h].z) + __uint_as_float(t[2 + h].z); }
#pragma unroll
    for (int o = 1; o < 4; o <<= 1)
#pragma unroll
        for (int i = 0; i < 4; ++i) v[i] += __shfl_xor_sync(0xffffffffu, v[i], o);
    const float m0 = v[0] * (1.f / D_), m1 = v[1] * (1.f / D_);
    const float r0 = rsqrtf(fmaxf(fmaf(-m0, m0, v[2] * (1.f / D_)), 0.f) + 1e-5f), r1 = rsqrtf(fmaxf(fmaf(-m1, m1, v[3] * (1.f / D_)), 0.f) + 1e-5f);
    return LnRow{r0, -m0 * r0, r1, -m1 * r1};
}
struct Stg {
    uint32_t b, par;
    __device__ __forceinline__ uint32_t acquire2(uint32_t sb, uint32_t wg) {
        mbar_wait(BAR_SREADY(sb, wg * 2), par & 1);
        mbar_wait(BAR_SREADY(sb, wg * 2 + 1), (par >> 1) & 1);
        par ^= 3;
        return sb + OFF_STG + wg * 16384;
    }
    __device__ __forceinline__ void publish(uint32_t sb, uint32_t wg, uint32_t lane) {
        fence_async_smem();
        __syncwarp();
        if (lane == 0) mbar_arrive(BAR_SFULL(sb, wg * 2 + b));
        b ^= 1;
    }
};

struct LnPar {
    uint4 p[8];
    __device__ __forceinline__ void load(uint32_t sb, uint32_t q4) {
#pragma unroll
        for (int i = 0; i < 8; ++i) p[i] = lds128(sb + OFF_PAR + i * 64 + q4 * 16);
    }
};
__device__ __forceinline__ void ln_norm(uint32_t (&xn)[32], const float (&x)[64], const LnRow& n) {
#pragma unroll
    for (int e = 0; e < 32; ++e) {
        const float rs = (e & 1) ? n.rs1 : n.rs0, nm = (e & 1) ? n.nm1 : n.nm0;
        xn[e] = pack2(fmaf(x[2 * e], rs, nm), fmaf(x[2 * e + 1], rs, nm));
    }
}
__device__ __forceinline__ void ln_emit(const uint32_t (&xr)[32], const LnPar& lp, uint32_t sb, uint32_t wg, const Idx& ix) {
#pragma unroll
    for (int i = 0; i < 8; ++i)
        stsm4(sb + OFF_STG + wg * 16384 + (i >> 2) * 8192 + (ix.pan ^ ((i & 3) << 5)), hfma2_bf16(xr[4 * i], lp.p[i].z, lp.p[i].x), hfma2_bf16(xr[4 * i + 1], lp.p[i].z, lp.p[i].x),
              hfma2_bf16(xr[4 * i + 2], lp.p[i].w, lp.p[i].y), hfma2_bf16(xr[4 * i + 3], lp.p[i].w, lp.p[i].y));
    fence_async_smem();
    __syncwarp();
    if (ix.lane < 2) mbar_arrive(BAR_SFULL(sb, wg * 2 + ix.lane));
    bar_sync(1 + wg, 128);
}
__device__ __forceinline__ void load_res(float (&xf)[64], float (&gf)[32], uint32_t buf, uint32_t tab) {
    IDX();
    uint32_t xr[32], gt[16];
#pragma unroll
    for (int i = 0; i < 8; ++i) ldsm4(buf + (i >> 2) * 8192 + (pan_addr ^ ((i & 3) << 5)), xr[4 * i], xr[4 * i + 1], xr[4 * i + 2], xr[4 * i + 3]);
#pragma unroll
    for (int cg = 0; cg < 16; ++cg) gt[cg] = lds32(tab + cg * 16 + q4 * 4);
#pragma unroll
    for (int i = 0; i < 32; ++i) unpack2(xr[i], xf[2 * i], xf[2 * i + 1]);
#pragma unroll
    for (int i = 0; i < 16; ++i) unpack2(gt[i], gf[2 * i], gf[2 * i + 1]);
}
__device__ __forceinline__ void fetch_halo(uint4* src, bool first, uint32_t sb, uint32_t W, uint32_t lane) {
    mbar_wait(BAR_ONE(sb, EV_KV), 0);
    mbar_wait2(BAR_SREADY(sb, 0), BAR_SREADY(sb, 1), 1);
    uint4 hv[8];
    uint32_t n = 0;
    while (true) {
        bool ok = true;
#pragma unroll
        for (int i = 0; i < 8; ++i) { hv[i] = first ? make_uint4(0, 0, 0, 0) : ld_pkt16(src + i * 32); ok = ok && hv[i].x != 0; }
        if (first || __all_sync(0xffffffffu, ok)) break;
        SPIN_GUARD(n);
    }
#pragma unroll
    for (int i = 0; i < 8; ++i) stsm4(sb + OFF_STG + W * 2048 + (i >> 2) * 8192 + (i & 3) * 512 + lane * 16, hv[i].x, hv[i].y, hv[i].z, hv[i].w);
    bar_arrive(NB_TAIL + W, 64);
    if (!first) {
#pragma unroll
        for (int i = 0; i < 8; ++i) src[i * 32] = make_uint4(0, 0, 0, 0);
    }
}

template <int OFF, int LEN>
__device__ __forceinline__ void glu_panel(const float (&a)[LEN], uint32_t buf, uint32_t bar) {
    IDX();
    uint32_t r[16];
#pragma unroll
    for (int i = 0; i < 16; ++i) r[i] = pack2(glu_half(a[OFF + 2 * i], a[OFF + 2 * i + 32]), glu_half(a[OFF + 2 * i + 1], a[OFF + 2 * i + 33]));
#pragma unroll
    for (int jn = 0; jn < 8; jn += 2) stsm4(buf + (pan_addr ^ (jn << 4)), r[jn * 2], r[jn * 2 + 1], r[jn * 2 + 2], r[jn * 2 + 3]);
    fence_async_smem();
    __syncwarp();
    if (lane == 0) mbar_arrive(bar);
}

__global__ void __launch_bounds__(384, 1)
fused_block_kernel(const __grid_constant__ Ptrs pt, const __grid_constant__ Maps mp) {
    uint32_t* const g_flags = pt.mail->flags;
    uint2* const g_mod = pt.mail->mod;
    uint4* const g_st1 = pt.mail->st1;
    uint32_t* const g_par2 = pt.mail->par2;
    uint4* const g_halo = pt.mail->halo;
    const __nv_bfloat16* __restrict__ cvec = pt.c;
    if (threadIdx.x == 224) { prefetch_map(&mp.wm8); prefetch_map(&mp.x); }
    extern __shared__ __align__(1024) uint8_t smem[];
    const uint32_t sb = smem_u32(smem);
    const uint32_t tid = threadIdx.x, tw = tid & 127, lane = tid & 31;
    const uint32_t warp = __shfl_sync(0xffffffffu, tid >> 5, 0), wg = warp >> 2;
    uint32_t rank; asm("mov.u32 %0, %%cluster_ctarank;" : "=r"(rank));
    rank = __shfl_sync(0xffffffffu, rank, 0);
    uint32_t ep;
    uint32_t smid; asm volatile("mov.u32 %0, %%smid;" : "=r"(smid));
    const int c = __shfl_sync(0xffffffffu, smid >> 1, 0);
    const int c7 = ((c - 32) * 37) >> 8;
    const int grp = c < 32 ? c & 7 : c < 60 ? c - 31 - 7 * c7 : c < 62 ? -1 : 0;
    const int j = c < 32 ? c >> 3 : c < 60 ? 4 + c7 : c < 62 ? (c - 60) * 2 + rank : c - 58;
    const bool aux = grp < 0;
    const int m = grp * 2 + rank;
    uint4* const g_st2 = g_halo + (m > 0 ? (m - 1) * 8 * 512 : 128);

    bool cluster_arrive_early = false;
    if (wg < 2) {
      ep = flag_get(g_flags + FL_DONE);
      uint16_t cw[8];
      {
          const __nv_bfloat16* cp = cvec + ((tw >> 5) * 32 + (tw & 3) * 2) * 8 + (lane >> 2);
#pragma unroll
          for (int i = 0; i < 8; ++i) asm volatile("ld.global.nc.u16 %0, [%1];" : "=h"(cw[i]) : "l"(cp + (i >> 1) * 64 + (i & 1) * 8));
      }
      asm volatile("setmaxnreg.inc.sync.aligned.u32 224;");
      if (tid == 0) TL(58);
      cluster_arrive();
      if (aux) {
        if (wg == 0) {
            const uint4 cv = *(const uint4*)(cvec + tw * 8);
            sts128(sb + OFF_STG + (tw >> 3) * 1024 + (tw & 7) * 16, pack2(silu_(bf_lo(cv.x)), silu_(bf_hi(cv.x))), pack2(silu_(bf_lo(cv.y)), silu_(bf_hi(cv.y))),
                   pack2(silu_(bf_lo(cv.z)), silu_(bf_hi(cv.z))), pack2(silu_(bf_lo(cv.w)), silu_(bf_hi(cv.w))));
            fence_async_smem();
        }
        cluster_wait();
        ep = __shfl_sync(0xffffffffu, ep, 0) / NCTA + 1;
        if (wg == 0) {
            if (tw == 0) {
                uint32_t n = 0;
                while (ld_pkt16(pt.mail->mod1 + 256).z != ep) { SPIN_GUARD(n); __nanosleep(200); }
                if (GODLY) __nanosleep(GODLY);
                mbar_arrive(BAR_ONE(sb, EV_GO));
            }
            bar_sync(1, 128);
            Ring r{0, 0};
#pragma unroll 1
            for (int p = 0; p < 4; ++p) {
                float acc[128];
#pragma unroll
                for (int i = 0; i < 128; ++i) acc[i] = 0.f;
                uint32_t prev = 0;
#pragma unroll 1
                for (int kc = 0; kc < 16; ++kc) {
                    mbar_wait(BAR_FULL(sb, r.slot), r.par);
                    wg_fence();
#pragma unroll
                    for (int k = 0; k < 4; ++k)
                        wgmma_n256(acc, mk_desc(d16(sb) + kc * 64, OFF_STG + k * 32, 16, 0, 1), mk_desc(d16(sb) + r.slot * (SLOT >> 4), k * 2048, 8192, 1024, 1));
                    wg_commit();
                    wg_wait<1>();
                    if (kc > 0 && tw == 0) mbar_arrive(BAR_EMPTY(sb, prev));
                    prev = r.slot;
                    r.next();
                }
                wg_wait<0>();
                if (tw == 0) mbar_arrive(BAR_EMPTY(sb, prev));
                if (tw < 4) {
#pragma unroll
                    for (int jn = 0; jn < 32; ++jn) sts32(sb + OFF_TAB + (jn * 4 + tw) * 4, pack2(acc[jn * 4], acc[jn * 4 + 1]));
                }
                bar_sync(1, 128);
                const int vec = 2 + p, blk = p * 4 + j;
                const uint32_t val = lds32(sb + OFF_TAB + tw * 4);
                if (vec == 2 || vec == 5) st_pkt(g_mod + (8 + blk) * 128 + tw, val, ep);
                else {
                    const float one = vec == 4 ? 1.f : 0.f;
                    g_par2[((blk & 3) * 16 + (tw >> 3)) * 16 + (tw & 3) * 4 + (vec - 3) * 2 + ((tw >> 2) & 1)] =
                        pack2(0.5f * bf_round(one + bf_lo(val)), 0.5f * bf_round(one + bf_hi(val)));
                }
                bar_sync(1, 128);
                if (tw == 0) {
                    if (vec == 3 || vec == 4) asm volatile("red.release.gpu.global.add.u32 [%0], 1;" :: "l"(&g_flags[FL_LN2]) : "memory");
                    TL(1 + p);
                }
            }
        }
      } else {
        Ring r{0, 0};
        Stg stg{0, 0};
        {
            IDX();
            uint32_t sa[4];
            uint4* const st1 = g_st1 + m * 128 + wg * 64 + w4 * 16 + g8;
            uint4* const mod_out = pt.mail->mod1 + g8 * 512 + (m * 8 + j) * 4 + q4;
            if (RESET && q4 < 2) st_pkt16(st1 + j * S_ + q4 * 8, 0, 0, 0, 0);
            if (wg == 0) {
                if (w4 == 0) st_pkt16(mod_out, 0, 0, 0, 0);
#pragma unroll
                for (int i = 0; i < 4; ++i) sa[i] = pack2(silu_(bf_lo(cw[2 * i])), silu_(bf_lo(cw[2 * i + 1])));
            }
            cluster_wait();
            ep = __shfl_sync(0xffffffffu, ep, 0) / NCTA + 1;
            uint32_t xr[32];
            float xf[64];
            const uint32_t buf0 = stg.acquire2(sb, wg);
            if (tid == 0) TL(24);
            if (tid == 128) TL(27);
            RowAcc ra;
#pragma unroll
            for (int i = 0; i < 8; ++i) ldsm4(buf0 + (i >> 2) * 8192 + (pan_addr ^ ((i & 3) << 5)), xr[4 * i], xr[4 * i + 1], xr[4 * i + 2], xr[4 * i + 3]);
#pragma unroll
            for (int e = 0; e < 32; ++e) { unpack2(xr[e], xf[2 * e], xf[2 * e + 1]); ra.add(2 * e, xf[2 * e]); ra.add(2 * e + 1, xf[2 * e + 1]); }
            ra.publish(st1 + j * S_, q4, ep);
            if (tid == 0) TL(26);
            if (wg == 0) {
                uint32_t af[8][4];
#pragma unroll
                for (int i = 0; i < 8; ++i)
#pragma unroll
                    for (int e = 0; e < 4; ++e) af[i][e] = __shfl_sync(0xffffffffu, sa[e], i * 4 + q4);
                float c[4][4] = {};
#pragma unroll
                for (int i = 0; i < 8; ++i) {
                    if (!(i & 1)) mbar_wait(BAR_ONE(sb, EV_WIN + (i >> 1)), 0);
                    if (i == 6 && tid == 0) TL(25);
#pragma unroll
                    for (int h = 0; h < 2; ++h) {
                        uint32_t b0, b1, b2, b3;
                        ldsm4t(sb + 5 * SLOT + i * 4096 + w4 * 1024 + h * 512 + (lane & 15) * 32 + (lane >> 4) * 16, b0, b1, b2, b3);
                        mma16816(c[2 * h], af[i][2 * h], 0u, af[i][2 * h + 1], 0u, b0, b1);
                        mma16816(c[2 * h + 1], af[i][2 * h], 0u, af[i][2 * h + 1], 0u, b2, b3);
                    }
                }
                if (lane < 4) sts128(sb + OFF_TAB + w4 * 64 + lane * 16, __float_as_uint(c[0][0] + c[2][0]), __float_as_uint(c[0][1] + c[2][1]),
                                     __float_as_uint(c[1][0] + c[3][0]), __float_as_uint(c[1][1] + c[3][1]));
                if (lane < 2) mbar_arrive_cta(BAR_ONE(sb, EV_P0), lane);
                bar_sync(1, 128);
                if (w4 == 0) {
                    float a[4] = {0.f, 0.f, 0.f, 0.f};
#pragma unroll
                    for (int i = 0; i < 4; ++i) {
                        const uint4 t = lds128(sb + OFF_TAB + i * 64 + q4 * 16);
                        a[0] += __uint_as_float(t.x); a[1] += __uint_as_float(t.y); a[2] += __uint_as_float(t.z); a[3] += __uint_as_float(t.w);
                    }
                    const float add = m >= 8 ? 1.f : 0.f;
                    st_pkt16(mod_out, pack2(bf_round(a[0]) + add, bf_round(a[1]) + add), pack2(bf_round(a[2]) + add, bf_round(a[3]) + add), ep, 0);
                    if (tid == 0) TL(3);
                }
            } else if (LWAIT >= 0) mbar_wait(BAR_ONE(sb, EV_WIN + LWAIT), 0);
            const LnRow n1 = merge_stats(st1, S_, q4, ep, sb, 0);
            if (tid == 0) TL(48);
            if (tid == 128) TL(28);
            ln_norm(xr, xf, n1);
            mbar_wait(BAR_ONE(sb, EV_PAR), 0);
            LnPar lp; lp.load(sb, q4);
            ln_emit(xr, lp, sb, wg, ix);
            if (tid == 0) { TL(8); TC(103); }
            if (tid == 128) TL(22);
        }
        {
            float kv[128], qa[64];
            mainloop32<true, LAGQ>(kv, qa, sb, wg, tw, r, EV_LAG0, 0, [&] { stg.acquire2(sb, wg); mbar_wait2(BAR_SREADY(sb, 2), BAR_SREADY(sb, 3), 1); });
            if (tid == 0) { TL(4); TC(104); }
            if (tid == 128) TL(50);
            CS(1);
            IDX();
            uint32_t k1[16], k2[16], v1[16], v2[16], qf[32];
#pragma unroll
            for (int i = 0; i < 8; ++i) qf[i] = pack2(qa[2 * i], qa[2 * i + 1]);
#pragma unroll
            for (int t = 0; t < 16; ++t) k2[t] = pack2(kv[4 * t + 2], kv[4 * t + 3]);
#pragma unroll
            for (int t = 0; t < 16; ++t) v2[t] = pack2(kv[64 + 4 * t + 2], kv[64 + 4 * t + 3]);
            const uint32_t nxt = warp + ((warp & 1) ? 3 : 1);
            if (nxt < 8) {
                const uint32_t dst = sb + OFF_STG + (nxt >> 2) * 16384 + (nxt & 3) * 2048 + lane * 16;
#pragma unroll
                for (int h = 0; h < 4; ++h) stsm4(dst + h * 512, k2[4 * h], k2[4 * h + 1], k2[4 * h + 2], k2[4 * h + 3]);
#pragma unroll
                for (int h = 0; h < 4; ++h) stsm4(dst + 8192 + h * 512, v2[4 * h], v2[4 * h + 1], v2[4 * h + 2], v2[4 * h + 3]);
                bar_arrive(NB_TAIL + nxt, 64);
            } else if (m < 15) {
                uint4* dst = g_halo + (m * 8 + j) * 512 + (w4 >> 1) * 256 + lane;
#pragma unroll
                for (int h = 0; h < 4; ++h) { if (!k2[4 * h]) k2[4 * h] = 0x8000u; if (!v2[4 * h]) v2[4 * h] = 0x8000u; }
#pragma unroll
                for (int h = 0; h < 4; ++h) st_pkt16(dst + h * 32, k2[4 * h], k2[4 * h + 1], k2[4 * h + 2], k2[4 * h + 3]);
#pragma unroll
                for (int h = 0; h < 4; ++h) st_pkt16(dst + 128 + h * 32, v2[4 * h], v2[4 * h + 1], v2[4 * h + 2], v2[4 * h + 3]);
            }
#pragma unroll
            for (int t = 0; t < 16; ++t) { k1[t] = pack2(kv[4 * t], kv[4 * t + 1]); v1[t] = pack2(kv[64 + 4 * t], kv[64 + 4 * t + 1]); }
#pragma unroll
            for (int i = 8; i < 32; ++i) qf[i] = pack2(qa[2 * i], qa[2 * i + 1]);
#pragma unroll
            for (int t = 0; t < 16; ++t) { v1[t] = movm(v1[t]); v2[t] = movm(v2[t]); }
            if (tid == 0) TL(33);
            CS(2);
            SCHED_FENCE(0);
            float s[4][3][4];
            auto qk = [&](float (&c)[4], int h, const uint32_t* k) {
                c[0] = c[1] = c[2] = c[3] = 0.f;
                mma16816(c, qf[h * 8], qf[h * 8 + 1], qf[h * 8 + 2], qf[h * 8 + 3], k[0], k[1]);
                mma16816(c, qf[h * 8 + 4], qf[h * 8 + 5], qf[h * 8 + 6], qf[h * 8 + 7], k[2], k[3]);
            };
#pragma unroll
            for (int h = 0; h < 4; ++h) { qk(s[h][1], h, k1 + 4 * h); qk(s[h][2], h, k2 + 4 * h); }
            CS(3);
            bar_sync(NB_TAIL + warp, 64);
            CS(4);
            if (tid == 0) TL(5);
            uint32_t k0[16], v0[16];
            const uint32_t mine = sb + OFF_STG + wg * 16384 + w4 * 2048;
#pragma unroll
            for (int h = 0; h < 4; ++h) ldsm4(mine + lane * 16 + h * 512, k0[4 * h], k0[4 * h + 1], k0[4 * h + 2], k0[4 * h + 3]);
#pragma unroll
            for (int h = 0; h < 4; ++h) ldsm4t(mine + lane * 16 + 8192 + h * 512, v0[4 * h], v0[4 * h + 1], v0[4 * h + 2], v0[4 * h + 3]);
#pragma unroll
            for (int h = 0; h < 4; ++h) qk(s[h][0], h, k0 + 4 * h);
            const bool lo0 = q4 * 2 > g8, lo1 = q4 * 2 + 1 > g8;
            const bool nopast = m == 0 && (warp & 5) == 0;
            const uint32_t lomask = (lo0 ? 0xFFFFu : 0u) | (lo1 ? 0xFFFF0000u : 0u);
            const float sl2 = 0.17677669529663687f * 1.4426950408889634f;
            float e0[8], e1[8], mx[8], sum[8], tt[8];
#pragma unroll
            for (int u = 0; u < 8; ++u) {
                const int h = u >> 1, hf = u & 1;
                e0[u] = lo0 ? ((hf == 0 && nopast) ? -INFINITY : s[h][hf][hf * 2]) : s[h][hf + 1][hf * 2];
                e1[u] = lo1 ? ((hf == 0 && nopast) ? -INFINITY : s[h][hf][hf * 2 + 1]) : s[h][hf + 1][hf * 2 + 1];
                mx[u] = fmaxf(e0[u], e1[u]);
                tt[u] = __shfl_xor_sync(0xffffffffu, mx[u], 1);
            }
            SCHED_FENCE(1);
#pragma unroll
            for (int u = 0; u < 8; ++u) { mx[u] = fmaxf(mx[u], tt[u]); tt[u] = __shfl_xor_sync(0xffffffffu, mx[u], 2); }
            SCHED_FENCE(2);
#pragma unroll
            for (int u = 0; u < 8; ++u) {
                const float c = -fmaxf(mx[u], tt[u]) * sl2;
                e0[u] = ex2(fmaf(e0[u], sl2, c)); e1[u] = ex2(fmaf(e1[u], sl2, c));
            }
            SCHED_FENCE(3);
#pragma unroll
            for (int u = 0; u < 8; ++u) { sum[u] = e0[u] + e1[u]; tt[u] = __shfl_xor_sync(0xffffffffu, sum[u], 1); }
            SCHED_FENCE(4);
#pragma unroll
            for (int u = 0; u < 8; ++u) { sum[u] += tt[u]; tt[u] = __shfl_xor_sync(0xffffffffu, sum[u], 2); }
            SCHED_FENCE(5);
#pragma unroll
            for (int u = 0; u < 8; ++u) sum[u] = rcp(sum[u] + tt[u]);
            SCHED_FENCE(6);
            CS(5);
            float o[8][2][4];
#pragma unroll
            for (int u = 0; u < 8; ++u) {
                const int h = u >> 1;
                const uint32_t p = pack2(e0[u] * sum[u], e1[u] * sum[u]);
                const uint32_t* va = ((u & 1) ? v1 : v0) + 4 * h;
                const uint32_t* vb = ((u & 1) ? v2 : v1) + 4 * h;
#pragma unroll
                for (int d = 0; d < 2; ++d) {
                    o[u][d][0] = o[u][d][1] = o[u][d][2] = o[u][d][3] = 0.f;
                    mma16816(o[u][d], va[2 * d], va[2 * d + 1], vb[2 * d], vb[2 * d + 1], p & lomask, p & ~lomask);
                }
            }
            SCHED_FENCE(7);
            const uint32_t orow = mine + (lane & 7) * 128 + (((lane >> 3) ^ (lane & 7)) << 4);
#pragma unroll
            for (int u = 0; u < 8; ++u)
                stsm4t((orow ^ (((u >> 1) & 1) << 6)) + (u >> 2) * 8192 + (u & 1) * 1024, pack2(o[u][0][0], o[u][0][1]), pack2(o[u][0][2], o[u][0][3]),
                       pack2(o[u][1][0], o[u][1][1]), pack2(o[u][1][2], o[u][1][3]));
            fence_async_smem();
            __syncwarp();
            if (lane < 2) mbar_arrive(BAR_SFULL(sb, wg * 2 + lane));
            CS(6);
            if (tid == 32) TL(41);
            bar_sync(1 + wg, 128);
            if (tid == 0) { TL(6); TC(106); }
            if (tid == 128) TL(44);
            CS(7);
        }
        {
            float acc[64], xf[64], gf[32];
            mainloop64<true, 16, LAGW, MIDW>(acc, sb, wg, tw, r, [&] {
                mbar_wait(BAR_ONE(sb, EV_GA), 0);
                load_res(xf, gf, stg.acquire2(sb, wg), sb + OFF_TAB);
            });
            if (tid == 0) { TL(7); TC(107); }
            if (tid == 128) TL(42);
            CS(10);
            IDX();
            RowAcc ra;
#pragma unroll
            for (int e = 0; e < 64; ++e) { acc[e] = fmaf(gf[(e >> 2) * 2 + (e & 1)], acc[e], xf[e]); ra.add(e, acc[e]); }
            ra.publish(g_st2 + j * 512 + wg * 64 + w4 * 16 + g8, q4, ep);
            if (tid == 0) TL(9);
            if (tid == 128) TL(34);
            CS(11);
            LnPar lp;
            {
                if (wg) mbar_wait2(BAR_EMPTY(sb, X1_SLOT), BAR_EMPTY(sb, X1_SLOT + 1), r.par ^ 1);
#pragma unroll
                for (int i = 0; i < 8; ++i)
                    stsm4(sb + (X1_SLOT + 2 - 2 * wg + (i >> 2)) * SLOT + (pan_addr ^ ((i & 3) << 5)), pack2(acc[8 * i], acc[8 * i + 1]), pack2(acc[8 * i + 2], acc[8 * i + 3]),
                          pack2(acc[8 * i + 4], acc[8 * i + 5]), pack2(acc[8 * i + 6], acc[8 * i + 7]));
                fence_async_smem();
                __syncwarp();
                CS(12);
                mbar_wait(BAR_ONE(sb, EV_LN2), 0);
                lp.load(sb, q4);
                CS(13);
            }
            const LnRow n2 = merge_stats(g_st2 + wg * 64 + w4 * 16 + g8, 512, q4, ep, sb, lane == 0 ? BAR_ONE(sb, EV_X1S + wg) : 0);
            if (tid == 0) TL(49);
            if (tid == 128) TL(45);
            CS(18);
            uint32_t xn[32];
            ln_norm(xn, acc, n2);
            ln_emit(xn, lp, sb, wg, ix);
            if (tid == 0) { TL(36); TC(109); }
            if (tid == 128) TL(43);
            CS(21);
        }
        {
            float a256[128], a128[64];
            mainloop32<true, LAG>(a256, a128, sb, wg, tw, r, EV_LAG1, 48, [&] {
                stg.acquire2(sb, wg);
                Ring q = r; if (!wg) q.next();
                mbar_wait(BAR_EMPTY(sb, q.slot), q.par ^ 1);
            });
            if (tid == 0) { TL(10); TC(110); }
            if (tid == 128) TL(51);
            glu_panel<0>(a256, sb + OFF_STG + wg * 16384, BAR_SFULL(sb, wg * 2));
            glu_panel<64>(a256, sb + OFF_STG + wg * 16384 + 8192, BAR_SFULL(sb, wg * 2 + 1));
            glu_panel<0>(a128, sb + (wg ? P3_SLOT1 : P3_SLOT0) * SLOT + 24576, BAR_ONE(sb, EV_P3 + wg));
            if (tid == 0) { TL(11); TC(111); }
            if (tid == 128) TL(52);
#pragma unroll 1
            for (int p = 0; p < 2; ++p) {
                float b256[128];
                mainloop32<false, LAGS>(b256, a128, sb, wg, tw, r, EV_LAG2 + p, 80 + 32 * p, [&] { stg.acquire2(sb, wg); });
                if (tid == 0) { TL(29 + 2 * p); TC(114 + 2 * p); }
                if (tid == 128) TL(53 + 2 * p);
                glu_panel<0>(b256, sb + OFF_STG + wg * 16384, BAR_SFULL(sb, wg * 2));
                glu_panel<64>(b256, sb + OFF_STG + wg * 16384 + 8192, BAR_SFULL(sb, wg * 2 + 1));
                if (tid == 0) { TL(30 + 2 * p); TC(115 + 2 * p); }
                if (tid == 128) TL(54 + 2 * p);
            }
            if (tid == 0) { TL(12); TC(112); }
        }
        {
            float acc[64], xf[64], gf[32];
            const uint32_t buf0 = sb + OFF_STG + wg * 16384;
            mainloop64<false, 56, LAGD, 40>(acc, sb, wg, tw, r, [&] {
                mbar_wait(BAR_ONE(sb, EV_GB), 0);
                load_res(xf, gf, stg.acquire2(sb, wg), sb + OFF_TAB + 256);
            });
            cluster_arrive();
            if (tid == 0) { TL(13); TC(113); }
            if (tid == 128) TL(57);
            IDX();
#pragma unroll
            for (int p = 0; p < 2; ++p) {
#pragma unroll
                for (int e = 32 * p; e < 32 * p + 32; ++e) acc[e] = fmaf(gf[(e >> 2) * 2 + (e & 1)], acc[e], xf[e]);
#pragma unroll
                for (int i = 4 * p; i < 4 * p + 4; ++i)
                    stsm4(buf0 + p * 8192 + (pan_addr ^ ((i & 3) << 5)), pack2(acc[8 * i], acc[8 * i + 1]), pack2(acc[8 * i + 2], acc[8 * i + 3]),
                          pack2(acc[8 * i + 4], acc[8 * i + 5]), pack2(acc[8 * i + 6], acc[8 * i + 7]));
                stg.publish(sb, wg, lane);
            }
            if (tid == 0) TL(14);
        }
      }
    } else {
        if (warp == 8 && !aux && elect_one()) {
#pragma unroll
            for (int i = 0; i < 4; ++i) mbar_init(BAR_SREADY(sb, i), 1);
#pragma unroll
            for (int i = 0; i < 4; ++i) mbar_init(BAR_ONE(sb, EV_WIN + i), 1);
#pragma unroll
            for (int i = 0; i < 4; ++i) {
                mbar_expect_tx(BAR_SREADY(sb, i), 8192);
                tma_load3(sb + OFF_STG + i * 8192, &mp.x, j * 128 + (i & 1) * 64, m * 64 + (i >> 1) * 32, BAR_SREADY(sb, i));
            }
#pragma unroll 1
            for (int i = 0; i < 4; ++i) {
                mbar_expect_tx(BAR_ONE(sb, EV_WIN + i), 8192);
                tma_load(sb + 5 * SLOT + i * 8192, &mp.wm8, 2 * i * 6144 + (m * 8 + j) * 16, 0, BAR_ONE(sb, EV_WIN + i));
                tma_load(sb + 5 * SLOT + i * 8192 + 4096, &mp.wm8, (2 * i + 1) * 6144 + (m * 8 + j) * 16, 0, BAR_ONE(sb, EV_WIN + i));
            }
        }
        __syncwarp();
        asm volatile("setmaxnreg.dec.sync.aligned.u32 56;");
        ep = flag_get(g_flags + FL_DONE);
        if (elect_one()) {
            if (warp == 8) {
                prefetch_map(&mp.wqkv); prefetch_map(&mp.wmod);
            } else if (warp < 11) {
                mbar_init(BAR_EMPTY(sb, NSLOT), 1);
#pragma unroll
                for (int i = 0; i < 2; ++i) mbar_init(BAR_SFULL(sb, (warp - 9) * 2 + i), 4);
#pragma unroll
                for (int i = 0; i < 3; ++i) {
                    mbar_init(BAR_EMPTY(sb, (warp - 9) * 3 + i), aux ? 1 : 4);
                    mbar_init(BAR_FULL(sb, (warp - 9) * 3 + i), 1); mbar_init(BAR_FULL(sb, (warp - 9) * 3 + i) + AF_REL, 1);
                }
            } else {
#pragma unroll
                for (int i = EV_P0; i < EV_COUNT; ++i) mbar_init(BAR_ONE(sb, i), i == EV_P0 ? 8 : (i == EV_P3 || i == EV_P31 || i >= EV_X1S) ? 4 : 1);
            }
            asm volatile("fence.mbarrier_init.release.cluster;" ::: "memory");
        }
        __syncwarp();
        cluster_arrive();
        cluster_wait();
        ep = __shfl_sync(0xffffffffu, ep, 0) / NCTA + 1;
        if (warp == 8) {
            const bool el = elect_one();
            Ring r{0, 1};
            if (aux) {
                mbar_wait(BAR_ONE(sb, EV_GO), 0);
#pragma unroll 1
                for (int it = 0; it < 64; ++it) {
                    const int col = 2048 + (it >> 4) * 1024 + j * 256;
                    mbar_wait(BAR_EMPTY(sb, r.slot), r.par);
                    const uint32_t st = sb + r.slot * SLOT, fb = BAR_FULL(sb, r.slot);
                    if (el) {
                        mbar_expect_tx(fb, 32768);
#pragma unroll
                        for (int b = 0; b < 4; ++b) tma_load(st + b * 8192, &mp.wmod, col + b * 64, (it & 15) * 64, fb);
                    }
                    r.next();
                }
            } else {
#pragma unroll 1
                for (int it = 0; it < 32; ++it) {
                    const int cb = j * 128 + rank * 64, k0 = kof(it, 2, j);
                    if (it == BW0) mbar_wait(BAR_ONE(sb, BWEV), 0);
                    if (it == BW1) mbar_wait(BAR_ONE(sb, EV_PAR), 0);
                    if (it == 5) mbar_wait(BAR_ONE(sb, EV_P0), 0);
                    if ((AGO & 1) && it == 6) mbar_wait(BAR_ONE(sb, EV_AGO), 0);
                    mbar_wait(BAR_EMPTY(sb, r.slot), r.par);
                    const uint32_t st = sb + r.slot * SLOT, fb = BAR_FULL(sb, r.slot);
                    if (el) {
                        mbar_expect_tx(fb, it < 4 ? 24576 : 28672);
                        tma_load_mc(st + 8192 + rank * 4096, &mp.wqkv, 1024 + cb, k0, fb);
                        tma_load_mc(st + 16384 + rank * 4096, &mp.wqkv, 2048 + cb, k0, fb);
                        tma_load_mc(st + 24576 + rank * 4096, &mp.wqkv, cb, k0, fb);
                        if (it < 4) mbar_arrive(fb + AF_REL);
                        if (it == PFWO + (m >> 1)) { tma_prefetch(&mp.wo, j * 128, m * 64); tma_prefetch(&mp.wo, j * 128 + 64, m * 64); }
                    }
                    r.next();
                }
                if (el) mbar_arrive(BAR_ONE(sb, EV_KV));
#pragma unroll 1
                for (int it = 0; it < 16; ++it) {
                    if ((AGO & 2) && it == 6) mbar_wait(BAR_ONE(sb, EV_AGO1), 0);
                    mbar_wait(BAR_EMPTY(sb, r.slot), r.par);
                    const uint32_t st = sb + r.slot * SLOT, fb = BAR_FULL(sb, r.slot);
                    if (el) {
                        mbar_expect_tx(fb, it < 2 ? 16384 : 24576);
                        tma_load_mc(st + 16384 + rank * 8192, &mp.wo, j * 128 + rank * 64, kof(it, 1, j), fb);
                        if (it < 2) mbar_arrive(fb + AF_REL);
                        if (it == 6) { prefetch_map(&mp.wg); prefetch_map(&mp.wu); }
                    }
                    r.next();
                }
                const CUtensorMap* wm = rank ? &mp.wu : &mp.wg;
#pragma unroll 1
                for (int g = 0; g < 96; ++g) {
                    if ((AGO & 4) && g == 6) mbar_wait(BAR_ONE(sb, EV_AGO2), 0);
                    const int p = g >> 5, cb = j * 448 + (p == 0 ? 0 : 64 + p * 128), k0 = p == 0 ? kof(g, 2, j) : (g & 31) * 32;
                    mbar_wait(BAR_EMPTY(sb, r.slot), r.par);
                    const uint32_t st = sb + r.slot * SLOT, fb = BAR_FULL(sb, r.slot);
                    if (el) {
                        mbar_expect_tx(fb, (g < 4 || p > 0) ? 24576 : 28672);
                        tma_load_mc(st + 8192 + rank * 4096, wm, cb, k0, fb);
                        tma_load_mc(st + 16384 + rank * 4096, wm, cb + 64, k0, fb);
                        if (p == 0) tma_load_mc(st + 24576 + rank * 4096, wm, cb + 128, k0, fb);
                        else if (ONEP) tma_load(st, &mp.h2l, k0, m * 128, fb);
                        if (g < 4) mbar_arrive(fb + AF_REL);
                        if (g == 90) prefetch_map(&mp.wd);
                    }
                    r.next();
                }
#pragma unroll 1
                for (int g = 0; g < 56; ++g) {
                    if (ONEP && (g == 0 || g == 24 || g == 40)) mbar_wait(BAR_ONE(sb, EV_H0 + (g >> 4)), 0);
                    const int k0 = kdown(g);
                    mbar_wait(BAR_EMPTY(sb, r.slot), r.par);
                    const uint32_t st = sb + r.slot * SLOT, fb = BAR_FULL(sb, r.slot);
                    if (el) {
                        mbar_expect_tx(fb, 32768);
                        tma_load_mc(st + 16384 + rank * 8192, &mp.wd, j * 128 + rank * 64, k0, fb);
                        if (ONEP) { tma_load(st, &mp.hb, k0, m * 128, fb); tma_load(st + 8192, &mp.hb, k0, m * 128 + 64, fb); }
                    }
                    r.next();
                }
            }
        } else if (aux) {
        } else if (warp == 11) {
            const bool el = elect_one();
            const int row0 = m * 128;
            const uint32_t* const fl = g_flags + FL_PROG + (m * 32 + (lane & 16) + (kof(lane & 15, 1, j) >> 6)) * FS;
            if (el) { prefetch_map(&mp.h1h); prefetch_map(&mp.h2h); prefetch_map(&mp.h2l); }
            {
                const uint4* pk = pt.mail->mod1 + grp * 512 + j * 32 + lane;
                uint4 a, b; uint32_t n = 0;
                mbar_wait(BAR_ONE(sb, EV_WIN3), 0);
                while (true) {
                    a = ld_pkt16(pk); b = ld_pkt16(pk + 256);
                    if (__all_sync(0xffffffffu, a.z == ep && b.z == ep)) break;
                    SPIN_GUARD(n);
                }
                sts128(sb + OFF_PAR + lane * 16, a.x, a.y, b.x, b.y);
                __syncwarp();
                if (lane == 0) { mbar_arrive(BAR_ONE(sb, EV_PAR)); TL(46); }
            }
            mbar_wait(BAR_ONE(sb, EV_P0), 0);
            Ring r{0, 1};
#pragma unroll 1
            for (int ph = 0; ph < 3; ++ph) {
                const int sh = ph == 1 ? 1 : 2, nst = 8 << sh;
                const uint32_t half = 16384 >> sh;
                const CUtensorMap* tm = ph == 0 ? &mp.h1h : ph == 1 ? &mp.o : &mp.h2h;
                if (ph == 1) fetch_halo(g_halo + ((m - 1) * 8 + j) * 512 + 256 + lane, m == 0, sb, 2, lane);
                const uint32_t target = ep * 8 + ST_H1 + ph;
                int a0 = 1 << sh, a1 = a0, fr = a0;
                r.skip(fr);
                uint32_t s0 = r.slot, s1 = r.slot, have = 0, n = 0;
                int k0 = j ? 0 : 128, k1 = k0;
#pragma unroll 1
                for (; fr < NSLOT; ++fr) { mbar_wait(BAR_EMPTY(sb, r.slot), r.par); r.next(); }
                uint32_t v = flag_get(fl);
                auto load = [&](int& a, uint32_t& sl, int& k, uint32_t w) {
                    const uint32_t fb = BAR_FULL(sb, sl) + (w ? 0 : AF_REL);
                    if (el) { if (!w) mbar_expect_tx(fb, half); tma_load(sb + sl * SLOT + w * half, tm, k, row0 + w * 64, fb); }
                    if (a == NSLOT - 1 && w == ((AGW >> ph) & 1) && el) mbar_arrive(BAR_ONE(sb, EV_AGO + ph));
                    ++a; if (++sl == NSLOT) sl = 0;
                    k += 128 >> sh; if (k == j * 128) k += 128;
                };
                do {
                    PS(0);
                    if (fr < 10 && mbar_test(BAR_EMPTY(sb, r.slot), r.par) && (ph < 2 || mbar_test(BAR_ONE(sb, EV_X1 + (fr < 8)), 0))) { ++fr; r.next(); }
                    SPIN_GUARD(n);
                    PS(1);
                    const bool ok = (int32_t)(v - target) >= 0;
                    v = flag_get(fl);
                    have = __ballot_sync(0xffffffffu, ok);
                    PS(2);
#pragma unroll 1
                    while (a1 < fr && (have & (0x10000u << (a1 >> (sh - 1))))) {
                        if (a1 == (1 << sh)) TL(16 + ph);
                        load(a1, s1, k1, 1);
                    }
                    PS(3);
#pragma unroll 1
                    while (a0 < fr && (have & (1u << (a0 >> (sh - 1))))) load(a0, s0, k0, 0);
                    PS(4);
                } while (have != 0xffffffffu);
                if (ph == 2) mbar_wait2(BAR_ONE(sb, EV_X1), BAR_ONE(sb, EV_X11), 0);
#pragma unroll 1
                while (a0 < nst) {
                    mbar_wait(BAR_EMPTY(sb, r.slot), r.par);
                    r.next();
                    load(a1, s1, k1, 1); load(a0, s0, k0, 0);
                }
            }
#pragma unroll 1
            for (int p = 0; p < 3; ++p) {
                uint32_t n = 0;
                while (!__all_sync(0xffffffffu, (int32_t)(flag_get(fl) - (ep * 8 + ST_H + p)) >= 0)) { SPIN_GUARD(n); __nanosleep(500); }
                if (el) mbar_arrive(BAR_ONE(sb, EV_H0 + p));
            }
        } else {
            const uint32_t w = warp - 9;
            const int row0 = m * 128 + w * 64;
            const uint32_t stg = sb + OFF_STG + w * 16384;
            uint32_t* const fl = g_flags + FL_PROG + (m * 32 + w * 16 + 2 * j) * FS;
            uint32_t b = 0, par = 0;
            const bool el = elect_one();
            auto store = [&](const CUtensorMap* tm, int col, bool nat = false) {
                mbar_wait(BAR_SFULL(sb, w * 2 + b), (par >> b) & 1);
                par ^= 1u << b;
                if (el) {
                    if (nat) tma_store3(tm, col, row0 >> 1, stg + b * 8192); else tma_store(tm, col, row0, stg + b * 8192);
                    bulk_commit();
                }
                b ^= 1;
            };
            auto load2 = [&](const CUtensorMap* tm, bool nat) {
                if (el) {
#pragma unroll
                    for (uint32_t i = 0; i < 2; ++i) {
                        mbar_expect_tx(BAR_SREADY(sb, w * 2 + i), 8192);
                        if (nat) tma_load3(stg + i * 8192, tm, j * 128 + i * 64, row0 >> 1, BAR_SREADY(sb, w * 2 + i));
                        else tma_load(stg + i * 8192, tm, j * 128 + i * 64, row0, BAR_SREADY(sb, w * 2 + i));
                    }
                }
            };
            auto send2 = [&](const CUtensorMap* tm, int step) {
                store(tm, j * 128); store(tm, j * 128 + 64);
                if (el) {
                    asm volatile("cp.async.bulk.wait_group 1;" ::: "memory"); flag_set(fl, ep * 8 + step);
                    bulk_wait_all(); flag_set(fl + FS, ep * 8 + step);
                }
            };
            auto free2 = [&]() { if (el) { mbar_arrive(BAR_SREADY(sb, w * 2)); mbar_arrive(BAR_SREADY(sb, w * 2 + 1)); } };
            auto gate = [&](int vec, int ev) {
                uint4 v; uint32_t n = 0;
                while (true) {
                    v = ld_pkt2(g_mod + vec * 512 + j * 64 + lane * 2);
                    if (__all_sync(0xffffffffu, v.y == ep && v.w == ep)) break;
                    SPIN_GUARD(n); __nanosleep(300);
                }
                asm volatile("st.shared.v2.u32 [%0], {%1, %2};" :: "r"(sb + OFF_TAB + (ev - EV_GA) * 256 + lane * 8), "r"(v.x), "r"(v.z) : "memory");
                __syncwarp();
                if (lane == 0) mbar_arrive(BAR_ONE(sb, ev));
            };
            if (el) { prefetch_map(&mp.h1s); prefetch_map(&mp.o); prefetch_map(&mp.x1); prefetch_map(&mp.h2s); prefetch_map(&mp.hb); prefetch_map(&mp.out); prefetch_map(&mp.wo); }
            if (el) { flag_set(fl, ep * 8); flag_set(fl + FS, ep * 8); }
            send2(&mp.h1s, ST_H1);
            if (w == 0) TL(47);
            free2();
            if (w == 0) fetch_halo(g_halo + ((m - 1) * 8 + j) * 512 + lane, m == 0, sb, 0, lane);
            else { mbar_wait(BAR_ONE(sb, EV_KV), 0); gate(2, EV_GA); }
            send2(&mp.o, ST_O);
            if (w == 0) TL(40); else TL(38);
            mbar_wait(BAR_ONE(sb, EV_OWN + w), 0);
            load2(&mp.x, true);
            if (w == 1) {
                uint32_t n = 0;
                while ((int32_t)(flag_get(g_flags + FL_LN2) - ep * 8) < 0) { SPIN_GUARD(n); __nanosleep(200); }
                const uint4 v = __ldcg((const uint4*)(g_par2 + j * 128) + lane);
                sts128(sb + OFF_PAR + lane * 16, v.x, v.y, v.z, v.w);
                __syncwarp();
                if (lane == 0) mbar_arrive(BAR_ONE(sb, EV_LN2));
            }
            mbar_wait(BAR_ONE(sb, EV_X1S + w), 0);
            if (el) {
                tma_store(&mp.x1, j * 128, row0, sb + (X1_SLOT + 2 - 2 * w) * SLOT); tma_store(&mp.x1, j * 128 + 64, row0, sb + (X1_SLOT + 3 - 2 * w) * SLOT);
                bulk_commit(); bulk_wait_read(); mbar_arrive(BAR_ONE(sb, EV_X1 + w));
            }
            send2(&mp.h2s, ST_H2);
            if (w == 0) TL(37);
            free2();
#pragma unroll 1
            for (int p = 0; p < 3; ++p) {
                const int col = j * 448 + (p ? 64 + p * 128 : 0);
                store(&mp.hb, col); store(&mp.hb, col + 64);
                if (p == 0) {
                    mbar_wait(BAR_ONE(sb, EV_P3 + w), 0);
                    if (el) { tma_store(&mp.hb, col + 128, row0, sb + (w ? P3_SLOT1 : P3_SLOT0) * SLOT + 24576); bulk_commit(); }
                }
                if (el) { bulk_wait_all(); flag_set(fl, ep * 8 + ST_H + p); flag_set(fl + FS, ep * 8 + ST_H + p); }
                if (p < 2) free2();
                if (p == 0 && w == 1) gate(5, EV_GB);
            }
            load2(&mp.x1, false);
            cluster_arrive_early = true;
            cluster_arrive();
            store(&mp.out, j * 128, true); store(&mp.out, j * 128 + 64, true);
            if (el) bulk_wait_read();
        }
        __syncwarp();
    }
    if (aux || (wg == 2 && !cluster_arrive_early)) cluster_arrive();
    cluster_wait();
    if (tid == 0) {
        TL(15);
        flag_add(pt.mail->flags + FL_DONE);
    }
}

typedef CUresult (*EncodeFn)(CUtensorMap*, CUtensorMapDataType, cuuint32_t, void*, const cuuint64_t*, const cuuint64_t*, const cuuint32_t*,
                             const cuuint32_t*, CUtensorMapInterleave, CUtensorMapSwizzle, CUtensorMapL2promotion, CUtensorMapFloatOOBfill);

void make_map(EncodeFn fn, CUtensorMap* m, const void* ptr, uint64_t rows, uint64_t cols, uint32_t brows, uint32_t bcols) {
    cuuint64_t dims[2] = {cols, rows}, strides[1] = {cols * 2};
    cuuint32_t box[2] = {bcols, brows}, es[2] = {1, 1};
    fn(m, CU_TENSOR_MAP_DATA_TYPE_BFLOAT16, 2, (void*)ptr, dims, strides, box, es, CU_TENSOR_MAP_INTERLEAVE_NONE,
       bcols == 64 ? CU_TENSOR_MAP_SWIZZLE_128B : bcols == 32 ? CU_TENSOR_MAP_SWIZZLE_64B : CU_TENSOR_MAP_SWIZZLE_NONE, CU_TENSOR_MAP_L2_PROMOTION_L2_256B, CU_TENSOR_MAP_FLOAT_OOB_FILL_NONE);
}

void make_map3(EncodeFn fn, CUtensorMap* m, const void* ptr) {
    cuuint64_t dims[3] = {D_, S_ / 2, 2}, strides[2] = {4 * D_, 2 * D_};
    cuuint32_t box[3] = {64, 32, 2}, es[3] = {1, 1, 1};
    fn(m, CU_TENSOR_MAP_DATA_TYPE_BFLOAT16, 3, (void*)ptr, dims, strides, box, es, CU_TENSOR_MAP_INTERLEAVE_NONE,
       CU_TENSOR_MAP_SWIZZLE_128B, CU_TENSOR_MAP_L2_PROMOTION_L2_256B, CU_TENSOR_MAP_FLOAT_OOB_FILL_NONE);
}

}

extern "C" void kernel_launch(void* const* d_in, const int* in_sizes, int n_in, void* d_out, int out_size) {
    (void)in_sizes; (void)n_in; (void)out_size;
    void* fnp = nullptr;
    cudaDriverEntryPointQueryResult qr;
    cudaGetDriverEntryPoint("cuTensorMapEncodeTiled", &fnp, cudaEnableDefault, &qr);
    EncodeFn fn = (EncodeFn)fnp;
    void *h1, *o, *x1, *h2, *hb, *mail;
    cudaGetSymbolAddress(&h1, g_h1);
    cudaGetSymbolAddress(&mail, g_mail);
    cudaGetSymbolAddress(&o, g_o);
    cudaGetSymbolAddress(&hb, g_hb);
    x1 = h1; h2 = o;
    Maps mp;
    make_map(fn, &mp.h1h, h1, S_, D_, 64, 32);
    make_map(fn, &mp.h2h, h2, S_, D_, 64, 32);
    make_map(fn, &mp.h1s, h1, S_, D_, 64, 64);
    make_map(fn, &mp.o, o, S_, D_, 64, 64);
    make_map(fn, &mp.h2l, h2, S_, D_, 128, 32);
    make_map(fn, &mp.h2s, h2, S_, D_, 64, 64);
    make_map(fn, &mp.hb, hb, S_, F_, 64, 64);
    make_map(fn, &mp.wqkv, d_in[1], D_, 3 * D_, 32, 64);
    make_map(fn, &mp.wo, d_in[2], D_, D_, 64, 64);
    make_map(fn, &mp.wg, d_in[4], D_, F_, 32, 64);
    make_map(fn, &mp.wu, d_in[5], D_, F_, 32, 64);
    make_map(fn, &mp.wd, d_in[6], F_, D_, 64, 64);
    make_map(fn, &mp.wmod, d_in[8], D_, 6 * D_, 64, 64);
    make_map(fn, &mp.wm8, d_in[8], D_ / 8, 8 * 6 * D_, 128, 16);
    make_map3(fn, &mp.x, d_in[0]);
    make_map(fn, &mp.x1, x1, S_, D_, 64, 64);
    make_map3(fn, &mp.out, d_out);
    cudaFuncSetAttribute(fused_block_kernel, cudaFuncAttributeMaxDynamicSharedMemorySize, SMEM_BYTES);
    cudaLaunchConfig_t cfg = {};
    cfg.gridDim = dim3(NCTA); cfg.blockDim = dim3(384); cfg.dynamicSmemBytes = SMEM_BYTES; cfg.stream = cudaStreamPerThread;
    cudaLaunchAttribute at[1];
    at[0].id = cudaLaunchAttributeClusterDimension; at[0].val.clusterDim.x = 2; at[0].val.clusterDim.y = 1; at[0].val.clusterDim.z = 1;
    cfg.attrs = at; cfg.numAttrs = 1;
    const Ptrs pt{(const __nv_bfloat16*)d_in[7], (Mail*)mail};
    cudaLaunchKernelEx(&cfg, fused_block_kernel, pt, mp);
}
```

```cpp
#include <cuda_runtime.h>
#include <cuda_bf16.h>
#include <cuda.h>
#include <stdint.h>
#include <stddef.h>

#define LAG 3
#define LAGS 3
#define LAGW 3
#define LAGD 3
#define LAGQ 4
#define MIDW 8
#define PFWO 14
#define FLAGRED 1
#define FS 1
#define AGO 7
#define AGW 6
#define LAGSIG 1
#define SIGW 1
#define SIGD 1
#define CSW 0
#define FENCES 1
#define LWAIT 2
#define RESET 1
#define BW0 0
#define BWEV EV_WIN
#define GODLY 0
#define BW1 3
#define KDEBUG 0

namespace {

constexpr int S_ = 2048, D_ = 1024, F_ = 3584;
constexpr int NCTA = 132;
constexpr int NSLOT = 6;
constexpr uint32_t SLOT = 32768;
constexpr uint32_t OFF_STG = NSLOT * SLOT;
constexpr uint32_t OFF_BAR = OFF_STG + 32768;
constexpr uint32_t OFF_PAR = OFF_BAR + 512;
constexpr uint32_t OFF_TAB = OFF_PAR + 768;
constexpr uint32_t OFF_TL = OFF_PAR + 2048;
constexpr uint32_t SMEM_BYTES = OFF_TL + (KDEBUG ? 512 : 0);
constexpr uint32_t P3_SLOT1 = (32 + 16 + 32) % NSLOT, P3_SLOT0 = (P3_SLOT1 + 1) % NSLOT;

constexpr uint32_t X1_SLOT = (32 + 16) % NSLOT;
static_assert(X1_SLOT + 3 < NSLOT && LAGW <= 4, "x1 parking");
constexpr int ST_H1 = 1, ST_O = 2, ST_H2 = 3, ST_H = 4, FL_DONE = 0, FL_LN2 = 1, FL_AUX = 32, FL_PROG = 64;

struct Maps {
    CUtensorMap h1h, h1s, o, h2h, h2l, h2s, hb, wqkv, wo, wg, wu, wd, wmod, wm8, x, x1, out, wg3, wu3, hb3;
};

struct Mail {
    uint32_t flags[16 * 32 * FS + 64];
    uint2 mod[6 * D_ / 2];
    uint4 mod1[8 * 512];
    uint4 st1[8 * S_];
    uint32_t par2[D_];
    uint4 halo[128 * 512];
};
struct Ptrs { const __nv_bfloat16* c; Mail* mail; };

__device__ __align__(128) Mail g_mail;
__device__ __align__(128) __nv_bfloat16 g_h1[S_ * D_];
__device__ __align__(128) __nv_bfloat16 g_o[S_ * D_];
__device__ __align__(128) __nv_bfloat16 g_hb[S_ * F_];
#define TL(i) do {} while (0)
#define TC(i) do {} while (0)
#define TS(g, which) do {} while (0)
#define CS(i) do {} while (0)

#define PS(i) do {} while (0)
__device__ __forceinline__ uint32_t smem_u32(const void* p) { return (uint32_t)__cvta_generic_to_shared(p); }
__device__ __forceinline__ void mbar_init(uint32_t bar, uint32_t cnt) { asm volatile("mbarrier.init.shared::cta.b64 [%0], %1;" :: "r"(bar), "r"(cnt) : "memory"); }
__device__ __forceinline__ void mbar_expect_tx(uint32_t bar, uint32_t bytes) { asm volatile("mbarrier.arrive.expect_tx.shared::cta.b64 _, [%0], %1;" :: "r"(bar), "r"(bytes) : "memory"); }
__device__ __forceinline__ void mbar_arrive(uint32_t bar) { asm volatile("mbarrier.arrive.shared::cta.b64 _, [%0];" :: "r"(bar) : "memory"); }
__device__ __forceinline__ void mbar_arrive_cta(uint32_t bar, uint32_t cta) {
    asm volatile("{\n.reg .b32 r;\nmapa.shared::cluster.u32 r, %0, %1;\nmbarrier.arrive.shared::cluster.b64 _, [r];\n}" :: "r"(bar), "r"(cta) : "memory");
}
__device__ __forceinline__ void mbar_wait(uint32_t bar, uint32_t parity) {
    asm volatile("{\n.reg .pred p;\n.reg .u32 n;\nmov.u32 n, 0;\n"
        "W_LOOP:\nmbarrier.try_wait.parity.shared::cta.b64 p, [%0], %1;\n@p bra W_DONE;\n"
        "add.u32 n, n, 1;\nsetp.lt.u32 p, n, 0x400000;\n@p bra W_LOOP;\ntrap;\nW_DONE:\n}" :: "r"(bar), "r"(parity) : "memory");
}
__device__ __forceinline__ void mbar_wait2(uint32_t b0, uint32_t b1, uint32_t parity) {
    asm volatile("{\n.reg .pred p, q;\n.reg .u32 n;\nmov.u32 n, 0;\n"
        "W_LOOP:\nmbarrier.try_wait.parity.shared::cta.b64 p, [%0], %2;\nmbarrier.try_wait.parity.shared::cta.b64 q, [%1], %2;\nand.pred p, p, q;\n@p bra W_DONE;\n"
        "add.u32 n, n, 1;\nsetp.lt.u32 p, n, 0x400000;\n@p bra W_LOOP;\ntrap;\nW_DONE:\n}" :: "r"(b0), "r"(b1), "r"(parity) : "memory");
}
__device__ __forceinline__ bool mbar_test(uint32_t bar, uint32_t parity) {
    uint32_t r; asm volatile("{\n.reg .pred p;\nmbarrier.test_wait.parity.shared::cta.b64 p, [%1], %2;\nselp.u32 %0, 1, 0, p;\n}" : "=r"(r) : "r"(bar), "r"(parity) : "memory"); return r;
}
__device__ __forceinline__ bool mbar_test2(uint32_t b0, uint32_t b1, uint32_t parity) {
    uint32_t r;
    asm volatile("{\n.reg .pred p, q;\nmbarrier.test_wait.parity.shared::cta.b64 p, [%1], %3;\nmbarrier.test_wait.parity.shared::cta.b64 q, [%2], %3;\n"
        "and.pred p, p, q;\nselp.u32 %0, 1, 0, p;\n}" : "=r"(r) : "r"(b0), "r"(b1), "r"(parity) : "memory");
    return r;
}
__device__ __forceinline__ void tma_load3(uint32_t dst, const CUtensorMap* m, int c0, int c1, uint32_t bar) {
    asm volatile("cp.async.bulk.tensor.3d.shared::cluster.global.mbarrier::complete_tx::bytes [%0], [%1, {%3, %4, %5}], [%2];"
        :: "r"(dst), "l"(m), "r"(bar), "r"(c0), "r"(c1), "r"(0) : "memory");
}
__device__ __forceinline__ void tma_store3(const CUtensorMap* m, int c0, int c1, int c2, uint32_t src) {
    asm volatile("cp.async.bulk.tensor.3d.global.shared::cta.bulk_group [%0, {%2, %3, %4}], [%1];" :: "l"(m), "r"(src), "r"(c0), "r"(c1), "r"(c2) : "memory");
}
__device__ __forceinline__ void tma_load3_mc(uint32_t dst, const CUtensorMap* m, int c1, int c2, uint32_t bar) {
    asm volatile("cp.async.bulk.tensor.3d.shared::cluster.global.mbarrier::complete_tx::bytes.multicast::cluster.L2::cache_hint [%0], [%1, {%3, %4, %5}], [%2], %6, %7;"
        :: "r"(dst), "l"(m), "r"(bar), "r"(0), "r"(c1), "r"(c2), "h"((uint16_t)3), "l"(0x12F0000000000000ull) : "memory");
}
__device__ __forceinline__ void tma_load(uint32_t dst, const CUtensorMap* m, int c0, int c1, uint32_t bar) {
    asm volatile("cp.async.bulk.tensor.2d.shared::cluster.global.mbarrier::complete_tx::bytes [%0], [%1, {%3, %4}], [%2];"
        :: "r"(dst), "l"(m), "r"(bar), "r"(c0), "r"(c1) : "memory");
}
__device__ __forceinline__ void tma_load_mc(uint32_t dst, const CUtensorMap* m, int c0, int c1, uint32_t bar) {
    asm volatile("cp.async.bulk.tensor.2d.shared::cluster.global.mbarrier::complete_tx::bytes.multicast::cluster.L2::cache_hint [%0], [%1, {%3, %4}], [%2], %5, %6;"
        :: "r"(dst), "l"(m), "r"(bar), "r"(c0), "r"(c1), "h"((uint16_t)3), "l"(0x12F0000000000000ull) : "memory");
}
__device__ __forceinline__ void tma_prefetch(const CUtensorMap* m, int c0, int c1) {
    asm volatile("cp.async.bulk.prefetch.tensor.2d.L2.global [%0, {%1, %2}];" :: "l"(m), "r"(c0), "r"(c1) : "memory");
}
__device__ __forceinline__ void tma_store(const CUtensorMap* m, int c0, int c1, uint32_t src) {
    asm volatile("cp.async.bulk.tensor.2d.global.shared::cta.bulk_group [%0, {%2, %3}], [%1];" :: "l"(m), "r"(src), "r"(c0), "r"(c1) : "memory");
}
__device__ __forceinline__ void bulk_commit() { asm volatile("cp.async.bulk.commit_group;" ::: "memory"); }
__device__ __forceinline__ void bulk_wait_read() { asm volatile("cp.async.bulk.wait_group.read 0;" ::: "memory"); }
__device__ __forceinline__ void bulk_wait_all() { asm volatile("cp.async.bulk.wait_group 0;" ::: "memory"); }
__device__ __forceinline__ void fence_async_smem() { asm volatile("fence.proxy.async.shared::cta;" ::: "memory"); }
__device__ __forceinline__ void prefetch_map(const CUtensorMap* m) { asm volatile("prefetch.tensormap [%0];" :: "l"(m) : "memory"); }
__device__ __forceinline__ void wg_fence() { asm volatile("wgmma.fence.sync.aligned;" ::: "memory"); }
__device__ __forceinline__ void wg_commit() { asm volatile("wgmma.commit_group.sync.aligned;" ::: "memory"); }
template <int N> __device__ __forceinline__ void wg_wait() { asm volatile("wgmma.wait_group.sync.aligned %0;" :: "n"(N) : "memory"); }
__device__ __forceinline__ void bar_sync(int id, int n) { asm volatile("bar.sync %0, %1;" :: "r"(id), "r"(n) : "memory"); }
__device__ __forceinline__ void bar_arrive(int id, int n) { asm volatile("bar.arrive %0, %1;" :: "r"(id), "r"(n) : "memory"); }
__device__ __forceinline__ void flag_add(uint32_t* f) { asm volatile("red.relaxed.gpu.global.add.u32 [%0], 1;" :: "l"(f) : "memory"); }
__device__ __forceinline__ void flag_set(uint32_t* f, uint32_t v) { asm volatile("red.relaxed.gpu.global.max.u32 [%0], %1;" :: "l"(f), "r"(v) : "memory"); }
__device__ __forceinline__ uint32_t flag_get(const uint32_t* f) { uint32_t v; asm volatile("ld.relaxed.gpu.global.u32 %0, [%1];" : "=r"(v) : "l"(f) : "memory"); return v; }
__device__ __forceinline__ uint32_t d16(uint32_t addr) { return (addr & 0x3FFFF) >> 4; }
__device__ __forceinline__ uint64_t mk_desc(uint32_t a16, uint32_t off, uint32_t lbo, uint32_t sbo, uint32_t swz) {
    const uint32_t lo = a16 + (off >> 4) + ((lbo >> 4) << 16), hi = (sbo >> 4) | (swz << 30);
    return ((uint64_t)hi << 32) | lo;
}
__device__ __forceinline__ uint32_t pack2(float lo, float hi) {
    uint32_t r; asm("cvt.rn.bf16x2.f32 %0, %1, %2;" : "=r"(r) : "f"(hi), "f"(lo)); return r;
}
__device__ __forceinline__ uint32_t hfma2_bf16(uint32_t a, uint32_t b, uint32_t c) {
    uint32_t r; asm("fma.rn.bf16x2 %0, %1, %2, %3;" : "=r"(r) : "r"(a), "r"(b), "r"(c)); return r;
}
__device__ __forceinline__ float bf_lo(uint32_t v) { return __uint_as_float(v << 16); }
__device__ __forceinline__ float bf_hi(uint32_t v) { return __uint_as_float(v & 0xFFFF0000u); }
__device__ __forceinline__ void unpack2(uint32_t v, float& lo, float& hi) {
    asm volatile("shl.b32 %0, %2, 16;\nand.b32 %1, %2, 0xffff0000;" : "=f"(lo), "=f"(hi) : "r"(v));
}
__device__ __forceinline__ float bf_round(float x) { return __bfloat162float(__float2bfloat16_rn(x)); }
__device__ __forceinline__ void stsm4(uint32_t addr, uint32_t r0, uint32_t r1, uint32_t r2, uint32_t r3) {
    asm volatile("stmatrix.sync.aligned.m8n8.x4.shared.b16 [%0], {%1, %2, %3, %4};" :: "r"(addr), "r"(r0), "r"(r1), "r"(r2), "r"(r3) : "memory");
}
__device__ __forceinline__ void stsm4t(uint32_t addr, uint32_t r0, uint32_t r1, uint32_t r2, uint32_t r3) {
    asm volatile("stmatrix.sync.aligned.m8n8.x4.trans.shared.b16 [%0], {%1, %2, %3, %4};" :: "r"(addr), "r"(r0), "r"(r1), "r"(r2), "r"(r3) : "memory");
}
__device__ __forceinline__ uint32_t movm(uint32_t a) { uint32_t d; asm volatile("movmatrix.sync.aligned.m8n8.trans.b16 %0, %1;" : "=r"(d) : "r"(a)); return d; }
__device__ __forceinline__ void ldsm4(uint32_t addr, uint32_t& r0, uint32_t& r1, uint32_t& r2, uint32_t& r3) {
    asm volatile("ldmatrix.sync.aligned.m8n8.x4.shared.b16 {%0, %1, %2, %3}, [%4];" : "=r"(r0), "=r"(r1), "=r"(r2), "=r"(r3) : "r"(addr) : "memory");
}
__device__ __forceinline__ void ldsm4t(uint32_t addr, uint32_t& r0, uint32_t& r1, uint32_t& r2, uint32_t& r3) {
    asm volatile("ldmatrix.sync.aligned.m8n8.x4.trans.shared.b16 {%0, %1, %2, %3}, [%4];" : "=r"(r0), "=r"(r1), "=r"(r2), "=r"(r3) : "r"(addr) : "memory");
}
__device__ __forceinline__ void mma16816(float (&c)[4], uint32_t a0, uint32_t a1, uint32_t a2, uint32_t a3, uint32_t b0, uint32_t b1) {
    asm("mma.sync.aligned.m16n8k16.row.col.f32.bf16.bf16.f32 {%0, %1, %2, %3}, {%4, %5, %6, %7}, {%8, %9}, {%0, %1, %2, %3};"
        : "+f"(c[0]), "+f"(c[1]), "+f"(c[2]), "+f"(c[3]) : "r"(a0), "r"(a1), "r"(a2), "r"(a3), "r"(b0), "r"(b1));
}
__device__ __forceinline__ float rcp(float x) { float r; asm("rcp.approx.ftz.f32 %0, %1;" : "=f"(r) : "f"(x)); return r; }
__device__ __forceinline__ float ex2(float x) { float r; asm("ex2.approx.ftz.f32 %0, %1;" : "=f"(r) : "f"(x)); return r; }
__device__ __forceinline__ float glu_half(float gh, float uh) {
    float t; asm("tanh.approx.f32 %0, %1;" : "=f"(t) : "f"(gh)); return fmaf(t, uh, uh);
}
__device__ __forceinline__ float silu_(float x) { return __fdividef(x, 1.f + __expf(-x)); }
__device__ __forceinline__ void st_pkt(void* p, uint32_t a, uint32_t b) {
    asm volatile("{\n.reg .b64 t;\nmov.b64 t, {%1, %2};\nst.relaxed.gpu.global.b64 [%0], t;\n}" :: "l"(p), "r"(a), "r"(b) : "memory");
}
__device__ __forceinline__ uint4 ld_pkt2(const void* p) {
    uint4 v; asm volatile("{\n.reg .b64 t, u;\nld.relaxed.gpu.global.v2.b64 {t, u}, [%4];\nmov.b64 {%0, %1}, t;\nmov.b64 {%2, %3}, u;\n}"
        : "=r"(v.x), "=r"(v.y), "=r"(v.z), "=r"(v.w) : "l"(p) : "memory"); return v;
}
__device__ __forceinline__ void st_pkt16(void* p, uint32_t a, uint32_t b, uint32_t c, uint32_t d) {
    asm volatile("{\n.reg .b64 t, u;\n.reg .b128 w;\nmov.b64 t, {%1, %2};\nmov.b64 u, {%3, %4};\nmov.b128 w, {t, u};\nst.relaxed.gpu.global.b128 [%0], w;\n}"
        :: "l"(p), "r"(a), "r"(b), "r"(c), "r"(d) : "memory");
}
__device__ __forceinline__ uint4 ld_pkt16(const void* p) {
    uint4 v; asm volatile("{\n.reg .b64 t, u;\n.reg .b128 w;\nld.relaxed.gpu.global.b128 w, [%4];\nmov.b128 {t, u}, w;\nmov.b64 {%0, %1}, t;\nmov.b64 {%2, %3}, u;\n}"
        : "=r"(v.x), "=r"(v.y), "=r"(v.z), "=r"(v.w) : "l"(p) : "memory"); return v;
}
#define SPIN_GUARD(n) do { if (++(n) > (1u << 22)) asm volatile("trap;"); } while (0)
__device__ __forceinline__ uint4 lds128(uint32_t a) { uint4 v; asm volatile("ld.shared.v4.u32 {%0, %1, %2, %3}, [%4];" : "=r"(v.x), "=r"(v.y), "=r"(v.z), "=r"(v.w) : "r"(a) : "memory"); return v; }
__device__ __forceinline__ void sts128(uint32_t a, uint32_t x, uint32_t y, uint32_t z, uint32_t w) { asm volatile("st.shared.v4.u32 [%0], {%1, %2, %3, %4};" :: "r"(a), "r"(x), "r"(y), "r"(z), "r"(w) : "memory"); }
__device__ __forceinline__ uint32_t lds32(uint32_t a) { uint32_t v; asm volatile("ld.shared.u32 %0, [%1];" : "=r"(v) : "r"(a) : "memory"); return v; }
__device__ __forceinline__ void sts32(uint32_t a, uint32_t v) { asm volatile("st.shared.u32 [%0], %1;" :: "r"(a), "r"(v) : "memory"); }
__device__ __forceinline__ bool elect_one() {
    uint32_t p; asm volatile("{\n.reg .pred q;\nelect.sync _|q, 0xffffffff;\nselp.u32 %0, 1, 0, q;\n}" : "=r"(p)); return p;
}
__device__ __forceinline__ void cluster_arrive() { asm volatile("barrier.cluster.arrive.relaxed.aligned;" ::: "memory"); }
__device__ __forceinline__ void cluster_wait() { asm volatile("barrier.cluster.wait.aligned;" ::: "memory"); }

__device__ __forceinline__ void wgmma_n128_z(float (&d)[64], uint64_t da, uint64_t db) {
    asm volatile("{\n.reg .pred p;\nsetp.ne.b32 p, 0, 0;\n"
        "wgmma.mma_async.sync.aligned.m64n128k16.f32.bf16.bf16 {"
        "%0, %1, %2, %3, %4, %5, %6, %7, %8, %9, %10, %11, %12, %13, %14, %15, "
        "%16, %17, %18, %19, %20, %21, %22, %23, %24, %25, %26, %27, %28, %29, %30, %31, "
        "%32, %33, %34, %35, %36, %37, %38, %39, %40, %41, %42, %43, %44, %45, %46, %47, "
        "%48, %49, %50, %51, %52, %53, %54, %55, %56, %57, %58, %59, %60, %61, %62, %63"
        "}, %64, %65, p, 1, 1, 0, 1;\n}\n"
        : "=f"(d[0]), "=f"(d[1]), "=f"(d[2]), "=f"(d[3]), "=f"(d[4]), "=f"(d[5]), "=f"(d[6]), "=f"(d[7]),
          "=f"(d[8]), "=f"(d[9]), "=f"(d[10]), "=f"(d[11]), "=f"(d[12]), "=f"(d[13]), "=f"(d[14]), "=f"(d[15]),
          "=f"(d[16]), "=f"(d[17]), "=f"(d[18]), "=f"(d[19]), "=f"(d[20]), "=f"(d[21]), "=f"(d[22]), "=f"(d[23]),
          "=f"(d[24]), "=f"(d[25]), "=f"(d[26]), "=f"(d[27]), "=f"(d[28]), "=f"(d[29]), "=f"(d[30]), "=f"(d[31]),
          "=f"(d[32]), "=f"(d[33]), "=f"(d[34]), "=f"(d[35]), "=f"(d[36]), "=f"(d[37]), "=f"(d[38]), "=f"(d[39]),
          "=f"(d[40]), "=f"(d[41]), "=f"(d[42]), "=f"(d[43]), "=f"(d[44]), "=f"(d[45]), "=f"(d[46]), "=f"(d[47]),
          "=f"(d[48]), "=f"(d[49]), "=f"(d[50]), "=f"(d[51]), "=f"(d[52]), "=f"(d[53]), "=f"(d[54]), "=f"(d[55]),
          "=f"(d[56]), "=f"(d[57]), "=f"(d[58]), "=f"(d[59]), "=f"(d[60]), "=f"(d[61]), "=f"(d[62]), "=f"(d[63])
        : "l"(da), "l"(db));
}
__device__ __forceinline__ void wgmma_n128(float (&d)[64], uint64_t da, uint64_t db) {
    asm volatile("{\n.reg .pred p;\nsetp.eq.b32 p, 0, 0;\n"
        "wgmma.mma_async.sync.aligned.m64n128k16.f32.bf16.bf16 {"
        "%0, %1, %2, %3, %4, %5, %6, %7, %8, %9, %10, %11, %12, %13, %14, %15, "
        "%16, %17, %18, %19, %20, %21, %22, %23, %24, %25, %26, %27, %28, %29, %30, %31, "
        "%32, %33, %34, %35, %36, %37, %38, %39, %40, %41, %42, %43, %44, %45, %46, %47, "
        "%48, %49, %50, %51, %52, %53, %54, %55, %56, %57, %58, %59, %60, %61, %62, %63"
        "}, %64, %65, p, 1, 1, 0, 1;\n}\n"
        : "+f"(d[0]), "+f"(d[1]), "+f"(d[2]), "+f"(d[3]), "+f"(d[4]), "+f"(d[5]), "+f"(d[6]), "+f"(d[7]),
          "+f"(d[8]), "+f"(d[9]), "+f"(d[10]), "+f"(d[11]), "+f"(d[12]), "+f"(d[13]), "+f"(d[14]), "+f"(d[15]),
          "+f"(d[16]), "+f"(d[17]), "+f"(d[18]), "+f"(d[19]), "+f"(d[20]), "+f"(d[21]), "+f"(d[22]), "+f"(d[23]),
          "+f"(d[24]), "+f"(d[25]), "+f"(d[26]), "+f"(d[27]), "+f"(d[28]), "+f"(d[29]), "+f"(d[30]), "+f"(d[31]),
          "+f"(d[32]), "+f"(d[33]), "+f"(d[34]), "+f"(d[35]), "+f"(d[36]), "+f"(d[37]), "+f"(d[38]), "+f"(d[39]),
          "+f"(d[40]), "+f"(d[41]), "+f"(d[42]), "+f"(d[43]), "+f"(d[44]), "+f"(d[45]), "+f"(d[46]), "+f"(d[47]),
          "+f"(d[48]), "+f"(d[49]), "+f"(d[50]), "+f"(d[51]), "+f"(d[52]), "+f"(d[53]), "+f"(d[54]), "+f"(d[55]),
          "+f"(d[56]), "+f"(d[57]), "+f"(d[58]), "+f"(d[59]), "+f"(d[60]), "+f"(d[61]), "+f"(d[62]), "+f"(d[63])
        : "l"(da), "l"(db));
}
__device__ __forceinline__ void wgmma_n176_z(float (&d)[88], uint64_t da, uint64_t db) {
    asm volatile("{\n.reg .pred p;\nsetp.ne.b32 p, 0, 0;\n"
        "wgmma.mma_async.sync.aligned.m64n176k16.f32.bf16.bf16 {"
        "%0, %1, %2, %3, %4, %5, %6, %7, %8, %9, %10, %11, %12, %13, %14, %15, "
        "%16, %17, %18, %19, %20, %21, %22, %23, %24, %25, %26, %27, %28, %29, %30, %31, "
        "%32, %33, %34, %35, %36, %37, %38, %39, %40, %41, %42, %43, %44, %45, %46, %47, "
        "%48, %49, %50, %51, %52, %53, %54, %55, %56, %57, %58, %59, %60, %61, %62, %63, "
        "%64, %65, %66, %67, %68, %69, %70, %71, %72, %73, %74, %75, %76, %77, %78, %79, "
        "%80, %81, %82, %83, %84, %85, %86, %87"
        "}, %88, %89, p, 1, 1, 0, 1;\n}\n"
        : "=f"(d[0]), "=f"(d[1]), "=f"(d[2]), "=f"(d[3]), "=f"(d[4]), "=f"(d[5]), "=f"(d[6]), "=f"(d[7]),
          "=f"(d[8]), "=f"(d[9]), "=f"(d[10]), "=f"(d[11]), "=f"(d[12]), "=f"(d[13]), "=f"(d[14]), "=f"(d[15]),
          "=f"(d[16]), "=f"(d[17]), "=f"(d[18]), "=f"(d[19]), "=f"(d[20]), "=f"(d[21]), "=f"(d[22]), "=f"(d[23]),
          "=f"(d[24]), "=f"(d[25]), "=f"(d[26]), "=f"(d[27]), "=f"(d[28]), "=f"(d[29]), "=f"(d[30]), "=f"(d[31]),
          "=f"(d[32]), "=f"(d[33]), "=f"(d[34]), "=f"(d[35]), "=f"(d[36]), "=f"(d[37]), "=f"(d[38]), "=f"(d[39]),
          "=f"(d[40]), "=f"(d[41]), "=f"(d[42]), "=f"(d[43]), "=f"(d[44]), "=f"(d[45]), "=f"(d[46]), "=f"(d[47]),
          "=f"(d[48]), "=f"(d[49]), "=f"(d[50]), "=f"(d[51]), "=f"(d[52]), "=f"(d[53]), "=f"(d[54]), "=f"(d[55]),
          "=f"(d[56]), "=f"(d[57]), "=f"(d[58]), "=f"(d[59]), "=f"(d[60]), "=f"(d[61]), "=f"(d[62]), "=f"(d[63]),
          "=f"(d[64]), "=f"(d[65]), "=f"(d[66]), "=f"(d[67]), "=f"(d[68]), "=f"(d[69]), "=f"(d[70]), "=f"(d[71]),
          "=f"(d[72]), "=f"(d[73]), "=f"(d[74]), "=f"(d[75]), "=f"(d[76]), "=f"(d[77]), "=f"(d[78]), "=f"(d[79]),
          "=f"(d[80]), "=f"(d[81]), "=f"(d[82]), "=f"(d[83]), "=f"(d[84]), "=f"(d[85]), "=f"(d[86]), "=f"(d[87])
        : "l"(da), "l"(db));
}
__device__ __forceinline__ void wgmma_n176(float (&d)[88], uint64_t da, uint64_t db) {
    asm volatile("{\n.reg .pred p;\nsetp.eq.b32 p, 0, 0;\n"
        "wgmma.mma_async.sync.aligned.m64n176k16.f32.bf16.bf16 {"
        "%0, %1, %2, %3, %4, %5, %6, %7, %8, %9, %10, %11, %12, %13, %14, %15, "
        "%16, %17, %18, %19, %20, %21, %22, %23, %24, %25, %26, %27, %28, %29, %30, %31, "
        "%32, %33, %34, %35, %36, %37, %38, %39, %40, %41, %42, %43, %44, %45, %46, %47, "
        "%48, %49, %50, %51, %52, %53, %54, %55, %56, %57, %58, %59, %60, %61, %62, %63, "
        "%64, %65, %66, %67, %68, %69, %70, %71, %72, %73, %74, %75, %76, %77, %78, %79, "
        "%80, %81, %82, %83, %84, %85, %86, %87"
        "}, %88, %89, p, 1, 1, 0, 1;\n}\n"
        : "+f"(d[0]), "+f"(d[1]), "+f"(d[2]), "+f"(d[3]), "+f"(d[4]), "+f"(d[5]), "+f"(d[6]), "+f"(d[7]),
          "+f"(d[8]), "+f"(d[9]), "+f"(d[10]), "+f"(d[11]), "+f"(d[12]), "+f"(d[13]), "+f"(d[14]), "+f"(d[15]),
          "+f"(d[16]), "+f"(d[17]), "+f"(d[18]), "+f"(d[19]), "+f"(d[20]), "+f"(d[21]), "+f"(d[22]), "+f"(d[23]),
          "+f"(d[24]), "+f"(d[25]), "+f"(d[26]), "+f"(d[27]), "+f"(d[28]), "+f"(d[29]), "+f"(d[30]), "+f"(d[31]),
          "+f"(d[32]), "+f"(d[33]), "+f"(d[34]), "+f"(d[35]), "+f"(d[36]), "+f"(d[37]), "+f"(d[38]), "+f"(d[39]),
          "+f"(d[40]), "+f"(d[41]), "+f"(d[42]), "+f"(d[43]), "+f"(d[44]), "+f"(d[45]), "+f"(d[46]), "+f"(d[47]),
          "+f"(d[48]), "+f"(d[49]), "+f"(d[50]), "+f"(d[51]), "+f"(d[52]), "+f"(d[53]), "+f"(d[54]), "+f"(d[55]),
          "+f"(d[56]), "+f"(d[57]), "+f"(d[58]), "+f"(d[59]), "+f"(d[60]), "+f"(d[61]), "+f"(d[62]), "+f"(d[63]),
          "+f"(d[64]), "+f"(d[65]), "+f"(d[66]), "+f"(d[67]), "+f"(d[68]), "+f"(d[69]), "+f"(d[70]), "+f"(d[71]),
          "+f"(d[72]), "+f"(d[73]), "+f"(d[74]), "+f"(d[75]), "+f"(d[76]), "+f"(d[77]), "+f"(d[78]), "+f"(d[79]),
          "+f"(d[80]), "+f"(d[81]), "+f"(d[82]), "+f"(d[83]), "+f"(d[84]), "+f"(d[85]), "+f"(d[86]), "+f"(d[87])
        : "l"(da), "l"(db));
}
__device__ __forceinline__ void wgmma_n256_z(float (&d)[128], uint64_t da, uint64_t db) {
    asm volatile("{\n.reg .pred p;\nsetp.ne.b32 p, 0, 0;\n"
        "wgmma.mma_async.sync.aligned.m64n256k16.f32.bf16.bf16 {"
        "%0, %1, %2, %3, %4, %5, %6, %7, %8, %9, %10, %11, %12, %13, %14, %15, "
        "%16, %17, %18, %19, %20, %21, %22, %23, %24, %25, %26, %27, %28, %29, %30, %31, "
        "%32, %33, %34, %35, %36, %37, %38, %39, %40, %41, %42, %43, %44, %45, %46, %47, "
        "%48, %49, %50, %51, %52, %53, %54, %55, %56, %57, %58, %59, %60, %61, %62, %63, "
        "%64, %65, %66, %67, %68, %69, %70, %71, %72, %73, %74, %75, %76, %77, %78, %79, "
        "%80, %81, %82, %83, %84, %85, %86, %87, %88, %89, %90, %91, %92, %93, %94, %95, "
        "%96, %97, %98, %99, %100, %101, %102, %103, %104, %105, %106, %107, %108, %109, %110, %111, "
        "%112, %113, %114, %115, %116, %117, %118, %119, %120, %121, %122, %123, %124, %125, %126, %127"
        "}, %128, %129, p, 1, 1, 0, 1;\n}\n"
        : "=f"(d[0]), "=f"(d[1]), "=f"(d[2]), "=f"(d[3]), "=f"(d[4]), "=f"(d[5]), "=f"(d[6]), "=f"(d[7]),
          "=f"(d[8]), "=f"(d[9]), "=f"(d[10]), "=f"(d[11]), "=f"(d[12]), "=f"(d[13]), "=f"(d[14]), "=f"(d[15]),
          "=f"(d[16]), "=f"(d[17]), "=f"(d[18]), "=f"(d[19]), "=f"(d[20]), "=f"(d[21]), "=f"(d[22]), "=f"(d[23]),
          "=f"(d[24]), "=f"(d[25]), "=f"(d[26]), "=f"(d[27]), "=f"(d[28]), "=f"(d[29]), "=f"(d[30]), "=f"(d[31]),
          "=f"(d[32]), "=f"(d[33]), "=f"(d[34]), "=f"(d[35]), "=f"(d[36]), "=f"(d[37]), "=f"(d[38]), "=f"(d[39]),
          "=f"(d[40]), "=f"(d[41]), "=f"(d[42]), "=f"(d[43]), "=f"(d[44]), "=f"(d[45]), "=f"(d[46]), "=f"(d[47]),
          "=f"(d[48]), "=f"(d[49]), "=f"(d[50]), "=f"(d[51]), "=f"(d[52]), "=f"(d[53]), "=f"(d[54]), "=f"(d[55]),
          "=f"(d[56]), "=f"(d[57]), "=f"(d[58]), "=f"(d[59]), "=f"(d[60]), "=f"(d[61]), "=f"(d[62]), "=f"(d[63]),
          "=f"(d[64]), "=f"(d[65]), "=f"(d[66]), "=f"(d[67]), "=f"(d[68]), "=f"(d[69]), "=f"(d[70]), "=f"(d[71]),
          "=f"(d[72]), "=f"(d[73]), "=f"(d[74]), "=f"(d[75]), "=f"(d[76]), "=f"(d[77]), "=f"(d[78]), "=f"(d[79]),
          "=f"(d[80]), "=f"(d[81]), "=f"(d[82]), "=f"(d[83]), "=f"(d[84]), "=f"(d[85]), "=f"(d[86]), "=f"(d[87]),
          "=f"(d[88]), "=f"(d[89]), "=f"(d[90]), "=f"(d[91]), "=f"(d[92]), "=f"(d[93]), "=f"(d[94]), "=f"(d[95]),
          "=f"(d[96]), "=f"(d[97]), "=f"(d[98]), "=f"(d[99]), "=f"(d[100]), "=f"(d[101]), "=f"(d[102]), "=f"(d[103]),
          "=f"(d[104]), "=f"(d[105]), "=f"(d[106]), "=f"(d[107]), "=f"(d[108]), "=f"(d[109]), "=f"(d[110]), "=f"(d[111]),
          "=f"(d[112]), "=f"(d[113]), "=f"(d[114]), "=f"(d[115]), "=f"(d[116]), "=f"(d[117]), "=f"(d[118]), "=f"(d[119]),
          "=f"(d[120]), "=f"(d[121]), "=f"(d[122]), "=f"(d[123]), "=f"(d[124]), "=f"(d[125]), "=f"(d[126]), "=f"(d[127])
        : "l"(da), "l"(db));
}
__device__ __forceinline__ void wgmma_n256(float (&d)[128], uint64_t da, uint64_t db) {
    asm volatile("{\n.reg .pred p;\nsetp.eq.b32 p, 0, 0;\n"
        "wgmma.mma_async.sync.aligned.m64n256k16.f32.bf16.bf16 {"
        "%0, %1, %2, %3, %4, %5, %6, %7, %8, %9, %10, %11, %12, %13, %14, %15, "
        "%16, %17, %18, %19, %20, %21, %22, %23, %24, %25, %26, %27, %28, %29, %30, %31, "
        "%32, %33, %34, %35, %36, %37, %38, %39, %40, %41, %42, %43, %44, %45, %46, %47, "
        "%48, %49, %50, %51, %52, %53, %54, %55, %56, %57, %58, %59, %60, %61, %62, %63, "
        "%64, %65, %66, %67, %68, %69, %70, %71, %72, %73, %74, %75, %76, %77, %78, %79, "
        "%80, %81, %82, %83, %84, %85, %86, %87, %88, %89, %90, %91, %92, %93, %94, %95, "
        "%96, %97, %98, %99, %100, %101, %102, %103, %104, %105, %106, %107, %108, %109, %110, %111, "
        "%112, %113, %114, %115, %116, %117, %118, %119, %120, %121, %122, %123, %124, %125, %126, %127"
        "}, %128, %129, p, 1, 1, 0, 1;\n}\n"
        : "+f"(d[0]), "+f"(d[1]), "+f"(d[2]), "+f"(d[3]), "+f"(d[4]), "+f"(d[5]), "+f"(d[6]), "+f"(d[7]),
          "+f"(d[8]), "+f"(d[9]), "+f"(d[10]), "+f"(d[11]), "+f"(d[12]), "+f"(d[13]), "+f"(d[14]), "+f"(d[15]),
          "+f"(d[16]), "+f"(d[17]), "+f"(d[18]), "+f"(d[19]), "+f"(d[20]), "+f"(d[21]), "+f"(d[22]), "+f"(d[23]),
          "+f"(d[24]), "+f"(d[25]), "+f"(d[26]), "+f"(d[27]), "+f"(d[28]), "+f"(d[29]), "+f"(d[30]), "+f"(d[31]),
          "+f"(d[32]), "+f"(d[33]), "+f"(d[34]), "+f"(d[35]), "+f"(d[36]), "+f"(d[37]), "+f"(d[38]), "+f"(d[39]),
          "+f"(d[40]), "+f"(d[41]), "+f"(d[42]), "+f"(d[43]), "+f"(d[44]), "+f"(d[45]), "+f"(d[46]), "+f"(d[47]),
          "+f"(d[48]), "+f"(d[49]), "+f"(d[50]), "+f"(d[51]), "+f"(d[52]), "+f"(d[53]), "+f"(d[54]), "+f"(d[55]),
          "+f"(d[56]), "+f"(d[57]), "+f"(d[58]), "+f"(d[59]), "+f"(d[60]), "+f"(d[61]), "+f"(d[62]), "+f"(d[63]),
          "+f"(d[64]), "+f"(d[65]), "+f"(d[66]), "+f"(d[67]), "+f"(d[68]), "+f"(d[69]), "+f"(d[70]), "+f"(d[71]),
          "+f"(d[72]), "+f"(d[73]), "+f"(d[74]), "+f"(d[75]), "+f"(d[76]), "+f"(d[77]), "+f"(d[78]), "+f"(d[79]),
          "+f"(d[80]), "+f"(d[81]), "+f"(d[82]), "+f"(d[83]), "+f"(d[84]), "+f"(d[85]), "+f"(d[86]), "+f"(d[87]),
          "+f"(d[88]), "+f"(d[89]), "+f"(d[90]), "+f"(d[91]), "+f"(d[92]), "+f"(d[93]), "+f"(d[94]), "+f"(d[95]),
          "+f"(d[96]), "+f"(d[97]), "+f"(d[98]), "+f"(d[99]), "+f"(d[100]), "+f"(d[101]), "+f"(d[102]), "+f"(d[103]),
          "+f"(d[104]), "+f"(d[105]), "+f"(d[106]), "+f"(d[107]), "+f"(d[108]), "+f"(d[109]), "+f"(d[110]), "+f"(d[111]),
          "+f"(d[112]), "+f"(d[113]), "+f"(d[114]), "+f"(d[115]), "+f"(d[116]), "+f"(d[117]), "+f"(d[118]), "+f"(d[119]),
          "+f"(d[120]), "+f"(d[121]), "+f"(d[122]), "+f"(d[123]), "+f"(d[124]), "+f"(d[125]), "+f"(d[126]), "+f"(d[127])
        : "l"(da), "l"(db));
}

struct Idx {
    uint32_t lane, warp, w4, q4, g8, prow, pan;
    __device__ __forceinline__ Idx() {
        uint32_t t; asm volatile("mov.u32 %0, %%tid.x;" : "=r"(t));
        lane = t & 31; warp = t >> 5; w4 = warp & 3; q4 = lane & 3; g8 = lane >> 2;
        prow = w4 * 16 + ((lane >> 3) & 1) * 8 + (lane & 7);
        pan = prow * 128 + (((lane >> 4) ^ (lane & 7)) << 4);
    }
};
#define IDX() const Idx ix; const uint32_t lane = ix.lane, warp = ix.warp, w4 = ix.w4, q4 = ix.q4, g8 = ix.g8, prow = ix.prow, pan_addr = ix.pan; \
    (void)lane; (void)warp; (void)w4; (void)q4; (void)g8; (void)prow; (void)pan_addr;

__device__ __forceinline__ int kof(int t, int sh, int j) {
    const int q = (t >> sh) - 1;
    return ((q < 0 ? j : q + (q >= j)) << 7) + ((t & ((1 << sh) - 1)) << (7 - sh));
}
constexpr int HC0 = 8 * 48, HC3 = HC0 + 3072;
__device__ __forceinline__ int hcol(int p, int j) { return HC0 + p * 1024 + j * 128; }
#define SCHED_FENCE(k) do { if ((FENCES >> (k)) & 1) asm volatile("{\n.reg .pred p;\nsetp.ne.u32 p, %0, %1;\n@p bra.uni S_SKIP;\ntrap;\nS_SKIP:\n}" :: "r"(sb), "n"(0xffffff00u + (k))); } while (0)

struct Ring {
    uint32_t slot, par;
    __device__ __forceinline__ void next() { if (++slot == NSLOT) { slot = 0; par ^= 1; } }
    __device__ __forceinline__ void skip(uint32_t n) { slot += n; if (slot >= NSLOT) { slot -= NSLOT; par ^= 1; } }
};
__device__ __forceinline__ uint32_t BAR_FULL(uint32_t sb, uint32_t s) { return sb + OFF_BAR + 8 * s; }
constexpr uint32_t AF_REL = 48;
__device__ __forceinline__ uint32_t BAR_EMPTY(uint32_t sb, uint32_t s) { return sb + OFF_BAR + 96 + 8 * s; }
__device__ __forceinline__ uint32_t BAR_SFULL(uint32_t sb, uint32_t i) { return sb + OFF_BAR + 152 + 8 * i; }
__device__ __forceinline__ uint32_t BAR_SREADY(uint32_t sb, uint32_t i) { return sb + OFF_BAR + 184 + 8 * i; }
__device__ __forceinline__ uint32_t BAR_ONE(uint32_t sb, uint32_t i) { return sb + OFF_BAR + 216 + 8 * i; }
enum { EV_WIN, EV_WIN1, EV_WIN2, EV_WIN3, EV_P0, EV_GA, EV_GB, EV_LN2, EV_LAG0, EV_LAG1, EV_LAG2, EV_LAG3, EV_LAG4, EV_LAG5, EV_OWN, EV_OWN1, EV_P3, EV_P31, EV_KV, EV_GO, EV_PAR, EV_AGO, EV_AGO1, EV_AGO2, EV_H0, EV_H1, EV_H2, EV_H3, EV_X1, EV_X11, EV_X1S, EV_X1S1, EV_COUNT };
constexpr int NB_TAIL = 4;

struct Rel {
    uint32_t base; bool sig;
    __device__ __forceinline__ Rel(uint32_t sb, uint32_t tw) {
        uint32_t a; asm("mapa.shared::cluster.u32 %0, %1, %2;" : "=r"(a) : "r"(BAR_EMPTY(sb, 0)), "r"((tw >> 5) & 1));
        base = __shfl_sync(0xffffffffu, a, 0); sig = (tw & ~32u) == 0;
    }
    __device__ __forceinline__ void operator()(uint32_t slot) const {
        if (sig) asm volatile("mbarrier.arrive.shared::cluster.b64 _, [%0];" :: "r"(base + 8 * slot) : "memory");
    }
};
struct LnRow { float rs0, nm0, rs1, nm1; };
struct Pipe {
    Rel rel; uint32_t p1, p2;
    __device__ __forceinline__ Pipe(uint32_t sb, uint32_t tw, uint32_t first) : rel(sb, tw), p1(first), p2(NSLOT) {}
    template <bool TWO> __device__ __forceinline__ void acquire(uint32_t sb, uint32_t wg, const Ring& r) {
        const uint32_t b0 = BAR_FULL(sb, r.slot), b1 = b0 + (wg ? 0 : AF_REL);
        const bool ready = TWO ? mbar_test2(b0, b1, r.par) : mbar_test(b0, r.par);
        wg_wait<1>();
        rel(p2);
        if (!ready) { if (TWO) mbar_wait2(b0, b1, r.par); else mbar_wait(b0, r.par); }
    }
    __device__ __forceinline__ void issued(uint32_t slot) { p2 = p1; p1 = slot; }
    __device__ __forceinline__ void drain1() { wg_wait<1>(); rel(p2); p2 = NSLOT; }
    __device__ __forceinline__ void drain0() { wg_wait<0>(); rel(p1); p1 = NSLOT; }
    template <bool TWO, int LG, int PRE, class Step> __device__ __forceinline__ void hold(uint32_t sb, Ring& r, uint32_t lag_bar, Step step) {
        drain1(); drain0();
        Ring q = r;
        auto landed = [&] { if (TWO) mbar_wait2(BAR_FULL(sb, q.slot), BAR_FULL(sb, q.slot) + AF_REL, q.par); else mbar_wait(BAR_FULL(sb, q.slot), q.par); q.next(); };
#pragma unroll 1
        for (int i = 0; i < PRE; ++i) landed();
        mbar_wait(lag_bar, 0);
#pragma unroll 1
        for (int i = 0; i < LG; ++i) {
            if (PRE < LG && i >= PRE) landed();
            step(r.slot);
            wg_wait<2>(); rel(p2); p2 = p1; p1 = r.slot;
            if (++r.slot == NSLOT) r.slot = 0;
        }
        r.par = q.par;
    }
};
template <bool TWO, bool FIRST, int NA, int NB>
__device__ __forceinline__ void step32(float (&aa)[NA], float (&ab)[NB], uint32_t sb, uint32_t wg, uint32_t slot, int own) {
    const uint32_t st = d16(sb) + slot * (SLOT >> 4);
    const uint32_t alo = own >= 0 ? d16(sb) + OFF_STG / 16 + wg * 1024 + (own >> 1) * 512 + (own & 1) * 4 : st + wg * 256;
    const uint32_t ahi = own >= 0 ? (1024 >> 4) | (1u << 30) : (512 >> 4) | (2u << 30);
    wg_fence();
#pragma unroll
    for (int k = 0; k < 2; ++k) {
        const uint64_t da = ((uint64_t)ahi << 32) | (alo + k * 2 + 0x10000);
        if constexpr (NA == 88) {
            const uint64_t d0 = mk_desc(st, 8192 + k * 2048, 8192, 1024, 1), d1 = mk_desc(st, 12288 + k * 2048, 8192, 1024, 1);
            if (FIRST && k == 0) { wgmma_n176_z(aa, da, d0); wgmma_n176_z(ab, da, d1); }
            else { wgmma_n176(aa, da, d0); wgmma_n176(ab, da, d1); }
        } else {
            const uint64_t d0 = mk_desc(st, 8192 + k * 2048, 4096, 1024, 1), d1 = mk_desc(st, 24576 + k * 2048, 4096, 1024, 1);
            if (FIRST && k == 0) { wgmma_n256_z(aa, da, d0); if constexpr (TWO) wgmma_n128_z(ab, da, d1); }
            else { wgmma_n256(aa, da, d0); if constexpr (TWO) wgmma_n128(ab, da, d1); }
        }
    }
    wg_commit();
}
template <bool TWO, int LG, int NA, int NB, class Tail>
__device__ __forceinline__ void mainloop32(float (&aa)[NA], float (&ab)[NB], uint32_t sb, uint32_t wg, uint32_t tw, Ring& r, uint32_t lag_ev, int g0, Tail tail) {
    mbar_wait(BAR_FULL(sb, r.slot), r.par);
    step32<TWO, true>(aa, ab, sb, wg, r.slot, TWO ? 0 : -1);
    TS(g0, 0);
    Pipe pp(sb, tw, r.slot);
    r.next();
    const int end = wg ? 32 : 32 - LG;
#pragma unroll 1
    for (int it = 1; it < end; ++it) {
        pp.acquire<TWO>(sb, wg, r);
        step32<TWO, false>(aa, ab, sb, wg, r.slot, TWO && it < 4 ? it : -1);
        pp.issued(r.slot);
        TS(g0 + it, 0);
        r.next();
    }
    if (wg == 0) pp.hold<TWO, LG, LG>(sb, r, BAR_ONE(sb, lag_ev), [&](uint32_t slot) { step32<TWO, false>(aa, ab, sb, 0, slot, -1); });
    if (LAGSIG == 2 && wg == 1 && tw == 0) mbar_arrive(BAR_ONE(sb, lag_ev));
    pp.drain1();
    if (LAGSIG == 1 && wg == 1 && tw == 0) mbar_arrive(BAR_ONE(sb, lag_ev));
    tail();
    pp.drain0();
    TS(g0 + 31, 1);
}
template <bool FIRST>
__device__ __forceinline__ void step64(float (&acc)[64], uint32_t sb, uint32_t wg, uint32_t slot, int own) {
    const uint32_t sbb = d16(sb) + slot * (SLOT >> 4), sa = own >= 0 ? d16(sb) + OFF_STG / 16 + wg * 1024 + own * 512 : sbb + wg * 512;
    wg_fence();
#pragma unroll
    for (int k = 0; k < 4; ++k) {
        const uint64_t da = mk_desc(sa, k * 32, 16, 1024, 1), db = mk_desc(sbb, 16384 + k * 2048, 8192, 1024, 1);
        if (FIRST && k == 0) wgmma_n128_z(acc, da, db); else wgmma_n128(acc, da, db);
    }
    wg_commit();
}
template <bool OWN, int NST, int LG, int MID, class Mid>
__device__ __forceinline__ void mainloop64(float (&acc)[64], uint32_t sb, uint32_t wg, uint32_t tw, Ring& r, Mid mid) {
    constexpr int G0 = OWN ? 32 : 144, SG = OWN ? SIGW : SIGD; (void)G0;
    const uint32_t lag_bar = BAR_ONE(sb, OWN ? EV_LAG4 : EV_LAG5);
    mbar_wait(BAR_FULL(sb, r.slot), r.par);
    step64<true>(acc, sb, wg, r.slot, OWN ? 0 : -1);
    TS(G0, 0);
    Pipe pp(sb, tw, r.slot);
    r.next();
    if (OWN) {
        mbar_wait(BAR_FULL(sb, r.slot), r.par);
        step64<false>(acc, sb, wg, r.slot, 1);
        TS(G0 + 1, 0);
        pp.drain0();
        TS(G0 + 1, 1);
        pp.rel(r.slot);
        if (tw == 0) mbar_arrive(BAR_ONE(sb, EV_OWN + wg));
        r.next();
    }
    int it = OWN ? 2 : 1;
    auto run = [&](int end) {
#pragma unroll 1
        do {
            if (SG > 2 && it == NST + 2 - SG && tw == 0) mbar_arrive(lag_bar);
            pp.acquire<OWN>(sb, wg, r);
            step64<false>(acc, sb, wg, r.slot, -1);
            pp.issued(r.slot);
            TS(G0 + it, 0);
            r.next();
        } while (++it < end);
    };
    run(wg ? MID : NST - LG);
    mid();
    if (wg) run(NST);
    else pp.hold<OWN, LG, (SG > 2 ? 2 : LG)>(sb, r, lag_bar, [&](uint32_t slot) { step64<false>(acc, sb, 0, slot, -1); });
    if (SG == 2 && wg == 1 && tw == 0) mbar_arrive(lag_bar);
    pp.drain1();
    if (SG == 1 && wg == 1 && tw == 0) mbar_arrive(lag_bar);
    pp.drain0();
    TS(G0 + NST - 1, 1);
}

struct RowAcc {
    float sm[4] = {0.f, 0.f, 0.f, 0.f}, sq[4] = {0.f, 0.f, 0.f, 0.f};
    __device__ __forceinline__ void add(int e, float x) { sm[e & 3] += x; sq[e & 3] = fmaf(x, x, sq[e & 3]); }
    __device__ __forceinline__ void publish(uint4* dst, uint32_t q4, uint32_t ep) const {
        const float s0 = sm[0] + sm[1], s1 = sm[2] + sm[3], q0 = sq[0] + sq[1], q1 = sq[2] + sq[3];
        const bool od = q4 & 1;
        float sv = (od ? s1 : s0) + __shfl_xor_sync(0xffffffffu, od ? s0 : s1, 1), qv = (od ? q1 : q0) + __shfl_xor_sync(0xffffffffu, od ? q0 : q1, 1);
        sv += __shfl_xor_sync(0xffffffffu, sv, 2); qv += __shfl_xor_sync(0xffffffffu, qv, 2);
        if (q4 < 2) st_pkt16(dst + q4 * 8, 0, __float_as_uint(sv), __float_as_uint(qv), ep);
    }
};
__device__ __forceinline__ LnRow merge_stats(const uint4* src, uint32_t stride, uint32_t q4, uint32_t ep, uint32_t sb, uint32_t sig) {
    uint4 t[4];
    uint32_t n = 0;
    while (true) {
#pragma unroll
        for (int i = 0; i < 4; ++i) t[i] = ld_pkt16(src + (q4 * 2 + (i >> 1)) * stride + (i & 1) * 8);
        if (sig) { mbar_arrive(sig); sig = 0; }
        const bool ok_ = __all_sync(0xffffffffu, t[0].w == ep && t[1].w == ep && t[2].w == ep && t[3].w == ep);
        if (stride == 512 && n < 4) CS(14 + n);
        if (ok_) break;
        SPIN_GUARD(n);
    }
    float v[4];
#pragma unroll
    for (int h = 0; h < 2; ++h) { v[h] = __uint_as_float(t[h].y) + __uint_as_float(t[2 + h].y); v[2 + h] = __uint_as_float(t[h].z) + __uint_as_float(t[2 + h].z); }
#pragma unroll
    for (int o = 1; o < 4; o <<= 1)
#pragma unroll
        for (int i = 0; i < 4; ++i) v[i] += __shfl_xor_sync(0xffffffffu, v[i], o);
    const float m0 = v[0] * (1.f / D_), m1 = v[1] * (1.f / D_);
    const float r0 = rsqrtf(fmaxf(fmaf(-m0, m0, v[2] * (1.f / D_)), 0.f) + 1e-5f), r1 = rsqrtf(fmaxf(fmaf(-m1, m1, v[3] * (1.f / D_)), 0.f) + 1e-5f);
    return LnRow{r0, -m0 * r0, r1, -m1 * r1};
}
struct Stg {
    uint32_t b, par;
    __device__ __forceinline__ uint32_t acquire2(uint32_t sb, uint32_t wg) {
        mbar_wait(BAR_SREADY(sb, wg * 2), par & 1);
        mbar_wait(BAR_SREADY(sb, wg * 2 + 1), (par >> 1) & 1);
        par ^= 3;
        return sb + OFF_STG + wg * 16384;
    }
    __device__ __forceinline__ void publish(uint32_t sb, uint32_t wg, uint32_t lane) {
        fence_async_smem();
        __syncwarp();
        if (lane == 0) mbar_arrive(BAR_SFULL(sb, wg * 2 + b));
        b ^= 1;
    }
};

struct LnPar {
    uint4 p[8];
    __device__ __forceinline__ void load(uint32_t sb, uint32_t q4) {
#pragma unroll
        for (int i = 0; i < 8; ++i) p[i] = lds128(sb + OFF_PAR + i * 64 + q4 * 16);
    }
};
__device__ __forceinline__ void ln_norm(uint32_t (&xn)[32], const float (&x)[64], const LnRow& n) {
#pragma unroll
    for (int e = 0; e < 32; ++e) {
        const float rs = (e & 1) ? n.rs1 : n.rs0, nm = (e & 1) ? n.nm1 : n.nm0;
        xn[e] = pack2(fmaf(x[2 * e], rs, nm), fmaf(x[2 * e + 1], rs, nm));
    }
}
__device__ __forceinline__ void ln_emit(const uint32_t (&xr)[32], const LnPar& lp, uint32_t sb, uint32_t wg, const Idx& ix) {
#pragma unroll
    for (int i = 0; i < 8; ++i)
        stsm4(sb + OFF_STG + wg * 16384 + (i >> 2) * 8192 + (ix.pan ^ ((i & 3) << 5)), hfma2_bf16(xr[4 * i], lp.p[i].z, lp.p[i].x), hfma2_bf16(xr[4 * i + 1], lp.p[i].z, lp.p[i].x),
              hfma2_bf16(xr[4 * i + 2], lp.p[i].w, lp.p[i].y), hfma2_bf16(xr[4 * i + 3], lp.p[i].w, lp.p[i].y));
    fence_async_smem();
    __syncwarp();
    if (ix.lane < 2) mbar_arrive(BAR_SFULL(sb, wg * 2 + ix.lane));
    bar_sync(1 + wg, 128);
}
__device__ __forceinline__ void load_res(float (&xf)[64], float (&gf)[32], uint32_t buf, uint32_t tab) {
    IDX();
    uint32_t xr[32], gt[16];
#pragma unroll
    for (int i = 0; i < 8; ++i) ldsm4(buf + (i >> 2) * 8192 + (pan_addr ^ ((i & 3) << 5)), xr[4 * i], xr[4 * i + 1], xr[4 * i + 2], xr[4 * i + 3]);
#pragma unroll
    for (int cg = 0; cg < 16; ++cg) gt[cg] = lds32(tab + cg * 16 + q4 * 4);
#pragma unroll
    for (int i = 0; i < 32; ++i) unpack2(xr[i], xf[2 * i], xf[2 * i + 1]);
#pragma unroll
    for (int i = 0; i < 16; ++i) unpack2(gt[i], gf[2 * i], gf[2 * i + 1]);
}
__device__ __forceinline__ void fetch_halo(uint4* src, bool first, uint32_t sb, uint32_t W, uint32_t lane) {
    mbar_wait(BAR_ONE(sb, EV_KV), 0);
    mbar_wait2(BAR_SREADY(sb, 0), BAR_SREADY(sb, 1), 1);
    uint4 hv[8];
    uint32_t n = 0;
    while (true) {
        bool ok = true;
#pragma unroll
        for (int i = 0; i < 8; ++i) { hv[i] = first ? make_uint4(0, 0, 0, 0) : ld_pkt16(src + i * 32); ok = ok && hv[i].x != 0; }
        if (first || __all_sync(0xffffffffu, ok)) break;
        SPIN_GUARD(n);
    }
#pragma unroll
    for (int i = 0; i < 8; ++i) stsm4(sb + OFF_STG + W * 2048 + (i >> 2) * 8192 + (i & 3) * 512 + lane * 16, hv[i].x, hv[i].y, hv[i].z, hv[i].w);
    bar_arrive(NB_TAIL + W, 64);
    if (!first) {
#pragma unroll
        for (int i = 0; i < 8; ++i) src[i * 32] = make_uint4(0, 0, 0, 0);
    }
}

template <int OG, int OU, int LEN>
__device__ __forceinline__ void glu_panel(const float (&g)[LEN], const float (&u)[LEN], uint32_t buf, uint32_t bar) {
    IDX();
    constexpr int NR = LEN - OU < 32 ? (LEN - OU) / 2 : 16;
    uint32_t r[NR];
#pragma unroll
    for (int i = 0; i < NR; ++i) r[i] = pack2(glu_half(g[OG + 2 * i], u[OU + 2 * i]), glu_half(g[OG + 2 * i + 1], u[OU + 2 * i + 1]));
#pragma unroll
    for (int jn = 0; jn < NR / 2; jn += 2) stsm4(buf + (pan_addr ^ (jn << 4)), r[jn * 2], r[jn * 2 + 1], r[jn * 2 + 2], r[jn * 2 + 3]);
    fence_async_smem();
    __syncwarp();
    if (lane == 0) mbar_arrive(bar);
}

template <int NP>
__device__ __forceinline__ void passes128(uint32_t sb, uint32_t wg, uint32_t tw, Ring& r, Stg& stg) {
#pragma unroll 1
    for (int p = 0; p < NP; ++p) {
        float b256[128], none[1];
        mainloop32<false, LAGS>(b256, none, sb, wg, tw, r, EV_LAG2 + p, 80 + 32 * (p & 1), [&] { stg.acquire2(sb, wg); });
        if (threadIdx.x == 0) { TL(29 + 2 * p); TC(114 + 2 * p); }
        if (threadIdx.x == 128) TL(53 + 2 * (p & 1));
        glu_panel<0, 32>(b256, b256, sb + OFF_STG + wg * 16384, BAR_SFULL(sb, wg * 2));
        glu_panel<64, 96>(b256, b256, sb + OFF_STG + wg * 16384 + 8192, BAR_SFULL(sb, wg * 2 + 1));
        if (threadIdx.x == 0) { TL(30 + 2 * p); TC(115 + 2 * p); }
        if (threadIdx.x == 128) TL(54 + 2 * (p & 1));
    }
}

__global__ void __launch_bounds__(384, 1)
fused_block_kernel(const __grid_constant__ Ptrs pt, const __grid_constant__ Maps mp) {
    uint32_t* const g_flags = pt.mail->flags;
    uint2* const g_mod = pt.mail->mod;
    uint4* const g_st1 = pt.mail->st1;
    uint32_t* const g_par2 = pt.mail->par2;
    uint4* const g_halo = pt.mail->halo;
    const __nv_bfloat16* __restrict__ cvec = pt.c;
    if (threadIdx.x == 224) { prefetch_map(&mp.wm8); prefetch_map(&mp.x); }
    extern __shared__ __align__(1024) uint8_t smem[];
    const uint32_t sb = smem_u32(smem);
    const uint32_t tid = threadIdx.x, tw = tid & 127, lane = tid & 31;
    const uint32_t warp = __shfl_sync(0xffffffffu, tid >> 5, 0), wg = warp >> 2;
    uint32_t rank; asm("mov.u32 %0, %%cluster_ctarank;" : "=r"(rank));
    rank = __shfl_sync(0xffffffffu, rank, 0);
    uint32_t ep;
    uint32_t smid; asm volatile("mov.u32 %0, %%smid;" : "=r"(smid));
    const int c = __shfl_sync(0xffffffffu, smid >> 1, 0);
    const int c7 = ((c - 32) * 37) >> 8;
    const int grp = c < 32 ? c & 7 : c < 60 ? c - 31 - 7 * c7 : c < 62 ? -1 : 0;
    const int j = c < 32 ? c >> 3 : c < 60 ? 4 + c7 : c < 62 ? (c - 60) * 2 + rank : c - 58;
    const bool aux = grp < 0;
    const int m = grp * 2 + rank;
    uint4* const g_st2 = g_halo + (m > 0 ? (m - 1) * 8 * 512 : 128);

    bool cluster_arrive_early = false;
    if (wg < 2) {
      ep = flag_get(g_flags + FL_DONE);
      uint16_t cw[8];
      {
          const __nv_bfloat16* cp = cvec + ((tw >> 5) * 32 + (tw & 3) * 2) * 8 + (lane >> 2);
#pragma unroll
          for (int i = 0; i < 8; ++i) asm volatile("ld.global.nc.u16 %0, [%1];" : "=h"(cw[i]) : "l"(cp + (i >> 1) * 64 + (i & 1) * 8));
      }
      asm volatile("setmaxnreg.inc.sync.aligned.u32 224;");
      if (tid == 0) TL(58);
      cluster_arrive();
      Ring r{0, 0};
      Stg stg{0, 0};
      if (aux) {
        if (wg == 0) {
            const uint4 cv = *(const uint4*)(cvec + tw * 8);
            sts128(sb + OFF_STG + (tw >> 3) * 1024 + (tw & 7) * 16, pack2(silu_(bf_lo(cv.x)), silu_(bf_hi(cv.x))), pack2(silu_(bf_lo(cv.y)), silu_(bf_hi(cv.y))),
                   pack2(silu_(bf_lo(cv.z)), silu_(bf_hi(cv.z))), pack2(silu_(bf_lo(cv.w)), silu_(bf_hi(cv.w))));
            fence_async_smem();
        }
        cluster_wait();
        ep = __shfl_sync(0xffffffffu, ep, 0) / NCTA + 1;
        if (wg == 0) {
            if (tw == 0) {
                uint32_t n = 0;
                while (ld_pkt16(pt.mail->mod1 + 256).z != ep) { SPIN_GUARD(n); __nanosleep(200); }
                if (GODLY) __nanosleep(GODLY);
                mbar_arrive(BAR_ONE(sb, EV_GO));
            }
            bar_sync(1, 128);
#pragma unroll 1
            for (int p = 0; p < 4; ++p) {
                float acc[128];
#pragma unroll
                for (int i = 0; i < 128; ++i) acc[i] = 0.f;
                uint32_t prev = 0;
#pragma unroll 1
                for (int kc = 0; kc < 16; ++kc) {
                    mbar_wait(BAR_FULL(sb, r.slot), r.par);
                    wg_fence();
#pragma unroll
                    for (int k = 0; k < 4; ++k)
                        wgmma_n256(acc, mk_desc(d16(sb) + kc * 64, OFF_STG + k * 32, 16, 0, 1), mk_desc(d16(sb) + r.slot * (SLOT >> 4), k * 2048, 8192, 1024, 1));
                    wg_commit();
                    wg_wait<1>();
                    if (kc > 0 && tw < 4) mbar_arrive(BAR_EMPTY(sb, prev));
                    prev = r.slot;
                    r.next();
                }
                wg_wait<0>();
                if (tw < 4) mbar_arrive(BAR_EMPTY(sb, prev));
                if (tw < 4) {
#pragma unroll
                    for (int jn = 0; jn < 32; ++jn) sts32(sb + OFF_TAB + (jn * 4 + tw) * 4, pack2(acc[jn * 4], acc[jn * 4 + 1]));
                }
                bar_sync(1, 128);
                const int vec = 2 + p, blk = p * 4 + j;
                const uint32_t val = lds32(sb + OFF_TAB + tw * 4);
                if (vec == 2 || vec == 5) st_pkt(g_mod + (8 + blk) * 128 + tw, val, ep);
                else {
                    const float one = vec == 4 ? 1.f : 0.f;
                    g_par2[((blk & 3) * 16 + (tw >> 3)) * 16 + (tw & 3) * 4 + (vec - 3) * 2 + ((tw >> 2) & 1)] =
                        pack2(0.5f * bf_round(one + bf_lo(val)), 0.5f * bf_round(one + bf_hi(val)));
                }
                bar_sync(1, 128);
                if (tw == 0) {
                    if (vec == 3 || vec == 4) asm volatile("red.release.gpu.global.add.u32 [%0], 1;" :: "l"(&g_flags[FL_LN2]) : "memory");
                    TL(1 + p);
                }
            }
            if (lane < 2) mbar_arrive_cta(BAR_ONE(sb, EV_P0), lane);
        }
        r = Ring{64 % NSLOT, (64 / NSLOT) & 1};
        mbar_wait(BAR_ONE(sb, EV_P0), 0);
        passes128<4>(sb, wg, tw, r, stg);
      } else {
        {
            IDX();
            uint32_t sa[4];
            uint4* const st1 = g_st1 + m * 128 + wg * 64 + w4 * 16 + g8;
            uint4* const mod_out = pt.mail->mod1 + g8 * 512 + (m * 8 + j) * 4 + q4;
            if (RESET && q4 < 2) st_pkt16(st1 + j * S_ + q4 * 8, 0, 0, 0, 0);
            if (wg == 0) {
                if (w4 == 0) st_pkt16(mod_out, 0, 0, 0, 0);
#pragma unroll
                for (int i = 0; i < 4; ++i) sa[i] = pack2(silu_(bf_lo(cw[2 * i])), silu_(bf_lo(cw[2 * i + 1])));
            }
            cluster_wait();
            ep = __shfl_sync(0xffffffffu, ep, 0) / NCTA + 1;
            uint32_t xr[32];
            float xf[64];
            const uint32_t buf0 = stg.acquire2(sb, wg);
            if (tid == 0) TL(24);
            if (tid == 128) TL(27);
            RowAcc ra;
#pragma unroll
            for (int i = 0; i < 8; ++i) ldsm4(buf0 + (i >> 2) * 8192 + (pan_addr ^ ((i & 3) << 5)), xr[4 * i], xr[4 * i + 1], xr[4 * i + 2], xr[4 * i + 3]);
#pragma unroll
            for (int e = 0; e < 32; ++e) { unpack2(xr[e], xf[2 * e], xf[2 * e + 1]); ra.add(2 * e, xf[2 * e]); ra.add(2 * e + 1, xf[2 * e + 1]); }
            ra.publish(st1 + j * S_, q4, ep);
            if (tid == 0) TL(26);
            if (wg == 0) {
                uint32_t af[8][4];
#pragma unroll
                for (int i = 0; i < 8; ++i)
#pragma unroll
                    for (int e = 0; e < 4; ++e) af[i][e] = __shfl_sync(0xffffffffu, sa[e], i * 4 + q4);
                float c[4][4] = {};
#pragma unroll
                for (int i = 0; i < 8; ++i) {
                    if (!(i & 1)) mbar_wait(BAR_ONE(sb, EV_WIN + (i >> 1)), 0);
                    if (i == 6 && tid == 0) TL(25);
#pragma unroll
                    for (int h = 0; h < 2; ++h) {
                        uint32_t b0, b1, b2, b3;
                        ldsm4t(sb + 5 * SLOT + i * 4096 + w4 * 1024 + h * 512 + (lane & 15) * 32 + (lane >> 4) * 16, b0, b1, b2, b3);
                        mma16816(c[2 * h], af[i][2 * h], 0u, af[i][2 * h + 1], 0u, b0, b1);
                        mma16816(c[2 * h + 1], af[i][2 * h], 0u, af[i][2 * h + 1], 0u, b2, b3);
                    }
                }
                if (lane < 4) sts128(sb + OFF_TAB + w4 * 64 + lane * 16, __float_as_uint(c[0][0] + c[2][0]), __float_as_uint(c[0][1] + c[2][1]),
                                     __float_as_uint(c[1][0] + c[3][0]), __float_as_uint(c[1][1] + c[3][1]));
                if (lane < 2) mbar_arrive_cta(BAR_ONE(sb, EV_P0), lane);
                bar_sync(1, 128);
                if (w4 == 0) {
                    float a[4] = {0.f, 0.f, 0.f, 0.f};
#pragma unroll
                    for (int i = 0; i < 4; ++i) {
                        const uint4 t = lds128(sb + OFF_TAB + i * 64 + q4 * 16);
                        a[0] += __uint_as_float(t.x); a[1] += __uint_as_float(t.y); a[2] += __uint_as_float(t.z); a[3] += __uint_as_float(t.w);
                    }
                    const float add = m >= 8 ? 1.f : 0.f;
                    st_pkt16(mod_out, pack2(bf_round(a[0]) + add, bf_round(a[1]) + add), pack2(bf_round(a[2]) + add, bf_round(a[3]) + add), ep, 0);
                    if (tid == 0) TL(3);
                }
            } else if (LWAIT >= 0) mbar_wait(BAR_ONE(sb, EV_WIN + LWAIT), 0);
            const LnRow n1 = merge_stats(st1, S_, q4, ep, sb, 0);
            if (tid == 0) TL(48);
            if (tid == 128) TL(28);
            ln_norm(xr, xf, n1);
            mbar_wait(BAR_ONE(sb, EV_PAR), 0);
            LnPar lp; lp.load(sb, q4);
            ln_emit(xr, lp, sb, wg, ix);
            if (tid == 0) { TL(8); TC(103); }
            if (tid == 128) TL(22);
        }
        {
            float kv[128], qa[64];
            mainloop32<true, LAGQ>(kv, qa, sb, wg, tw, r, EV_LAG0, 0, [&] { stg.acquire2(sb, wg); mbar_wait2(BAR_SREADY(sb, 2), BAR_SREADY(sb, 3), 1); });
            if (tid == 0) { TL(4); TC(104); }
            if (tid == 128) TL(50);
            CS(1);
            IDX();
            uint32_t k1[16], k2[16], v1[16], v2[16], qf[32];
#pragma unroll
            for (int i = 0; i < 8; ++i) qf[i] = pack2(qa[2 * i], qa[2 * i + 1]);
#pragma unroll
            for (int t = 0; t < 16; ++t) k2[t] = pack2(kv[4 * t + 2], kv[4 * t + 3]);
#pragma unroll
            for (int t = 0; t < 16; ++t) v2[t] = pack2(kv[64 + 4 * t + 2], kv[64 + 4 * t + 3]);
            const uint32_t nxt = warp + ((warp & 1) ? 3 : 1);
            if (nxt < 8) {
                const uint32_t dst = sb + OFF_STG + (nxt >> 2) * 16384 + (nxt & 3) * 2048 + lane * 16;
#pragma unroll
                for (int h = 0; h < 4; ++h) stsm4(dst + h * 512, k2[4 * h], k2[4 * h + 1], k2[4 * h + 2], k2[4 * h + 3]);
#pragma unroll
                for (int h = 0; h < 4; ++h) stsm4(dst + 8192 + h * 512, v2[4 * h], v2[4 * h + 1], v2[4 * h + 2], v2[4 * h + 3]);
                bar_arrive(NB_TAIL + nxt, 64);
            } else if (m < 15) {
                uint4* dst = g_halo + (m * 8 + j) * 512 + (w4 >> 1) * 256 + lane;
#pragma unroll
                for (int h = 0; h < 4; ++h) { if (!k2[4 * h]) k2[4 * h] = 0x8000u; if (!v2[4 * h]) v2[4 * h] = 0x8000u; }
#pragma unroll
                for (int h = 0; h < 4; ++h) st_pkt16(dst + h * 32, k2[4 * h], k2[4 * h + 1], k2[4 * h + 2], k2[4 * h + 3]);
#pragma unroll
                for (int h = 0; h < 4; ++h) st_pkt16(dst + 128 + h * 32, v2[4 * h], v2[4 * h + 1], v2[4 * h + 2], v2[4 * h + 3]);
            }
#pragma unroll
            for (int t = 0; t < 16; ++t) { k1[t] = pack2(kv[4 * t], kv[4 * t + 1]); v1[t] = pack2(kv[64 + 4 * t], kv[64 + 4 * t + 1]); }
#pragma unroll
            for (int i = 8; i < 32; ++i) qf[i] = pack2(qa[2 * i], qa[2 * i + 1]);
#pragma unroll
            for (int t = 0; t < 16; ++t) { v1[t] = movm(v1[t]); v2[t] = movm(v2[t]); }
            if (tid == 0) TL(33);
            CS(2);
            SCHED_FENCE(0);
            float s[4][3][4];
            auto qk = [&](float (&c)[4], int h, const uint32_t* k) {
                c[0] = c[1] = c[2] = c[3] = 0.f;
                mma16816(c, qf[h * 8], qf[h * 8 + 1], qf[h * 8 + 2], qf[h * 8 + 3], k[0], k[1]);
                mma16816(c, qf[h * 8 + 4], qf[h * 8 + 5], qf[h * 8 + 6], qf[h * 8 + 7], k[2], k[3]);
            };
#pragma unroll
            for (int h = 0; h < 4; ++h) { qk(s[h][1], h, k1 + 4 * h); qk(s[h][2], h, k2 + 4 * h); }
            CS(3);
            bar_sync(NB_TAIL + warp, 64);
            CS(4);
            if (tid == 0) TL(5);
            uint32_t k0[16], v0[16];
            const uint32_t mine = sb + OFF_STG + wg * 16384 + w4 * 2048;
#pragma unroll
            for (int h = 0; h < 4; ++h) ldsm4(mine + lane * 16 + h * 512, k0[4 * h], k0[4 * h + 1], k0[4 * h + 2], k0[4 * h + 3]);
#pragma unroll
            for (int h = 0; h < 4; ++h) ldsm4t(mine + lane * 16 + 8192 + h * 512, v0[4 * h], v0[4 * h + 1], v0[4 * h + 2], v0[4 * h + 3]);
#pragma unroll
            for (int h = 0; h < 4; ++h) qk(s[h][0], h, k0 + 4 * h);
            const bool lo0 = q4 * 2 > g8, lo1 = q4 * 2 + 1 > g8;
            const bool nopast = m == 0 && (warp & 5) == 0;
            const uint32_t lomask = (lo0 ? 0xFFFFu : 0u) | (lo1 ? 0xFFFF0000u : 0u);
            const float sl2 = 0.17677669529663687f * 1.4426950408889634f;
            float e0[8], e1[8], mx[8], sum[8], tt[8];
#pragma unroll
            for (int u = 0; u < 8; ++u) {
                const int h = u >> 1, hf = u & 1;
                e0[u] = lo0 ? ((hf == 0 && nopast) ? -INFINITY : s[h][hf][hf * 2]) : s[h][hf + 1][hf * 2];
                e1[u] = lo1 ? ((hf == 0 && nopast) ? -INFINITY : s[h][hf][hf * 2 + 1]) : s[h][hf + 1][hf * 2 + 1];
                mx[u] = fmaxf(e0[u], e1[u]);
                tt[u] = __shfl_xor_sync(0xffffffffu, mx[u], 1);
            }
            SCHED_FENCE(1);
#pragma unroll
            for (int u = 0; u < 8; ++u) { mx[u] = fmaxf(mx[u], tt[u]); tt[u] = __shfl_xor_sync(0xffffffffu, mx[u], 2); }
            SCHED_FENCE(2);
#pragma unroll
            for (int u = 0; u < 8; ++u) {
                const float c = -fmaxf(mx[u], tt[u]) * sl2;
                e0[u] = ex2(fmaf(e0[u], sl2, c)); e1[u] = ex2(fmaf(e1[u], sl2, c));
            }
            SCHED_FENCE(3);
#pragma unroll
            for (int u = 0; u < 8; ++u) { sum[u] = e0[u] + e1[u]; tt[u] = __shfl_xor_sync(0xffffffffu, sum[u], 1); }
            SCHED_FENCE(4);
#pragma unroll
            for (int u = 0; u < 8; ++u) { sum[u] += tt[u]; tt[u] = __shfl_xor_sync(0xffffffffu, sum[u], 2); }
            SCHED_FENCE(5);
#pragma unroll
            for (int u = 0; u < 8; ++u) sum[u] = rcp(sum[u] + tt[u]);
            SCHED_FENCE(6);
            CS(5);
            float o[8][2][4];
#pragma unroll
            for (int u = 0; u < 8; ++u) {
                const int h = u >> 1;
                const uint32_t p = pack2(e0[u] * sum[u], e1[u] * sum[u]);
                const uint32_t* va = ((u & 1) ? v1 : v0) + 4 * h;
                const uint32_t* vb = ((u & 1) ? v2 : v1) + 4 * h;
#pragma unroll
                for (int d = 0; d < 2; ++d) {
                    o[u][d][0] = o[u][d][1] = o[u][d][2] = o[u][d][3] = 0.f;
                    mma16816(o[u][d], va[2 * d], va[2 * d + 1], vb[2 * d], vb[2 * d + 1], p & lomask, p & ~lomask);
                }
            }
            SCHED_FENCE(7);
            const uint32_t orow = mine + (lane & 7) * 128 + (((lane >> 3) ^ (lane & 7)) << 4);
#pragma unroll
            for (int u = 0; u < 8; ++u)
                stsm4t((orow ^ (((u >> 1) & 1) << 6)) + (u >> 2) * 8192 + (u & 1) * 1024, pack2(o[u][0][0], o[u][0][1]), pack2(o[u][0][2], o[u][0][3]),
                       pack2(o[u][1][0], o[u][1][1]), pack2(o[u][1][2], o[u][1][3]));
            fence_async_smem();
            __syncwarp();
            if (lane < 2) mbar_arrive(BAR_SFULL(sb, wg * 2 + lane));
            CS(6);
            if (tid == 32) TL(41);
            bar_sync(1 + wg, 128);
            if (tid == 0) { TL(6); TC(106); }
            if (tid == 128) TL(44);
            CS(7);
        }
        {
            float acc[64], xf[64], gf[32];
            mainloop64<true, 16, LAGW, MIDW>(acc, sb, wg, tw, r, [&] {
                mbar_wait(BAR_ONE(sb, EV_GA), 0);
                load_res(xf, gf, stg.acquire2(sb, wg), sb + OFF_TAB);
            });
            if (tid == 0) { TL(7); TC(107); }
            if (tid == 128) TL(42);
            CS(10);
            IDX();
            RowAcc ra;
#pragma unroll
            for (int e = 0; e < 64; ++e) { acc[e] = fmaf(gf[(e >> 2) * 2 + (e & 1)], acc[e], xf[e]); ra.add(e, acc[e]); }
            ra.publish(g_st2 + j * 512 + wg * 64 + w4 * 16 + g8, q4, ep);
            if (tid == 0) TL(9);
            if (tid == 128) TL(34);
            CS(11);
            LnPar lp;
            {
                if (wg) mbar_wait2(BAR_EMPTY(sb, X1_SLOT), BAR_EMPTY(sb, X1_SLOT + 1), r.par ^ 1);
#pragma unroll
                for (int i = 0; i < 8; ++i)
                    stsm4(sb + (X1_SLOT + 2 - 2 * wg + (i >> 2)) * SLOT + (pan_addr ^ ((i & 3) << 5)), pack2(acc[8 * i], acc[8 * i + 1]), pack2(acc[8 * i + 2], acc[8 * i + 3]),
                          pack2(acc[8 * i + 4], acc[8 * i + 5]), pack2(acc[8 * i + 6], acc[8 * i + 7]));
                fence_async_smem();
                __syncwarp();
                CS(12);
                mbar_wait(BAR_ONE(sb, EV_LN2), 0);
                lp.load(sb, q4);
                CS(13);
            }
            const LnRow n2 = merge_stats(g_st2 + wg * 64 + w4 * 16 + g8, 512, q4, ep, sb, lane == 0 ? BAR_ONE(sb, EV_X1S + wg) : 0);
            if (tid == 0) TL(49);
            if (tid == 128) TL(45);
            CS(18);
            uint32_t xn[32];
            ln_norm(xn, acc, n2);
            ln_emit(xn, lp, sb, wg, ix);
            if (tid == 0) { TL(36); TC(109); }
            if (tid == 128) TL(43);
            CS(21);
        }
        {
            float ag[88], au[88];
            mainloop32<true, LAG>(ag, au, sb, wg, tw, r, EV_LAG1, 48, [&] {
                stg.acquire2(sb, wg);
                Ring q = r; if (!wg) q.next();
                mbar_wait(BAR_EMPTY(sb, q.slot), q.par ^ 1);
            });
            if (tid == 0) { TL(10); TC(110); }
            if (tid == 128) TL(51);
            glu_panel<0, 0>(ag, au, sb + OFF_STG + wg * 16384, BAR_SFULL(sb, wg * 2));
            glu_panel<32, 32>(ag, au, sb + OFF_STG + wg * 16384 + 8192, BAR_SFULL(sb, wg * 2 + 1));
            glu_panel<64, 64>(ag, au, sb + (wg ? P3_SLOT1 : P3_SLOT0) * SLOT + 24576, BAR_ONE(sb, EV_P3 + wg));
            if (tid == 0) { TL(11); TC(111); }
            if (tid == 128) TL(52);
        }
        passes128<2>(sb, wg, tw, r, stg);
        if (tid == 0) { TL(12); TC(112); }
        {
            float acc[64], xf[64], gf[32];
            const uint32_t buf0 = sb + OFF_STG + wg * 16384;
            mainloop64<false, 56, LAGD, 40>(acc, sb, wg, tw, r, [&] {
                mbar_wait(BAR_ONE(sb, EV_GB), 0);
                load_res(xf, gf, stg.acquire2(sb, wg), sb + OFF_TAB + 256);
            });
            cluster_arrive();
            if (tid == 0) { TL(13); TC(113); }
            if (tid == 128) TL(57);
            IDX();
#pragma unroll
            for (int p = 0; p < 2; ++p) {
#pragma unroll
                for (int e = 32 * p; e < 32 * p + 32; ++e) acc[e] = fmaf(gf[(e >> 2) * 2 + (e & 1)], acc[e], xf[e]);
#pragma unroll
                for (int i = 4 * p; i < 4 * p + 4; ++i)
                    stsm4(buf0 + p * 8192 + (pan_addr ^ ((i & 3) << 5)), pack2(acc[8 * i], acc[8 * i + 1]), pack2(acc[8 * i + 2], acc[8 * i + 3]),
                          pack2(acc[8 * i + 4], acc[8 * i + 5]), pack2(acc[8 * i + 6], acc[8 * i + 7]));
                stg.publish(sb, wg, lane);
            }
            if (tid == 0) TL(14);
        }
      }
    } else {
        if (warp == 8 && !aux && elect_one()) {
#pragma unroll
            for (int i = 0; i < 4; ++i) mbar_init(BAR_SREADY(sb, i), 1);
#pragma unroll
            for (int i = 0; i < 4; ++i) mbar_init(BAR_ONE(sb, EV_WIN + i), 1);
#pragma unroll
            for (int i = 0; i < 4; ++i) {
                mbar_expect_tx(BAR_SREADY(sb, i), 8192);
                tma_load3(sb + OFF_STG + i * 8192, &mp.x, j * 128 + (i & 1) * 64, m * 64 + (i >> 1) * 32, BAR_SREADY(sb, i));
            }
#pragma unroll 1
            for (int i = 0; i < 4; ++i) {
                mbar_expect_tx(BAR_ONE(sb, EV_WIN + i), 8192);
                tma_load(sb + 5 * SLOT + i * 8192, &mp.wm8, 2 * i * 6144 + (m * 8 + j) * 16, 0, BAR_ONE(sb, EV_WIN + i));
                tma_load(sb + 5 * SLOT + i * 8192 + 4096, &mp.wm8, (2 * i + 1) * 6144 + (m * 8 + j) * 16, 0, BAR_ONE(sb, EV_WIN + i));
            }
        }
        __syncwarp();
        asm volatile("setmaxnreg.dec.sync.aligned.u32 56;");
        ep = flag_get(g_flags + FL_DONE);
        if (elect_one()) {
            if (warp == 8) {
                prefetch_map(&mp.wqkv); prefetch_map(&mp.wmod);
            } else if (warp < 11) {
                mbar_init(BAR_EMPTY(sb, NSLOT), 1);
#pragma unroll
                for (int i = 0; i < 2; ++i) { mbar_init(BAR_SFULL(sb, (warp - 9) * 2 + i), 4); if (aux) mbar_init(BAR_SREADY(sb, (warp - 9) * 2 + i), 1); }
#pragma unroll
                for (int i = 0; i < 3; ++i) {
                    mbar_init(BAR_EMPTY(sb, (warp - 9) * 3 + i), 4);
                    mbar_init(BAR_FULL(sb, (warp - 9) * 3 + i), 1); mbar_init(BAR_FULL(sb, (warp - 9) * 3 + i) + AF_REL, 1);
                }
            } else {
#pragma unroll
                for (int i = EV_P0; i < EV_COUNT; ++i) mbar_init(BAR_ONE(sb, i), i == EV_P0 ? 8 : (i == EV_P3 || i == EV_P31 || i >= EV_X1S) ? 4 : 1);
            }
            asm volatile("fence.mbarrier_init.release.cluster;" ::: "memory");
        }
        __syncwarp();
        cluster_arrive();
        cluster_wait();
        ep = __shfl_sync(0xffffffffu, ep, 0) / NCTA + 1;
        if (warp == 8) {
            const bool el = elect_one();
            Ring r{0, 1};
            if (aux) {
                mbar_wait(BAR_ONE(sb, EV_GO), 0);
#pragma unroll 1
                for (int it = 0; it < 64; ++it) {
                    const int col = 2048 + (it >> 4) * 1024 + j * 256;
                    mbar_wait(BAR_EMPTY(sb, r.slot), r.par);
                    const uint32_t st = sb + r.slot * SLOT, fb = BAR_FULL(sb, r.slot);
                    if (el) {
                        mbar_expect_tx(fb, 32768);
#pragma unroll
                        for (int b = 0; b < 4; ++b) tma_load(st + b * 8192, &mp.wmod, col + b * 64, (it & 15) * 64, fb);
                    }
                    r.next();
                }
                mbar_wait(BAR_ONE(sb, EV_P0), 0);
                const CUtensorMap* wm = rank ? &mp.wu : &mp.wg;
#pragma unroll 1
                for (int g = 0; g < 128; ++g) {
                    const int mx = (j >> 1) * 8 + (g >> 5) * 2 + rank, k0 = (g & 31) * 32;
                    if (k0 == 0) {
                        uint32_t n = 0;
                        while (!__all_sync(0xffffffffu, (int32_t)(flag_get(g_flags + FL_PROG + (mx * 32 + lane) * FS) - (ep * 8 + ST_H2)) >= 0)) { SPIN_GUARD(n); __nanosleep(500); }
                    }
                    mbar_wait(BAR_EMPTY(sb, r.slot), r.par);
                    const uint32_t st = sb + r.slot * SLOT, fb = BAR_FULL(sb, r.slot);
                    if (el) {
                        mbar_expect_tx(fb, 24576);
                        tma_load_mc(st + 8192 + rank * 4096, wm, HC3, k0, fb);
                        tma_load_mc(st + 16384 + rank * 4096, wm, HC3 + 64, k0, fb);
                        tma_load(st, &mp.h2l, k0, mx * 128, fb);
                    }
                    r.next();
                }
            } else {
#pragma unroll 1
                for (int it = 0; it < 32; ++it) {
                    const int cb = j * 128 + rank * 64, k0 = kof(it, 2, j);
                    if (it == BW0) mbar_wait(BAR_ONE(sb, BWEV), 0);
                    if (it == BW1) mbar_wait(BAR_ONE(sb, EV_PAR), 0);
                    if (it == 5) mbar_wait(BAR_ONE(sb, EV_P0), 0);
                    if ((AGO & 1) && it == 6) mbar_wait(BAR_ONE(sb, EV_AGO), 0);
                    mbar_wait(BAR_EMPTY(sb, r.slot), r.par);
                    const uint32_t st = sb + r.slot * SLOT, fb = BAR_FULL(sb, r.slot);
                    if (el) {
                        mbar_expect_tx(fb, it < 4 ? 24576 : 28672);
                        tma_load_mc(st + 8192 + rank * 4096, &mp.wqkv, 1024 + cb, k0, fb);
                        tma_load_mc(st + 16384 + rank * 4096, &mp.wqkv, 2048 + cb, k0, fb);
                        tma_load_mc(st + 24576 + rank * 4096, &mp.wqkv, cb, k0, fb);
                        if (it < 4) mbar_arrive(fb + AF_REL);
                        if (it == PFWO + (m >> 1)) { tma_prefetch(&mp.wo, j * 128, m * 64); tma_prefetch(&mp.wo, j * 128 + 64, m * 64); }
                    }
                    r.next();
                }
                if (el) mbar_arrive(BAR_ONE(sb, EV_KV));
#pragma unroll 1
                for (int it = 0; it < 16; ++it) {
                    if ((AGO & 2) && it == 6) mbar_wait(BAR_ONE(sb, EV_AGO1), 0);
                    mbar_wait(BAR_EMPTY(sb, r.slot), r.par);
                    const uint32_t st = sb + r.slot * SLOT, fb = BAR_FULL(sb, r.slot);
                    if (el) {
                        mbar_expect_tx(fb, it < 2 ? 16384 : 24576);
                        tma_load_mc(st + 16384 + rank * 8192, &mp.wo, j * 128 + rank * 64, kof(it, 1, j), fb);
                        if (it < 2) mbar_arrive(fb + AF_REL);
                        if (it == 6) { prefetch_map(rank ? &mp.wu : &mp.wg); prefetch_map(rank ? &mp.wu3 : &mp.wg3); }
                    }
                    r.next();
                }
                const CUtensorMap* wm = rank ? &mp.wu : &mp.wg;
#pragma unroll 1
                for (int g = 0; g < 96; ++g) {
                    if ((AGO & 4) && g == 6) mbar_wait(BAR_ONE(sb, EV_AGO2), 0);
                    const int p = g >> 5, cb = hcol(p, j), k0 = p == 0 ? kof(g, 2, j) : (g & 31) * 32;
                    mbar_wait(BAR_EMPTY(sb, r.slot), r.par);
                    const uint32_t st = sb + r.slot * SLOT, fb = BAR_FULL(sb, r.slot);
                    if (el) {
                        mbar_expect_tx(fb, (g < 4 || p > 0) ? 24576 : 28672);
                        tma_load_mc(st + 8192 + rank * 4096, wm, cb, k0, fb);
                        tma_load_mc(st + 16384 + rank * 4096, wm, cb + 64, k0, fb);
                        if (p == 0) tma_load3_mc(st + 24576 + rank * 4096, rank ? &mp.wu3 : &mp.wg3, j, k0, fb);
                        else tma_load(st, &mp.h2l, k0, m * 128, fb);
                        if (g < 4) mbar_arrive(fb + AF_REL);
                        if (g == 90) prefetch_map(&mp.wd);
                    }
                    r.next();
                }
#pragma unroll 1
                for (int g = 0; g < 56; ++g) {
                    if (g == 0 || (g & 15) == 6 && g > 6) mbar_wait(BAR_ONE(sb, EV_H0 + (g >> 4)), 0);
                    const int k0 = g * 64;
                    mbar_wait(BAR_EMPTY(sb, r.slot), r.par);
                    const uint32_t st = sb + r.slot * SLOT, fb = BAR_FULL(sb, r.slot);
                    if (el) {
                        mbar_expect_tx(fb, 32768);
                        tma_load_mc(st + 16384 + rank * 8192, &mp.wd, j * 128 + rank * 64, k0, fb);
                        tma_load(st, &mp.hb, k0, m * 128, fb); tma_load(st + 8192, &mp.hb, k0, m * 128 + 64, fb);
                    }
                    r.next();
                }
            }
        } else if (aux) {
            if (warp < 11) {
                const uint32_t w = warp - 9;
                const bool el = elect_one();
#pragma unroll 1
                for (int p = 0; p < 4; ++p) {
                    const int mx = (j >> 1) * 8 + p * 2 + rank;
                    if (el) { mbar_arrive(BAR_SREADY(sb, w * 2)); mbar_arrive(BAR_SREADY(sb, w * 2 + 1)); }
                    mbar_wait2(BAR_SFULL(sb, w * 2), BAR_SFULL(sb, w * 2 + 1), p & 1);
                    if (el) {
                        tma_store(&mp.hb, HC3, mx * 128 + w * 64, sb + OFF_STG + w * 16384); tma_store(&mp.hb, HC3 + 64, mx * 128 + w * 64, sb + OFF_STG + w * 16384 + 8192);
                        bulk_commit(); bulk_wait_all(); flag_set(g_flags + FL_AUX + mx * 2 + w, ep * 8 + ST_H + 3);
                    }
                }
            }
        } else if (warp == 11) {
            const bool el = elect_one();
            const int row0 = m * 128;
            const uint32_t* const fl = g_flags + FL_PROG + (m * 32 + (lane & 16) + (kof(lane & 15, 1, j) >> 6)) * FS;
            if (el) { prefetch_map(&mp.h1h); prefetch_map(&mp.h2h); prefetch_map(&mp.h2l); }
            {
                const uint4* pk = pt.mail->mod1 + grp * 512 + j * 32 + lane;
                uint4 a, b; uint32_t n = 0;
                mbar_wait(BAR_ONE(sb, EV_WIN3), 0);
                while (true) {
                    a = ld_pkt16(pk); b = ld_pkt16(pk + 256);
                    if (__all_sync(0xffffffffu, a.z == ep && b.z == ep)) break;
                    SPIN_GUARD(n);
                }
                sts128(sb + OFF_PAR + lane * 16, a.x, a.y, b.x, b.y);
                __syncwarp();
                if (lane == 0) { mbar_arrive(BAR_ONE(sb, EV_PAR)); TL(46); }
            }
            mbar_wait(BAR_ONE(sb, EV_P0), 0);
            Ring r{0, 1};
#pragma unroll 1
            for (int ph = 0; ph < 3; ++ph) {
                const int sh = ph == 1 ? 1 : 2, nst = 8 << sh;
                const uint32_t half = 16384 >> sh;
                const CUtensorMap* tm = ph == 0 ? &mp.h1h : ph == 1 ? &mp.o : &mp.h2h;
                if (ph == 1) fetch_halo(g_halo + ((m - 1) * 8 + j) * 512 + 256 + lane, m == 0, sb, 2, lane);
                const uint32_t target = ep * 8 + ST_H1 + ph;
                int a0 = 1 << sh, a1 = a0, fr = a0;
                r.skip(fr);
                uint32_t s0 = r.slot, s1 = r.slot, have = 0, n = 0;
                int k0 = j ? 0 : 128, k1 = k0;
#pragma unroll 1
                for (; fr < NSLOT; ++fr) { mbar_wait(BAR_EMPTY(sb, r.slot), r.par); r.next(); }
                uint32_t v = flag_get(fl);
                auto load = [&](int& a, uint32_t& sl, int& k, uint32_t w) {
                    const uint32_t fb = BAR_FULL(sb, sl) + (w ? 0 : AF_REL);
                    if (el) { if (!w) mbar_expect_tx(fb, half); tma_load(sb + sl * SLOT + w * half, tm, k, row0 + w * 64, fb); }
                    if (a == NSLOT - 1 && w == ((AGW >> ph) & 1) && el) mbar_arrive(BAR_ONE(sb, EV_AGO + ph));
                    ++a; if (++sl == NSLOT) sl = 0;
                    k += 128 >> sh; if (k == j * 128) k += 128;
                };
                do {
                    PS(0);
                    if (fr < 10 && mbar_test(BAR_EMPTY(sb, r.slot), r.par) && (ph < 2 || mbar_test(BAR_ONE(sb, EV_X1 + (fr < 8)), 0))) { ++fr; r.next(); }
                    SPIN_GUARD(n);
                    PS(1);
                    const bool ok = (int32_t)(v - target) >= 0;
                    v = flag_get(fl);
                    have = __ballot_sync(0xffffffffu, ok);
                    PS(2);
#pragma unroll 1
                    while (a1 < fr && (have & (0x10000u << (a1 >> (sh - 1))))) {
                        if (a1 == (1 << sh)) TL(16 + ph);
                        load(a1, s1, k1, 1);
                    }
                    PS(3);
#pragma unroll 1
                    while (a0 < fr && (have & (1u << (a0 >> (sh - 1))))) load(a0, s0, k0, 0);
                    PS(4);
                } while (have != 0xffffffffu);
                if (ph == 2) mbar_wait2(BAR_ONE(sb, EV_X1), BAR_ONE(sb, EV_X11), 0);
#pragma unroll 1
                while (a0 < nst) {
                    mbar_wait(BAR_EMPTY(sb, r.slot), r.par);
                    r.next();
                    load(a1, s1, k1, 1); load(a0, s0, k0, 0);
                }
            }
#pragma unroll 1
            for (int p = 0; p < 4; ++p) {
                const uint32_t* f = p < 3 ? fl : g_flags + FL_AUX + m * 2 + (lane & 1);
                uint32_t n = 0;
                while (!__all_sync(0xffffffffu, (int32_t)(flag_get(f) - (ep * 8 + ST_H + p)) >= 0)) { SPIN_GUARD(n); __nanosleep(500); }
                if (el) mbar_arrive(BAR_ONE(sb, EV_H0 + p));
            }
        } else {
            const uint32_t w = warp - 9;
            const int row0 = m * 128 + w * 64;
            const uint32_t stg = sb + OFF_STG + w * 16384;
            uint32_t* const fl = g_flags + FL_PROG + (m * 32 + w * 16 + 2 * j) * FS;
            uint32_t b = 0, par = 0;
            const bool el = elect_one();
            auto store = [&](const CUtensorMap* tm, int col, bool nat = false) {
                mbar_wait(BAR_SFULL(sb, w * 2 + b), (par >> b) & 1);
                par ^= 1u << b;
                if (el) {
                    if (nat) tma_store3(tm, col, row0 >> 1, 0, stg + b * 8192); else tma_store(tm, col, row0, stg + b * 8192);
                    bulk_commit();
                }
                b ^= 1;
            };
            auto load2 = [&](const CUtensorMap* tm, bool nat) {
                if (el) {
#pragma unroll
                    for (uint32_t i = 0; i < 2; ++i) {
                        mbar_expect_tx(BAR_SREADY(sb, w * 2 + i), 8192);
                        if (nat) tma_load3(stg + i * 8192, tm, j * 128 + i * 64, row0 >> 1, BAR_SREADY(sb, w * 2 + i));
                        else tma_load(stg + i * 8192, tm, j * 128 + i * 64, row0, BAR_SREADY(sb, w * 2 + i));
                    }
                }
            };
            auto send2 = [&](const CUtensorMap* tm, int step) {
                store(tm, j * 128); store(tm, j * 128 + 64);
                if (el) {
                    asm volatile("cp.async.bulk.wait_group 1;" ::: "memory"); flag_set(fl, ep * 8 + step);
                    bulk_wait_all(); flag_set(fl + FS, ep * 8 + step);
                }
            };
            auto free2 = [&]() { if (el) { mbar_arrive(BAR_SREADY(sb, w * 2)); mbar_arrive(BAR_SREADY(sb, w * 2 + 1)); } };
            auto gate = [&](int vec, int ev) {
                uint4 v; uint32_t n = 0;
                while (true) {
                    v = ld_pkt2(g_mod + vec * 512 + j * 64 + lane * 2);
                    if (__all_sync(0xffffffffu, v.y == ep && v.w == ep)) break;
                    SPIN_GUARD(n); __nanosleep(300);
                }
                asm volatile("st.shared.v2.u32 [%0], {%1, %2};" :: "r"(sb + OFF_TAB + (ev - EV_GA) * 256 + lane * 8), "r"(v.x), "r"(v.z) : "memory");
                __syncwarp();
                if (lane == 0) mbar_arrive(BAR_ONE(sb, ev));
            };
            if (el) { prefetch_map(&mp.h1s); prefetch_map(&mp.o); prefetch_map(&mp.x1); prefetch_map(&mp.h2s); prefetch_map(&mp.hb); prefetch_map(&mp.out); prefetch_map(&mp.wo); }
            if (el) { flag_set(fl, ep * 8); flag_set(fl + FS, ep * 8); }
            send2(&mp.h1s, ST_H1);
            if (w == 0) TL(47);
            free2();
            if (w == 0) fetch_halo(g_halo + ((m - 1) * 8 + j) * 512 + lane, m == 0, sb, 0, lane);
            else { mbar_wait(BAR_ONE(sb, EV_KV), 0); gate(2, EV_GA); }
            send2(&mp.o, ST_O);
            if (w == 0) TL(40); else TL(38);
            mbar_wait(BAR_ONE(sb, EV_OWN + w), 0);
            load2(&mp.x, true);
            if (w == 1) {
                uint32_t n = 0;
                while ((int32_t)(flag_get(g_flags + FL_LN2) - ep * 8) < 0) { SPIN_GUARD(n); __nanosleep(200); }
                const uint4 v = __ldcg((const uint4*)(g_par2 + j * 128) + lane);
                sts128(sb + OFF_PAR + lane * 16, v.x, v.y, v.z, v.w);
                __syncwarp();
                if (lane == 0) mbar_arrive(BAR_ONE(sb, EV_LN2));
            }
            mbar_wait(BAR_ONE(sb, EV_X1S + w), 0);
            if (el) {
                tma_store(&mp.x1, j * 128, row0, sb + (X1_SLOT + 2 - 2 * w) * SLOT); tma_store(&mp.x1, j * 128 + 64, row0, sb + (X1_SLOT + 3 - 2 * w) * SLOT);
                bulk_commit(); bulk_wait_read(); mbar_arrive(BAR_ONE(sb, EV_X1 + w));
            }
            send2(&mp.h2s, ST_H2);
            if (el) { prefetch_map(&mp.hb); prefetch_map(&mp.hb3); }
            if (w == 0) TL(37);
            free2();
#pragma unroll 1
            for (int p = 0; p < 3; ++p) {
                const int col = hcol(p, j);
                store(&mp.hb, col); store(&mp.hb, col + 64);
                if (p == 0) {
                    mbar_wait(BAR_ONE(sb, EV_P3 + w), 0);
                    if (el) { tma_store3(&mp.hb3, 0, j, row0, sb + (w ? P3_SLOT1 : P3_SLOT0) * SLOT + 24576); bulk_commit(); }
                }
                if (el) { bulk_wait_all(); flag_set(fl, ep * 8 + ST_H + p); flag_set(fl + FS, ep * 8 + ST_H + p); }
                if (p < 2) free2();
                if (p == 0 && w == 1) gate(5, EV_GB);
            }
            load2(&mp.x1, false);
            cluster_arrive_early = true;
            cluster_arrive();
            store(&mp.out, j * 128, true); store(&mp.out, j * 128 + 64, true);
            if (el) bulk_wait_read();
        }
        __syncwarp();
    }
    if (aux || (wg == 2 && !cluster_arrive_early)) cluster_arrive();
    cluster_wait();
    if (tid == 0) {
        TL(15);
        flag_add(pt.mail->flags + FL_DONE);
    }
}

typedef CUresult (*EncodeFn)(CUtensorMap*, CUtensorMapDataType, cuuint32_t, void*, const cuuint64_t*, const cuuint64_t*, const cuuint32_t*,
                             const cuuint32_t*, CUtensorMapInterleave, CUtensorMapSwizzle, CUtensorMapL2promotion, CUtensorMapFloatOOBfill);

void make_map(EncodeFn fn, CUtensorMap* m, const void* ptr, uint64_t rows, uint64_t cols, uint32_t brows, uint32_t bcols) {
    cuuint64_t dims[2] = {cols, rows}, strides[1] = {cols * 2};
    cuuint32_t box[2] = {bcols, brows}, es[2] = {1, 1};
    fn(m, CU_TENSOR_MAP_DATA_TYPE_BFLOAT16, 2, (void*)ptr, dims, strides, box, es, CU_TENSOR_MAP_INTERLEAVE_NONE,
       bcols == 64 ? CU_TENSOR_MAP_SWIZZLE_128B : bcols == 32 ? CU_TENSOR_MAP_SWIZZLE_64B : CU_TENSOR_MAP_SWIZZLE_NONE, CU_TENSOR_MAP_L2_PROMOTION_L2_256B, CU_TENSOR_MAP_FLOAT_OOB_FILL_NONE);
}

void make_map3(EncodeFn fn, CUtensorMap* m, const void* ptr) {
    cuuint64_t dims[3] = {D_, S_ / 2, 2}, strides[2] = {4 * D_, 2 * D_};
    cuuint32_t box[3] = {64, 32, 2}, es[3] = {1, 1, 1};
    fn(m, CU_TENSOR_MAP_DATA_TYPE_BFLOAT16, 3, (void*)ptr, dims, strides, box, es, CU_TENSOR_MAP_INTERLEAVE_NONE,
       CU_TENSOR_MAP_SWIZZLE_128B, CU_TENSOR_MAP_L2_PROMOTION_L2_256B, CU_TENSOR_MAP_FLOAT_OOB_FILL_NONE);
}

void make_map48(EncodeFn fn, CUtensorMap* m, const void* ptr, uint64_t rows, uint32_t brows) {
    cuuint64_t dims[3] = {48, 8, rows}, strides[2] = {96, 2 * F_};
    cuuint32_t box[3] = {64, 1, brows}, es[3] = {1, 1, 1};
    fn(m, CU_TENSOR_MAP_DATA_TYPE_BFLOAT16, 3, (void*)ptr, dims, strides, box, es, CU_TENSOR_MAP_INTERLEAVE_NONE,
       CU_TENSOR_MAP_SWIZZLE_128B, CU_TENSOR_MAP_L2_PROMOTION_L2_256B, CU_TENSOR_MAP_FLOAT_OOB_FILL_NONE);
}

}

extern "C" void kernel_launch(void* const* d_in, const int* in_sizes, int n_in, void* d_out, int out_size) {
    (void)in_sizes; (void)n_in; (void)out_size;
    void* fnp = nullptr;
    cudaDriverEntryPointQueryResult qr;
    cudaGetDriverEntryPoint("cuTensorMapEncodeTiled", &fnp, cudaEnableDefault, &qr);
    EncodeFn fn = (EncodeFn)fnp;
    void *h1, *o, *x1, *h2, *hb, *mail;
    cudaGetSymbolAddress(&h1, g_h1);
    cudaGetSymbolAddress(&mail, g_mail);
    cudaGetSymbolAddress(&o, g_o);
    cudaGetSymbolAddress(&hb, g_hb);
    x1 = h1; h2 = o;
    Maps mp;
    make_map(fn, &mp.h1h, h1, S_, D_, 64, 32);
    make_map(fn, &mp.h2h, h2, S_, D_, 64, 32);
    make_map(fn, &mp.h1s, h1, S_, D_, 64, 64);
    make_map(fn, &mp.o, o, S_, D_, 64, 64);
    make_map(fn, &mp.h2l, h2, S_, D_, 128, 32);
    make_map(fn, &mp.h2s, h2, S_, D_, 64, 64);
    make_map(fn, &mp.hb, hb, S_, F_, 64, 64);
    make_map(fn, &mp.wqkv, d_in[1], D_, 3 * D_, 32, 64);
    make_map(fn, &mp.wo, d_in[2], D_, D_, 64, 64);
    make_map(fn, &mp.wg, d_in[4], D_, F_, 32, 64);
    make_map(fn, &mp.wu, d_in[5], D_, F_, 32, 64);
    make_map(fn, &mp.wd, d_in[6], F_, D_, 64, 64);
    make_map(fn, &mp.wmod, d_in[8], D_, 6 * D_, 64, 64);
    make_map(fn, &mp.wm8, d_in[8], D_ / 8, 8 * 6 * D_, 128, 16);
    make_map3(fn, &mp.x, d_in[0]);
    make_map(fn, &mp.x1, x1, S_, D_, 64, 64);
    make_map3(fn, &mp.out, d_out);
    make_map48(fn, &mp.wg3, d_in[4], D_, 32);
    make_map48(fn, &mp.wu3, d_in[5], D_, 32);
    make_map48(fn, &mp.hb3, hb, S_, 64);
    cudaFuncSetAttribute(fused_block_kernel, cudaFuncAttributeMaxDynamicSharedMemorySize, SMEM_BYTES);
    cudaLaunchConfig_t cfg = {};
    cfg.gridDim = dim3(NCTA); cfg.blockDim = dim3(384); cfg.dynamicSmemBytes = SMEM_BYTES; cfg.stream = cudaStreamPerThread;
    cudaLaunchAttribute at[1];
    at[0].id = cudaLaunchAttributeClusterDimension; at[0].val.clusterDim.x = 2; at[0].val.clusterDim.y = 1; at[0].val.clusterDim.z = 1;
    cfg.attrs = at; cfg.numAttrs = 1;
    const Ptrs pt{(const __nv_bfloat16*)d_in[7], (Mail*)mail};
    cudaLaunchKernelEx(&cfg, fused_block_kernel, pt, mp);
}
```

```cpp
#include <cuda_runtime.h>
#include <cuda_bf16.h>
#include <cuda.h>
#include <stdint.h>
#include <stddef.h>

#define LAG 3
#define LAGS 3
#define LAGW 3
#define LAGQ 4
#define MIDW 8
#define PFWO 14
#define FLAGRED 1
#define FS 1
#define AGO 7
#define AGW 6
#define CSW 0
#define FENCES 1
#define LWAIT 2
#define BW0 0
#define BWEV EV_WIN
#define GODLY 0
#define BW1 3
#define KDEBUG 0

namespace {

constexpr int S_ = 2048, D_ = 1024, F_ = 3584;
constexpr int NCTA = 132;
constexpr int NSLOT = 6;
constexpr uint32_t SLOT = 32768;
constexpr uint32_t OFF_STG = NSLOT * SLOT;
constexpr uint32_t OFF_BAR = OFF_STG + 32768;
constexpr uint32_t OFF_PAR = OFF_BAR + 512;
constexpr uint32_t OFF_TAB = OFF_PAR + 768;
constexpr uint32_t OFF_TL = OFF_PAR + 2048;
constexpr uint32_t SMEM_BYTES = OFF_TL + (KDEBUG ? 512 : 0);
constexpr uint32_t P3_SLOT1 = (32 + 16 + 32) % NSLOT, P3_SLOT0 = (P3_SLOT1 + 1) % NSLOT;

constexpr uint32_t X1_SLOT = (32 + 16) % NSLOT;
static_assert(X1_SLOT + 3 < NSLOT && LAGW <= 4, "x1 parking");
constexpr int ST_H1 = 1, ST_O = 2, ST_H2 = 3, ST_H = 4, FL_DONE = 0, FL_LN2 = 1, FL_AUX = 32, FL_PROG = 64;

struct Maps {
    CUtensorMap h1h, h1s, o, h2h, h2l, h2s, hb, wqkv, wo, wg, wu, wd, wmod, wm8, x, x1, out, wg3, wu3, hb3;
};

struct Mail {
    uint32_t flags[16 * 32 * FS + 64];
    uint2 mod[6 * D_ / 2];
    uint4 mod1[8 * 512];
    uint4 st1[128 * 512];
    uint32_t par2[D_];
    uint4 halo[128 * 512];
};
struct Ptrs { const __nv_bfloat16* c; Mail* mail; };

__device__ __align__(128) Mail g_mail;
__device__ __align__(128) __nv_bfloat16 g_h1[S_ * D_];
__device__ __align__(128) __nv_bfloat16 g_o[S_ * D_];
__device__ __align__(128) __nv_bfloat16 g_hb[S_ * F_];
#define TL(i) do {} while (0)
#define TC(i) do {} while (0)
#define TS(g, which) do {} while (0)
#define CS(i) do {} while (0)

#define PS(i) do {} while (0)
__device__ __forceinline__ uint32_t smem_u32(const void* p) { return (uint32_t)__cvta_generic_to_shared(p); }
__device__ __forceinline__ void mbar_init(uint32_t bar, uint32_t cnt) { asm volatile("mbarrier.init.shared::cta.b64 [%0], %1;" :: "r"(bar), "r"(cnt) : "memory"); }
__device__ __forceinline__ void mbar_expect_tx(uint32_t bar, uint32_t bytes) { asm volatile("mbarrier.arrive.expect_tx.shared::cta.b64 _, [%0], %1;" :: "r"(bar), "r"(bytes) : "memory"); }
__device__ __forceinline__ void mbar_arrive(uint32_t bar) { asm volatile("mbarrier.arrive.shared::cta.b64 _, [%0];" :: "r"(bar) : "memory"); }
__device__ __forceinline__ void mbar_arrive_cta(uint32_t bar, uint32_t cta) {
    asm volatile("{\n.reg .b32 r;\nmapa.shared::cluster.u32 r, %0, %1;\nmbarrier.arrive.shared::cluster.b64 _, [r];\n}" :: "r"(bar), "r"(cta) : "memory");
}
__device__ __forceinline__ void mbar_wait(uint32_t bar, uint32_t parity) {
    asm volatile("{\n.reg .pred p;\n.reg .u32 n;\nmov.u32 n, 0;\n"
        "W_LOOP:\nmbarrier.try_wait.parity.shared::cta.b64 p, [%0], %1;\n@p bra W_DONE;\n"
        "add.u32 n, n, 1;\nsetp.lt.u32 p, n, 0x400000;\n@p bra W_LOOP;\ntrap;\nW_DONE:\n}" :: "r"(bar), "r"(parity) : "memory");
}
__device__ __forceinline__ void mbar_wait2(uint32_t b0, uint32_t b1, uint32_t parity) {
    asm volatile("{\n.reg .pred p, q;\n.reg .u32 n;\nmov.u32 n, 0;\n"
        "W_LOOP:\nmbarrier.try_wait.parity.shared::cta.b64 p, [%0], %2;\nmbarrier.try_wait.parity.shared::cta.b64 q, [%1], %2;\nand.pred p, p, q;\n@p bra W_DONE;\n"
        "add.u32 n, n, 1;\nsetp.lt.u32 p, n, 0x400000;\n@p bra W_LOOP;\ntrap;\nW_DONE:\n}" :: "r"(b0), "r"(b1), "r"(parity) : "memory");
}
__device__ __forceinline__ bool mbar_test(uint32_t bar, uint32_t parity) {
    uint32_t r; asm volatile("{\n.reg .pred p;\nmbarrier.test_wait.parity.shared::cta.b64 p, [%1], %2;\nselp.u32 %0, 1, 0, p;\n}" : "=r"(r) : "r"(bar), "r"(parity) : "memory"); return r;
}
__device__ __forceinline__ bool mbar_test2(uint32_t b0, uint32_t b1, uint32_t parity) {
    uint32_t r;
    asm volatile("{\n.reg .pred p, q;\nmbarrier.test_wait.parity.shared::cta.b64 p, [%1], %3;\nmbarrier.test_wait.parity.shared::cta.b64 q, [%2], %3;\n"
        "and.pred p, p, q;\nselp.u32 %0, 1, 0, p;\n}" : "=r"(r) : "r"(b0), "r"(b1), "r"(parity) : "memory");
    return r;
}
__device__ __forceinline__ void tma_load3(uint32_t dst, const CUtensorMap* m, int c0, int c1, uint32_t bar) {
    asm volatile("cp.async.bulk.tensor.3d.shared::cluster.global.mbarrier::complete_tx::bytes [%0], [%1, {%3, %4, %5}], [%2];"
        :: "r"(dst), "l"(m), "r"(bar), "r"(c0), "r"(c1), "r"(0) : "memory");
}
__device__ __forceinline__ void tma_store3(const CUtensorMap* m, int c0, int c1, int c2, uint32_t src) {
    asm volatile("cp.async.bulk.tensor.3d.global.shared::cta.bulk_group [%0, {%2, %3, %4}], [%1];" :: "l"(m), "r"(src), "r"(c0), "r"(c1), "r"(c2) : "memory");
}
__device__ __forceinline__ void tma_load3_mc(uint32_t dst, const CUtensorMap* m, int c1, int c2, uint32_t bar) {
    asm volatile("cp.async.bulk.tensor.3d.shared::cluster.global.mbarrier::complete_tx::bytes.multicast::cluster.L2::cache_hint [%0], [%1, {%3, %4, %5}], [%2], %6, %7;"
        :: "r"(dst), "l"(m), "r"(bar), "r"(0), "r"(c1), "r"(c2), "h"((uint16_t)3), "l"(0x12F0000000000000ull) : "memory");
}
__device__ __forceinline__ void tma_load(uint32_t dst, const CUtensorMap* m, int c0, int c1, uint32_t bar) {
    asm volatile("cp.async.bulk.tensor.2d.shared::cluster.global.mbarrier::complete_tx::bytes [%0], [%1, {%3, %4}], [%2];"
        :: "r"(dst), "l"(m), "r"(bar), "r"(c0), "r"(c1) : "memory");
}
__device__ __forceinline__ void tma_load_mc(uint32_t dst, const CUtensorMap* m, int c0, int c1, uint32_t bar) {
    asm volatile("cp.async.bulk.tensor.2d.shared::cluster.global.mbarrier::complete_tx::bytes.multicast::cluster.L2::cache_hint [%0], [%1, {%3, %4}], [%2], %5, %6;"
        :: "r"(dst), "l"(m), "r"(bar), "r"(c0), "r"(c1), "h"((uint16_t)3), "l"(0x12F0000000000000ull) : "memory");
}
__device__ __forceinline__ void tma_prefetch(const CUtensorMap* m, int c0, int c1) {
    asm volatile("cp.async.bulk.prefetch.tensor.2d.L2.global [%0, {%1, %2}];" :: "l"(m), "r"(c0), "r"(c1) : "memory");
}
__device__ __forceinline__ void tma_store(const CUtensorMap* m, int c0, int c1, uint32_t src) {
    asm volatile("cp.async.bulk.tensor.2d.global.shared::cta.bulk_group [%0, {%2, %3}], [%1];" :: "l"(m), "r"(src), "r"(c0), "r"(c1) : "memory");
}
__device__ __forceinline__ void bulk_commit() { asm volatile("cp.async.bulk.commit_group;" ::: "memory"); }
__device__ __forceinline__ void bulk_wait_read() { asm volatile("cp.async.bulk.wait_group.read 0;" ::: "memory"); }
__device__ __forceinline__ void bulk_wait_all() { asm volatile("cp.async.bulk.wait_group 0;" ::: "memory"); }
__device__ __forceinline__ void fence_async_smem() { asm volatile("fence.proxy.async.shared::cta;" ::: "memory"); }
__device__ __forceinline__ void prefetch_map(const CUtensorMap* m) { asm volatile("prefetch.tensormap [%0];" :: "l"(m) : "memory"); }
__device__ __forceinline__ void wg_fence() { asm volatile("wgmma.fence.sync.aligned;" ::: "memory"); }
__device__ __forceinline__ void wg_commit() { asm volatile("wgmma.commit_group.sync.aligned;" ::: "memory"); }
template <int N> __device__ __forceinline__ void wg_wait() { asm volatile("wgmma.wait_group.sync.aligned %0;" :: "n"(N) : "memory"); }
__device__ __forceinline__ void bar_sync(int id, int n) { asm volatile("bar.sync %0, %1;" :: "r"(id), "r"(n) : "memory"); }
__device__ __forceinline__ void bar_arrive(int id, int n) { asm volatile("bar.arrive %0, %1;" :: "r"(id), "r"(n) : "memory"); }
__device__ __forceinline__ void flag_add(uint32_t* f) { asm volatile("red.relaxed.gpu.global.add.u32 [%0], 1;" :: "l"(f) : "memory"); }
__device__ __forceinline__ void flag_set(uint32_t* f, uint32_t v) { asm volatile("red.relaxed.gpu.global.max.u32 [%0], %1;" :: "l"(f), "r"(v) : "memory"); }
__device__ __forceinline__ uint32_t flag_get(const uint32_t* f) { uint32_t v; asm volatile("ld.relaxed.gpu.global.u32 %0, [%1];" : "=r"(v) : "l"(f) : "memory"); return v; }
__device__ __forceinline__ uint32_t d16(uint32_t addr) { return (addr & 0x3FFFF) >> 4; }
__device__ __forceinline__ uint64_t mk_desc(uint32_t a16, uint32_t off, uint32_t lbo, uint32_t sbo, uint32_t swz) {
    const uint32_t lo = a16 + (off >> 4) + ((lbo >> 4) << 16), hi = (sbo >> 4) | (swz << 30);
    return ((uint64_t)hi << 32) | lo;
}
__device__ __forceinline__ uint32_t pack2(float lo, float hi) {
    uint32_t r; asm("cvt.rn.bf16x2.f32 %0, %1, %2;" : "=r"(r) : "f"(hi), "f"(lo)); return r;
}
__device__ __forceinline__ uint32_t hfma2_bf16(uint32_t a, uint32_t b, uint32_t c) {
    uint32_t r; asm("fma.rn.bf16x2 %0, %1, %2, %3;" : "=r"(r) : "r"(a), "r"(b), "r"(c)); return r;
}
__device__ __forceinline__ float bf_lo(uint32_t v) { return __uint_as_float(v << 16); }
__device__ __forceinline__ float bf_hi(uint32_t v) { return __uint_as_float(v & 0xFFFF0000u); }
__device__ __forceinline__ void unpack2(uint32_t v, float& lo, float& hi) {
    asm volatile("shl.b32 %0, %2, 16;\nand.b32 %1, %2, 0xffff0000;" : "=f"(lo), "=f"(hi) : "r"(v));
}
__device__ __forceinline__ float bf_round(float x) { return __bfloat162float(__float2bfloat16_rn(x)); }
__device__ __forceinline__ void stsm4(uint32_t addr, uint32_t r0, uint32_t r1, uint32_t r2, uint32_t r3) {
    asm volatile("stmatrix.sync.aligned.m8n8.x4.shared.b16 [%0], {%1, %2, %3, %4};" :: "r"(addr), "r"(r0), "r"(r1), "r"(r2), "r"(r3) : "memory");
}
__device__ __forceinline__ void stsm4t(uint32_t addr, uint32_t r0, uint32_t r1, uint32_t r2, uint32_t r3) {
    asm volatile("stmatrix.sync.aligned.m8n8.x4.trans.shared.b16 [%0], {%1, %2, %3, %4};" :: "r"(addr), "r"(r0), "r"(r1), "r"(r2), "r"(r3) : "memory");
}
__device__ __forceinline__ uint32_t movm(uint32_t a) { uint32_t d; asm volatile("movmatrix.sync.aligned.m8n8.trans.b16 %0, %1;" : "=r"(d) : "r"(a)); return d; }
__device__ __forceinline__ void ldsm4(uint32_t addr, uint32_t& r0, uint32_t& r1, uint32_t& r2, uint32_t& r3) {
    asm volatile("ldmatrix.sync.aligned.m8n8.x4.shared.b16 {%0, %1, %2, %3}, [%4];" : "=r"(r0), "=r"(r1), "=r"(r2), "=r"(r3) : "r"(addr) : "memory");
}
__device__ __forceinline__ void ldsm4t(uint32_t addr, uint32_t& r0, uint32_t& r1, uint32_t& r2, uint32_t& r3) {
    asm volatile("ldmatrix.sync.aligned.m8n8.x4.trans.shared.b16 {%0, %1, %2, %3}, [%4];" : "=r"(r0), "=r"(r1), "=r"(r2), "=r"(r3) : "r"(addr) : "memory");
}
__device__ __forceinline__ void mma16816(float (&c)[4], uint32_t a0, uint32_t a1, uint32_t a2, uint32_t a3, uint32_t b0, uint32_t b1) {
    asm("mma.sync.aligned.m16n8k16.row.col.f32.bf16.bf16.f32 {%0, %1, %2, %3}, {%4, %5, %6, %7}, {%8, %9}, {%0, %1, %2, %3};"
        : "+f"(c[0]), "+f"(c[1]), "+f"(c[2]), "+f"(c[3]) : "r"(a0), "r"(a1), "r"(a2), "r"(a3), "r"(b0), "r"(b1));
}
__device__ __forceinline__ float rcp(float x) { float r; asm("rcp.approx.ftz.f32 %0, %1;" : "=f"(r) : "f"(x)); return r; }
__device__ __forceinline__ float ex2(float x) { float r; asm("ex2.approx.ftz.f32 %0, %1;" : "=f"(r) : "f"(x)); return r; }
__device__ __forceinline__ float glu_half(float gh, float uh) {
    float t; asm("tanh.approx.f32 %0, %1;" : "=f"(t) : "f"(gh)); return fmaf(t, uh, uh);
}
__device__ __forceinline__ float silu_(float x) { return __fdividef(x, 1.f + __expf(-x)); }
__device__ __forceinline__ void st_pkt(void* p, uint32_t a, uint32_t b) {
    asm volatile("{\n.reg .b64 t;\nmov.b64 t, {%1, %2};\nst.relaxed.gpu.global.b64 [%0], t;\n}" :: "l"(p), "r"(a), "r"(b) : "memory");
}
__device__ __forceinline__ uint4 ld_pkt2(const void* p) {
    uint4 v; asm volatile("{\n.reg .b64 t, u;\nld.relaxed.gpu.global.v2.b64 {t, u}, [%4];\nmov.b64 {%0, %1}, t;\nmov.b64 {%2, %3}, u;\n}"
        : "=r"(v.x), "=r"(v.y), "=r"(v.z), "=r"(v.w) : "l"(p) : "memory"); return v;
}
__device__ __forceinline__ void st_pkt16(void* p, uint32_t a, uint32_t b, uint32_t c, uint32_t d) {
    asm volatile("{\n.reg .b64 t, u;\n.reg .b128 w;\nmov.b64 t, {%1, %2};\nmov.b64 u, {%3, %4};\nmov.b128 w, {t, u};\nst.relaxed.gpu.global.b128 [%0], w;\n}"
        :: "l"(p), "r"(a), "r"(b), "r"(c), "r"(d) : "memory");
}
__device__ __forceinline__ uint4 ld_pkt16(const void* p) {
    uint4 v; asm volatile("{\n.reg .b64 t, u;\n.reg .b128 w;\nld.relaxed.gpu.global.b128 w, [%4];\nmov.b128 {t, u}, w;\nmov.b64 {%0, %1}, t;\nmov.b64 {%2, %3}, u;\n}"
        : "=r"(v.x), "=r"(v.y), "=r"(v.z), "=r"(v.w) : "l"(p) : "memory"); return v;
}
#define SPIN_GUARD(n) do { if (++(n) > (1u << 22)) asm volatile("trap;"); } while (0)
__device__ __forceinline__ uint4 lds128(uint32_t a) { uint4 v; asm volatile("ld.shared.v4.u32 {%0, %1, %2, %3}, [%4];" : "=r"(v.x), "=r"(v.y), "=r"(v.z), "=r"(v.w) : "r"(a) : "memory"); return v; }
__device__ __forceinline__ void sts128(uint32_t a, uint32_t x, uint32_t y, uint32_t z, uint32_t w) { asm volatile("st.shared.v4.u32 [%0], {%1, %2, %3, %4};" :: "r"(a), "r"(x), "r"(y), "r"(z), "r"(w) : "memory"); }
__device__ __forceinline__ uint32_t lds32(uint32_t a) { uint32_t v; asm volatile("ld.shared.u32 %0, [%1];" : "=r"(v) : "r"(a) : "memory"); return v; }
__device__ __forceinline__ void sts32(uint32_t a, uint32_t v) { asm volatile("st.shared.u32 [%0], %1;" :: "r"(a), "r"(v) : "memory"); }
__device__ __forceinline__ bool elect_one() {
    uint32_t p; asm volatile("{\n.reg .pred q;\nelect.sync _|q, 0xffffffff;\nselp.u32 %0, 1, 0, q;\n}" : "=r"(p)); return p;
}
__device__ __forceinline__ void cluster_arrive() { asm volatile("barrier.cluster.arrive.relaxed.aligned;" ::: "memory"); }
__device__ __forceinline__ void cluster_wait() { asm volatile("barrier.cluster.wait.aligned;" ::: "memory"); }

__device__ __forceinline__ void wgmma_n128_z(float (&d)[64], uint64_t da, uint64_t db) {
    asm volatile("{\n.reg .pred p;\nsetp.ne.b32 p, 0, 0;\n"
        "wgmma.mma_async.sync.aligned.m64n128k16.f32.bf16.bf16 {"
        "%0, %1, %2, %3, %4, %5, %6, %7, %8, %9, %10, %11, %12, %13, %14, %15, "
        "%16, %17, %18, %19, %20, %21, %22, %23, %24, %25, %26, %27, %28, %29, %30, %31, "
        "%32, %33, %34, %35, %36, %37, %38, %39, %40, %41, %42, %43, %44, %45, %46, %47, "
        "%48, %49, %50, %51, %52, %53, %54, %55, %56, %57, %58, %59, %60, %61, %62, %63"
        "}, %64, %65, p, 1, 1, 0, 1;\n}\n"
        : "=f"(d[0]), "=f"(d[1]), "=f"(d[2]), "=f"(d[3]), "=f"(d[4]), "=f"(d[5]), "=f"(d[6]), "=f"(d[7]),
          "=f"(d[8]), "=f"(d[9]), "=f"(d[10]), "=f"(d[11]), "=f"(d[12]), "=f"(d[13]), "=f"(d[14]), "=f"(d[15]),
          "=f"(d[16]), "=f"(d[17]), "=f"(d[18]), "=f"(d[19]), "=f"(d[20]), "=f"(d[21]), "=f"(d[22]), "=f"(d[23]),
          "=f"(d[24]), "=f"(d[25]), "=f"(d[26]), "=f"(d[27]), "=f"(d[28]), "=f"(d[29]), "=f"(d[30]), "=f"(d[31]),
          "=f"(d[32]), "=f"(d[33]), "=f"(d[34]), "=f"(d[35]), "=f"(d[36]), "=f"(d[37]), "=f"(d[38]), "=f"(d[39]),
          "=f"(d[40]), "=f"(d[41]), "=f"(d[42]), "=f"(d[43]), "=f"(d[44]), "=f"(d[45]), "=f"(d[46]), "=f"(d[47]),
          "=f"(d[48]), "=f"(d[49]), "=f"(d[50]), "=f"(d[51]), "=f"(d[52]), "=f"(d[53]), "=f"(d[54]), "=f"(d[55]),
          "=f"(d[56]), "=f"(d[57]), "=f"(d[58]), "=f"(d[59]), "=f"(d[60]), "=f"(d[61]), "=f"(d[62]), "=f"(d[63])
        : "l"(da), "l"(db));
}
__device__ __forceinline__ void wgmma_n128(float (&d)[64], uint64_t da, uint64_t db) {
    asm volatile("{\n.reg .pred p;\nsetp.eq.b32 p, 0, 0;\n"
        "wgmma.mma_async.sync.aligned.m64n128k16.f32.bf16.bf16 {"
        "%0, %1, %2, %3, %4, %5, %6, %7, %8, %9, %10, %11, %12, %13, %14, %15, "
        "%16, %17, %18, %19, %20, %21, %22, %23, %24, %25, %26, %27, %28, %29, %30, %31, "
        "%32, %33, %34, %35, %36, %37, %38, %39, %40, %41, %42, %43, %44, %45, %46, %47, "
        "%48, %49, %50, %51, %52, %53, %54, %55, %56, %57, %58, %59, %60, %61, %62, %63"
        "}, %64, %65, p, 1, 1, 0, 1;\n}\n"
        : "+f"(d[0]), "+f"(d[1]), "+f"(d[2]), "+f"(d[3]), "+f"(d[4]), "+f"(d[5]), "+f"(d[6]), "+f"(d[7]),
          "+f"(d[8]), "+f"(d[9]), "+f"(d[10]), "+f"(d[11]), "+f"(d[12]), "+f"(d[13]), "+f"(d[14]), "+f"(d[15]),
          "+f"(d[16]), "+f"(d[17]), "+f"(d[18]), "+f"(d[19]), "+f"(d[20]), "+f"(d[21]), "+f"(d[22]), "+f"(d[23]),
          "+f"(d[24]), "+f"(d[25]), "+f"(d[26]), "+f"(d[27]), "+f"(d[28]), "+f"(d[29]), "+f"(d[30]), "+f"(d[31]),
          "+f"(d[32]), "+f"(d[33]), "+f"(d[34]), "+f"(d[35]), "+f"(d[36]), "+f"(d[37]), "+f"(d[38]), "+f"(d[39]),
          "+f"(d[40]), "+f"(d[41]), "+f"(d[42]), "+f"(d[43]), "+f"(d[44]), "+f"(d[45]), "+f"(d[46]), "+f"(d[47]),
          "+f"(d[48]), "+f"(d[49]), "+f"(d[50]), "+f"(d[51]), "+f"(d[52]), "+f"(d[53]), "+f"(d[54]), "+f"(d[55]),
          "+f"(d[56]), "+f"(d[57]), "+f"(d[58]), "+f"(d[59]), "+f"(d[60]), "+f"(d[61]), "+f"(d[62]), "+f"(d[63])
        : "l"(da), "l"(db));
}
__device__ __forceinline__ void wgmma_n176_z(float (&d)[88], uint64_t da, uint64_t db) {
    asm volatile("{\n.reg .pred p;\nsetp.ne.b32 p, 0, 0;\n"
        "wgmma.mma_async.sync.aligned.m64n176k16.f32.bf16.bf16 {"
        "%0, %1, %2, %3, %4, %5, %6, %7, %8, %9, %10, %11, %12, %13, %14, %15, "
        "%16, %17, %18, %19, %20, %21, %22, %23, %24, %25, %26, %27, %28, %29, %30, %31, "
        "%32, %33, %34, %35, %36, %37, %38, %39, %40, %41, %42, %43, %44, %45, %46, %47, "
        "%48, %49, %50, %51, %52, %53, %54, %55, %56, %57, %58, %59, %60, %61, %62, %63, "
        "%64, %65, %66, %67, %68, %69, %70, %71, %72, %73, %74, %75, %76, %77, %78, %79, "
        "%80, %81, %82, %83, %84, %85, %86, %87"
        "}, %88, %89, p, 1, 1, 0, 1;\n}\n"
        : "=f"(d[0]), "=f"(d[1]), "=f"(d[2]), "=f"(d[3]), "=f"(d[4]), "=f"(d[5]), "=f"(d[6]), "=f"(d[7]),
          "=f"(d[8]), "=f"(d[9]), "=f"(d[10]), "=f"(d[11]), "=f"(d[12]), "=f"(d[13]), "=f"(d[14]), "=f"(d[15]),
          "=f"(d[16]), "=f"(d[17]), "=f"(d[18]), "=f"(d[19]), "=f"(d[20]), "=f"(d[21]), "=f"(d[22]), "=f"(d[23]),
          "=f"(d[24]), "=f"(d[25]), "=f"(d[26]), "=f"(d[27]), "=f"(d[28]), "=f"(d[29]), "=f"(d[30]), "=f"(d[31]),
          "=f"(d[32]), "=f"(d[33]), "=f"(d[34]), "=f"(d[35]), "=f"(d[36]), "=f"(d[37]), "=f"(d[38]), "=f"(d[39]),
          "=f"(d[40]), "=f"(d[41]), "=f"(d[42]), "=f"(d[43]), "=f"(d[44]), "=f"(d[45]), "=f"(d[46]), "=f"(d[47]),
          "=f"(d[48]), "=f"(d[49]), "=f"(d[50]), "=f"(d[51]), "=f"(d[52]), "=f"(d[53]), "=f"(d[54]), "=f"(d[55]),
          "=f"(d[56]), "=f"(d[57]), "=f"(d[58]), "=f"(d[59]), "=f"(d[60]), "=f"(d[61]), "=f"(d[62]), "=f"(d[63]),
          "=f"(d[64]), "=f"(d[65]), "=f"(d[66]), "=f"(d[67]), "=f"(d[68]), "=f"(d[69]), "=f"(d[70]), "=f"(d[71]),
          "=f"(d[72]), "=f"(d[73]), "=f"(d[74]), "=f"(d[75]), "=f"(d[76]), "=f"(d[77]), "=f"(d[78]), "=f"(d[79]),
          "=f"(d[80]), "=f"(d[81]), "=f"(d[82]), "=f"(d[83]), "=f"(d[84]), "=f"(d[85]), "=f"(d[86]), "=f"(d[87])
        : "l"(da), "l"(db));
}
__device__ __forceinline__ void wgmma_n176(float (&d)[88], uint64_t da, uint64_t db) {
    asm volatile("{\n.reg .pred p;\nsetp.eq.b32 p, 0, 0;\n"
        "wgmma.mma_async.sync.aligned.m64n176k16.f32.bf16.bf16 {"
        "%0, %1, %2, %3, %4, %5, %6, %7, %8, %9, %10, %11, %12, %13, %14, %15, "
        "%16, %17, %18, %19, %20, %21, %22, %23, %24, %25, %26, %27, %28, %29, %30, %31, "
        "%32, %33, %34, %35, %36, %37, %38, %39, %40, %41, %42, %43, %44, %45, %46, %47, "
        "%48, %49, %50, %51, %52, %53, %54, %55, %56, %57, %58, %59, %60, %61, %62, %63, "
        "%64, %65, %66, %67, %68, %69, %70, %71, %72, %73, %74, %75, %76, %77, %78, %79, "
        "%80, %81, %82, %83, %84, %85, %86, %87"
        "}, %88, %89, p, 1, 1, 0, 1;\n}\n"
        : "+f"(d[0]), "+f"(d[1]), "+f"(d[2]), "+f"(d[3]), "+f"(d[4]), "+f"(d[5]), "+f"(d[6]), "+f"(d[7]),
          "+f"(d[8]), "+f"(d[9]), "+f"(d[10]), "+f"(d[11]), "+f"(d[12]), "+f"(d[13]), "+f"(d[14]), "+f"(d[15]),
          "+f"(d[16]), "+f"(d[17]), "+f"(d[18]), "+f"(d[19]), "+f"(d[20]), "+f"(d[21]), "+f"(d[22]), "+f"(d[23]),
          "+f"(d[24]), "+f"(d[25]), "+f"(d[26]), "+f"(d[27]), "+f"(d[28]), "+f"(d[29]), "+f"(d[30]), "+f"(d[31]),
          "+f"(d[32]), "+f"(d[33]), "+f"(d[34]), "+f"(d[35]), "+f"(d[36]), "+f"(d[37]), "+f"(d[38]), "+f"(d[39]),
          "+f"(d[40]), "+f"(d[41]), "+f"(d[42]), "+f"(d[43]), "+f"(d[44]), "+f"(d[45]), "+f"(d[46]), "+f"(d[47]),
          "+f"(d[48]), "+f"(d[49]), "+f"(d[50]), "+f"(d[51]), "+f"(d[52]), "+f"(d[53]), "+f"(d[54]), "+f"(d[55]),
          "+f"(d[56]), "+f"(d[57]), "+f"(d[58]), "+f"(d[59]), "+f"(d[60]), "+f"(d[61]), "+f"(d[62]), "+f"(d[63]),
          "+f"(d[64]), "+f"(d[65]), "+f"(d[66]), "+f"(d[67]), "+f"(d[68]), "+f"(d[69]), "+f"(d[70]), "+f"(d[71]),
          "+f"(d[72]), "+f"(d[73]), "+f"(d[74]), "+f"(d[75]), "+f"(d[76]), "+f"(d[77]), "+f"(d[78]), "+f"(d[79]),
          "+f"(d[80]), "+f"(d[81]), "+f"(d[82]), "+f"(d[83]), "+f"(d[84]), "+f"(d[85]), "+f"(d[86]), "+f"(d[87])
        : "l"(da), "l"(db));
}
__device__ __forceinline__ void wgmma_n256_z(float (&d)[128], uint64_t da, uint64_t db) {
    asm volatile("{\n.reg .pred p;\nsetp.ne.b32 p, 0, 0;\n"
        "wgmma.mma_async.sync.aligned.m64n256k16.f32.bf16.bf16 {"
        "%0, %1, %2, %3, %4, %5, %6, %7, %8, %9, %10, %11, %12, %13, %14, %15, "
        "%16, %17, %18, %19, %20, %21, %22, %23, %24, %25, %26, %27, %28, %29, %30, %31, "
        "%32, %33, %34, %35, %36, %37, %38, %39, %40, %41, %42, %43, %44, %45, %46, %47, "
        "%48, %49, %50, %51, %52, %53, %54, %55, %56, %57, %58, %59, %60, %61, %62, %63, "
        "%64, %65, %66, %67, %68, %69, %70, %71, %72, %73, %74, %75, %76, %77, %78, %79, "
        "%80, %81, %82, %83, %84, %85, %86, %87, %88, %89, %90, %91, %92, %93, %94, %95, "
        "%96, %97, %98, %99, %100, %101, %102, %103, %104, %105, %106, %107, %108, %109, %110, %111, "
        "%112, %113, %114, %115, %116, %117, %118, %119, %120, %121, %122, %123, %124, %125, %126, %127"
        "}, %128, %129, p, 1, 1, 0, 1;\n}\n"
        : "=f"(d[0]), "=f"(d[1]), "=f"(d[2]), "=f"(d[3]), "=f"(d[4]), "=f"(d[5]), "=f"(d[6]), "=f"(d[7]),
          "=f"(d[8]), "=f"(d[9]), "=f"(d[10]), "=f"(d[11]), "=f"(d[12]), "=f"(d[13]), "=f"(d[14]), "=f"(d[15]),
          "=f"(d[16]), "=f"(d[17]), "=f"(d[18]), "=f"(d[19]), "=f"(d[20]), "=f"(d[21]), "=f"(d[22]), "=f"(d[23]),
          "=f"(d[24]), "=f"(d[25]), "=f"(d[26]), "=f"(d[27]), "=f"(d[28]), "=f"(d[29]), "=f"(d[30]), "=f"(d[31]),
          "=f"(d[32]), "=f"(d[33]), "=f"(d[34]), "=f"(d[35]), "=f"(d[36]), "=f"(d[37]), "=f"(d[38]), "=f"(d[39]),
          "=f"(d[40]), "=f"(d[41]), "=f"(d[42]), "=f"(d[43]), "=f"(d[44]), "=f"(d[45]), "=f"(d[46]), "=f"(d[47]),
          "=f"(d[48]), "=f"(d[49]), "=f"(d[50]), "=f"(d[51]), "=f"(d[52]), "=f"(d[53]), "=f"(d[54]), "=f"(d[55]),
          "=f"(d[56]), "=f"(d[57]), "=f"(d[58]), "=f"(d[59]), "=f"(d[60]), "=f"(d[61]), "=f"(d[62]), "=f"(d[63]),
          "=f"(d[64]), "=f"(d[65]), "=f"(d[66]), "=f"(d[67]), "=f"(d[68]), "=f"(d[69]), "=f"(d[70]), "=f"(d[71]),
          "=f"(d[72]), "=f"(d[73]), "=f"(d[74]), "=f"(d[75]), "=f"(d[76]), "=f"(d[77]), "=f"(d[78]), "=f"(d[79]),
          "=f"(d[80]), "=f"(d[81]), "=f"(d[82]), "=f"(d[83]), "=f"(d[84]), "=f"(d[85]), "=f"(d[86]), "=f"(d[87]),
          "=f"(d[88]), "=f"(d[89]), "=f"(d[90]), "=f"(d[91]), "=f"(d[92]), "=f"(d[93]), "=f"(d[94]), "=f"(d[95]),
          "=f"(d[96]), "=f"(d[97]), "=f"(d[98]), "=f"(d[99]), "=f"(d[100]), "=f"(d[101]), "=f"(d[102]), "=f"(d[103]),
          "=f"(d[104]), "=f"(d[105]), "=f"(d[106]), "=f"(d[107]), "=f"(d[108]), "=f"(d[109]), "=f"(d[110]), "=f"(d[111]),
          "=f"(d[112]), "=f"(d[113]), "=f"(d[114]), "=f"(d[115]), "=f"(d[116]), "=f"(d[117]), "=f"(d[118]), "=f"(d[119]),
          "=f"(d[120]), "=f"(d[121]), "=f"(d[122]), "=f"(d[123]), "=f"(d[124]), "=f"(d[125]), "=f"(d[126]), "=f"(d[127])
        : "l"(da), "l"(db));
}
__device__ __forceinline__ void wgmma_n256(float (&d)[128], uint64_t da, uint64_t db) {
    asm volatile("{\n.reg .pred p;\nsetp.eq.b32 p, 0, 0;\n"
        "wgmma.mma_async.sync.aligned.m64n256k16.f32.bf16.bf16 {"
        "%0, %1, %2, %3, %4, %5, %6, %7, %8, %9, %10, %11, %12, %13, %14, %15, "
        "%16, %17, %18, %19, %20, %21, %22, %23, %24, %25, %26, %27, %28, %29, %30, %31, "
        "%32, %33, %34, %35, %36, %37, %38, %39, %40, %41, %42, %43, %44, %45, %46, %47, "
        "%48, %49, %50, %51, %52, %53, %54, %55, %56, %57, %58, %59, %60, %61, %62, %63, "
        "%64, %65, %66, %67, %68, %69, %70, %71, %72, %73, %74, %75, %76, %77, %78, %79, "
        "%80, %81, %82, %83, %84, %85, %86, %87, %88, %89, %90, %91, %92, %93, %94, %95, "
        "%96, %97, %98, %99, %100, %101, %102, %103, %104, %105, %106, %107, %108, %109, %110, %111, "
        "%112, %113, %114, %115, %116, %117, %118, %119, %120, %121, %122, %123, %124, %125, %126, %127"
        "}, %128, %129, p, 1, 1, 0, 1;\n}\n"
        : "+f"(d[0]), "+f"(d[1]), "+f"(d[2]), "+f"(d[3]), "+f"(d[4]), "+f"(d[5]), "+f"(d[6]), "+f"(d[7]),
          "+f"(d[8]), "+f"(d[9]), "+f"(d[10]), "+f"(d[11]), "+f"(d[12]), "+f"(d[13]), "+f"(d[14]), "+f"(d[15]),
          "+f"(d[16]), "+f"(d[17]), "+f"(d[18]), "+f"(d[19]), "+f"(d[20]), "+f"(d[21]), "+f"(d[22]), "+f"(d[23]),
          "+f"(d[24]), "+f"(d[25]), "+f"(d[26]), "+f"(d[27]), "+f"(d[28]), "+f"(d[29]), "+f"(d[30]), "+f"(d[31]),
          "+f"(d[32]), "+f"(d[33]), "+f"(d[34]), "+f"(d[35]), "+f"(d[36]), "+f"(d[37]), "+f"(d[38]), "+f"(d[39]),
          "+f"(d[40]), "+f"(d[41]), "+f"(d[42]), "+f"(d[43]), "+f"(d[44]), "+f"(d[45]), "+f"(d[46]), "+f"(d[47]),
          "+f"(d[48]), "+f"(d[49]), "+f"(d[50]), "+f"(d[51]), "+f"(d[52]), "+f"(d[53]), "+f"(d[54]), "+f"(d[55]),
          "+f"(d[56]), "+f"(d[57]), "+f"(d[58]), "+f"(d[59]), "+f"(d[60]), "+f"(d[61]), "+f"(d[62]), "+f"(d[63]),
          "+f"(d[64]), "+f"(d[65]), "+f"(d[66]), "+f"(d[67]), "+f"(d[68]), "+f"(d[69]), "+f"(d[70]), "+f"(d[71]),
          "+f"(d[72]), "+f"(d[73]), "+f"(d[74]), "+f"(d[75]), "+f"(d[76]), "+f"(d[77]), "+f"(d[78]), "+f"(d[79]),
          "+f"(d[80]), "+f"(d[81]), "+f"(d[82]), "+f"(d[83]), "+f"(d[84]), "+f"(d[85]), "+f"(d[86]), "+f"(d[87]),
          "+f"(d[88]), "+f"(d[89]), "+f"(d[90]), "+f"(d[91]), "+f"(d[92]), "+f"(d[93]), "+f"(d[94]), "+f"(d[95]),
          "+f"(d[96]), "+f"(d[97]), "+f"(d[98]), "+f"(d[99]), "+f"(d[100]), "+f"(d[101]), "+f"(d[102]), "+f"(d[103]),
          "+f"(d[104]), "+f"(d[105]), "+f"(d[106]), "+f"(d[107]), "+f"(d[108]), "+f"(d[109]), "+f"(d[110]), "+f"(d[111]),
          "+f"(d[112]), "+f"(d[113]), "+f"(d[114]), "+f"(d[115]), "+f"(d[116]), "+f"(d[117]), "+f"(d[118]), "+f"(d[119]),
          "+f"(d[120]), "+f"(d[121]), "+f"(d[122]), "+f"(d[123]), "+f"(d[124]), "+f"(d[125]), "+f"(d[126]), "+f"(d[127])
        : "l"(da), "l"(db));
}

struct Idx {
    uint32_t lane, warp, w4, q4, g8, prow, pan;
    __device__ __forceinline__ Idx() {
        uint32_t t; asm volatile("mov.u32 %0, %%tid.x;" : "=r"(t));
        lane = t & 31; warp = t >> 5; w4 = warp & 3; q4 = lane & 3; g8 = lane >> 2;
        prow = w4 * 16 + ((lane >> 3) & 1) * 8 + (lane & 7);
        pan = prow * 128 + (((lane >> 4) ^ (lane & 7)) << 4);
    }
};
#define IDX() const Idx ix; const uint32_t lane = ix.lane, warp = ix.warp, w4 = ix.w4, q4 = ix.q4, g8 = ix.g8, prow = ix.prow, pan_addr = ix.pan; \
    (void)lane; (void)warp; (void)w4; (void)q4; (void)g8; (void)prow; (void)pan_addr;

__device__ __forceinline__ int kof(int t, int sh, int j) {
    const int q = (t >> sh) - 1;
    return ((q < 0 ? j : q + (q >= j)) << 7) + ((t & ((1 << sh) - 1)) << (7 - sh));
}
constexpr int HC0 = 8 * 48, HC3 = HC0 + 3072;
__device__ __forceinline__ int hcol(int p, int j) { return HC0 + p * 1024 + j * 128; }
#define SCHED_FENCE(k) do { if ((FENCES >> (k)) & 1) asm volatile("{\n.reg .pred p;\nsetp.ne.u32 p, %0, %1;\n@p bra.uni S_SKIP;\ntrap;\nS_SKIP:\n}" :: "r"(sb), "n"(0xffffff00u + (k))); } while (0)

struct Ring {
    uint32_t slot, par;
    __device__ __forceinline__ void next() { if (++slot == NSLOT) { slot = 0; par ^= 1; } }
    __device__ __forceinline__ void skip(uint32_t n) { slot += n; if (slot >= NSLOT) { slot -= NSLOT; par ^= 1; } }
};
__device__ __forceinline__ uint32_t BAR_FULL(uint32_t sb, uint32_t s) { return sb + OFF_BAR + 8 * s; }
constexpr uint32_t AF_REL = 48;
__device__ __forceinline__ uint32_t BAR_EMPTY(uint32_t sb, uint32_t s) { return sb + OFF_BAR + 96 + 8 * s; }
__device__ __forceinline__ uint32_t BAR_SFULL(uint32_t sb, uint32_t i) { return sb + OFF_BAR + 152 + 8 * i; }
__device__ __forceinline__ uint32_t BAR_SREADY(uint32_t sb, uint32_t i) { return sb + OFF_BAR + 184 + 8 * i; }
__device__ __forceinline__ uint32_t BAR_ONE(uint32_t sb, uint32_t i) { return sb + OFF_BAR + 216 + 8 * i; }
enum { EV_WIN, EV_WIN1, EV_WIN2, EV_WIN3, EV_P0, EV_GA, EV_GB, EV_LN2, EV_LAG0, EV_LAG1, EV_LAG2, EV_LAG3, EV_LAG4, EV_LAG5, EV_OWN, EV_OWN1, EV_P3, EV_P31, EV_KV, EV_GO, EV_PAR, EV_AGO, EV_AGO1, EV_AGO2, EV_H0, EV_H1, EV_H2, EV_H3, EV_X1, EV_X11, EV_X1S, EV_X1S1, EV_COUNT };
constexpr int NB_TAIL = 4;

struct Rel {
    uint32_t base; bool sig;
    __device__ __forceinline__ Rel(uint32_t sb, uint32_t tw) {
        uint32_t a; asm("mapa.shared::cluster.u32 %0, %1, %2;" : "=r"(a) : "r"(BAR_EMPTY(sb, 0)), "r"((tw >> 5) & 1));
        base = __shfl_sync(0xffffffffu, a, 0); sig = (tw & ~32u) == 0;
    }
    __device__ __forceinline__ void operator()(uint32_t slot) const {
        if (sig) asm volatile("mbarrier.arrive.shared::cluster.b64 _, [%0];" :: "r"(base + 8 * slot) : "memory");
    }
};
struct LnRow { float rs0, nm0, rs1, nm1; };
struct Pipe {
    Rel rel; uint32_t p1, p2;
    __device__ __forceinline__ Pipe(uint32_t sb, uint32_t tw, uint32_t first) : rel(sb, tw), p1(first), p2(NSLOT) {}
    template <bool TWO> __device__ __forceinline__ void acquire(uint32_t sb, uint32_t af, const Ring& r) {
        const uint32_t b0 = BAR_FULL(sb, r.slot), b1 = b0 + af;
        const bool ready = TWO ? mbar_test2(b0, b1, r.par) : mbar_test(b0, r.par);
        wg_wait<1>();
        rel(p2);
        if (!ready) { if (TWO) mbar_wait2(b0, b1, r.par); else mbar_wait(b0, r.par); }
    }
    __device__ __forceinline__ void issued(uint32_t slot) { p2 = p1; p1 = slot; }
    __device__ __forceinline__ void drain1() { wg_wait<1>(); rel(p2); p2 = NSLOT; }
    __device__ __forceinline__ void drain0() { wg_wait<0>(); rel(p1); p1 = NSLOT; }
    template <bool TWO, int LG, class Step> __device__ __forceinline__ void hold(uint32_t sb, uint32_t af, Ring& r, uint32_t lag_bar, Step step) {
        drain1(); drain0();
        Ring q = r;
#pragma unroll 1
        for (int i = 0; i < LG; ++i) { if (TWO) mbar_wait2(BAR_FULL(sb, q.slot), BAR_FULL(sb, q.slot) + af, q.par); else mbar_wait(BAR_FULL(sb, q.slot), q.par); q.next(); }
        mbar_wait(lag_bar, 0);
#pragma unroll 1
        do {
            step(r.slot);
            wg_wait<2>(); rel(p2); p2 = p1; p1 = r.slot;
            if (++r.slot == NSLOT) r.slot = 0;
        } while (r.slot != q.slot);
        r.par = q.par;
    }
};
template <bool TWO, bool FIRST, int NA, int NB>
__device__ __forceinline__ void step32(float (&aa)[NA], float (&ab)[NB], uint32_t sb, uint32_t wg, uint32_t slot, int own) {
    const uint32_t st = d16(sb) + slot * (SLOT >> 4);
    const uint32_t alo = own >= 0 ? d16(sb) + OFF_STG / 16 + wg * 1024 + (own >> 1) * 512 + (own & 1) * 4 : st + wg * 256;
    const uint32_t ahi = own >= 0 ? (1024 >> 4) | (1u << 30) : (512 >> 4) | (2u << 30);
    wg_fence();
#pragma unroll
    for (int k = 0; k < 2; ++k) {
        const uint64_t da = ((uint64_t)ahi << 32) | (alo + k * 2 + 0x10000);
        if constexpr (NA == 88) {
            const uint64_t d0 = mk_desc(st, 8192 + k * 2048, 8192, 1024, 1), d1 = mk_desc(st, 12288 + k * 2048, 8192, 1024, 1);
            if (FIRST && k == 0) { wgmma_n176_z(aa, da, d0); wgmma_n176_z(ab, da, d1); }
            else { wgmma_n176(aa, da, d0); wgmma_n176(ab, da, d1); }
        } else {
            const uint64_t d0 = mk_desc(st, 8192 + k * 2048, 4096, 1024, 1), d1 = mk_desc(st, 24576 + k * 2048, 4096, 1024, 1);
            if (FIRST && k == 0) { wgmma_n256_z(aa, da, d0); if constexpr (TWO) wgmma_n128_z(ab, da, d1); }
            else { wgmma_n256(aa, da, d0); if constexpr (TWO) wgmma_n128(ab, da, d1); }
        }
    }
    wg_commit();
}
template <bool TWO, int LG, int NA, int NB, class Tail>
__device__ __forceinline__ void mainloop32(float (&aa)[NA], float (&ab)[NB], uint32_t sb, uint32_t wg, uint32_t tw, Ring& r, uint32_t lag_ev, int g0, Tail tail) {
    mbar_wait(BAR_FULL(sb, r.slot), r.par);
    step32<TWO, true>(aa, ab, sb, wg, r.slot, TWO ? 0 : -1);
    TS(g0, 0);
    Pipe pp(sb, tw, r.slot);
    r.next();
    const int end = wg ? 32 : 32 - LG;
#pragma unroll 1
    for (int it = 1; it < end; ++it) {
        pp.acquire<TWO>(sb, wg ? 0 : AF_REL, r);
        step32<TWO, false>(aa, ab, sb, wg, r.slot, TWO && it < 4 ? it : -1);
        pp.issued(r.slot);
        TS(g0 + it, 0);
        r.next();
    }
    if (wg == 0) pp.hold<TWO, LG>(sb, AF_REL, r, BAR_ONE(sb, lag_ev), [&](uint32_t slot) { step32<TWO, false>(aa, ab, sb, 0, slot, -1); });
    pp.drain1();
    if (wg == 1 && tw == 0) mbar_arrive(BAR_ONE(sb, lag_ev));
    tail();
    pp.drain0();
    TS(g0 + 31, 1);
}
template <bool FIRST>
__device__ __forceinline__ void step64(float (&acc)[64], uint32_t sb, uint32_t wg, uint32_t slot, int own) {
    const uint32_t sbb = d16(sb) + slot * (SLOT >> 4), sa = own >= 0 ? d16(sb) + OFF_STG / 16 + wg * 1024 + own * 512 : sbb + wg * 512;
    wg_fence();
#pragma unroll
    for (int k = 0; k < 4; ++k) {
        const uint64_t da = mk_desc(sa, k * 32, 16, 1024, 1), db = mk_desc(sbb, 16384 + k * 2048, 8192, 1024, 1);
        if (FIRST && k == 0) wgmma_n128_z(acc, da, db); else wgmma_n128(acc, da, db);
    }
    wg_commit();
}
template <class Mid>
__device__ __forceinline__ void mainloop64(float (&acc)[64], bool wo, uint32_t sb, uint32_t wg, uint32_t tw, Ring& r, Mid mid) {
    const int g0 = wo ? 32 : 144, nst = wo ? 16 : 56; (void)g0;
    const uint32_t lag_bar = BAR_ONE(sb, wo ? EV_LAG4 : EV_LAG5), af = wo && !wg ? AF_REL : 0;
    mbar_wait(BAR_FULL(sb, r.slot), r.par);
    step64<true>(acc, sb, wg, r.slot, wo ? 0 : -1);
    TS(g0, 0);
    Pipe pp(sb, tw, r.slot);
    r.next();
    int it = 1;
    auto run = [&](int end, int own) {
#pragma unroll 1
        do {
            pp.acquire<true>(sb, af, r);
            step64<false>(acc, sb, wg, r.slot, own);
            pp.issued(r.slot);
            TS(g0 + it, 0);
            r.next();
            if (own > 0) {
                own = -1;
                pp.drain1(); pp.drain0();
                TS(g0 + 1, 1);
                if (tw == 0) mbar_arrive(BAR_ONE(sb, EV_OWN + wg));
            }
        } while (++it < end);
    };
    run(wg ? nst - MIDW : nst - LAGW, wo ? 1 : -1);
    mid();
    if (wg) run(nst, -1);
    else pp.hold<true, LAGW>(sb, af, r, lag_bar, [&](uint32_t slot) { step64<false>(acc, sb, 0, slot, -1); });
    pp.drain1();
    if (wg == 1 && tw == 0) mbar_arrive(lag_bar);
    pp.drain0();
    TS(g0 + nst - 1, 1);
}

struct RowAcc {
    float sm[4] = {0.f, 0.f, 0.f, 0.f}, sq[4] = {0.f, 0.f, 0.f, 0.f};
    __device__ __forceinline__ void add(int e, float x) { sm[e & 3] += x; sq[e & 3] = fmaf(x, x, sq[e & 3]); }
    __device__ __forceinline__ void publish(uint4* dst, uint32_t q4, uint32_t ep) const {
        const float s0 = sm[0] + sm[1], s1 = sm[2] + sm[3], q0 = sq[0] + sq[1], q1 = sq[2] + sq[3];
        const bool od = q4 & 1;
        float sv = (od ? s1 : s0) + __shfl_xor_sync(0xffffffffu, od ? s0 : s1, 1), qv = (od ? q1 : q0) + __shfl_xor_sync(0xffffffffu, od ? q0 : q1, 1);
        sv += __shfl_xor_sync(0xffffffffu, sv, 2); qv += __shfl_xor_sync(0xffffffffu, qv, 2);
        if (q4 < 2) st_pkt16(dst + q4 * 8, 0, __float_as_uint(sv), __float_as_uint(qv), ep);
    }
};
__device__ __forceinline__ LnRow merge_stats(const uint4* src, uint32_t q4, uint32_t ep, uint32_t sb, uint32_t sig) {
    uint4 t[4];
    uint32_t n = 0;
    while (true) {
#pragma unroll
        for (int i = 0; i < 4; ++i) t[i] = ld_pkt16(src + (q4 * 2 + (i >> 1)) * 512 + (i & 1) * 8);
        if (sig) { mbar_arrive(sig); sig = 0; }
        const bool ok_ = __all_sync(0xffffffffu, t[0].w == ep && t[1].w == ep && t[2].w == ep && t[3].w == ep);
        if (n < 4) CS(14 + n);
        if (ok_) break;
        SPIN_GUARD(n);
    }
    float v[4];
#pragma unroll
    for (int h = 0; h < 2; ++h) { v[h] = __uint_as_float(t[h].y) + __uint_as_float(t[2 + h].y); v[2 + h] = __uint_as_float(t[h].z) + __uint_as_float(t[2 + h].z); }
#pragma unroll
    for (int o = 1; o < 4; o <<= 1)
#pragma unroll
        for (int i = 0; i < 4; ++i) v[i] += __shfl_xor_sync(0xffffffffu, v[i], o);
    const float m0 = v[0] * (1.f / D_), m1 = v[1] * (1.f / D_);
    const float r0 = rsqrtf(fmaxf(fmaf(-m0, m0, v[2] * (1.f / D_)), 0.f) + 1e-5f), r1 = rsqrtf(fmaxf(fmaf(-m1, m1, v[3] * (1.f / D_)), 0.f) + 1e-5f);
    return LnRow{r0, -m0 * r0, r1, -m1 * r1};
}
struct Stg {
    uint32_t b, par;
    __device__ __forceinline__ uint32_t acquire2(uint32_t sb, uint32_t wg) {
        mbar_wait(BAR_SREADY(sb, wg * 2), par & 1);
        mbar_wait(BAR_SREADY(sb, wg * 2 + 1), (par >> 1) & 1);
        par ^= 3;
        return sb + OFF_STG + wg * 16384;
    }
    __device__ __forceinline__ void publish(uint32_t sb, uint32_t wg, uint32_t lane) {
        fence_async_smem();
        __syncwarp();
        if (lane == 0) mbar_arrive(BAR_SFULL(sb, wg * 2 + b));
        b ^= 1;
    }
};

struct LnPar {
    uint4 p[8];
    __device__ __forceinline__ void load(uint32_t sb, uint32_t q4) {
#pragma unroll
        for (int i = 0; i < 8; ++i) p[i] = lds128(sb + OFF_PAR + i * 64 + q4 * 16);
    }
};
__device__ __forceinline__ void ln_norm(uint32_t (&xn)[32], const float (&x)[64], const LnRow& n) {
#pragma unroll
    for (int e = 0; e < 32; ++e) {
        const float rs = (e & 1) ? n.rs1 : n.rs0, nm = (e & 1) ? n.nm1 : n.nm0;
        xn[e] = pack2(fmaf(x[2 * e], rs, nm), fmaf(x[2 * e + 1], rs, nm));
    }
}
__device__ __forceinline__ void ln_emit(const uint32_t (&xr)[32], const LnPar& lp, uint32_t sb, uint32_t wg, const Idx& ix) {
#pragma unroll
    for (int i = 0; i < 8; ++i)
        stsm4(sb + OFF_STG + wg * 16384 + (i >> 2) * 8192 + (ix.pan ^ ((i & 3) << 5)), hfma2_bf16(xr[4 * i], lp.p[i].z, lp.p[i].x), hfma2_bf16(xr[4 * i + 1], lp.p[i].z, lp.p[i].x),
              hfma2_bf16(xr[4 * i + 2], lp.p[i].w, lp.p[i].y), hfma2_bf16(xr[4 * i + 3], lp.p[i].w, lp.p[i].y));
    fence_async_smem();
    __syncwarp();
    if (ix.lane < 2) mbar_arrive(BAR_SFULL(sb, wg * 2 + ix.lane));
    bar_sync(1 + wg, 128);
}
__device__ __forceinline__ void load_slab(float (&x)[64], uint32_t buf) {
    IDX();
    uint32_t xr[32];
#pragma unroll
    for (int i = 0; i < 8; ++i) ldsm4(buf + (i >> 2) * 8192 + (pan_addr ^ ((i & 3) << 5)), xr[4 * i], xr[4 * i + 1], xr[4 * i + 2], xr[4 * i + 3]);
#pragma unroll
    for (int i = 0; i < 32; ++i) unpack2(xr[i], x[2 * i], x[2 * i + 1]);
}
__device__ __forceinline__ void store_slab(const float (&x)[64], uint32_t buf, uint32_t pitch, uint32_t pan, int i0, int i1) {
#pragma unroll
    for (int i = i0; i < i1; ++i)
        stsm4(buf + (i >> 2) * pitch + (pan ^ ((i & 3) << 5)), pack2(x[8 * i], x[8 * i + 1]), pack2(x[8 * i + 2], x[8 * i + 3]), pack2(x[8 * i + 4], x[8 * i + 5]), pack2(x[8 * i + 6], x[8 * i + 7]));
}
__device__ __forceinline__ void fetch_halo(uint4* src, bool first, uint32_t sb, uint32_t W, uint32_t lane) {
    mbar_wait(BAR_ONE(sb, EV_KV), 0);
    mbar_wait2(BAR_SREADY(sb, 0), BAR_SREADY(sb, 1), 1);
    uint4 hv[8];
    uint32_t n = 0;
    while (true) {
        bool ok = true;
#pragma unroll
        for (int i = 0; i < 8; ++i) { hv[i] = first ? make_uint4(0, 0, 0, 0) : ld_pkt16(src + i * 32); ok = ok && hv[i].x != 0; }
        if (first || __all_sync(0xffffffffu, ok)) break;
        SPIN_GUARD(n);
    }
#pragma unroll
    for (int i = 0; i < 8; ++i) stsm4(sb + OFF_STG + W * 2048 + (i >> 2) * 8192 + (i & 3) * 512 + lane * 16, hv[i].x, hv[i].y, hv[i].z, hv[i].w);
    bar_arrive(NB_TAIL + W, 64);
    if (!first) {
#pragma unroll
        for (int i = 0; i < 8; ++i) src[i * 32] = make_uint4(0, 0, 0, 0);
    }
}

template <int OG, int OU, int LEN>
__device__ __forceinline__ void glu_panel(const float (&g)[LEN], const float (&u)[LEN], uint32_t buf, uint32_t bar) {
    IDX();
    constexpr int NR = LEN - OU < 32 ? (LEN - OU) / 2 : 16;
    uint32_t r[NR];
#pragma unroll
    for (int i = 0; i < NR; ++i) r[i] = pack2(glu_half(g[OG + 2 * i], u[OU + 2 * i]), glu_half(g[OG + 2 * i + 1], u[OU + 2 * i + 1]));
#pragma unroll
    for (int jn = 0; jn < NR / 2; jn += 2) stsm4(buf + (pan_addr ^ (jn << 4)), r[jn * 2], r[jn * 2 + 1], r[jn * 2 + 2], r[jn * 2 + 3]);
    fence_async_smem();
    __syncwarp();
    if (lane == 0) mbar_arrive(bar);
}

template <int NP>
__device__ __forceinline__ void passes128(uint32_t sb, uint32_t wg, uint32_t tw, Ring& r, Stg& stg) {
#pragma unroll 1
    for (int p = 0; p < NP; ++p) {
        float b256[128], none[1];
        mainloop32<false, LAGS>(b256, none, sb, wg, tw, r, EV_LAG2 + p, 80 + 32 * (p & 1), [&] { stg.acquire2(sb, wg); });
        if (threadIdx.x == 0) { TL(29 + 2 * p); TC(114 + 2 * p); }
        if (threadIdx.x == 128) TL(53 + 2 * (p & 1));
        glu_panel<0, 32>(b256, b256, sb + OFF_STG + wg * 16384, BAR_SFULL(sb, wg * 2));
        glu_panel<64, 96>(b256, b256, sb + OFF_STG + wg * 16384 + 8192, BAR_SFULL(sb, wg * 2 + 1));
        if (threadIdx.x == 0) { TL(30 + 2 * p); TC(115 + 2 * p); }
        if (threadIdx.x == 128) TL(54 + 2 * (p & 1));
    }
}

__global__ void __launch_bounds__(384, 1)
fused_block_kernel(const __grid_constant__ Ptrs pt, const __grid_constant__ Maps mp) {
    uint32_t* const g_flags = pt.mail->flags;
    uint2* const g_mod = pt.mail->mod;
    uint4* const g_st1 = pt.mail->st1;
    uint32_t* const g_par2 = pt.mail->par2;
    uint4* const g_halo = pt.mail->halo;
    const __nv_bfloat16* __restrict__ cvec = pt.c;
    if (threadIdx.x == 224) { prefetch_map(&mp.wm8); prefetch_map(&mp.x); }
    extern __shared__ __align__(1024) uint8_t smem[];
    const uint32_t sb = smem_u32(smem);
    const uint32_t tid = threadIdx.x, tw = tid & 127, lane = tid & 31;
    const uint32_t warp = __shfl_sync(0xffffffffu, tid >> 5, 0), wg = warp >> 2;
    uint32_t rank; asm("mov.u32 %0, %%cluster_ctarank;" : "=r"(rank));
    rank = __shfl_sync(0xffffffffu, rank, 0);
    uint32_t ep;
    uint32_t smid; asm volatile("mov.u32 %0, %%smid;" : "=r"(smid));
    const int c = __shfl_sync(0xffffffffu, smid >> 1, 0);
    const int c7 = ((c - 32) * 37) >> 8;
    const int grp = c < 32 ? c & 7 : c < 60 ? c - 31 - 7 * c7 : c < 62 ? -1 : 0;
    const int j = c < 32 ? c >> 3 : c < 60 ? 4 + c7 : c < 62 ? (c - 60) * 2 + rank : c - 58;
    const bool aux = grp < 0;
    const int m = grp * 2 + rank;
    uint4* const g_st2 = g_halo + (m > 0 ? (m - 1) * 8 * 512 : 128);

    bool cluster_arrive_early = false;
    if (wg < 2) {
      if (!KDEBUG) cluster_arrive();
      ep = flag_get(g_flags + FL_DONE);
      uint16_t cw[8];
      {
          const __nv_bfloat16* cp = cvec + ((tw >> 5) * 32 + (tw & 3) * 2) * 8 + (lane >> 2);
#pragma unroll
          for (int i = 0; i < 8; ++i) asm volatile("ld.global.nc.u16 %0, [%1];" : "=h"(cw[i]) : "l"(cp + (i >> 1) * 64 + (i & 1) * 8));
      }
      asm volatile("setmaxnreg.inc.sync.aligned.u32 224;");
      if (tid == 0) TL(58);
      if (KDEBUG) cluster_arrive();
      Ring r{0, 0};
      Stg stg{0, 0};
      if (aux) {
        if (wg == 0) {
            const uint4 cv = *(const uint4*)(cvec + tw * 8);
            sts128(sb + OFF_STG + (tw >> 3) * 1024 + (tw & 7) * 16, pack2(silu_(bf_lo(cv.x)), silu_(bf_hi(cv.x))), pack2(silu_(bf_lo(cv.y)), silu_(bf_hi(cv.y))),
                   pack2(silu_(bf_lo(cv.z)), silu_(bf_hi(cv.z))), pack2(silu_(bf_lo(cv.w)), silu_(bf_hi(cv.w))));
            fence_async_smem();
        }
        cluster_wait();
        ep = __shfl_sync(0xffffffffu, ep, 0) / NCTA + 1;
        if (wg == 0) {
            if (tw == 0) {
                uint32_t n = 0;
                while (ld_pkt16(pt.mail->mod1 + 256).z != ep) { SPIN_GUARD(n); __nanosleep(200); }
                if (GODLY) __nanosleep(GODLY);
                mbar_arrive(BAR_ONE(sb, EV_GO));
            }
            bar_sync(1, 128);
#pragma unroll 1
            for (int p = 0; p < 4; ++p) {
                float acc[128];
#pragma unroll
                for (int i = 0; i < 128; ++i) acc[i] = 0.f;
                uint32_t prev = 0;
#pragma unroll 1
                for (int kc = 0; kc < 16; ++kc) {
                    mbar_wait(BAR_FULL(sb, r.slot), r.par);
                    wg_fence();
#pragma unroll
                    for (int k = 0; k < 4; ++k)
                        wgmma_n256(acc, mk_desc(d16(sb) + kc * 64, OFF_STG + k * 32, 16, 0, 1), mk_desc(d16(sb) + r.slot * (SLOT >> 4), k * 2048, 8192, 1024, 1));
                    wg_commit();
                    wg_wait<1>();
                    if (kc > 0 && tw < 4) mbar_arrive(BAR_EMPTY(sb, prev));
                    prev = r.slot;
                    r.next();
                }
                wg_wait<0>();
                if (tw < 4) mbar_arrive(BAR_EMPTY(sb, prev));
                if (tw < 4) {
#pragma unroll
                    for (int jn = 0; jn < 32; ++jn) sts32(sb + OFF_TAB + (jn * 4 + tw) * 4, pack2(acc[jn * 4], acc[jn * 4 + 1]));
                }
                bar_sync(1, 128);
                const int vec = 2 + p, blk = p * 4 + j;
                const uint32_t val = lds32(sb + OFF_TAB + tw * 4);
                if (vec == 2 || vec == 5) st_pkt(g_mod + (8 + blk) * 128 + tw, val, ep);
                else {
                    const float one = vec == 4 ? 1.f : 0.f;
                    g_par2[((blk & 3) * 16 + (tw >> 3)) * 16 + (tw & 3) * 4 + (vec - 3) * 2 + ((tw >> 2) & 1)] =
                        pack2(0.5f * bf_round(one + bf_lo(val)), 0.5f * bf_round(one + bf_hi(val)));
                }
                bar_sync(1, 128);
                if (tw == 0) {
                    if (vec == 3 || vec == 4) asm volatile("red.release.gpu.global.add.u32 [%0], 1;" :: "l"(&g_flags[FL_LN2]) : "memory");
                    TL(1 + p);
                }
            }
            if (lane < 2) mbar_arrive_cta(BAR_ONE(sb, EV_P0), lane);
        }
        r = Ring{64 % NSLOT, (64 / NSLOT) & 1};
        mbar_wait(BAR_ONE(sb, EV_P0), 0);
        passes128<4>(sb, wg, tw, r, stg);
      } else {
        float xs[64];
        {
            IDX();
            if (q4 < 2) st_pkt16(g_st1 + (m * 8 + j) * 512 + wg * 64 + w4 * 16 + g8 + q4 * 8, 0, 0, 0, 0);
            if (warp == 0) st_pkt16(pt.mail->mod1 + g8 * 512 + (m * 8 + j) * 4 + q4, 0, 0, 0, 0);
            sts128(sb + tid * 16, pack2(silu_(bf_lo(cw[0])), silu_(bf_lo(cw[1]))), pack2(silu_(bf_lo(cw[2])), silu_(bf_lo(cw[3]))),
                   pack2(silu_(bf_lo(cw[4])), silu_(bf_lo(cw[5]))), pack2(silu_(bf_lo(cw[6])), silu_(bf_lo(cw[7]))));
            cluster_wait();
            ep = __shfl_sync(0xffffffffu, ep, 0) / NCTA + 1;
            load_slab(xs, stg.acquire2(sb, wg));
            if (tid == 0) TL(24);
            if (tid == 128) TL(27);
        }
#pragma unroll 1
        for (int blk = 0; ; ++blk) {
        {
            IDX();
            uint4* const st = (blk ? g_st2 : g_st1 + m * 8 * 512) + wg * 64 + w4 * 16 + g8;
            RowAcc ra;
#pragma unroll
            for (int e = 0; e < 64; ++e) ra.add(e, xs[e]);
            ra.publish(st + j * 512, q4, ep);
            if (tid == 0) TL(blk ? 9 : 26);
            if (tid == 128 && blk) TL(34);
            if (blk) CS(11);
            LnPar lp;
            if (blk == 0) {
            uint4* const mod_out = pt.mail->mod1 + g8 * 512 + (m * 8 + j) * 4 + q4;
            if (wg == 0) {
                uint4 af[8];
#pragma unroll
                for (int i = 0; i < 8; ++i) af[i] = lds128(sb + w4 * 512 + i * 64 + q4 * 16);
                float c[4][4] = {};
#pragma unroll
                for (int i = 0; i < 8; ++i) {
                    if (!(i & 1)) mbar_wait(BAR_ONE(sb, EV_WIN + (i >> 1)), 0);
                    if (i == 6 && tid == 0) TL(25);
#pragma unroll
                    for (int h = 0; h < 2; ++h) {
                        uint32_t b0, b1, b2, b3;
                        ldsm4t(sb + 5 * SLOT + i * 4096 + w4 * 1024 + h * 512 + (lane & 15) * 32 + (lane >> 4) * 16, b0, b1, b2, b3);
                        mma16816(c[2 * h], h ? af[i].z : af[i].x, 0u, h ? af[i].w : af[i].y, 0u, b0, b1);
                        mma16816(c[2 * h + 1], h ? af[i].z : af[i].x, 0u, h ? af[i].w : af[i].y, 0u, b2, b3);
                    }
                }
                if (lane < 4) sts128(sb + OFF_TAB + w4 * 64 + lane * 16, __float_as_uint(c[0][0] + c[2][0]), __float_as_uint(c[0][1] + c[2][1]),
                                     __float_as_uint(c[1][0] + c[3][0]), __float_as_uint(c[1][1] + c[3][1]));
                if (lane < 2) mbar_arrive_cta(BAR_ONE(sb, EV_P0), lane);
                bar_sync(1, 128);
                if (w4 == 0) {
                    float a[4] = {0.f, 0.f, 0.f, 0.f};
#pragma unroll
                    for (int i = 0; i < 4; ++i) {
                        const uint4 t = lds128(sb + OFF_TAB + i * 64 + q4 * 16);
                        a[0] += __uint_as_float(t.x); a[1] += __uint_as_float(t.y); a[2] += __uint_as_float(t.z); a[3] += __uint_as_float(t.w);
                    }
                    const float add = m >= 8 ? 1.f : 0.f;
                    st_pkt16(mod_out, pack2(bf_round(a[0]) + add, bf_round(a[1]) + add), pack2(bf_round(a[2]) + add, bf_round(a[3]) + add), ep, 0);
                    if (tid == 0) TL(3);
                }
            } else if (LWAIT >= 0) mbar_wait(BAR_ONE(sb, EV_WIN + LWAIT), 0);
            } else {
                if (wg) mbar_wait2(BAR_EMPTY(sb, X1_SLOT), BAR_EMPTY(sb, X1_SLOT + 1), r.par ^ 1);
                store_slab(xs, sb + (X1_SLOT + 2 - 2 * wg) * SLOT, SLOT, pan_addr, 0, 8);
                fence_async_smem();
                __syncwarp();
                CS(12);
                mbar_wait(BAR_ONE(sb, EV_LN2), 0);
            }
            lp.load(sb, q4);
            if (blk) CS(13);
            const LnRow n = merge_stats(st, q4, ep, sb, blk && lane == 0 ? BAR_ONE(sb, EV_X1S + wg) : 0);
            if (tid == 0) TL(blk ? 49 : 48);
            if (tid == 128) TL(blk ? 45 : 28);
            if (blk) CS(18);
            uint32_t xn[32];
            ln_norm(xn, xs, n);
            if (blk == 0) { mbar_wait(BAR_ONE(sb, EV_PAR), 0); lp.load(sb, q4); }
            ln_emit(xn, lp, sb, wg, ix);
            if (tid == 0) { TL(blk ? 36 : 8); TC(blk ? 109 : 103); }
            if (tid == 128) TL(blk ? 43 : 22);
            if (blk) CS(21);
        }
        if (blk == 0) {
        {
            float kv[128], qa[64];
            mainloop32<true, LAGQ>(kv, qa, sb, wg, tw, r, EV_LAG0, 0, [&] { stg.acquire2(sb, wg); mbar_wait2(BAR_SREADY(sb, 2), BAR_SREADY(sb, 3), 1); });
            if (tid == 0) { TL(4); TC(104); }
            if (tid == 128) TL(50);
            CS(1);
            IDX();
            uint32_t k1[16], k2[16], v1[16], v2[16], qf[32];
#pragma unroll
            for (int i = 0; i < 8; ++i) qf[i] = pack2(qa[2 * i], qa[2 * i + 1]);
#pragma unroll
            for (int t = 0; t < 16; ++t) k2[t] = pack2(kv[4 * t + 2], kv[4 * t + 3]);
#pragma unroll
            for (int t = 0; t < 16; ++t) v2[t] = pack2(kv[64 + 4 * t + 2], kv[64 + 4 * t + 3]);
            const uint32_t nxt = warp + ((warp & 1) ? 3 : 1);
            if (nxt < 8) {
                const uint32_t dst = sb + OFF_STG + (nxt >> 2) * 16384 + (nxt & 3) * 2048 + lane * 16;
#pragma unroll
                for (int h = 0; h < 4; ++h) stsm4(dst + h * 512, k2[4 * h], k2[4 * h + 1], k2[4 * h + 2], k2[4 * h + 3]);
#pragma unroll
                for (int h = 0; h < 4; ++h) stsm4(dst + 8192 + h * 512, v2[4 * h], v2[4 * h + 1], v2[4 * h + 2], v2[4 * h + 3]);
                bar_arrive(NB_TAIL + nxt, 64);
            } else if (m < 15) {
                uint4* dst = g_halo + (m * 8 + j) * 512 + (w4 >> 1) * 256 + lane;
#pragma unroll
                for (int h = 0; h < 4; ++h) { if (!k2[4 * h]) k2[4 * h] = 0x8000u; if (!v2[4 * h]) v2[4 * h] = 0x8000u; }
#pragma unroll
                for (int h = 0; h < 4; ++h) st_pkt16(dst + h * 32, k2[4 * h], k2[4 * h + 1], k2[4 * h + 2], k2[4 * h + 3]);
#pragma unroll
                for (int h = 0; h < 4; ++h) st_pkt16(dst + 128 + h * 32, v2[4 * h], v2[4 * h + 1], v2[4 * h + 2], v2[4 * h + 3]);
            }
#pragma unroll
            for (int t = 0; t < 16; ++t) { k1[t] = pack2(kv[4 * t], kv[4 * t + 1]); v1[t] = pack2(kv[64 + 4 * t], kv[64 + 4 * t + 1]); }
#pragma unroll
            for (int i = 8; i < 32; ++i) qf[i] = pack2(qa[2 * i], qa[2 * i + 1]);
#pragma unroll
            for (int t = 0; t < 16; ++t) { v1[t] = movm(v1[t]); v2[t] = movm(v2[t]); }
            if (tid == 0) TL(33);
            CS(2);
            SCHED_FENCE(0);
            float s[4][3][4];
            auto qk = [&](float (&c)[4], int h, const uint32_t* k) {
                c[0] = c[1] = c[2] = c[3] = 0.f;
                mma16816(c, qf[h * 8], qf[h * 8 + 1], qf[h * 8 + 2], qf[h * 8 + 3], k[0], k[1]);
                mma16816(c, qf[h * 8 + 4], qf[h * 8 + 5], qf[h * 8 + 6], qf[h * 8 + 7], k[2], k[3]);
            };
#pragma unroll
            for (int h = 0; h < 4; ++h) { qk(s[h][1], h, k1 + 4 * h); qk(s[h][2], h, k2 + 4 * h); }
            CS(3);
            bar_sync(NB_TAIL + warp, 64);
            CS(4);
            if (tid == 0) TL(5);
            uint32_t k0[16], v0[16];
            const uint32_t mine = sb + OFF_STG + wg * 16384 + w4 * 2048;
#pragma unroll
            for (int h = 0; h < 4; ++h) ldsm4(mine + lane * 16 + h * 512, k0[4 * h], k0[4 * h + 1], k0[4 * h + 2], k0[4 * h + 3]);
#pragma unroll
            for (int h = 0; h < 4; ++h) ldsm4t(mine + lane * 16 + 8192 + h * 512, v0[4 * h], v0[4 * h + 1], v0[4 * h + 2], v0[4 * h + 3]);
#pragma unroll
            for (int h = 0; h < 4; ++h) qk(s[h][0], h, k0 + 4 * h);
            const bool lo0 = q4 * 2 > g8, lo1 = q4 * 2 + 1 > g8;
            const bool nopast = m == 0 && (warp & 5) == 0;
            const uint32_t lomask = (lo0 ? 0xFFFFu : 0u) | (lo1 ? 0xFFFF0000u : 0u);
            const float sl2 = 0.17677669529663687f * 1.4426950408889634f;
            float e0[8], e1[8], mx[8], sum[8], tt[8];
#pragma unroll
            for (int u = 0; u < 8; ++u) {
                const int h = u >> 1, hf = u & 1;
                e0[u] = lo0 ? ((hf == 0 && nopast) ? -INFINITY : s[h][hf][hf * 2]) : s[h][hf + 1][hf * 2];
                e1[u] = lo1 ? ((hf == 0 && nopast) ? -INFINITY : s[h][hf][hf * 2 + 1]) : s[h][hf + 1][hf * 2 + 1];
                mx[u] = fmaxf(e0[u], e1[u]);
                tt[u] = __shfl_xor_sync(0xffffffffu, mx[u], 1);
            }
            SCHED_FENCE(1);
#pragma unroll
            for (int u = 0; u < 8; ++u) { mx[u] = fmaxf(mx[u], tt[u]); tt[u] = __shfl_xor_sync(0xffffffffu, mx[u], 2); }
            SCHED_FENCE(2);
#pragma unroll
            for (int u = 0; u < 8; ++u) {
                const float c = -fmaxf(mx[u], tt[u]) * sl2;
                e0[u] = ex2(fmaf(e0[u], sl2, c)); e1[u] = ex2(fmaf(e1[u], sl2, c));
            }
            SCHED_FENCE(3);
#pragma unroll
            for (int u = 0; u < 8; ++u) { sum[u] = e0[u] + e1[u]; tt[u] = __shfl_xor_sync(0xffffffffu, sum[u], 1); }
            SCHED_FENCE(4);
#pragma unroll
            for (int u = 0; u < 8; ++u) { sum[u] += tt[u]; tt[u] = __shfl_xor_sync(0xffffffffu, sum[u], 2); }
            SCHED_FENCE(5);
#pragma unroll
            for (int u = 0; u < 8; ++u) sum[u] = rcp(sum[u] + tt[u]);
            SCHED_FENCE(6);
            CS(5);
            float o[8][2][4];
#pragma unroll
            for (int u = 0; u < 8; ++u) {
                const int h = u >> 1;
                const uint32_t p = pack2(e0[u] * sum[u], e1[u] * sum[u]);
                const uint32_t* va = ((u & 1) ? v1 : v0) + 4 * h;
                const uint32_t* vb = ((u & 1) ? v2 : v1) + 4 * h;
#pragma unroll
                for (int d = 0; d < 2; ++d) {
                    o[u][d][0] = o[u][d][1] = o[u][d][2] = o[u][d][3] = 0.f;
                    mma16816(o[u][d], va[2 * d], va[2 * d + 1], vb[2 * d], vb[2 * d + 1], p & lomask, p & ~lomask);
                }
            }
            SCHED_FENCE(7);
            const uint32_t orow = mine + (lane & 7) * 128 + (((lane >> 3) ^ (lane & 7)) << 4);
#pragma unroll
            for (int u = 0; u < 8; ++u)
                stsm4t((orow ^ (((u >> 1) & 1) << 6)) + (u >> 2) * 8192 + (u & 1) * 1024, pack2(o[u][0][0], o[u][0][1]), pack2(o[u][0][2], o[u][0][3]),
                       pack2(o[u][1][0], o[u][1][1]), pack2(o[u][1][2], o[u][1][3]));
            fence_async_smem();
            __syncwarp();
            if (lane < 2) mbar_arrive(BAR_SFULL(sb, wg * 2 + lane));
            CS(6);
            if (tid == 32) TL(41);
            bar_sync(1 + wg, 128);
            if (tid == 0) { TL(6); TC(106); }
            if (tid == 128) TL(44);
            CS(7);
        }
        } else {
        {
            float ag[88], au[88];
            mainloop32<true, LAG>(ag, au, sb, wg, tw, r, EV_LAG1, 48, [&] {
                stg.acquire2(sb, wg);
                Ring q = r; if (!wg) q.next();
                mbar_wait(BAR_EMPTY(sb, q.slot), q.par ^ 1);
            });
            if (tid == 0) { TL(10); TC(110); }
            if (tid == 128) TL(51);
            glu_panel<0, 0>(ag, au, sb + OFF_STG + wg * 16384, BAR_SFULL(sb, wg * 2));
            glu_panel<32, 32>(ag, au, sb + OFF_STG + wg * 16384 + 8192, BAR_SFULL(sb, wg * 2 + 1));
            glu_panel<64, 64>(ag, au, sb + (wg ? P3_SLOT1 : P3_SLOT0) * SLOT + 24576, BAR_ONE(sb, EV_P3 + wg));
            if (tid == 0) { TL(11); TC(111); }
            if (tid == 128) TL(52);
        }
        passes128<2>(sb, wg, tw, r, stg);
        if (tid == 0) { TL(12); TC(112); }
        }
        {
            float acc[64], gf[32];
            mainloop64(acc, blk == 0, sb, wg, tw, r, [&] {
                mbar_wait(BAR_ONE(sb, EV_GA + blk), 0);
                load_slab(xs, stg.acquire2(sb, wg));
                uint32_t gt[16];
#pragma unroll
                for (int cg = 0; cg < 16; ++cg) gt[cg] = lds32(sb + OFF_TAB + blk * 256 + cg * 16 + (tw & 3) * 4);
#pragma unroll
                for (int i = 0; i < 16; ++i) unpack2(gt[i], gf[2 * i], gf[2 * i + 1]);
            });
            if (tid == 0) { TL(blk ? 13 : 7); TC(blk ? 113 : 107); }
            if (tid == 128) TL(blk ? 57 : 42);
            if (!blk) CS(10);
#pragma unroll
            for (int e = 0; e < 64; ++e) xs[e] = fmaf(gf[(e >> 2) * 2 + (e & 1)], acc[e], xs[e]);
        }
        if (blk) break;
        }
        cluster_arrive();
        {
            IDX();
#pragma unroll
            for (int p = 0; p < 2; ++p) {
                store_slab(xs, sb + OFF_STG + wg * 16384, 8192, pan_addr, 4 * p, 4 * p + 4);
                stg.publish(sb, wg, lane);
            }
            if (tid == 0) TL(14);
        }
      }
    } else {
        if (warp == 8 && !aux && elect_one()) {
#pragma unroll
            for (int i = 0; i < 4; ++i) mbar_init(BAR_SREADY(sb, i), 1);
#pragma unroll
            for (int i = 0; i < 4; ++i) mbar_init(BAR_ONE(sb, EV_WIN + i), 1);
#pragma unroll
            for (int i = 0; i < 4; ++i) {
                mbar_expect_tx(BAR_SREADY(sb, i), 8192);
                tma_load3(sb + OFF_STG + i * 8192, &mp.x, j * 128 + (i & 1) * 64, m * 64 + (i >> 1) * 32, BAR_SREADY(sb, i));
            }
#pragma unroll 1
            for (int i = 0; i < 4; ++i) {
                mbar_expect_tx(BAR_ONE(sb, EV_WIN + i), 8192);
                tma_load(sb + 5 * SLOT + i * 8192, &mp.wm8, 2 * i * 6144 + (m * 8 + j) * 16, 0, BAR_ONE(sb, EV_WIN + i));
                tma_load(sb + 5 * SLOT + i * 8192 + 4096, &mp.wm8, (2 * i + 1) * 6144 + (m * 8 + j) * 16, 0, BAR_ONE(sb, EV_WIN + i));
            }
        }
        __syncwarp();
        asm volatile("setmaxnreg.dec.sync.aligned.u32 56;");
        if (elect_one()) {
            if (warp == 8) {
                prefetch_map(&mp.wqkv); prefetch_map(&mp.wmod);
            } else if (warp < 11) {
                mbar_init(BAR_EMPTY(sb, NSLOT), 1);
#pragma unroll
                for (int i = 0; i < 2; ++i) { mbar_init(BAR_SFULL(sb, (warp - 9) * 2 + i), 4); if (aux) mbar_init(BAR_SREADY(sb, (warp - 9) * 2 + i), 1); }
#pragma unroll
                for (int i = 0; i < 3; ++i) {
                    mbar_init(BAR_EMPTY(sb, (warp - 9) * 3 + i), 4);
                    mbar_init(BAR_FULL(sb, (warp - 9) * 3 + i), 1); mbar_init(BAR_FULL(sb, (warp - 9) * 3 + i) + AF_REL, 1);
                }
            } else {
#pragma unroll
                for (int i = EV_P0; i < EV_COUNT; ++i) mbar_init(BAR_ONE(sb, i), i == EV_P0 ? 8 : (i == EV_P3 || i == EV_P31 || i >= EV_X1S) ? 4 : 1);
            }
            asm volatile("fence.mbarrier_init.release.cluster;" ::: "memory");
        }
        __syncwarp();
        cluster_arrive();
        ep = 0;
        if (warp != 8 || aux) ep = flag_get(g_flags + FL_DONE);
        cluster_wait();
        ep = __shfl_sync(0xffffffffu, ep, 0) / NCTA + 1;
        if (warp == 8) {
            const bool el = elect_one();
            Ring r{0, 1};
            if (aux) {
                mbar_wait(BAR_ONE(sb, EV_GO), 0);
#pragma unroll 1
                for (int it = 0; it < 64; ++it) {
                    const int col = 2048 + (it >> 4) * 1024 + j * 256;
                    mbar_wait(BAR_EMPTY(sb, r.slot), r.par);
                    const uint32_t st = sb + r.slot * SLOT, fb = BAR_FULL(sb, r.slot);
                    if (el) {
                        mbar_expect_tx(fb, 32768);
#pragma unroll
                        for (int b = 0; b < 4; ++b) tma_load(st + b * 8192, &mp.wmod, col + b * 64, (it & 15) * 64, fb);
                    }
                    r.next();
                }
                mbar_wait(BAR_ONE(sb, EV_P0), 0);
                const CUtensorMap* wm = rank ? &mp.wu : &mp.wg;
#pragma unroll 1
                for (int g = 0; g < 128; ++g) {
                    const int mx = (j >> 1) * 8 + (g >> 5) * 2 + rank, k0 = (g & 31) * 32;
                    if (k0 == 0) {
                        uint32_t n = 0;
                        while (!__all_sync(0xffffffffu, (int32_t)(flag_get(g_flags + FL_PROG + (mx * 32 + lane) * FS) - (ep * 8 + ST_H2)) >= 0)) { SPIN_GUARD(n); __nanosleep(500); }
                    }
                    mbar_wait(BAR_EMPTY(sb, r.slot), r.par);
                    const uint32_t st = sb + r.slot * SLOT, fb = BAR_FULL(sb, r.slot);
                    if (el) {
                        mbar_expect_tx(fb, 24576);
                        tma_load_mc(st + 8192 + rank * 4096, wm, HC3, k0, fb);
                        tma_load_mc(st + 16384 + rank * 4096, wm, HC3 + 64, k0, fb);
                        tma_load(st, &mp.h2l, k0, mx * 128, fb);
                    }
                    r.next();
                }
            } else {
#pragma unroll 1
                for (int it = 0; it < 32; ++it) {
                    const int cb = j * 128 + rank * 64, k0 = kof(it, 2, j);
                    if (it == BW0) mbar_wait(BAR_ONE(sb, BWEV), 0);
                    if (it == BW1) mbar_wait(BAR_ONE(sb, EV_PAR), 0);
                    if (it == 5) mbar_wait(BAR_ONE(sb, EV_P0), 0);
                    if ((AGO & 1) && it == 6) mbar_wait(BAR_ONE(sb, EV_AGO), 0);
                    mbar_wait(BAR_EMPTY(sb, r.slot), r.par);
                    const uint32_t st = sb + r.slot * SLOT, fb = BAR_FULL(sb, r.slot);
                    if (el) {
                        mbar_expect_tx(fb, it < 4 ? 24576 : 28672);
                        tma_load_mc(st + 8192 + rank * 4096, &mp.wqkv, 1024 + cb, k0, fb);
                        tma_load_mc(st + 16384 + rank * 4096, &mp.wqkv, 2048 + cb, k0, fb);
                        tma_load_mc(st + 24576 + rank * 4096, &mp.wqkv, cb, k0, fb);
                        if (it < 4) mbar_arrive(fb + AF_REL);
                        if (it == PFWO + (m >> 1)) { tma_prefetch(&mp.wo, j * 128, m * 64); tma_prefetch(&mp.wo, j * 128 + 64, m * 64); }
                    }
                    r.next();
                }
                if (el) mbar_arrive(BAR_ONE(sb, EV_KV));
#pragma unroll 1
                for (int it = 0; it < 16; ++it) {
                    if ((AGO & 2) && it == 6) mbar_wait(BAR_ONE(sb, EV_AGO1), 0);
                    mbar_wait(BAR_EMPTY(sb, r.slot), r.par);
                    const uint32_t st = sb + r.slot * SLOT, fb = BAR_FULL(sb, r.slot);
                    if (el) {
                        mbar_expect_tx(fb, it < 2 ? 16384 : 24576);
                        tma_load_mc(st + 16384 + rank * 8192, &mp.wo, j * 128 + rank * 64, kof(it, 1, j), fb);
                        if (it < 2) mbar_arrive(fb + AF_REL);
                        if (it == 6) { prefetch_map(rank ? &mp.wu : &mp.wg); prefetch_map(rank ? &mp.wu3 : &mp.wg3); }
                    }
                    r.next();
                }
                const CUtensorMap* wm = rank ? &mp.wu : &mp.wg;
#pragma unroll 1
                for (int g = 0; g < 96; ++g) {
                    if ((AGO & 4) && g == 6) mbar_wait(BAR_ONE(sb, EV_AGO2), 0);
                    const int p = g >> 5, cb = hcol(p, j), k0 = p == 0 ? kof(g, 2, j) : (g & 31) * 32;
                    mbar_wait(BAR_EMPTY(sb, r.slot), r.par);
                    const uint32_t st = sb + r.slot * SLOT, fb = BAR_FULL(sb, r.slot);
                    if (el) {
                        mbar_expect_tx(fb, (g < 4 || p > 0) ? 24576 : 28672);
                        tma_load_mc(st + 8192 + rank * 4096, wm, cb, k0, fb);
                        tma_load_mc(st + 16384 + rank * 4096, wm, cb + 64, k0, fb);
                        if (p == 0) tma_load3_mc(st + 24576 + rank * 4096, rank ? &mp.wu3 : &mp.wg3, j, k0, fb);
                        else tma_load(st, &mp.h2l, k0, m * 128, fb);
                        if (g < 4) mbar_arrive(fb + AF_REL);
                        if (g == 90) prefetch_map(&mp.wd);
                    }
                    r.next();
                }
#pragma unroll 1
                for (int g = 0; g < 56; ++g) {
                    if (g == 0 || (g & 15) == 6 && g > 6) mbar_wait(BAR_ONE(sb, EV_H0 + (g >> 4)), 0);
                    const int k0 = g * 64;
                    mbar_wait(BAR_EMPTY(sb, r.slot), r.par);
                    const uint32_t st = sb + r.slot * SLOT, fb = BAR_FULL(sb, r.slot);
                    if (el) {
                        mbar_expect_tx(fb, 32768);
                        tma_load_mc(st + 16384 + rank * 8192, &mp.wd, j * 128 + rank * 64, k0, fb);
                        tma_load(st, &mp.hb, k0, m * 128, fb); tma_load(st + 8192, &mp.hb, k0, m * 128 + 64, fb);
                    }
                    r.next();
                }
            }
        } else if (aux) {
            if (warp < 11) {
                const uint32_t w = warp - 9;
                const bool el = elect_one();
#pragma unroll 1
                for (int p = 0; p < 4; ++p) {
                    const int mx = (j >> 1) * 8 + p * 2 + rank;
                    if (el) { mbar_arrive(BAR_SREADY(sb, w * 2)); mbar_arrive(BAR_SREADY(sb, w * 2 + 1)); }
                    mbar_wait2(BAR_SFULL(sb, w * 2), BAR_SFULL(sb, w * 2 + 1), p & 1);
                    if (el) {
                        tma_store(&mp.hb, HC3, mx * 128 + w * 64, sb + OFF_STG + w * 16384); tma_store(&mp.hb, HC3 + 64, mx * 128 + w * 64, sb + OFF_STG + w * 16384 + 8192);
                        bulk_commit(); bulk_wait_all(); flag_set(g_flags + FL_AUX + mx * 2 + w, ep * 8 + ST_H + 3);
                    }
                }
            }
        } else if (warp == 11) {
            const bool el = elect_one();
            const int row0 = m * 128;
            const uint32_t* const fl = g_flags + FL_PROG + (m * 32 + (lane & 16) + (kof(lane & 15, 1, j) >> 6)) * FS;
            if (el) { prefetch_map(&mp.h1h); prefetch_map(&mp.h2h); prefetch_map(&mp.h2l); }
            {
                const uint4* pk = pt.mail->mod1 + grp * 512 + j * 32 + lane;
                uint4 a, b; uint32_t n = 0;
                mbar_wait(BAR_ONE(sb, EV_WIN3), 0);
                while (true) {
                    a = ld_pkt16(pk); b = ld_pkt16(pk + 256);
                    if (__all_sync(0xffffffffu, a.z == ep && b.z == ep)) break;
                    SPIN_GUARD(n);
                }
                sts128(sb + OFF_PAR + lane * 16, a.x, a.y, b.x, b.y);
                __syncwarp();
                if (lane == 0) { mbar_arrive(BAR_ONE(sb, EV_PAR)); TL(46); }
            }
            mbar_wait(BAR_ONE(sb, EV_P0), 0);
            Ring r{0, 1};
#pragma unroll 1
            for (int ph = 0; ph < 3; ++ph) {
                const int sh = ph == 1 ? 1 : 2, nst = 8 << sh;
                const uint32_t half = 16384 >> sh;
                const CUtensorMap* tm = ph == 0 ? &mp.h1h : ph == 1 ? &mp.o : &mp.h2h;
                if (ph == 1) fetch_halo(g_halo + ((m - 1) * 8 + j) * 512 + 256 + lane, m == 0, sb, 2, lane);
                const uint32_t target = ep * 8 + ST_H1 + ph;
                int a0 = 1 << sh, a1 = a0, fr = a0;
                r.skip(fr);
                uint32_t s0 = r.slot, s1 = r.slot, have = 0, n = 0;
                int k0 = j ? 0 : 128, k1 = k0;
#pragma unroll 1
                for (; fr < NSLOT; ++fr) { mbar_wait(BAR_EMPTY(sb, r.slot), r.par); r.next(); }
                uint32_t v = flag_get(fl);
                auto load = [&](int& a, uint32_t& sl, int& k, uint32_t w) {
                    const uint32_t fb = BAR_FULL(sb, sl) + (w ? 0 : AF_REL);
                    if (el) { if (!w) mbar_expect_tx(fb, half); tma_load(sb + sl * SLOT + w * half, tm, k, row0 + w * 64, fb); }
                    if (a == NSLOT - 1 && w == ((AGW >> ph) & 1) && el) mbar_arrive(BAR_ONE(sb, EV_AGO + ph));
                    ++a; if (++sl == NSLOT) sl = 0;
                    k += 128 >> sh; if (k == j * 128) k += 128;
                };
                do {
                    PS(0);
                    if (fr < 10 && mbar_test(BAR_EMPTY(sb, r.slot), r.par) && (ph < 2 || mbar_test(BAR_ONE(sb, EV_X1 + (fr < 8)), 0))) { ++fr; r.next(); }
                    SPIN_GUARD(n);
                    PS(1);
                    const bool ok = (int32_t)(v - target) >= 0;
                    v = flag_get(fl);
                    have = __ballot_sync(0xffffffffu, ok);
                    PS(2);
#pragma unroll 1
                    while (a1 < fr && (have & (0x10000u << (a1 >> (sh - 1))))) {
                        if (a1 == (1 << sh)) TL(16 + ph);
                        load(a1, s1, k1, 1);
                    }
                    PS(3);
#pragma unroll 1
                    while (a0 < fr && (have & (1u << (a0 >> (sh - 1))))) load(a0, s0, k0, 0);
                    PS(4);
                } while (have != 0xffffffffu);
                if (ph == 2) mbar_wait2(BAR_ONE(sb, EV_X1), BAR_ONE(sb, EV_X11), 0);
#pragma unroll 1
                while (a0 < nst) {
                    mbar_wait(BAR_EMPTY(sb, r.slot), r.par);
                    r.next();
                    load(a1, s1, k1, 1); load(a0, s0, k0, 0);
                }
            }
#pragma unroll 1
            for (int p = 0; p < 4; ++p) {
                const uint32_t* f = p < 3 ? fl : g_flags + FL_AUX + m * 2 + (lane & 1);
                uint32_t n = 0;
                while (!__all_sync(0xffffffffu, (int32_t)(flag_get(f) - (ep * 8 + ST_H + p)) >= 0)) { SPIN_GUARD(n); __nanosleep(500); }
                if (el) mbar_arrive(BAR_ONE(sb, EV_H0 + p));
            }
        } else {
            const uint32_t w = warp - 9;
            const int row0 = m * 128 + w * 64;
            const uint32_t stg = sb + OFF_STG + w * 16384;
            uint32_t* const fl = g_flags + FL_PROG + (m * 32 + w * 16 + 2 * j) * FS;
            uint32_t b = 0, par = 0;
            const bool el = elect_one();
            auto store = [&](const CUtensorMap* tm, int col, bool nat = false) {
                mbar_wait(BAR_SFULL(sb, w * 2 + b), (par >> b) & 1);
                par ^= 1u << b;
                if (el) {
                    if (nat) tma_store3(tm, col, row0 >> 1, 0, stg + b * 8192); else tma_store(tm, col, row0, stg + b * 8192);
                    bulk_commit();
                }
                b ^= 1;
            };
            auto load2 = [&](const CUtensorMap* tm, bool nat) {
                if (el) {
#pragma unroll
                    for (uint32_t i = 0; i < 2; ++i) {
                        mbar_expect_tx(BAR_SREADY(sb, w * 2 + i), 8192);
                        if (nat) tma_load3(stg + i * 8192, tm, j * 128 + i * 64, row0 >> 1, BAR_SREADY(sb, w * 2 + i));
                        else tma_load(stg + i * 8192, tm, j * 128 + i * 64, row0, BAR_SREADY(sb, w * 2 + i));
                    }
                }
            };
            auto send2 = [&](const CUtensorMap* tm, int step) {
                store(tm, j * 128); store(tm, j * 128 + 64);
                if (el) {
                    asm volatile("cp.async.bulk.wait_group 1;" ::: "memory"); flag_set(fl, ep * 8 + step);
                    bulk_wait_all(); flag_set(fl + FS, ep * 8 + step);
                }
            };
            auto free2 = [&]() { if (el) { mbar_arrive(BAR_SREADY(sb, w * 2)); mbar_arrive(BAR_SREADY(sb, w * 2 + 1)); } };
            auto gate = [&](int vec, int ev) {
                uint4 v; uint32_t n = 0;
                while (true) {
                    v = ld_pkt2(g_mod + vec * 512 + j * 64 + lane * 2);
                    if (__all_sync(0xffffffffu, v.y == ep && v.w == ep)) break;
                    SPIN_GUARD(n); __nanosleep(300);
                }
                asm volatile("st.shared.v2.u32 [%0], {%1, %2};" :: "r"(sb + OFF_TAB + (ev - EV_GA) * 256 + lane * 8), "r"(v.x), "r"(v.z) : "memory");
                __syncwarp();
                if (lane == 0) mbar_arrive(BAR_ONE(sb, ev));
            };
            if (el) { prefetch_map(&mp.h1s); prefetch_map(&mp.o); prefetch_map(&mp.x1); prefetch_map(&mp.h2s); prefetch_map(&mp.hb); prefetch_map(&mp.out); prefetch_map(&mp.wo); }
            if (el) { flag_set(fl, ep * 8); flag_set(fl + FS, ep * 8); }
            send2(&mp.h1s, ST_H1);
            if (w == 0) TL(47);
            free2();
            if (w == 0) fetch_halo(g_halo + ((m - 1) * 8 + j) * 512 + lane, m == 0, sb, 0, lane);
            else { mbar_wait(BAR_ONE(sb, EV_KV), 0); gate(2, EV_GA); }
            send2(&mp.o, ST_O);
            if (w == 0) TL(40); else TL(38);
            mbar_wait(BAR_ONE(sb, EV_OWN + w), 0);
            load2(&mp.x, true);
            if (w == 1) {
                uint32_t n = 0;
                while ((int32_t)(flag_get(g_flags + FL_LN2) - ep * 8) < 0) { SPIN_GUARD(n); __nanosleep(200); }
                const uint4 v = __ldcg((const uint4*)(g_par2 + j * 128) + lane);
                sts128(sb + OFF_PAR + lane * 16, v.x, v.y, v.z, v.w);
                __syncwarp();
                if (lane == 0) mbar_arrive(BAR_ONE(sb, EV_LN2));
            }
            mbar_wait(BAR_ONE(sb, EV_X1S + w), 0);
            if (el) {
                tma_store(&mp.x1, j * 128, row0, sb + (X1_SLOT + 2 - 2 * w) * SLOT); tma_store(&mp.x1, j * 128 + 64, row0, sb + (X1_SLOT + 3 - 2 * w) * SLOT);
                bulk_commit(); bulk_wait_read(); mbar_arrive(BAR_ONE(sb, EV_X1 + w));
            }
            send2(&mp.h2s, ST_H2);
            if (el) { prefetch_map(&mp.hb); prefetch_map(&mp.hb3); }
            if (w == 0) TL(37);
            free2();
#pragma unroll 1
            for (int p = 0; p < 3; ++p) {
                const int col = hcol(p, j);
                store(&mp.hb, col); store(&mp.hb, col + 64);
                if (p == 0) {
                    mbar_wait(BAR_ONE(sb, EV_P3 + w), 0);
                    if (el) { tma_store3(&mp.hb3, 0, j, row0, sb + (w ? P3_SLOT1 : P3_SLOT0) * SLOT + 24576); bulk_commit(); }
                }
                if (el) { bulk_wait_all(); flag_set(fl, ep * 8 + ST_H + p); flag_set(fl + FS, ep * 8 + ST_H + p); }
                if (p < 2) free2();
                if (p == 0 && w == 1) gate(5, EV_GB);
            }
            load2(&mp.x1, false);
            cluster_arrive_early = true;
            cluster_arrive();
            store(&mp.out, j * 128, true); store(&mp.out, j * 128 + 64, true);
            if (el) bulk_wait_read();
        }
        __syncwarp();
    }
    if (aux || (wg == 2 && !cluster_arrive_early)) cluster_arrive();
    cluster_wait();
    if (tid == 0) {
        TL(15);
        flag_add(pt.mail->flags + FL_DONE);
    }
}

typedef CUresult (*EncodeFn)(CUtensorMap*, CUtensorMapDataType, cuuint32_t, void*, const cuuint64_t*, const cuuint64_t*, const cuuint32_t*,
                             const cuuint32_t*, CUtensorMapInterleave, CUtensorMapSwizzle, CUtensorMapL2promotion, CUtensorMapFloatOOBfill);

void make_map(EncodeFn fn, CUtensorMap* m, const void* ptr, uint64_t rows, uint64_t cols, uint32_t brows, uint32_t bcols) {
    cuuint64_t dims[2] = {cols, rows}, strides[1] = {cols * 2};
    cuuint32_t box[2] = {bcols, brows}, es[2] = {1, 1};
    fn(m, CU_TENSOR_MAP_DATA_TYPE_BFLOAT16, 2, (void*)ptr, dims, strides, box, es, CU_TENSOR_MAP_INTERLEAVE_NONE,
       bcols == 64 ? CU_TENSOR_MAP_SWIZZLE_128B : bcols == 32 ? CU_TENSOR_MAP_SWIZZLE_64B : CU_TENSOR_MAP_SWIZZLE_NONE, CU_TENSOR_MAP_L2_PROMOTION_L2_256B, CU_TENSOR_MAP_FLOAT_OOB_FILL_NONE);
}

void make_map3(EncodeFn fn, CUtensorMap* m, const void* ptr) {
    cuuint64_t dims[3] = {D_, S_ / 2, 2}, strides[2] = {4 * D_, 2 * D_};
    cuuint32_t box[3] = {64, 32, 2}, es[3] = {1, 1, 1};
    fn(m, CU_TENSOR_MAP_DATA_TYPE_BFLOAT16, 3, (void*)ptr, dims, strides, box, es, CU_TENSOR_MAP_INTERLEAVE_NONE,
       CU_TENSOR_MAP_SWIZZLE_128B, CU_TENSOR_MAP_L2_PROMOTION_L2_256B, CU_TENSOR_MAP_FLOAT_OOB_FILL_NONE);
}

void make_map48(EncodeFn fn, CUtensorMap* m, const void* ptr, uint64_t rows, uint32_t brows) {
    cuuint64_t dims[3] = {48, 8, rows}, strides[2] = {96, 2 * F_};
    cuuint32_t box[3] = {64, 1, brows}, es[3] = {1, 1, 1};
    fn(m, CU_TENSOR_MAP_DATA_TYPE_BFLOAT16, 3, (void*)ptr, dims, strides, box, es, CU_TENSOR_MAP_INTERLEAVE_NONE,
       CU_TENSOR_MAP_SWIZZLE_128B, CU_TENSOR_MAP_L2_PROMOTION_L2_256B, CU_TENSOR_MAP_FLOAT_OOB_FILL_NONE);
}

}

extern "C" void kernel_launch(void* const* d_in, const int* in_sizes, int n_in, void* d_out, int out_size) {
    (void)in_sizes; (void)n_in; (void)out_size;
    void* fnp = nullptr;
    cudaDriverEntryPointQueryResult qr;
    cudaGetDriverEntryPoint("cuTensorMapEncodeTiled", &fnp, cudaEnableDefault, &qr);
    EncodeFn fn = (EncodeFn)fnp;
    void *h1, *o, *x1, *h2, *hb, *mail;
    cudaGetSymbolAddress(&h1, g_h1);
    cudaGetSymbolAddress(&mail, g_mail);
    cudaGetSymbolAddress(&o, g_o);
    cudaGetSymbolAddress(&hb, g_hb);
    x1 = h1; h2 = o;
    Maps mp;
    make_map(fn, &mp.h1h, h1, S_, D_, 64, 32);
    make_map(fn, &mp.h2h, h2, S_, D_, 64, 32);
    make_map(fn, &mp.h1s, h1, S_, D_, 64, 64);
    make_map(fn, &mp.o, o, S_, D_, 64, 64);
    make_map(fn, &mp.h2l, h2, S_, D_, 128, 32);
    make_map(fn, &mp.h2s, h2, S_, D_, 64, 64);
    make_map(fn, &mp.hb, hb, S_, F_, 64, 64);
    make_map(fn, &mp.wqkv, d_in[1], D_, 3 * D_, 32, 64);
    make_map(fn, &mp.wo, d_in[2], D_, D_, 64, 64);
    make_map(fn, &mp.wg, d_in[4], D_, F_, 32, 64);
    make_map(fn, &mp.wu, d_in[5], D_, F_, 32, 64);
    make_map(fn, &mp.wd, d_in[6], F_, D_, 64, 64);
    make_map(fn, &mp.wmod, d_in[8], D_, 6 * D_, 64, 64);
    make_map(fn, &mp.wm8, d_in[8], D_ / 8, 8 * 6 * D_, 128, 16);
    make_map3(fn, &mp.x, d_in[0]);
    make_map(fn, &mp.x1, x1, S_, D_, 64, 64);
    make_map3(fn, &mp.out, d_out);
    make_map48(fn, &mp.wg3, d_in[4], D_, 32);
    make_map48(fn, &mp.wu3, d_in[5], D_, 32);
    make_map48(fn, &mp.hb3, hb, S_, 64);
    cudaFuncSetAttribute(fused_block_kernel, cudaFuncAttributeMaxDynamicSharedMemorySize, SMEM_BYTES);
    cudaLaunchConfig_t cfg = {};
    cfg.gridDim = dim3(NCTA); cfg.blockDim = dim3(384); cfg.dynamicSmemBytes = SMEM_BYTES; cfg.stream = cudaStreamPerThread;
    cudaLaunchAttribute at[1];
    at[0].id = cudaLaunchAttributeClusterDimension; at[0].val.clusterDim.x = 2; at[0].val.clusterDim.y = 1; at[0].val.clusterDim.z = 1;
    cfg.attrs = at; cfg.numAttrs = 1;
    const Ptrs pt{(const __nv_bfloat16*)d_in[7], (Mail*)mail};
    cudaLaunchKernelEx(&cfg, fused_block_kernel, pt, mp);
}
```

```cpp
#include <cuda_runtime.h>
#include <cuda_bf16.h>
#include <cuda.h>
#include <stdint.h>
#include <stddef.h>

#define LAG 3
#define LAGS 3
#define LAGW 3
#define LAGQ 4
#define MIDW 8
#define PFWO 14
#define FLAGRED 1
#define FS 1
#define AGO 7
#define AGW 6
#define CSW 0
#define FENCES 1
#define LWAIT 2
#define BW0 0
#define BWEV EV_WIN
#define GODLY 0
#define BW1 3
#define PDLY 500
#define H2ALIAS o
#define KDEBUG 0

namespace {

constexpr int S_ = 2048, D_ = 1024, F_ = 3584;
constexpr int NCTA = 132;
constexpr int NSLOT = 6;
constexpr uint32_t SLOT = 32768;
constexpr uint32_t OFF_STG = NSLOT * SLOT;
constexpr uint32_t OFF_BAR = OFF_STG + 32768;
constexpr uint32_t OFF_PAR = OFF_BAR + 512;
constexpr uint32_t OFF_TAB = OFF_PAR + 768;
constexpr uint32_t OFF_TL = OFF_PAR + 2048;
constexpr uint32_t SMEM_BYTES = OFF_TL + (KDEBUG ? 512 : 0);
constexpr uint32_t P3_SLOT1 = (32 + 16 + 32) % NSLOT, P3_SLOT0 = (P3_SLOT1 + 1) % NSLOT;

constexpr int ST_H1 = 1, ST_O = 2, ST_H2 = 3, ST_H = 4, FL_DONE = 0, FL_LN2 = 1, FL_AUX = 32, FL_PROG = 64;

struct Maps {
    CUtensorMap h1h, h1s, o, h2h, h2l, h2s, hb, wqkv, wo, wg, wu, wd, wmod, wm8, x, out, wg3, wu3, hb3;
};

struct Mail {
    uint32_t flags[16 * 32 * FS + 64];
    uint2 mod[6 * D_ / 2];
    uint4 mod1[8 * 512];
    uint4 st1[128 * 512];
    uint32_t par2[D_];
    uint4 halo[128 * 512];
};
struct Ptrs { const __nv_bfloat16* c; Mail* mail; };

__device__ __align__(128) Mail g_mail;
__device__ __align__(128) __nv_bfloat16 g_h1[S_ * D_];
__device__ __align__(128) __nv_bfloat16 g_o[S_ * D_];
__device__ __align__(128) __nv_bfloat16 g_hb[S_ * F_];
#define TL(i) do {} while (0)
#define TC(i) do {} while (0)
#define TS(g, which) do {} while (0)
#define CS(i) do {} while (0)

#define PS(i) do {} while (0)
__device__ __forceinline__ uint32_t smem_u32(const void* p) { return (uint32_t)__cvta_generic_to_shared(p); }
__device__ __forceinline__ void mbar_init(uint32_t bar, uint32_t cnt) { asm volatile("mbarrier.init.shared::cta.b64 [%0], %1;" :: "r"(bar), "r"(cnt) : "memory"); }
__device__ __forceinline__ void mbar_expect_tx(uint32_t bar, uint32_t bytes) { asm volatile("mbarrier.arrive.expect_tx.shared::cta.b64 _, [%0], %1;" :: "r"(bar), "r"(bytes) : "memory"); }
__device__ __forceinline__ void mbar_arrive(uint32_t bar) { asm volatile("mbarrier.arrive.shared::cta.b64 _, [%0];" :: "r"(bar) : "memory"); }
__device__ __forceinline__ void mbar_arrive_cta(uint32_t bar, uint32_t cta) {
    asm volatile("{\n.reg .b32 r;\nmapa.shared::cluster.u32 r, %0, %1;\nmbarrier.arrive.shared::cluster.b64 _, [r];\n}" :: "r"(bar), "r"(cta) : "memory");
}
__device__ __forceinline__ void mbar_wait(uint32_t bar, uint32_t parity) {
    asm volatile("{\n.reg .pred p;\n.reg .u32 n;\nmov.u32 n, 0;\n"
        "W_LOOP:\nmbarrier.try_wait.parity.shared::cta.b64 p, [%0], %1;\n@p bra W_DONE;\n"
        "add.u32 n, n, 1;\nsetp.lt.u32 p, n, 0x400000;\n@p bra W_LOOP;\ntrap;\nW_DONE:\n}" :: "r"(bar), "r"(parity) : "memory");
}
__device__ __forceinline__ void mbar_wait2(uint32_t b0, uint32_t b1, uint32_t parity) {
    asm volatile("{\n.reg .pred p, q;\n.reg .u32 n;\nmov.u32 n, 0;\n"
        "W_LOOP:\nmbarrier.try_wait.parity.shared::cta.b64 p, [%0], %2;\nmbarrier.try_wait.parity.shared::cta.b64 q, [%1], %2;\nand.pred p, p, q;\n@p bra W_DONE;\n"
        "add.u32 n, n, 1;\nsetp.lt.u32 p, n, 0x400000;\n@p bra W_LOOP;\ntrap;\nW_DONE:\n}" :: "r"(b0), "r"(b1), "r"(parity) : "memory");
}
__device__ __forceinline__ bool mbar_test(uint32_t bar, uint32_t parity) {
    uint32_t r; asm volatile("{\n.reg .pred p;\nmbarrier.test_wait.parity.shared::cta.b64 p, [%1], %2;\nselp.u32 %0, 1, 0, p;\n}" : "=r"(r) : "r"(bar), "r"(parity) : "memory"); return r;
}
__device__ __forceinline__ bool mbar_test2(uint32_t b0, uint32_t b1, uint32_t parity) {
    uint32_t r;
    asm volatile("{\n.reg .pred p, q;\nmbarrier.test_wait.parity.shared::cta.b64 p, [%1], %3;\nmbarrier.test_wait.parity.shared::cta.b64 q, [%2], %3;\n"
        "and.pred p, p, q;\nselp.u32 %0, 1, 0, p;\n}" : "=r"(r) : "r"(b0), "r"(b1), "r"(parity) : "memory");
    return r;
}
__device__ __forceinline__ void tma_load3(uint32_t dst, const CUtensorMap* m, int c0, int c1, uint32_t bar) {
    asm volatile("cp.async.bulk.tensor.3d.shared::cluster.global.mbarrier::complete_tx::bytes [%0], [%1, {%3, %4, %5}], [%2];"
        :: "r"(dst), "l"(m), "r"(bar), "r"(c0), "r"(c1), "r"(0) : "memory");
}
__device__ __forceinline__ void tma_store3(const CUtensorMap* m, int c0, int c1, int c2, uint32_t src) {
    asm volatile("cp.async.bulk.tensor.3d.global.shared::cta.bulk_group [%0, {%2, %3, %4}], [%1];" :: "l"(m), "r"(src), "r"(c0), "r"(c1), "r"(c2) : "memory");
}
__device__ __forceinline__ void tma_load3_mc(uint32_t dst, const CUtensorMap* m, int c1, int c2, uint32_t bar) {
    asm volatile("cp.async.bulk.tensor.3d.shared::cluster.global.mbarrier::complete_tx::bytes.multicast::cluster.L2::cache_hint [%0], [%1, {%3, %4, %5}], [%2], %6, %7;"
        :: "r"(dst), "l"(m), "r"(bar), "r"(0), "r"(c1), "r"(c2), "h"((uint16_t)3), "l"(0x12F0000000000000ull) : "memory");
}
__device__ __forceinline__ void tma_load(uint32_t dst, const CUtensorMap* m, int c0, int c1, uint32_t bar) {
    asm volatile("cp.async.bulk.tensor.2d.shared::cluster.global.mbarrier::complete_tx::bytes [%0], [%1, {%3, %4}], [%2];"
        :: "r"(dst), "l"(m), "r"(bar), "r"(c0), "r"(c1) : "memory");
}
__device__ __forceinline__ void tma_load_mc(uint32_t dst, const CUtensorMap* m, int c0, int c1, uint32_t bar) {
    asm volatile("cp.async.bulk.tensor.2d.shared::cluster.global.mbarrier::complete_tx::bytes.multicast::cluster.L2::cache_hint [%0], [%1, {%3, %4}], [%2], %5, %6;"
        :: "r"(dst), "l"(m), "r"(bar), "r"(c0), "r"(c1), "h"((uint16_t)3), "l"(0x12F0000000000000ull) : "memory");
}
__device__ __forceinline__ void tma_prefetch(const CUtensorMap* m, int c0, int c1) {
    asm volatile("cp.async.bulk.prefetch.tensor.2d.L2.global [%0, {%1, %2}];" :: "l"(m), "r"(c0), "r"(c1) : "memory");
}
__device__ __forceinline__ void tma_store(const CUtensorMap* m, int c0, int c1, uint32_t src) {
    asm volatile("cp.async.bulk.tensor.2d.global.shared::cta.bulk_group [%0, {%2, %3}], [%1];" :: "l"(m), "r"(src), "r"(c0), "r"(c1) : "memory");
}
__device__ __forceinline__ void bulk_commit() { asm volatile("cp.async.bulk.commit_group;" ::: "memory"); }
__device__ __forceinline__ void bulk_wait_read() { asm volatile("cp.async.bulk.wait_group.read 0;" ::: "memory"); }
__device__ __forceinline__ void bulk_wait_all() { asm volatile("cp.async.bulk.wait_group 0;" ::: "memory"); }
__device__ __forceinline__ void fence_async_smem() { asm volatile("fence.proxy.async.shared::cta;" ::: "memory"); }
__device__ __forceinline__ void prefetch_map(const CUtensorMap* m) { asm volatile("prefetch.tensormap [%0];" :: "l"(m) : "memory"); }
__device__ __forceinline__ void wg_fence() { asm volatile("wgmma.fence.sync.aligned;" ::: "memory"); }
__device__ __forceinline__ void wg_commit() { asm volatile("wgmma.commit_group.sync.aligned;" ::: "memory"); }
template <int N> __device__ __forceinline__ void wg_wait() { asm volatile("wgmma.wait_group.sync.aligned %0;" :: "n"(N) : "memory"); }
__device__ __forceinline__ void bar_sync(int id, int n) { asm volatile("bar.sync %0, %1;" :: "r"(id), "r"(n) : "memory"); }
__device__ __forceinline__ void bar_arrive(int id, int n) { asm volatile("bar.arrive %0, %1;" :: "r"(id), "r"(n) : "memory"); }
__device__ __forceinline__ void flag_add(uint32_t* f) { asm volatile("red.relaxed.gpu.global.add.u32 [%0], 1;" :: "l"(f) : "memory"); }
__device__ __forceinline__ void flag_set(uint32_t* f, uint32_t v) { asm volatile("red.relaxed.gpu.global.max.u32 [%0], %1;" :: "l"(f), "r"(v) : "memory"); }
__device__ __forceinline__ uint32_t flag_get(const uint32_t* f) { uint32_t v; asm volatile("ld.relaxed.gpu.global.u32 %0, [%1];" : "=r"(v) : "l"(f) : "memory"); return v; }
__device__ __forceinline__ uint32_t d16(uint32_t addr) { return (addr & 0x3FFFF) >> 4; }
__device__ __forceinline__ uint64_t mk_desc(uint32_t a16, uint32_t off, uint32_t lbo, uint32_t sbo, uint32_t swz) {
    const uint32_t lo = a16 + (off >> 4) + ((lbo >> 4) << 16), hi = (sbo >> 4) | (swz << 30);
    return ((uint64_t)hi << 32) | lo;
}
__device__ __forceinline__ uint32_t pack2(float lo, float hi) {
    uint32_t r; asm("cvt.rn.bf16x2.f32 %0, %1, %2;" : "=r"(r) : "f"(hi), "f"(lo)); return r;
}
__device__ __forceinline__ uint32_t hfma2_bf16(uint32_t a, uint32_t b, uint32_t c) {
    uint32_t r; asm("fma.rn.bf16x2 %0, %1, %2, %3;" : "=r"(r) : "r"(a), "r"(b), "r"(c)); return r;
}
__device__ __forceinline__ float bf_lo(uint32_t v) { return __uint_as_float(v << 16); }
__device__ __forceinline__ float bf_hi(uint32_t v) { return __uint_as_float(v & 0xFFFF0000u); }
__device__ __forceinline__ void unpack2(uint32_t v, float& lo, float& hi) {
    asm volatile("shl.b32 %0, %2, 16;\nand.b32 %1, %2, 0xffff0000;" : "=f"(lo), "=f"(hi) : "r"(v));
}
__device__ __forceinline__ float bf_round(float x) { return __bfloat162float(__float2bfloat16_rn(x)); }
__device__ __forceinline__ void stsm4(uint32_t addr, uint32_t r0, uint32_t r1, uint32_t r2, uint32_t r3) {
    asm volatile("stmatrix.sync.aligned.m8n8.x4.shared.b16 [%0], {%1, %2, %3, %4};" :: "r"(addr), "r"(r0), "r"(r1), "r"(r2), "r"(r3) : "memory");
}
__device__ __forceinline__ void stsm4t(uint32_t addr, uint32_t r0, uint32_t r1, uint32_t r2, uint32_t r3) {
    asm volatile("stmatrix.sync.aligned.m8n8.x4.trans.shared.b16 [%0], {%1, %2, %3, %4};" :: "r"(addr), "r"(r0), "r"(r1), "r"(r2), "r"(r3) : "memory");
}
__device__ __forceinline__ uint32_t movm(uint32_t a) { uint32_t d; asm volatile("movmatrix.sync.aligned.m8n8.trans.b16 %0, %1;" : "=r"(d) : "r"(a)); return d; }
__device__ __forceinline__ void ldsm4(uint32_t addr, uint32_t& r0, uint32_t& r1, uint32_t& r2, uint32_t& r3) {
    asm volatile("ldmatrix.sync.aligned.m8n8.x4.shared.b16 {%0, %1, %2, %3}, [%4];" : "=r"(r0), "=r"(r1), "=r"(r2), "=r"(r3) : "r"(addr) : "memory");
}
__device__ __forceinline__ void ldsm4t(uint32_t addr, uint32_t& r0, uint32_t& r1, uint32_t& r2, uint32_t& r3) {
    asm volatile("ldmatrix.sync.aligned.m8n8.x4.trans.shared.b16 {%0, %1, %2, %3}, [%4];" : "=r"(r0), "=r"(r1), "=r"(r2), "=r"(r3) : "r"(addr) : "memory");
}
__device__ __forceinline__ void mma16816(float (&c)[4], uint32_t a0, uint32_t a1, uint32_t a2, uint32_t a3, uint32_t b0, uint32_t b1) {
    asm("mma.sync.aligned.m16n8k16.row.col.f32.bf16.bf16.f32 {%0, %1, %2, %3}, {%4, %5, %6, %7}, {%8, %9}, {%0, %1, %2, %3};"
        : "+f"(c[0]), "+f"(c[1]), "+f"(c[2]), "+f"(c[3]) : "r"(a0), "r"(a1), "r"(a2), "r"(a3), "r"(b0), "r"(b1));
}
__device__ __forceinline__ float rcp(float x) { float r; asm("rcp.approx.ftz.f32 %0, %1;" : "=f"(r) : "f"(x)); return r; }
__device__ __forceinline__ float ex2(float x) { float r; asm("ex2.approx.ftz.f32 %0, %1;" : "=f"(r) : "f"(x)); return r; }
__device__ __forceinline__ float glu_half(float gh, float uh) {
    float t; asm("tanh.approx.f32 %0, %1;" : "=f"(t) : "f"(gh)); return fmaf(t, uh, uh);
}
__device__ __forceinline__ float silu_(float x) { return __fdividef(x, 1.f + __expf(-x)); }
__device__ __forceinline__ void st_pkt(void* p, uint32_t a, uint32_t b) {
    asm volatile("{\n.reg .b64 t;\nmov.b64 t, {%1, %2};\nst.relaxed.gpu.global.b64 [%0], t;\n}" :: "l"(p), "r"(a), "r"(b) : "memory");
}
__device__ __forceinline__ uint4 ld_pkt2(const void* p) {
    uint4 v; asm volatile("{\n.reg .b64 t, u;\nld.relaxed.gpu.global.v2.b64 {t, u}, [%4];\nmov.b64 {%0, %1}, t;\nmov.b64 {%2, %3}, u;\n}"
        : "=r"(v.x), "=r"(v.y), "=r"(v.z), "=r"(v.w) : "l"(p) : "memory"); return v;
}
__device__ __forceinline__ void st_pkt16(void* p, uint32_t a, uint32_t b, uint32_t c, uint32_t d) {
    asm volatile("{\n.reg .b64 t, u;\n.reg .b128 w;\nmov.b64 t, {%1, %2};\nmov.b64 u, {%3, %4};\nmov.b128 w, {t, u};\nst.relaxed.gpu.global.b128 [%0], w;\n}"
        :: "l"(p), "r"(a), "r"(b), "r"(c), "r"(d) : "memory");
}
__device__ __forceinline__ uint4 ld_pkt16(const void* p) {
    uint4 v; asm volatile("{\n.reg .b64 t, u;\n.reg .b128 w;\nld.relaxed.gpu.global.b128 w, [%4];\nmov.b128 {t, u}, w;\nmov.b64 {%0, %1}, t;\nmov.b64 {%2, %3}, u;\n}"
        : "=r"(v.x), "=r"(v.y), "=r"(v.z), "=r"(v.w) : "l"(p) : "memory"); return v;
}
#define SPIN_GUARD(n) do { if (++(n) > (1u << 22)) asm volatile("trap;"); } while (0)
__device__ __forceinline__ uint4 lds128(uint32_t a) { uint4 v; asm volatile("ld.shared.v4.u32 {%0, %1, %2, %3}, [%4];" : "=r"(v.x), "=r"(v.y), "=r"(v.z), "=r"(v.w) : "r"(a) : "memory"); return v; }
__device__ __forceinline__ void sts128(uint32_t a, uint32_t x, uint32_t y, uint32_t z, uint32_t w) { asm volatile("st.shared.v4.u32 [%0], {%1, %2, %3, %4};" :: "r"(a), "r"(x), "r"(y), "r"(z), "r"(w) : "memory"); }
__device__ __forceinline__ uint32_t lds32(uint32_t a) { uint32_t v; asm volatile("ld.shared.u32 %0, [%1];" : "=r"(v) : "r"(a) : "memory"); return v; }
__device__ __forceinline__ void sts32(uint32_t a, uint32_t v) { asm volatile("st.shared.u32 [%0], %1;" :: "r"(a), "r"(v) : "memory"); }
__device__ __forceinline__ bool elect_one() {
    uint32_t p; asm volatile("{\n.reg .pred q;\nelect.sync _|q, 0xffffffff;\nselp.u32 %0, 1, 0, q;\n}" : "=r"(p)); return p;
}
__device__ __forceinline__ void cluster_arrive() { asm volatile("barrier.cluster.arrive.relaxed.aligned;" ::: "memory"); }
__device__ __forceinline__ void cluster_wait() { asm volatile("barrier.cluster.wait.aligned;" ::: "memory"); }

__device__ __forceinline__ void wgmma_n128_z(float (&d)[64], uint64_t da, uint64_t db) {
    asm volatile("{\n.reg .pred p;\nsetp.ne.b32 p, 0, 0;\n"
        "wgmma.mma_async.sync.aligned.m64n128k16.f32.bf16.bf16 {"
        "%0, %1, %2, %3, %4, %5, %6, %7, %8, %9, %10, %11, %12, %13, %14, %15, "
        "%16, %17, %18, %19, %20, %21, %22, %23, %24, %25, %26, %27, %28, %29, %30, %31, "
        "%32, %33, %34, %35, %36, %37, %38, %39, %40, %41, %42, %43, %44, %45, %46, %47, "
        "%48, %49, %50, %51, %52, %53, %54, %55, %56, %57, %58, %59, %60, %61, %62, %63"
        "}, %64, %65, p, 1, 1, 0, 1;\n}\n"
        : "=f"(d[0]), "=f"(d[1]), "=f"(d[2]), "=f"(d[3]), "=f"(d[4]), "=f"(d[5]), "=f"(d[6]), "=f"(d[7]),
          "=f"(d[8]), "=f"(d[9]), "=f"(d[10]), "=f"(d[11]), "=f"(d[12]), "=f"(d[13]), "=f"(d[14]), "=f"(d[15]),
          "=f"(d[16]), "=f"(d[17]), "=f"(d[18]), "=f"(d[19]), "=f"(d[20]), "=f"(d[21]), "=f"(d[22]), "=f"(d[23]),
          "=f"(d[24]), "=f"(d[25]), "=f"(d[26]), "=f"(d[27]), "=f"(d[28]), "=f"(d[29]), "=f"(d[30]), "=f"(d[31]),
          "=f"(d[32]), "=f"(d[33]), "=f"(d[34]), "=f"(d[35]), "=f"(d[36]), "=f"(d[37]), "=f"(d[38]), "=f"(d[39]),
          "=f"(d[40]), "=f"(d[41]), "=f"(d[42]), "=f"(d[43]), "=f"(d[44]), "=f"(d[45]), "=f"(d[46]), "=f"(d[47]),
          "=f"(d[48]), "=f"(d[49]), "=f"(d[50]), "=f"(d[51]), "=f"(d[52]), "=f"(d[53]), "=f"(d[54]), "=f"(d[55]),
          "=f"(d[56]), "=f"(d[57]), "=f"(d[58]), "=f"(d[59]), "=f"(d[60]), "=f"(d[61]), "=f"(d[62]), "=f"(d[63])
        : "l"(da), "l"(db));
}
__device__ __forceinline__ void wgmma_n128(float (&d)[64], uint64_t da, uint64_t db) {
    asm volatile("{\n.reg .pred p;\nsetp.eq.b32 p, 0, 0;\n"
        "wgmma.mma_async.sync.aligned.m64n128k16.f32.bf16.bf16 {"
        "%0, %1, %2, %3, %4, %5, %6, %7, %8, %9, %10, %11, %12, %13, %14, %15, "
        "%16, %17, %18, %19, %20, %21, %22, %23, %24, %25, %26, %27, %28, %29, %30, %31, "
        "%32, %33, %34, %35, %36, %37, %38, %39, %40, %41, %42, %43, %44, %45, %46, %47, "
        "%48, %49, %50, %51, %52, %53, %54, %55, %56, %57, %58, %59, %60, %61, %62, %63"
        "}, %64, %65, p, 1, 1, 0, 1;\n}\n"
        : "+f"(d[0]), "+f"(d[1]), "+f"(d[2]), "+f"(d[3]), "+f"(d[4]), "+f"(d[5]), "+f"(d[6]), "+f"(d[7]),
          "+f"(d[8]), "+f"(d[9]), "+f"(d[10]), "+f"(d[11]), "+f"(d[12]), "+f"(d[13]), "+f"(d[14]), "+f"(d[15]),
          "+f"(d[16]), "+f"(d[17]), "+f"(d[18]), "+f"(d[19]), "+f"(d[20]), "+f"(d[21]), "+f"(d[22]), "+f"(d[23]),
          "+f"(d[24]), "+f"(d[25]), "+f"(d[26]), "+f"(d[27]), "+f"(d[28]), "+f"(d[29]), "+f"(d[30]), "+f"(d[31]),
          "+f"(d[32]), "+f"(d[33]), "+f"(d[34]), "+f"(d[35]), "+f"(d[36]), "+f"(d[37]), "+f"(d[38]), "+f"(d[39]),
          "+f"(d[40]), "+f"(d[41]), "+f"(d[42]), "+f"(d[43]), "+f"(d[44]), "+f"(d[45]), "+f"(d[46]), "+f"(d[47]),
          "+f"(d[48]), "+f"(d[49]), "+f"(d[50]), "+f"(d[51]), "+f"(d[52]), "+f"(d[53]), "+f"(d[54]), "+f"(d[55]),
          "+f"(d[56]), "+f"(d[57]), "+f"(d[58]), "+f"(d[59]), "+f"(d[60]), "+f"(d[61]), "+f"(d[62]), "+f"(d[63])
        : "l"(da), "l"(db));
}
__device__ __forceinline__ void wgmma_n176_z(float (&d)[88], uint64_t da, uint64_t db) {
    asm volatile("{\n.reg .pred p;\nsetp.ne.b32 p, 0, 0;\n"
        "wgmma.mma_async.sync.aligned.m64n176k16.f32.bf16.bf16 {"
        "%0, %1, %2, %3, %4, %5, %6, %7, %8, %9, %10, %11, %12, %13, %14, %15, "
        "%16, %17, %18, %19, %20, %21, %22, %23, %24, %25, %26, %27, %28, %29, %30, %31, "
        "%32, %33, %34, %35, %36, %37, %38, %39, %40, %41, %42, %43, %44, %45, %46, %47, "
        "%48, %49, %50, %51, %52, %53, %54, %55, %56, %57, %58, %59, %60, %61, %62, %63, "
        "%64, %65, %66, %67, %68, %69, %70, %71, %72, %73, %74, %75, %76, %77, %78, %79, "
        "%80, %81, %82, %83, %84, %85, %86, %87"
        "}, %88, %89, p, 1, 1, 0, 1;\n}\n"
        : "=f"(d[0]), "=f"(d[1]), "=f"(d[2]), "=f"(d[3]), "=f"(d[4]), "=f"(d[5]), "=f"(d[6]), "=f"(d[7]),
          "=f"(d[8]), "=f"(d[9]), "=f"(d[10]), "=f"(d[11]), "=f"(d[12]), "=f"(d[13]), "=f"(d[14]), "=f"(d[15]),
          "=f"(d[16]), "=f"(d[17]), "=f"(d[18]), "=f"(d[19]), "=f"(d[20]), "=f"(d[21]), "=f"(d[22]), "=f"(d[23]),
          "=f"(d[24]), "=f"(d[25]), "=f"(d[26]), "=f"(d[27]), "=f"(d[28]), "=f"(d[29]), "=f"(d[30]), "=f"(d[31]),
          "=f"(d[32]), "=f"(d[33]), "=f"(d[34]), "=f"(d[35]), "=f"(d[36]), "=f"(d[37]), "=f"(d[38]), "=f"(d[39]),
          "=f"(d[40]), "=f"(d[41]), "=f"(d[42]), "=f"(d[43]), "=f"(d[44]), "=f"(d[45]), "=f"(d[46]), "=f"(d[47]),
          "=f"(d[48]), "=f"(d[49]), "=f"(d[50]), "=f"(d[51]), "=f"(d[52]), "=f"(d[53]), "=f"(d[54]), "=f"(d[55]),
          "=f"(d[56]), "=f"(d[57]), "=f"(d[58]), "=f"(d[59]), "=f"(d[60]), "=f"(d[61]), "=f"(d[62]), "=f"(d[63]),
          "=f"(d[64]), "=f"(d[65]), "=f"(d[66]), "=f"(d[67]), "=f"(d[68]), "=f"(d[69]), "=f"(d[70]), "=f"(d[71]),
          "=f"(d[72]), "=f"(d[73]), "=f"(d[74]), "=f"(d[75]), "=f"(d[76]), "=f"(d[77]), "=f"(d[78]), "=f"(d[79]),
          "=f"(d[80]), "=f"(d[81]), "=f"(d[82]), "=f"(d[83]), "=f"(d[84]), "=f"(d[85]), "=f"(d[86]), "=f"(d[87])
        : "l"(da), "l"(db));
}
__device__ __forceinline__ void wgmma_n176(float (&d)[88], uint64_t da, uint64_t db) {
    asm volatile("{\n.reg .pred p;\nsetp.eq.b32 p, 0, 0;\n"
        "wgmma.mma_async.sync.aligned.m64n176k16.f32.bf16.bf16 {"
        "%0, %1, %2, %3, %4, %5, %6, %7, %8, %9, %10, %11, %12, %13, %14, %15, "
        "%16, %17, %18, %19, %20, %21, %22, %23, %24, %25, %26, %27, %28, %29, %30, %31, "
        "%32, %33, %34, %35, %36, %37, %38, %39, %40, %41, %42, %43, %44, %45, %46, %47, "
        "%48, %49, %50, %51, %52, %53, %54, %55, %56, %57, %58, %59, %60, %61, %62, %63, "
        "%64, %65, %66, %67, %68, %69, %70, %71, %72, %73, %74, %75, %76, %77, %78, %79, "
        "%80, %81, %82, %83, %84, %85, %86, %87"
        "}, %88, %89, p, 1, 1, 0, 1;\n}\n"
        : "+f"(d[0]), "+f"(d[1]), "+f"(d[2]), "+f"(d[3]), "+f"(d[4]), "+f"(d[5]), "+f"(d[6]), "+f"(d[7]),
          "+f"(d[8]), "+f"(d[9]), "+f"(d[10]), "+f"(d[11]), "+f"(d[12]), "+f"(d[13]), "+f"(d[14]), "+f"(d[15]),
          "+f"(d[16]), "+f"(d[17]), "+f"(d[18]), "+f"(d[19]), "+f"(d[20]), "+f"(d[21]), "+f"(d[22]), "+f"(d[23]),
          "+f"(d[24]), "+f"(d[25]), "+f"(d[26]), "+f"(d[27]), "+f"(d[28]), "+f"(d[29]), "+f"(d[30]), "+f"(d[31]),
          "+f"(d[32]), "+f"(d[33]), "+f"(d[34]), "+f"(d[35]), "+f"(d[36]), "+f"(d[37]), "+f"(d[38]), "+f"(d[39]),
          "+f"(d[40]), "+f"(d[41]), "+f"(d[42]), "+f"(d[43]), "+f"(d[44]), "+f"(d[45]), "+f"(d[46]), "+f"(d[47]),
          "+f"(d[48]), "+f"(d[49]), "+f"(d[50]), "+f"(d[51]), "+f"(d[52]), "+f"(d[53]), "+f"(d[54]), "+f"(d[55]),
          "+f"(d[56]), "+f"(d[57]), "+f"(d[58]), "+f"(d[59]), "+f"(d[60]), "+f"(d[61]), "+f"(d[62]), "+f"(d[63]),
          "+f"(d[64]), "+f"(d[65]), "+f"(d[66]), "+f"(d[67]), "+f"(d[68]), "+f"(d[69]), "+f"(d[70]), "+f"(d[71]),
          "+f"(d[72]), "+f"(d[73]), "+f"(d[74]), "+f"(d[75]), "+f"(d[76]), "+f"(d[77]), "+f"(d[78]), "+f"(d[79]),
          "+f"(d[80]), "+f"(d[81]), "+f"(d[82]), "+f"(d[83]), "+f"(d[84]), "+f"(d[85]), "+f"(d[86]), "+f"(d[87])
        : "l"(da), "l"(db));
}
__device__ __forceinline__ void wgmma_n256_z(float (&d)[128], uint64_t da, uint64_t db) {
    asm volatile("{\n.reg .pred p;\nsetp.ne.b32 p, 0, 0;\n"
        "wgmma.mma_async.sync.aligned.m64n256k16.f32.bf16.bf16 {"
        "%0, %1, %2, %3, %4, %5, %6, %7, %8, %9, %10, %11, %12, %13, %14, %15, "
        "%16, %17, %18, %19, %20, %21, %22, %23, %24, %25, %26, %27, %28, %29, %30, %31, "
        "%32, %33, %34, %35, %36, %37, %38, %39, %40, %41, %42, %43, %44, %45, %46, %47, "
        "%48, %49, %50, %51, %52, %53, %54, %55, %56, %57, %58, %59, %60, %61, %62, %63, "
        "%64, %65, %66, %67, %68, %69, %70, %71, %72, %73, %74, %75, %76, %77, %78, %79, "
        "%80, %81, %82, %83, %84, %85, %86, %87, %88, %89, %90, %91, %92, %93, %94, %95, "
        "%96, %97, %98, %99, %100, %101, %102, %103, %104, %105, %106, %107, %108, %109, %110, %111, "
        "%112, %113, %114, %115, %116, %117, %118, %119, %120, %121, %122, %123, %124, %125, %126, %127"
        "}, %128, %129, p, 1, 1, 0, 1;\n}\n"
        : "=f"(d[0]), "=f"(d[1]), "=f"(d[2]), "=f"(d[3]), "=f"(d[4]), "=f"(d[5]), "=f"(d[6]), "=f"(d[7]),
          "=f"(d[8]), "=f"(d[9]), "=f"(d[10]), "=f"(d[11]), "=f"(d[12]), "=f"(d[13]), "=f"(d[14]), "=f"(d[15]),
          "=f"(d[16]), "=f"(d[17]), "=f"(d[18]), "=f"(d[19]), "=f"(d[20]), "=f"(d[21]), "=f"(d[22]), "=f"(d[23]),
          "=f"(d[24]), "=f"(d[25]), "=f"(d[26]), "=f"(d[27]), "=f"(d[28]), "=f"(d[29]), "=f"(d[30]), "=f"(d[31]),
          "=f"(d[32]), "=f"(d[33]), "=f"(d[34]), "=f"(d[35]), "=f"(d[36]), "=f"(d[37]), "=f"(d[38]), "=f"(d[39]),
          "=f"(d[40]), "=f"(d[41]), "=f"(d[42]), "=f"(d[43]), "=f"(d[44]), "=f"(d[45]), "=f"(d[46]), "=f"(d[47]),
          "=f"(d[48]), "=f"(d[49]), "=f"(d[50]), "=f"(d[51]), "=f"(d[52]), "=f"(d[53]), "=f"(d[54]), "=f"(d[55]),
          "=f"(d[56]), "=f"(d[57]), "=f"(d[58]), "=f"(d[59]), "=f"(d[60]), "=f"(d[61]), "=f"(d[62]), "=f"(d[63]),
          "=f"(d[64]), "=f"(d[65]), "=f"(d[66]), "=f"(d[67]), "=f"(d[68]), "=f"(d[69]), "=f"(d[70]), "=f"(d[71]),
          "=f"(d[72]), "=f"(d[73]), "=f"(d[74]), "=f"(d[75]), "=f"(d[76]), "=f"(d[77]), "=f"(d[78]), "=f"(d[79]),
          "=f"(d[80]), "=f"(d[81]), "=f"(d[82]), "=f"(d[83]), "=f"(d[84]), "=f"(d[85]), "=f"(d[86]), "=f"(d[87]),
          "=f"(d[88]), "=f"(d[89]), "=f"(d[90]), "=f"(d[91]), "=f"(d[92]), "=f"(d[93]), "=f"(d[94]), "=f"(d[95]),
          "=f"(d[96]), "=f"(d[97]), "=f"(d[98]), "=f"(d[99]), "=f"(d[100]), "=f"(d[101]), "=f"(d[102]), "=f"(d[103]),
          "=f"(d[104]), "=f"(d[105]), "=f"(d[106]), "=f"(d[107]), "=f"(d[108]), "=f"(d[109]), "=f"(d[110]), "=f"(d[111]),
          "=f"(d[112]), "=f"(d[113]), "=f"(d[114]), "=f"(d[115]), "=f"(d[116]), "=f"(d[117]), "=f"(d[118]), "=f"(d[119]),
          "=f"(d[120]), "=f"(d[121]), "=f"(d[122]), "=f"(d[123]), "=f"(d[124]), "=f"(d[125]), "=f"(d[126]), "=f"(d[127])
        : "l"(da), "l"(db));
}
__device__ __forceinline__ void wgmma_n256(float (&d)[128], uint64_t da, uint64_t db) {
    asm volatile("{\n.reg .pred p;\nsetp.eq.b32 p, 0, 0;\n"
        "wgmma.mma_async.sync.aligned.m64n256k16.f32.bf16.bf16 {"
        "%0, %1, %2, %3, %4, %5, %6, %7, %8, %9, %10, %11, %12, %13, %14, %15, "
        "%16, %17, %18, %19, %20, %21, %22, %23, %24, %25, %26, %27, %28, %29, %30, %31, "
        "%32, %33, %34, %35, %36, %37, %38, %39, %40, %41, %42, %43, %44, %45, %46, %47, "
        "%48, %49, %50, %51, %52, %53, %54, %55, %56, %57, %58, %59, %60, %61, %62, %63, "
        "%64, %65, %66, %67, %68, %69, %70, %71, %72, %73, %74, %75, %76, %77, %78, %79, "
        "%80, %81, %82, %83, %84, %85, %86, %87, %88, %89, %90, %91, %92, %93, %94, %95, "
        "%96, %97, %98, %99, %100, %101, %102, %103, %104, %105, %106, %107, %108, %109, %110, %111, "
        "%112, %113, %114, %115, %116, %117, %118, %119, %120, %121, %122, %123, %124, %125, %126, %127"
        "}, %128, %129, p, 1, 1, 0, 1;\n}\n"
        : "+f"(d[0]), "+f"(d[1]), "+f"(d[2]), "+f"(d[3]), "+f"(d[4]), "+f"(d[5]), "+f"(d[6]), "+f"(d[7]),
          "+f"(d[8]), "+f"(d[9]), "+f"(d[10]), "+f"(d[11]), "+f"(d[12]), "+f"(d[13]), "+f"(d[14]), "+f"(d[15]),
          "+f"(d[16]), "+f"(d[17]), "+f"(d[18]), "+f"(d[19]), "+f"(d[20]), "+f"(d[21]), "+f"(d[22]), "+f"(d[23]),
          "+f"(d[24]), "+f"(d[25]), "+f"(d[26]), "+f"(d[27]), "+f"(d[28]), "+f"(d[29]), "+f"(d[30]), "+f"(d[31]),
          "+f"(d[32]), "+f"(d[33]), "+f"(d[34]), "+f"(d[35]), "+f"(d[36]), "+f"(d[37]), "+f"(d[38]), "+f"(d[39]),
          "+f"(d[40]), "+f"(d[41]), "+f"(d[42]), "+f"(d[43]), "+f"(d[44]), "+f"(d[45]), "+f"(d[46]), "+f"(d[47]),
          "+f"(d[48]), "+f"(d[49]), "+f"(d[50]), "+f"(d[51]), "+f"(d[52]), "+f"(d[53]), "+f"(d[54]), "+f"(d[55]),
          "+f"(d[56]), "+f"(d[57]), "+f"(d[58]), "+f"(d[59]), "+f"(d[60]), "+f"(d[61]), "+f"(d[62]), "+f"(d[63]),
          "+f"(d[64]), "+f"(d[65]), "+f"(d[66]), "+f"(d[67]), "+f"(d[68]), "+f"(d[69]), "+f"(d[70]), "+f"(d[71]),
          "+f"(d[72]), "+f"(d[73]), "+f"(d[74]), "+f"(d[75]), "+f"(d[76]), "+f"(d[77]), "+f"(d[78]), "+f"(d[79]),
          "+f"(d[80]), "+f"(d[81]), "+f"(d[82]), "+f"(d[83]), "+f"(d[84]), "+f"(d[85]), "+f"(d[86]), "+f"(d[87]),
          "+f"(d[88]), "+f"(d[89]), "+f"(d[90]), "+f"(d[91]), "+f"(d[92]), "+f"(d[93]), "+f"(d[94]), "+f"(d[95]),
          "+f"(d[96]), "+f"(d[97]), "+f"(d[98]), "+f"(d[99]), "+f"(d[100]), "+f"(d[101]), "+f"(d[102]), "+f"(d[103]),
          "+f"(d[104]), "+f"(d[105]), "+f"(d[106]), "+f"(d[107]), "+f"(d[108]), "+f"(d[109]), "+f"(d[110]), "+f"(d[111]),
          "+f"(d[112]), "+f"(d[113]), "+f"(d[114]), "+f"(d[115]), "+f"(d[116]), "+f"(d[117]), "+f"(d[118]), "+f"(d[119]),
          "+f"(d[120]), "+f"(d[121]), "+f"(d[122]), "+f"(d[123]), "+f"(d[124]), "+f"(d[125]), "+f"(d[126]), "+f"(d[127])
        : "l"(da), "l"(db));
}

struct Idx {
    uint32_t lane, warp, w4, q4, g8, prow, pan;
    __device__ __forceinline__ Idx() {
        uint32_t t; asm volatile("mov.u32 %0, %%tid.x;" : "=r"(t));
        lane = t & 31; warp = t >> 5; w4 = warp & 3; q4 = lane & 3; g8 = lane >> 2;
        prow = w4 * 16 + ((lane >> 3) & 1) * 8 + (lane & 7);
        pan = prow * 128 + (((lane >> 4) ^ (lane & 7)) << 4);
    }
};
#define IDX() const Idx ix; const uint32_t lane = ix.lane, warp = ix.warp, w4 = ix.w4, q4 = ix.q4, g8 = ix.g8, prow = ix.prow, pan_addr = ix.pan; \
    (void)lane; (void)warp; (void)w4; (void)q4; (void)g8; (void)prow; (void)pan_addr;

__device__ __forceinline__ int kof(int t, int sh, int j) {
    const int q = (t >> sh) - 1;
    return ((q < 0 ? j : q + (q >= j)) << 7) + ((t & ((1 << sh) - 1)) << (7 - sh));
}
constexpr int HC0 = 8 * 48, HC3 = HC0 + 3072;
__device__ __forceinline__ int hcol(int p, int j) { return HC0 + p * 1024 + j * 128; }
#define SCHED_FENCE(k) do { if ((FENCES >> (k)) & 1) asm volatile("{\n.reg .pred p;\nsetp.ne.u32 p, %0, %1;\n@p bra.uni S_SKIP;\ntrap;\nS_SKIP:\n}" :: "r"(sb), "n"(0xffffff00u + (k))); } while (0)

struct Ring {
    uint32_t slot, par;
    __device__ __forceinline__ void next() { if (++slot == NSLOT) { slot = 0; par ^= 1; } }
    __device__ __forceinline__ void skip(uint32_t n) { slot += n; if (slot >= NSLOT) { slot -= NSLOT; par ^= 1; } }
};
__device__ __forceinline__ uint32_t BAR_FULL(uint32_t sb, uint32_t s) { return sb + OFF_BAR + 8 * s; }
constexpr uint32_t AF_REL = 48;
__device__ __forceinline__ uint32_t BAR_EMPTY(uint32_t sb, uint32_t s) { return sb + OFF_BAR + 96 + 8 * s; }
__device__ __forceinline__ uint32_t BAR_SFULL(uint32_t sb, uint32_t i) { return sb + OFF_BAR + 152 + 8 * i; }
__device__ __forceinline__ uint32_t BAR_SREADY(uint32_t sb, uint32_t i) { return sb + OFF_BAR + 184 + 8 * i; }
__device__ __forceinline__ uint32_t BAR_ONE(uint32_t sb, uint32_t i) { return sb + OFF_BAR + 216 + 8 * i; }
enum { EV_WIN, EV_WIN1, EV_WIN2, EV_WIN3, EV_P0, EV_GA, EV_GB, EV_LN2, EV_LAG0, EV_LAG1, EV_LAG2, EV_LAG3, EV_LAG4, EV_LAG5, EV_OWN, EV_OWN1, EV_P3, EV_P31, EV_KV, EV_GO, EV_PAR, EV_AGO, EV_AGO1, EV_AGO2, EV_H0, EV_H1, EV_H2, EV_H3, EV_COUNT };
constexpr int NB_TAIL = 4;

struct Rel {
    uint32_t base; bool sig;
    __device__ __forceinline__ Rel(uint32_t sb, uint32_t tw) {
        uint32_t a; asm("mapa.shared::cluster.u32 %0, %1, %2;" : "=r"(a) : "r"(BAR_EMPTY(sb, 0)), "r"((tw >> 5) & 1));
        base = __shfl_sync(0xffffffffu, a, 0); sig = (tw & ~32u) == 0;
    }
    __device__ __forceinline__ void operator()(uint32_t slot) const {
        if (sig) asm volatile("mbarrier.arrive.shared::cluster.b64 _, [%0];" :: "r"(base + 8 * slot) : "memory");
    }
};
struct LnRow { float rs0, nm0, rs1, nm1; };
struct Pipe {
    Rel rel; uint32_t p1, p2;
    __device__ __forceinline__ Pipe(uint32_t sb, uint32_t tw, uint32_t first) : rel(sb, tw), p1(first), p2(NSLOT) {}
    template <bool TWO> __device__ __forceinline__ void acquire(uint32_t sb, uint32_t af, const Ring& r) {
        const uint32_t b0 = BAR_FULL(sb, r.slot), b1 = b0 + af;
        const bool ready = TWO ? mbar_test2(b0, b1, r.par) : mbar_test(b0, r.par);
        wg_wait<1>();
        rel(p2);
        if (!ready) { if (TWO) mbar_wait2(b0, b1, r.par); else mbar_wait(b0, r.par); }
    }
    __device__ __forceinline__ void issued(uint32_t slot) { p2 = p1; p1 = slot; }
    __device__ __forceinline__ void drain1() { wg_wait<1>(); rel(p2); p2 = NSLOT; }
    __device__ __forceinline__ void drain0() { wg_wait<0>(); rel(p1); p1 = NSLOT; }
    template <bool TWO, int LG, class Step> __device__ __forceinline__ void hold(uint32_t sb, uint32_t af, Ring& r, uint32_t lag_bar, Step step) {
        drain1(); drain0();
        Ring q = r;
#pragma unroll 1
        for (int i = 0; i < LG; ++i) { if (TWO) mbar_wait2(BAR_FULL(sb, q.slot), BAR_FULL(sb, q.slot) + af, q.par); else mbar_wait(BAR_FULL(sb, q.slot), q.par); q.next(); }
        mbar_wait(lag_bar, 0);
#pragma unroll 1
        do {
            step(r.slot);
            wg_wait<2>(); rel(p2); p2 = p1; p1 = r.slot;
            if (++r.slot == NSLOT) r.slot = 0;
        } while (r.slot != q.slot);
        r.par = q.par;
    }
};
template <bool TWO, bool FIRST, int NA, int NB>
__device__ __forceinline__ void step32(float (&aa)[NA], float (&ab)[NB], uint32_t sb, uint32_t wg, uint32_t slot, int own) {
    const uint32_t st = d16(sb) + slot * (SLOT >> 4);
    const uint32_t alo = own >= 0 ? d16(sb) + OFF_STG / 16 + wg * 1024 + (own >> 1) * 512 + (own & 1) * 4 : st + wg * 256;
    const uint32_t ahi = own >= 0 ? (1024 >> 4) | (1u << 30) : (512 >> 4) | (2u << 30);
    wg_fence();
#pragma unroll
    for (int k = 0; k < 2; ++k) {
        const uint64_t da = ((uint64_t)ahi << 32) | (alo + k * 2 + 0x10000);
        if constexpr (NA == 88) {
            const uint64_t d0 = mk_desc(st, 8192 + k * 2048, 8192, 1024, 1), d1 = mk_desc(st, 12288 + k * 2048, 8192, 1024, 1);
            if (FIRST && k == 0) { wgmma_n176_z(aa, da, d0); wgmma_n176_z(ab, da, d1); }
            else { wgmma_n176(aa, da, d0); wgmma_n176(ab, da, d1); }
        } else {
            const uint64_t d0 = mk_desc(st, 8192 + k * 2048, 4096, 1024, 1), d1 = mk_desc(st, 24576 + k * 2048, 4096, 1024, 1);
            if (FIRST && k == 0) { wgmma_n256_z(aa, da, d0); if constexpr (TWO) wgmma_n128_z(ab, da, d1); }
            else { wgmma_n256(aa, da, d0); if constexpr (TWO) wgmma_n128(ab, da, d1); }
        }
    }
    wg_commit();
}
template <bool TWO, int LG, int NA, int NB, class Tail>
__device__ __forceinline__ void mainloop32(float (&aa)[NA], float (&ab)[NB], uint32_t sb, uint32_t wg, uint32_t tw, Ring& r, uint32_t lag_ev, int g0, Tail tail) {
    mbar_wait(BAR_FULL(sb, r.slot), r.par);
    step32<TWO, true>(aa, ab, sb, wg, r.slot, TWO ? 0 : -1);
    TS(g0, 0);
    Pipe pp(sb, tw, r.slot);
    r.next();
    const int end = wg ? 32 : 32 - LG;
#pragma unroll 1
    for (int it = 1; it < end; ++it) {
        pp.acquire<TWO>(sb, wg ? 0 : AF_REL, r);
        step32<TWO, false>(aa, ab, sb, wg, r.slot, TWO && it < 4 ? it : -1);
        pp.issued(r.slot);
        TS(g0 + it, 0);
        r.next();
    }
    if (wg == 0) pp.hold<TWO, LG>(sb, AF_REL, r, BAR_ONE(sb, lag_ev), [&](uint32_t slot) { step32<TWO, false>(aa, ab, sb, 0, slot, -1); });
    pp.drain1();
    if (wg == 1 && tw == 0) mbar_arrive(BAR_ONE(sb, lag_ev));
    tail();
    pp.drain0();
    TS(g0 + 31, 1);
}
template <bool FIRST>
__device__ __forceinline__ void step64(float (&acc)[64], uint32_t sb, uint32_t wg, uint32_t slot, int own) {
    const uint32_t sbb = d16(sb) + slot * (SLOT >> 4), sa = own >= 0 ? d16(sb) + OFF_STG / 16 + wg * 1024 + own * 512 : sbb + wg * 512;
    wg_fence();
#pragma unroll
    for (int k = 0; k < 4; ++k) {
        const uint64_t da = mk_desc(sa, k * 32, 16, 1024, 1), db = mk_desc(sbb, 16384 + k * 2048, 8192, 1024, 1);
        if (FIRST && k == 0) wgmma_n128_z(acc, da, db); else wgmma_n128(acc, da, db);
    }
    wg_commit();
}
template <class Mid>
__device__ __forceinline__ void mainloop64(float (&acc)[64], bool wo, uint32_t sb, uint32_t wg, uint32_t tw, Ring& r, Mid mid) {
    const int g0 = wo ? 32 : 144, nst = wo ? 16 : 56; (void)g0;
    const uint32_t lag_bar = BAR_ONE(sb, wo ? EV_LAG4 : EV_LAG5), af = wo && !wg ? AF_REL : 0;
    mbar_wait(BAR_FULL(sb, r.slot), r.par);
    step64<true>(acc, sb, wg, r.slot, wo ? 0 : -1);
    TS(g0, 0);
    Pipe pp(sb, tw, r.slot);
    r.next();
    int it = 1;
    auto run = [&](int end, int own) {
#pragma unroll 1
        do {
            pp.acquire<true>(sb, af, r);
            step64<false>(acc, sb, wg, r.slot, own);
            pp.issued(r.slot);
            TS(g0 + it, 0);
            r.next();
            if (own > 0) {
                own = -1;
                pp.drain1(); pp.drain0();
                TS(g0 + 1, 1);
                if (tw == 0) mbar_arrive(BAR_ONE(sb, EV_OWN + wg));
            }
        } while (++it < end);
    };
    run(wg ? nst - MIDW : nst - LAGW, wo ? 1 : -1);
    mid();
    if (wg) run(nst, -1);
    else pp.hold<true, LAGW>(sb, af, r, lag_bar, [&](uint32_t slot) { step64<false>(acc, sb, 0, slot, -1); });
    pp.drain1();
    if (wg == 1 && tw == 0) mbar_arrive(lag_bar);
    pp.drain0();
    TS(g0 + nst - 1, 1);
}

struct RowAcc {
    float sm[4] = {0.f, 0.f, 0.f, 0.f}, sq[4] = {0.f, 0.f, 0.f, 0.f};
    __device__ __forceinline__ void add(int e, float x) { sm[e & 3] += x; sq[e & 3] = fmaf(x, x, sq[e & 3]); }
    __device__ __forceinline__ void publish(uint4* dst, uint32_t q4, uint32_t ep) const {
        const float s0 = sm[0] + sm[1], s1 = sm[2] + sm[3], q0 = sq[0] + sq[1], q1 = sq[2] + sq[3];
        const bool od = q4 & 1;
        float sv = (od ? s1 : s0) + __shfl_xor_sync(0xffffffffu, od ? s0 : s1, 1), qv = (od ? q1 : q0) + __shfl_xor_sync(0xffffffffu, od ? q0 : q1, 1);
        sv += __shfl_xor_sync(0xffffffffu, sv, 2); qv += __shfl_xor_sync(0xffffffffu, qv, 2);
        if (q4 < 2) st_pkt16(dst + q4 * 8, 0, __float_as_uint(sv), __float_as_uint(qv), ep);
    }
};
__device__ __forceinline__ LnRow merge_stats(const uint4* src, uint32_t q4, uint32_t ep, uint32_t sb) {
    uint4 t[4];
    uint32_t n = 0;
    while (true) {
#pragma unroll
        for (int i = 0; i < 4; ++i) t[i] = ld_pkt16(src + (q4 * 2 + (i >> 1)) * 512 + (i & 1) * 8);
        const bool ok_ = __all_sync(0xffffffffu, t[0].w == ep && t[1].w == ep && t[2].w == ep && t[3].w == ep);
        if (n < 4) CS(14 + n);
        if (ok_) break;
        SPIN_GUARD(n);
    }
    float v[4];
#pragma unroll
    for (int h = 0; h < 2; ++h) { v[h] = __uint_as_float(t[h].y) + __uint_as_float(t[2 + h].y); v[2 + h] = __uint_as_float(t[h].z) + __uint_as_float(t[2 + h].z); }
#pragma unroll
    for (int o = 1; o < 4; o <<= 1)
#pragma unroll
        for (int i = 0; i < 4; ++i) v[i] += __shfl_xor_sync(0xffffffffu, v[i], o);
    const float m0 = v[0] * (1.f / D_), m1 = v[1] * (1.f / D_);
    const float r0 = rsqrtf(fmaxf(fmaf(-m0, m0, v[2] * (1.f / D_)), 0.f) + 1e-5f), r1 = rsqrtf(fmaxf(fmaf(-m1, m1, v[3] * (1.f / D_)), 0.f) + 1e-5f);
    return LnRow{r0, -m0 * r0, r1, -m1 * r1};
}
struct Stg {
    uint32_t b, par;
    __device__ __forceinline__ uint32_t acquire2(uint32_t sb, uint32_t wg) {
        mbar_wait(BAR_SREADY(sb, wg * 2), par & 1);
        mbar_wait(BAR_SREADY(sb, wg * 2 + 1), (par >> 1) & 1);
        par ^= 3;
        return sb + OFF_STG + wg * 16384;
    }
    __device__ __forceinline__ void publish(uint32_t sb, uint32_t wg, uint32_t lane) {
        fence_async_smem();
        __syncwarp();
        if (lane == 0) mbar_arrive(BAR_SFULL(sb, wg * 2 + b));
        b ^= 1;
    }
};

struct LnPar {
    uint4 p[8];
    __device__ __forceinline__ void load(uint32_t sb, uint32_t q4) {
#pragma unroll
        for (int i = 0; i < 8; ++i) p[i] = lds128(sb + OFF_PAR + i * 64 + q4 * 16);
    }
};
__device__ __forceinline__ void ln_norm(uint32_t (&xn)[32], const float (&x)[64], const LnRow& n) {
#pragma unroll
    for (int e = 0; e < 32; ++e) {
        const float rs = (e & 1) ? n.rs1 : n.rs0, nm = (e & 1) ? n.nm1 : n.nm0;
        xn[e] = pack2(fmaf(x[2 * e], rs, nm), fmaf(x[2 * e + 1], rs, nm));
    }
}
__device__ __forceinline__ void ln_emit(const uint32_t (&xr)[32], const LnPar& lp, uint32_t sb, uint32_t wg, const Idx& ix) {
#pragma unroll
    for (int i = 0; i < 8; ++i)
        stsm4(sb + OFF_STG + wg * 16384 + (i >> 2) * 8192 + (ix.pan ^ ((i & 3) << 5)), hfma2_bf16(xr[4 * i], lp.p[i].z, lp.p[i].x), hfma2_bf16(xr[4 * i + 1], lp.p[i].z, lp.p[i].x),
              hfma2_bf16(xr[4 * i + 2], lp.p[i].w, lp.p[i].y), hfma2_bf16(xr[4 * i + 3], lp.p[i].w, lp.p[i].y));
    fence_async_smem();
    __syncwarp();
    if (ix.lane < 2) mbar_arrive(BAR_SFULL(sb, wg * 2 + ix.lane));
    bar_sync(1 + wg, 128);
}
__device__ __forceinline__ void load_slab(uint32_t (&xr)[32], uint32_t buf) {
    IDX();
#pragma unroll
    for (int i = 0; i < 8; ++i) ldsm4(buf + (i >> 2) * 8192 + (pan_addr ^ ((i & 3) << 5)), xr[4 * i], xr[4 * i + 1], xr[4 * i + 2], xr[4 * i + 3]);
}
__device__ __forceinline__ void unpack_slab(float (&x)[64], const uint32_t (&xr)[32]) {
#pragma unroll
    for (int i = 0; i < 32; ++i) unpack2(xr[i], x[2 * i], x[2 * i + 1]);
}
__device__ __forceinline__ void store_slab(const float (&x)[64], uint32_t buf, uint32_t pitch, uint32_t pan, int i0, int i1) {
#pragma unroll
    for (int i = i0; i < i1; ++i)
        stsm4(buf + (i >> 2) * pitch + (pan ^ ((i & 3) << 5)), pack2(x[8 * i], x[8 * i + 1]), pack2(x[8 * i + 2], x[8 * i + 3]), pack2(x[8 * i + 4], x[8 * i + 5]), pack2(x[8 * i + 6], x[8 * i + 7]));
}
__device__ __forceinline__ void fetch_halo(uint4* src, bool first, uint32_t sb, uint32_t W, uint32_t lane) {
    mbar_wait(BAR_ONE(sb, EV_KV), 0);
    mbar_wait2(BAR_SREADY(sb, 0), BAR_SREADY(sb, 1), 1);
    uint4 hv[8];
    uint32_t n = 0;
    while (true) {
        bool ok = true;
#pragma unroll
        for (int i = 0; i < 8; ++i) { hv[i] = first ? make_uint4(0, 0, 0, 0) : ld_pkt16(src + i * 32); ok = ok && hv[i].x != 0; }
        if (first || __all_sync(0xffffffffu, ok)) break;
        SPIN_GUARD(n);
    }
#pragma unroll
    for (int i = 0; i < 8; ++i) stsm4(sb + OFF_STG + W * 2048 + (i >> 2) * 8192 + (i & 3) * 512 + lane * 16, hv[i].x, hv[i].y, hv[i].z, hv[i].w);
    bar_arrive(NB_TAIL + W, 64);
    if (!first) {
#pragma unroll
        for (int i = 0; i < 8; ++i) src[i * 32] = make_uint4(0, 0, 0, 0);
    }
}

template <int OG, int OU, int LEN>
__device__ __forceinline__ void glu_panel(const float (&g)[LEN], const float (&u)[LEN], uint32_t buf, uint32_t bar) {
    IDX();
    constexpr int NR = LEN - OU < 32 ? (LEN - OU) / 2 : 16;
    uint32_t r[NR];
#pragma unroll
    for (int i = 0; i < NR; ++i) r[i] = pack2(glu_half(g[OG + 2 * i], u[OU + 2 * i]), glu_half(g[OG + 2 * i + 1], u[OU + 2 * i + 1]));
#pragma unroll
    for (int jn = 0; jn < NR / 2; jn += 2) stsm4(buf + (pan_addr ^ (jn << 4)), r[jn * 2], r[jn * 2 + 1], r[jn * 2 + 2], r[jn * 2 + 3]);
    fence_async_smem();
    __syncwarp();
    if (lane == 0) mbar_arrive(bar);
}

template <int NP>
__device__ __forceinline__ void passes128(uint32_t sb, uint32_t wg, uint32_t tw, Ring& r, Stg& stg) {
#pragma unroll 1
    for (int p = 0; p < NP; ++p) {
        float b256[128], none[1];
        mainloop32<false, LAGS>(b256, none, sb, wg, tw, r, EV_LAG2 + p, 80 + 32 * (p & 1), [&] { stg.acquire2(sb, wg); });
        if (threadIdx.x == 0) { TL(29 + 2 * p); TC(114 + 2 * p); }
        if (threadIdx.x == 128) TL(53 + 2 * (p & 1));
        glu_panel<0, 32>(b256, b256, sb + OFF_STG + wg * 16384, BAR_SFULL(sb, wg * 2));
        glu_panel<64, 96>(b256, b256, sb + OFF_STG + wg * 16384 + 8192, BAR_SFULL(sb, wg * 2 + 1));
        if (threadIdx.x == 0) { TL(30 + 2 * p); TC(115 + 2 * p); }
        if (threadIdx.x == 128) TL(54 + 2 * (p & 1));
    }
}

__global__ void __launch_bounds__(384, 1)
fused_block_kernel(const __grid_constant__ Ptrs pt, const __grid_constant__ Maps mp) {
    uint32_t* const g_flags = pt.mail->flags;
    uint2* const g_mod = pt.mail->mod;
    uint4* const g_st1 = pt.mail->st1;
    uint32_t* const g_par2 = pt.mail->par2;
    uint4* const g_halo = pt.mail->halo;
    const __nv_bfloat16* __restrict__ cvec = pt.c;
    if (threadIdx.x == 224) { prefetch_map(&mp.wm8); prefetch_map(&mp.x); }
    extern __shared__ __align__(1024) uint8_t smem[];
    const uint32_t sb = smem_u32(smem);
    const uint32_t tid = threadIdx.x, tw = tid & 127, lane = tid & 31;
    const uint32_t warp = __shfl_sync(0xffffffffu, tid >> 5, 0), wg = warp >> 2;
    uint32_t rank; asm("mov.u32 %0, %%cluster_ctarank;" : "=r"(rank));
    rank = __shfl_sync(0xffffffffu, rank, 0);
    uint32_t ep;
    uint32_t smid; asm volatile("mov.u32 %0, %%smid;" : "=r"(smid));
    const int c = __shfl_sync(0xffffffffu, smid >> 1, 0);
    const int c7 = ((c - 32) * 37) >> 8;
    const int grp = c < 32 ? c & 7 : c < 60 ? c - 31 - 7 * c7 : c < 62 ? -1 : 0;
    const int j = c < 32 ? c >> 3 : c < 60 ? 4 + c7 : c < 62 ? (c - 60) * 2 + rank : c - 58;
    const bool aux = grp < 0;
    const int m = grp * 2 + rank;
    uint4* const g_st2 = g_halo + (m > 0 ? (m - 1) * 8 * 512 : 128);

    bool cluster_arrive_early = false;
    if (wg < 2) {
      if (!KDEBUG) cluster_arrive();
      ep = flag_get(g_flags + FL_DONE);
      uint16_t cw[8];
      {
          const __nv_bfloat16* cp = cvec + ((tw >> 5) * 32 + (tw & 3) * 2) * 8 + (lane >> 2);
#pragma unroll
          for (int i = 0; i < 8; ++i) asm volatile("ld.global.nc.u16 %0, [%1];" : "=h"(cw[i]) : "l"(cp + (i >> 1) * 64 + (i & 1) * 8));
      }
      asm volatile("setmaxnreg.inc.sync.aligned.u32 224;");
      if (tid == 0) TL(58);
      if (KDEBUG) cluster_arrive();
      Ring r{0, 0};
      Stg stg{0, 0};
      if (aux) {
        if (wg == 0) {
            const uint4 cv = *(const uint4*)(cvec + tw * 8);
            sts128(sb + OFF_STG + (tw >> 3) * 1024 + (tw & 7) * 16, pack2(silu_(bf_lo(cv.x)), silu_(bf_hi(cv.x))), pack2(silu_(bf_lo(cv.y)), silu_(bf_hi(cv.y))),
                   pack2(silu_(bf_lo(cv.z)), silu_(bf_hi(cv.z))), pack2(silu_(bf_lo(cv.w)), silu_(bf_hi(cv.w))));
            fence_async_smem();
        }
        cluster_wait();
        ep = __shfl_sync(0xffffffffu, ep, 0) / NCTA + 1;
        if (wg == 0) {
            if (tw == 0) {
                uint32_t n = 0;
                while (ld_pkt16(pt.mail->mod1 + 256).z != ep) { SPIN_GUARD(n); __nanosleep(200); }
                if (GODLY) __nanosleep(GODLY);
                mbar_arrive(BAR_ONE(sb, EV_GO));
            }
            bar_sync(1, 128);
#pragma unroll 1
            for (int p = 0; p < 4; ++p) {
                float acc[128];
#pragma unroll
                for (int i = 0; i < 128; ++i) acc[i] = 0.f;
                uint32_t prev = 0;
#pragma unroll 1
                for (int kc = 0; kc < 16; ++kc) {
                    mbar_wait(BAR_FULL(sb, r.slot), r.par);
                    wg_fence();
#pragma unroll
                    for (int k = 0; k < 4; ++k)
                        wgmma_n256(acc, mk_desc(d16(sb) + kc * 64, OFF_STG + k * 32, 16, 0, 1), mk_desc(d16(sb) + r.slot * (SLOT >> 4), k * 2048, 8192, 1024, 1));
                    wg_commit();
                    wg_wait<1>();
                    if (kc > 0 && tw < 4) mbar_arrive(BAR_EMPTY(sb, prev));
                    prev = r.slot;
                    r.next();
                }
                wg_wait<0>();
                if (tw < 4) mbar_arrive(BAR_EMPTY(sb, prev));
                if (tw < 4) {
#pragma unroll
                    for (int jn = 0; jn < 32; ++jn) sts32(sb + OFF_TAB + (jn * 4 + tw) * 4, pack2(acc[jn * 4], acc[jn * 4 + 1]));
                }
                bar_sync(1, 128);
                const int vec = 2 + p, blk = p * 4 + j;
                const uint32_t val = lds32(sb + OFF_TAB + tw * 4);
                if (vec == 2 || vec == 5) st_pkt(g_mod + (8 + blk) * 128 + tw, val, ep);
                else {
                    const float one = vec == 4 ? 1.f : 0.f;
                    g_par2[((blk & 3) * 16 + (tw >> 3)) * 16 + (tw & 3) * 4 + (vec - 3) * 2 + ((tw >> 2) & 1)] =
                        pack2(0.5f * bf_round(one + bf_lo(val)), 0.5f * bf_round(one + bf_hi(val)));
                }
                bar_sync(1, 128);
                if (tw == 0) {
                    if (vec == 3 || vec == 4) asm volatile("red.release.gpu.global.add.u32 [%0], 1;" :: "l"(&g_flags[FL_LN2]) : "memory");
                    TL(1 + p);
                }
            }
            if (lane < 2) mbar_arrive_cta(BAR_ONE(sb, EV_P0), lane);
        }
        r = Ring{64 % NSLOT, (64 / NSLOT) & 1};
        mbar_wait(BAR_ONE(sb, EV_P0), 0);
        passes128<4>(sb, wg, tw, r, stg);
      } else {
        float xs[64];
        uint32_t xp[32];
        {
            IDX();
            if (q4 < 2) st_pkt16(g_st1 + (m * 8 + j) * 512 + wg * 64 + w4 * 16 + g8 + q4 * 8, 0, 0, 0, 0);
            if (warp == 0) st_pkt16(pt.mail->mod1 + g8 * 512 + (m * 8 + j) * 4 + q4, 0, 0, 0, 0);
            sts128(sb + tid * 16, pack2(silu_(bf_lo(cw[0])), silu_(bf_lo(cw[1]))), pack2(silu_(bf_lo(cw[2])), silu_(bf_lo(cw[3]))),
                   pack2(silu_(bf_lo(cw[4])), silu_(bf_lo(cw[5]))), pack2(silu_(bf_lo(cw[6])), silu_(bf_lo(cw[7]))));
            cluster_wait();
            ep = __shfl_sync(0xffffffffu, ep, 0) / NCTA + 1;
            load_slab(xp, stg.acquire2(sb, wg));
            unpack_slab(xs, xp);
            if (tid == 0) TL(24);
            if (tid == 128) TL(27);
        }
#pragma unroll 1
        for (int blk = 0; ; ++blk) {
        {
            IDX();
            uint4* const st = (blk ? g_st2 : g_st1 + m * 8 * 512) + wg * 64 + w4 * 16 + g8;
            RowAcc ra;
#pragma unroll
            for (int e = 0; e < 64; ++e) ra.add(e, xs[e]);
            ra.publish(st + j * 512, q4, ep);
            uint32_t t_pub = 0; if (PDLY) asm volatile("mov.u32 %0, %%clock;" : "=r"(t_pub));
            if (tid == 0) TL(blk ? 9 : 26);
            if (tid == 128 && blk) TL(34);
            if (blk) CS(11);
            LnPar lp;
            if (blk == 0) {
            uint4* const mod_out = pt.mail->mod1 + g8 * 512 + (m * 8 + j) * 4 + q4;
            if (wg == 0) {
                uint4 af[8];
#pragma unroll
                for (int i = 0; i < 8; ++i) af[i] = lds128(sb + w4 * 512 + i * 64 + q4 * 16);
                float c[4][4] = {};
#pragma unroll
                for (int i = 0; i < 8; ++i) {
                    if (!(i & 1)) mbar_wait(BAR_ONE(sb, EV_WIN + (i >> 1)), 0);
                    if (i == 6 && tid == 0) TL(25);
#pragma unroll
                    for (int h = 0; h < 2; ++h) {
                        uint32_t b0, b1, b2, b3;
                        ldsm4t(sb + 5 * SLOT + i * 4096 + w4 * 1024 + h * 512 + (lane & 15) * 32 + (lane >> 4) * 16, b0, b1, b2, b3);
                        mma16816(c[2 * h], h ? af[i].z : af[i].x, 0u, h ? af[i].w : af[i].y, 0u, b0, b1);
                        mma16816(c[2 * h + 1], h ? af[i].z : af[i].x, 0u, h ? af[i].w : af[i].y, 0u, b2, b3);
                    }
                }
                if (lane < 4) sts128(sb + OFF_TAB + w4 * 64 + lane * 16, __float_as_uint(c[0][0] + c[2][0]), __float_as_uint(c[0][1] + c[2][1]),
                                     __float_as_uint(c[1][0] + c[3][0]), __float_as_uint(c[1][1] + c[3][1]));
                if (lane < 2) mbar_arrive_cta(BAR_ONE(sb, EV_P0), lane);
                bar_sync(1, 128);
                if (w4 == 0) {
                    float a[4] = {0.f, 0.f, 0.f, 0.f};
#pragma unroll
                    for (int i = 0; i < 4; ++i) {
                        const uint4 t = lds128(sb + OFF_TAB + i * 64 + q4 * 16);
                        a[0] += __uint_as_float(t.x); a[1] += __uint_as_float(t.y); a[2] += __uint_as_float(t.z); a[3] += __uint_as_float(t.w);
                    }
                    const float add = m >= 8 ? 1.f : 0.f;
                    st_pkt16(mod_out, pack2(bf_round(a[0]) + add, bf_round(a[1]) + add), pack2(bf_round(a[2]) + add, bf_round(a[3]) + add), ep, 0);
                    if (tid == 0) TL(3);
                }
            } else if (LWAIT >= 0) mbar_wait(BAR_ONE(sb, EV_WIN + LWAIT), 0);
            } else {
                mbar_wait(BAR_ONE(sb, EV_LN2), 0);
            }
            lp.load(sb, q4);
#pragma unroll
            for (int e = 0; e < 32; ++e) xp[e] = pack2(xs[2 * e], xs[2 * e + 1]);
            if (PDLY && blk) { uint32_t t1; do { asm volatile("mov.u32 %0, %%clock;" : "=r"(t1)); } while (t1 - t_pub < PDLY); }
            if (blk) CS(13);
            const LnRow n = merge_stats(st, q4, ep, sb);
            if (tid == 0) TL(blk ? 49 : 48);
            if (tid == 128) TL(blk ? 45 : 28);
            if (blk) CS(18);
            uint32_t xn[32];
            ln_norm(xn, xs, n);
            if (blk == 0) { mbar_wait(BAR_ONE(sb, EV_PAR), 0); lp.load(sb, q4); }
            ln_emit(xn, lp, sb, wg, ix);
            if (tid == 0) { TL(blk ? 36 : 8); TC(blk ? 109 : 103); }
            if (tid == 128) TL(blk ? 43 : 22);
            if (blk) CS(21);
        }
        if (blk == 0) {
        {
            float kv[128], qa[64];
            mainloop32<true, LAGQ>(kv, qa, sb, wg, tw, r, EV_LAG0, 0, [&] { stg.acquire2(sb, wg); mbar_wait2(BAR_SREADY(sb, 2), BAR_SREADY(sb, 3), 1); });
            if (tid == 0) { TL(4); TC(104); }
            if (tid == 128) TL(50);
            CS(1);
            IDX();
            uint32_t k1[16], k2[16], v1[16], v2[16], qf[32];
#pragma unroll
            for (int i = 0; i < 8; ++i) qf[i] = pack2(qa[2 * i], qa[2 * i + 1]);
#pragma unroll
            for (int t = 0; t < 16; ++t) k2[t] = pack2(kv[4 * t + 2], kv[4 * t + 3]);
#pragma unroll
            for (int t = 0; t < 16; ++t) v2[t] = pack2(kv[64 + 4 * t + 2], kv[64 + 4 * t + 3]);
            const uint32_t nxt = warp + ((warp & 1) ? 3 : 1);
            if (nxt < 8) {
                const uint32_t dst = sb + OFF_STG + (nxt >> 2) * 16384 + (nxt & 3) * 2048 + lane * 16;
#pragma unroll
                for (int h = 0; h < 4; ++h) stsm4(dst + h * 512, k2[4 * h], k2[4 * h + 1], k2[4 * h + 2], k2[4 * h + 3]);
#pragma unroll
                for (int h = 0; h < 4; ++h) stsm4(dst + 8192 + h * 512, v2[4 * h], v2[4 * h + 1], v2[4 * h + 2], v2[4 * h + 3]);
                bar_arrive(NB_TAIL + nxt, 64);
            } else if (m < 15) {
                uint4* dst = g_halo + (m * 8 + j) * 512 + (w4 >> 1) * 256 + lane;
#pragma unroll
                for (int h = 0; h < 4; ++h) { if (!k2[4 * h]) k2[4 * h] = 0x8000u; if (!v2[4 * h]) v2[4 * h] = 0x8000u; }
#pragma unroll
                for (int h = 0; h < 4; ++h) st_pkt16(dst + h * 32, k2[4 * h], k2[4 * h + 1], k2[4 * h + 2], k2[4 * h + 3]);
#pragma unroll
                for (int h = 0; h < 4; ++h) st_pkt16(dst + 128 + h * 32, v2[4 * h], v2[4 * h + 1], v2[4 * h + 2], v2[4 * h + 3]);
            }
#pragma unroll
            for (int t = 0; t < 16; ++t) { k1[t] = pack2(kv[4 * t], kv[4 * t + 1]); v1[t] = pack2(kv[64 + 4 * t], kv[64 + 4 * t + 1]); }
#pragma unroll
            for (int i = 8; i < 32; ++i) qf[i] = pack2(qa[2 * i], qa[2 * i + 1]);
#pragma unroll
            for (int t = 0; t < 16; ++t) { v1[t] = movm(v1[t]); v2[t] = movm(v2[t]); }
            if (tid == 0) TL(33);
            CS(2);
            SCHED_FENCE(0);
            float s[4][3][4];
            auto qk = [&](float (&c)[4], int h, const uint32_t* k) {
                c[0] = c[1] = c[2] = c[3] = 0.f;
                mma16816(c, qf[h * 8], qf[h * 8 + 1], qf[h * 8 + 2], qf[h * 8 + 3], k[0], k[1]);
                mma16816(c, qf[h * 8 + 4], qf[h * 8 + 5], qf[h * 8 + 6], qf[h * 8 + 7], k[2], k[3]);
            };
#pragma unroll
            for (int h = 0; h < 4; ++h) { qk(s[h][1], h, k1 + 4 * h); qk(s[h][2], h, k2 + 4 * h); }
            CS(3);
            bar_sync(NB_TAIL + warp, 64);
            CS(4);
            if (tid == 0) TL(5);
            uint32_t k0[16], v0[16];
            const uint32_t mine = sb + OFF_STG + wg * 16384 + w4 * 2048;
#pragma unroll
            for (int h = 0; h < 4; ++h) ldsm4(mine + lane * 16 + h * 512, k0[4 * h], k0[4 * h + 1], k0[4 * h + 2], k0[4 * h + 3]);
#pragma unroll
            for (int h = 0; h < 4; ++h) ldsm4t(mine + lane * 16 + 8192 + h * 512, v0[4 * h], v0[4 * h + 1], v0[4 * h + 2], v0[4 * h + 3]);
#pragma unroll
            for (int h = 0; h < 4; ++h) qk(s[h][0], h, k0 + 4 * h);
            const bool lo0 = q4 * 2 > g8, lo1 = q4 * 2 + 1 > g8;
            const bool nopast = m == 0 && (warp & 5) == 0;
            const uint32_t lomask = (lo0 ? 0xFFFFu : 0u) | (lo1 ? 0xFFFF0000u : 0u);
            const float sl2 = 0.17677669529663687f * 1.4426950408889634f;
            float e0[8], e1[8], mx[8], sum[8], tt[8];
#pragma unroll
            for (int u = 0; u < 8; ++u) {
                const int h = u >> 1, hf = u & 1;
                e0[u] = lo0 ? ((hf == 0 && nopast) ? -INFINITY : s[h][hf][hf * 2]) : s[h][hf + 1][hf * 2];
                e1[u] = lo1 ? ((hf == 0 && nopast) ? -INFINITY : s[h][hf][hf * 2 + 1]) : s[h][hf + 1][hf * 2 + 1];
                mx[u] = fmaxf(e0[u], e1[u]);
                tt[u] = __shfl_xor_sync(0xffffffffu, mx[u], 1);
            }
            SCHED_FENCE(1);
#pragma unroll
            for (int u = 0; u < 8; ++u) { mx[u] = fmaxf(mx[u], tt[u]); tt[u] = __shfl_xor_sync(0xffffffffu, mx[u], 2); }
            SCHED_FENCE(2);
#pragma unroll
            for (int u = 0; u < 8; ++u) {
                const float c = -fmaxf(mx[u], tt[u]) * sl2;
                e0[u] = ex2(fmaf(e0[u], sl2, c)); e1[u] = ex2(fmaf(e1[u], sl2, c));
            }
            SCHED_FENCE(3);
#pragma unroll
            for (int u = 0; u < 8; ++u) { sum[u] = e0[u] + e1[u]; tt[u] = __shfl_xor_sync(0xffffffffu, sum[u], 1); }
            SCHED_FENCE(4);
#pragma unroll
            for (int u = 0; u < 8; ++u) { sum[u] += tt[u]; tt[u] = __shfl_xor_sync(0xffffffffu, sum[u], 2); }
            SCHED_FENCE(5);
#pragma unroll
            for (int u = 0; u < 8; ++u) sum[u] = rcp(sum[u] + tt[u]);
            SCHED_FENCE(6);
            CS(5);
            float o[8][2][4];
#pragma unroll
            for (int u = 0; u < 8; ++u) {
                const int h = u >> 1;
                const uint32_t p = pack2(e0[u] * sum[u], e1[u] * sum[u]);
                const uint32_t* va = ((u & 1) ? v1 : v0) + 4 * h;
                const uint32_t* vb = ((u & 1) ? v2 : v1) + 4 * h;
#pragma unroll
                for (int d = 0; d < 2; ++d) {
                    o[u][d][0] = o[u][d][1] = o[u][d][2] = o[u][d][3] = 0.f;
                    mma16816(o[u][d], va[2 * d], va[2 * d + 1], vb[2 * d], vb[2 * d + 1], p & lomask, p & ~lomask);
                }
            }
            SCHED_FENCE(7);
            const uint32_t orow = mine + (lane & 7) * 128 + (((lane >> 3) ^ (lane & 7)) << 4);
#pragma unroll
            for (int u = 0; u < 8; ++u)
                stsm4t((orow ^ (((u >> 1) & 1) << 6)) + (u >> 2) * 8192 + (u & 1) * 1024, pack2(o[u][0][0], o[u][0][1]), pack2(o[u][0][2], o[u][0][3]),
                       pack2(o[u][1][0], o[u][1][1]), pack2(o[u][1][2], o[u][1][3]));
            fence_async_smem();
            __syncwarp();
            if (lane < 2) mbar_arrive(BAR_SFULL(sb, wg * 2 + lane));
            CS(6);
            if (tid == 32) TL(41);
            bar_sync(1 + wg, 128);
            if (tid == 0) { TL(6); TC(106); }
            if (tid == 128) TL(44);
            CS(7);
#pragma unroll
            for (int e = 0; e < 32; ++e) xp[e] = qf[e];
        }
        } else {
        {
            float ag[88], au[88];
            mainloop32<true, LAG>(ag, au, sb, wg, tw, r, EV_LAG1, 48, [&] {
                stg.acquire2(sb, wg);
                Ring q = r; if (!wg) q.next();
                mbar_wait(BAR_EMPTY(sb, q.slot), q.par ^ 1);
            });
            if (tid == 0) { TL(10); TC(110); }
            if (tid == 128) TL(51);
            glu_panel<0, 0>(ag, au, sb + OFF_STG + wg * 16384, BAR_SFULL(sb, wg * 2));
            glu_panel<32, 32>(ag, au, sb + OFF_STG + wg * 16384 + 8192, BAR_SFULL(sb, wg * 2 + 1));
            glu_panel<64, 64>(ag, au, sb + (wg ? P3_SLOT1 : P3_SLOT0) * SLOT + 24576, BAR_ONE(sb, EV_P3 + wg));
            if (tid == 0) { TL(11); TC(111); }
            if (tid == 128) TL(52);
        }
        passes128<2>(sb, wg, tw, r, stg);
        if (tid == 0) { TL(12); TC(112); }
        }
        {
            float acc[64], gf[32];
            mainloop64(acc, blk == 0, sb, wg, tw, r, [&] {
                mbar_wait(BAR_ONE(sb, EV_GA + blk), 0);
                const uint32_t buf = stg.acquire2(sb, wg);
                if (blk == 0) load_slab(xp, buf);
                unpack_slab(xs, xp);
                uint32_t gt[16];
#pragma unroll
                for (int cg = 0; cg < 16; ++cg) gt[cg] = lds32(sb + OFF_TAB + blk * 256 + cg * 16 + (tw & 3) * 4);
#pragma unroll
                for (int i = 0; i < 16; ++i) unpack2(gt[i], gf[2 * i], gf[2 * i + 1]);
            });
            if (tid == 0) { TL(blk ? 13 : 7); TC(blk ? 113 : 107); }
            if (tid == 128) TL(blk ? 57 : 42);
            if (!blk) CS(10);
#pragma unroll
            for (int e = 0; e < 64; ++e) xs[e] = fmaf(gf[(e >> 2) * 2 + (e & 1)], acc[e], xs[e]);
        }
        if (blk) break;
        }
        cluster_arrive();
        {
            IDX();
#pragma unroll
            for (int p = 0; p < 2; ++p) {
                store_slab(xs, sb + OFF_STG + wg * 16384, 8192, pan_addr, 4 * p, 4 * p + 4);
                stg.publish(sb, wg, lane);
            }
            if (tid == 0) TL(14);
        }
      }
    } else {
        if (warp == 8 && !aux && elect_one()) {
#pragma unroll
            for (int i = 0; i < 4; ++i) mbar_init(BAR_SREADY(sb, i), 1);
#pragma unroll
            for (int i = 0; i < 4; ++i) mbar_init(BAR_ONE(sb, EV_WIN + i), 1);
#pragma unroll
            for (int i = 0; i < 4; ++i) {
                mbar_expect_tx(BAR_SREADY(sb, i), 8192);
                tma_load3(sb + OFF_STG + i * 8192, &mp.x, j * 128 + (i & 1) * 64, m * 64 + (i >> 1) * 32, BAR_SREADY(sb, i));
            }
#pragma unroll 1
            for (int i = 0; i < 4; ++i) {
                mbar_expect_tx(BAR_ONE(sb, EV_WIN + i), 8192);
                tma_load(sb + 5 * SLOT + i * 8192, &mp.wm8, 2 * i * 6144 + (m * 8 + j) * 16, 0, BAR_ONE(sb, EV_WIN + i));
                tma_load(sb + 5 * SLOT + i * 8192 + 4096, &mp.wm8, (2 * i + 1) * 6144 + (m * 8 + j) * 16, 0, BAR_ONE(sb, EV_WIN + i));
            }
        }
        __syncwarp();
        asm volatile("setmaxnreg.dec.sync.aligned.u32 56;");
        if (elect_one()) {
            if (warp == 8) {
                prefetch_map(&mp.wqkv); prefetch_map(&mp.wmod);
            } else if (warp < 11) {
                mbar_init(BAR_EMPTY(sb, NSLOT), 1);
#pragma unroll
                for (int i = 0; i < 2; ++i) { mbar_init(BAR_SFULL(sb, (warp - 9) * 2 + i), 4); if (aux) mbar_init(BAR_SREADY(sb, (warp - 9) * 2 + i), 1); }
#pragma unroll
                for (int i = 0; i < 3; ++i) {
                    mbar_init(BAR_EMPTY(sb, (warp - 9) * 3 + i), 4);
                    mbar_init(BAR_FULL(sb, (warp - 9) * 3 + i), 1); mbar_init(BAR_FULL(sb, (warp - 9) * 3 + i) + AF_REL, 1);
                }
            } else {
#pragma unroll
                for (int i = EV_P0; i < EV_COUNT; ++i) mbar_init(BAR_ONE(sb, i), i == EV_P0 ? 8 : (i == EV_P3 || i == EV_P31) ? 4 : 1);
            }
            asm volatile("fence.mbarrier_init.release.cluster;" ::: "memory");
        }
        __syncwarp();
        cluster_arrive();
        ep = 0;
        if (warp != 8 || aux) ep = flag_get(g_flags + FL_DONE);
        cluster_wait();
        ep = __shfl_sync(0xffffffffu, ep, 0) / NCTA + 1;
        if (warp == 8) {
            const bool el = elect_one();
            Ring r{0, 1};
            if (aux) {
                mbar_wait(BAR_ONE(sb, EV_GO), 0);
#pragma unroll 1
                for (int it = 0; it < 64; ++it) {
                    const int col = 2048 + (it >> 4) * 1024 + j * 256;
                    mbar_wait(BAR_EMPTY(sb, r.slot), r.par);
                    const uint32_t st = sb + r.slot * SLOT, fb = BAR_FULL(sb, r.slot);
                    if (el) {
                        mbar_expect_tx(fb, 32768);
#pragma unroll
                        for (int b = 0; b < 4; ++b) tma_load(st + b * 8192, &mp.wmod, col + b * 64, (it & 15) * 64, fb);
                    }
                    r.next();
                }
                mbar_wait(BAR_ONE(sb, EV_P0), 0);
                const CUtensorMap* wm = rank ? &mp.wu : &mp.wg;
#pragma unroll 1
                for (int g = 0; g < 128; ++g) {
                    const int mx = (j >> 1) * 8 + (g >> 5) * 2 + rank, k0 = (g & 31) * 32;
                    if (k0 == 0) {
                        uint32_t n = 0;
                        while (!__all_sync(0xffffffffu, (int32_t)(flag_get(g_flags + FL_PROG + (mx * 32 + lane) * FS) - (ep * 8 + ST_H2)) >= 0)) { SPIN_GUARD(n); __nanosleep(500); }
                    }
                    mbar_wait(BAR_EMPTY(sb, r.slot), r.par);
                    const uint32_t st = sb + r.slot * SLOT, fb = BAR_FULL(sb, r.slot);
                    if (el) {
                        mbar_expect_tx(fb, 24576);
                        tma_load_mc(st + 8192 + rank * 4096, wm, HC3, k0, fb);
                        tma_load_mc(st + 16384 + rank * 4096, wm, HC3 + 64, k0, fb);
                        tma_load(st, &mp.h2l, k0, mx * 128, fb);
                    }
                    r.next();
                }
            } else {
#pragma unroll 1
                for (int it = 0; it < 32; ++it) {
                    const int cb = j * 128 + rank * 64, k0 = kof(it, 2, j);
                    if (it == BW0) mbar_wait(BAR_ONE(sb, BWEV), 0);
                    if (it == BW1) mbar_wait(BAR_ONE(sb, EV_PAR), 0);
                    if (it == 5) mbar_wait(BAR_ONE(sb, EV_P0), 0);
                    if ((AGO & 1) && it == 6) mbar_wait(BAR_ONE(sb, EV_AGO), 0);
                    mbar_wait(BAR_EMPTY(sb, r.slot), r.par);
                    const uint32_t st = sb + r.slot * SLOT, fb = BAR_FULL(sb, r.slot);
                    if (el) {
                        mbar_expect_tx(fb, it < 4 ? 24576 : 28672);
                        tma_load_mc(st + 8192 + rank * 4096, &mp.wqkv, 1024 + cb, k0, fb);
                        tma_load_mc(st + 16384 + rank * 4096, &mp.wqkv, 2048 + cb, k0, fb);
                        tma_load_mc(st + 24576 + rank * 4096, &mp.wqkv, cb, k0, fb);
                        if (it < 4) mbar_arrive(fb + AF_REL);
                        if (it == PFWO + (m >> 1)) { tma_prefetch(&mp.wo, j * 128, m * 64); tma_prefetch(&mp.wo, j * 128 + 64, m * 64); }
                    }
                    r.next();
                }
                if (el) mbar_arrive(BAR_ONE(sb, EV_KV));
#pragma unroll 1
                for (int it = 0; it < 16; ++it) {
                    if ((AGO & 2) && it == 6) mbar_wait(BAR_ONE(sb, EV_AGO1), 0);
                    mbar_wait(BAR_EMPTY(sb, r.slot), r.par);
                    const uint32_t st = sb + r.slot * SLOT, fb = BAR_FULL(sb, r.slot);
                    if (el) {
                        mbar_expect_tx(fb, it < 2 ? 16384 : 24576);
                        tma_load_mc(st + 16384 + rank * 8192, &mp.wo, j * 128 + rank * 64, kof(it, 1, j), fb);
                        if (it < 2) mbar_arrive(fb + AF_REL);
                        if (it == 6) { prefetch_map(rank ? &mp.wu : &mp.wg); prefetch_map(rank ? &mp.wu3 : &mp.wg3); }
                    }
                    r.next();
                }
                const CUtensorMap* wm = rank ? &mp.wu : &mp.wg;
#pragma unroll 1
                for (int g = 0; g < 96; ++g) {
                    if ((AGO & 4) && g == 6) mbar_wait(BAR_ONE(sb, EV_AGO2), 0);
                    const int p = g >> 5, cb = hcol(p, j), k0 = p == 0 ? kof(g, 2, j) : (g & 31) * 32;
                    mbar_wait(BAR_EMPTY(sb, r.slot), r.par);
                    const uint32_t st = sb + r.slot * SLOT, fb = BAR_FULL(sb, r.slot);
                    if (el) {
                        mbar_expect_tx(fb, (g < 4 || p > 0) ? 24576 : 28672);
                        tma_load_mc(st + 8192 + rank * 4096, wm, cb, k0, fb);
                        tma_load_mc(st + 16384 + rank * 4096, wm, cb + 64, k0, fb);
                        if (p == 0) tma_load3_mc(st + 24576 + rank * 4096, rank ? &mp.wu3 : &mp.wg3, j, k0, fb);
                        else tma_load(st, &mp.h2l, k0, m * 128, fb);
                        if (g < 4) mbar_arrive(fb + AF_REL);
                        if (g == 60) prefetch_map(&mp.wd);
                    }
                    r.next();
                }
#pragma unroll 1
                for (int g = 0; g < 56; ++g) {
                    if (g == 0 || (g & 15) == 6 && g > 6) mbar_wait(BAR_ONE(sb, EV_H0 + (g >> 4)), 0);
                    const int k0 = g * 64;
                    mbar_wait(BAR_EMPTY(sb, r.slot), r.par);
                    const uint32_t st = sb + r.slot * SLOT, fb = BAR_FULL(sb, r.slot);
                    if (el) {
                        mbar_expect_tx(fb, 32768);
                        tma_load_mc(st + 16384 + rank * 8192, &mp.wd, j * 128 + rank * 64, k0, fb);
                        tma_load(st, &mp.hb, k0, m * 128, fb); tma_load(st + 8192, &mp.hb, k0, m * 128 + 64, fb);
                    }
                    r.next();
                }
            }
        } else if (aux) {
            if (warp < 11) {
                const uint32_t w = warp - 9;
                const bool el = elect_one();
#pragma unroll 1
                for (int p = 0; p < 4; ++p) {
                    const int mx = (j >> 1) * 8 + p * 2 + rank;
                    if (el) { mbar_arrive(BAR_SREADY(sb, w * 2)); mbar_arrive(BAR_SREADY(sb, w * 2 + 1)); }
                    mbar_wait2(BAR_SFULL(sb, w * 2), BAR_SFULL(sb, w * 2 + 1), p & 1);
                    if (el) {
                        tma_store(&mp.hb, HC3, mx * 128 + w * 64, sb + OFF_STG + w * 16384); tma_store(&mp.hb, HC3 + 64, mx * 128 + w * 64, sb + OFF_STG + w * 16384 + 8192);
                        bulk_commit(); bulk_wait_all(); flag_set(g_flags + FL_AUX + mx * 2 + w, ep * 8 + ST_H + 3);
                    }
                }
            }
        } else if (warp == 11) {
            const bool el = elect_one();
            const int row0 = m * 128;
            const uint32_t* const fl = g_flags + FL_PROG + (m * 32 + (lane & 16) + (kof(lane & 15, 1, j) >> 6)) * FS;
            if (el) { prefetch_map(&mp.h1h); prefetch_map(&mp.h2h); prefetch_map(&mp.h2l); }
            {
                const uint4* pk = pt.mail->mod1 + grp * 512 + j * 32 + lane;
                uint4 a, b; uint32_t n = 0;
                mbar_wait(BAR_ONE(sb, EV_WIN3), 0);
                while (true) {
                    a = ld_pkt16(pk); b = ld_pkt16(pk + 256);
                    if (__all_sync(0xffffffffu, a.z == ep && b.z == ep)) break;
                    SPIN_GUARD(n);
                }
                sts128(sb + OFF_PAR + lane * 16, a.x, a.y, b.x, b.y);
                __syncwarp();
                if (lane == 0) { mbar_arrive(BAR_ONE(sb, EV_PAR)); TL(46); }
            }
            mbar_wait(BAR_ONE(sb, EV_P0), 0);
            Ring r{0, 1};
#pragma unroll 1
            for (int ph = 0; ph < 3; ++ph) {
                const int sh = ph == 1 ? 1 : 2, nst = 8 << sh;
                const uint32_t half = 16384 >> sh;
                const CUtensorMap* tm = ph == 0 ? &mp.h1h : ph == 1 ? &mp.o : &mp.h2h;
                if (ph == 1) fetch_halo(g_halo + ((m - 1) * 8 + j) * 512 + 256 + lane, m == 0, sb, 2, lane);
                const uint32_t target = ep * 8 + ST_H1 + ph;
                int a0 = 1 << sh, a1 = a0, fr = a0;
                r.skip(fr);
                uint32_t s0 = r.slot, s1 = r.slot, have = 0, n = 0;
                int k0 = j ? 0 : 128, k1 = k0;
#pragma unroll 1
                for (; fr < NSLOT; ++fr) { mbar_wait(BAR_EMPTY(sb, r.slot), r.par); r.next(); }
                uint32_t v = flag_get(fl);
                auto load = [&](int& a, uint32_t& sl, int& k, uint32_t w) {
                    const uint32_t fb = BAR_FULL(sb, sl) + (w ? 0 : AF_REL);
                    if (el) { if (!w) mbar_expect_tx(fb, half); tma_load(sb + sl * SLOT + w * half, tm, k, row0 + w * 64, fb); }
                    if (a == NSLOT - 1 && w == ((AGW >> ph) & 1) && el) mbar_arrive(BAR_ONE(sb, EV_AGO + ph));
                    ++a; if (++sl == NSLOT) sl = 0;
                    k += 128 >> sh; if (k == j * 128) k += 128;
                };
                do {
                    PS(0);
                    if (fr < 2 * NSLOT && mbar_test(BAR_EMPTY(sb, r.slot), r.par)) { ++fr; r.next(); }
                    SPIN_GUARD(n);
                    PS(1);
                    const bool ok = (int32_t)(v - target) >= 0;
                    v = flag_get(fl);
                    have = __ballot_sync(0xffffffffu, ok);
                    PS(2);
#pragma unroll 1
                    while (a1 < fr && (have & (0x10000u << (a1 >> (sh - 1))))) {
                        if (a1 == (1 << sh)) TL(16 + ph);
                        load(a1, s1, k1, 1);
                    }
                    PS(3);
#pragma unroll 1
                    while (a0 < fr && (have & (1u << (a0 >> (sh - 1))))) load(a0, s0, k0, 0);
                    PS(4);
                } while (have != 0xffffffffu);
#pragma unroll 1
                while (a0 < nst) {
                    mbar_wait(BAR_EMPTY(sb, r.slot), r.par);
                    r.next();
                    load(a1, s1, k1, 1); load(a0, s0, k0, 0);
                }
            }
#pragma unroll 1
            for (int p = 0; p < 4; ++p) {
                const uint32_t* f = p < 3 ? fl : g_flags + FL_AUX + m * 2 + (lane & 1);
                uint32_t n = 0;
                while (!__all_sync(0xffffffffu, (int32_t)(flag_get(f) - (ep * 8 + ST_H + p)) >= 0)) { SPIN_GUARD(n); __nanosleep(500); }
                if (el) mbar_arrive(BAR_ONE(sb, EV_H0 + p));
            }
        } else {
            const uint32_t w = warp - 9;
            const int row0 = m * 128 + w * 64;
            const uint32_t stg = sb + OFF_STG + w * 16384;
            uint32_t* const fl = g_flags + FL_PROG + (m * 32 + w * 16 + 2 * j) * FS;
            uint32_t b = 0, par = 0;
            const bool el = elect_one();
            auto store = [&](const CUtensorMap* tm, int col, bool nat = false) {
                mbar_wait(BAR_SFULL(sb, w * 2 + b), (par >> b) & 1);
                par ^= 1u << b;
                if (el) {
                    if (nat) tma_store3(tm, col, row0 >> 1, 0, stg + b * 8192); else tma_store(tm, col, row0, stg + b * 8192);
                    bulk_commit();
                }
                b ^= 1;
            };
            auto send2 = [&](const CUtensorMap* tm, int step) {
                store(tm, j * 128); store(tm, j * 128 + 64);
                if (el) {
                    asm volatile("cp.async.bulk.wait_group 1;" ::: "memory"); flag_set(fl, ep * 8 + step);
                    bulk_wait_all(); flag_set(fl + FS, ep * 8 + step);
                }
            };
            auto free2 = [&]() { if (el) { mbar_arrive(BAR_SREADY(sb, w * 2)); mbar_arrive(BAR_SREADY(sb, w * 2 + 1)); } };
            auto gate = [&](int vec, int ev) {
                uint4 v; uint32_t n = 0;
                while (true) {
                    v = ld_pkt2(g_mod + vec * 512 + j * 64 + lane * 2);
                    if (__all_sync(0xffffffffu, v.y == ep && v.w == ep)) break;
                    SPIN_GUARD(n); __nanosleep(300);
                }
                asm volatile("st.shared.v2.u32 [%0], {%1, %2};" :: "r"(sb + OFF_TAB + (ev - EV_GA) * 256 + lane * 8), "r"(v.x), "r"(v.z) : "memory");
                __syncwarp();
                if (lane == 0) mbar_arrive(BAR_ONE(sb, ev));
            };
            if (el) { prefetch_map(&mp.h1s); prefetch_map(&mp.o); prefetch_map(&mp.h2s); prefetch_map(&mp.hb); prefetch_map(&mp.out); prefetch_map(&mp.wo); }
            if (el) { flag_set(fl, ep * 8); flag_set(fl + FS, ep * 8); }
            send2(&mp.h1s, ST_H1);
            if (w == 0) TL(47);
            free2();
            if (w == 0) fetch_halo(g_halo + ((m - 1) * 8 + j) * 512 + lane, m == 0, sb, 0, lane);
            else { mbar_wait(BAR_ONE(sb, EV_KV), 0); gate(2, EV_GA); }
            send2(&mp.o, ST_O);
            if (w == 0) TL(40); else TL(38);
            mbar_wait(BAR_ONE(sb, EV_OWN + w), 0);
            if (el) {
#pragma unroll
                for (uint32_t i = 0; i < 2; ++i) {
                    mbar_expect_tx(BAR_SREADY(sb, w * 2 + i), 8192);
                    tma_load3(stg + i * 8192, &mp.x, j * 128 + i * 64, row0 >> 1, BAR_SREADY(sb, w * 2 + i));
                }
            }
            if (w == 1) {
                uint32_t n = 0;
                while ((int32_t)(flag_get(g_flags + FL_LN2) - ep * 8) < 0) { SPIN_GUARD(n); __nanosleep(200); }
                const uint4 v = __ldcg((const uint4*)(g_par2 + j * 128) + lane);
                sts128(sb + OFF_PAR + lane * 16, v.x, v.y, v.z, v.w);
                __syncwarp();
                if (lane == 0) mbar_arrive(BAR_ONE(sb, EV_LN2));
            }
            send2(&mp.h2s, ST_H2);
            if (el) { prefetch_map(&mp.hb); prefetch_map(&mp.hb3); }
            if (w == 0) TL(37);
            free2();
#pragma unroll 1
            for (int p = 0; p < 3; ++p) {
                const int col = hcol(p, j);
                store(&mp.hb, col); store(&mp.hb, col + 64);
                if (p == 0) {
                    mbar_wait(BAR_ONE(sb, EV_P3 + w), 0);
                    if (el) { tma_store3(&mp.hb3, 0, j, row0, sb + (w ? P3_SLOT1 : P3_SLOT0) * SLOT + 24576); bulk_commit(); }
                }
                if (el) { bulk_wait_all(); flag_set(fl, ep * 8 + ST_H + p); flag_set(fl + FS, ep * 8 + ST_H + p); }
                free2();
                if (p == 0 && w == 1) gate(5, EV_GB);
            }
            cluster_arrive_early = true;
            cluster_arrive();
            store(&mp.out, j * 128, true); store(&mp.out, j * 128 + 64, true);
            if (el) bulk_wait_read();
        }
        __syncwarp();
    }
    if (aux || (wg == 2 && !cluster_arrive_early)) cluster_arrive();
    cluster_wait();
    if (tid == 0) {
        TL(15);
        flag_add(pt.mail->flags + FL_DONE);
    }
}

typedef CUresult (*EncodeFn)(CUtensorMap*, CUtensorMapDataType, cuuint32_t, void*, const cuuint64_t*, const cuuint64_t*, const cuuint32_t*,
                             const cuuint32_t*, CUtensorMapInterleave, CUtensorMapSwizzle, CUtensorMapL2promotion, CUtensorMapFloatOOBfill);

void make_map(EncodeFn fn, CUtensorMap* m, const void* ptr, uint64_t rows, uint64_t cols, uint32_t brows, uint32_t bcols) {
    cuuint64_t dims[2] = {cols, rows}, strides[1] = {cols * 2};
    cuuint32_t box[2] = {bcols, brows}, es[2] = {1, 1};
    fn(m, CU_TENSOR_MAP_DATA_TYPE_BFLOAT16, 2, (void*)ptr, dims, strides, box, es, CU_TENSOR_MAP_INTERLEAVE_NONE,
       bcols == 64 ? CU_TENSOR_MAP_SWIZZLE_128B : bcols == 32 ? CU_TENSOR_MAP_SWIZZLE_64B : CU_TENSOR_MAP_SWIZZLE_NONE, CU_TENSOR_MAP_L2_PROMOTION_L2_256B, CU_TENSOR_MAP_FLOAT_OOB_FILL_NONE);
}

void make_map3(EncodeFn fn, CUtensorMap* m, const void* ptr) {
    cuuint64_t dims[3] = {D_, S_ / 2, 2}, strides[2] = {4 * D_, 2 * D_};
    cuuint32_t box[3] = {64, 32, 2}, es[3] = {1, 1, 1};
    fn(m, CU_TENSOR_MAP_DATA_TYPE_BFLOAT16, 3, (void*)ptr, dims, strides, box, es, CU_TENSOR_MAP_INTERLEAVE_NONE,
       CU_TENSOR_MAP_SWIZZLE_128B, CU_TENSOR_MAP_L2_PROMOTION_L2_256B, CU_TENSOR_MAP_FLOAT_OOB_FILL_NONE);
}

void make_map48(EncodeFn fn, CUtensorMap* m, const void* ptr, uint64_t rows, uint32_t brows) {
    cuuint64_t dims[3] = {48, 8, rows}, strides[2] = {96, 2 * F_};
    cuuint32_t box[3] = {64, 1, brows}, es[3] = {1, 1, 1};
    fn(m, CU_TENSOR_MAP_DATA_TYPE_BFLOAT16, 3, (void*)ptr, dims, strides, box, es, CU_TENSOR_MAP_INTERLEAVE_NONE,
       CU_TENSOR_MAP_SWIZZLE_128B, CU_TENSOR_MAP_L2_PROMOTION_L2_256B, CU_TENSOR_MAP_FLOAT_OOB_FILL_NONE);
}

}

extern "C" void kernel_launch(void* const* d_in, const int* in_sizes, int n_in, void* d_out, int out_size) {
    (void)in_sizes; (void)n_in; (void)out_size;
    void* fnp = nullptr;
    cudaDriverEntryPointQueryResult qr;
    cudaGetDriverEntryPoint("cuTensorMapEncodeTiled", &fnp, cudaEnableDefault, &qr);
    EncodeFn fn = (EncodeFn)fnp;
    void *h1, *o, *h2, *hb, *mail;
    cudaGetSymbolAddress(&h1, g_h1);
    cudaGetSymbolAddress(&mail, g_mail);
    cudaGetSymbolAddress(&o, g_o);
    cudaGetSymbolAddress(&hb, g_hb);
    h2 = H2ALIAS;
    Maps mp;
    make_map(fn, &mp.h1h, h1, S_, D_, 64, 32);
    make_map(fn, &mp.h2h, h2, S_, D_, 64, 32);
    make_map(fn, &mp.h1s, h1, S_, D_, 64, 64);
    make_map(fn, &mp.o, o, S_, D_, 64, 64);
    make_map(fn, &mp.h2l, h2, S_, D_, 128, 32);
    make_map(fn, &mp.h2s, h2, S_, D_, 64, 64);
    make_map(fn, &mp.hb, hb, S_, F_, 64, 64);
    make_map(fn, &mp.wqkv, d_in[1], D_, 3 * D_, 32, 64);
    make_map(fn, &mp.wo, d_in[2], D_, D_, 64, 64);
    make_map(fn, &mp.wg, d_in[4], D_, F_, 32, 64);
    make_map(fn, &mp.wu, d_in[5], D_, F_, 32, 64);
    make_map(fn, &mp.wd, d_in[6], F_, D_, 64, 64);
    make_map(fn, &mp.wmod, d_in[8], D_, 6 * D_, 64, 64);
    make_map(fn, &mp.wm8, d_in[8], D_ / 8, 8 * 6 * D_, 128, 16);
    make_map3(fn, &mp.x, d_in[0]);
    make_map3(fn, &mp.out, d_out);
    make_map48(fn, &mp.wg3, d_in[4], D_, 32);
    make_map48(fn, &mp.wu3, d_in[5], D_, 32);
    make_map48(fn, &mp.hb3, hb, S_, 64);
    cudaFuncSetAttribute(fused_block_kernel, cudaFuncAttributeMaxDynamicSharedMemorySize, SMEM_BYTES);
    cudaLaunchConfig_t cfg = {};
    cfg.gridDim = dim3(NCTA); cfg.blockDim = dim3(384); cfg.dynamicSmemBytes = SMEM_BYTES; cfg.stream = cudaStreamPerThread;
    cudaLaunchAttribute at[1];
    at[0].id = cudaLaunchAttributeClusterDimension; at[0].val.clusterDim.x = 2; at[0].val.clusterDim.y = 1; at[0].val.clusterDim.z = 1;
    cfg.attrs = at; cfg.numAttrs = 1;
    const Ptrs pt{(const __nv_bfloat16*)d_in[7], (Mail*)mail};
    cudaLaunchKernelEx(&cfg, fused_block_kernel, pt, mp);
}
```

```cpp
#include <cuda_runtime.h>
#include <cuda_bf16.h>
#include <cuda.h>
#include <stdint.h>
#include <stddef.h>

#define LAG 3
#define LAGS 4
#define LAGW 3
#define LAGQ 4
#define MIDW 8
#define PFWO 14
#define FLAGRED 1
#define FS 1
#define AGO 7
#define AGW 6
#define CSW 0
#define FENCES 1
#define LWAIT 2
#define BW0 0
#define BWEV EV_WIN
#define GODLY 0
#define BW1 3
#define PDLY 500
#define H2ALIAS o
#define HD1 6000
#define HD0 6000
#define HP 2200
#define KORD 1
#define KDEBUG 0

namespace {

constexpr int S_ = 2048, D_ = 1024, F_ = 3584;
constexpr int NCTA = 132;
constexpr int NSLOT = 6;
constexpr uint32_t SLOT = 32768;
constexpr uint32_t OFF_STG = NSLOT * SLOT;
constexpr uint32_t OFF_BAR = OFF_STG + 32768;
constexpr uint32_t OFF_PAR = OFF_BAR + 512;
constexpr uint32_t OFF_TAB = OFF_PAR + 768;
constexpr uint32_t OFF_TL = OFF_PAR + 2048;
constexpr uint32_t SMEM_BYTES = OFF_TL + (KDEBUG ? 512 : 0);
constexpr uint32_t P3_SLOT1 = (32 + 16 + 32) % NSLOT, P3_SLOT0 = (P3_SLOT1 + 1) % NSLOT;

constexpr int ST_H1 = 1, ST_O = 2, ST_H2 = 3, ST_H = 4, FL_DONE = 0, FL_LN2 = 1, FL_AUX = 32, FL_PROG = 64;

struct Maps {
    CUtensorMap h1h, h1s, o, h2h, h2l, h2s, hb, wqkv, wo, wg, wu, wd, wmod, wm8, x, out, wg3, wu3, hb3;
};

struct Mail {
    uint32_t flags[16 * 32 * FS + 64];
    uint2 mod[6 * D_ / 2];
    uint4 mod1[8 * 512];
    uint4 st1[128 * 512];
    uint32_t par2[D_];
    uint4 halo[128 * 512];
};
struct Ptrs { const __nv_bfloat16* c; Mail* mail; };

__device__ __align__(128) Mail g_mail;
__device__ __align__(128) __nv_bfloat16 g_h1[S_ * D_];
__device__ __align__(128) __nv_bfloat16 g_o[S_ * D_];
__device__ __align__(128) __nv_bfloat16 g_hb[S_ * F_];
#define TL(i) do {} while (0)
#define TC(i) do {} while (0)
#define TS(g, which) do {} while (0)
#define CS(i) do {} while (0)

#define PS(i) do {} while (0)
__device__ __forceinline__ uint32_t smem_u32(const void* p) { return (uint32_t)__cvta_generic_to_shared(p); }
__device__ __forceinline__ void mbar_init(uint32_t bar, uint32_t cnt) { asm volatile("mbarrier.init.shared::cta.b64 [%0], %1;" :: "r"(bar), "r"(cnt) : "memory"); }
__device__ __forceinline__ void mbar_expect_tx(uint32_t bar, uint32_t bytes) { asm volatile("mbarrier.arrive.expect_tx.shared::cta.b64 _, [%0], %1;" :: "r"(bar), "r"(bytes) : "memory"); }
__device__ __forceinline__ void mbar_arrive(uint32_t bar) { asm volatile("mbarrier.arrive.shared::cta.b64 _, [%0];" :: "r"(bar) : "memory"); }
__device__ __forceinline__ void mbar_arrive_cta(uint32_t bar, uint32_t cta) {
    asm volatile("{\n.reg .b32 r;\nmapa.shared::cluster.u32 r, %0, %1;\nmbarrier.arrive.shared::cluster.b64 _, [r];\n}" :: "r"(bar), "r"(cta) : "memory");
}
__device__ __forceinline__ void mbar_wait(uint32_t bar, uint32_t parity) {
    asm volatile("{\n.reg .pred p;\n.reg .u32 n;\nmov.u32 n, 0;\n"
        "W_LOOP:\nmbarrier.try_wait.parity.shared::cta.b64 p, [%0], %1;\n@p bra W_DONE;\n"
        "add.u32 n, n, 1;\nsetp.lt.u32 p, n, 0x400000;\n@p bra W_LOOP;\ntrap;\nW_DONE:\n}" :: "r"(bar), "r"(parity) : "memory");
}
__device__ __forceinline__ void mbar_wait2(uint32_t b0, uint32_t b1, uint32_t parity) {
    asm volatile("{\n.reg .pred p, q;\n.reg .u32 n;\nmov.u32 n, 0;\n"
        "W_LOOP:\nmbarrier.try_wait.parity.shared::cta.b64 p, [%0], %2;\nmbarrier.try_wait.parity.shared::cta.b64 q, [%1], %2;\nand.pred p, p, q;\n@p bra W_DONE;\n"
        "add.u32 n, n, 1;\nsetp.lt.u32 p, n, 0x400000;\n@p bra W_LOOP;\ntrap;\nW_DONE:\n}" :: "r"(b0), "r"(b1), "r"(parity) : "memory");
}
__device__ __forceinline__ bool mbar_test(uint32_t bar, uint32_t parity) {
    uint32_t r; asm volatile("{\n.reg .pred p;\nmbarrier.test_wait.parity.shared::cta.b64 p, [%1], %2;\nselp.u32 %0, 1, 0, p;\n}" : "=r"(r) : "r"(bar), "r"(parity) : "memory"); return r;
}
__device__ __forceinline__ bool mbar_test2(uint32_t b0, uint32_t b1, uint32_t parity) {
    uint32_t r;
    asm volatile("{\n.reg .pred p, q;\nmbarrier.test_wait.parity.shared::cta.b64 p, [%1], %3;\nmbarrier.test_wait.parity.shared::cta.b64 q, [%2], %3;\n"
        "and.pred p, p, q;\nselp.u32 %0, 1, 0, p;\n}" : "=r"(r) : "r"(b0), "r"(b1), "r"(parity) : "memory");
    return r;
}
__device__ __forceinline__ void tma_load3(uint32_t dst, const CUtensorMap* m, int c0, int c1, uint32_t bar) {
    asm volatile("cp.async.bulk.tensor.3d.shared::cluster.global.mbarrier::complete_tx::bytes [%0], [%1, {%3, %4, %5}], [%2];"
        :: "r"(dst), "l"(m), "r"(bar), "r"(c0), "r"(c1), "r"(0) : "memory");
}
__device__ __forceinline__ void tma_store3(const CUtensorMap* m, int c0, int c1, int c2, uint32_t src) {
    asm volatile("cp.async.bulk.tensor.3d.global.shared::cta.bulk_group [%0, {%2, %3, %4}], [%1];" :: "l"(m), "r"(src), "r"(c0), "r"(c1), "r"(c2) : "memory");
}
__device__ __forceinline__ void tma_load3_mc(uint32_t dst, const CUtensorMap* m, int c1, int c2, uint32_t bar) {
    asm volatile("cp.async.bulk.tensor.3d.shared::cluster.global.mbarrier::complete_tx::bytes.multicast::cluster.L2::cache_hint [%0], [%1, {%3, %4, %5}], [%2], %6, %7;"
        :: "r"(dst), "l"(m), "r"(bar), "r"(0), "r"(c1), "r"(c2), "h"((uint16_t)3), "l"(0x12F0000000000000ull) : "memory");
}
__device__ __forceinline__ void tma_load(uint32_t dst, const CUtensorMap* m, int c0, int c1, uint32_t bar) {
    asm volatile("cp.async.bulk.tensor.2d.shared::cluster.global.mbarrier::complete_tx::bytes [%0], [%1, {%3, %4}], [%2];"
        :: "r"(dst), "l"(m), "r"(bar), "r"(c0), "r"(c1) : "memory");
}
__device__ __forceinline__ void tma_load_mc(uint32_t dst, const CUtensorMap* m, int c0, int c1, uint32_t bar) {
    asm volatile("cp.async.bulk.tensor.2d.shared::cluster.global.mbarrier::complete_tx::bytes.multicast::cluster.L2::cache_hint [%0], [%1, {%3, %4}], [%2], %5, %6;"
        :: "r"(dst), "l"(m), "r"(bar), "r"(c0), "r"(c1), "h"((uint16_t)3), "l"(0x12F0000000000000ull) : "memory");
}
__device__ __forceinline__ void tma_prefetch(const CUtensorMap* m, int c0, int c1) {
    asm volatile("cp.async.bulk.prefetch.tensor.2d.L2.global [%0, {%1, %2}];" :: "l"(m), "r"(c0), "r"(c1) : "memory");
}
__device__ __forceinline__ void tma_store(const CUtensorMap* m, int c0, int c1, uint32_t src) {
    asm volatile("cp.async.bulk.tensor.2d.global.shared::cta.bulk_group [%0, {%2, %3}], [%1];" :: "l"(m), "r"(src), "r"(c0), "r"(c1) : "memory");
}
__device__ __forceinline__ void bulk_commit() { asm volatile("cp.async.bulk.commit_group;" ::: "memory"); }
__device__ __forceinline__ void bulk_wait_read() { asm volatile("cp.async.bulk.wait_group.read 0;" ::: "memory"); }
__device__ __forceinline__ void bulk_wait_all() { asm volatile("cp.async.bulk.wait_group 0;" ::: "memory"); }
__device__ __forceinline__ void fence_async_smem() { asm volatile("fence.proxy.async.shared::cta;" ::: "memory"); }
__device__ __forceinline__ void prefetch_map(const CUtensorMap* m) { asm volatile("prefetch.tensormap [%0];" :: "l"(m) : "memory"); }
__device__ __forceinline__ void wg_fence() { asm volatile("wgmma.fence.sync.aligned;" ::: "memory"); }
__device__ __forceinline__ void wg_commit() { asm volatile("wgmma.commit_group.sync.aligned;" ::: "memory"); }
template <int N> __device__ __forceinline__ void wg_wait() { asm volatile("wgmma.wait_group.sync.aligned %0;" :: "n"(N) : "memory"); }
__device__ __forceinline__ void bar_sync(int id, int n) { asm volatile("bar.sync %0, %1;" :: "r"(id), "r"(n) : "memory"); }
__device__ __forceinline__ void bar_arrive(int id, int n) { asm volatile("bar.arrive %0, %1;" :: "r"(id), "r"(n) : "memory"); }
__device__ __forceinline__ void flag_add(uint32_t* f) { asm volatile("red.relaxed.gpu.global.add.u32 [%0], 1;" :: "l"(f) : "memory"); }
__device__ __forceinline__ void flag_set(uint32_t* f, uint32_t v) { asm volatile("red.relaxed.gpu.global.max.u32 [%0], %1;" :: "l"(f), "r"(v) : "memory"); }
__device__ __forceinline__ uint32_t flag_get(const uint32_t* f) { uint32_t v; asm volatile("ld.relaxed.gpu.global.u32 %0, [%1];" : "=r"(v) : "l"(f) : "memory"); return v; }
__device__ __forceinline__ uint32_t d16(uint32_t addr) { return (addr & 0x3FFFF) >> 4; }
__device__ __forceinline__ uint64_t mk_desc(uint32_t a16, uint32_t off, uint32_t lbo, uint32_t sbo, uint32_t swz) {
    const uint32_t lo = a16 + (off >> 4) + ((lbo >> 4) << 16), hi = (sbo >> 4) | (swz << 30);
    return ((uint64_t)hi << 32) | lo;
}
__device__ __forceinline__ uint32_t pack2(float lo, float hi) {
    uint32_t r; asm("cvt.rn.bf16x2.f32 %0, %1, %2;" : "=r"(r) : "f"(hi), "f"(lo)); return r;
}
__device__ __forceinline__ uint32_t hfma2_bf16(uint32_t a, uint32_t b, uint32_t c) {
    uint32_t r; asm("fma.rn.bf16x2 %0, %1, %2, %3;" : "=r"(r) : "r"(a), "r"(b), "r"(c)); return r;
}
__device__ __forceinline__ float bf_lo(uint32_t v) { return __uint_as_float(v << 16); }
__device__ __forceinline__ float bf_hi(uint32_t v) { return __uint_as_float(v & 0xFFFF0000u); }
__device__ __forceinline__ void unpack2(uint32_t v, float& lo, float& hi) {
    asm volatile("shl.b32 %0, %2, 16;\nand.b32 %1, %2, 0xffff0000;" : "=f"(lo), "=f"(hi) : "r"(v));
}
__device__ __forceinline__ float bf_round(float x) { return __bfloat162float(__float2bfloat16_rn(x)); }
__device__ __forceinline__ void stsm4(uint32_t addr, uint32_t r0, uint32_t r1, uint32_t r2, uint32_t r3) {
    asm volatile("stmatrix.sync.aligned.m8n8.x4.shared.b16 [%0], {%1, %2, %3, %4};" :: "r"(addr), "r"(r0), "r"(r1), "r"(r2), "r"(r3) : "memory");
}
__device__ __forceinline__ void stsm4t(uint32_t addr, uint32_t r0, uint32_t r1, uint32_t r2, uint32_t r3) {
    asm volatile("stmatrix.sync.aligned.m8n8.x4.trans.shared.b16 [%0], {%1, %2, %3, %4};" :: "r"(addr), "r"(r0), "r"(r1), "r"(r2), "r"(r3) : "memory");
}
__device__ __forceinline__ uint32_t movm(uint32_t a) { uint32_t d; asm volatile("movmatrix.sync.aligned.m8n8.trans.b16 %0, %1;" : "=r"(d) : "r"(a)); return d; }
__device__ __forceinline__ void ldsm4(uint32_t addr, uint32_t& r0, uint32_t& r1, uint32_t& r2, uint32_t& r3) {
    asm volatile("ldmatrix.sync.aligned.m8n8.x4.shared.b16 {%0, %1, %2, %3}, [%4];" : "=r"(r0), "=r"(r1), "=r"(r2), "=r"(r3) : "r"(addr) : "memory");
}
__device__ __forceinline__ void ldsm4t(uint32_t addr, uint32_t& r0, uint32_t& r1, uint32_t& r2, uint32_t& r3) {
    asm volatile("ldmatrix.sync.aligned.m8n8.x4.trans.shared.b16 {%0, %1, %2, %3}, [%4];" : "=r"(r0), "=r"(r1), "=r"(r2), "=r"(r3) : "r"(addr) : "memory");
}
__device__ __forceinline__ void mma16816(float (&c)[4], uint32_t a0, uint32_t a1, uint32_t a2, uint32_t a3, uint32_t b0, uint32_t b1) {
    asm("mma.sync.aligned.m16n8k16.row.col.f32.bf16.bf16.f32 {%0, %1, %2, %3}, {%4, %5, %6, %7}, {%8, %9}, {%0, %1, %2, %3};"
        : "+f"(c[0]), "+f"(c[1]), "+f"(c[2]), "+f"(c[3]) : "r"(a0), "r"(a1), "r"(a2), "r"(a3), "r"(b0), "r"(b1));
}
__device__ __forceinline__ float rcp(float x) { float r; asm("rcp.approx.ftz.f32 %0, %1;" : "=f"(r) : "f"(x)); return r; }
__device__ __forceinline__ float ex2(float x) { float r; asm("ex2.approx.ftz.f32 %0, %1;" : "=f"(r) : "f"(x)); return r; }
__device__ __forceinline__ float glu_half(float gh, float uh) {
    float t; asm("tanh.approx.f32 %0, %1;" : "=f"(t) : "f"(gh)); return fmaf(t, uh, uh);
}
__device__ __forceinline__ float silu_(float x) { return __fdividef(x, 1.f + __expf(-x)); }
__device__ __forceinline__ void st_pkt(void* p, uint32_t a, uint32_t b) {
    asm volatile("{\n.reg .b64 t;\nmov.b64 t, {%1, %2};\nst.relaxed.gpu.global.b64 [%0], t;\n}" :: "l"(p), "r"(a), "r"(b) : "memory");
}
__device__ __forceinline__ uint4 ld_pkt2(const void* p) {
    uint4 v; asm volatile("{\n.reg .b64 t, u;\nld.relaxed.gpu.global.v2.b64 {t, u}, [%4];\nmov.b64 {%0, %1}, t;\nmov.b64 {%2, %3}, u;\n}"
        : "=r"(v.x), "=r"(v.y), "=r"(v.z), "=r"(v.w) : "l"(p) : "memory"); return v;
}
__device__ __forceinline__ void st_pkt16(void* p, uint32_t a, uint32_t b, uint32_t c, uint32_t d) {
    asm volatile("{\n.reg .b64 t, u;\n.reg .b128 w;\nmov.b64 t, {%1, %2};\nmov.b64 u, {%3, %4};\nmov.b128 w, {t, u};\nst.relaxed.gpu.global.b128 [%0], w;\n}"
        :: "l"(p), "r"(a), "r"(b), "r"(c), "r"(d) : "memory");
}
__device__ __forceinline__ uint4 ld_pkt16(const void* p) {
    uint4 v; asm volatile("{\n.reg .b64 t, u;\n.reg .b128 w;\nld.relaxed.gpu.global.b128 w, [%4];\nmov.b128 {t, u}, w;\nmov.b64 {%0, %1}, t;\nmov.b64 {%2, %3}, u;\n}"
        : "=r"(v.x), "=r"(v.y), "=r"(v.z), "=r"(v.w) : "l"(p) : "memory"); return v;
}
#define SPIN_GUARD(n) do { if (++(n) > (1u << 22)) asm volatile("trap;"); } while (0)
__device__ __forceinline__ uint4 lds128(uint32_t a) { uint4 v; asm volatile("ld.shared.v4.u32 {%0, %1, %2, %3}, [%4];" : "=r"(v.x), "=r"(v.y), "=r"(v.z), "=r"(v.w) : "r"(a) : "memory"); return v; }
__device__ __forceinline__ void sts128(uint32_t a, uint32_t x, uint32_t y, uint32_t z, uint32_t w) { asm volatile("st.shared.v4.u32 [%0], {%1, %2, %3, %4};" :: "r"(a), "r"(x), "r"(y), "r"(z), "r"(w) : "memory"); }
__device__ __forceinline__ uint32_t lds32(uint32_t a) { uint32_t v; asm volatile("ld.shared.u32 %0, [%1];" : "=r"(v) : "r"(a) : "memory"); return v; }
__device__ __forceinline__ void sts32(uint32_t a, uint32_t v) { asm volatile("st.shared.u32 [%0], %1;" :: "r"(a), "r"(v) : "memory"); }
__device__ __forceinline__ bool elect_one() {
    uint32_t p; asm volatile("{\n.reg .pred q;\nelect.sync _|q, 0xffffffff;\nselp.u32 %0, 1, 0, q;\n}" : "=r"(p)); return p;
}
__device__ __forceinline__ void pause(uint32_t cycles) {
    uint32_t t0, t; asm volatile("mov.u32 %0, %%clock;" : "=r"(t0));
    do { __nanosleep(64); asm volatile("mov.u32 %0, %%clock;" : "=r"(t)); } while (t - t0 < cycles);
}
__device__ __forceinline__ void cluster_arrive() { asm volatile("barrier.cluster.arrive.relaxed.aligned;" ::: "memory"); }
__device__ __forceinline__ void cluster_wait() { asm volatile("barrier.cluster.wait.aligned;" ::: "memory"); }

__device__ __forceinline__ void wgmma_n128_z(float (&d)[64], uint64_t da, uint64_t db) {
    asm volatile("{\n.reg .pred p;\nsetp.ne.b32 p, 0, 0;\n"
        "wgmma.mma_async.sync.aligned.m64n128k16.f32.bf16.bf16 {"
        "%0, %1, %2, %3, %4, %5, %6, %7, %8, %9, %10, %11, %12, %13, %14, %15, "
        "%16, %17, %18, %19, %20, %21, %22, %23, %24, %25, %26, %27, %28, %29, %30, %31, "
        "%32, %33, %34, %35, %36, %37, %38, %39, %40, %41, %42, %43, %44, %45, %46, %47, "
        "%48, %49, %50, %51, %52, %53, %54, %55, %56, %57, %58, %59, %60, %61, %62, %63"
        "}, %64, %65, p, 1, 1, 0, 1;\n}\n"
        : "=f"(d[0]), "=f"(d[1]), "=f"(d[2]), "=f"(d[3]), "=f"(d[4]), "=f"(d[5]), "=f"(d[6]), "=f"(d[7]),
          "=f"(d[8]), "=f"(d[9]), "=f"(d[10]), "=f"(d[11]), "=f"(d[12]), "=f"(d[13]), "=f"(d[14]), "=f"(d[15]),
          "=f"(d[16]), "=f"(d[17]), "=f"(d[18]), "=f"(d[19]), "=f"(d[20]), "=f"(d[21]), "=f"(d[22]), "=f"(d[23]),
          "=f"(d[24]), "=f"(d[25]), "=f"(d[26]), "=f"(d[27]), "=f"(d[28]), "=f"(d[29]), "=f"(d[30]), "=f"(d[31]),
          "=f"(d[32]), "=f"(d[33]), "=f"(d[34]), "=f"(d[35]), "=f"(d[36]), "=f"(d[37]), "=f"(d[38]), "=f"(d[39]),
          "=f"(d[40]), "=f"(d[41]), "=f"(d[42]), "=f"(d[43]), "=f"(d[44]), "=f"(d[45]), "=f"(d[46]), "=f"(d[47]),
          "=f"(d[48]), "=f"(d[49]), "=f"(d[50]), "=f"(d[51]), "=f"(d[52]), "=f"(d[53]), "=f"(d[54]), "=f"(d[55]),
          "=f"(d[56]), "=f"(d[57]), "=f"(d[58]), "=f"(d[59]), "=f"(d[60]), "=f"(d[61]), "=f"(d[62]), "=f"(d[63])
        : "l"(da), "l"(db));
}
__device__ __forceinline__ void wgmma_n128(float (&d)[64], uint64_t da, uint64_t db) {
    asm volatile("{\n.reg .pred p;\nsetp.eq.b32 p, 0, 0;\n"
        "wgmma.mma_async.sync.aligned.m64n128k16.f32.bf16.bf16 {"
        "%0, %1, %2, %3, %4, %5, %6, %7, %8, %9, %10, %11, %12, %13, %14, %15, "
        "%16, %17, %18, %19, %20, %21, %22, %23, %24, %25, %26, %27, %28, %29, %30, %31, "
        "%32, %33, %34, %35, %36, %37, %38, %39, %40, %41, %42, %43, %44, %45, %46, %47, "
        "%48, %49, %50, %51, %52, %53, %54, %55, %56, %57, %58, %59, %60, %61, %62, %63"
        "}, %64, %65, p, 1, 1, 0, 1;\n}\n"
        : "+f"(d[0]), "+f"(d[1]), "+f"(d[2]), "+f"(d[3]), "+f"(d[4]), "+f"(d[5]), "+f"(d[6]), "+f"(d[7]),
          "+f"(d[8]), "+f"(d[9]), "+f"(d[10]), "+f"(d[11]), "+f"(d[12]), "+f"(d[13]), "+f"(d[14]), "+f"(d[15]),
          "+f"(d[16]), "+f"(d[17]), "+f"(d[18]), "+f"(d[19]), "+f"(d[20]), "+f"(d[21]), "+f"(d[22]), "+f"(d[23]),
          "+f"(d[24]), "+f"(d[25]), "+f"(d[26]), "+f"(d[27]), "+f"(d[28]), "+f"(d[29]), "+f"(d[30]), "+f"(d[31]),
          "+f"(d[32]), "+f"(d[33]), "+f"(d[34]), "+f"(d[35]), "+f"(d[36]), "+f"(d[37]), "+f"(d[38]), "+f"(d[39]),
          "+f"(d[40]), "+f"(d[41]), "+f"(d[42]), "+f"(d[43]), "+f"(d[44]), "+f"(d[45]), "+f"(d[46]), "+f"(d[47]),
          "+f"(d[48]), "+f"(d[49]), "+f"(d[50]), "+f"(d[51]), "+f"(d[52]), "+f"(d[53]), "+f"(d[54]), "+f"(d[55]),
          "+f"(d[56]), "+f"(d[57]), "+f"(d[58]), "+f"(d[59]), "+f"(d[60]), "+f"(d[61]), "+f"(d[62]), "+f"(d[63])
        : "l"(da), "l"(db));
}
__device__ __forceinline__ void wgmma_n176_z(float (&d)[88], uint64_t da, uint64_t db) {
    asm volatile("{\n.reg .pred p;\nsetp.ne.b32 p, 0, 0;\n"
        "wgmma.mma_async.sync.aligned.m64n176k16.f32.bf16.bf16 {"
        "%0, %1, %2, %3, %4, %5, %6, %7, %8, %9, %10, %11, %12, %13, %14, %15, "
        "%16, %17, %18, %19, %20, %21, %22, %23, %24, %25, %26, %27, %28, %29, %30, %31, "
        "%32, %33, %34, %35, %36, %37, %38, %39, %40, %41, %42, %43, %44, %45, %46, %47, "
        "%48, %49, %50, %51, %52, %53, %54, %55, %56, %57, %58, %59, %60, %61, %62, %63, "
        "%64, %65, %66, %67, %68, %69, %70, %71, %72, %73, %74, %75, %76, %77, %78, %79, "
        "%80, %81, %82, %83, %84, %85, %86, %87"
        "}, %88, %89, p, 1, 1, 0, 1;\n}\n"
        : "=f"(d[0]), "=f"(d[1]), "=f"(d[2]), "=f"(d[3]), "=f"(d[4]), "=f"(d[5]), "=f"(d[6]), "=f"(d[7]),
          "=f"(d[8]), "=f"(d[9]), "=f"(d[10]), "=f"(d[11]), "=f"(d[12]), "=f"(d[13]), "=f"(d[14]), "=f"(d[15]),
          "=f"(d[16]), "=f"(d[17]), "=f"(d[18]), "=f"(d[19]), "=f"(d[20]), "=f"(d[21]), "=f"(d[22]), "=f"(d[23]),
          "=f"(d[24]), "=f"(d[25]), "=f"(d[26]), "=f"(d[27]), "=f"(d[28]), "=f"(d[29]), "=f"(d[30]), "=f"(d[31]),
          "=f"(d[32]), "=f"(d[33]), "=f"(d[34]), "=f"(d[35]), "=f"(d[36]), "=f"(d[37]), "=f"(d[38]), "=f"(d[39]),
          "=f"(d[40]), "=f"(d[41]), "=f"(d[42]), "=f"(d[43]), "=f"(d[44]), "=f"(d[45]), "=f"(d[46]), "=f"(d[47]),
          "=f"(d[48]), "=f"(d[49]), "=f"(d[50]), "=f"(d[51]), "=f"(d[52]), "=f"(d[53]), "=f"(d[54]), "=f"(d[55]),
          "=f"(d[56]), "=f"(d[57]), "=f"(d[58]), "=f"(d[59]), "=f"(d[60]), "=f"(d[61]), "=f"(d[62]), "=f"(d[63]),
          "=f"(d[64]), "=f"(d[65]), "=f"(d[66]), "=f"(d[67]), "=f"(d[68]), "=f"(d[69]), "=f"(d[70]), "=f"(d[71]),
          "=f"(d[72]), "=f"(d[73]), "=f"(d[74]), "=f"(d[75]), "=f"(d[76]), "=f"(d[77]), "=f"(d[78]), "=f"(d[79]),
          "=f"(d[80]), "=f"(d[81]), "=f"(d[82]), "=f"(d[83]), "=f"(d[84]), "=f"(d[85]), "=f"(d[86]), "=f"(d[87])
        : "l"(da), "l"(db));
}
__device__ __forceinline__ void wgmma_n176(float (&d)[88], uint64_t da, uint64_t db) {
    asm volatile("{\n.reg .pred p;\nsetp.eq.b32 p, 0, 0;\n"
        "wgmma.mma_async.sync.aligned.m64n176k16.f32.bf16.bf16 {"
        "%0, %1, %2, %3, %4, %5, %6, %7, %8, %9, %10, %11, %12, %13, %14, %15, "
        "%16, %17, %18, %19, %20, %21, %22, %23, %24, %25, %26, %27, %28, %29, %30, %31, "
        "%32, %33, %34, %35, %36, %37, %38, %39, %40, %41, %42, %43, %44, %45, %46, %47, "
        "%48, %49, %50, %51, %52, %53, %54, %55, %56, %57, %58, %59, %60, %61, %62, %63, "
        "%64, %65, %66, %67, %68, %69, %70, %71, %72, %73, %74, %75, %76, %77, %78, %79, "
        "%80, %81, %82, %83, %84, %85, %86, %87"
        "}, %88, %89, p, 1, 1, 0, 1;\n}\n"
        : "+f"(d[0]), "+f"(d[1]), "+f"(d[2]), "+f"(d[3]), "+f"(d[4]), "+f"(d[5]), "+f"(d[6]), "+f"(d[7]),
          "+f"(d[8]), "+f"(d[9]), "+f"(d[10]), "+f"(d[11]), "+f"(d[12]), "+f"(d[13]), "+f"(d[14]), "+f"(d[15]),
          "+f"(d[16]), "+f"(d[17]), "+f"(d[18]), "+f"(d[19]), "+f"(d[20]), "+f"(d[21]), "+f"(d[22]), "+f"(d[23]),
          "+f"(d[24]), "+f"(d[25]), "+f"(d[26]), "+f"(d[27]), "+f"(d[28]), "+f"(d[29]), "+f"(d[30]), "+f"(d[31]),
          "+f"(d[32]), "+f"(d[33]), "+f"(d[34]), "+f"(d[35]), "+f"(d[36]), "+f"(d[37]), "+f"(d[38]), "+f"(d[39]),
          "+f"(d[40]), "+f"(d[41]), "+f"(d[42]), "+f"(d[43]), "+f"(d[44]), "+f"(d[45]), "+f"(d[46]), "+f"(d[47]),
          "+f"(d[48]), "+f"(d[49]), "+f"(d[50]), "+f"(d[51]), "+f"(d[52]), "+f"(d[53]), "+f"(d[54]), "+f"(d[55]),
          "+f"(d[56]), "+f"(d[57]), "+f"(d[58]), "+f"(d[59]), "+f"(d[60]), "+f"(d[61]), "+f"(d[62]), "+f"(d[63]),
          "+f"(d[64]), "+f"(d[65]), "+f"(d[66]), "+f"(d[67]), "+f"(d[68]), "+f"(d[69]), "+f"(d[70]), "+f"(d[71]),
          "+f"(d[72]), "+f"(d[73]), "+f"(d[74]), "+f"(d[75]), "+f"(d[76]), "+f"(d[77]), "+f"(d[78]), "+f"(d[79]),
          "+f"(d[80]), "+f"(d[81]), "+f"(d[82]), "+f"(d[83]), "+f"(d[84]), "+f"(d[85]), "+f"(d[86]), "+f"(d[87])
        : "l"(da), "l"(db));
}
__device__ __forceinline__ void wgmma_n256_z(float (&d)[128], uint64_t da, uint64_t db) {
    asm volatile("{\n.reg .pred p;\nsetp.ne.b32 p, 0, 0;\n"
        "wgmma.mma_async.sync.aligned.m64n256k16.f32.bf16.bf16 {"
        "%0, %1, %2, %3, %4, %5, %6, %7, %8, %9, %10, %11, %12, %13, %14, %15, "
        "%16, %17, %18, %19, %20, %21, %22, %23, %24, %25, %26, %27, %28, %29, %30, %31, "
        "%32, %33, %34, %35, %36, %37, %38, %39, %40, %41, %42, %43, %44, %45, %46, %47, "
        "%48, %49, %50, %51, %52, %53, %54, %55, %56, %57, %58, %59, %60, %61, %62, %63, "
        "%64, %65, %66, %67, %68, %69, %70, %71, %72, %73, %74, %75, %76, %77, %78, %79, "
        "%80, %81, %82, %83, %84, %85, %86, %87, %88, %89, %90, %91, %92, %93, %94, %95, "
        "%96, %97, %98, %99, %100, %101, %102, %103, %104, %105, %106, %107, %108, %109, %110, %111, "
        "%112, %113, %114, %115, %116, %117, %118, %119, %120, %121, %122, %123, %124, %125, %126, %127"
        "}, %128, %129, p, 1, 1, 0, 1;\n}\n"
        : "=f"(d[0]), "=f"(d[1]), "=f"(d[2]), "=f"(d[3]), "=f"(d[4]), "=f"(d[5]), "=f"(d[6]), "=f"(d[7]),
          "=f"(d[8]), "=f"(d[9]), "=f"(d[10]), "=f"(d[11]), "=f"(d[12]), "=f"(d[13]), "=f"(d[14]), "=f"(d[15]),
          "=f"(d[16]), "=f"(d[17]), "=f"(d[18]), "=f"(d[19]), "=f"(d[20]), "=f"(d[21]), "=f"(d[22]), "=f"(d[23]),
          "=f"(d[24]), "=f"(d[25]), "=f"(d[26]), "=f"(d[27]), "=f"(d[28]), "=f"(d[29]), "=f"(d[30]), "=f"(d[31]),
          "=f"(d[32]), "=f"(d[33]), "=f"(d[34]), "=f"(d[35]), "=f"(d[36]), "=f"(d[37]), "=f"(d[38]), "=f"(d[39]),
          "=f"(d[40]), "=f"(d[41]), "=f"(d[42]), "=f"(d[43]), "=f"(d[44]), "=f"(d[45]), "=f"(d[46]), "=f"(d[47]),
          "=f"(d[48]), "=f"(d[49]), "=f"(d[50]), "=f"(d[51]), "=f"(d[52]), "=f"(d[53]), "=f"(d[54]), "=f"(d[55]),
          "=f"(d[56]), "=f"(d[57]), "=f"(d[58]), "=f"(d[59]), "=f"(d[60]), "=f"(d[61]), "=f"(d[62]), "=f"(d[63]),
          "=f"(d[64]), "=f"(d[65]), "=f"(d[66]), "=f"(d[67]), "=f"(d[68]), "=f"(d[69]), "=f"(d[70]), "=f"(d[71]),
          "=f"(d[72]), "=f"(d[73]), "=f"(d[74]), "=f"(d[75]), "=f"(d[76]), "=f"(d[77]), "=f"(d[78]), "=f"(d[79]),
          "=f"(d[80]), "=f"(d[81]), "=f"(d[82]), "=f"(d[83]), "=f"(d[84]), "=f"(d[85]), "=f"(d[86]), "=f"(d[87]),
          "=f"(d[88]), "=f"(d[89]), "=f"(d[90]), "=f"(d[91]), "=f"(d[92]), "=f"(d[93]), "=f"(d[94]), "=f"(d[95]),
          "=f"(d[96]), "=f"(d[97]), "=f"(d[98]), "=f"(d[99]), "=f"(d[100]), "=f"(d[101]), "=f"(d[102]), "=f"(d[103]),
          "=f"(d[104]), "=f"(d[105]), "=f"(d[106]), "=f"(d[107]), "=f"(d[108]), "=f"(d[109]), "=f"(d[110]), "=f"(d[111]),
          "=f"(d[112]), "=f"(d[113]), "=f"(d[114]), "=f"(d[115]), "=f"(d[116]), "=f"(d[117]), "=f"(d[118]), "=f"(d[119]),
          "=f"(d[120]), "=f"(d[121]), "=f"(d[122]), "=f"(d[123]), "=f"(d[124]), "=f"(d[125]), "=f"(d[126]), "=f"(d[127])
        : "l"(da), "l"(db));
}
__device__ __forceinline__ void wgmma_n256(float (&d)[128], uint64_t da, uint64_t db) {
    asm volatile("{\n.reg .pred p;\nsetp.eq.b32 p, 0, 0;\n"
        "wgmma.mma_async.sync.aligned.m64n256k16.f32.bf16.bf16 {"
        "%0, %1, %2, %3, %4, %5, %6, %7, %8, %9, %10, %11, %12, %13, %14, %15, "
        "%16, %17, %18, %19, %20, %21, %22, %23, %24, %25, %26, %27, %28, %29, %30, %31, "
        "%32, %33, %34, %35, %36, %37, %38, %39, %40, %41, %42, %43, %44, %45, %46, %47, "
        "%48, %49, %50, %51, %52, %53, %54, %55, %56, %57, %58, %59, %60, %61, %62, %63, "
        "%64, %65, %66, %67, %68, %69, %70, %71, %72, %73, %74, %75, %76, %77, %78, %79, "
        "%80, %81, %82, %83, %84, %85, %86, %87, %88, %89, %90, %91, %92, %93, %94, %95, "
        "%96, %97, %98, %99, %100, %101, %102, %103, %104, %105, %106, %107, %108, %109, %110, %111, "
        "%112, %113, %114, %115, %116, %117, %118, %119, %120, %121, %122, %123, %124, %125, %126, %127"
        "}, %128, %129, p, 1, 1, 0, 1;\n}\n"
        : "+f"(d[0]), "+f"(d[1]), "+f"(d[2]), "+f"(d[3]), "+f"(d[4]), "+f"(d[5]), "+f"(d[6]), "+f"(d[7]),
          "+f"(d[8]), "+f"(d[9]), "+f"(d[10]), "+f"(d[11]), "+f"(d[12]), "+f"(d[13]), "+f"(d[14]), "+f"(d[15]),
          "+f"(d[16]), "+f"(d[17]), "+f"(d[18]), "+f"(d[19]), "+f"(d[20]), "+f"(d[21]), "+f"(d[22]), "+f"(d[23]),
          "+f"(d[24]), "+f"(d[25]), "+f"(d[26]), "+f"(d[27]), "+f"(d[28]), "+f"(d[29]), "+f"(d[30]), "+f"(d[31]),
          "+f"(d[32]), "+f"(d[33]), "+f"(d[34]), "+f"(d[35]), "+f"(d[36]), "+f"(d[37]), "+f"(d[38]), "+f"(d[39]),
          "+f"(d[40]), "+f"(d[41]), "+f"(d[42]), "+f"(d[43]), "+f"(d[44]), "+f"(d[45]), "+f"(d[46]), "+f"(d[47]),
          "+f"(d[48]), "+f"(d[49]), "+f"(d[50]), "+f"(d[51]), "+f"(d[52]), "+f"(d[53]), "+f"(d[54]), "+f"(d[55]),
          "+f"(d[56]), "+f"(d[57]), "+f"(d[58]), "+f"(d[59]), "+f"(d[60]), "+f"(d[61]), "+f"(d[62]), "+f"(d[63]),
          "+f"(d[64]), "+f"(d[65]), "+f"(d[66]), "+f"(d[67]), "+f"(d[68]), "+f"(d[69]), "+f"(d[70]), "+f"(d[71]),
          "+f"(d[72]), "+f"(d[73]), "+f"(d[74]), "+f"(d[75]), "+f"(d[76]), "+f"(d[77]), "+f"(d[78]), "+f"(d[79]),
          "+f"(d[80]), "+f"(d[81]), "+f"(d[82]), "+f"(d[83]), "+f"(d[84]), "+f"(d[85]), "+f"(d[86]), "+f"(d[87]),
          "+f"(d[88]), "+f"(d[89]), "+f"(d[90]), "+f"(d[91]), "+f"(d[92]), "+f"(d[93]), "+f"(d[94]), "+f"(d[95]),
          "+f"(d[96]), "+f"(d[97]), "+f"(d[98]), "+f"(d[99]), "+f"(d[100]), "+f"(d[101]), "+f"(d[102]), "+f"(d[103]),
          "+f"(d[104]), "+f"(d[105]), "+f"(d[106]), "+f"(d[107]), "+f"(d[108]), "+f"(d[109]), "+f"(d[110]), "+f"(d[111]),
          "+f"(d[112]), "+f"(d[113]), "+f"(d[114]), "+f"(d[115]), "+f"(d[116]), "+f"(d[117]), "+f"(d[118]), "+f"(d[119]),
          "+f"(d[120]), "+f"(d[121]), "+f"(d[122]), "+f"(d[123]), "+f"(d[124]), "+f"(d[125]), "+f"(d[126]), "+f"(d[127])
        : "l"(da), "l"(db));
}

struct Idx {
    uint32_t lane, warp, w4, q4, g8, prow, pan;
    __device__ __forceinline__ Idx() {
        uint32_t t; asm volatile("mov.u32 %0, %%tid.x;" : "=r"(t));
        lane = t & 31; warp = t >> 5; w4 = warp & 3; q4 = lane & 3; g8 = lane >> 2;
        prow = w4 * 16 + ((lane >> 3) & 1) * 8 + (lane & 7);
        pan = prow * 128 + (((lane >> 4) ^ (lane & 7)) << 4);
    }
};
#define IDX() const Idx ix; const uint32_t lane = ix.lane, warp = ix.warp, w4 = ix.w4, q4 = ix.q4, g8 = ix.g8, prow = ix.prow, pan_addr = ix.pan; \
    (void)lane; (void)warp; (void)w4; (void)q4; (void)g8; (void)prow; (void)pan_addr;

__device__ __forceinline__ int kof(int t, int sh, int j) {
    const int p = t >> (sh - 1), pn = p < 2 ? p : p >= 9, q = p - 2 - 7 * pn;
    return ((p < 2 ? j : q + (q >= j)) << 7) + (pn << 6) + ((t & (sh - 1)) << 5);
}
constexpr int HC0 = 8 * 48, HC3 = HC0 + 3072;
__device__ __forceinline__ int hcol(int p, int j) { return HC0 + p * 1024 + j * 128; }
#define SCHED_FENCE(k) do { if ((FENCES >> (k)) & 1) asm volatile("{\n.reg .pred p;\nsetp.ne.u32 p, %0, %1;\n@p bra.uni S_SKIP;\ntrap;\nS_SKIP:\n}" :: "r"(sb), "n"(0xffffff00u + (k))); } while (0)

struct Ring {
    uint32_t slot, par;
    __device__ __forceinline__ void next() { if (++slot == NSLOT) { slot = 0; par ^= 1; } }
    __device__ __forceinline__ void skip(uint32_t n) { slot += n; if (slot >= NSLOT) { slot -= NSLOT; par ^= 1; } }
};
__device__ __forceinline__ uint32_t BAR_FULL(uint32_t sb, uint32_t s) { return sb + OFF_BAR + 8 * s; }
constexpr uint32_t AF_REL = 48;
__device__ __forceinline__ uint32_t BAR_EMPTY(uint32_t sb, uint32_t s) { return sb + OFF_BAR + 96 + 8 * s; }
__device__ __forceinline__ uint32_t BAR_SFULL(uint32_t sb, uint32_t i) { return sb + OFF_BAR + 152 + 8 * i; }
__device__ __forceinline__ uint32_t BAR_SREADY(uint32_t sb, uint32_t i) { return sb + OFF_BAR + 184 + 8 * i; }
__device__ __forceinline__ uint32_t BAR_ONE(uint32_t sb, uint32_t i) { return sb + OFF_BAR + 216 + 8 * i; }
enum { EV_WIN, EV_WIN1, EV_WIN2, EV_WIN3, EV_P0, EV_GA, EV_GB, EV_LN2, EV_LAG0, EV_LAG1, EV_LAG2, EV_LAG3, EV_LAG4, EV_LAG5, EV_OWN, EV_OWN1, EV_P3, EV_P31, EV_KV, EV_GO, EV_PAR, EV_AGO, EV_AGO1, EV_AGO2, EV_H0, EV_H1, EV_H2, EV_H3, EV_COUNT };
constexpr int NB_TAIL = 4;

struct Rel {
    uint32_t base; bool sig;
    __device__ __forceinline__ Rel(uint32_t sb, uint32_t tw) {
        uint32_t a; asm("mapa.shared::cluster.u32 %0, %1, %2;" : "=r"(a) : "r"(BAR_EMPTY(sb, 0)), "r"((tw >> 5) & 1));
        base = __shfl_sync(0xffffffffu, a, 0); sig = (tw & ~32u) == 0;
    }
    __device__ __forceinline__ void operator()(uint32_t slot) const {
        if (sig) asm volatile("mbarrier.arrive.shared::cluster.b64 _, [%0];" :: "r"(base + 8 * slot) : "memory");
    }
};
struct LnRow { float rs0, nm0, rs1, nm1; };
struct Pipe {
    Rel rel; uint32_t p1, p2;
    __device__ __forceinline__ Pipe(uint32_t sb, uint32_t tw, uint32_t first) : rel(sb, tw), p1(first), p2(NSLOT) {}
    template <bool TWO> __device__ __forceinline__ void acquire(uint32_t sb, uint32_t af, const Ring& r) {
        const uint32_t b0 = BAR_FULL(sb, r.slot), b1 = b0 + af;
        const bool ready = TWO ? mbar_test2(b0, b1, r.par) : mbar_test(b0, r.par);
        wg_wait<1>();
        rel(p2);
        if (!ready) { if (TWO) mbar_wait2(b0, b1, r.par); else mbar_wait(b0, r.par); }
    }
    __device__ __forceinline__ void issued(uint32_t slot) { p2 = p1; p1 = slot; }
    __device__ __forceinline__ void drain1() { wg_wait<1>(); rel(p2); p2 = NSLOT; }
    __device__ __forceinline__ void drain0() { wg_wait<0>(); rel(p1); p1 = NSLOT; }
    template <bool TWO, int LG, class Step> __device__ __forceinline__ void hold(uint32_t sb, uint32_t af, Ring& r, uint32_t lag_bar, Step step) {
        drain1(); drain0();
        Ring q = r;
#pragma unroll 1
        for (int i = 0; i < LG; ++i) { if (TWO) mbar_wait2(BAR_FULL(sb, q.slot), BAR_FULL(sb, q.slot) + af, q.par); else mbar_wait(BAR_FULL(sb, q.slot), q.par); q.next(); }
        mbar_wait(lag_bar, 0);
#pragma unroll 1
        do {
            step(r.slot);
            wg_wait<2>(); rel(p2); p2 = p1; p1 = r.slot;
            if (++r.slot == NSLOT) r.slot = 0;
        } while (r.slot != q.slot);
        r.par = q.par;
    }
};
template <bool TWO, bool FIRST, int NA, int NB>
__device__ __forceinline__ void step32(float (&aa)[NA], float (&ab)[NB], uint32_t sb, uint32_t wg, uint32_t slot, int own) {
    const uint32_t st = d16(sb) + slot * (SLOT >> 4);
    const uint32_t alo = own >= 0 ? d16(sb) + OFF_STG / 16 + wg * 1024 + (own >> 1) * 512 + (own & 1) * 4 : st + wg * 256;
    const uint32_t ahi = own >= 0 ? (1024 >> 4) | (1u << 30) : (512 >> 4) | (2u << 30);
    wg_fence();
#pragma unroll
    for (int k = 0; k < 2; ++k) {
        const uint64_t da = ((uint64_t)ahi << 32) | (alo + k * 2 + 0x10000);
        if constexpr (NA == 88) {
            const uint64_t d0 = mk_desc(st, 8192 + k * 2048, 8192, 1024, 1), d1 = mk_desc(st, 12288 + k * 2048, 8192, 1024, 1);
            if (FIRST && k == 0) { wgmma_n176_z(aa, da, d0); wgmma_n176_z(ab, da, d1); }
            else { wgmma_n176(aa, da, d0); wgmma_n176(ab, da, d1); }
        } else {
            const uint64_t d0 = mk_desc(st, 8192 + k * 2048, 4096, 1024, 1), d1 = mk_desc(st, 24576 + k * 2048, 4096, 1024, 1);
            if (FIRST && k == 0) { wgmma_n256_z(aa, da, d0); if constexpr (TWO) wgmma_n128_z(ab, da, d1); }
            else { wgmma_n256(aa, da, d0); if constexpr (TWO) wgmma_n128(ab, da, d1); }
        }
    }
    wg_commit();
}
template <bool TWO, int LG, int NA, int NB, class Tail>
__device__ __forceinline__ void mainloop32(float (&aa)[NA], float (&ab)[NB], uint32_t sb, uint32_t wg, uint32_t tw, Ring& r, uint32_t lag_ev, int g0, Tail tail) {
    mbar_wait(BAR_FULL(sb, r.slot), r.par);
    step32<TWO, true>(aa, ab, sb, wg, r.slot, TWO ? 0 : -1);
    TS(g0, 0);
    Pipe pp(sb, tw, r.slot);
    r.next();
    const int end = wg ? 32 : 32 - LG;
#pragma unroll 1
    for (int it = 1; it < end; ++it) {
        pp.acquire<TWO>(sb, wg ? 0 : AF_REL, r);
        step32<TWO, false>(aa, ab, sb, wg, r.slot, TWO && it < 4 ? it : -1);
        pp.issued(r.slot);
        TS(g0 + it, 0);
        r.next();
    }
    if (wg == 0) pp.hold<TWO, LG>(sb, AF_REL, r, BAR_ONE(sb, lag_ev), [&](uint32_t slot) { step32<TWO, false>(aa, ab, sb, 0, slot, -1); });
    pp.drain1();
    if (wg == 1 && tw == 0) mbar_arrive(BAR_ONE(sb, lag_ev));
    tail();
    pp.drain0();
    TS(g0 + 31, 1);
}
template <bool FIRST>
__device__ __forceinline__ void step64(float (&acc)[64], uint32_t sb, uint32_t wg, uint32_t slot, int own) {
    const uint32_t sbb = d16(sb) + slot * (SLOT >> 4), sa = own >= 0 ? d16(sb) + OFF_STG / 16 + wg * 1024 + own * 512 : sbb + wg * 512;
    wg_fence();
#pragma unroll
    for (int k = 0; k < 4; ++k) {
        const uint64_t da = mk_desc(sa, k * 32, 16, 1024, 1), db = mk_desc(sbb, 16384 + k * 2048, 8192, 1024, 1);
        if (FIRST && k == 0) wgmma_n128_z(acc, da, db); else wgmma_n128(acc, da, db);
    }
    wg_commit();
}
template <class Mid>
__device__ __forceinline__ void mainloop64(float (&acc)[64], bool wo, uint32_t sb, uint32_t wg, uint32_t tw, Ring& r, Mid mid) {
    const int g0 = wo ? 32 : 144, nst = wo ? 16 : 56; (void)g0;
    const uint32_t lag_bar = BAR_ONE(sb, wo ? EV_LAG4 : EV_LAG5), af = wo && !wg ? AF_REL : 0;
    mbar_wait(BAR_FULL(sb, r.slot), r.par);
    step64<true>(acc, sb, wg, r.slot, wo ? 0 : -1);
    TS(g0, 0);
    Pipe pp(sb, tw, r.slot);
    r.next();
    int it = 1;
    auto run = [&](int end, int own) {
#pragma unroll 1
        do {
            pp.acquire<true>(sb, af, r);
            step64<false>(acc, sb, wg, r.slot, own);
            pp.issued(r.slot);
            TS(g0 + it, 0);
            r.next();
            if (own > 0) {
                own = -1;
                pp.drain1(); pp.drain0();
                TS(g0 + 1, 1);
                if (tw == 0) mbar_arrive(BAR_ONE(sb, EV_OWN + wg));
            }
        } while (++it < end);
    };
    run(wg ? nst - MIDW : nst - LAGW, wo ? 1 : -1);
    mid();
    if (wg) run(nst, -1);
    else pp.hold<true, LAGW>(sb, af, r, lag_bar, [&](uint32_t slot) { step64<false>(acc, sb, 0, slot, -1); });
    pp.drain1();
    if (wg == 1 && tw == 0) mbar_arrive(lag_bar);
    pp.drain0();
    TS(g0 + nst - 1, 1);
}

struct RowAcc {
    float sm[4] = {0.f, 0.f, 0.f, 0.f}, sq[4] = {0.f, 0.f, 0.f, 0.f};
    __device__ __forceinline__ void add(int e, float x) { sm[e & 3] += x; sq[e & 3] = fmaf(x, x, sq[e & 3]); }
    __device__ __forceinline__ void publish(uint4* dst, uint32_t q4, uint32_t ep) const {
        const float s0 = sm[0] + sm[1], s1 = sm[2] + sm[3], q0 = sq[0] + sq[1], q1 = sq[2] + sq[3];
        const bool od = q4 & 1;
        float sv = (od ? s1 : s0) + __shfl_xor_sync(0xffffffffu, od ? s0 : s1, 1), qv = (od ? q1 : q0) + __shfl_xor_sync(0xffffffffu, od ? q0 : q1, 1);
        sv += __shfl_xor_sync(0xffffffffu, sv, 2); qv += __shfl_xor_sync(0xffffffffu, qv, 2);
        if (q4 < 2) st_pkt16(dst + q4 * 8, 0, __float_as_uint(sv), __float_as_uint(qv), ep);
    }
};
__device__ __forceinline__ LnRow merge_stats(const uint4* src, uint32_t q4, uint32_t ep, uint32_t sb) {
    uint4 t[4];
    uint32_t n = 0;
    while (true) {
#pragma unroll
        for (int i = 0; i < 4; ++i) t[i] = ld_pkt16(src + (q4 * 2 + (i >> 1)) * 512 + (i & 1) * 8);
        const bool ok_ = __all_sync(0xffffffffu, t[0].w == ep && t[1].w == ep && t[2].w == ep && t[3].w == ep);
        if (n < 4) CS(14 + n);
        if (ok_) break;
        SPIN_GUARD(n);
    }
    float v[4];
#pragma unroll
    for (int h = 0; h < 2; ++h) { v[h] = __uint_as_float(t[h].y) + __uint_as_float(t[2 + h].y); v[2 + h] = __uint_as_float(t[h].z) + __uint_as_float(t[2 + h].z); }
#pragma unroll
    for (int o = 1; o < 4; o <<= 1)
#pragma unroll
        for (int i = 0; i < 4; ++i) v[i] += __shfl_xor_sync(0xffffffffu, v[i], o);
    const float m0 = v[0] * (1.f / D_), m1 = v[1] * (1.f / D_);
    const float r0 = rsqrtf(fmaxf(fmaf(-m0, m0, v[2] * (1.f / D_)), 0.f) + 1e-5f), r1 = rsqrtf(fmaxf(fmaf(-m1, m1, v[3] * (1.f / D_)), 0.f) + 1e-5f);
    return LnRow{r0, -m0 * r0, r1, -m1 * r1};
}
struct Stg {
    uint32_t b, par;
    __device__ __forceinline__ uint32_t acquire2(uint32_t sb, uint32_t wg) {
        mbar_wait(BAR_SREADY(sb, wg * 2), par & 1);
        mbar_wait(BAR_SREADY(sb, wg * 2 + 1), (par >> 1) & 1);
        par ^= 3;
        return sb + OFF_STG + wg * 16384;
    }
    __device__ __forceinline__ void publish(uint32_t sb, uint32_t wg, uint32_t lane) {
        fence_async_smem();
        __syncwarp();
        if (lane == 0) mbar_arrive(BAR_SFULL(sb, wg * 2 + b));
        b ^= 1;
    }
};

struct LnPar {
    uint4 p[8];
    __device__ __forceinline__ void load(uint32_t sb, uint32_t q4) {
#pragma unroll
        for (int i = 0; i < 8; ++i) p[i] = lds128(sb + OFF_PAR + i * 64 + q4 * 16);
    }
};
__device__ __forceinline__ void ln_norm(uint32_t (&xn)[32], const float (&x)[64], const LnRow& n) {
#pragma unroll
    for (int e = 0; e < 32; ++e) {
        const float rs = (e & 1) ? n.rs1 : n.rs0, nm = (e & 1) ? n.nm1 : n.nm0;
        xn[e] = pack2(fmaf(x[2 * e], rs, nm), fmaf(x[2 * e + 1], rs, nm));
    }
}
__device__ __forceinline__ void ln_emit(const uint32_t (&xr)[32], const LnPar& lp, uint32_t sb, uint32_t wg, const Idx& ix) {
#pragma unroll
    for (int i = 0; i < 8; ++i)
        stsm4(sb + OFF_STG + wg * 16384 + (i >> 2) * 8192 + (ix.pan ^ ((i & 3) << 5)), hfma2_bf16(xr[4 * i], lp.p[i].z, lp.p[i].x), hfma2_bf16(xr[4 * i + 1], lp.p[i].z, lp.p[i].x),
              hfma2_bf16(xr[4 * i + 2], lp.p[i].w, lp.p[i].y), hfma2_bf16(xr[4 * i + 3], lp.p[i].w, lp.p[i].y));
    fence_async_smem();
    __syncwarp();
    if (ix.lane < 2) mbar_arrive(BAR_SFULL(sb, wg * 2 + ix.lane));
    bar_sync(1 + wg, 128);
}
__device__ __forceinline__ void load_slab(uint32_t (&xr)[32], uint32_t buf) {
    IDX();
#pragma unroll
    for (int i = 0; i < 8; ++i) ldsm4(buf + (i >> 2) * 8192 + (pan_addr ^ ((i & 3) << 5)), xr[4 * i], xr[4 * i + 1], xr[4 * i + 2], xr[4 * i + 3]);
}
__device__ __forceinline__ void unpack_slab(float (&x)[64], const uint32_t (&xr)[32]) {
#pragma unroll
    for (int i = 0; i < 32; ++i) unpack2(xr[i], x[2 * i], x[2 * i + 1]);
}
__device__ __forceinline__ void store_slab(const float (&x)[64], uint32_t buf, uint32_t pitch, uint32_t pan, int i0, int i1) {
#pragma unroll
    for (int i = i0; i < i1; ++i)
        stsm4(buf + (i >> 2) * pitch + (pan ^ ((i & 3) << 5)), pack2(x[8 * i], x[8 * i + 1]), pack2(x[8 * i + 2], x[8 * i + 3]), pack2(x[8 * i + 4], x[8 * i + 5]), pack2(x[8 * i + 6], x[8 * i + 7]));
}
__device__ __forceinline__ void fetch_halo(uint4* src, bool first, uint32_t sb, uint32_t W, uint32_t lane) {
    mbar_wait(BAR_ONE(sb, EV_KV), 0);
    mbar_wait2(BAR_SREADY(sb, 0), BAR_SREADY(sb, 1), 1);
    uint4 hv[8];
    uint32_t n = 0;
    while (true) {
        bool ok = true;
#pragma unroll
        for (int i = 0; i < 8; ++i) { hv[i] = first ? make_uint4(0, 0, 0, 0) : ld_pkt16(src + i * 32); ok = ok && hv[i].x != 0; }
        if (first || __all_sync(0xffffffffu, ok)) break;
        SPIN_GUARD(n);
    }
#pragma unroll
    for (int i = 0; i < 8; ++i) stsm4(sb + OFF_STG + W * 2048 + (i >> 2) * 8192 + (i & 3) * 512 + lane * 16, hv[i].x, hv[i].y, hv[i].z, hv[i].w);
    bar_arrive(NB_TAIL + W, 64);
    if (!first) {
#pragma unroll
        for (int i = 0; i < 8; ++i) src[i * 32] = make_uint4(0, 0, 0, 0);
    }
}

template <int OG, int OU, int LEN>
__device__ __forceinline__ void glu_panel(const float (&g)[LEN], const float (&u)[LEN], uint32_t buf, uint32_t bar) {
    IDX();
    constexpr int NR = LEN - OU < 32 ? (LEN - OU) / 2 : 16;
    uint32_t r[NR];
#pragma unroll
    for (int i = 0; i < NR; ++i) r[i] = pack2(glu_half(g[OG + 2 * i], u[OU + 2 * i]), glu_half(g[OG + 2 * i + 1], u[OU + 2 * i + 1]));
#pragma unroll
    for (int jn = 0; jn < NR / 2; jn += 2) stsm4(buf + (pan_addr ^ (jn << 4)), r[jn * 2], r[jn * 2 + 1], r[jn * 2 + 2], r[jn * 2 + 3]);
    fence_async_smem();
    __syncwarp();
    if (lane == 0) mbar_arrive(bar);
}

template <int NP>
__device__ __forceinline__ void passes128(uint32_t sb, uint32_t wg, uint32_t tw, Ring& r, Stg& stg) {
#pragma unroll 1
    for (int p = 0; p < NP; ++p) {
        float b256[128], none[1];
        mainloop32<false, LAGS>(b256, none, sb, wg, tw, r, EV_LAG2 + p, 80 + 32 * (p & 1), [&] { stg.acquire2(sb, wg); });
        if (threadIdx.x == 0) { TL(29 + 2 * p); TC(114 + 2 * p); }
        if (threadIdx.x == 128) TL(53 + 2 * (p & 1));
        glu_panel<0, 32>(b256, b256, sb + OFF_STG + wg * 16384, BAR_SFULL(sb, wg * 2));
        glu_panel<64, 96>(b256, b256, sb + OFF_STG + wg * 16384 + 8192, BAR_SFULL(sb, wg * 2 + 1));
        if (threadIdx.x == 0) { TL(30 + 2 * p); TC(115 + 2 * p); }
        if (threadIdx.x == 128) TL(54 + 2 * (p & 1));
    }
}

__global__ void __launch_bounds__(384, 1)
fused_block_kernel(const __grid_constant__ Ptrs pt, const __grid_constant__ Maps mp) {
    uint32_t* const g_flags = pt.mail->flags;
    uint2* const g_mod = pt.mail->mod;
    uint4* const g_st1 = pt.mail->st1;
    uint32_t* const g_par2 = pt.mail->par2;
    uint4* const g_halo = pt.mail->halo;
    const __nv_bfloat16* __restrict__ cvec = pt.c;
    if (threadIdx.x == 224) { prefetch_map(&mp.wm8); prefetch_map(&mp.x); }
    extern __shared__ __align__(1024) uint8_t smem[];
    const uint32_t sb = smem_u32(smem);
    const uint32_t tid = threadIdx.x, tw = tid & 127, lane = tid & 31;
    const uint32_t warp = __shfl_sync(0xffffffffu, tid >> 5, 0), wg = warp >> 2;
    uint32_t rank; asm("mov.u32 %0, %%cluster_ctarank;" : "=r"(rank));
    rank = __shfl_sync(0xffffffffu, rank, 0);
    uint32_t ep;
    uint32_t smid; asm volatile("mov.u32 %0, %%smid;" : "=r"(smid));
    const int c = __shfl_sync(0xffffffffu, smid >> 1, 0);
    const int c7 = ((c - 32) * 37) >> 8;
    const int grp = c < 32 ? c & 7 : c < 60 ? c - 31 - 7 * c7 : c < 62 ? -1 : 0;
    const int j = c < 32 ? c >> 3 : c < 60 ? 4 + c7 : c < 62 ? (c - 60) * 2 + rank : c - 58;
    const bool aux = grp < 0;
    const int m = grp * 2 + rank;
    uint4* const g_st2 = g_halo + (m > 0 ? (m - 1) * 8 * 512 : 128);

    bool cluster_arrive_early = false;
    if (wg < 2) {
      if (!KDEBUG) cluster_arrive();
      ep = flag_get(g_flags + FL_DONE);
      uint16_t cw[8];
      {
          const __nv_bfloat16* cp = cvec + ((tw >> 5) * 32 + (tw & 3) * 2) * 8 + (lane >> 2);
#pragma unroll
          for (int i = 0; i < 8; ++i) asm volatile("ld.global.nc.u16 %0, [%1];" : "=h"(cw[i]) : "l"(cp + (i >> 1) * 64 + (i & 1) * 8));
      }
      asm volatile("setmaxnreg.inc.sync.aligned.u32 224;");
      if (tid == 0) TL(58);
      if (KDEBUG) cluster_arrive();
      Ring r{0, 0};
      Stg stg{0, 0};
      if (aux) {
        if (wg == 0) {
            const uint4 cv = *(const uint4*)(cvec + tw * 8);
            sts128(sb + OFF_STG + (tw >> 3) * 1024 + (tw & 7) * 16, pack2(silu_(bf_lo(cv.x)), silu_(bf_hi(cv.x))), pack2(silu_(bf_lo(cv.y)), silu_(bf_hi(cv.y))),
                   pack2(silu_(bf_lo(cv.z)), silu_(bf_hi(cv.z))), pack2(silu_(bf_lo(cv.w)), silu_(bf_hi(cv.w))));
            fence_async_smem();
        }
        cluster_wait();
        ep = __shfl_sync(0xffffffffu, ep, 0) / NCTA + 1;
        if (wg == 0) {
            if (tw == 0) {
                uint32_t n = 0;
                while (ld_pkt16(pt.mail->mod1 + 256).z != ep) { SPIN_GUARD(n); __nanosleep(200); }
                if (GODLY) __nanosleep(GODLY);
                mbar_arrive(BAR_ONE(sb, EV_GO));
            }
            bar_sync(1, 128);
#pragma unroll 1
            for (int p = 0; p < 4; ++p) {
                float acc[128];
#pragma unroll
                for (int i = 0; i < 128; ++i) acc[i] = 0.f;
                uint32_t prev = 0;
#pragma unroll 1
                for (int kc = 0; kc < 16; ++kc) {
                    mbar_wait(BAR_FULL(sb, r.slot), r.par);
                    wg_fence();
#pragma unroll
                    for (int k = 0; k < 4; ++k)
                        wgmma_n256(acc, mk_desc(d16(sb) + kc * 64, OFF_STG + k * 32, 16, 0, 1), mk_desc(d16(sb) + r.slot * (SLOT >> 4), k * 2048, 8192, 1024, 1));
                    wg_commit();
                    wg_wait<1>();
                    if (kc > 0 && tw < 4) mbar_arrive(BAR_EMPTY(sb, prev));
                    prev = r.slot;
                    r.next();
                }
                wg_wait<0>();
                if (tw < 4) mbar_arrive(BAR_EMPTY(sb, prev));
                if (tw < 4) {
#pragma unroll
                    for (int jn = 0; jn < 32; ++jn) sts32(sb + OFF_TAB + (jn * 4 + tw) * 4, pack2(acc[jn * 4], acc[jn * 4 + 1]));
                }
                bar_sync(1, 128);
                const int vec = 2 + p, blk = p * 4 + j;
                const uint32_t val = lds32(sb + OFF_TAB + tw * 4);
                if (vec == 2 || vec == 5) st_pkt(g_mod + (8 + blk) * 128 + tw, val, ep);
                else {
                    const float one = vec == 4 ? 1.f : 0.f;
                    g_par2[((blk & 3) * 16 + (tw >> 3)) * 16 + (tw & 3) * 4 + (vec - 3) * 2 + ((tw >> 2) & 1)] =
                        pack2(0.5f * bf_round(one + bf_lo(val)), 0.5f * bf_round(one + bf_hi(val)));
                }
                bar_sync(1, 128);
                if (tw == 0) {
                    if (vec == 3 || vec == 4) asm volatile("red.release.gpu.global.add.u32 [%0], 1;" :: "l"(&g_flags[FL_LN2]) : "memory");
                    TL(1 + p);
                }
            }
            if (lane < 2) mbar_arrive_cta(BAR_ONE(sb, EV_P0), lane);
        }
        r = Ring{64 % NSLOT, (64 / NSLOT) & 1};
        mbar_wait(BAR_ONE(sb, EV_P0), 0);
        passes128<4>(sb, wg, tw, r, stg);
      } else {
        float xs[64];
        uint32_t xp[32];
        {
            IDX();
            if (q4 < 2) st_pkt16(g_st1 + (m * 8 + j) * 512 + wg * 64 + w4 * 16 + g8 + q4 * 8, 0, 0, 0, 0);
            if (warp == 0) st_pkt16(pt.mail->mod1 + g8 * 512 + (m * 8 + j) * 4 + q4, 0, 0, 0, 0);
            sts128(sb + tid * 16, pack2(silu_(bf_lo(cw[0])), silu_(bf_lo(cw[1]))), pack2(silu_(bf_lo(cw[2])), silu_(bf_lo(cw[3]))),
                   pack2(silu_(bf_lo(cw[4])), silu_(bf_lo(cw[5]))), pack2(silu_(bf_lo(cw[6])), silu_(bf_lo(cw[7]))));
            cluster_wait();
            ep = __shfl_sync(0xffffffffu, ep, 0) / NCTA + 1;
            load_slab(xp, stg.acquire2(sb, wg));
            unpack_slab(xs, xp);
            if (tid == 0) TL(24);
            if (tid == 128) TL(27);
        }
#pragma unroll 1
        for (int blk = 0; ; ++blk) {
        {
            IDX();
            uint4* const st = (blk ? g_st2 : g_st1 + m * 8 * 512) + wg * 64 + w4 * 16 + g8;
            RowAcc ra;
#pragma unroll
            for (int e = 0; e < 64; ++e) ra.add(e, xs[e]);
            ra.publish(st + j * 512, q4, ep);
            uint32_t t_pub = 0; if (PDLY) asm volatile("mov.u32 %0, %%clock;" : "=r"(t_pub));
            if (tid == 0) TL(blk ? 9 : 26);
            if (tid == 128 && blk) TL(34);
            if (blk) CS(11);
            LnPar lp;
            if (blk == 0) {
            uint4* const mod_out = pt.mail->mod1 + g8 * 512 + (m * 8 + j) * 4 + q4;
            if (wg == 0) {
                uint4 af[8];
#pragma unroll
                for (int i = 0; i < 8; ++i) af[i] = lds128(sb + w4 * 512 + i * 64 + q4 * 16);
                float c[4][4] = {};
#pragma unroll
                for (int i = 0; i < 8; ++i) {
                    if (!(i & 1)) mbar_wait(BAR_ONE(sb, EV_WIN + (i >> 1)), 0);
                    if (i == 6 && tid == 0) TL(25);
#pragma unroll
                    for (int h = 0; h < 2; ++h) {
                        uint32_t b0, b1, b2, b3;
                        ldsm4t(sb + 5 * SLOT + i * 4096 + w4 * 1024 + h * 512 + (lane & 15) * 32 + (lane >> 4) * 16, b0, b1, b2, b3);
                        mma16816(c[2 * h], h ? af[i].z : af[i].x, 0u, h ? af[i].w : af[i].y, 0u, b0, b1);
                        mma16816(c[2 * h + 1], h ? af[i].z : af[i].x, 0u, h ? af[i].w : af[i].y, 0u, b2, b3);
                    }
                }
                if (lane < 4) sts128(sb + OFF_TAB + w4 * 64 + lane * 16, __float_as_uint(c[0][0] + c[2][0]), __float_as_uint(c[0][1] + c[2][1]),
                                     __float_as_uint(c[1][0] + c[3][0]), __float_as_uint(c[1][1] + c[3][1]));
                if (lane < 2) mbar_arrive_cta(BAR_ONE(sb, EV_P0), lane);
                bar_sync(1, 128);
                if (w4 == 0) {
                    float a[4] = {0.f, 0.f, 0.f, 0.f};
#pragma unroll
                    for (int i = 0; i < 4; ++i) {
                        const uint4 t = lds128(sb + OFF_TAB + i * 64 + q4 * 16);
                        a[0] += __uint_as_float(t.x); a[1] += __uint_as_float(t.y); a[2] += __uint_as_float(t.z); a[3] += __uint_as_float(t.w);
                    }
                    const float add = m >= 8 ? 1.f : 0.f;
                    st_pkt16(mod_out, pack2(bf_round(a[0]) + add, bf_round(a[1]) + add), pack2(bf_round(a[2]) + add, bf_round(a[3]) + add), ep, 0);
                    if (tid == 0) TL(3);
                }
            } else if (LWAIT >= 0) mbar_wait(BAR_ONE(sb, EV_WIN + LWAIT), 0);
            } else {
                mbar_wait(BAR_ONE(sb, EV_LN2), 0);
            }
            lp.load(sb, q4);
#pragma unroll
            for (int e = 0; e < 32; ++e) xp[e] = pack2(xs[2 * e], xs[2 * e + 1]);
            if (PDLY && blk) { uint32_t t1; do { asm volatile("mov.u32 %0, %%clock;" : "=r"(t1)); } while (t1 - t_pub < PDLY); }
            if (blk) CS(13);
            const LnRow n = merge_stats(st, q4, ep, sb);
            if (tid == 0) TL(blk ? 49 : 48);
            if (tid == 128) TL(blk ? 45 : 28);
            if (blk) CS(18);
            uint32_t xn[32];
            ln_norm(xn, xs, n);
            if (blk == 0) { mbar_wait(BAR_ONE(sb, EV_PAR), 0); lp.load(sb, q4); }
            ln_emit(xn, lp, sb, wg, ix);
            if (tid == 0) { TL(blk ? 36 : 8); TC(blk ? 109 : 103); }
            if (tid == 128) TL(blk ? 43 : 22);
            if (blk) CS(21);
        }
        if (blk == 0) {
        {
            float kv[128], qa[64];
            mainloop32<true, LAGQ>(kv, qa, sb, wg, tw, r, EV_LAG0, 0, [&] { stg.acquire2(sb, wg); mbar_wait2(BAR_SREADY(sb, 2), BAR_SREADY(sb, 3), 1); });
            if (tid == 0) { TL(4); TC(104); }
            if (tid == 128) TL(50);
            CS(1);
            IDX();
            uint32_t k1[16], k2[16], v1[16], v2[16], qf[32];
#pragma unroll
            for (int i = 0; i < 8; ++i) qf[i] = pack2(qa[2 * i], qa[2 * i + 1]);
#pragma unroll
            for (int t = 0; t < 16; ++t) k2[t] = pack2(kv[4 * t + 2], kv[4 * t + 3]);
#pragma unroll
            for (int t = 0; t < 16; ++t) v2[t] = pack2(kv[64 + 4 * t + 2], kv[64 + 4 * t + 3]);
            const uint32_t nxt = warp + ((warp & 1) ? 3 : 1);
            if (nxt < 8) {
                const uint32_t dst = sb + OFF_STG + (nxt >> 2) * 16384 + (nxt & 3) * 2048 + lane * 16;
#pragma unroll
                for (int h = 0; h < 4; ++h) stsm4(dst + h * 512, k2[4 * h], k2[4 * h + 1], k2[4 * h + 2], k2[4 * h + 3]);
#pragma unroll
                for (int h = 0; h < 4; ++h) stsm4(dst + 8192 + h * 512, v2[4 * h], v2[4 * h + 1], v2[4 * h + 2], v2[4 * h + 3]);
                bar_arrive(NB_TAIL + nxt, 64);
            } else if (m < 15) {
                uint4* dst = g_halo + (m * 8 + j) * 512 + (w4 >> 1) * 256 + lane;
#pragma unroll
                for (int h = 0; h < 4; ++h) { if (!k2[4 * h]) k2[4 * h] = 0x8000u; if (!v2[4 * h]) v2[4 * h] = 0x8000u; }
#pragma unroll
                for (int h = 0; h < 4; ++h) st_pkt16(dst + h * 32, k2[4 * h], k2[4 * h + 1], k2[4 * h + 2], k2[4 * h + 3]);
#pragma unroll
                for (int h = 0; h < 4; ++h) st_pkt16(dst + 128 + h * 32, v2[4 * h], v2[4 * h + 1], v2[4 * h + 2], v2[4 * h + 3]);
            }
#pragma unroll
            for (int t = 0; t < 16; ++t) { k1[t] = pack2(kv[4 * t], kv[4 * t + 1]); v1[t] = pack2(kv[64 + 4 * t], kv[64 + 4 * t + 1]); }
#pragma unroll
            for (int i = 8; i < 32; ++i) qf[i] = pack2(qa[2 * i], qa[2 * i + 1]);
#pragma unroll
            for (int t = 0; t < 16; ++t) { v1[t] = movm(v1[t]); v2[t] = movm(v2[t]); }
            if (tid == 0) TL(33);
            CS(2);
            SCHED_FENCE(0);
            float s[4][3][4];
            auto qk = [&](float (&c)[4], int h, const uint32_t* k) {
                c[0] = c[1] = c[2] = c[3] = 0.f;
                mma16816(c, qf[h * 8], qf[h * 8 + 1], qf[h * 8 + 2], qf[h * 8 + 3], k[0], k[1]);
                mma16816(c, qf[h * 8 + 4], qf[h * 8 + 5], qf[h * 8 + 6], qf[h * 8 + 7], k[2], k[3]);
            };
#pragma unroll
            for (int h = 0; h < 4; ++h) { qk(s[h][1], h, k1 + 4 * h); qk(s[h][2], h, k2 + 4 * h); }
            CS(3);
            bar_sync(NB_TAIL + warp, 64);
            CS(4);
            if (tid == 0) TL(5);
            uint32_t k0[16], v0[16];
            const uint32_t mine = sb + OFF_STG + wg * 16384 + w4 * 2048;
#pragma unroll
            for (int h = 0; h < 4; ++h) ldsm4(mine + lane * 16 + h * 512, k0[4 * h], k0[4 * h + 1], k0[4 * h + 2], k0[4 * h + 3]);
#pragma unroll
            for (int h = 0; h < 4; ++h) ldsm4t(mine + lane * 16 + 8192 + h * 512, v0[4 * h], v0[4 * h + 1], v0[4 * h + 2], v0[4 * h + 3]);
#pragma unroll
            for (int h = 0; h < 4; ++h) qk(s[h][0], h, k0 + 4 * h);
            const bool lo0 = q4 * 2 > g8, lo1 = q4 * 2 + 1 > g8;
            const bool nopast = m == 0 && (warp & 5) == 0;
            const uint32_t lomask = (lo0 ? 0xFFFFu : 0u) | (lo1 ? 0xFFFF0000u : 0u);
            const float sl2 = 0.17677669529663687f * 1.4426950408889634f;
            float e0[8], e1[8], mx[8], sum[8], tt[8];
#pragma unroll
            for (int u = 0; u < 8; ++u) {
                const int h = u >> 1, hf = u & 1;
                e0[u] = lo0 ? ((hf == 0 && nopast) ? -INFINITY : s[h][hf][hf * 2]) : s[h][hf + 1][hf * 2];
                e1[u] = lo1 ? ((hf == 0 && nopast) ? -INFINITY : s[h][hf][hf * 2 + 1]) : s[h][hf + 1][hf * 2 + 1];
                mx[u] = fmaxf(e0[u], e1[u]);
                tt[u] = __shfl_xor_sync(0xffffffffu, mx[u], 1);
            }
            SCHED_FENCE(1);
#pragma unroll
            for (int u = 0; u < 8; ++u) { mx[u] = fmaxf(mx[u], tt[u]); tt[u] = __shfl_xor_sync(0xffffffffu, mx[u], 2); }
            SCHED_FENCE(2);
#pragma unroll
            for (int u = 0; u < 8; ++u) {
                const float c = -fmaxf(mx[u], tt[u]) * sl2;
                e0[u] = ex2(fmaf(e0[u], sl2, c)); e1[u] = ex2(fmaf(e1[u], sl2, c));
            }
            SCHED_FENCE(3);
#pragma unroll
            for (int u = 0; u < 8; ++u) { sum[u] = e0[u] + e1[u]; tt[u] = __shfl_xor_sync(0xffffffffu, sum[u], 1); }
            SCHED_FENCE(4);
#pragma unroll
            for (int u = 0; u < 8; ++u) { sum[u] += tt[u]; tt[u] = __shfl_xor_sync(0xffffffffu, sum[u], 2); }
            SCHED_FENCE(5);
#pragma unroll
            for (int u = 0; u < 8; ++u) sum[u] = rcp(sum[u] + tt[u]);
            SCHED_FENCE(6);
            CS(5);
            float o[8][2][4];
#pragma unroll
            for (int u = 0; u < 8; ++u) {
                const int h = u >> 1;
                const uint32_t p = pack2(e0[u] * sum[u], e1[u] * sum[u]);
                const uint32_t* va = ((u & 1) ? v1 : v0) + 4 * h;
                const uint32_t* vb = ((u & 1) ? v2 : v1) + 4 * h;
#pragma unroll
                for (int d = 0; d < 2; ++d) {
                    o[u][d][0] = o[u][d][1] = o[u][d][2] = o[u][d][3] = 0.f;
                    mma16816(o[u][d], va[2 * d], va[2 * d + 1], vb[2 * d], vb[2 * d + 1], p & lomask, p & ~lomask);
                }
            }
            SCHED_FENCE(7);
            const uint32_t orow = mine + (lane & 7) * 128 + (((lane >> 3) ^ (lane & 7)) << 4);
#pragma unroll
            for (int u = 0; u < 8; ++u)
                stsm4t((orow ^ (((u >> 1) & 1) << 6)) + (u >> 2) * 8192 + (u & 1) * 1024, pack2(o[u][0][0], o[u][0][1]), pack2(o[u][0][2], o[u][0][3]),
                       pack2(o[u][1][0], o[u][1][1]), pack2(o[u][1][2], o[u][1][3]));
            fence_async_smem();
            __syncwarp();
            if (lane < 2) mbar_arrive(BAR_SFULL(sb, wg * 2 + lane));
            CS(6);
            if (tid == 32) TL(41);
            bar_sync(1 + wg, 128);
            if (tid == 0) { TL(6); TC(106); }
            if (tid == 128) TL(44);
            CS(7);
#pragma unroll
            for (int e = 0; e < 32; ++e) xp[e] = qf[e];
        }
        } else {
        {
            float ag[88], au[88];
            mainloop32<true, LAG>(ag, au, sb, wg, tw, r, EV_LAG1, 48, [&] {
                stg.acquire2(sb, wg);
                Ring q = r; if (!wg) q.next();
                mbar_wait(BAR_EMPTY(sb, q.slot), q.par ^ 1);
            });
            if (tid == 0) { TL(10); TC(110); }
            if (tid == 128) TL(51);
            glu_panel<0, 0>(ag, au, sb + OFF_STG + wg * 16384, BAR_SFULL(sb, wg * 2));
            glu_panel<32, 32>(ag, au, sb + OFF_STG + wg * 16384 + 8192, BAR_SFULL(sb, wg * 2 + 1));
            glu_panel<64, 64>(ag, au, sb + (wg ? P3_SLOT1 : P3_SLOT0) * SLOT + 24576, BAR_ONE(sb, EV_P3 + wg));
            if (tid == 0) { TL(11); TC(111); }
            if (tid == 128) TL(52);
        }
        passes128<2>(sb, wg, tw, r, stg);
        if (tid == 0) { TL(12); TC(112); }
        }
        {
            float acc[64], gf[32];
            mainloop64(acc, blk == 0, sb, wg, tw, r, [&] {
                mbar_wait(BAR_ONE(sb, EV_GA + blk), 0);
                const uint32_t buf = stg.acquire2(sb, wg);
                if (blk == 0) load_slab(xp, buf);
                unpack_slab(xs, xp);
                uint32_t gt[16];
#pragma unroll
                for (int cg = 0; cg < 16; ++cg) gt[cg] = lds32(sb + OFF_TAB + blk * 256 + cg * 16 + (tw & 3) * 4);
#pragma unroll
                for (int i = 0; i < 16; ++i) unpack2(gt[i], gf[2 * i], gf[2 * i + 1]);
            });
            if (tid == 0) { TL(blk ? 13 : 7); TC(blk ? 113 : 107); }
            if (tid == 128) TL(blk ? 57 : 42);
            if (!blk) CS(10);
#pragma unroll
            for (int e = 0; e < 64; ++e) xs[e] = fmaf(gf[(e >> 2) * 2 + (e & 1)], acc[e], xs[e]);
        }
        if (blk) break;
        }
        cluster_arrive();
        {
            IDX();
#pragma unroll
            for (int p = 0; p < 2; ++p) {
                store_slab(xs, sb + OFF_STG + wg * 16384, 8192, pan_addr, 4 * p, 4 * p + 4);
                stg.publish(sb, wg, lane);
            }
            if (tid == 0) TL(14);
        }
      }
    } else {
        if (warp == 8 && !aux && elect_one()) {
#pragma unroll
            for (int i = 0; i < 4; ++i) mbar_init(BAR_SREADY(sb, i), 1);
#pragma unroll
            for (int i = 0; i < 4; ++i) mbar_init(BAR_ONE(sb, EV_WIN + i), 1);
#pragma unroll
            for (int i = 0; i < 4; ++i) {
                mbar_expect_tx(BAR_SREADY(sb, i), 8192);
                tma_load3(sb + OFF_STG + i * 8192, &mp.x, j * 128 + (i & 1) * 64, m * 64 + (i >> 1) * 32, BAR_SREADY(sb, i));
            }
#pragma unroll 1
            for (int i = 0; i < 4; ++i) {
                mbar_expect_tx(BAR_ONE(sb, EV_WIN + i), 8192);
                tma_load(sb + 5 * SLOT + i * 8192, &mp.wm8, 2 * i * 6144 + (m * 8 + j) * 16, 0, BAR_ONE(sb, EV_WIN + i));
                tma_load(sb + 5 * SLOT + i * 8192 + 4096, &mp.wm8, (2 * i + 1) * 6144 + (m * 8 + j) * 16, 0, BAR_ONE(sb, EV_WIN + i));
            }
        }
        __syncwarp();
        asm volatile("setmaxnreg.dec.sync.aligned.u32 56;");
        if (elect_one()) {
            if (warp == 8) {
                prefetch_map(&mp.wqkv); prefetch_map(&mp.wmod);
            } else if (warp < 11) {
                mbar_init(BAR_EMPTY(sb, NSLOT), 1);
#pragma unroll
                for (int i = 0; i < 2; ++i) { mbar_init(BAR_SFULL(sb, (warp - 9) * 2 + i), 4); if (aux) mbar_init(BAR_SREADY(sb, (warp - 9) * 2 + i), 1); }
#pragma unroll
                for (int i = 0; i < 3; ++i) {
                    mbar_init(BAR_EMPTY(sb, (warp - 9) * 3 + i), 4);
                    mbar_init(BAR_FULL(sb, (warp - 9) * 3 + i), 1); mbar_init(BAR_FULL(sb, (warp - 9) * 3 + i) + AF_REL, 1);
                }
            } else {
#pragma unroll
                for (int i = EV_P0; i < EV_COUNT; ++i) mbar_init(BAR_ONE(sb, i), i == EV_P0 ? 8 : (i == EV_P3 || i == EV_P31) ? 4 : 1);
            }
            asm volatile("fence.mbarrier_init.release.cluster;" ::: "memory");
        }
        __syncwarp();
        cluster_arrive();
        ep = 0;
        if (warp != 8 || aux) ep = flag_get(g_flags + FL_DONE);
        cluster_wait();
        ep = __shfl_sync(0xffffffffu, ep, 0) / NCTA + 1;
        if (warp == 8) {
            const bool el = elect_one();
            Ring r{0, 1};
            if (aux) {
                mbar_wait(BAR_ONE(sb, EV_GO), 0);
#pragma unroll 1
                for (int it = 0; it < 64; ++it) {
                    const int col = 2048 + (it >> 4) * 1024 + j * 256;
                    mbar_wait(BAR_EMPTY(sb, r.slot), r.par);
                    const uint32_t st = sb + r.slot * SLOT, fb = BAR_FULL(sb, r.slot);
                    if (el) {
                        mbar_expect_tx(fb, 32768);
#pragma unroll
                        for (int b = 0; b < 4; ++b) tma_load(st + b * 8192, &mp.wmod, col + b * 64, (it & 15) * 64, fb);
                    }
                    r.next();
                }
                mbar_wait(BAR_ONE(sb, EV_P0), 0);
                const CUtensorMap* wm = rank ? &mp.wu : &mp.wg;
#pragma unroll 1
                for (int g = 0; g < 128; ++g) {
                    const int mx = (j >> 1) * 8 + (g >> 5) * 2 + rank, k0 = (g & 31) * 32;
                    if (k0 == 0) {
                        uint32_t n = 0;
                        while (!__all_sync(0xffffffffu, (int32_t)(flag_get(g_flags + FL_PROG + (mx * 32 + lane) * FS) - (ep * 8 + ST_H2)) >= 0)) { SPIN_GUARD(n); __nanosleep(500); }
                    }
                    mbar_wait(BAR_EMPTY(sb, r.slot), r.par);
                    const uint32_t st = sb + r.slot * SLOT, fb = BAR_FULL(sb, r.slot);
                    if (el) {
                        mbar_expect_tx(fb, 24576);
                        tma_load_mc(st + 8192 + rank * 4096, wm, HC3, k0, fb);
                        tma_load_mc(st + 16384 + rank * 4096, wm, HC3 + 64, k0, fb);
                        tma_load(st, &mp.h2l, k0, mx * 128, fb);
                    }
                    r.next();
                }
            } else {
#pragma unroll 1
                for (int it = 0; it < 32; ++it) {
                    const int cb = j * 128 + rank * 64, k0 = kof(it, 2, j);
                    if (it == BW0) mbar_wait(BAR_ONE(sb, BWEV), 0);
                    if (it == BW1) mbar_wait(BAR_ONE(sb, EV_PAR), 0);
                    if (it == 5) mbar_wait(BAR_ONE(sb, EV_P0), 0);
                    if ((AGO & 1) && it == 6) mbar_wait(BAR_ONE(sb, EV_AGO), 0);
                    mbar_wait(BAR_EMPTY(sb, r.slot), r.par);
                    const uint32_t st = sb + r.slot * SLOT, fb = BAR_FULL(sb, r.slot);
                    if (el) {
                        mbar_expect_tx(fb, it < 4 ? 24576 : 28672);
                        tma_load_mc(st + 8192 + rank * 4096, &mp.wqkv, 1024 + cb, k0, fb);
                        tma_load_mc(st + 16384 + rank * 4096, &mp.wqkv, 2048 + cb, k0, fb);
                        tma_load_mc(st + 24576 + rank * 4096, &mp.wqkv, cb, k0, fb);
                        if (it < 4) mbar_arrive(fb + AF_REL);
                        if (it == PFWO + (m >> 1)) { tma_prefetch(&mp.wo, j * 128, m * 64); tma_prefetch(&mp.wo, j * 128 + 64, m * 64); }
                    }
                    r.next();
                }
                if (el) mbar_arrive(BAR_ONE(sb, EV_KV));
#pragma unroll 1
                for (int it = 0; it < 16; ++it) {
                    if ((AGO & 2) && it == 6) mbar_wait(BAR_ONE(sb, EV_AGO1), 0);
                    mbar_wait(BAR_EMPTY(sb, r.slot), r.par);
                    const uint32_t st = sb + r.slot * SLOT, fb = BAR_FULL(sb, r.slot);
                    if (el) {
                        mbar_expect_tx(fb, it < 2 ? 16384 : 24576);
                        tma_load_mc(st + 16384 + rank * 8192, &mp.wo, j * 128 + rank * 64, kof(it, 1, j), fb);
                        if (it < 2) mbar_arrive(fb + AF_REL);
                        if (it == 6) { prefetch_map(rank ? &mp.wu : &mp.wg); prefetch_map(rank ? &mp.wu3 : &mp.wg3); }
                    }
                    r.next();
                }
                const CUtensorMap* wm = rank ? &mp.wu : &mp.wg;
#pragma unroll 1
                for (int g = 0; g < 96; ++g) {
                    if ((AGO & 4) && g == 6) mbar_wait(BAR_ONE(sb, EV_AGO2), 0);
                    const int p = g >> 5, cb = hcol(p, j), k0 = p == 0 ? kof(g, 2, j) : (g & 31) * 32;
                    mbar_wait(BAR_EMPTY(sb, r.slot), r.par);
                    const uint32_t st = sb + r.slot * SLOT, fb = BAR_FULL(sb, r.slot);
                    if (el) {
                        mbar_expect_tx(fb, (g < 4 || p > 0) ? 24576 : 28672);
                        tma_load_mc(st + 8192 + rank * 4096, wm, cb, k0, fb);
                        tma_load_mc(st + 16384 + rank * 4096, wm, cb + 64, k0, fb);
                        if (p == 0) tma_load3_mc(st + 24576 + rank * 4096, rank ? &mp.wu3 : &mp.wg3, j, k0, fb);
                        else tma_load(st, &mp.h2l, k0, m * 128, fb);
                        if (g < 4) mbar_arrive(fb + AF_REL);
                        if (g == 60) prefetch_map(&mp.wd);
                    }
                    r.next();
                }
#pragma unroll 1
                for (int g = 0; g < 56; ++g) {
                    if (g == 0 || (g & 15) == 6 && g > 6) mbar_wait(BAR_ONE(sb, EV_H0 + (g >> 4)), 0);
                    const int k0 = g * 64;
                    mbar_wait(BAR_EMPTY(sb, r.slot), r.par);
                    const uint32_t st = sb + r.slot * SLOT, fb = BAR_FULL(sb, r.slot);
                    if (el) {
                        mbar_expect_tx(fb, 32768);
                        tma_load_mc(st + 16384 + rank * 8192, &mp.wd, j * 128 + rank * 64, k0, fb);
                        tma_load(st, &mp.hb, k0, m * 128, fb); tma_load(st + 8192, &mp.hb, k0, m * 128 + 64, fb);
                    }
                    r.next();
                }
            }
        } else if (aux) {
            if (warp < 11) {
                const uint32_t w = warp - 9;
                const bool el = elect_one();
#pragma unroll 1
                for (int p = 0; p < 4; ++p) {
                    const int mx = (j >> 1) * 8 + p * 2 + rank;
                    if (el) { mbar_arrive(BAR_SREADY(sb, w * 2)); mbar_arrive(BAR_SREADY(sb, w * 2 + 1)); }
                    mbar_wait2(BAR_SFULL(sb, w * 2), BAR_SFULL(sb, w * 2 + 1), p & 1);
                    if (el) {
                        tma_store(&mp.hb, HC3, mx * 128 + w * 64, sb + OFF_STG + w * 16384); tma_store(&mp.hb, HC3 + 64, mx * 128 + w * 64, sb + OFF_STG + w * 16384 + 8192);
                        bulk_commit(); bulk_wait_all(); flag_set(g_flags + FL_AUX + mx * 2 + w, ep * 8 + ST_H + 3);
                    }
                }
            }
        } else if (warp == 11) {
            const bool el = elect_one();
            const int row0 = m * 128;
            const uint32_t* const fl = g_flags + FL_PROG + (m * 32 + (lane & 16) + (kof(lane & 15, 1, j) >> 6)) * FS;
            if (el) { prefetch_map(&mp.h1h); prefetch_map(&mp.h2h); prefetch_map(&mp.h2l); }
            {
                const uint4* pk = pt.mail->mod1 + grp * 512 + j * 32 + lane;
                uint4 a, b; uint32_t n = 0;
                mbar_wait(BAR_ONE(sb, EV_WIN3), 0);
                while (true) {
                    a = ld_pkt16(pk); b = ld_pkt16(pk + 256);
                    if (__all_sync(0xffffffffu, a.z == ep && b.z == ep)) break;
                    SPIN_GUARD(n);
                }
                sts128(sb + OFF_PAR + lane * 16, a.x, a.y, b.x, b.y);
                __syncwarp();
                if (lane == 0) { mbar_arrive(BAR_ONE(sb, EV_PAR)); TL(46); }
            }
            mbar_wait(BAR_ONE(sb, EV_P0), 0);
            Ring r{0, 1};
#pragma unroll 1
            for (int ph = 0; ph < 3; ++ph) {
                const int sh = ph == 1 ? 1 : 2, nst = 8 << sh;
                const uint32_t half = 16384 >> sh;
                const CUtensorMap* tm = ph == 0 ? &mp.h1h : ph == 1 ? &mp.o : &mp.h2h;
                if (ph == 1) fetch_halo(g_halo + ((m - 1) * 8 + j) * 512 + 256 + lane, m == 0, sb, 2, lane);
                const uint32_t target = ep * 8 + ST_H1 + ph;
                int a0 = 1 << sh, a1 = a0, fr = a0;
                r.skip(fr);
                uint32_t s0 = r.slot, s1 = r.slot, have = 0, n = 0;
                int k0 = j ? 0 : 128, k1 = k0;
#pragma unroll 1
                for (; fr < NSLOT; ++fr) { mbar_wait(BAR_EMPTY(sb, r.slot), r.par); r.next(); }
                uint32_t v = flag_get(fl);
                auto load = [&](int& a, uint32_t& sl, int& k, uint32_t w) {
                    const uint32_t fb = BAR_FULL(sb, sl) + (w ? 0 : AF_REL);
                    if (el) { if (!w) mbar_expect_tx(fb, half); tma_load(sb + sl * SLOT + w * half, tm, k, row0 + w * 64, fb); }
                    if (a == NSLOT - 1 && w == ((AGW >> ph) & 1) && el) mbar_arrive(BAR_ONE(sb, EV_AGO + ph));
                    ++a; if (++sl == NSLOT) sl = 0;
                    k = kof(a, sh, j);
                };
                do {
                    PS(0);
                    if (fr < 2 * NSLOT && mbar_test(BAR_EMPTY(sb, r.slot), r.par)) { ++fr; r.next(); }
                    SPIN_GUARD(n);
                    PS(1);
                    const bool ok = (int32_t)(v - target) >= 0;
                    v = flag_get(fl);
                    have = __ballot_sync(0xffffffffu, ok);
                    PS(2);
#pragma unroll 1
                    while (a1 < fr && (have & (0x10000u << (a1 >> (sh - 1))))) {
                        if (a1 == (1 << sh)) TL(16 + ph);
                        load(a1, s1, k1, 1);
                    }
                    PS(3);
#pragma unroll 1
                    while (a0 < fr && (have & (1u << (a0 >> (sh - 1))))) load(a0, s0, k0, 0);
                    PS(4);
                } while (have != 0xffffffffu);
#pragma unroll 1
                while (a0 < nst) {
                    mbar_wait(BAR_EMPTY(sb, r.slot), r.par);
                    r.next();
                    load(a1, s1, k1, 1); load(a0, s0, k0, 0);
                }
            }
#pragma unroll 1
            for (int p = 0; p < 4; ++p) {
                const uint32_t* f = p < 3 ? fl : g_flags + FL_AUX + m * 2 + (lane & 1);
                uint32_t n = 0;
                while (!__all_sync(0xffffffffu, (int32_t)(flag_get(f) - (ep * 8 + ST_H + p)) >= 0)) { SPIN_GUARD(n); __nanosleep(500); }
                if (el) mbar_arrive(BAR_ONE(sb, EV_H0 + p));
            }
        } else {
            const uint32_t w = warp - 9;
            const int row0 = m * 128 + w * 64;
            const uint32_t stg = sb + OFF_STG + w * 16384;
            uint32_t* const fl = g_flags + FL_PROG + (m * 32 + w * 16 + 2 * j) * FS;
            uint32_t b = 0, par = 0;
            const bool el = elect_one();
            auto store = [&](const CUtensorMap* tm, int col, bool nat = false) {
                mbar_wait(BAR_SFULL(sb, w * 2 + b), (par >> b) & 1);
                par ^= 1u << b;
                if (el) {
                    if (nat) tma_store3(tm, col, row0 >> 1, 0, stg + b * 8192); else tma_store(tm, col, row0, stg + b * 8192);
                    bulk_commit();
                }
                b ^= 1;
            };
            auto send2 = [&](const CUtensorMap* tm, int step) {
                store(tm, j * 128); store(tm, j * 128 + 64);
                if (el) {
                    asm volatile("cp.async.bulk.wait_group 1;" ::: "memory"); flag_set(fl, ep * 8 + step);
                    bulk_wait_all(); flag_set(fl + FS, ep * 8 + step);
                }
            };
            auto free2 = [&]() { if (el) { mbar_arrive(BAR_SREADY(sb, w * 2)); mbar_arrive(BAR_SREADY(sb, w * 2 + 1)); } };
            auto gate = [&](int vec, int ev) {
                uint4 v; uint32_t n = 0;
                while (true) {
                    v = ld_pkt2(g_mod + vec * 512 + j * 64 + lane * 2);
                    if (__all_sync(0xffffffffu, v.y == ep && v.w == ep)) break;
                    SPIN_GUARD(n); __nanosleep(300);
                }
                asm volatile("st.shared.v2.u32 [%0], {%1, %2};" :: "r"(sb + OFF_TAB + (ev - EV_GA) * 256 + lane * 8), "r"(v.x), "r"(v.z) : "memory");
                __syncwarp();
                if (lane == 0) mbar_arrive(BAR_ONE(sb, ev));
            };
            if (el) { prefetch_map(&mp.h1s); prefetch_map(&mp.o); prefetch_map(&mp.h2s); prefetch_map(&mp.hb); prefetch_map(&mp.out); prefetch_map(&mp.wo); }
            if (el) { flag_set(fl, ep * 8); flag_set(fl + FS, ep * 8); }
            send2(&mp.h1s, ST_H1);
            if (w == 0) TL(47);
            free2();
            if (w == 0) fetch_halo(g_halo + ((m - 1) * 8 + j) * 512 + lane, m == 0, sb, 0, lane);
            else { mbar_wait(BAR_ONE(sb, EV_KV), 0); gate(2, EV_GA); }
            send2(&mp.o, ST_O);
            if (w == 0) TL(40); else TL(38);
            mbar_wait(BAR_ONE(sb, EV_OWN + w), 0);
            if (el) {
#pragma unroll
                for (uint32_t i = 0; i < 2; ++i) {
                    mbar_expect_tx(BAR_SREADY(sb, w * 2 + i), 8192);
                    tma_load3(stg + i * 8192, &mp.x, j * 128 + i * 64, row0 >> 1, BAR_SREADY(sb, w * 2 + i));
                }
            }
            if (w == 1) {
                uint32_t n = 0;
                while ((int32_t)(flag_get(g_flags + FL_LN2) - ep * 8) < 0) { SPIN_GUARD(n); __nanosleep(200); }
                const uint4 v = __ldcg((const uint4*)(g_par2 + j * 128) + lane);
                sts128(sb + OFF_PAR + lane * 16, v.x, v.y, v.z, v.w);
                __syncwarp();
                if (lane == 0) mbar_arrive(BAR_ONE(sb, EV_LN2));
            }
            send2(&mp.h2s, ST_H2);
            if (el) { prefetch_map(&mp.hb); prefetch_map(&mp.hb3); }
            if (w == 0) TL(37);
            free2();
#pragma unroll 1
            for (int p = 0; p < 3; ++p) {
                const int col = hcol(p, j);
                mbar_wait(BAR_SFULL(sb, w * 2), par & 1);
                pause(w ? HD1 : HD0); store(&mp.hb, col);
                pause(HP); store(&mp.hb, col + 64);
                if (p == 0) {
                    pause(HP);
                    mbar_wait(BAR_ONE(sb, EV_P3 + w), 0);
                    if (el) { tma_store3(&mp.hb3, 0, j, row0, sb + (w ? P3_SLOT1 : P3_SLOT0) * SLOT + 24576); bulk_commit(); }
                }
                if (el) { bulk_wait_all(); flag_set(fl, ep * 8 + ST_H + p); flag_set(fl + FS, ep * 8 + ST_H + p); }
                free2();
                if (p == 0 && w == 1) gate(5, EV_GB);
            }
            cluster_arrive_early = true;
            cluster_arrive();
            store(&mp.out, j * 128, true); store(&mp.out, j * 128 + 64, true);
            if (el) bulk_wait_read();
        }
        __syncwarp();
    }
    if (aux || (wg == 2 && !cluster_arrive_early)) cluster_arrive();
    cluster_wait();
    if (tid == 0) {
        TL(15);
        flag_add(pt.mail->flags + FL_DONE);
    }
}

typedef CUresult (*EncodeFn)(CUtensorMap*, CUtensorMapDataType, cuuint32_t, void*, const cuuint64_t*, const cuuint64_t*, const cuuint32_t*,
                             const cuuint32_t*, CUtensorMapInterleave, CUtensorMapSwizzle, CUtensorMapL2promotion, CUtensorMapFloatOOBfill);

void make_map(EncodeFn fn, CUtensorMap* m, const void* ptr, uint64_t rows, uint64_t cols, uint32_t brows, uint32_t bcols) {
    cuuint64_t dims[2] = {cols, rows}, strides[1] = {cols * 2};
    cuuint32_t box[2] = {bcols, brows}, es[2] = {1, 1};
    fn(m, CU_TENSOR_MAP_DATA_TYPE_BFLOAT16, 2, (void*)ptr, dims, strides, box, es, CU_TENSOR_MAP_INTERLEAVE_NONE,
       bcols == 64 ? CU_TENSOR_MAP_SWIZZLE_128B : bcols == 32 ? CU_TENSOR_MAP_SWIZZLE_64B : CU_TENSOR_MAP_SWIZZLE_NONE, CU_TENSOR_MAP_L2_PROMOTION_L2_256B, CU_TENSOR_MAP_FLOAT_OOB_FILL_NONE);
}

void make_map3(EncodeFn fn, CUtensorMap* m, const void* ptr) {
    cuuint64_t dims[3] = {D_, S_ / 2, 2}, strides[2] = {4 * D_, 2 * D_};
    cuuint32_t box[3] = {64, 32, 2}, es[3] = {1, 1, 1};
    fn(m, CU_TENSOR_MAP_DATA_TYPE_BFLOAT16, 3, (void*)ptr, dims, strides, box, es, CU_TENSOR_MAP_INTERLEAVE_NONE,
       CU_TENSOR_MAP_SWIZZLE_128B, CU_TENSOR_MAP_L2_PROMOTION_L2_256B, CU_TENSOR_MAP_FLOAT_OOB_FILL_NONE);
}

void make_map48(EncodeFn fn, CUtensorMap* m, const void* ptr, uint64_t rows, uint32_t brows) {
    cuuint64_t dims[3] = {48, 8, rows}, strides[2] = {96, 2 * F_};
    cuuint32_t box[3] = {64, 1, brows}, es[3] = {1, 1, 1};
    fn(m, CU_TENSOR_MAP_DATA_TYPE_BFLOAT16, 3, (void*)ptr, dims, strides, box, es, CU_TENSOR_MAP_INTERLEAVE_NONE,
       CU_TENSOR_MAP_SWIZZLE_128B, CU_TENSOR_MAP_L2_PROMOTION_L2_256B, CU_TENSOR_MAP_FLOAT_OOB_FILL_NONE);
}

}

extern "C" void kernel_launch(void* const* d_in, const int* in_sizes, int n_in, void* d_out, int out_size) {
    (void)in_sizes; (void)n_in; (void)out_size;
    void* fnp = nullptr;
    cudaDriverEntryPointQueryResult qr;
    cudaGetDriverEntryPoint("cuTensorMapEncodeTiled", &fnp, cudaEnableDefault, &qr);
    EncodeFn fn = (EncodeFn)fnp;
    void *h1, *o, *h2, *hb, *mail;
    cudaGetSymbolAddress(&h1, g_h1);
    cudaGetSymbolAddress(&mail, g_mail);
    cudaGetSymbolAddress(&o, g_o);
    cudaGetSymbolAddress(&hb, g_hb);
    h2 = H2ALIAS;
    Maps mp;
    make_map(fn, &mp.h1h, h1, S_, D_, 64, 32);
    make_map(fn, &mp.h2h, h2, S_, D_, 64, 32);
    make_map(fn, &mp.h1s, h1, S_, D_, 64, 64);
    make_map(fn, &mp.o, o, S_, D_, 64, 64);
    make_map(fn, &mp.h2l, h2, S_, D_, 128, 32);
    make_map(fn, &mp.h2s, h2, S_, D_, 64, 64);
    make_map(fn, &mp.hb, hb, S_, F_, 64, 64);
    make_map(fn, &mp.wqkv, d_in[1], D_, 3 * D_, 32, 64);
    make_map(fn, &mp.wo, d_in[2], D_, D_, 64, 64);
    make_map(fn, &mp.wg, d_in[4], D_, F_, 32, 64);
    make_map(fn, &mp.wu, d_in[5], D_, F_, 32, 64);
    make_map(fn, &mp.wd, d_in[6], F_, D_, 64, 64);
    make_map(fn, &mp.wmod, d_in[8], D_, 6 * D_, 64, 64);
    make_map(fn, &mp.wm8, d_in[8], D_ / 8, 8 * 6 * D_, 128, 16);
    make_map3(fn, &mp.x, d_in[0]);
    make_map3(fn, &mp.out, d_out);
    make_map48(fn, &mp.wg3, d_in[4], D_, 32);
    make_map48(fn, &mp.wu3, d_in[5], D_, 32);
    make_map48(fn, &mp.hb3, hb, S_, 64);
    cudaFuncSetAttribute(fused_block_kernel, cudaFuncAttributeMaxDynamicSharedMemorySize, SMEM_BYTES);
    cudaLaunchConfig_t cfg = {};
    cfg.gridDim = dim3(NCTA); cfg.blockDim = dim3(384); cfg.dynamicSmemBytes = SMEM_BYTES; cfg.stream = cudaStreamPerThread;
    cudaLaunchAttribute at[1];
    at[0].id = cudaLaunchAttributeClusterDimension; at[0].val.clusterDim.x = 2; at[0].val.clusterDim.y = 1; at[0].val.clusterDim.z = 1;
    cfg.attrs = at; cfg.numAttrs = 1;
    const Ptrs pt{(const __nv_bfloat16*)d_in[7], (Mail*)mail};
    cudaLaunchKernelEx(&cfg, fused_block_kernel, pt, mp);
}
```

```cpp
#include <cuda_runtime.h>
#include <cuda_bf16.h>
#include <cuda.h>
#include <stdint.h>
#include <stddef.h>

#define LAG 3
#define LAGS 4
#define LAGW 3
#define LAGQ 4
#define MIDW 8
#define PFWO 14
#define FLAGRED 1
#define FS 1
#define P1H 2000
#define AGW 6
#define CSW 0
#define FENCES 1
#define LWAIT 2
#define BW0 0
#define BWEV EV_WIN
#define GODLY 0
#define BW1 3
#define PDLY 500
#define H2ALIAS o
#define HD1 6000
#define HD0 6000
#define HP 2200
#define LAGD 3
#define MIDD 44
#define KDEBUG 0

namespace {

constexpr int S_ = 2048, D_ = 1024, F_ = 3584;
constexpr int NCTA = 132;
constexpr int NSLOT = 6;
constexpr uint32_t SLOT = 32768;
constexpr uint32_t OFF_STG = NSLOT * SLOT;
constexpr uint32_t OFF_BAR = OFF_STG + 32768;
constexpr uint32_t OFF_PAR = OFF_BAR + 512;
constexpr uint32_t OFF_TAB = OFF_PAR + 768;
constexpr uint32_t OFF_TL = OFF_PAR + 2048;
constexpr uint32_t SMEM_BYTES = OFF_TL + (KDEBUG ? 512 : 0);
constexpr uint32_t P3_SLOT1 = (32 + 16 + 32) % NSLOT, P3_SLOT0 = (P3_SLOT1 + 1) % NSLOT;

constexpr int ST_H1 = 1, ST_O = 2, ST_H2 = 3, ST_H = 4, FL_DONE = 0, FL_LN2 = 1, FL_AUX = 32, FL_PROG = 64;

struct Maps {
    CUtensorMap h1h, h1s, o, h2h, h2l, h2s, hb, wqkv, wo, wg, wu, wd, wmod, wm8, x, out, wg3, wu3, hb3;
};

struct Mail {
    uint32_t flags[16 * 32 * FS + 64];
    uint2 mod[6 * D_ / 2];
    uint4 mod1[8 * 512];
    uint4 st1[128 * 512];
    uint32_t par2[D_];
    uint4 halo[128 * 512];
};
struct Ptrs { const __nv_bfloat16* c; Mail* mail; };

__device__ __align__(128) Mail g_mail;
__device__ __align__(128) __nv_bfloat16 g_h1[S_ * D_];
__device__ __align__(128) __nv_bfloat16 g_o[S_ * D_];
__device__ __align__(128) __nv_bfloat16 g_hb[S_ * F_];
#define TL(i) do {} while (0)
#define TC(i) do {} while (0)
#define TS(g, which) do {} while (0)
#define CS(i) do {} while (0)

#define PS(i) do {} while (0)
__device__ __forceinline__ uint32_t smem_u32(const void* p) { return (uint32_t)__cvta_generic_to_shared(p); }
__device__ __forceinline__ void mbar_init(uint32_t bar, uint32_t cnt) { asm volatile("mbarrier.init.shared::cta.b64 [%0], %1;" :: "r"(bar), "r"(cnt) : "memory"); }
__device__ __forceinline__ void mbar_expect_tx(uint32_t bar, uint32_t bytes) { asm volatile("mbarrier.arrive.expect_tx.shared::cta.b64 _, [%0], %1;" :: "r"(bar), "r"(bytes) : "memory"); }
__device__ __forceinline__ void mbar_arrive(uint32_t bar) { asm volatile("mbarrier.arrive.shared::cta.b64 _, [%0];" :: "r"(bar) : "memory"); }
__device__ __forceinline__ void mbar_arrive_cta(uint32_t bar, uint32_t cta) {
    asm volatile("{\n.reg .b32 r;\nmapa.shared::cluster.u32 r, %0, %1;\nmbarrier.arrive.shared::cluster.b64 _, [r];\n}" :: "r"(bar), "r"(cta) : "memory");
}
__device__ __forceinline__ void mbar_wait(uint32_t bar, uint32_t parity) {
    asm volatile("{\n.reg .pred p;\n.reg .u32 n;\nmov.u32 n, 0;\n"
        "W_LOOP:\nmbarrier.try_wait.parity.shared::cta.b64 p, [%0], %1;\n@p bra W_DONE;\n"
        "add.u32 n, n, 1;\nsetp.lt.u32 p, n, 0x400000;\n@p bra W_LOOP;\ntrap;\nW_DONE:\n}" :: "r"(bar), "r"(parity) : "memory");
}
__device__ __forceinline__ void mbar_wait2(uint32_t b0, uint32_t b1, uint32_t parity) {
    asm volatile("{\n.reg .pred p, q;\n.reg .u32 n;\nmov.u32 n, 0;\n"
        "W_LOOP:\nmbarrier.try_wait.parity.shared::cta.b64 p, [%0], %2;\nmbarrier.try_wait.parity.shared::cta.b64 q, [%1], %2;\nand.pred p, p, q;\n@p bra W_DONE;\n"
        "add.u32 n, n, 1;\nsetp.lt.u32 p, n, 0x400000;\n@p bra W_LOOP;\ntrap;\nW_DONE:\n}" :: "r"(b0), "r"(b1), "r"(parity) : "memory");
}
__device__ __forceinline__ bool mbar_test(uint32_t bar, uint32_t parity) {
    uint32_t r; asm volatile("{\n.reg .pred p;\nmbarrier.test_wait.parity.shared::cta.b64 p, [%1], %2;\nselp.u32 %0, 1, 0, p;\n}" : "=r"(r) : "r"(bar), "r"(parity) : "memory"); return r;
}
__device__ __forceinline__ bool mbar_test2(uint32_t b0, uint32_t b1, uint32_t parity) {
    uint32_t r;
    asm volatile("{\n.reg .pred p, q;\nmbarrier.test_wait.parity.shared::cta.b64 p, [%1], %3;\nmbarrier.test_wait.parity.shared::cta.b64 q, [%2], %3;\n"
        "and.pred p, p, q;\nselp.u32 %0, 1, 0, p;\n}" : "=r"(r) : "r"(b0), "r"(b1), "r"(parity) : "memory");
    return r;
}
__device__ __forceinline__ void tma_load3(uint32_t dst, const CUtensorMap* m, int c0, int c1, uint32_t bar) {
    asm volatile("cp.async.bulk.tensor.3d.shared::cluster.global.mbarrier::complete_tx::bytes [%0], [%1, {%3, %4, %5}], [%2];"
        :: "r"(dst), "l"(m), "r"(bar), "r"(c0), "r"(c1), "r"(0) : "memory");
}
__device__ __forceinline__ void tma_store3(const CUtensorMap* m, int c0, int c1, int c2, uint32_t src) {
    asm volatile("cp.async.bulk.tensor.3d.global.shared::cta.bulk_group [%0, {%2, %3, %4}], [%1];" :: "l"(m), "r"(src), "r"(c0), "r"(c1), "r"(c2) : "memory");
}
__device__ __forceinline__ void tma_load3_mc(uint32_t dst, const CUtensorMap* m, int c1, int c2, uint32_t bar) {
    asm volatile("cp.async.bulk.tensor.3d.shared::cluster.global.mbarrier::complete_tx::bytes.multicast::cluster.L2::cache_hint [%0], [%1, {%3, %4, %5}], [%2], %6, %7;"
        :: "r"(dst), "l"(m), "r"(bar), "r"(0), "r"(c1), "r"(c2), "h"((uint16_t)3), "l"(0x12F0000000000000ull) : "memory");
}
__device__ __forceinline__ void tma_load(uint32_t dst, const CUtensorMap* m, int c0, int c1, uint32_t bar) {
    asm volatile("cp.async.bulk.tensor.2d.shared::cluster.global.mbarrier::complete_tx::bytes [%0], [%1, {%3, %4}], [%2];"
        :: "r"(dst), "l"(m), "r"(bar), "r"(c0), "r"(c1) : "memory");
}
__device__ __forceinline__ void tma_load_mc(uint32_t dst, const CUtensorMap* m, int c0, int c1, uint32_t bar) {
    asm volatile("cp.async.bulk.tensor.2d.shared::cluster.global.mbarrier::complete_tx::bytes.multicast::cluster.L2::cache_hint [%0], [%1, {%3, %4}], [%2], %5, %6;"
        :: "r"(dst), "l"(m), "r"(bar), "r"(c0), "r"(c1), "h"((uint16_t)3), "l"(0x12F0000000000000ull) : "memory");
}
__device__ __forceinline__ void tma_prefetch(const CUtensorMap* m, int c0, int c1) {
    asm volatile("cp.async.bulk.prefetch.tensor.2d.L2.global [%0, {%1, %2}];" :: "l"(m), "r"(c0), "r"(c1) : "memory");
}
__device__ __forceinline__ void tma_store(const CUtensorMap* m, int c0, int c1, uint32_t src) {
    asm volatile("cp.async.bulk.tensor.2d.global.shared::cta.bulk_group [%0, {%2, %3}], [%1];" :: "l"(m), "r"(src), "r"(c0), "r"(c1) : "memory");
}
__device__ __forceinline__ void bulk_commit() { asm volatile("cp.async.bulk.commit_group;" ::: "memory"); }
__device__ __forceinline__ void bulk_wait_read() { asm volatile("cp.async.bulk.wait_group.read 0;" ::: "memory"); }
__device__ __forceinline__ void bulk_wait_all() { asm volatile("cp.async.bulk.wait_group 0;" ::: "memory"); }
__device__ __forceinline__ void fence_async_smem() { asm volatile("fence.proxy.async.shared::cta;" ::: "memory"); }
__device__ __forceinline__ void prefetch_map(const CUtensorMap* m) { asm volatile("prefetch.tensormap [%0];" :: "l"(m) : "memory"); }
__device__ __forceinline__ void wg_fence() { asm volatile("wgmma.fence.sync.aligned;" ::: "memory"); }
__device__ __forceinline__ void wg_commit() { asm volatile("wgmma.commit_group.sync.aligned;" ::: "memory"); }
template <int N> __device__ __forceinline__ void wg_wait() { asm volatile("wgmma.wait_group.sync.aligned %0;" :: "n"(N) : "memory"); }
__device__ __forceinline__ void bar_sync(int id, int n) { asm volatile("bar.sync %0, %1;" :: "r"(id), "r"(n) : "memory"); }
__device__ __forceinline__ void bar_arrive(int id, int n) { asm volatile("bar.arrive %0, %1;" :: "r"(id), "r"(n) : "memory"); }
__device__ __forceinline__ void flag_add(uint32_t* f) { asm volatile("red.relaxed.gpu.global.add.u32 [%0], 1;" :: "l"(f) : "memory"); }
__device__ __forceinline__ void flag_set(uint32_t* f, uint32_t v) { asm volatile("red.relaxed.gpu.global.max.u32 [%0], %1;" :: "l"(f), "r"(v) : "memory"); }
__device__ __forceinline__ uint32_t flag_get(const uint32_t* f) { uint32_t v; asm volatile("ld.relaxed.gpu.global.u32 %0, [%1];" : "=r"(v) : "l"(f) : "memory"); return v; }
__device__ __forceinline__ uint32_t d16(uint32_t addr) { return (addr & 0x3FFFF) >> 4; }
__device__ __forceinline__ uint64_t mk_desc(uint32_t a16, uint32_t off, uint32_t lbo, uint32_t sbo, uint32_t swz) {
    const uint32_t lo = a16 + (off >> 4) + ((lbo >> 4) << 16), hi = (sbo >> 4) | (swz << 30);
    return ((uint64_t)hi << 32) | lo;
}
__device__ __forceinline__ uint32_t pack2(float lo, float hi) {
    uint32_t r; asm("cvt.rn.bf16x2.f32 %0, %1, %2;" : "=r"(r) : "f"(hi), "f"(lo)); return r;
}
__device__ __forceinline__ uint32_t hfma2_bf16(uint32_t a, uint32_t b, uint32_t c) {
    uint32_t r; asm("fma.rn.bf16x2 %0, %1, %2, %3;" : "=r"(r) : "r"(a), "r"(b), "r"(c)); return r;
}
__device__ __forceinline__ float bf_lo(uint32_t v) { return __uint_as_float(v << 16); }
__device__ __forceinline__ float bf_hi(uint32_t v) { return __uint_as_float(v & 0xFFFF0000u); }
__device__ __forceinline__ void unpack2(uint32_t v, float& lo, float& hi) {
    asm volatile("shl.b32 %0, %2, 16;\nand.b32 %1, %2, 0xffff0000;" : "=f"(lo), "=f"(hi) : "r"(v));
}
__device__ __forceinline__ float bf_round(float x) { return __bfloat162float(__float2bfloat16_rn(x)); }
__device__ __forceinline__ void stsm4(uint32_t addr, uint32_t r0, uint32_t r1, uint32_t r2, uint32_t r3) {
    asm volatile("stmatrix.sync.aligned.m8n8.x4.shared.b16 [%0], {%1, %2, %3, %4};" :: "r"(addr), "r"(r0), "r"(r1), "r"(r2), "r"(r3) : "memory");
}
__device__ __forceinline__ void stsm4t(uint32_t addr, uint32_t r0, uint32_t r1, uint32_t r2, uint32_t r3) {
    asm volatile("stmatrix.sync.aligned.m8n8.x4.trans.shared.b16 [%0], {%1, %2, %3, %4};" :: "r"(addr), "r"(r0), "r"(r1), "r"(r2), "r"(r3) : "memory");
}
__device__ __forceinline__ uint32_t movm(uint32_t a) { uint32_t d; asm volatile("movmatrix.sync.aligned.m8n8.trans.b16 %0, %1;" : "=r"(d) : "r"(a)); return d; }
__device__ __forceinline__ void ldsm4(uint32_t addr, uint32_t& r0, uint32_t& r1, uint32_t& r2, uint32_t& r3) {
    asm volatile("ldmatrix.sync.aligned.m8n8.x4.shared.b16 {%0, %1, %2, %3}, [%4];" : "=r"(r0), "=r"(r1), "=r"(r2), "=r"(r3) : "r"(addr) : "memory");
}
__device__ __forceinline__ void ldsm4t(uint32_t addr, uint32_t& r0, uint32_t& r1, uint32_t& r2, uint32_t& r3) {
    asm volatile("ldmatrix.sync.aligned.m8n8.x4.trans.shared.b16 {%0, %1, %2, %3}, [%4];" : "=r"(r0), "=r"(r1), "=r"(r2), "=r"(r3) : "r"(addr) : "memory");
}
__device__ __forceinline__ void mma16816(float (&c)[4], uint32_t a0, uint32_t a1, uint32_t a2, uint32_t a3, uint32_t b0, uint32_t b1) {
    asm("mma.sync.aligned.m16n8k16.row.col.f32.bf16.bf16.f32 {%0, %1, %2, %3}, {%4, %5, %6, %7}, {%8, %9}, {%0, %1, %2, %3};"
        : "+f"(c[0]), "+f"(c[1]), "+f"(c[2]), "+f"(c[3]) : "r"(a0), "r"(a1), "r"(a2), "r"(a3), "r"(b0), "r"(b1));
}
__device__ __forceinline__ float rcp(float x) { float r; asm("rcp.approx.ftz.f32 %0, %1;" : "=f"(r) : "f"(x)); return r; }
__device__ __forceinline__ float ex2(float x) { float r; asm("ex2.approx.ftz.f32 %0, %1;" : "=f"(r) : "f"(x)); return r; }
__device__ __forceinline__ float glu_half(float gh, float uh) {
    float t; asm("tanh.approx.f32 %0, %1;" : "=f"(t) : "f"(gh)); return fmaf(t, uh, uh);
}
__device__ __forceinline__ float silu_(float x) { return __fdividef(x, 1.f + __expf(-x)); }
__device__ __forceinline__ void st_pkt(void* p, uint32_t a, uint32_t b) {
    asm volatile("{\n.reg .b64 t;\nmov.b64 t, {%1, %2};\nst.relaxed.gpu.global.b64 [%0], t;\n}" :: "l"(p), "r"(a), "r"(b) : "memory");
}
__device__ __forceinline__ uint4 ld_pkt2(const void* p) {
    uint4 v; asm volatile("{\n.reg .b64 t, u;\nld.relaxed.gpu.global.v2.b64 {t, u}, [%4];\nmov.b64 {%0, %1}, t;\nmov.b64 {%2, %3}, u;\n}"
        : "=r"(v.x), "=r"(v.y), "=r"(v.z), "=r"(v.w) : "l"(p) : "memory"); return v;
}
__device__ __forceinline__ void st_pkt16(void* p, uint32_t a, uint32_t b, uint32_t c, uint32_t d) {
    asm volatile("{\n.reg .b64 t, u;\n.reg .b128 w;\nmov.b64 t, {%1, %2};\nmov.b64 u, {%3, %4};\nmov.b128 w, {t, u};\nst.relaxed.gpu.global.b128 [%0], w;\n}"
        :: "l"(p), "r"(a), "r"(b), "r"(c), "r"(d) : "memory");
}
__device__ __forceinline__ uint4 ld_pkt16(const void* p) {
    uint4 v; asm volatile("{\n.reg .b64 t, u;\n.reg .b128 w;\nld.relaxed.gpu.global.b128 w, [%4];\nmov.b128 {t, u}, w;\nmov.b64 {%0, %1}, t;\nmov.b64 {%2, %3}, u;\n}"
        : "=r"(v.x), "=r"(v.y), "=r"(v.z), "=r"(v.w) : "l"(p) : "memory"); return v;
}
#define SPIN_GUARD(n) do { if (++(n) > (1u << 22)) asm volatile("trap;"); } while (0)
__device__ __forceinline__ uint4 lds128(uint32_t a) { uint4 v; asm volatile("ld.shared.v4.u32 {%0, %1, %2, %3}, [%4];" : "=r"(v.x), "=r"(v.y), "=r"(v.z), "=r"(v.w) : "r"(a) : "memory"); return v; }
__device__ __forceinline__ void sts128(uint32_t a, uint32_t x, uint32_t y, uint32_t z, uint32_t w) { asm volatile("st.shared.v4.u32 [%0], {%1, %2, %3, %4};" :: "r"(a), "r"(x), "r"(y), "r"(z), "r"(w) : "memory"); }
__device__ __forceinline__ uint32_t lds32(uint32_t a) { uint32_t v; asm volatile("ld.shared.u32 %0, [%1];" : "=r"(v) : "r"(a) : "memory"); return v; }
__device__ __forceinline__ void sts32(uint32_t a, uint32_t v) { asm volatile("st.shared.u32 [%0], %1;" :: "r"(a), "r"(v) : "memory"); }
__device__ __forceinline__ bool elect_one() {
    uint32_t p; asm volatile("{\n.reg .pred q;\nelect.sync _|q, 0xffffffff;\nselp.u32 %0, 1, 0, q;\n}" : "=r"(p)); return p;
}
__device__ __forceinline__ void pause(uint32_t cycles) {
    uint32_t t0, t; asm volatile("mov.u32 %0, %%clock;" : "=r"(t0));
    do { __nanosleep(64); asm volatile("mov.u32 %0, %%clock;" : "=r"(t)); } while (t - t0 < cycles);
}
__device__ __forceinline__ void cluster_arrive() { asm volatile("barrier.cluster.arrive.relaxed.aligned;" ::: "memory"); }
__device__ __forceinline__ void cluster_wait() { asm volatile("barrier.cluster.wait.aligned;" ::: "memory"); }

__device__ __forceinline__ void wgmma_n128_z(float (&d)[64], uint64_t da, uint64_t db) {
    asm volatile("{\n.reg .pred p;\nsetp.ne.b32 p, 0, 0;\n"
        "wgmma.mma_async.sync.aligned.m64n128k16.f32.bf16.bf16 {"
        "%0, %1, %2, %3, %4, %5, %6, %7, %8, %9, %10, %11, %12, %13, %14, %15, "
        "%16, %17, %18, %19, %20, %21, %22, %23, %24, %25, %26, %27, %28, %29, %30, %31, "
        "%32, %33, %34, %35, %36, %37, %38, %39, %40, %41, %42, %43, %44, %45, %46, %47, "
        "%48, %49, %50, %51, %52, %53, %54, %55, %56, %57, %58, %59, %60, %61, %62, %63"
        "}, %64, %65, p, 1, 1, 0, 1;\n}\n"
        : "=f"(d[0]), "=f"(d[1]), "=f"(d[2]), "=f"(d[3]), "=f"(d[4]), "=f"(d[5]), "=f"(d[6]), "=f"(d[7]),
          "=f"(d[8]), "=f"(d[9]), "=f"(d[10]), "=f"(d[11]), "=f"(d[12]), "=f"(d[13]), "=f"(d[14]), "=f"(d[15]),
          "=f"(d[16]), "=f"(d[17]), "=f"(d[18]), "=f"(d[19]), "=f"(d[20]), "=f"(d[21]), "=f"(d[22]), "=f"(d[23]),
          "=f"(d[24]), "=f"(d[25]), "=f"(d[26]), "=f"(d[27]), "=f"(d[28]), "=f"(d[29]), "=f"(d[30]), "=f"(d[31]),
          "=f"(d[32]), "=f"(d[33]), "=f"(d[34]), "=f"(d[35]), "=f"(d[36]), "=f"(d[37]), "=f"(d[38]), "=f"(d[39]),
          "=f"(d[40]), "=f"(d[41]), "=f"(d[42]), "=f"(d[43]), "=f"(d[44]), "=f"(d[45]), "=f"(d[46]), "=f"(d[47]),
          "=f"(d[48]), "=f"(d[49]), "=f"(d[50]), "=f"(d[51]), "=f"(d[52]), "=f"(d[53]), "=f"(d[54]), "=f"(d[55]),
          "=f"(d[56]), "=f"(d[57]), "=f"(d[58]), "=f"(d[59]), "=f"(d[60]), "=f"(d[61]), "=f"(d[62]), "=f"(d[63])
        : "l"(da), "l"(db));
}
__device__ __forceinline__ void wgmma_n128(float (&d)[64], uint64_t da, uint64_t db) {
    asm volatile("{\n.reg .pred p;\nsetp.eq.b32 p, 0, 0;\n"
        "wgmma.mma_async.sync.aligned.m64n128k16.f32.bf16.bf16 {"
        "%0, %1, %2, %3, %4, %5, %6, %7, %8, %9, %10, %11, %12, %13, %14, %15, "
        "%16, %17, %18, %19, %20, %21, %22, %23, %24, %25, %26, %27, %28, %29, %30, %31, "
        "%32, %33, %34, %35, %36, %37, %38, %39, %40, %41, %42, %43, %44, %45, %46, %47, "
        "%48, %49, %50, %51, %52, %53, %54, %55, %56, %57, %58, %59, %60, %61, %62, %63"
        "}, %64, %65, p, 1, 1, 0, 1;\n}\n"
        : "+f"(d[0]), "+f"(d[1]), "+f"(d[2]), "+f"(d[3]), "+f"(d[4]), "+f"(d[5]), "+f"(d[6]), "+f"(d[7]),
          "+f"(d[8]), "+f"(d[9]), "+f"(d[10]), "+f"(d[11]), "+f"(d[12]), "+f"(d[13]), "+f"(d[14]), "+f"(d[15]),
          "+f"(d[16]), "+f"(d[17]), "+f"(d[18]), "+f"(d[19]), "+f"(d[20]), "+f"(d[21]), "+f"(d[22]), "+f"(d[23]),
          "+f"(d[24]), "+f"(d[25]), "+f"(d[26]), "+f"(d[27]), "+f"(d[28]), "+f"(d[29]), "+f"(d[30]), "+f"(d[31]),
          "+f"(d[32]), "+f"(d[33]), "+f"(d[34]), "+f"(d[35]), "+f"(d[36]), "+f"(d[37]), "+f"(d[38]), "+f"(d[39]),
          "+f"(d[40]), "+f"(d[41]), "+f"(d[42]), "+f"(d[43]), "+f"(d[44]), "+f"(d[45]), "+f"(d[46]), "+f"(d[47]),
          "+f"(d[48]), "+f"(d[49]), "+f"(d[50]), "+f"(d[51]), "+f"(d[52]), "+f"(d[53]), "+f"(d[54]), "+f"(d[55]),
          "+f"(d[56]), "+f"(d[57]), "+f"(d[58]), "+f"(d[59]), "+f"(d[60]), "+f"(d[61]), "+f"(d[62]), "+f"(d[63])
        : "l"(da), "l"(db));
}
__device__ __forceinline__ void wgmma_n176_z(float (&d)[88], uint64_t da, uint64_t db) {
    asm volatile("{\n.reg .pred p;\nsetp.ne.b32 p, 0, 0;\n"
        "wgmma.mma_async.sync.aligned.m64n176k16.f32.bf16.bf16 {"
        "%0, %1, %2, %3, %4, %5, %6, %7, %8, %9, %10, %11, %12, %13, %14, %15, "
        "%16, %17, %18, %19, %20, %21, %22, %23, %24, %25, %26, %27, %28, %29, %30, %31, "
        "%32, %33, %34, %35, %36, %37, %38, %39, %40, %41, %42, %43, %44, %45, %46, %47, "
        "%48, %49, %50, %51, %52, %53, %54, %55, %56, %57, %58, %59, %60, %61, %62, %63, "
        "%64, %65, %66, %67, %68, %69, %70, %71, %72, %73, %74, %75, %76, %77, %78, %79, "
        "%80, %81, %82, %83, %84, %85, %86, %87"
        "}, %88, %89, p, 1, 1, 0, 1;\n}\n"
        : "=f"(d[0]), "=f"(d[1]), "=f"(d[2]), "=f"(d[3]), "=f"(d[4]), "=f"(d[5]), "=f"(d[6]), "=f"(d[7]),
          "=f"(d[8]), "=f"(d[9]), "=f"(d[10]), "=f"(d[11]), "=f"(d[12]), "=f"(d[13]), "=f"(d[14]), "=f"(d[15]),
          "=f"(d[16]), "=f"(d[17]), "=f"(d[18]), "=f"(d[19]), "=f"(d[20]), "=f"(d[21]), "=f"(d[22]), "=f"(d[23]),
          "=f"(d[24]), "=f"(d[25]), "=f"(d[26]), "=f"(d[27]), "=f"(d[28]), "=f"(d[29]), "=f"(d[30]), "=f"(d[31]),
          "=f"(d[32]), "=f"(d[33]), "=f"(d[34]), "=f"(d[35]), "=f"(d[36]), "=f"(d[37]), "=f"(d[38]), "=f"(d[39]),
          "=f"(d[40]), "=f"(d[41]), "=f"(d[42]), "=f"(d[43]), "=f"(d[44]), "=f"(d[45]), "=f"(d[46]), "=f"(d[47]),
          "=f"(d[48]), "=f"(d[49]), "=f"(d[50]), "=f"(d[51]), "=f"(d[52]), "=f"(d[53]), "=f"(d[54]), "=f"(d[55]),
          "=f"(d[56]), "=f"(d[57]), "=f"(d[58]), "=f"(d[59]), "=f"(d[60]), "=f"(d[61]), "=f"(d[62]), "=f"(d[63]),
          "=f"(d[64]), "=f"(d[65]), "=f"(d[66]), "=f"(d[67]), "=f"(d[68]), "=f"(d[69]), "=f"(d[70]), "=f"(d[71]),
          "=f"(d[72]), "=f"(d[73]), "=f"(d[74]), "=f"(d[75]), "=f"(d[76]), "=f"(d[77]), "=f"(d[78]), "=f"(d[79]),
          "=f"(d[80]), "=f"(d[81]), "=f"(d[82]), "=f"(d[83]), "=f"(d[84]), "=f"(d[85]), "=f"(d[86]), "=f"(d[87])
        : "l"(da), "l"(db));
}
__device__ __forceinline__ void wgmma_n176(float (&d)[88], uint64_t da, uint64_t db) {
    asm volatile("{\n.reg .pred p;\nsetp.eq.b32 p, 0, 0;\n"
        "wgmma.mma_async.sync.aligned.m64n176k16.f32.bf16.bf16 {"
        "%0, %1, %2, %3, %4, %5, %6, %7, %8, %9, %10, %11, %12, %13, %14, %15, "
        "%16, %17, %18, %19, %20, %21, %22, %23, %24, %25, %26, %27, %28, %29, %30, %31, "
        "%32, %33, %34, %35, %36, %37, %38, %39, %40, %41, %42, %43, %44, %45, %46, %47, "
        "%48, %49, %50, %51, %52, %53, %54, %55, %56, %57, %58, %59, %60, %61, %62, %63, "
        "%64, %65, %66, %67, %68, %69, %70, %71, %72, %73, %74, %75, %76, %77, %78, %79, "
        "%80, %81, %82, %83, %84, %85, %86, %87"
        "}, %88, %89, p, 1, 1, 0, 1;\n}\n"
        : "+f"(d[0]), "+f"(d[1]), "+f"(d[2]), "+f"(d[3]), "+f"(d[4]), "+f"(d[5]), "+f"(d[6]), "+f"(d[7]),
          "+f"(d[8]), "+f"(d[9]), "+f"(d[10]), "+f"(d[11]), "+f"(d[12]), "+f"(d[13]), "+f"(d[14]), "+f"(d[15]),
          "+f"(d[16]), "+f"(d[17]), "+f"(d[18]), "+f"(d[19]), "+f"(d[20]), "+f"(d[21]), "+f"(d[22]), "+f"(d[23]),
          "+f"(d[24]), "+f"(d[25]), "+f"(d[26]), "+f"(d[27]), "+f"(d[28]), "+f"(d[29]), "+f"(d[30]), "+f"(d[31]),
          "+f"(d[32]), "+f"(d[33]), "+f"(d[34]), "+f"(d[35]), "+f"(d[36]), "+f"(d[37]), "+f"(d[38]), "+f"(d[39]),
          "+f"(d[40]), "+f"(d[41]), "+f"(d[42]), "+f"(d[43]), "+f"(d[44]), "+f"(d[45]), "+f"(d[46]), "+f"(d[47]),
          "+f"(d[48]), "+f"(d[49]), "+f"(d[50]), "+f"(d[51]), "+f"(d[52]), "+f"(d[53]), "+f"(d[54]), "+f"(d[55]),
          "+f"(d[56]), "+f"(d[57]), "+f"(d[58]), "+f"(d[59]), "+f"(d[60]), "+f"(d[61]), "+f"(d[62]), "+f"(d[63]),
          "+f"(d[64]), "+f"(d[65]), "+f"(d[66]), "+f"(d[67]), "+f"(d[68]), "+f"(d[69]), "+f"(d[70]), "+f"(d[71]),
          "+f"(d[72]), "+f"(d[73]), "+f"(d[74]), "+f"(d[75]), "+f"(d[76]), "+f"(d[77]), "+f"(d[78]), "+f"(d[79]),
          "+f"(d[80]), "+f"(d[81]), "+f"(d[82]), "+f"(d[83]), "+f"(d[84]), "+f"(d[85]), "+f"(d[86]), "+f"(d[87])
        : "l"(da), "l"(db));
}
__device__ __forceinline__ void wgmma_n256_z(float (&d)[128], uint64_t da, uint64_t db) {
    asm volatile("{\n.reg .pred p;\nsetp.ne.b32 p, 0, 0;\n"
        "wgmma.mma_async.sync.aligned.m64n256k16.f32.bf16.bf16 {"
        "%0, %1, %2, %3, %4, %5, %6, %7, %8, %9, %10, %11, %12, %13, %14, %15, "
        "%16, %17, %18, %19, %20, %21, %22, %23, %24, %25, %26, %27, %28, %29, %30, %31, "
        "%32, %33, %34, %35, %36, %37, %38, %39, %40, %41, %42, %43, %44, %45, %46, %47, "
        "%48, %49, %50, %51, %52, %53, %54, %55, %56, %57, %58, %59, %60, %61, %62, %63, "
        "%64, %65, %66, %67, %68, %69, %70, %71, %72, %73, %74, %75, %76, %77, %78, %79, "
        "%80, %81, %82, %83, %84, %85, %86, %87, %88, %89, %90, %91, %92, %93, %94, %95, "
        "%96, %97, %98, %99, %100, %101, %102, %103, %104, %105, %106, %107, %108, %109, %110, %111, "
        "%112, %113, %114, %115, %116, %117, %118, %119, %120, %121, %122, %123, %124, %125, %126, %127"
        "}, %128, %129, p, 1, 1, 0, 1;\n}\n"
        : "=f"(d[0]), "=f"(d[1]), "=f"(d[2]), "=f"(d[3]), "=f"(d[4]), "=f"(d[5]), "=f"(d[6]), "=f"(d[7]),
          "=f"(d[8]), "=f"(d[9]), "=f"(d[10]), "=f"(d[11]), "=f"(d[12]), "=f"(d[13]), "=f"(d[14]), "=f"(d[15]),
          "=f"(d[16]), "=f"(d[17]), "=f"(d[18]), "=f"(d[19]), "=f"(d[20]), "=f"(d[21]), "=f"(d[22]), "=f"(d[23]),
          "=f"(d[24]), "=f"(d[25]), "=f"(d[26]), "=f"(d[27]), "=f"(d[28]), "=f"(d[29]), "=f"(d[30]), "=f"(d[31]),
          "=f"(d[32]), "=f"(d[33]), "=f"(d[34]), "=f"(d[35]), "=f"(d[36]), "=f"(d[37]), "=f"(d[38]), "=f"(d[39]),
          "=f"(d[40]), "=f"(d[41]), "=f"(d[42]), "=f"(d[43]), "=f"(d[44]), "=f"(d[45]), "=f"(d[46]), "=f"(d[47]),
          "=f"(d[48]), "=f"(d[49]), "=f"(d[50]), "=f"(d[51]), "=f"(d[52]), "=f"(d[53]), "=f"(d[54]), "=f"(d[55]),
          "=f"(d[56]), "=f"(d[57]), "=f"(d[58]), "=f"(d[59]), "=f"(d[60]), "=f"(d[61]), "=f"(d[62]), "=f"(d[63]),
          "=f"(d[64]), "=f"(d[65]), "=f"(d[66]), "=f"(d[67]), "=f"(d[68]), "=f"(d[69]), "=f"(d[70]), "=f"(d[71]),
          "=f"(d[72]), "=f"(d[73]), "=f"(d[74]), "=f"(d[75]), "=f"(d[76]), "=f"(d[77]), "=f"(d[78]), "=f"(d[79]),
          "=f"(d[80]), "=f"(d[81]), "=f"(d[82]), "=f"(d[83]), "=f"(d[84]), "=f"(d[85]), "=f"(d[86]), "=f"(d[87]),
          "=f"(d[88]), "=f"(d[89]), "=f"(d[90]), "=f"(d[91]), "=f"(d[92]), "=f"(d[93]), "=f"(d[94]), "=f"(d[95]),
          "=f"(d[96]), "=f"(d[97]), "=f"(d[98]), "=f"(d[99]), "=f"(d[100]), "=f"(d[101]), "=f"(d[102]), "=f"(d[103]),
          "=f"(d[104]), "=f"(d[105]), "=f"(d[106]), "=f"(d[107]), "=f"(d[108]), "=f"(d[109]), "=f"(d[110]), "=f"(d[111]),
          "=f"(d[112]), "=f"(d[113]), "=f"(d[114]), "=f"(d[115]), "=f"(d[116]), "=f"(d[117]), "=f"(d[118]), "=f"(d[119]),
          "=f"(d[120]), "=f"(d[121]), "=f"(d[122]), "=f"(d[123]), "=f"(d[124]), "=f"(d[125]), "=f"(d[126]), "=f"(d[127])
        : "l"(da), "l"(db));
}
__device__ __forceinline__ void wgmma_n256(float (&d)[128], uint64_t da, uint64_t db) {
    asm volatile("{\n.reg .pred p;\nsetp.eq.b32 p, 0, 0;\n"
        "wgmma.mma_async.sync.aligned.m64n256k16.f32.bf16.bf16 {"
        "%0, %1, %2, %3, %4, %5, %6, %7, %8, %9, %10, %11, %12, %13, %14, %15, "
        "%16, %17, %18, %19, %20, %21, %22, %23, %24, %25, %26, %27, %28, %29, %30, %31, "
        "%32, %33, %34, %35, %36, %37, %38, %39, %40, %41, %42, %43, %44, %45, %46, %47, "
        "%48, %49, %50, %51, %52, %53, %54, %55, %56, %57, %58, %59, %60, %61, %62, %63, "
        "%64, %65, %66, %67, %68, %69, %70, %71, %72, %73, %74, %75, %76, %77, %78, %79, "
        "%80, %81, %82, %83, %84, %85, %86, %87, %88, %89, %90, %91, %92, %93, %94, %95, "
        "%96, %97, %98, %99, %100, %101, %102, %103, %104, %105, %106, %107, %108, %109, %110, %111, "
        "%112, %113, %114, %115, %116, %117, %118, %119, %120, %121, %122, %123, %124, %125, %126, %127"
        "}, %128, %129, p, 1, 1, 0, 1;\n}\n"
        : "+f"(d[0]), "+f"(d[1]), "+f"(d[2]), "+f"(d[3]), "+f"(d[4]), "+f"(d[5]), "+f"(d[6]), "+f"(d[7]),
          "+f"(d[8]), "+f"(d[9]), "+f"(d[10]), "+f"(d[11]), "+f"(d[12]), "+f"(d[13]), "+f"(d[14]), "+f"(d[15]),
          "+f"(d[16]), "+f"(d[17]), "+f"(d[18]), "+f"(d[19]), "+f"(d[20]), "+f"(d[21]), "+f"(d[22]), "+f"(d[23]),
          "+f"(d[24]), "+f"(d[25]), "+f"(d[26]), "+f"(d[27]), "+f"(d[28]), "+f"(d[29]), "+f"(d[30]), "+f"(d[31]),
          "+f"(d[32]), "+f"(d[33]), "+f"(d[34]), "+f"(d[35]), "+f"(d[36]), "+f"(d[37]), "+f"(d[38]), "+f"(d[39]),
          "+f"(d[40]), "+f"(d[41]), "+f"(d[42]), "+f"(d[43]), "+f"(d[44]), "+f"(d[45]), "+f"(d[46]), "+f"(d[47]),
          "+f"(d[48]), "+f"(d[49]), "+f"(d[50]), "+f"(d[51]), "+f"(d[52]), "+f"(d[53]), "+f"(d[54]), "+f"(d[55]),
          "+f"(d[56]), "+f"(d[57]), "+f"(d[58]), "+f"(d[59]), "+f"(d[60]), "+f"(d[61]), "+f"(d[62]), "+f"(d[63]),
          "+f"(d[64]), "+f"(d[65]), "+f"(d[66]), "+f"(d[67]), "+f"(d[68]), "+f"(d[69]), "+f"(d[70]), "+f"(d[71]),
          "+f"(d[72]), "+f"(d[73]), "+f"(d[74]), "+f"(d[75]), "+f"(d[76]), "+f"(d[77]), "+f"(d[78]), "+f"(d[79]),
          "+f"(d[80]), "+f"(d[81]), "+f"(d[82]), "+f"(d[83]), "+f"(d[84]), "+f"(d[85]), "+f"(d[86]), "+f"(d[87]),
          "+f"(d[88]), "+f"(d[89]), "+f"(d[90]), "+f"(d[91]), "+f"(d[92]), "+f"(d[93]), "+f"(d[94]), "+f"(d[95]),
          "+f"(d[96]), "+f"(d[97]), "+f"(d[98]), "+f"(d[99]), "+f"(d[100]), "+f"(d[101]), "+f"(d[102]), "+f"(d[103]),
          "+f"(d[104]), "+f"(d[105]), "+f"(d[106]), "+f"(d[107]), "+f"(d[108]), "+f"(d[109]), "+f"(d[110]), "+f"(d[111]),
          "+f"(d[112]), "+f"(d[113]), "+f"(d[114]), "+f"(d[115]), "+f"(d[116]), "+f"(d[117]), "+f"(d[118]), "+f"(d[119]),
          "+f"(d[120]), "+f"(d[121]), "+f"(d[122]), "+f"(d[123]), "+f"(d[124]), "+f"(d[125]), "+f"(d[126]), "+f"(d[127])
        : "l"(da), "l"(db));
}

struct Idx {
    uint32_t lane, warp, w4, q4, g8, prow, pan;
    __device__ __forceinline__ Idx() {
        uint32_t t; asm volatile("mov.u32 %0, %%tid.x;" : "=r"(t));
        lane = t & 31; warp = t >> 5; w4 = warp & 3; q4 = lane & 3; g8 = lane >> 2;
        prow = w4 * 16 + ((lane >> 3) & 1) * 8 + (lane & 7);
        pan = prow * 128 + (((lane >> 4) ^ (lane & 7)) << 4);
    }
};
#define IDX() const Idx ix; const uint32_t lane = ix.lane, warp = ix.warp, w4 = ix.w4, q4 = ix.q4, g8 = ix.g8, prow = ix.prow, pan_addr = ix.pan; \
    (void)lane; (void)warp; (void)w4; (void)q4; (void)g8; (void)prow; (void)pan_addr;

__device__ __forceinline__ int kof(int t, int sh, int j) {
    const int p = t >> (sh - 1), pn = p < 2 ? p : p >= 9, q = p - 2 - 7 * pn;
    return ((p < 2 ? j : q + (q >= j)) << 7) + (pn << 6) + ((t & (sh - 1)) << 5);
}
constexpr int HC0 = 8 * 48, HC3 = HC0 + 3072;
__device__ __forceinline__ int hcol(int p, int j) { return HC0 + p * 1024 + j * 128; }
#define SCHED_FENCE(k) do { if ((FENCES >> (k)) & 1) asm volatile("{\n.reg .pred p;\nsetp.ne.u32 p, %0, %1;\n@p bra.uni S_SKIP;\ntrap;\nS_SKIP:\n}" :: "r"(sb), "n"(0xffffff00u + (k))); } while (0)

struct Ring {
    uint32_t slot, par;
    __device__ __forceinline__ void next() { if (++slot == NSLOT) { slot = 0; par ^= 1; } }
    __device__ __forceinline__ void skip(uint32_t n) { slot += n; if (slot >= NSLOT) { slot -= NSLOT; par ^= 1; } }
};
__device__ __forceinline__ uint32_t BAR_FULL(uint32_t sb, uint32_t s) { return sb + OFF_BAR + 8 * s; }
constexpr uint32_t AF_REL = 48;
__device__ __forceinline__ uint32_t BAR_EMPTY(uint32_t sb, uint32_t s) { return sb + OFF_BAR + 96 + 8 * s; }
__device__ __forceinline__ uint32_t BAR_SFULL(uint32_t sb, uint32_t i) { return sb + OFF_BAR + 152 + 8 * i; }
__device__ __forceinline__ uint32_t BAR_SREADY(uint32_t sb, uint32_t i) { return sb + OFF_BAR + 184 + 8 * i; }
__device__ __forceinline__ uint32_t BAR_ONE(uint32_t sb, uint32_t i) { return sb + OFF_BAR + 216 + 8 * i; }
enum { EV_WIN, EV_WIN1, EV_WIN2, EV_WIN3, EV_P0, EV_GA, EV_GB, EV_LN2, EV_LAG0, EV_LAG1, EV_LAG2, EV_LAG3, EV_LAG4, EV_LAG5, EV_OWN, EV_OWN1, EV_P3, EV_P31, EV_KV, EV_GO, EV_PAR, EV_AGO, EV_AGO1, EV_AGO2, EV_FGO, EV_FGO1, EV_FGO2, EV_H0, EV_H1, EV_H2, EV_H3, EV_COUNT };
constexpr int NB_TAIL = 4;

struct Rel {
    uint32_t base; bool sig;
    __device__ __forceinline__ Rel(uint32_t sb, uint32_t tw) {
        uint32_t a; asm("mapa.shared::cluster.u32 %0, %1, %2;" : "=r"(a) : "r"(BAR_EMPTY(sb, 0)), "r"((tw >> 5) & 1));
        base = __shfl_sync(0xffffffffu, a, 0); sig = (tw & ~32u) == 0;
    }
    __device__ __forceinline__ void operator()(uint32_t slot) const {
        if (sig) asm volatile("mbarrier.arrive.shared::cluster.b64 _, [%0];" :: "r"(base + 8 * slot) : "memory");
    }
};
struct LnRow { float rs0, nm0, rs1, nm1; };
struct Pipe {
    Rel rel; uint32_t p1, p2;
    __device__ __forceinline__ Pipe(uint32_t sb, uint32_t tw, uint32_t first) : rel(sb, tw), p1(first), p2(NSLOT) {}
    template <bool TWO> __device__ __forceinline__ void acquire(uint32_t sb, uint32_t af, const Ring& r) {
        const uint32_t b0 = BAR_FULL(sb, r.slot), b1 = b0 + af;
        const bool ready = TWO ? mbar_test2(b0, b1, r.par) : mbar_test(b0, r.par);
        wg_wait<1>();
        rel(p2);
        if (!ready) { if (TWO) mbar_wait2(b0, b1, r.par); else mbar_wait(b0, r.par); }
    }
    __device__ __forceinline__ void issued(uint32_t slot) { p2 = p1; p1 = slot; }
    __device__ __forceinline__ void drain1() { wg_wait<1>(); rel(p2); p2 = NSLOT; }
    __device__ __forceinline__ void drain0() { wg_wait<0>(); rel(p1); p1 = NSLOT; }
    template <bool TWO, class Step> __device__ __forceinline__ void hold(int LG, uint32_t sb, uint32_t af, Ring& r, uint32_t lag_bar, Step step) {
        Ring q = r;
#pragma unroll 1
        for (int i = 0; i < LG; ++i) { if (TWO) mbar_wait2(BAR_FULL(sb, q.slot), BAR_FULL(sb, q.slot) + af, q.par); else mbar_wait(BAR_FULL(sb, q.slot), q.par); q.next(); }
        mbar_wait(lag_bar, 0);
#pragma unroll 1
        do {
            step(r.slot);
            wg_wait<2>(); rel(p2); p2 = p1; p1 = r.slot;
            if (++r.slot == NSLOT) r.slot = 0;
        } while (r.slot != q.slot);
        r.par = q.par;
    }
};
template <bool TWO, bool FIRST, int NA, int NB>
__device__ __forceinline__ void step32(float (&aa)[NA], float (&ab)[NB], uint32_t sb, uint32_t wg, uint32_t slot, int own) {
    const uint32_t st = d16(sb) + slot * (SLOT >> 4);
    const uint32_t alo = own >= 0 ? d16(sb) + OFF_STG / 16 + wg * 1024 + (own >> 1) * 512 + (own & 1) * 4 : st + wg * 256;
    const uint32_t ahi = own >= 0 ? (1024 >> 4) | (1u << 30) : (512 >> 4) | (2u << 30);
    wg_fence();
#pragma unroll
    for (int k = 0; k < 2; ++k) {
        const uint64_t da = ((uint64_t)ahi << 32) | (alo + k * 2 + 0x10000);
        if constexpr (NA == 88) {
            const uint64_t d0 = mk_desc(st, 8192 + k * 2048, 8192, 1024, 1), d1 = mk_desc(st, 12288 + k * 2048, 8192, 1024, 1);
            if (FIRST && k == 0) { wgmma_n176_z(aa, da, d0); wgmma_n176_z(ab, da, d1); }
            else { wgmma_n176(aa, da, d0); wgmma_n176(ab, da, d1); }
        } else {
            const uint64_t d0 = mk_desc(st, 8192 + k * 2048, 4096, 1024, 1), d1 = mk_desc(st, 24576 + k * 2048, 4096, 1024, 1);
            if (FIRST && k == 0) { wgmma_n256_z(aa, da, d0); if constexpr (TWO) wgmma_n128_z(ab, da, d1); }
            else { wgmma_n256(aa, da, d0); if constexpr (TWO) wgmma_n128(ab, da, d1); }
        }
    }
    wg_commit();
}
template <bool TWO, int LG, int NA, int NB, class Tail>
__device__ __forceinline__ void mainloop32(float (&aa)[NA], float (&ab)[NB], uint32_t sb, uint32_t wg, uint32_t tw, Ring& r, uint32_t lag_ev, int g0, Tail tail) {
    mbar_wait(BAR_FULL(sb, r.slot), r.par);
    step32<TWO, true>(aa, ab, sb, wg, r.slot, TWO ? 0 : -1);
    TS(g0, 0);
    Pipe pp(sb, tw, r.slot);
    r.next();
    const int end = wg ? 32 : 32 - LG;
#pragma unroll 1
    for (int it = 1; it < end; ++it) {
        pp.acquire<TWO>(sb, wg ? 0 : AF_REL, r);
        step32<TWO, false>(aa, ab, sb, wg, r.slot, TWO && it < 4 ? it : -1);
        pp.issued(r.slot);
        TS(g0 + it, 0);
        r.next();
    }
    if (wg == 0) { pp.drain1(); pp.drain0(); pp.hold<TWO>(LG, sb, AF_REL, r, BAR_ONE(sb, lag_ev), [&](uint32_t slot) { step32<TWO, false>(aa, ab, sb, 0, slot, -1); }); }
    pp.drain1();
    if (wg == 1 && tw == 0) mbar_arrive(BAR_ONE(sb, lag_ev));
    tail();
    pp.drain0();
    TS(g0 + 31, 1);
}
template <bool FIRST>
__device__ __forceinline__ void step64(float (&acc)[64], uint32_t sb, uint32_t wg, uint32_t slot, int own) {
    const uint32_t sbb = d16(sb) + slot * (SLOT >> 4), sa = own >= 0 ? d16(sb) + OFF_STG / 16 + wg * 1024 + own * 512 : sbb + wg * 512;
    wg_fence();
#pragma unroll
    for (int k = 0; k < 4; ++k) {
        const uint64_t da = mk_desc(sa, k * 32, 16, 1024, 1), db = mk_desc(sbb, 16384 + k * 2048, 8192, 1024, 1);
        if (FIRST && k == 0) wgmma_n128_z(acc, da, db); else wgmma_n128(acc, da, db);
    }
    wg_commit();
}
template <class Mid>
__device__ __forceinline__ void mainloop64(float (&acc)[64], bool wo, uint32_t sb, uint32_t wg, uint32_t tw, Ring& r, Mid mid) {
    const int g0 = wo ? 32 : 144, nst = wo ? 16 : 56, lg = wo ? LAGW : LAGD; (void)g0;
    const uint32_t lag_bar = BAR_ONE(sb, wo ? EV_LAG4 : EV_LAG5), af = wo && !wg ? AF_REL : 0;
    mbar_wait(BAR_FULL(sb, r.slot), r.par);
    if (!wo) CS(28);
    step64<true>(acc, sb, wg, r.slot, wo ? 0 : -1);
    if (!wo) CS(29);
    TS(g0, 0);
    Pipe pp(sb, tw, r.slot);
    r.next();
    int it = 1;
    auto run = [&](int end, int own) {
#pragma unroll 1
        do {
            pp.acquire<true>(sb, af, r);
            step64<false>(acc, sb, wg, r.slot, own);
            pp.issued(r.slot);
            TS(g0 + it, 0);
            r.next();
            if (own > 0) {
                own = -1;
                pp.drain1(); pp.drain0();
                TS(g0 + 1, 1);
                if (tw == 0) mbar_arrive(BAR_ONE(sb, EV_OWN + wg));
            }
        } while (++it < end);
    };
    run(wg ? (wo ? MIDW : MIDD) : nst - lg, wo ? 1 : -1);
    mid();
    if (wg) run(nst, -1);
    else { pp.drain1(); pp.drain0(); pp.hold<true>(lg, sb, af, r, lag_bar, [&](uint32_t slot) { step64<false>(acc, sb, 0, slot, -1); }); }
    pp.drain1();
    if (wg == 1 && tw == 0) mbar_arrive(lag_bar);
    pp.drain0();
    TS(g0 + nst - 1, 1);
}

struct RowAcc {
    float sm[4] = {0.f, 0.f, 0.f, 0.f}, sq[4] = {0.f, 0.f, 0.f, 0.f};
    __device__ __forceinline__ void add(int e, float x) { sm[e & 3] += x; sq[e & 3] = fmaf(x, x, sq[e & 3]); }
    __device__ __forceinline__ void publish(uint4* dst, uint32_t q4, uint32_t ep) const {
        const float s0 = sm[0] + sm[1], s1 = sm[2] + sm[3], q0 = sq[0] + sq[1], q1 = sq[2] + sq[3];
        const bool od = q4 & 1;
        float sv = (od ? s1 : s0) + __shfl_xor_sync(0xffffffffu, od ? s0 : s1, 1), qv = (od ? q1 : q0) + __shfl_xor_sync(0xffffffffu, od ? q0 : q1, 1);
        sv += __shfl_xor_sync(0xffffffffu, sv, 2); qv += __shfl_xor_sync(0xffffffffu, qv, 2);
        if (q4 < 2) st_pkt16(dst + q4 * 8, 0, __float_as_uint(sv), __float_as_uint(qv), ep);
    }
};
__device__ __forceinline__ LnRow merge_stats(const uint4* src, uint32_t q4, uint32_t ep, uint32_t sb) {
    uint4 t[4];
    uint32_t n = 0;
    while (true) {
#pragma unroll
        for (int i = 0; i < 4; ++i) t[i] = ld_pkt16(src + (q4 * 2 + (i >> 1)) * 512 + (i & 1) * 8);
        const bool ok_ = __all_sync(0xffffffffu, t[0].w == ep && t[1].w == ep && t[2].w == ep && t[3].w == ep);
        if (n < 4) CS(14 + n);
        if (ok_) break;
        SPIN_GUARD(n);
    }
    float v[4];
#pragma unroll
    for (int h = 0; h < 2; ++h) { v[h] = __uint_as_float(t[h].y) + __uint_as_float(t[2 + h].y); v[2 + h] = __uint_as_float(t[h].z) + __uint_as_float(t[2 + h].z); }
#pragma unroll
    for (int o = 1; o < 4; o <<= 1)
#pragma unroll
        for (int i = 0; i < 4; ++i) v[i] += __shfl_xor_sync(0xffffffffu, v[i], o);
    const float m0 = v[0] * (1.f / D_), m1 = v[1] * (1.f / D_);
    const float r0 = rsqrtf(fmaxf(fmaf(-m0, m0, v[2] * (1.f / D_)), 0.f) + 1e-5f), r1 = rsqrtf(fmaxf(fmaf(-m1, m1, v[3] * (1.f / D_)), 0.f) + 1e-5f);
    return LnRow{r0, -m0 * r0, r1, -m1 * r1};
}
struct Stg {
    uint32_t b, par;
    __device__ __forceinline__ uint32_t acquire2(uint32_t sb, uint32_t wg) {
        mbar_wait(BAR_SREADY(sb, wg * 2), par & 1);
        mbar_wait(BAR_SREADY(sb, wg * 2 + 1), (par >> 1) & 1);
        par ^= 3;
        return sb + OFF_STG + wg * 16384;
    }
    __device__ __forceinline__ void publish(uint32_t sb, uint32_t wg, uint32_t lane) {
        fence_async_smem();
        __syncwarp();
        if (lane == 0) mbar_arrive(BAR_SFULL(sb, wg * 2 + b));
        b ^= 1;
    }
};

struct LnPar {
    uint4 p[8];
    __device__ __forceinline__ void load(uint32_t sb, uint32_t q4) {
#pragma unroll
        for (int i = 0; i < 8; ++i) p[i] = lds128(sb + OFF_PAR + i * 64 + q4 * 16);
    }
};
__device__ __forceinline__ void ln_norm(uint32_t (&xn)[32], const float (&x)[64], const LnRow& n) {
#pragma unroll
    for (int e = 0; e < 32; ++e) {
        const float rs = (e & 1) ? n.rs1 : n.rs0, nm = (e & 1) ? n.nm1 : n.nm0;
        xn[e] = pack2(fmaf(x[2 * e], rs, nm), fmaf(x[2 * e + 1], rs, nm));
    }
}
__device__ __forceinline__ void ln_emit(const uint32_t (&xr)[32], const LnPar& lp, uint32_t sb, uint32_t wg, const Idx& ix) {
#pragma unroll
    for (int i = 0; i < 8; ++i)
        stsm4(sb + OFF_STG + wg * 16384 + (i >> 2) * 8192 + (ix.pan ^ ((i & 3) << 5)), hfma2_bf16(xr[4 * i], lp.p[i].z, lp.p[i].x), hfma2_bf16(xr[4 * i + 1], lp.p[i].z, lp.p[i].x),
              hfma2_bf16(xr[4 * i + 2], lp.p[i].w, lp.p[i].y), hfma2_bf16(xr[4 * i + 3], lp.p[i].w, lp.p[i].y));
    fence_async_smem();
    __syncwarp();
    if (ix.lane < 2) mbar_arrive(BAR_SFULL(sb, wg * 2 + ix.lane));
    bar_sync(1 + wg, 128);
}
__device__ __forceinline__ void load_slab(uint32_t (&xr)[32], uint32_t buf) {
    IDX();
#pragma unroll
    for (int i = 0; i < 8; ++i) ldsm4(buf + (i >> 2) * 8192 + (pan_addr ^ ((i & 3) << 5)), xr[4 * i], xr[4 * i + 1], xr[4 * i + 2], xr[4 * i + 3]);
}
__device__ __forceinline__ void unpack_slab(float (&x)[64], const uint32_t (&xr)[32]) {
#pragma unroll
    for (int i = 0; i < 32; ++i) unpack2(xr[i], x[2 * i], x[2 * i + 1]);
}
__device__ __forceinline__ void store_slab(const float (&x)[64], uint32_t buf, uint32_t pitch, uint32_t pan, int i0, int i1) {
#pragma unroll
    for (int i = i0; i < i1; ++i)
        stsm4(buf + (i >> 2) * pitch + (pan ^ ((i & 3) << 5)), pack2(x[8 * i], x[8 * i + 1]), pack2(x[8 * i + 2], x[8 * i + 3]), pack2(x[8 * i + 4], x[8 * i + 5]), pack2(x[8 * i + 6], x[8 * i + 7]));
}
__device__ __forceinline__ void fetch_halo(uint4* src, bool first, uint32_t sb, uint32_t W, uint32_t lane) {
    mbar_wait(BAR_ONE(sb, EV_KV), 0);
    mbar_wait2(BAR_SREADY(sb, 0), BAR_SREADY(sb, 1), 1);
    uint4 hv[8];
    uint32_t n = 0;
    while (true) {
        bool ok = true;
#pragma unroll
        for (int i = 0; i < 8; ++i) { hv[i] = first ? make_uint4(0, 0, 0, 0) : ld_pkt16(src + i * 32); ok = ok && hv[i].x != 0; }
        if (first || __all_sync(0xffffffffu, ok)) break;
        SPIN_GUARD(n);
    }
#pragma unroll
    for (int i = 0; i < 8; ++i) stsm4(sb + OFF_STG + W * 2048 + (i >> 2) * 8192 + (i & 3) * 512 + lane * 16, hv[i].x, hv[i].y, hv[i].z, hv[i].w);
    bar_arrive(NB_TAIL + W, 64);
    if (!first) {
#pragma unroll
        for (int i = 0; i < 8; ++i) src[i * 32] = make_uint4(0, 0, 0, 0);
    }
}

template <int OG, int OU, int LEN>
__device__ __forceinline__ void glu_panel(const float (&g)[LEN], const float (&u)[LEN], uint32_t buf, uint32_t bar) {
    IDX();
    constexpr int NR = LEN - OU < 32 ? (LEN - OU) / 2 : 16;
    uint32_t r[NR];
#pragma unroll
    for (int i = 0; i < NR; ++i) r[i] = pack2(glu_half(g[OG + 2 * i], u[OU + 2 * i]), glu_half(g[OG + 2 * i + 1], u[OU + 2 * i + 1]));
#pragma unroll
    for (int jn = 0; jn < NR / 2; jn += 2) stsm4(buf + (pan_addr ^ (jn << 4)), r[jn * 2], r[jn * 2 + 1], r[jn * 2 + 2], r[jn * 2 + 3]);
    fence_async_smem();
    __syncwarp();
    if (lane == 0) mbar_arrive(bar);
}

template <int NP>
__device__ __forceinline__ void passes128(uint32_t sb, uint32_t wg, uint32_t tw, Ring& r, Stg& stg) {
#pragma unroll 1
    for (int p = 0; p < NP; ++p) {
        float b256[128], none[1];
        mainloop32<false, LAGS>(b256, none, sb, wg, tw, r, EV_LAG2 + p, 80 + 32 * (p & 1), [&] { stg.acquire2(sb, wg); });
        if (threadIdx.x == 0) { TL(29 + 2 * p); TC(114 + 2 * p); }
        if (threadIdx.x == 128) TL(53 + 2 * (p & 1));
        CS(24 + 2 * (p & 1));
        glu_panel<0, 32>(b256, b256, sb + OFF_STG + wg * 16384, BAR_SFULL(sb, wg * 2));
        glu_panel<64, 96>(b256, b256, sb + OFF_STG + wg * 16384 + 8192, BAR_SFULL(sb, wg * 2 + 1));
        if (threadIdx.x == 0) { TL(30 + 2 * p); TC(115 + 2 * p); }
        if (threadIdx.x == 128) TL(54 + 2 * (p & 1));
        CS(25 + 2 * (p & 1));
    }
}

__global__ void __launch_bounds__(384, 1)
fused_block_kernel(const __grid_constant__ Ptrs pt, const __grid_constant__ Maps mp) {
    uint32_t* const g_flags = pt.mail->flags;
    uint2* const g_mod = pt.mail->mod;
    uint4* const g_st1 = pt.mail->st1;
    uint32_t* const g_par2 = pt.mail->par2;
    uint4* const g_halo = pt.mail->halo;
    const __nv_bfloat16* __restrict__ cvec = pt.c;
    if (threadIdx.x == 224) { prefetch_map(&mp.wm8); prefetch_map(&mp.x); }
    extern __shared__ __align__(1024) uint8_t smem[];
    const uint32_t sb = smem_u32(smem);
    const uint32_t tid = threadIdx.x, tw = tid & 127, lane = tid & 31;
    const uint32_t warp = __shfl_sync(0xffffffffu, tid >> 5, 0), wg = warp >> 2;
    uint32_t rank; asm("mov.u32 %0, %%cluster_ctarank;" : "=r"(rank));
    rank = __shfl_sync(0xffffffffu, rank, 0);
    uint32_t ep;
    uint32_t smid; asm volatile("mov.u32 %0, %%smid;" : "=r"(smid));
    const int c = __shfl_sync(0xffffffffu, smid >> 1, 0);
    const int c7 = ((c - 32) * 37) >> 8;
    const int grp = c < 32 ? c & 7 : c < 60 ? c - 31 - 7 * c7 : c < 62 ? -1 : 0;
    const int j = c < 32 ? c >> 3 : c < 60 ? 4 + c7 : c < 62 ? (c - 60) * 2 + rank : c - 58;
    const bool aux = grp < 0;
    const int m = grp * 2 + rank;
    uint4* const g_st2 = g_halo + (m > 0 ? (m - 1) * 8 * 512 : 128);

    bool cluster_arrive_early = false;
    if (wg < 2) {
      if (!KDEBUG) cluster_arrive();
      ep = flag_get(g_flags + FL_DONE);
      uint16_t cw[8];
      {
          const __nv_bfloat16* cp = cvec + ((tw >> 5) * 32 + (tw & 3) * 2) * 8 + (lane >> 2);
#pragma unroll
          for (int i = 0; i < 8; ++i) asm volatile("ld.global.nc.u16 %0, [%1];" : "=h"(cw[i]) : "l"(cp + (i >> 1) * 64 + (i & 1) * 8));
      }
      asm volatile("setmaxnreg.inc.sync.aligned.u32 224;");
      if (tid == 0) TL(58);
      if (KDEBUG) cluster_arrive();
      Ring r{0, 0};
      Stg stg{0, 0};
      if (aux) {
        if (wg == 0) {
            const uint4 cv = *(const uint4*)(cvec + tw * 8);
            sts128(sb + OFF_STG + (tw >> 3) * 1024 + (tw & 7) * 16, pack2(silu_(bf_lo(cv.x)), silu_(bf_hi(cv.x))), pack2(silu_(bf_lo(cv.y)), silu_(bf_hi(cv.y))),
                   pack2(silu_(bf_lo(cv.z)), silu_(bf_hi(cv.z))), pack2(silu_(bf_lo(cv.w)), silu_(bf_hi(cv.w))));
            fence_async_smem();
        }
        cluster_wait();
        ep = __shfl_sync(0xffffffffu, ep, 0) / NCTA + 1;
        if (wg == 0) {
            if (tw == 0) {
                uint32_t n = 0;
                while (ld_pkt16(pt.mail->mod1 + 256).z != ep) { SPIN_GUARD(n); __nanosleep(200); }
                if (GODLY) __nanosleep(GODLY);
                mbar_arrive(BAR_ONE(sb, EV_GO));
            }
            bar_sync(1, 128);
#pragma unroll 1
            for (int p = 0; p < 4; ++p) {
                float acc[128];
#pragma unroll
                for (int i = 0; i < 128; ++i) acc[i] = 0.f;
                uint32_t prev = 0;
#pragma unroll 1
                for (int kc = 0; kc < 16; ++kc) {
                    mbar_wait(BAR_FULL(sb, r.slot), r.par);
                    wg_fence();
#pragma unroll
                    for (int k = 0; k < 4; ++k)
                        wgmma_n256(acc, mk_desc(d16(sb) + kc * 64, OFF_STG + k * 32, 16, 0, 1), mk_desc(d16(sb) + r.slot * (SLOT >> 4), k * 2048, 8192, 1024, 1));
                    wg_commit();
                    wg_wait<1>();
                    if (kc > 0 && tw < 4) mbar_arrive(BAR_EMPTY(sb, prev));
                    prev = r.slot;
                    r.next();
                }
                wg_wait<0>();
                if (tw < 4) mbar_arrive(BAR_EMPTY(sb, prev));
                if (tw < 4) {
#pragma unroll
                    for (int jn = 0; jn < 32; ++jn) sts32(sb + OFF_TAB + (jn * 4 + tw) * 4, pack2(acc[jn * 4], acc[jn * 4 + 1]));
                }
                bar_sync(1, 128);
                const int vec = 2 + p, blk = p * 4 + j;
                const uint32_t val = lds32(sb + OFF_TAB + tw * 4);
                if (vec == 2 || vec == 5) st_pkt(g_mod + (8 + blk) * 128 + tw, val, ep);
                else {
                    const float one = vec == 4 ? 1.f : 0.f;
                    g_par2[((blk & 3) * 16 + (tw >> 3)) * 16 + (tw & 3) * 4 + (vec - 3) * 2 + ((tw >> 2) & 1)] =
                        pack2(0.5f * bf_round(one + bf_lo(val)), 0.5f * bf_round(one + bf_hi(val)));
                }
                bar_sync(1, 128);
                if (tw == 0) {
                    if (vec == 3 || vec == 4) asm volatile("red.release.gpu.global.add.u32 [%0], 1;" :: "l"(&g_flags[FL_LN2]) : "memory");
                    TL(1 + p);
                }
            }
            if (lane < 2) mbar_arrive_cta(BAR_ONE(sb, EV_P0), lane);
        }
        r = Ring{64 % NSLOT, (64 / NSLOT) & 1};
        mbar_wait(BAR_ONE(sb, EV_P0), 0);
        passes128<4>(sb, wg, tw, r, stg);
      } else {
        float xs[64];
        uint32_t xp[32];
        {
            IDX();
            if (q4 < 2) st_pkt16(g_st1 + (m * 8 + j) * 512 + wg * 64 + w4 * 16 + g8 + q4 * 8, 0, 0, 0, 0);
            if (warp == 0) st_pkt16(pt.mail->mod1 + g8 * 512 + (m * 8 + j) * 4 + q4, 0, 0, 0, 0);
            sts128(sb + tid * 16, pack2(silu_(bf_lo(cw[0])), silu_(bf_lo(cw[1]))), pack2(silu_(bf_lo(cw[2])), silu_(bf_lo(cw[3]))),
                   pack2(silu_(bf_lo(cw[4])), silu_(bf_lo(cw[5]))), pack2(silu_(bf_lo(cw[6])), silu_(bf_lo(cw[7]))));
            cluster_wait();
            ep = __shfl_sync(0xffffffffu, ep, 0) / NCTA + 1;
            load_slab(xp, stg.acquire2(sb, wg));
            unpack_slab(xs, xp);
            if (tid == 0) TL(24);
            if (tid == 128) TL(27);
        }
#pragma unroll 1
        for (int blk = 0; ; ++blk) {
        {
            IDX();
            uint4* const st = (blk ? g_st2 : g_st1 + m * 8 * 512) + wg * 64 + w4 * 16 + g8;
            RowAcc ra;
#pragma unroll
            for (int e = 0; e < 64; ++e) ra.add(e, xs[e]);
            ra.publish(st + j * 512, q4, ep);
            uint32_t t_pub = 0; if (PDLY) asm volatile("mov.u32 %0, %%clock;" : "=r"(t_pub));
            if (tid == 0) TL(blk ? 9 : 26);
            if (tid == 128 && blk) TL(34);
            if (blk) CS(11);
            LnPar lp;
            if (blk == 0) {
            uint4* const mod_out = pt.mail->mod1 + g8 * 512 + (m * 8 + j) * 4 + q4;
            if (wg == 0) {
                uint4 af[8];
#pragma unroll
                for (int i = 0; i < 8; ++i) af[i] = lds128(sb + w4 * 512 + i * 64 + q4 * 16);
                float c[4][4] = {};
#pragma unroll
                for (int i = 0; i < 8; ++i) {
                    if (!(i & 1)) mbar_wait(BAR_ONE(sb, EV_WIN + (i >> 1)), 0);
                    if (i == 6 && tid == 0) TL(25);
#pragma unroll
                    for (int h = 0; h < 2; ++h) {
                        uint32_t b0, b1, b2, b3;
                        ldsm4t(sb + 5 * SLOT + i * 4096 + w4 * 1024 + h * 512 + (lane & 15) * 32 + (lane >> 4) * 16, b0, b1, b2, b3);
                        mma16816(c[2 * h], h ? af[i].z : af[i].x, 0u, h ? af[i].w : af[i].y, 0u, b0, b1);
                        mma16816(c[2 * h + 1], h ? af[i].z : af[i].x, 0u, h ? af[i].w : af[i].y, 0u, b2, b3);
                    }
                }
                if (lane < 4) sts128(sb + OFF_TAB + w4 * 64 + lane * 16, __float_as_uint(c[0][0] + c[2][0]), __float_as_uint(c[0][1] + c[2][1]),
                                     __float_as_uint(c[1][0] + c[3][0]), __float_as_uint(c[1][1] + c[3][1]));
                if (lane < 2) mbar_arrive_cta(BAR_ONE(sb, EV_P0), lane);
                bar_sync(1, 128);
                if (w4 == 0) {
                    float a[4] = {0.f, 0.f, 0.f, 0.f};
#pragma unroll
                    for (int i = 0; i < 4; ++i) {
                        const uint4 t = lds128(sb + OFF_TAB + i * 64 + q4 * 16);
                        a[0] += __uint_as_float(t.x); a[1] += __uint_as_float(t.y); a[2] += __uint_as_float(t.z); a[3] += __uint_as_float(t.w);
                    }
                    const float add = m >= 8 ? 1.f : 0.f;
                    st_pkt16(mod_out, pack2(bf_round(a[0]) + add, bf_round(a[1]) + add), pack2(bf_round(a[2]) + add, bf_round(a[3]) + add), ep, 0);
                    if (tid == 0) TL(3);
                }
            } else if (LWAIT >= 0) mbar_wait(BAR_ONE(sb, EV_WIN + LWAIT), 0);
            } else {
                mbar_wait(BAR_ONE(sb, EV_LN2), 0);
            }
            lp.load(sb, q4);
#pragma unroll
            for (int e = 0; e < 32; ++e) xp[e] = pack2(xs[2 * e], xs[2 * e + 1]);
            if (PDLY && blk) { uint32_t t1; do { asm volatile("mov.u32 %0, %%clock;" : "=r"(t1)); } while (t1 - t_pub < PDLY); }
            if (blk) CS(13);
            const LnRow n = merge_stats(st, q4, ep, sb);
            if (tid == 0) TL(blk ? 49 : 48);
            if (tid == 128) TL(blk ? 45 : 28);
            if (blk) CS(18);
            uint32_t xn[32];
            ln_norm(xn, xs, n);
            if (blk == 0) { mbar_wait(BAR_ONE(sb, EV_PAR), 0); lp.load(sb, q4); }
            ln_emit(xn, lp, sb, wg, ix);
            if (tid == 0) { TL(blk ? 36 : 8); TC(blk ? 109 : 103); }
            if (tid == 128) TL(blk ? 43 : 22);
            if (blk) CS(21);
        }
        if (blk == 0) {
        {
            float kv[128], qa[64];
            mainloop32<true, LAGQ>(kv, qa, sb, wg, tw, r, EV_LAG0, 0, [&] { stg.acquire2(sb, wg); mbar_wait2(BAR_SREADY(sb, 2), BAR_SREADY(sb, 3), 1); });
            if (tid == 0) { TL(4); TC(104); }
            if (tid == 128) TL(50);
            CS(1);
            IDX();
            uint32_t k1[16], k2[16], v1[16], v2[16], qf[32];
#pragma unroll
            for (int i = 0; i < 8; ++i) qf[i] = pack2(qa[2 * i], qa[2 * i + 1]);
#pragma unroll
            for (int t = 0; t < 16; ++t) k2[t] = pack2(kv[4 * t + 2], kv[4 * t + 3]);
#pragma unroll
            for (int t = 0; t < 16; ++t) v2[t] = pack2(kv[64 + 4 * t + 2], kv[64 + 4 * t + 3]);
            const uint32_t nxt = warp + ((warp & 1) ? 3 : 1);
            if (nxt < 8) {
                const uint32_t dst = sb + OFF_STG + (nxt >> 2) * 16384 + (nxt & 3) * 2048 + lane * 16;
#pragma unroll
                for (int h = 0; h < 4; ++h) stsm4(dst + h * 512, k2[4 * h], k2[4 * h + 1], k2[4 * h + 2], k2[4 * h + 3]);
#pragma unroll
                for (int h = 0; h < 4; ++h) stsm4(dst + 8192 + h * 512, v2[4 * h], v2[4 * h + 1], v2[4 * h + 2], v2[4 * h + 3]);
                bar_arrive(NB_TAIL + nxt, 64);
            } else if (m < 15) {
                uint4* dst = g_halo + (m * 8 + j) * 512 + (w4 >> 1) * 256 + lane;
#pragma unroll
                for (int h = 0; h < 4; ++h) { if (!k2[4 * h]) k2[4 * h] = 0x8000u; if (!v2[4 * h]) v2[4 * h] = 0x8000u; }
#pragma unroll
                for (int h = 0; h < 4; ++h) st_pkt16(dst + h * 32, k2[4 * h], k2[4 * h + 1], k2[4 * h + 2], k2[4 * h + 3]);
#pragma unroll
                for (int h = 0; h < 4; ++h) st_pkt16(dst + 128 + h * 32, v2[4 * h], v2[4 * h + 1], v2[4 * h + 2], v2[4 * h + 3]);
            }
#pragma unroll
            for (int t = 0; t < 16; ++t) { k1[t] = pack2(kv[4 * t], kv[4 * t + 1]); v1[t] = pack2(kv[64 + 4 * t], kv[64 + 4 * t + 1]); }
#pragma unroll
            for (int i = 8; i < 32; ++i) qf[i] = pack2(qa[2 * i], qa[2 * i + 1]);
#pragma unroll
            for (int t = 0; t < 16; ++t) { v1[t] = movm(v1[t]); v2[t] = movm(v2[t]); }
            if (tid == 0) TL(33);
            CS(2);
            SCHED_FENCE(0);
            float s[4][3][4];
            auto qk = [&](float (&c)[4], int h, const uint32_t* k) {
                c[0] = c[1] = c[2] = c[3] = 0.f;
                mma16816(c, qf[h * 8], qf[h * 8 + 1], qf[h * 8 + 2], qf[h * 8 + 3], k[0], k[1]);
                mma16816(c, qf[h * 8 + 4], qf[h * 8 + 5], qf[h * 8 + 6], qf[h * 8 + 7], k[2], k[3]);
            };
#pragma unroll
            for (int h = 0; h < 4; ++h) { qk(s[h][1], h, k1 + 4 * h); qk(s[h][2], h, k2 + 4 * h); }
            CS(3);
            bar_sync(NB_TAIL + warp, 64);
            CS(4);
            if (tid == 0) TL(5);
            uint32_t k0[16], v0[16];
            const uint32_t mine = sb + OFF_STG + wg * 16384 + w4 * 2048;
#pragma unroll
            for (int h = 0; h < 4; ++h) ldsm4(mine + lane * 16 + h * 512, k0[4 * h], k0[4 * h + 1], k0[4 * h + 2], k0[4 * h + 3]);
#pragma unroll
            for (int h = 0; h < 4; ++h) ldsm4t(mine + lane * 16 + 8192 + h * 512, v0[4 * h], v0[4 * h + 1], v0[4 * h + 2], v0[4 * h + 3]);
#pragma unroll
            for (int h = 0; h < 4; ++h) qk(s[h][0], h, k0 + 4 * h);
            const bool lo0 = q4 * 2 > g8, lo1 = q4 * 2 + 1 > g8;
            const bool nopast = m == 0 && (warp & 5) == 0;
            const uint32_t lomask = (lo0 ? 0xFFFFu : 0u) | (lo1 ? 0xFFFF0000u : 0u);
            const float sl2 = 0.17677669529663687f * 1.4426950408889634f;
            float e0[8], e1[8], mx[8], sum[8], tt[8];
#pragma unroll
            for (int u = 0; u < 8; ++u) {
                const int h = u >> 1, hf = u & 1;
                e0[u] = lo0 ? ((hf == 0 && nopast) ? -INFINITY : s[h][hf][hf * 2]) : s[h][hf + 1][hf * 2];
                e1[u] = lo1 ? ((hf == 0 && nopast) ? -INFINITY : s[h][hf][hf * 2 + 1]) : s[h][hf + 1][hf * 2 + 1];
                mx[u] = fmaxf(e0[u], e1[u]);
                tt[u] = __shfl_xor_sync(0xffffffffu, mx[u], 1);
            }
            SCHED_FENCE(1);
#pragma unroll
            for (int u = 0; u < 8; ++u) { mx[u] = fmaxf(mx[u], tt[u]); tt[u] = __shfl_xor_sync(0xffffffffu, mx[u], 2); }
            SCHED_FENCE(2);
#pragma unroll
            for (int u = 0; u < 8; ++u) {
                const float c = -fmaxf(mx[u], tt[u]) * sl2;
                e0[u] = ex2(fmaf(e0[u], sl2, c)); e1[u] = ex2(fmaf(e1[u], sl2, c));
            }
            SCHED_FENCE(3);
#pragma unroll
            for (int u = 0; u < 8; ++u) { sum[u] = e0[u] + e1[u]; tt[u] = __shfl_xor_sync(0xffffffffu, sum[u], 1); }
            SCHED_FENCE(4);
#pragma unroll
            for (int u = 0; u < 8; ++u) { sum[u] += tt[u]; tt[u] = __shfl_xor_sync(0xffffffffu, sum[u], 2); }
            SCHED_FENCE(5);
#pragma unroll
            for (int u = 0; u < 8; ++u) sum[u] = rcp(sum[u] + tt[u]);
            SCHED_FENCE(6);
            CS(5);
            float o[8][2][4];
#pragma unroll
            for (int u = 0; u < 8; ++u) {
                const int h = u >> 1;
                const uint32_t p = pack2(e0[u] * sum[u], e1[u] * sum[u]);
                const uint32_t* va = ((u & 1) ? v1 : v0) + 4 * h;
                const uint32_t* vb = ((u & 1) ? v2 : v1) + 4 * h;
#pragma unroll
                for (int d = 0; d < 2; ++d) {
                    o[u][d][0] = o[u][d][1] = o[u][d][2] = o[u][d][3] = 0.f;
                    mma16816(o[u][d], va[2 * d], va[2 * d + 1], vb[2 * d], vb[2 * d + 1], p & lomask, p & ~lomask);
                }
            }
            SCHED_FENCE(7);
            const uint32_t orow = mine + (lane & 7) * 128 + (((lane >> 3) ^ (lane & 7)) << 4);
#pragma unroll
            for (int u = 0; u < 8; ++u)
                stsm4t((orow ^ (((u >> 1) & 1) << 6)) + (u >> 2) * 8192 + (u & 1) * 1024, pack2(o[u][0][0], o[u][0][1]), pack2(o[u][0][2], o[u][0][3]),
                       pack2(o[u][1][0], o[u][1][1]), pack2(o[u][1][2], o[u][1][3]));
            fence_async_smem();
            __syncwarp();
            if (lane < 2) mbar_arrive(BAR_SFULL(sb, wg * 2 + lane));
            CS(6);
            if (tid == 32) TL(41);
            bar_sync(1 + wg, 128);
            if (tid == 0) { TL(6); TC(106); }
            if (tid == 128) TL(44);
            CS(7);
#pragma unroll
            for (int e = 0; e < 32; ++e) xp[e] = qf[e];
        }
        } else {
        {
            float ag[88], au[88];
            mainloop32<true, LAG>(ag, au, sb, wg, tw, r, EV_LAG1, 48, [&] {
                stg.acquire2(sb, wg);
                Ring q = r; if (!wg) q.next();
                mbar_wait(BAR_EMPTY(sb, q.slot), q.par ^ 1);
            });
            if (tid == 0) { TL(10); TC(110); }
            if (tid == 128) TL(51);
            CS(22);
            glu_panel<0, 0>(ag, au, sb + OFF_STG + wg * 16384, BAR_SFULL(sb, wg * 2));
            glu_panel<32, 32>(ag, au, sb + OFF_STG + wg * 16384 + 8192, BAR_SFULL(sb, wg * 2 + 1));
            glu_panel<64, 64>(ag, au, sb + (wg ? P3_SLOT1 : P3_SLOT0) * SLOT + 24576, BAR_ONE(sb, EV_P3 + wg));
            if (tid == 0) { TL(11); TC(111); }
            if (tid == 128) TL(52);
            CS(23);
        }
        passes128<2>(sb, wg, tw, r, stg);
        if (tid == 0) { TL(12); TC(112); }
        }
        {
            float acc[64], gf[32];
            mainloop64(acc, blk == 0, sb, wg, tw, r, [&] {
                mbar_wait(BAR_ONE(sb, EV_GA + blk), 0);
                const uint32_t buf = stg.acquire2(sb, wg);
                if (blk == 0) load_slab(xp, buf);
                unpack_slab(xs, xp);
                uint32_t gt[16];
#pragma unroll
                for (int cg = 0; cg < 16; ++cg) gt[cg] = lds32(sb + OFF_TAB + blk * 256 + cg * 16 + (tw & 3) * 4);
#pragma unroll
                for (int i = 0; i < 16; ++i) unpack2(gt[i], gf[2 * i], gf[2 * i + 1]);
            });
            if (tid == 0) { TL(blk ? 13 : 7); TC(blk ? 113 : 107); }
            if (tid == 128) TL(blk ? 57 : 42);
            CS(blk ? 30 : 10);
#pragma unroll
            for (int e = 0; e < 64; ++e) xs[e] = fmaf(gf[(e >> 2) * 2 + (e & 1)], acc[e], xs[e]);
        }
        if (blk) break;
        }
        cluster_arrive();
        {
            IDX();
#pragma unroll
            for (int p = 0; p < 2; ++p) {
                store_slab(xs, sb + OFF_STG + wg * 16384, 8192, pan_addr, 4 * p, 4 * p + 4);
                stg.publish(sb, wg, lane);
            }
            if (tid == 0) TL(14);
            CS(31);
        }
      }
    } else {
        if (warp == 8 && !aux && elect_one()) {
#pragma unroll
            for (int i = 0; i < 4; ++i) mbar_init(BAR_SREADY(sb, i), 1);
#pragma unroll
            for (int i = 0; i < 4; ++i) mbar_init(BAR_ONE(sb, EV_WIN + i), 1);
#pragma unroll
            for (int i = 0; i < 4; ++i) {
                mbar_expect_tx(BAR_SREADY(sb, i), 8192);
                tma_load3(sb + OFF_STG + i * 8192, &mp.x, j * 128 + (i & 1) * 64, m * 64 + (i >> 1) * 32, BAR_SREADY(sb, i));
            }
#pragma unroll 1
            for (int i = 0; i < 4; ++i) {
                mbar_expect_tx(BAR_ONE(sb, EV_WIN + i), 8192);
                tma_load(sb + 5 * SLOT + i * 8192, &mp.wm8, 2 * i * 6144 + (m * 8 + j) * 16, 0, BAR_ONE(sb, EV_WIN + i));
                tma_load(sb + 5 * SLOT + i * 8192 + 4096, &mp.wm8, (2 * i + 1) * 6144 + (m * 8 + j) * 16, 0, BAR_ONE(sb, EV_WIN + i));
            }
        }
        __syncwarp();
        asm volatile("setmaxnreg.dec.sync.aligned.u32 56;");
        if (elect_one()) {
            if (warp == 8) {
                prefetch_map(&mp.wqkv); prefetch_map(&mp.wmod);
            } else if (warp < 11) {
                mbar_init(BAR_EMPTY(sb, NSLOT), 1);
#pragma unroll
                for (int i = 0; i < 2; ++i) { mbar_init(BAR_SFULL(sb, (warp - 9) * 2 + i), 4); if (aux) mbar_init(BAR_SREADY(sb, (warp - 9) * 2 + i), 1); }
#pragma unroll
                for (int i = 0; i < 3; ++i) {
                    mbar_init(BAR_EMPTY(sb, (warp - 9) * 3 + i), 4);
                    mbar_init(BAR_FULL(sb, (warp - 9) * 3 + i), 1); mbar_init(BAR_FULL(sb, (warp - 9) * 3 + i) + AF_REL, 1);
                }
            } else {
#pragma unroll
                for (int i = EV_P0; i < EV_COUNT; ++i) mbar_init(BAR_ONE(sb, i), i == EV_P0 ? 8 : (i == EV_P3 || i == EV_P31) ? 4 : 1);
            }
            asm volatile("fence.mbarrier_init.release.cluster;" ::: "memory");
        }
        __syncwarp();
        cluster_arrive();
        ep = 0;
        if (warp != 8 || aux) ep = flag_get(g_flags + FL_DONE);
        cluster_wait();
        ep = __shfl_sync(0xffffffffu, ep, 0) / NCTA + 1;
        if (warp == 8) {
            const bool el = elect_one();
            Ring r{0, 1};
            if (aux) {
                mbar_wait(BAR_ONE(sb, EV_GO), 0);
#pragma unroll 1
                for (int it = 0; it < 64; ++it) {
                    const int col = 2048 + (it >> 4) * 1024 + j * 256;
                    mbar_wait(BAR_EMPTY(sb, r.slot), r.par);
                    const uint32_t st = sb + r.slot * SLOT, fb = BAR_FULL(sb, r.slot);
                    if (el) {
                        mbar_expect_tx(fb, 32768);
#pragma unroll
                        for (int b = 0; b < 4; ++b) tma_load(st + b * 8192, &mp.wmod, col + b * 64, (it & 15) * 64, fb);
                    }
                    r.next();
                }
                mbar_wait(BAR_ONE(sb, EV_P0), 0);
                const CUtensorMap* wm = rank ? &mp.wu : &mp.wg;
#pragma unroll 1
                for (int g = 0; g < 128; ++g) {
                    const int mx = (j >> 1) * 8 + (g >> 5) * 2 + rank, k0 = (g & 31) * 32;
                    if (k0 == 0) {
                        uint32_t n = 0;
                        while (!__all_sync(0xffffffffu, (int32_t)(flag_get(g_flags + FL_PROG + (mx * 32 + lane) * FS) - (ep * 8 + ST_H2)) >= 0)) { SPIN_GUARD(n); __nanosleep(500); }
                    }
                    mbar_wait(BAR_EMPTY(sb, r.slot), r.par);
                    const uint32_t st = sb + r.slot * SLOT, fb = BAR_FULL(sb, r.slot);
                    if (el) {
                        mbar_expect_tx(fb, 24576);
                        tma_load_mc(st + 8192 + rank * 4096, wm, HC3, k0, fb);
                        tma_load_mc(st + 16384 + rank * 4096, wm, HC3 + 64, k0, fb);
                        tma_load(st, &mp.h2l, k0, mx * 128, fb);
                    }
                    r.next();
                }
            } else {
#pragma unroll 1
                for (int it = 0; it < 32; ++it) {
                    const int cb = j * 128 + rank * 64, k0 = kof(it, 2, j);
                    if (it == BW0) mbar_wait(BAR_ONE(sb, BWEV), 0);
                    if (it == BW1) mbar_wait(BAR_ONE(sb, EV_PAR), 0);
                    if (it == 5) mbar_wait(BAR_ONE(sb, EV_P0), 0);
                    if (it == 6) mbar_wait(BAR_ONE(sb, (AGW & 1) ? EV_AGO : EV_FGO), 0);
                    mbar_wait(BAR_EMPTY(sb, r.slot), r.par);
                    const uint32_t st = sb + r.slot * SLOT, fb = BAR_FULL(sb, r.slot);
                    if (el) {
                        mbar_expect_tx(fb, it < 4 ? 24576 : 28672);
                        tma_load_mc(st + 8192 + rank * 4096, &mp.wqkv, 1024 + cb, k0, fb);
                        tma_load_mc(st + 16384 + rank * 4096, &mp.wqkv, 2048 + cb, k0, fb);
                        tma_load_mc(st + 24576 + rank * 4096, &mp.wqkv, cb, k0, fb);
                        if (it < 4) mbar_arrive(fb + AF_REL);
                        if (it == PFWO + (m >> 1)) { tma_prefetch(&mp.wo, j * 128, m * 64); tma_prefetch(&mp.wo, j * 128 + 64, m * 64); }
                    }
                    r.next();
                }
                if (el) mbar_arrive(BAR_ONE(sb, EV_KV));
#pragma unroll 1
                for (int it = 0; it < 16; ++it) {
                    if (it == 6) mbar_wait(BAR_ONE(sb, (AGW & 2) ? EV_AGO1 : EV_FGO1), 0);
                    mbar_wait(BAR_EMPTY(sb, r.slot), r.par);
                    const uint32_t st = sb + r.slot * SLOT, fb = BAR_FULL(sb, r.slot);
                    if (el) {
                        mbar_expect_tx(fb, it < 2 ? 16384 : 24576);
                        tma_load_mc(st + 16384 + rank * 8192, &mp.wo, j * 128 + rank * 64, kof(it, 1, j), fb);
                        if (it < 2) mbar_arrive(fb + AF_REL);
                        if (it == 6) { prefetch_map(rank ? &mp.wu : &mp.wg); prefetch_map(rank ? &mp.wu3 : &mp.wg3); }
                    }
                    r.next();
                }
                const CUtensorMap* wm = rank ? &mp.wu : &mp.wg;
#pragma unroll 1
                for (int g = 0; g < 96; ++g) {
                    if (g == 6) mbar_wait(BAR_ONE(sb, (AGW & 4) ? EV_AGO2 : EV_FGO2), 0);
                    const int p = g >> 5, cb = hcol(p, j), k0 = p == 0 ? kof(g, 2, j) : (g & 31) * 32;
                    mbar_wait(BAR_EMPTY(sb, r.slot), r.par);
                    const uint32_t st = sb + r.slot * SLOT, fb = BAR_FULL(sb, r.slot);
                    if (el) {
                        mbar_expect_tx(fb, (g < 4 || p > 0) ? 24576 : 28672);
                        tma_load_mc(st + 8192 + rank * 4096, wm, cb, k0, fb);
                        tma_load_mc(st + 16384 + rank * 4096, wm, cb + 64, k0, fb);
                        if (p == 0) tma_load3_mc(st + 24576 + rank * 4096, rank ? &mp.wu3 : &mp.wg3, j, k0, fb);
                        else tma_load(st, &mp.h2l, k0, m * 128, fb);
                        if (g < 4) mbar_arrive(fb + AF_REL);
                        if (g == 60) prefetch_map(&mp.wd);
                    }
                    r.next();
                }
#pragma unroll 1
                for (int g = 0; g < 56; ++g) {
                    if (g == 0 || (g & 15) == 6 && g > 6) mbar_wait(BAR_ONE(sb, EV_H0 + (g >> 4)), 0);
                    const int k0 = g * 64;
                    mbar_wait(BAR_EMPTY(sb, r.slot), r.par);
                    const uint32_t st = sb + r.slot * SLOT, fb = BAR_FULL(sb, r.slot);
                    if (el) {
                        mbar_expect_tx(fb, 32768);
                        tma_load_mc(st + 16384 + rank * 8192, &mp.wd, j * 128 + rank * 64, k0, fb);
                        tma_load(st, &mp.hb, k0, m * 128, fb); tma_load(st + 8192, &mp.hb, k0, m * 128 + 64, fb);
                    }
                    r.next();
                }
            }
        } else if (aux) {
            if (warp < 11) {
                const uint32_t w = warp - 9;
                const bool el = elect_one();
#pragma unroll 1
                for (int p = 0; p < 4; ++p) {
                    const int mx = (j >> 1) * 8 + p * 2 + rank;
                    if (el) { mbar_arrive(BAR_SREADY(sb, w * 2)); mbar_arrive(BAR_SREADY(sb, w * 2 + 1)); }
                    mbar_wait2(BAR_SFULL(sb, w * 2), BAR_SFULL(sb, w * 2 + 1), p & 1);
                    if (el) {
                        tma_store(&mp.hb, HC3, mx * 128 + w * 64, sb + OFF_STG + w * 16384); tma_store(&mp.hb, HC3 + 64, mx * 128 + w * 64, sb + OFF_STG + w * 16384 + 8192);
                        bulk_commit(); bulk_wait_all(); flag_set(g_flags + FL_AUX + mx * 2 + w, ep * 8 + ST_H + 3);
                    }
                }
            }
        } else if (warp == 11) {
            const bool el = elect_one();
            const int row0 = m * 128;
            const uint32_t* const fl = g_flags + FL_PROG + (m * 32 + (lane & 16) + (kof(lane & 15, 1, j) >> 6)) * FS;
            if (el) { prefetch_map(&mp.h1h); prefetch_map(&mp.h2h); prefetch_map(&mp.h2l); }
            {
                const uint4* pk = pt.mail->mod1 + grp * 512 + j * 32 + lane;
                uint4 a, b; uint32_t n = 0;
                mbar_wait(BAR_ONE(sb, EV_WIN3), 0);
                while (true) {
                    a = ld_pkt16(pk); b = ld_pkt16(pk + 256);
                    if (__all_sync(0xffffffffu, a.z == ep && b.z == ep)) break;
                    SPIN_GUARD(n);
                }
                sts128(sb + OFF_PAR + lane * 16, a.x, a.y, b.x, b.y);
                __syncwarp();
                if (lane == 0) { mbar_arrive(BAR_ONE(sb, EV_PAR)); TL(46); }
            }
            mbar_wait(BAR_ONE(sb, EV_P0), 0);
            Ring r{0, 1};
#pragma unroll 1
            for (int ph = 0; ph < 3; ++ph) {
                const int sh = ph == 1 ? 1 : 2, nst = 8 << sh;
                const uint32_t half = 16384 >> sh;
                const CUtensorMap* tm = ph == 0 ? &mp.h1h : ph == 1 ? &mp.o : &mp.h2h;
                if (ph == 1) fetch_halo(g_halo + ((m - 1) * 8 + j) * 512 + 256 + lane, m == 0, sb, 2, lane);
                const uint32_t target = ep * 8 + ST_H1 + ph;
                int a0 = 1 << sh, a1 = a0, fr = a0;
                r.skip(fr);
                uint32_t s0 = r.slot, s1 = r.slot, have = 0, n = 0;
                int k0 = j ? 0 : 128, k1 = k0;
#pragma unroll 1
                for (; fr < NSLOT; ++fr) { mbar_wait(BAR_EMPTY(sb, r.slot), r.par); r.next(); }
                uint32_t v = flag_get(fl);
                auto load = [&](int& a, uint32_t& sl, int& k, uint32_t w) {
                    const uint32_t fb = BAR_FULL(sb, sl) + (w ? 0 : AF_REL);
                    if (el) { if (!w) mbar_expect_tx(fb, half); tma_load(sb + sl * SLOT + w * half, tm, k, row0 + w * 64, fb); }
                    if (a == NSLOT - 1 && el) mbar_arrive(BAR_ONE(sb, (w ? EV_AGO : EV_FGO) + ph));
                    ++a; if (++sl == NSLOT) sl = 0;
                    k = kof(a, sh, j);
                };
                do {
                    PS(0);
                    if (fr < 9 && mbar_test(BAR_EMPTY(sb, r.slot), r.par)) { ++fr; r.next(); }
                    SPIN_GUARD(n);
                    PS(1);
                    const bool ok = (int32_t)(v - target) >= 0;
                    v = flag_get(fl);
                    have = __ballot_sync(0xffffffffu, ok);
                    PS(2);
#pragma unroll 1
                    while (a1 < fr && (have & (0x10000u << (a1 >> (sh - 1))))) {
                        if (a1 == (1 << sh)) TL(16 + ph);
                        load(a1, s1, k1, 1);
                    }
                    PS(3);
#pragma unroll 1
                    while (a0 < fr && (have & (1u << (a0 >> (sh - 1))))) load(a0, s0, k0, 0);
                    PS(4);
                } while (~have & 0x01fc01fcu);
#pragma unroll 1
                while (a0 < nst) {
                    if (a0 == 9 << (sh - 1)) while (!__all_sync(0xffffffffu, (int32_t)(flag_get(fl) - target) >= 0)) SPIN_GUARD(n);
                    mbar_wait(BAR_EMPTY(sb, r.slot), r.par);
                    r.next();
                    load(a1, s1, k1, 1); load(a0, s0, k0, 0);
                }
            }
#pragma unroll 1
            for (int p = 0; p < 4; ++p) {
                const uint32_t* f = p < 3 ? fl : g_flags + FL_AUX + m * 2 + (lane & 1);
                uint32_t n = 0;
                while (!__all_sync(0xffffffffu, (int32_t)(flag_get(f) - (ep * 8 + ST_H + p)) >= 0)) { SPIN_GUARD(n); __nanosleep(500); }
                if (el) mbar_arrive(BAR_ONE(sb, EV_H0 + p));
            }
        } else {
            const uint32_t w = warp - 9;
            const int row0 = m * 128 + w * 64;
            const uint32_t stg = sb + OFF_STG + w * 16384;
            uint32_t* const fl = g_flags + FL_PROG + (m * 32 + w * 16 + 2 * j) * FS;
            uint32_t b = 0, par = 0;
            const bool el = elect_one();
            auto store = [&](const CUtensorMap* tm, int col, bool nat = false) {
                mbar_wait(BAR_SFULL(sb, w * 2 + b), (par >> b) & 1);
                par ^= 1u << b;
                if (el) {
                    if (nat) tma_store3(tm, col, row0 >> 1, 0, stg + b * 8192); else tma_store(tm, col, row0, stg + b * 8192);
                    bulk_commit();
                }
                b ^= 1;
            };
            auto send2 = [&](const CUtensorMap* tm, int step) {
                const bool now = step == ST_O && w;
                store(tm, j * 128);
                if (!now) {
                    if (el) { bulk_wait_all(); flag_set(fl, ep * 8 + step); }
                    mbar_wait(BAR_ONE(sb, EV_FGO + step - ST_H1), 0);
                    if (step != ST_O) pause(w ? P1H : P1H + 1000);
                }
                store(tm, j * 128 + 64);
                if (el) {
                    if (now) { asm volatile("cp.async.bulk.wait_group 1;" ::: "memory"); flag_set(fl, ep * 8 + step); }
                    bulk_wait_all(); flag_set(fl + FS, ep * 8 + step);
                }
            };
            auto free2 = [&]() { if (el) { mbar_arrive(BAR_SREADY(sb, w * 2)); mbar_arrive(BAR_SREADY(sb, w * 2 + 1)); } };
            auto gate = [&](int vec, int ev) {
                uint4 v; uint32_t n = 0;
                while (true) {
                    v = ld_pkt2(g_mod + vec * 512 + j * 64 + lane * 2);
                    if (__all_sync(0xffffffffu, v.y == ep && v.w == ep)) break;
                    SPIN_GUARD(n); __nanosleep(300);
                }
                asm volatile("st.shared.v2.u32 [%0], {%1, %2};" :: "r"(sb + OFF_TAB + (ev - EV_GA) * 256 + lane * 8), "r"(v.x), "r"(v.z) : "memory");
                __syncwarp();
                if (lane == 0) mbar_arrive(BAR_ONE(sb, ev));
            };
            if (el) { prefetch_map(&mp.h1s); prefetch_map(&mp.o); prefetch_map(&mp.h2s); prefetch_map(&mp.hb); prefetch_map(&mp.out); prefetch_map(&mp.wo); }
            if (el) { flag_set(fl, ep * 8); flag_set(fl + FS, ep * 8); }
            send2(&mp.h1s, ST_H1);
            if (w == 0) TL(47);
            free2();
            if (w == 0) fetch_halo(g_halo + ((m - 1) * 8 + j) * 512 + lane, m == 0, sb, 0, lane);
            else { mbar_wait(BAR_ONE(sb, EV_KV), 0); gate(2, EV_GA); }
            send2(&mp.o, ST_O);
            if (w == 0) TL(40); else TL(38);
            mbar_wait(BAR_ONE(sb, EV_OWN + w), 0);
            if (el) {
#pragma unroll
                for (uint32_t i = 0; i < 2; ++i) {
                    mbar_expect_tx(BAR_SREADY(sb, w * 2 + i), 8192);
                    tma_load3(stg + i * 8192, &mp.x, j * 128 + i * 64, row0 >> 1, BAR_SREADY(sb, w * 2 + i));
                }
            }
            if (w == 1) {
                uint32_t n = 0;
                while ((int32_t)(flag_get(g_flags + FL_LN2) - ep * 8) < 0) { SPIN_GUARD(n); __nanosleep(200); }
                const uint4 v = __ldcg((const uint4*)(g_par2 + j * 128) + lane);
                sts128(sb + OFF_PAR + lane * 16, v.x, v.y, v.z, v.w);
                __syncwarp();
                if (lane == 0) mbar_arrive(BAR_ONE(sb, EV_LN2));
            }
            send2(&mp.h2s, ST_H2);
            if (el) { prefetch_map(&mp.hb); prefetch_map(&mp.hb3); }
            if (w == 0) TL(37);
            free2();
#pragma unroll 1
            for (int p = 0; p < 3; ++p) {
                const int col = hcol(p, j);
                mbar_wait(BAR_SFULL(sb, w * 2), par & 1);
                pause(w ? HD1 : HD0); store(&mp.hb, col);
                pause(HP); store(&mp.hb, col + 64);
                if (p == 0) {
                    pause(HP);
                    mbar_wait(BAR_ONE(sb, EV_P3 + w), 0);
                    if (el) { tma_store3(&mp.hb3, 0, j, row0, sb + (w ? P3_SLOT1 : P3_SLOT0) * SLOT + 24576); bulk_commit(); }
                }
                if (el) { bulk_wait_all(); flag_set(fl, ep * 8 + ST_H + p); flag_set(fl + FS, ep * 8 + ST_H + p); }
                free2();
                if (p == 0 && w == 1) gate(5, EV_GB);
            }
            cluster_arrive_early = true;
            cluster_arrive();
            store(&mp.out, j * 128, true); store(&mp.out, j * 128 + 64, true);
            if (el) bulk_wait_read();
        }
        __syncwarp();
    }
    if (aux || (wg == 2 && !cluster_arrive_early)) cluster_arrive();
    cluster_wait();
    CS(32);
    if (KDEBUG == 5) __syncthreads();
    if (tid == 0) {
        TL(15);
        flag_add(pt.mail->flags + FL_DONE);
    }
}

typedef CUresult (*EncodeFn)(CUtensorMap*, CUtensorMapDataType, cuuint32_t, void*, const cuuint64_t*, const cuuint64_t*, const cuuint32_t*,
                             const cuuint32_t*, CUtensorMapInterleave, CUtensorMapSwizzle, CUtensorMapL2promotion, CUtensorMapFloatOOBfill);

void make_map(EncodeFn fn, CUtensorMap* m, const void* ptr, uint64_t rows, uint64_t cols, uint32_t brows, uint32_t bcols) {
    cuuint64_t dims[2] = {cols, rows}, strides[1] = {cols * 2};
    cuuint32_t box[2] = {bcols, brows}, es[2] = {1, 1};
    fn(m, CU_TENSOR_MAP_DATA_TYPE_BFLOAT16, 2, (void*)ptr, dims, strides, box, es, CU_TENSOR_MAP_INTERLEAVE_NONE,
       bcols == 64 ? CU_TENSOR_MAP_SWIZZLE_128B : bcols == 32 ? CU_TENSOR_MAP_SWIZZLE_64B : CU_TENSOR_MAP_SWIZZLE_NONE, CU_TENSOR_MAP_L2_PROMOTION_L2_256B, CU_TENSOR_MAP_FLOAT_OOB_FILL_NONE);
}

void make_map3(EncodeFn fn, CUtensorMap* m, const void* ptr) {
    cuuint64_t dims[3] = {D_, S_ / 2, 2}, strides[2] = {4 * D_, 2 * D_};
    cuuint32_t box[3] = {64, 32, 2}, es[3] = {1, 1, 1};
    fn(m, CU_TENSOR_MAP_DATA_TYPE_BFLOAT16, 3, (void*)ptr, dims, strides, box, es, CU_TENSOR_MAP_INTERLEAVE_NONE,
       CU_TENSOR_MAP_SWIZZLE_128B, CU_TENSOR_MAP_L2_PROMOTION_L2_256B, CU_TENSOR_MAP_FLOAT_OOB_FILL_NONE);
}

void make_map48(EncodeFn fn, CUtensorMap* m, const void* ptr, uint64_t rows, uint32_t brows) {
    cuuint64_t dims[3] = {48, 8, rows}, strides[2] = {96, 2 * F_};
    cuuint32_t box[3] = {64, 1, brows}, es[3] = {1, 1, 1};
    fn(m, CU_TENSOR_MAP_DATA_TYPE_BFLOAT16, 3, (void*)ptr, dims, strides, box, es, CU_TENSOR_MAP_INTERLEAVE_NONE,
       CU_TENSOR_MAP_SWIZZLE_128B, CU_TENSOR_MAP_L2_PROMOTION_L2_256B, CU_TENSOR_MAP_FLOAT_OOB_FILL_NONE);
}

}

extern "C" void kernel_launch(void* const* d_in, const int* in_sizes, int n_in, void* d_out, int out_size) {
    (void)in_sizes; (void)n_in; (void)out_size;
    void* fnp = nullptr;
    cudaDriverEntryPointQueryResult qr;
    cudaGetDriverEntryPoint("cuTensorMapEncodeTiled", &fnp, cudaEnableDefault, &qr);
    EncodeFn fn = (EncodeFn)fnp;
    void *h1, *o, *h2, *hb, *mail;
    cudaGetSymbolAddress(&h1, g_h1);
    cudaGetSymbolAddress(&mail, g_mail);
    cudaGetSymbolAddress(&o, g_o);
    cudaGetSymbolAddress(&hb, g_hb);
    h2 = H2ALIAS;
    Maps mp;
    make_map(fn, &mp.h1h, h1, S_, D_, 64, 32);
    make_map(fn, &mp.h2h, h2, S_, D_, 64, 32);
    make_map(fn, &mp.h1s, h1, S_, D_, 64, 64);
    make_map(fn, &mp.o, o, S_, D_, 64, 64);
    make_map(fn, &mp.h2l, h2, S_, D_, 128, 32);
    make_map(fn, &mp.h2s, h2, S_, D_, 64, 64);
    make_map(fn, &mp.hb, hb, S_, F_, 64, 64);
    make_map(fn, &mp.wqkv, d_in[1], D_, 3 * D_, 32, 64);
    make_map(fn, &mp.wo, d_in[2], D_, D_, 64, 64);
    make_map(fn, &mp.wg, d_in[4], D_, F_, 32, 64);
    make_map(fn, &mp.wu, d_in[5], D_, F_, 32, 64);
    make_map(fn, &mp.wd, d_in[6], F_, D_, 64, 64);
    make_map(fn, &mp.wmod, d_in[8], D_, 6 * D_, 64, 64);
    make_map(fn, &mp.wm8, d_in[8], D_ / 8, 8 * 6 * D_, 128, 16);
    make_map3(fn, &mp.x, d_in[0]);
    make_map3(fn, &mp.out, d_out);
    make_map48(fn, &mp.wg3, d_in[4], D_, 32);
    make_map48(fn, &mp.wu3, d_in[5], D_, 32);
    make_map48(fn, &mp.hb3, hb, S_, 64);
    cudaFuncSetAttribute(fused_block_kernel, cudaFuncAttributeMaxDynamicSharedMemorySize, SMEM_BYTES);
    cudaLaunchConfig_t cfg = {};
    cfg.gridDim = dim3(NCTA); cfg.blockDim = dim3(384); cfg.dynamicSmemBytes = SMEM_BYTES; cfg.stream = cudaStreamPerThread;
    cudaLaunchAttribute at[1];
    at[0].id = cudaLaunchAttributeClusterDimension; at[0].val.clusterDim.x = 2; at[0].val.clusterDim.y = 1; at[0].val.clusterDim.z = 1;
    cfg.attrs = at; cfg.numAttrs = 1;
    const Ptrs pt{(const __nv_bfloat16*)d_in[7], (Mail*)mail};
    cudaLaunchKernelEx(&cfg, fused_block_kernel, pt, mp);
}
```

```cpp
#include <cuda_runtime.h>
#include <cuda_bf16.h>
#include <cuda.h>
#include <stdint.h>
#include <stddef.h>

#define LAG 4
#define LAGS 4
#define LAGW 3
#define LAGQ 4
#define MIDW 8
#define PFWO 14
#define FLAGRED 1
#define FS 1
#define P1H 2000
#define AGW 6
#define CSW 0
#define FENCES 1
#define LWAIT 2
#define BW0 0
#define BWEV EV_WIN
#define GODLY 0
#define BW1 3
#define PDLY 500
#define H2ALIAS o
#define HD1 5500
#define HD0 5500
#define HP 2200
#define LAGD 4
#define MIDD 44
#define KDEBUG 0

namespace {

constexpr int S_ = 2048, D_ = 1024, F_ = 3584;
constexpr int NCTA = 132;
constexpr int NSLOT = 6;
constexpr uint32_t SLOT = 32768;
constexpr uint32_t OFF_STG = NSLOT * SLOT;
constexpr uint32_t OFF_BAR = OFF_STG + 32768;
constexpr uint32_t OFF_PAR = OFF_BAR + 512;
constexpr uint32_t OFF_TAB = OFF_PAR + 768;
constexpr uint32_t OFF_TL = OFF_PAR + 2048;
constexpr uint32_t SMEM_BYTES = OFF_TL + (KDEBUG ? 512 : 0);
constexpr uint32_t P3_SLOT1 = (32 + 16 + 32) % NSLOT, P3_SLOT0 = (P3_SLOT1 + 1) % NSLOT;

constexpr int ST_H1 = 1, ST_O = 2, ST_H2 = 3, ST_H = 4, FL_DONE = 0, FL_LN2 = 1, FL_AUX = 32, FL_PROG = 64;

struct Maps {
    CUtensorMap h1h, h1s, o, h2h, h2l, h2s, hb, wqkv, wo, wg, wu, wd, wmod, wm8, x, out, wg3, wu3, hb3;
};

struct Mail {
    uint32_t flags[16 * 32 * FS + 64];
    uint2 mod[6 * D_ / 2];
    uint4 mod1[8 * 512];
    uint4 st1[128 * 512];
    uint32_t par2[D_];
    uint4 halo[128 * 512];
};
struct Ptrs { const __nv_bfloat16* c; Mail* mail; };

__device__ __align__(128) Mail g_mail;
__device__ __align__(128) __nv_bfloat16 g_h1[S_ * D_];
__device__ __align__(128) __nv_bfloat16 g_o[S_ * D_];
__device__ __align__(128) __nv_bfloat16 g_hb[S_ * F_];
#define TL(i) do {} while (0)
#define TC(i) do {} while (0)
#define TS(g, which) do {} while (0)
#define CS(i) do {} while (0)

#define PS(i) do {} while (0)
__device__ __forceinline__ uint32_t smem_u32(const void* p) { return (uint32_t)__cvta_generic_to_shared(p); }
__device__ __forceinline__ void mbar_init(uint32_t bar, uint32_t cnt) { asm volatile("mbarrier.init.shared::cta.b64 [%0], %1;" :: "r"(bar), "r"(cnt) : "memory"); }
__device__ __forceinline__ void mbar_expect_tx(uint32_t bar, uint32_t bytes) { asm volatile("mbarrier.arrive.expect_tx.shared::cta.b64 _, [%0], %1;" :: "r"(bar), "r"(bytes) : "memory"); }
__device__ __forceinline__ void mbar_arrive(uint32_t bar) { asm volatile("mbarrier.arrive.shared::cta.b64 _, [%0];" :: "r"(bar) : "memory"); }
__device__ __forceinline__ void mbar_arrive_cta(uint32_t bar, uint32_t cta) {
    asm volatile("{\n.reg .b32 r;\nmapa.shared::cluster.u32 r, %0, %1;\nmbarrier.arrive.shared::cluster.b64 _, [r];\n}" :: "r"(bar), "r"(cta) : "memory");
}
__device__ __forceinline__ void mbar_wait(uint32_t bar, uint32_t parity) {
    asm volatile("{\n.reg .pred p;\n.reg .u32 n;\nmov.u32 n, 0;\n"
        "W_LOOP:\nmbarrier.try_wait.parity.shared::cta.b64 p, [%0], %1;\n@p bra W_DONE;\n"
        "add.u32 n, n, 1;\nsetp.lt.u32 p, n, 0x400000;\n@p bra W_LOOP;\ntrap;\nW_DONE:\n}" :: "r"(bar), "r"(parity) : "memory");
}
__device__ __forceinline__ void mbar_wait2(uint32_t b0, uint32_t b1, uint32_t parity) {
    asm volatile("{\n.reg .pred p, q;\n.reg .u32 n;\nmov.u32 n, 0;\n"
        "W_LOOP:\nmbarrier.try_wait.parity.shared::cta.b64 p, [%0], %2;\nmbarrier.try_wait.parity.shared::cta.b64 q, [%1], %2;\nand.pred p, p, q;\n@p bra W_DONE;\n"
        "add.u32 n, n, 1;\nsetp.lt.u32 p, n, 0x400000;\n@p bra W_LOOP;\ntrap;\nW_DONE:\n}" :: "r"(b0), "r"(b1), "r"(parity) : "memory");
}
__device__ __forceinline__ bool mbar_test(uint32_t bar, uint32_t parity) {
    uint32_t r; asm volatile("{\n.reg .pred p;\nmbarrier.test_wait.parity.shared::cta.b64 p, [%1], %2;\nselp.u32 %0, 1, 0, p;\n}" : "=r"(r) : "r"(bar), "r"(parity) : "memory"); return r;
}
__device__ __forceinline__ bool mbar_test2(uint32_t b0, uint32_t b1, uint32_t parity) {
    uint32_t r;
    asm volatile("{\n.reg .pred p, q;\nmbarrier.test_wait.parity.shared::cta.b64 p, [%1], %3;\nmbarrier.test_wait.parity.shared::cta.b64 q, [%2], %3;\n"
        "and.pred p, p, q;\nselp.u32 %0, 1, 0, p;\n}" : "=r"(r) : "r"(b0), "r"(b1), "r"(parity) : "memory");
    return r;
}
__device__ __forceinline__ void tma_load3(uint32_t dst, const CUtensorMap* m, int c0, int c1, uint32_t bar) {
    asm volatile("cp.async.bulk.tensor.3d.shared::cluster.global.mbarrier::complete_tx::bytes [%0], [%1, {%3, %4, %5}], [%2];"
        :: "r"(dst), "l"(m), "r"(bar), "r"(c0), "r"(c1), "r"(0) : "memory");
}
__device__ __forceinline__ void tma_store3(const CUtensorMap* m, int c0, int c1, int c2, uint32_t src) {
    asm volatile("cp.async.bulk.tensor.3d.global.shared::cta.bulk_group [%0, {%2, %3, %4}], [%1];" :: "l"(m), "r"(src), "r"(c0), "r"(c1), "r"(c2) : "memory");
}
__device__ __forceinline__ void tma_load3_mc(uint32_t dst, const CUtensorMap* m, int c1, int c2, uint32_t bar) {
    asm volatile("cp.async.bulk.tensor.3d.shared::cluster.global.mbarrier::complete_tx::bytes.multicast::cluster.L2::cache_hint [%0], [%1, {%3, %4, %5}], [%2], %6, %7;"
        :: "r"(dst), "l"(m), "r"(bar), "r"(0), "r"(c1), "r"(c2), "h"((uint16_t)3), "l"(0x12F0000000000000ull) : "memory");
}
__device__ __forceinline__ void tma_load(uint32_t dst, const CUtensorMap* m, int c0, int c1, uint32_t bar) {
    asm volatile("cp.async.bulk.tensor.2d.shared::cluster.global.mbarrier::complete_tx::bytes [%0], [%1, {%3, %4}], [%2];"
        :: "r"(dst), "l"(m), "r"(bar), "r"(c0), "r"(c1) : "memory");
}
__device__ __forceinline__ void tma_load_mc(uint32_t dst, const CUtensorMap* m, int c0, int c1, uint32_t bar) {
    asm volatile("cp.async.bulk.tensor.2d.shared::cluster.global.mbarrier::complete_tx::bytes.multicast::cluster.L2::cache_hint [%0], [%1, {%3, %4}], [%2], %5, %6;"
        :: "r"(dst), "l"(m), "r"(bar), "r"(c0), "r"(c1), "h"((uint16_t)3), "l"(0x12F0000000000000ull) : "memory");
}
__device__ __forceinline__ void tma_prefetch(const CUtensorMap* m, int c0, int c1) {
    asm volatile("cp.async.bulk.prefetch.tensor.2d.L2.global [%0, {%1, %2}];" :: "l"(m), "r"(c0), "r"(c1) : "memory");
}
__device__ __forceinline__ void tma_store(const CUtensorMap* m, int c0, int c1, uint32_t src) {
    asm volatile("cp.async.bulk.tensor.2d.global.shared::cta.bulk_group [%0, {%2, %3}], [%1];" :: "l"(m), "r"(src), "r"(c0), "r"(c1) : "memory");
}
__device__ __forceinline__ void bulk_commit() { asm volatile("cp.async.bulk.commit_group;" ::: "memory"); }
__device__ __forceinline__ void bulk_wait_read() { asm volatile("cp.async.bulk.wait_group.read 0;" ::: "memory"); }
__device__ __forceinline__ void bulk_wait_all() { asm volatile("cp.async.bulk.wait_group 0;" ::: "memory"); }
__device__ __forceinline__ void fence_async_smem() { asm volatile("fence.proxy.async.shared::cta;" ::: "memory"); }
__device__ __forceinline__ void prefetch_map(const CUtensorMap* m) { asm volatile("prefetch.tensormap [%0];" :: "l"(m) : "memory"); }
__device__ __forceinline__ void wg_fence() { asm volatile("wgmma.fence.sync.aligned;" ::: "memory"); }
__device__ __forceinline__ void wg_commit() { asm volatile("wgmma.commit_group.sync.aligned;" ::: "memory"); }
template <int N> __device__ __forceinline__ void wg_wait() { asm volatile("wgmma.wait_group.sync.aligned %0;" :: "n"(N) : "memory"); }
__device__ __forceinline__ void bar_sync(int id, int n) { asm volatile("bar.sync %0, %1;" :: "r"(id), "r"(n) : "memory"); }
__device__ __forceinline__ void bar_arrive(int id, int n) { asm volatile("bar.arrive %0, %1;" :: "r"(id), "r"(n) : "memory"); }
__device__ __forceinline__ void flag_add(uint32_t* f) { asm volatile("red.relaxed.gpu.global.add.u32 [%0], 1;" :: "l"(f) : "memory"); }
__device__ __forceinline__ void flag_set(uint32_t* f, uint32_t v) { asm volatile("red.relaxed.gpu.global.max.u32 [%0], %1;" :: "l"(f), "r"(v) : "memory"); }
__device__ __forceinline__ uint32_t flag_get(const uint32_t* f) { uint32_t v; asm volatile("ld.relaxed.gpu.global.u32 %0, [%1];" : "=r"(v) : "l"(f) : "memory"); return v; }
__device__ __forceinline__ uint32_t d16(uint32_t addr) { return (addr & 0x3FFFF) >> 4; }
__device__ __forceinline__ uint64_t mk_desc(uint32_t a16, uint32_t off, uint32_t lbo, uint32_t sbo, uint32_t swz) {
    const uint32_t lo = a16 + (off >> 4) + ((lbo >> 4) << 16), hi = (sbo >> 4) | (swz << 30);
    return ((uint64_t)hi << 32) | lo;
}
__device__ __forceinline__ uint32_t pack2(float lo, float hi) {
    uint32_t r; asm("cvt.rn.bf16x2.f32 %0, %1, %2;" : "=r"(r) : "f"(hi), "f"(lo)); return r;
}
__device__ __forceinline__ uint32_t hfma2_bf16(uint32_t a, uint32_t b, uint32_t c) {
    uint32_t r; asm("fma.rn.bf16x2 %0, %1, %2, %3;" : "=r"(r) : "r"(a), "r"(b), "r"(c)); return r;
}
__device__ __forceinline__ float bf_lo(uint32_t v) { return __uint_as_float(v << 16); }
__device__ __forceinline__ float bf_hi(uint32_t v) { return __uint_as_float(v & 0xFFFF0000u); }
__device__ __forceinline__ void unpack2(uint32_t v, float& lo, float& hi) {
    asm volatile("shl.b32 %0, %2, 16;\nand.b32 %1, %2, 0xffff0000;" : "=f"(lo), "=f"(hi) : "r"(v));
}
__device__ __forceinline__ float bf_round(float x) { return __bfloat162float(__float2bfloat16_rn(x)); }
__device__ __forceinline__ void stsm4(uint32_t addr, uint32_t r0, uint32_t r1, uint32_t r2, uint32_t r3) {
    asm volatile("stmatrix.sync.aligned.m8n8.x4.shared.b16 [%0], {%1, %2, %3, %4};" :: "r"(addr), "r"(r0), "r"(r1), "r"(r2), "r"(r3) : "memory");
}
__device__ __forceinline__ void stsm4t(uint32_t addr, uint32_t r0, uint32_t r1, uint32_t r2, uint32_t r3) {
    asm volatile("stmatrix.sync.aligned.m8n8.x4.trans.shared.b16 [%0], {%1, %2, %3, %4};" :: "r"(addr), "r"(r0), "r"(r1), "r"(r2), "r"(r3) : "memory");
}
__device__ __forceinline__ uint32_t movm(uint32_t a) { uint32_t d; asm volatile("movmatrix.sync.aligned.m8n8.trans.b16 %0, %1;" : "=r"(d) : "r"(a)); return d; }
__device__ __forceinline__ void ldsm4(uint32_t addr, uint32_t& r0, uint32_t& r1, uint32_t& r2, uint32_t& r3) {
    asm volatile("ldmatrix.sync.aligned.m8n8.x4.shared.b16 {%0, %1, %2, %3}, [%4];" : "=r"(r0), "=r"(r1), "=r"(r2), "=r"(r3) : "r"(addr) : "memory");
}
__device__ __forceinline__ void ldsm4t(uint32_t addr, uint32_t& r0, uint32_t& r1, uint32_t& r2, uint32_t& r3) {
    asm volatile("ldmatrix.sync.aligned.m8n8.x4.trans.shared.b16 {%0, %1, %2, %3}, [%4];" : "=r"(r0), "=r"(r1), "=r"(r2), "=r"(r3) : "r"(addr) : "memory");
}
__device__ __forceinline__ void mma16816(float (&c)[4], uint32_t a0, uint32_t a1, uint32_t a2, uint32_t a3, uint32_t b0, uint32_t b1) {
    asm("mma.sync.aligned.m16n8k16.row.col.f32.bf16.bf16.f32 {%0, %1, %2, %3}, {%4, %5, %6, %7}, {%8, %9}, {%0, %1, %2, %3};"
        : "+f"(c[0]), "+f"(c[1]), "+f"(c[2]), "+f"(c[3]) : "r"(a0), "r"(a1), "r"(a2), "r"(a3), "r"(b0), "r"(b1));
}
__device__ __forceinline__ float rcp(float x) { float r; asm("rcp.approx.ftz.f32 %0, %1;" : "=f"(r) : "f"(x)); return r; }
__device__ __forceinline__ float ex2(float x) { float r; asm("ex2.approx.ftz.f32 %0, %1;" : "=f"(r) : "f"(x)); return r; }
__device__ __forceinline__ float tanh_(float x) { float t; asm("tanh.approx.f32 %0, %1;" : "=f"(t) : "f"(x)); return t; }
__device__ __forceinline__ float silu_(float x) { return __fdividef(x, 1.f + __expf(-x)); }
__device__ __forceinline__ void st_pkt(void* p, uint32_t a, uint32_t b) {
    asm volatile("{\n.reg .b64 t;\nmov.b64 t, {%1, %2};\nst.relaxed.gpu.global.b64 [%0], t;\n}" :: "l"(p), "r"(a), "r"(b) : "memory");
}
__device__ __forceinline__ uint4 ld_pkt2(const void* p) {
    uint4 v; asm volatile("{\n.reg .b64 t, u;\nld.relaxed.gpu.global.v2.b64 {t, u}, [%4];\nmov.b64 {%0, %1}, t;\nmov.b64 {%2, %3}, u;\n}"
        : "=r"(v.x), "=r"(v.y), "=r"(v.z), "=r"(v.w) : "l"(p) : "memory"); return v;
}
__device__ __forceinline__ void st_pkt16(void* p, uint32_t a, uint32_t b, uint32_t c, uint32_t d) {
    asm volatile("{\n.reg .b64 t, u;\n.reg .b128 w;\nmov.b64 t, {%1, %2};\nmov.b64 u, {%3, %4};\nmov.b128 w, {t, u};\nst.relaxed.gpu.global.b128 [%0], w;\n}"
        :: "l"(p), "r"(a), "r"(b), "r"(c), "r"(d) : "memory");
}
__device__ __forceinline__ uint4 ld_pkt16(const void* p) {
    uint4 v; asm volatile("{\n.reg .b64 t, u;\n.reg .b128 w;\nld.relaxed.gpu.global.b128 w, [%4];\nmov.b128 {t, u}, w;\nmov.b64 {%0, %1}, t;\nmov.b64 {%2, %3}, u;\n}"
        : "=r"(v.x), "=r"(v.y), "=r"(v.z), "=r"(v.w) : "l"(p) : "memory"); return v;
}
#define SPIN_GUARD(n) do { if (++(n) > (1u << 22)) asm volatile("trap;"); } while (0)
__device__ __forceinline__ uint4 lds128(uint32_t a) { uint4 v; asm volatile("ld.shared.v4.u32 {%0, %1, %2, %3}, [%4];" : "=r"(v.x), "=r"(v.y), "=r"(v.z), "=r"(v.w) : "r"(a) : "memory"); return v; }
__device__ __forceinline__ void sts128(uint32_t a, uint32_t x, uint32_t y, uint32_t z, uint32_t w) { asm volatile("st.shared.v4.u32 [%0], {%1, %2, %3, %4};" :: "r"(a), "r"(x), "r"(y), "r"(z), "r"(w) : "memory"); }
__device__ __forceinline__ uint32_t lds32(uint32_t a) { uint32_t v; asm volatile("ld.shared.u32 %0, [%1];" : "=r"(v) : "r"(a) : "memory"); return v; }
__device__ __forceinline__ void sts32(uint32_t a, uint32_t v) { asm volatile("st.shared.u32 [%0], %1;" :: "r"(a), "r"(v) : "memory"); }
__device__ __forceinline__ bool elect_one() {
    uint32_t p; asm volatile("{\n.reg .pred q;\nelect.sync _|q, 0xffffffff;\nselp.u32 %0, 1, 0, q;\n}" : "=r"(p)); return p;
}
__device__ __forceinline__ void pause(uint32_t cycles) {
    uint32_t t0, t; asm volatile("mov.u32 %0, %%clock;" : "=r"(t0));
    do { __nanosleep(64); asm volatile("mov.u32 %0, %%clock;" : "=r"(t)); } while (t - t0 < cycles);
}
__device__ __forceinline__ void cluster_arrive() { asm volatile("barrier.cluster.arrive.relaxed.aligned;" ::: "memory"); }
__device__ __forceinline__ void cluster_wait() { asm volatile("barrier.cluster.wait.aligned;" ::: "memory"); }

__device__ __forceinline__ void wgmma_n128_z(float (&d)[64], uint64_t da, uint64_t db) {
    asm volatile("{\n.reg .pred p;\nsetp.ne.b32 p, 0, 0;\n"
        "wgmma.mma_async.sync.aligned.m64n128k16.f32.bf16.bf16 {"
        "%0, %1, %2, %3, %4, %5, %6, %7, %8, %9, %10, %11, %12, %13, %14, %15, "
        "%16, %17, %18, %19, %20, %21, %22, %23, %24, %25, %26, %27, %28, %29, %30, %31, "
        "%32, %33, %34, %35, %36, %37, %38, %39, %40, %41, %42, %43, %44, %45, %46, %47, "
        "%48, %49, %50, %51, %52, %53, %54, %55, %56, %57, %58, %59, %60, %61, %62, %63"
        "}, %64, %65, p, 1, 1, 0, 1;\n}\n"
        : "=f"(d[0]), "=f"(d[1]), "=f"(d[2]), "=f"(d[3]), "=f"(d[4]), "=f"(d[5]), "=f"(d[6]), "=f"(d[7]),
          "=f"(d[8]), "=f"(d[9]), "=f"(d[10]), "=f"(d[11]), "=f"(d[12]), "=f"(d[13]), "=f"(d[14]), "=f"(d[15]),
          "=f"(d[16]), "=f"(d[17]), "=f"(d[18]), "=f"(d[19]), "=f"(d[20]), "=f"(d[21]), "=f"(d[22]), "=f"(d[23]),
          "=f"(d[24]), "=f"(d[25]), "=f"(d[26]), "=f"(d[27]), "=f"(d[28]), "=f"(d[29]), "=f"(d[30]), "=f"(d[31]),
          "=f"(d[32]), "=f"(d[33]), "=f"(d[34]), "=f"(d[35]), "=f"(d[36]), "=f"(d[37]), "=f"(d[38]), "=f"(d[39]),
          "=f"(d[40]), "=f"(d[41]), "=f"(d[42]), "=f"(d[43]), "=f"(d[44]), "=f"(d[45]), "=f"(d[46]), "=f"(d[47]),
          "=f"(d[48]), "=f"(d[49]), "=f"(d[50]), "=f"(d[51]), "=f"(d[52]), "=f"(d[53]), "=f"(d[54]), "=f"(d[55]),
          "=f"(d[56]), "=f"(d[57]), "=f"(d[58]), "=f"(d[59]), "=f"(d[60]), "=f"(d[61]), "=f"(d[62]), "=f"(d[63])
        : "l"(da), "l"(db));
}
__device__ __forceinline__ void wgmma_n128(float (&d)[64], uint64_t da, uint64_t db) {
    asm volatile("{\n.reg .pred p;\nsetp.eq.b32 p, 0, 0;\n"
        "wgmma.mma_async.sync.aligned.m64n128k16.f32.bf16.bf16 {"
        "%0, %1, %2, %3, %4, %5, %6, %7, %8, %9, %10, %11, %12, %13, %14, %15, "
        "%16, %17, %18, %19, %20, %21, %22, %23, %24, %25, %26, %27, %28, %29, %30, %31, "
        "%32, %33, %34, %35, %36, %37, %38, %39, %40, %41, %42, %43, %44, %45, %46, %47, "
        "%48, %49, %50, %51, %52, %53, %54, %55, %56, %57, %58, %59, %60, %61, %62, %63"
        "}, %64, %65, p, 1, 1, 0, 1;\n}\n"
        : "+f"(d[0]), "+f"(d[1]), "+f"(d[2]), "+f"(d[3]), "+f"(d[4]), "+f"(d[5]), "+f"(d[6]), "+f"(d[7]),
          "+f"(d[8]), "+f"(d[9]), "+f"(d[10]), "+f"(d[11]), "+f"(d[12]), "+f"(d[13]), "+f"(d[14]), "+f"(d[15]),
          "+f"(d[16]), "+f"(d[17]), "+f"(d[18]), "+f"(d[19]), "+f"(d[20]), "+f"(d[21]), "+f"(d[22]), "+f"(d[23]),
          "+f"(d[24]), "+f"(d[25]), "+f"(d[26]), "+f"(d[27]), "+f"(d[28]), "+f"(d[29]), "+f"(d[30]), "+f"(d[31]),
          "+f"(d[32]), "+f"(d[33]), "+f"(d[34]), "+f"(d[35]), "+f"(d[36]), "+f"(d[37]), "+f"(d[38]), "+f"(d[39]),
          "+f"(d[40]), "+f"(d[41]), "+f"(d[42]), "+f"(d[43]), "+f"(d[44]), "+f"(d[45]), "+f"(d[46]), "+f"(d[47]),
          "+f"(d[48]), "+f"(d[49]), "+f"(d[50]), "+f"(d[51]), "+f"(d[52]), "+f"(d[53]), "+f"(d[54]), "+f"(d[55]),
          "+f"(d[56]), "+f"(d[57]), "+f"(d[58]), "+f"(d[59]), "+f"(d[60]), "+f"(d[61]), "+f"(d[62]), "+f"(d[63])
        : "l"(da), "l"(db));
}
__device__ __forceinline__ void wgmma_n176_z(float (&d)[88], uint64_t da, uint64_t db) {
    asm volatile("{\n.reg .pred p;\nsetp.ne.b32 p, 0, 0;\n"
        "wgmma.mma_async.sync.aligned.m64n176k16.f32.bf16.bf16 {"
        "%0, %1, %2, %3, %4, %5, %6, %7, %8, %9, %10, %11, %12, %13, %14, %15, "
        "%16, %17, %18, %19, %20, %21, %22, %23, %24, %25, %26, %27, %28, %29, %30, %31, "
        "%32, %33, %34, %35, %36, %37, %38, %39, %40, %41, %42, %43, %44, %45, %46, %47, "
        "%48, %49, %50, %51, %52, %53, %54, %55, %56, %57, %58, %59, %60, %61, %62, %63, "
        "%64, %65, %66, %67, %68, %69, %70, %71, %72, %73, %74, %75, %76, %77, %78, %79, "
        "%80, %81, %82, %83, %84, %85, %86, %87"
        "}, %88, %89, p, 1, 1, 0, 1;\n}\n"
        : "=f"(d[0]), "=f"(d[1]), "=f"(d[2]), "=f"(d[3]), "=f"(d[4]), "=f"(d[5]), "=f"(d[6]), "=f"(d[7]),
          "=f"(d[8]), "=f"(d[9]), "=f"(d[10]), "=f"(d[11]), "=f"(d[12]), "=f"(d[13]), "=f"(d[14]), "=f"(d[15]),
          "=f"(d[16]), "=f"(d[17]), "=f"(d[18]), "=f"(d[19]), "=f"(d[20]), "=f"(d[21]), "=f"(d[22]), "=f"(d[23]),
          "=f"(d[24]), "=f"(d[25]), "=f"(d[26]), "=f"(d[27]), "=f"(d[28]), "=f"(d[29]), "=f"(d[30]), "=f"(d[31]),
          "=f"(d[32]), "=f"(d[33]), "=f"(d[34]), "=f"(d[35]), "=f"(d[36]), "=f"(d[37]), "=f"(d[38]), "=f"(d[39]),
          "=f"(d[40]), "=f"(d[41]), "=f"(d[42]), "=f"(d[43]), "=f"(d[44]), "=f"(d[45]), "=f"(d[46]), "=f"(d[47]),
          "=f"(d[48]), "=f"(d[49]), "=f"(d[50]), "=f"(d[51]), "=f"(d[52]), "=f"(d[53]), "=f"(d[54]), "=f"(d[55]),
          "=f"(d[56]), "=f"(d[57]), "=f"(d[58]), "=f"(d[59]), "=f"(d[60]), "=f"(d[61]), "=f"(d[62]), "=f"(d[63]),
          "=f"(d[64]), "=f"(d[65]), "=f"(d[66]), "=f"(d[67]), "=f"(d[68]), "=f"(d[69]), "=f"(d[70]), "=f"(d[71]),
          "=f"(d[72]), "=f"(d[73]), "=f"(d[74]), "=f"(d[75]), "=f"(d[76]), "=f"(d[77]), "=f"(d[78]), "=f"(d[79]),
          "=f"(d[80]), "=f"(d[81]), "=f"(d[82]), "=f"(d[83]), "=f"(d[84]), "=f"(d[85]), "=f"(d[86]), "=f"(d[87])
        : "l"(da), "l"(db));
}
__device__ __forceinline__ void wgmma_n176(float (&d)[88], uint64_t da, uint64_t db) {
    asm volatile("{\n.reg .pred p;\nsetp.eq.b32 p, 0, 0;\n"
        "wgmma.mma_async.sync.aligned.m64n176k16.f32.bf16.bf16 {"
        "%0, %1, %2, %3, %4, %5, %6, %7, %8, %9, %10, %11, %12, %13, %14, %15, "
        "%16, %17, %18, %19, %20, %21, %22, %23, %24, %25, %26, %27, %28, %29, %30, %31, "
        "%32, %33, %34, %35, %36, %37, %38, %39, %40, %41, %42, %43, %44, %45, %46, %47, "
        "%48, %49, %50, %51, %52, %53, %54, %55, %56, %57, %58, %59, %60, %61, %62, %63, "
        "%64, %65, %66, %67, %68, %69, %70, %71, %72, %73, %74, %75, %76, %77, %78, %79, "
        "%80, %81, %82, %83, %84, %85, %86, %87"
        "}, %88, %89, p, 1, 1, 0, 1;\n}\n"
        : "+f"(d[0]), "+f"(d[1]), "+f"(d[2]), "+f"(d[3]), "+f"(d[4]), "+f"(d[5]), "+f"(d[6]), "+f"(d[7]),
          "+f"(d[8]), "+f"(d[9]), "+f"(d[10]), "+f"(d[11]), "+f"(d[12]), "+f"(d[13]), "+f"(d[14]), "+f"(d[15]),
          "+f"(d[16]), "+f"(d[17]), "+f"(d[18]), "+f"(d[19]), "+f"(d[20]), "+f"(d[21]), "+f"(d[22]), "+f"(d[23]),
          "+f"(d[24]), "+f"(d[25]), "+f"(d[26]), "+f"(d[27]), "+f"(d[28]), "+f"(d[29]), "+f"(d[30]), "+f"(d[31]),
          "+f"(d[32]), "+f"(d[33]), "+f"(d[34]), "+f"(d[35]), "+f"(d[36]), "+f"(d[37]), "+f"(d[38]), "+f"(d[39]),
          "+f"(d[40]), "+f"(d[41]), "+f"(d[42]), "+f"(d[43]), "+f"(d[44]), "+f"(d[45]), "+f"(d[46]), "+f"(d[47]),
          "+f"(d[48]), "+f"(d[49]), "+f"(d[50]), "+f"(d[51]), "+f"(d[52]), "+f"(d[53]), "+f"(d[54]), "+f"(d[55]),
          "+f"(d[56]), "+f"(d[57]), "+f"(d[58]), "+f"(d[59]), "+f"(d[60]), "+f"(d[61]), "+f"(d[62]), "+f"(d[63]),
          "+f"(d[64]), "+f"(d[65]), "+f"(d[66]), "+f"(d[67]), "+f"(d[68]), "+f"(d[69]), "+f"(d[70]), "+f"(d[71]),
          "+f"(d[72]), "+f"(d[73]), "+f"(d[74]), "+f"(d[75]), "+f"(d[76]), "+f"(d[77]), "+f"(d[78]), "+f"(d[79]),
          "+f"(d[80]), "+f"(d[81]), "+f"(d[82]), "+f"(d[83]), "+f"(d[84]), "+f"(d[85]), "+f"(d[86]), "+f"(d[87])
        : "l"(da), "l"(db));
}
__device__ __forceinline__ void wgmma_n256_z(float (&d)[128], uint64_t da, uint64_t db) {
    asm volatile("{\n.reg .pred p;\nsetp.ne.b32 p, 0, 0;\n"
        "wgmma.mma_async.sync.aligned.m64n256k16.f32.bf16.bf16 {"
        "%0, %1, %2, %3, %4, %5, %6, %7, %8, %9, %10, %11, %12, %13, %14, %15, "
        "%16, %17, %18, %19, %20, %21, %22, %23, %24, %25, %26, %27, %28, %29, %30, %31, "
        "%32, %33, %34, %35, %36, %37, %38, %39, %40, %41, %42, %43, %44, %45, %46, %47, "
        "%48, %49, %50, %51, %52, %53, %54, %55, %56, %57, %58, %59, %60, %61, %62, %63, "
        "%64, %65, %66, %67, %68, %69, %70, %71, %72, %73, %74, %75, %76, %77, %78, %79, "
        "%80, %81, %82, %83, %84, %85, %86, %87, %88, %89, %90, %91, %92, %93, %94, %95, "
        "%96, %97, %98, %99, %100, %101, %102, %103, %104, %105, %106, %107, %108, %109, %110, %111, "
        "%112, %113, %114, %115, %116, %117, %118, %119, %120, %121, %122, %123, %124, %125, %126, %127"
        "}, %128, %129, p, 1, 1, 0, 1;\n}\n"
        : "=f"(d[0]), "=f"(d[1]), "=f"(d[2]), "=f"(d[3]), "=f"(d[4]), "=f"(d[5]), "=f"(d[6]), "=f"(d[7]),
          "=f"(d[8]), "=f"(d[9]), "=f"(d[10]), "=f"(d[11]), "=f"(d[12]), "=f"(d[13]), "=f"(d[14]), "=f"(d[15]),
          "=f"(d[16]), "=f"(d[17]), "=f"(d[18]), "=f"(d[19]), "=f"(d[20]), "=f"(d[21]), "=f"(d[22]), "=f"(d[23]),
          "=f"(d[24]), "=f"(d[25]), "=f"(d[26]), "=f"(d[27]), "=f"(d[28]), "=f"(d[29]), "=f"(d[30]), "=f"(d[31]),
          "=f"(d[32]), "=f"(d[33]), "=f"(d[34]), "=f"(d[35]), "=f"(d[36]), "=f"(d[37]), "=f"(d[38]), "=f"(d[39]),
          "=f"(d[40]), "=f"(d[41]), "=f"(d[42]), "=f"(d[43]), "=f"(d[44]), "=f"(d[45]), "=f"(d[46]), "=f"(d[47]),
          "=f"(d[48]), "=f"(d[49]), "=f"(d[50]), "=f"(d[51]), "=f"(d[52]), "=f"(d[53]), "=f"(d[54]), "=f"(d[55]),
          "=f"(d[56]), "=f"(d[57]), "=f"(d[58]), "=f"(d[59]), "=f"(d[60]), "=f"(d[61]), "=f"(d[62]), "=f"(d[63]),
          "=f"(d[64]), "=f"(d[65]), "=f"(d[66]), "=f"(d[67]), "=f"(d[68]), "=f"(d[69]), "=f"(d[70]), "=f"(d[71]),
          "=f"(d[72]), "=f"(d[73]), "=f"(d[74]), "=f"(d[75]), "=f"(d[76]), "=f"(d[77]), "=f"(d[78]), "=f"(d[79]),
          "=f"(d[80]), "=f"(d[81]), "=f"(d[82]), "=f"(d[83]), "=f"(d[84]), "=f"(d[85]), "=f"(d[86]), "=f"(d[87]),
          "=f"(d[88]), "=f"(d[89]), "=f"(d[90]), "=f"(d[91]), "=f"(d[92]), "=f"(d[93]), "=f"(d[94]), "=f"(d[95]),
          "=f"(d[96]), "=f"(d[97]), "=f"(d[98]), "=f"(d[99]), "=f"(d[100]), "=f"(d[101]), "=f"(d[102]), "=f"(d[103]),
          "=f"(d[104]), "=f"(d[105]), "=f"(d[106]), "=f"(d[107]), "=f"(d[108]), "=f"(d[109]), "=f"(d[110]), "=f"(d[111]),
          "=f"(d[112]), "=f"(d[113]), "=f"(d[114]), "=f"(d[115]), "=f"(d[116]), "=f"(d[117]), "=f"(d[118]), "=f"(d[119]),
          "=f"(d[120]), "=f"(d[121]), "=f"(d[122]), "=f"(d[123]), "=f"(d[124]), "=f"(d[125]), "=f"(d[126]), "=f"(d[127])
        : "l"(da), "l"(db));
}
__device__ __forceinline__ void wgmma_n256(float (&d)[128], uint64_t da, uint64_t db) {
    asm volatile("{\n.reg .pred p;\nsetp.eq.b32 p, 0, 0;\n"
        "wgmma.mma_async.sync.aligned.m64n256k16.f32.bf16.bf16 {"
        "%0, %1, %2, %3, %4, %5, %6, %7, %8, %9, %10, %11, %12, %13, %14, %15, "
        "%16, %17, %18, %19, %20, %21, %22, %23, %24, %25, %26, %27, %28, %29, %30, %31, "
        "%32, %33, %34, %35, %36, %37, %38, %39, %40, %41, %42, %43, %44, %45, %46, %47, "
        "%48, %49, %50, %51, %52, %53, %54, %55, %56, %57, %58, %59, %60, %61, %62, %63, "
        "%64, %65, %66, %67, %68, %69, %70, %71, %72, %73, %74, %75, %76, %77, %78, %79, "
        "%80, %81, %82, %83, %84, %85, %86, %87, %88, %89, %90, %91, %92, %93, %94, %95, "
        "%96, %97, %98, %99, %100, %101, %102, %103, %104, %105, %106, %107, %108, %109, %110, %111, "
        "%112, %113, %114, %115, %116, %117, %118, %119, %120, %121, %122, %123, %124, %125, %126, %127"
        "}, %128, %129, p, 1, 1, 0, 1;\n}\n"
        : "+f"(d[0]), "+f"(d[1]), "+f"(d[2]), "+f"(d[3]), "+f"(d[4]), "+f"(d[5]), "+f"(d[6]), "+f"(d[7]),
          "+f"(d[8]), "+f"(d[9]), "+f"(d[10]), "+f"(d[11]), "+f"(d[12]), "+f"(d[13]), "+f"(d[14]), "+f"(d[15]),
          "+f"(d[16]), "+f"(d[17]), "+f"(d[18]), "+f"(d[19]), "+f"(d[20]), "+f"(d[21]), "+f"(d[22]), "+f"(d[23]),
          "+f"(d[24]), "+f"(d[25]), "+f"(d[26]), "+f"(d[27]), "+f"(d[28]), "+f"(d[29]), "+f"(d[30]), "+f"(d[31]),
          "+f"(d[32]), "+f"(d[33]), "+f"(d[34]), "+f"(d[35]), "+f"(d[36]), "+f"(d[37]), "+f"(d[38]), "+f"(d[39]),
          "+f"(d[40]), "+f"(d[41]), "+f"(d[42]), "+f"(d[43]), "+f"(d[44]), "+f"(d[45]), "+f"(d[46]), "+f"(d[47]),
          "+f"(d[48]), "+f"(d[49]), "+f"(d[50]), "+f"(d[51]), "+f"(d[52]), "+f"(d[53]), "+f"(d[54]), "+f"(d[55]),
          "+f"(d[56]), "+f"(d[57]), "+f"(d[58]), "+f"(d[59]), "+f"(d[60]), "+f"(d[61]), "+f"(d[62]), "+f"(d[63]),
          "+f"(d[64]), "+f"(d[65]), "+f"(d[66]), "+f"(d[67]), "+f"(d[68]), "+f"(d[69]), "+f"(d[70]), "+f"(d[71]),
          "+f"(d[72]), "+f"(d[73]), "+f"(d[74]), "+f"(d[75]), "+f"(d[76]), "+f"(d[77]), "+f"(d[78]), "+f"(d[79]),
          "+f"(d[80]), "+f"(d[81]), "+f"(d[82]), "+f"(d[83]), "+f"(d[84]), "+f"(d[85]), "+f"(d[86]), "+f"(d[87]),
          "+f"(d[88]), "+f"(d[89]), "+f"(d[90]), "+f"(d[91]), "+f"(d[92]), "+f"(d[93]), "+f"(d[94]), "+f"(d[95]),
          "+f"(d[96]), "+f"(d[97]), "+f"(d[98]), "+f"(d[99]), "+f"(d[100]), "+f"(d[101]), "+f"(d[102]), "+f"(d[103]),
          "+f"(d[104]), "+f"(d[105]), "+f"(d[106]), "+f"(d[107]), "+f"(d[108]), "+f"(d[109]), "+f"(d[110]), "+f"(d[111]),
          "+f"(d[112]), "+f"(d[113]), "+f"(d[114]), "+f"(d[115]), "+f"(d[116]), "+f"(d[117]), "+f"(d[118]), "+f"(d[119]),
          "+f"(d[120]), "+f"(d[121]), "+f"(d[122]), "+f"(d[123]), "+f"(d[124]), "+f"(d[125]), "+f"(d[126]), "+f"(d[127])
        : "l"(da), "l"(db));
}

struct Idx {
    uint32_t lane, warp, w4, q4, g8, prow, pan;
    __device__ __forceinline__ Idx() {
        uint32_t t; asm volatile("mov.u32 %0, %%tid.x;" : "=r"(t));
        lane = t & 31; warp = t >> 5; w4 = warp & 3; q4 = lane & 3; g8 = lane >> 2;
        prow = w4 * 16 + ((lane >> 3) & 1) * 8 + (lane & 7);
        pan = prow * 128 + (((lane >> 4) ^ (lane & 7)) << 4);
    }
};
#define IDX() const Idx ix; const uint32_t lane = ix.lane, warp = ix.warp, w4 = ix.w4, q4 = ix.q4, g8 = ix.g8, prow = ix.prow, pan_addr = ix.pan; \
    (void)lane; (void)warp; (void)w4; (void)q4; (void)g8; (void)prow; (void)pan_addr;

__device__ __forceinline__ int kof(int t, int sh, int j) {
    const int p = t >> (sh - 1), pn = p < 2 ? p : p >= 9, q = p - 2 - 7 * pn;
    return ((p < 2 ? j : q + (q >= j)) << 7) + (pn << 6) + ((t & (sh - 1)) << 5);
}
constexpr int HC0 = 8 * 48, HC3 = HC0 + 3072;
__device__ __forceinline__ int hcol(int p, int j) { return HC0 + p * 1024 + j * 128; }
#define SCHED_FENCE(k) do { if ((FENCES >> (k)) & 1) asm volatile("{\n.reg .pred p;\nsetp.ne.u32 p, %0, %1;\n@p bra.uni S_SKIP;\ntrap;\nS_SKIP:\n}" :: "r"(sb), "n"(0xffffff00u + (k))); } while (0)

struct Ring {
    uint32_t slot, par;
    __device__ __forceinline__ void next() { if (++slot == NSLOT) { slot = 0; par ^= 1; } }
    __device__ __forceinline__ void skip(uint32_t n) { slot += n; if (slot >= NSLOT) { slot -= NSLOT; par ^= 1; } }
};
__device__ __forceinline__ uint32_t BAR_FULL(uint32_t sb, uint32_t s) { return sb + OFF_BAR + 8 * s; }
constexpr uint32_t AF_REL = 48;
__device__ __forceinline__ uint32_t BAR_EMPTY(uint32_t sb, uint32_t s) { return sb + OFF_BAR + 96 + 8 * s; }
__device__ __forceinline__ uint32_t BAR_SFULL(uint32_t sb, uint32_t i) { return sb + OFF_BAR + 152 + 8 * i; }
__device__ __forceinline__ uint32_t BAR_SREADY(uint32_t sb, uint32_t i) { return sb + OFF_BAR + 184 + 8 * i; }
__device__ __forceinline__ uint32_t BAR_ONE(uint32_t sb, uint32_t i) { return sb + OFF_BAR + 216 + 8 * i; }
enum { EV_WIN, EV_WIN1, EV_WIN2, EV_WIN3, EV_P0, EV_GA, EV_GB, EV_LN2, EV_LAG0, EV_LAG1, EV_LAG2, EV_LAG3, EV_LAG4, EV_LAG5, EV_OWN, EV_OWN1, EV_KV, EV_GO, EV_PAR, EV_AGO, EV_AGO1, EV_AGO2, EV_FGO, EV_FGO1, EV_FGO2, EV_H0, EV_H1, EV_H2, EV_H3, EV_COUNT };
constexpr int NB_TAIL = 4;

struct Rel {
    uint32_t base; bool sig;
    __device__ __forceinline__ Rel(uint32_t sb, uint32_t tw) {
        uint32_t a; asm("mapa.shared::cluster.u32 %0, %1, %2;" : "=r"(a) : "r"(BAR_EMPTY(sb, 0)), "r"((tw >> 5) & 1));
        base = __shfl_sync(0xffffffffu, a, 0); sig = (tw & ~32u) == 0;
    }
    __device__ __forceinline__ void operator()(uint32_t slot) const {
        if (sig) asm volatile("mbarrier.arrive.shared::cluster.b64 _, [%0];" :: "r"(base + 8 * slot) : "memory");
    }
};
struct LnRow { float rs0, nm0, rs1, nm1; };
struct Pipe {
    Rel rel; uint32_t p1, p2;
    __device__ __forceinline__ Pipe(uint32_t sb, uint32_t tw, uint32_t first) : rel(sb, tw), p1(first), p2(NSLOT) {}
    template <bool TWO> __device__ __forceinline__ void acquire(uint32_t sb, uint32_t af, const Ring& r) {
        const uint32_t b0 = BAR_FULL(sb, r.slot), b1 = b0 + af;
        const bool ready = TWO ? mbar_test2(b0, b1, r.par) : mbar_test(b0, r.par);
        wg_wait<1>();
        rel(p2);
        if (!ready) { if (TWO) mbar_wait2(b0, b1, r.par); else mbar_wait(b0, r.par); }
    }
    __device__ __forceinline__ void issued(uint32_t slot) { p2 = p1; p1 = slot; }
    __device__ __forceinline__ void drain1() { wg_wait<1>(); rel(p2); p2 = NSLOT; }
    __device__ __forceinline__ void drain0() { wg_wait<0>(); rel(p1); p1 = NSLOT; }
    template <bool TWO, class Step> __device__ __forceinline__ void hold(int LG, uint32_t sb, uint32_t af, Ring& r, uint32_t lag_bar, Step step) {
        Ring q = r;
#pragma unroll 1
        for (int i = 0; i < LG; ++i) { if (TWO) mbar_wait2(BAR_FULL(sb, q.slot), BAR_FULL(sb, q.slot) + af, q.par); else mbar_wait(BAR_FULL(sb, q.slot), q.par); q.next(); }
        mbar_wait(lag_bar, 0);
#pragma unroll 1
        do {
            step(r.slot);
            wg_wait<2>(); rel(p2); p2 = p1; p1 = r.slot;
            if (++r.slot == NSLOT) r.slot = 0;
        } while (r.slot != q.slot);
        r.par = q.par;
    }
};
template <bool TWO, bool FIRST, int NA, int NB>
__device__ __forceinline__ void step32(float (&aa)[NA], float (&ab)[NB], uint32_t sb, uint32_t wg, uint32_t slot, int own) {
    const uint32_t st = d16(sb) + slot * (SLOT >> 4);
    const uint32_t alo = own >= 0 ? d16(sb) + OFF_STG / 16 + wg * 1024 + (own >> 1) * 512 + (own & 1) * 4 : st + wg * 256;
    const uint32_t ahi = own >= 0 ? (1024 >> 4) | (1u << 30) : (512 >> 4) | (2u << 30);
    wg_fence();
#pragma unroll
    for (int k = 0; k < 2; ++k) {
        const uint64_t da = ((uint64_t)ahi << 32) | (alo + k * 2 + 0x10000);
        if constexpr (NA == 88) {
            const uint64_t d0 = mk_desc(st, 8192 + k * 2048, 8192, 1024, 1), d1 = mk_desc(st, 12288 + k * 2048, 8192, 1024, 1);
            if (FIRST && k == 0) { wgmma_n176_z(aa, da, d0); wgmma_n176_z(ab, da, d1); }
            else { wgmma_n176(aa, da, d0); wgmma_n176(ab, da, d1); }
        } else {
            const uint64_t d0 = mk_desc(st, 8192 + k * 2048, 4096, 1024, 1), d1 = mk_desc(st, 24576 + k * 2048, 4096, 1024, 1);
            if (FIRST && k == 0) { wgmma_n256_z(aa, da, d0); if constexpr (TWO) wgmma_n128_z(ab, da, d1); }
            else { wgmma_n256(aa, da, d0); if constexpr (TWO) wgmma_n128(ab, da, d1); }
        }
    }
    wg_commit();
}
template <bool TWO, int LG, int NA, int NB, class Tail>
__device__ __forceinline__ void mainloop32(float (&aa)[NA], float (&ab)[NB], uint32_t sb, uint32_t wg, uint32_t tw, Ring& r, uint32_t lag_ev, int g0, Tail tail) {
    mbar_wait(BAR_FULL(sb, r.slot), r.par);
    step32<TWO, true>(aa, ab, sb, wg, r.slot, TWO ? 0 : -1);
    TS(g0, 0);
    Pipe pp(sb, tw, r.slot);
    r.next();
    const int end = wg ? 32 : 32 - LG;
#pragma unroll 1
    for (int it = 1; it < end; ++it) {
        pp.acquire<TWO>(sb, wg ? 0 : AF_REL, r);
        step32<TWO, false>(aa, ab, sb, wg, r.slot, TWO && it < 4 ? it : -1);
        pp.issued(r.slot);
        TS(g0 + it, 0);
        r.next();
    }
    if (wg == 0) { pp.drain1(); pp.drain0(); pp.hold<TWO>(LG, sb, AF_REL, r, BAR_ONE(sb, lag_ev), [&](uint32_t slot) { step32<TWO, false>(aa, ab, sb, 0, slot, -1); }); }
    pp.drain1();
    if (wg == 1 && tw == 0) mbar_arrive(BAR_ONE(sb, lag_ev));
    tail();
    pp.drain0();
    TS(g0 + 31, 1);
}
template <bool FIRST>
__device__ __forceinline__ void step64(float (&acc)[64], uint32_t sb, uint32_t wg, uint32_t slot, int own) {
    const uint32_t sbb = d16(sb) + slot * (SLOT >> 4), sa = own >= 0 ? d16(sb) + OFF_STG / 16 + wg * 1024 + own * 512 : sbb + wg * 512;
    wg_fence();
#pragma unroll
    for (int k = 0; k < 4; ++k) {
        const uint64_t da = mk_desc(sa, k * 32, 16, 1024, 1), db = mk_desc(sbb, 16384 + k * 2048, 8192, 1024, 1);
        if (FIRST && k == 0) wgmma_n128_z(acc, da, db); else wgmma_n128(acc, da, db);
    }
    wg_commit();
}
template <class Mid>
__device__ __forceinline__ void mainloop64(float (&acc)[64], bool wo, uint32_t sb, uint32_t wg, uint32_t tw, Ring& r, Mid mid) {
    const int g0 = wo ? 32 : 144, nst = wo ? 16 : 56, lg = wo ? LAGW : LAGD; (void)g0;
    const uint32_t lag_bar = BAR_ONE(sb, wo ? EV_LAG4 : EV_LAG5), af = wo && !wg ? AF_REL : 0;
    mbar_wait(BAR_FULL(sb, r.slot), r.par);
    if (!wo) CS(28);
    step64<true>(acc, sb, wg, r.slot, wo ? 0 : -1);
    if (!wo) CS(29);
    TS(g0, 0);
    Pipe pp(sb, tw, r.slot);
    r.next();
    int it = 1;
    auto run = [&](int end, int own) {
#pragma unroll 1
        do {
            pp.acquire<true>(sb, af, r);
            step64<false>(acc, sb, wg, r.slot, own);
            pp.issued(r.slot);
            TS(g0 + it, 0);
            r.next();
            if (own > 0) {
                own = -1;
                pp.drain1(); pp.drain0();
                TS(g0 + 1, 1);
                if (tw == 0) mbar_arrive(BAR_ONE(sb, EV_OWN + wg));
            }
        } while (++it < end);
    };
    run(wg ? (wo ? MIDW : MIDD) : nst - lg, wo ? 1 : -1);
    mid();
    if (wg) run(nst, -1);
    else { pp.drain1(); pp.drain0(); pp.hold<true>(lg, sb, af, r, lag_bar, [&](uint32_t slot) { step64<false>(acc, sb, 0, slot, -1); }); }
    pp.drain1();
    if (wg == 1 && tw == 0) mbar_arrive(lag_bar);
    pp.drain0();
    TS(g0 + nst - 1, 1);
}

struct RowAcc {
    float sm[4] = {0.f, 0.f, 0.f, 0.f}, sq[4] = {0.f, 0.f, 0.f, 0.f};
    __device__ __forceinline__ void add(int e, float x) { sm[e & 3] += x; sq[e & 3] = fmaf(x, x, sq[e & 3]); }
    __device__ __forceinline__ void publish(uint4* dst, uint32_t q4, uint32_t ep) const {
        const float s0 = sm[0] + sm[1], s1 = sm[2] + sm[3], q0 = sq[0] + sq[1], q1 = sq[2] + sq[3];
        const bool od = q4 & 1;
        float sv = (od ? s1 : s0) + __shfl_xor_sync(0xffffffffu, od ? s0 : s1, 1), qv = (od ? q1 : q0) + __shfl_xor_sync(0xffffffffu, od ? q0 : q1, 1);
        sv += __shfl_xor_sync(0xffffffffu, sv, 2); qv += __shfl_xor_sync(0xffffffffu, qv, 2);
        if (q4 < 2) st_pkt16(dst + q4 * 8, 0, __float_as_uint(sv), __float_as_uint(qv), ep);
    }
};
__device__ __forceinline__ LnRow merge_stats(const uint4* src, uint32_t q4, uint32_t ep, uint32_t sb) {
    uint4 t[4];
    uint32_t n = 0;
    while (true) {
#pragma unroll
        for (int i = 0; i < 4; ++i) t[i] = ld_pkt16(src + (q4 * 2 + (i >> 1)) * 512 + (i & 1) * 8);
        const bool ok_ = __all_sync(0xffffffffu, t[0].w == ep && t[1].w == ep && t[2].w == ep && t[3].w == ep);
        if (n < 4) CS(14 + n);
        if (ok_) break;
        SPIN_GUARD(n);
    }
    float v[4];
#pragma unroll
    for (int h = 0; h < 2; ++h) { v[h] = __uint_as_float(t[h].y) + __uint_as_float(t[2 + h].y); v[2 + h] = __uint_as_float(t[h].z) + __uint_as_float(t[2 + h].z); }
#pragma unroll
    for (int o = 1; o < 4; o <<= 1)
#pragma unroll
        for (int i = 0; i < 4; ++i) v[i] += __shfl_xor_sync(0xffffffffu, v[i], o);
    const float m0 = v[0] * (1.f / D_), m1 = v[1] * (1.f / D_);
    const float r0 = rsqrtf(fmaxf(fmaf(-m0, m0, v[2] * (1.f / D_)), 0.f) + 1e-5f), r1 = rsqrtf(fmaxf(fmaf(-m1, m1, v[3] * (1.f / D_)), 0.f) + 1e-5f);
    return LnRow{r0, -m0 * r0, r1, -m1 * r1};
}
struct Stg {
    uint32_t b, par;
    __device__ __forceinline__ uint32_t acquire2(uint32_t sb, uint32_t wg) {
        mbar_wait(BAR_SREADY(sb, wg * 2), par & 1);
        mbar_wait(BAR_SREADY(sb, wg * 2 + 1), (par >> 1) & 1);
        par ^= 3;
        return sb + OFF_STG + wg * 16384;
    }
    __device__ __forceinline__ void publish(uint32_t sb, uint32_t wg, uint32_t lane) {
        fence_async_smem();
        __syncwarp();
        if (lane == 0) mbar_arrive(BAR_SFULL(sb, wg * 2 + b));
        b ^= 1;
    }
};

struct LnPar {
    uint4 p[8];
    __device__ __forceinline__ void load(uint32_t sb, uint32_t q4) {
#pragma unroll
        for (int i = 0; i < 8; ++i) p[i] = lds128(sb + OFF_PAR + i * 64 + q4 * 16);
    }
};
__device__ __forceinline__ void ln_norm(uint32_t (&xn)[32], const float (&x)[64], const LnRow& n) {
#pragma unroll
    for (int e = 0; e < 32; ++e) {
        const float rs = (e & 1) ? n.rs1 : n.rs0, nm = (e & 1) ? n.nm1 : n.nm0;
        xn[e] = pack2(fmaf(x[2 * e], rs, nm), fmaf(x[2 * e + 1], rs, nm));
    }
}
__device__ __forceinline__ void ln_emit(const uint32_t (&xr)[32], const LnPar& lp, uint32_t sb, uint32_t wg, const Idx& ix) {
#pragma unroll
    for (int i = 0; i < 8; ++i)
        stsm4(sb + OFF_STG + wg * 16384 + (i >> 2) * 8192 + (ix.pan ^ ((i & 3) << 5)), hfma2_bf16(xr[4 * i], lp.p[i].z, lp.p[i].x), hfma2_bf16(xr[4 * i + 1], lp.p[i].z, lp.p[i].x),
              hfma2_bf16(xr[4 * i + 2], lp.p[i].w, lp.p[i].y), hfma2_bf16(xr[4 * i + 3], lp.p[i].w, lp.p[i].y));
    fence_async_smem();
    __syncwarp();
    if (ix.lane < 2) mbar_arrive(BAR_SFULL(sb, wg * 2 + ix.lane));
    bar_sync(1 + wg, 128);
}
__device__ __forceinline__ void load_slab(uint32_t (&xr)[32], uint32_t buf) {
    IDX();
#pragma unroll
    for (int i = 0; i < 8; ++i) ldsm4(buf + (i >> 2) * 8192 + (pan_addr ^ ((i & 3) << 5)), xr[4 * i], xr[4 * i + 1], xr[4 * i + 2], xr[4 * i + 3]);
}
__device__ __forceinline__ void unpack_slab(float (&x)[64], const uint32_t (&xr)[32]) {
#pragma unroll
    for (int i = 0; i < 32; ++i) unpack2(xr[i], x[2 * i], x[2 * i + 1]);
}
__device__ __forceinline__ void store_slab(const float (&x)[64], uint32_t buf, uint32_t pitch, uint32_t pan, int i0, int i1) {
#pragma unroll
    for (int i = i0; i < i1; ++i)
        stsm4(buf + (i >> 2) * pitch + (pan ^ ((i & 3) << 5)), pack2(x[8 * i], x[8 * i + 1]), pack2(x[8 * i + 2], x[8 * i + 3]), pack2(x[8 * i + 4], x[8 * i + 5]), pack2(x[8 * i + 6], x[8 * i + 7]));
}
__device__ __forceinline__ void fetch_halo(uint4* src, bool first, uint32_t sb, uint32_t W, uint32_t lane) {
    mbar_wait(BAR_ONE(sb, EV_KV), 0);
    mbar_wait2(BAR_SREADY(sb, 0), BAR_SREADY(sb, 1), 1);
    uint4 hv[8];
    uint32_t n = 0;
    while (true) {
        bool ok = true;
#pragma unroll
        for (int i = 0; i < 8; ++i) { hv[i] = first ? make_uint4(0, 0, 0, 0) : ld_pkt16(src + i * 32); ok = ok && hv[i].x != 0; }
        if (first || __all_sync(0xffffffffu, ok)) break;
        SPIN_GUARD(n);
    }
#pragma unroll
    for (int i = 0; i < 8; ++i) stsm4(sb + OFF_STG + W * 2048 + (i >> 2) * 8192 + (i & 3) * 512 + lane * 16, hv[i].x, hv[i].y, hv[i].z, hv[i].w);
    bar_arrive(NB_TAIL + W, 64);
    if (!first) {
#pragma unroll
        for (int i = 0; i < 8; ++i) src[i * 32] = make_uint4(0, 0, 0, 0);
    }
}

template <int NG, class G, class U, class Buf>
__device__ __forceinline__ void glu(uint32_t sb, uint32_t wg, G g, U u, Buf buf) {
    IDX();
#pragma unroll
    for (int k = 0; k < NG; ++k) {
        float h[8];
#pragma unroll
        for (int e = 0; e < 8; ++e) h[e] = fmaf(tanh_(g(8 * k + e)), u(8 * k + e), u(8 * k + e));
        stsm4(buf(k >> 2) + (pan_addr ^ ((k & 3) << 5)), pack2(h[0], h[1]), pack2(h[2], h[3]), pack2(h[4], h[5]), pack2(h[6], h[7]));
    }
    fence_async_smem();
    __syncwarp();
    if (lane < 2) mbar_arrive(BAR_SFULL(sb, wg * 2 + lane));
}

template <int NP>
__device__ __forceinline__ void passes128(uint32_t sb, uint32_t wg, uint32_t tw, Ring& r, Stg& stg) {
#pragma unroll 1
    for (int p = 0; p < NP; ++p) {
        float b256[128], none[1];
        mainloop32<false, LAGS>(b256, none, sb, wg, tw, r, EV_LAG2 + p, 80 + 32 * (p & 1), [&] { stg.acquire2(sb, wg); });
        if (threadIdx.x == 0) { TL(29 + 2 * p); TC(114 + 2 * p); }
        if (threadIdx.x == 128) TL(53 + 2 * (p & 1));
        CS(24 + 2 * (p & 1));
        glu<8>(sb, wg, [&](int i) { return b256[i + (i & 32)]; }, [&](int i) { return b256[i + (i & 32) + 32]; }, [&](int pn) { return sb + OFF_STG + wg * 16384 + pn * 8192; });
        if (threadIdx.x == 0) { TL(30 + 2 * p); TC(115 + 2 * p); }
        if (threadIdx.x == 128) TL(54 + 2 * (p & 1));
        CS(25 + 2 * (p & 1));
    }
}

__global__ void __launch_bounds__(384, 1)
fused_block_kernel(const __grid_constant__ Ptrs pt, const __grid_constant__ Maps mp) {
    uint32_t* const g_flags = pt.mail->flags;
    uint2* const g_mod = pt.mail->mod;
    uint4* const g_st1 = pt.mail->st1;
    uint32_t* const g_par2 = pt.mail->par2;
    uint4* const g_halo = pt.mail->halo;
    const __nv_bfloat16* __restrict__ cvec = pt.c;
    if (threadIdx.x == 224) { prefetch_map(&mp.wm8); prefetch_map(&mp.x); }
    extern __shared__ __align__(1024) uint8_t smem[];
    const uint32_t sb = smem_u32(smem);
    const uint32_t tid = threadIdx.x, tw = tid & 127, lane = tid & 31;
    const uint32_t warp = __shfl_sync(0xffffffffu, tid >> 5, 0), wg = warp >> 2;
    uint32_t rank; asm("mov.u32 %0, %%cluster_ctarank;" : "=r"(rank));
    rank = __shfl_sync(0xffffffffu, rank, 0);
    uint32_t ep;
    uint32_t smid; asm volatile("mov.u32 %0, %%smid;" : "=r"(smid));
    const int c = __shfl_sync(0xffffffffu, smid >> 1, 0);
    const int c7 = ((c - 32) * 37) >> 8;
    const int grp = c < 32 ? c & 7 : c < 60 ? c - 31 - 7 * c7 : c < 62 ? -1 : 0;
    const int j = c < 32 ? c >> 3 : c < 60 ? 4 + c7 : c < 62 ? (c - 60) * 2 + rank : c - 58;
    const bool aux = grp < 0;
    const int m = grp * 2 + rank;
    uint4* const g_st2 = g_halo + (m > 0 ? (m - 1) * 8 * 512 : 128);

    bool cluster_arrive_early = false;
    if (wg < 2) {
      if (!KDEBUG) cluster_arrive();
      ep = flag_get(g_flags + FL_DONE);
      uint16_t cw[8];
      {
          const __nv_bfloat16* cp = cvec + ((tw >> 5) * 32 + (tw & 3) * 2) * 8 + (lane >> 2);
#pragma unroll
          for (int i = 0; i < 8; ++i) asm volatile("ld.global.nc.u16 %0, [%1];" : "=h"(cw[i]) : "l"(cp + (i >> 1) * 64 + (i & 1) * 8));
      }
      asm volatile("setmaxnreg.inc.sync.aligned.u32 224;");
      if (tid == 0) TL(58);
      if (KDEBUG) cluster_arrive();
      Ring r{0, 0};
      Stg stg{0, 0};
      if (aux) {
        if (wg == 0) {
            const uint4 cv = *(const uint4*)(cvec + tw * 8);
            sts128(sb + OFF_STG + (tw >> 3) * 1024 + (tw & 7) * 16, pack2(silu_(bf_lo(cv.x)), silu_(bf_hi(cv.x))), pack2(silu_(bf_lo(cv.y)), silu_(bf_hi(cv.y))),
                   pack2(silu_(bf_lo(cv.z)), silu_(bf_hi(cv.z))), pack2(silu_(bf_lo(cv.w)), silu_(bf_hi(cv.w))));
            fence_async_smem();
        }
        cluster_wait();
        ep = __shfl_sync(0xffffffffu, ep, 0) / NCTA + 1;
        if (wg == 0) {
            if (tw == 0) {
                uint32_t n = 0;
                while (ld_pkt16(pt.mail->mod1 + 256).z != ep) { SPIN_GUARD(n); __nanosleep(200); }
                if (GODLY) __nanosleep(GODLY);
                mbar_arrive(BAR_ONE(sb, EV_GO));
            }
            bar_sync(1, 128);
#pragma unroll 1
            for (int p = 0; p < 4; ++p) {
                float acc[128];
#pragma unroll
                for (int i = 0; i < 128; ++i) acc[i] = 0.f;
                uint32_t prev = 0;
#pragma unroll 1
                for (int kc = 0; kc < 16; ++kc) {
                    mbar_wait(BAR_FULL(sb, r.slot), r.par);
                    wg_fence();
#pragma unroll
                    for (int k = 0; k < 4; ++k)
                        wgmma_n256(acc, mk_desc(d16(sb) + kc * 64, OFF_STG + k * 32, 16, 0, 1), mk_desc(d16(sb) + r.slot * (SLOT >> 4), k * 2048, 8192, 1024, 1));
                    wg_commit();
                    wg_wait<1>();
                    if (kc > 0 && tw < 4) mbar_arrive(BAR_EMPTY(sb, prev));
                    prev = r.slot;
                    r.next();
                }
                wg_wait<0>();
                if (tw < 4) mbar_arrive(BAR_EMPTY(sb, prev));
                if (tw < 4) {
#pragma unroll
                    for (int jn = 0; jn < 32; ++jn) sts32(sb + OFF_TAB + (jn * 4 + tw) * 4, pack2(acc[jn * 4], acc[jn * 4 + 1]));
                }
                bar_sync(1, 128);
                const int vec = 2 + p, blk = p * 4 + j;
                const uint32_t val = lds32(sb + OFF_TAB + tw * 4);
                if (vec == 2 || vec == 5) st_pkt(g_mod + (8 + blk) * 128 + tw, val, ep);
                else {
                    const float one = vec == 4 ? 1.f : 0.f;
                    g_par2[((blk & 3) * 16 + (tw >> 3)) * 16 + (tw & 3) * 4 + (vec - 3) * 2 + ((tw >> 2) & 1)] =
                        pack2(0.5f * bf_round(one + bf_lo(val)), 0.5f * bf_round(one + bf_hi(val)));
                }
                bar_sync(1, 128);
                if (tw == 0) {
                    if (vec == 3 || vec == 4) asm volatile("red.release.gpu.global.add.u32 [%0], 1;" :: "l"(&g_flags[FL_LN2]) : "memory");
                    TL(1 + p);
                }
            }
            if (lane < 2) mbar_arrive_cta(BAR_ONE(sb, EV_P0), lane);
        }
        r = Ring{64 % NSLOT, (64 / NSLOT) & 1};
        mbar_wait(BAR_ONE(sb, EV_P0), 0);
        passes128<4>(sb, wg, tw, r, stg);
      } else {
        float xs[64];
        uint32_t xp[32];
        {
            IDX();
            if (q4 < 2) st_pkt16(g_st1 + (m * 8 + j) * 512 + wg * 64 + w4 * 16 + g8 + q4 * 8, 0, 0, 0, 0);
            if (warp == 0) st_pkt16(pt.mail->mod1 + g8 * 512 + (m * 8 + j) * 4 + q4, 0, 0, 0, 0);
            sts128(sb + tid * 16, pack2(silu_(bf_lo(cw[0])), silu_(bf_lo(cw[1]))), pack2(silu_(bf_lo(cw[2])), silu_(bf_lo(cw[3]))),
                   pack2(silu_(bf_lo(cw[4])), silu_(bf_lo(cw[5]))), pack2(silu_(bf_lo(cw[6])), silu_(bf_lo(cw[7]))));
            cluster_wait();
            ep = __shfl_sync(0xffffffffu, ep, 0) / NCTA + 1;
            load_slab(xp, stg.acquire2(sb, wg));
            unpack_slab(xs, xp);
            if (tid == 0) TL(24);
            if (tid == 128) TL(27);
        }
#pragma unroll 1
        for (int blk = 0; ; ++blk) {
        {
            IDX();
            uint4* const st = (blk ? g_st2 : g_st1 + m * 8 * 512) + wg * 64 + w4 * 16 + g8;
            RowAcc ra;
#pragma unroll
            for (int e = 0; e < 64; ++e) ra.add(e, xs[e]);
            ra.publish(st + j * 512, q4, ep);
            uint32_t t_pub = 0; if (PDLY) asm volatile("mov.u32 %0, %%clock;" : "=r"(t_pub));
            if (tid == 0) TL(blk ? 9 : 26);
            if (tid == 128 && blk) TL(34);
            if (blk) CS(11);
            LnPar lp;
            if (blk == 0) {
            uint4* const mod_out = pt.mail->mod1 + g8 * 512 + (m * 8 + j) * 4 + q4;
            if (wg == 0) {
                uint4 af[8];
#pragma unroll
                for (int i = 0; i < 8; ++i) af[i] = lds128(sb + w4 * 512 + i * 64 + q4 * 16);
                float c[4][4] = {};
#pragma unroll
                for (int i = 0; i < 8; ++i) {
                    if (!(i & 1)) mbar_wait(BAR_ONE(sb, EV_WIN + (i >> 1)), 0);
                    if (i == 6 && tid == 0) TL(25);
#pragma unroll
                    for (int h = 0; h < 2; ++h) {
                        uint32_t b0, b1, b2, b3;
                        ldsm4t(sb + 5 * SLOT + i * 4096 + w4 * 1024 + h * 512 + (lane & 15) * 32 + (lane >> 4) * 16, b0, b1, b2, b3);
                        mma16816(c[2 * h], h ? af[i].z : af[i].x, 0u, h ? af[i].w : af[i].y, 0u, b0, b1);
                        mma16816(c[2 * h + 1], h ? af[i].z : af[i].x, 0u, h ? af[i].w : af[i].y, 0u, b2, b3);
                    }
                }
                if (lane < 4) sts128(sb + OFF_TAB + w4 * 64 + lane * 16, __float_as_uint(c[0][0] + c[2][0]), __float_as_uint(c[0][1] + c[2][1]),
                                     __float_as_uint(c[1][0] + c[3][0]), __float_as_uint(c[1][1] + c[3][1]));
                if (lane < 2) mbar_arrive_cta(BAR_ONE(sb, EV_P0), lane);
                bar_sync(1, 128);
                if (w4 == 0) {
                    float a[4] = {0.f, 0.f, 0.f, 0.f};
#pragma unroll
                    for (int i = 0; i < 4; ++i) {
                        const uint4 t = lds128(sb + OFF_TAB + i * 64 + q4 * 16);
                        a[0] += __uint_as_float(t.x); a[1] += __uint_as_float(t.y); a[2] += __uint_as_float(t.z); a[3] += __uint_as_float(t.w);
                    }
                    const float add = m >= 8 ? 1.f : 0.f;
                    st_pkt16(mod_out, pack2(bf_round(a[0]) + add, bf_round(a[1]) + add), pack2(bf_round(a[2]) + add, bf_round(a[3]) + add), ep, 0);
                    if (tid == 0) TL(3);
                }
            } else if (LWAIT >= 0) mbar_wait(BAR_ONE(sb, EV_WIN + LWAIT), 0);
            } else {
                mbar_wait(BAR_ONE(sb, EV_LN2), 0);
            }
            lp.load(sb, q4);
#pragma unroll
            for (int e = 0; e < 32; ++e) xp[e] = pack2(xs[2 * e], xs[2 * e + 1]);
            if (PDLY && blk) { uint32_t t1; do { asm volatile("mov.u32 %0, %%clock;" : "=r"(t1)); } while (t1 - t_pub < PDLY); }
            if (blk) CS(13);
            const LnRow n = merge_stats(st, q4, ep, sb);
            if (tid == 0) TL(blk ? 49 : 48);
            if (tid == 128) TL(blk ? 45 : 28);
            if (blk) CS(18);
            uint32_t xn[32];
            ln_norm(xn, xs, n);
            if (blk == 0) { mbar_wait(BAR_ONE(sb, EV_PAR), 0); lp.load(sb, q4); }
            ln_emit(xn, lp, sb, wg, ix);
            if (tid == 0) { TL(blk ? 36 : 8); TC(blk ? 109 : 103); }
            if (tid == 128) TL(blk ? 43 : 22);
            if (blk) CS(21);
        }
        if (blk == 0) {
        {
            float kv[128], qa[64];
            mainloop32<true, LAGQ>(kv, qa, sb, wg, tw, r, EV_LAG0, 0, [&] { stg.acquire2(sb, wg); mbar_wait2(BAR_SREADY(sb, 2), BAR_SREADY(sb, 3), 1); });
            if (tid == 0) { TL(4); TC(104); }
            if (tid == 128) TL(50);
            CS(1);
            IDX();
            uint32_t k1[16], k2[16], v1[16], v2[16], qf[32];
#pragma unroll
            for (int i = 0; i < 8; ++i) qf[i] = pack2(qa[2 * i], qa[2 * i + 1]);
#pragma unroll
            for (int t = 0; t < 16; ++t) k2[t] = pack2(kv[4 * t + 2], kv[4 * t + 3]);
#pragma unroll
            for (int t = 0; t < 16; ++t) v2[t] = pack2(kv[64 + 4 * t + 2], kv[64 + 4 * t + 3]);
            const uint32_t nxt = warp + ((warp & 1) ? 3 : 1);
            if (nxt < 8) {
                const uint32_t dst = sb + OFF_STG + (nxt >> 2) * 16384 + (nxt & 3) * 2048 + lane * 16;
#pragma unroll
                for (int h = 0; h < 4; ++h) stsm4(dst + h * 512, k2[4 * h], k2[4 * h + 1], k2[4 * h + 2], k2[4 * h + 3]);
#pragma unroll
                for (int h = 0; h < 4; ++h) stsm4(dst + 8192 + h * 512, v2[4 * h], v2[4 * h + 1], v2[4 * h + 2], v2[4 * h + 3]);
                bar_arrive(NB_TAIL + nxt, 64);
            } else if (m < 15) {
                uint4* dst = g_halo + (m * 8 + j) * 512 + (w4 >> 1) * 256 + lane;
#pragma unroll
                for (int h = 0; h < 4; ++h) { if (!k2[4 * h]) k2[4 * h] = 0x8000u; if (!v2[4 * h]) v2[4 * h] = 0x8000u; }
#pragma unroll
                for (int h = 0; h < 4; ++h) st_pkt16(dst + h * 32, k2[4 * h], k2[4 * h + 1], k2[4 * h + 2], k2[4 * h + 3]);
#pragma unroll
                for (int h = 0; h < 4; ++h) st_pkt16(dst + 128 + h * 32, v2[4 * h], v2[4 * h + 1], v2[4 * h + 2], v2[4 * h + 3]);
            }
#pragma unroll
            for (int t = 0; t < 16; ++t) { k1[t] = pack2(kv[4 * t], kv[4 * t + 1]); v1[t] = pack2(kv[64 + 4 * t], kv[64 + 4 * t + 1]); }
#pragma unroll
            for (int i = 8; i < 32; ++i) qf[i] = pack2(qa[2 * i], qa[2 * i + 1]);
#pragma unroll
            for (int t = 0; t < 16; ++t) { v1[t] = movm(v1[t]); v2[t] = movm(v2[t]); }
            if (tid == 0) TL(33);
            CS(2);
            SCHED_FENCE(0);
            float s[4][3][4];
            auto qk = [&](float (&c)[4], int h, const uint32_t* k) {
                c[0] = c[1] = c[2] = c[3] = 0.f;
                mma16816(c, qf[h * 8], qf[h * 8 + 1], qf[h * 8 + 2], qf[h * 8 + 3], k[0], k[1]);
                mma16816(c, qf[h * 8 + 4], qf[h * 8 + 5], qf[h * 8 + 6], qf[h * 8 + 7], k[2], k[3]);
            };
#pragma unroll
            for (int h = 0; h < 4; ++h) { qk(s[h][1], h, k1 + 4 * h); qk(s[h][2], h, k2 + 4 * h); }
            CS(3);
            bar_sync(NB_TAIL + warp, 64);
            CS(4);
            if (tid == 0) TL(5);
            uint32_t k0[16], v0[16];
            const uint32_t mine = sb + OFF_STG + wg * 16384 + w4 * 2048;
#pragma unroll
            for (int h = 0; h < 4; ++h) ldsm4(mine + lane * 16 + h * 512, k0[4 * h], k0[4 * h + 1], k0[4 * h + 2], k0[4 * h + 3]);
#pragma unroll
            for (int h = 0; h < 4; ++h) ldsm4t(mine + lane * 16 + 8192 + h * 512, v0[4 * h], v0[4 * h + 1], v0[4 * h + 2], v0[4 * h + 3]);
#pragma unroll
            for (int h = 0; h < 4; ++h) qk(s[h][0], h, k0 + 4 * h);
            const bool lo0 = q4 * 2 > g8, lo1 = q4 * 2 + 1 > g8;
            const bool nopast = m == 0 && (warp & 5) == 0;
            const uint32_t lomask = (lo0 ? 0xFFFFu : 0u) | (lo1 ? 0xFFFF0000u : 0u);
            const float sl2 = 0.17677669529663687f * 1.4426950408889634f;
            float e0[8], e1[8], mx[8], sum[8], tt[8];
#pragma unroll
            for (int u = 0; u < 8; ++u) {
                const int h = u >> 1, hf = u & 1;
                e0[u] = lo0 ? ((hf == 0 && nopast) ? -INFINITY : s[h][hf][hf * 2]) : s[h][hf + 1][hf * 2];
                e1[u] = lo1 ? ((hf == 0 && nopast) ? -INFINITY : s[h][hf][hf * 2 + 1]) : s[h][hf + 1][hf * 2 + 1];
                mx[u] = fmaxf(e0[u], e1[u]);
                tt[u] = __shfl_xor_sync(0xffffffffu, mx[u], 1);
            }
            SCHED_FENCE(1);
#pragma unroll
            for (int u = 0; u < 8; ++u) { mx[u] = fmaxf(mx[u], tt[u]); tt[u] = __shfl_xor_sync(0xffffffffu, mx[u], 2); }
            SCHED_FENCE(2);
#pragma unroll
            for (int u = 0; u < 8; ++u) {
                const float c = -fmaxf(mx[u], tt[u]) * sl2;
                e0[u] = ex2(fmaf(e0[u], sl2, c)); e1[u] = ex2(fmaf(e1[u], sl2, c));
            }
            SCHED_FENCE(3);
#pragma unroll
            for (int u = 0; u < 8; ++u) { sum[u] = e0[u] + e1[u]; tt[u] = __shfl_xor_sync(0xffffffffu, sum[u], 1); }
            SCHED_FENCE(4);
#pragma unroll
            for (int u = 0; u < 8; ++u) { sum[u] += tt[u]; tt[u] = __shfl_xor_sync(0xffffffffu, sum[u], 2); }
            SCHED_FENCE(5);
#pragma unroll
            for (int u = 0; u < 8; ++u) sum[u] = rcp(sum[u] + tt[u]);
            SCHED_FENCE(6);
            CS(5);
            float o[8][2][4];
#pragma unroll
            for (int u = 0; u < 8; ++u) {
                const int h = u >> 1;
                const uint32_t p = pack2(e0[u] * sum[u], e1[u] * sum[u]);
                const uint32_t* va = ((u & 1) ? v1 : v0) + 4 * h;
                const uint32_t* vb = ((u & 1) ? v2 : v1) + 4 * h;
#pragma unroll
                for (int d = 0; d < 2; ++d) {
                    o[u][d][0] = o[u][d][1] = o[u][d][2] = o[u][d][3] = 0.f;
                    mma16816(o[u][d], va[2 * d], va[2 * d + 1], vb[2 * d], vb[2 * d + 1], p & lomask, p & ~lomask);
                }
            }
            SCHED_FENCE(7);
            const uint32_t orow = mine + (lane & 7) * 128 + (((lane >> 3) ^ (lane & 7)) << 4);
#pragma unroll
            for (int u = 0; u < 8; ++u)
                stsm4t((orow ^ (((u >> 1) & 1) << 6)) + (u >> 2) * 8192 + (u & 1) * 1024, pack2(o[u][0][0], o[u][0][1]), pack2(o[u][0][2], o[u][0][3]),
                       pack2(o[u][1][0], o[u][1][1]), pack2(o[u][1][2], o[u][1][3]));
            fence_async_smem();
            __syncwarp();
            if (lane < 2) mbar_arrive(BAR_SFULL(sb, wg * 2 + lane));
            CS(6);
            if (tid == 32) TL(41);
            bar_sync(1 + wg, 128);
            if (tid == 0) { TL(6); TC(106); }
            if (tid == 128) TL(44);
            CS(7);
#pragma unroll
            for (int e = 0; e < 32; ++e) xp[e] = qf[e];
        }
        } else {
        {
            float ag[88], au[88];
            mainloop32<true, LAG>(ag, au, sb, wg, tw, r, EV_LAG1, 48, [&] {
                stg.acquire2(sb, wg);
                Ring q = r; if (!wg) q.next();
                mbar_wait(BAR_EMPTY(sb, q.slot), q.par ^ 1);
            });
            if (tid == 0) { TL(10); TC(110); }
            if (tid == 128) TL(51);
            CS(22);
            glu<11>(sb, wg, [&](int i) { return ag[i]; }, [&](int i) { return au[i]; },
                    [&](int pn) { return pn < 2 ? sb + OFF_STG + wg * 16384 + pn * 8192 : sb + (wg ? P3_SLOT1 : P3_SLOT0) * SLOT + 24576; });
            if (tid == 0) { TL(11); TC(111); }
            if (tid == 128) TL(52);
            CS(23);
        }
        passes128<2>(sb, wg, tw, r, stg);
        if (tid == 0) { TL(12); TC(112); }
        }
        {
            float acc[64], gf[32];
            mainloop64(acc, blk == 0, sb, wg, tw, r, [&] {
                mbar_wait(BAR_ONE(sb, EV_GA + blk), 0);
                const uint32_t buf = stg.acquire2(sb, wg);
                if (blk == 0) load_slab(xp, buf);
                unpack_slab(xs, xp);
                uint32_t gt[16];
#pragma unroll
                for (int cg = 0; cg < 16; ++cg) gt[cg] = lds32(sb + OFF_TAB + blk * 256 + cg * 16 + (tw & 3) * 4);
#pragma unroll
                for (int i = 0; i < 16; ++i) unpack2(gt[i], gf[2 * i], gf[2 * i + 1]);
            });
            if (tid == 0) { TL(blk ? 13 : 7); TC(blk ? 113 : 107); }
            if (tid == 128) TL(blk ? 57 : 42);
            CS(blk ? 30 : 10);
#pragma unroll
            for (int e = 0; e < 64; ++e) xs[e] = fmaf(gf[(e >> 2) * 2 + (e & 1)], acc[e], xs[e]);
        }
        if (blk) break;
        }
        cluster_arrive();
        {
            IDX();
#pragma unroll
            for (int p = 0; p < 2; ++p) {
                store_slab(xs, sb + OFF_STG + wg * 16384, 8192, pan_addr, 4 * p, 4 * p + 4);
                stg.publish(sb, wg, lane);
            }
            if (tid == 0) TL(14);
            CS(31);
        }
      }
    } else {
        if (warp == 8 && !aux && elect_one()) {
#pragma unroll
            for (int i = 0; i < 4; ++i) mbar_init(BAR_SREADY(sb, i), 1);
#pragma unroll
            for (int i = 0; i < 4; ++i) mbar_init(BAR_ONE(sb, EV_WIN + i), 1);
#pragma unroll
            for (int i = 0; i < 4; ++i) {
                mbar_expect_tx(BAR_SREADY(sb, i), 8192);
                tma_load3(sb + OFF_STG + i * 8192, &mp.x, j * 128 + (i & 1) * 64, m * 64 + (i >> 1) * 32, BAR_SREADY(sb, i));
            }
#pragma unroll 1
            for (int i = 0; i < 4; ++i) {
                mbar_expect_tx(BAR_ONE(sb, EV_WIN + i), 8192);
                tma_load(sb + 5 * SLOT + i * 8192, &mp.wm8, 2 * i * 6144 + (m * 8 + j) * 16, 0, BAR_ONE(sb, EV_WIN + i));
                tma_load(sb + 5 * SLOT + i * 8192 + 4096, &mp.wm8, (2 * i + 1) * 6144 + (m * 8 + j) * 16, 0, BAR_ONE(sb, EV_WIN + i));
            }
        }
        __syncwarp();
        asm volatile("setmaxnreg.dec.sync.aligned.u32 56;");
        if (elect_one()) {
            if (warp == 8) {
                prefetch_map(&mp.wqkv); prefetch_map(&mp.wmod);
            } else if (warp < 11) {
                mbar_init(BAR_EMPTY(sb, NSLOT), 1);
#pragma unroll
                for (int i = 0; i < 2; ++i) { mbar_init(BAR_SFULL(sb, (warp - 9) * 2 + i), 4); if (aux) mbar_init(BAR_SREADY(sb, (warp - 9) * 2 + i), 1); }
#pragma unroll
                for (int i = 0; i < 3; ++i) {
                    mbar_init(BAR_EMPTY(sb, (warp - 9) * 3 + i), 4);
                    mbar_init(BAR_FULL(sb, (warp - 9) * 3 + i), 1); mbar_init(BAR_FULL(sb, (warp - 9) * 3 + i) + AF_REL, 1);
                }
            } else {
#pragma unroll
                for (int i = EV_P0; i < EV_COUNT; ++i) mbar_init(BAR_ONE(sb, i), i == EV_P0 ? 8 : 1);
            }
            asm volatile("fence.mbarrier_init.release.cluster;" ::: "memory");
        }
        __syncwarp();
        cluster_arrive();
        ep = 0;
        if (warp != 8 || aux) ep = flag_get(g_flags + FL_DONE);
        cluster_wait();
        ep = __shfl_sync(0xffffffffu, ep, 0) / NCTA + 1;
        if (warp == 8) {
            const bool el = elect_one();
            Ring r{0, 1};
            if (aux) {
                mbar_wait(BAR_ONE(sb, EV_GO), 0);
#pragma unroll 1
                for (int it = 0; it < 64; ++it) {
                    const int col = 2048 + (it >> 4) * 1024 + j * 256;
                    mbar_wait(BAR_EMPTY(sb, r.slot), r.par);
                    const uint32_t st = sb + r.slot * SLOT, fb = BAR_FULL(sb, r.slot);
                    if (el) {
                        mbar_expect_tx(fb, 32768);
#pragma unroll
                        for (int b = 0; b < 4; ++b) tma_load(st + b * 8192, &mp.wmod, col + b * 64, (it & 15) * 64, fb);
                    }
                    r.next();
                }
                mbar_wait(BAR_ONE(sb, EV_P0), 0);
                const CUtensorMap* wm = rank ? &mp.wu : &mp.wg;
#pragma unroll 1
                for (int g = 0; g < 128; ++g) {
                    const int mx = (j >> 1) * 8 + (g >> 5) * 2 + rank, k0 = (g & 31) * 32;
                    if (k0 == 0) {
                        uint32_t n = 0;
                        while (!__all_sync(0xffffffffu, (int32_t)(flag_get(g_flags + FL_PROG + (mx * 32 + lane) * FS) - (ep * 8 + ST_H2)) >= 0)) { SPIN_GUARD(n); __nanosleep(500); }
                    }
                    mbar_wait(BAR_EMPTY(sb, r.slot), r.par);
                    const uint32_t st = sb + r.slot * SLOT, fb = BAR_FULL(sb, r.slot);
                    if (el) {
                        mbar_expect_tx(fb, 24576);
                        tma_load_mc(st + 8192 + rank * 4096, wm, HC3, k0, fb);
                        tma_load_mc(st + 16384 + rank * 4096, wm, HC3 + 64, k0, fb);
                        tma_load(st, &mp.h2l, k0, mx * 128, fb);
                    }
                    r.next();
                }
            } else {
#pragma unroll 1
                for (int it = 0; it < 32; ++it) {
                    const int cb = j * 128 + rank * 64, k0 = kof(it, 2, j);
                    if (it == BW0) mbar_wait(BAR_ONE(sb, BWEV), 0);
                    if (it == BW1) mbar_wait(BAR_ONE(sb, EV_PAR), 0);
                    if (it == 5) mbar_wait(BAR_ONE(sb, EV_P0), 0);
                    if (it == 6) mbar_wait(BAR_ONE(sb, (AGW & 1) ? EV_AGO : EV_FGO), 0);
                    mbar_wait(BAR_EMPTY(sb, r.slot), r.par);
                    const uint32_t st = sb + r.slot * SLOT, fb = BAR_FULL(sb, r.slot);
                    if (el) {
                        mbar_expect_tx(fb, it < 4 ? 24576 : 28672);
                        tma_load_mc(st + 8192 + rank * 4096, &mp.wqkv, 1024 + cb, k0, fb);
                        tma_load_mc(st + 16384 + rank * 4096, &mp.wqkv, 2048 + cb, k0, fb);
                        tma_load_mc(st + 24576 + rank * 4096, &mp.wqkv, cb, k0, fb);
                        if (it < 4) mbar_arrive(fb + AF_REL);
                        if (it == PFWO + (m >> 1)) { tma_prefetch(&mp.wo, j * 128, m * 64); tma_prefetch(&mp.wo, j * 128 + 64, m * 64); }
                    }
                    r.next();
                }
                if (el) mbar_arrive(BAR_ONE(sb, EV_KV));
#pragma unroll 1
                for (int it = 0; it < 16; ++it) {
                    if (it == 6) mbar_wait(BAR_ONE(sb, (AGW & 2) ? EV_AGO1 : EV_FGO1), 0);
                    mbar_wait(BAR_EMPTY(sb, r.slot), r.par);
                    const uint32_t st = sb + r.slot * SLOT, fb = BAR_FULL(sb, r.slot);
                    if (el) {
                        mbar_expect_tx(fb, it < 2 ? 16384 : 24576);
                        tma_load_mc(st + 16384 + rank * 8192, &mp.wo, j * 128 + rank * 64, kof(it, 1, j), fb);
                        if (it < 2) mbar_arrive(fb + AF_REL);
                        if (it == 6) { prefetch_map(rank ? &mp.wu : &mp.wg); prefetch_map(rank ? &mp.wu3 : &mp.wg3); }
                    }
                    r.next();
                }
                const CUtensorMap* wm = rank ? &mp.wu : &mp.wg;
#pragma unroll 1
                for (int g = 0; g < 96; ++g) {
                    if (g == 6) mbar_wait(BAR_ONE(sb, (AGW & 4) ? EV_AGO2 : EV_FGO2), 0);
                    const int p = g >> 5, cb = hcol(p, j), k0 = p == 0 ? kof(g, 2, j) : (g & 31) * 32;
                    mbar_wait(BAR_EMPTY(sb, r.slot), r.par);
                    const uint32_t st = sb + r.slot * SLOT, fb = BAR_FULL(sb, r.slot);
                    if (el) {
                        mbar_expect_tx(fb, (g < 4 || p > 0) ? 24576 : 28672);
                        tma_load_mc(st + 8192 + rank * 4096, wm, cb, k0, fb);
                        tma_load_mc(st + 16384 + rank * 4096, wm, cb + 64, k0, fb);
                        if (p == 0) tma_load3_mc(st + 24576 + rank * 4096, rank ? &mp.wu3 : &mp.wg3, j, k0, fb);
                        else tma_load(st, &mp.h2l, k0, m * 128, fb);
                        if (g < 4) mbar_arrive(fb + AF_REL);
                        if (g == 60) prefetch_map(&mp.wd);
                    }
                    r.next();
                }
#pragma unroll 1
                for (int g = 0; g < 56; ++g) {
                    if (g == 0 || (g & 15) == 6 && g > 6) mbar_wait(BAR_ONE(sb, EV_H0 + (g >> 4)), 0);
                    const int k0 = g * 64;
                    mbar_wait(BAR_EMPTY(sb, r.slot), r.par);
                    const uint32_t st = sb + r.slot * SLOT, fb = BAR_FULL(sb, r.slot);
                    if (el) {
                        mbar_expect_tx(fb, 32768);
                        tma_load_mc(st + 16384 + rank * 8192, &mp.wd, j * 128 + rank * 64, k0, fb);
                        tma_load(st, &mp.hb, k0, m * 128, fb); tma_load(st + 8192, &mp.hb, k0, m * 128 + 64, fb);
                    }
                    r.next();
                }
            }
        } else if (aux) {
            if (warp < 11) {
                const uint32_t w = warp - 9;
                const bool el = elect_one();
#pragma unroll 1
                for (int p = 0; p < 4; ++p) {
                    const int mx = (j >> 1) * 8 + p * 2 + rank;
                    if (el) { mbar_arrive(BAR_SREADY(sb, w * 2)); mbar_arrive(BAR_SREADY(sb, w * 2 + 1)); }
                    mbar_wait2(BAR_SFULL(sb, w * 2), BAR_SFULL(sb, w * 2 + 1), p & 1);
                    if (el) {
                        tma_store(&mp.hb, HC3, mx * 128 + w * 64, sb + OFF_STG + w * 16384); tma_store(&mp.hb, HC3 + 64, mx * 128 + w * 64, sb + OFF_STG + w * 16384 + 8192);
                        bulk_commit(); bulk_wait_all(); flag_set(g_flags + FL_AUX + mx * 2 + w, ep * 8 + ST_H + 3);
                    }
                }
            }
        } else if (warp == 11) {
            const bool el = elect_one();
            const int row0 = m * 128;
            const uint32_t* const fl = g_flags + FL_PROG + (m * 32 + (lane & 16) + (kof(lane & 15, 1, j) >> 6)) * FS;
            if (el) { prefetch_map(&mp.h1h); prefetch_map(&mp.h2h); prefetch_map(&mp.h2l); }
            {
                const uint4* pk = pt.mail->mod1 + grp * 512 + j * 32 + lane;
                uint4 a, b; uint32_t n = 0;
                mbar_wait(BAR_ONE(sb, EV_WIN3), 0);
                while (true) {
                    a = ld_pkt16(pk); b = ld_pkt16(pk + 256);
                    if (__all_sync(0xffffffffu, a.z == ep && b.z == ep)) break;
                    SPIN_GUARD(n);
                }
                sts128(sb + OFF_PAR + lane * 16, a.x, a.y, b.x, b.y);
                __syncwarp();
                if (lane == 0) { mbar_arrive(BAR_ONE(sb, EV_PAR)); TL(46); }
            }
            mbar_wait(BAR_ONE(sb, EV_P0), 0);
            Ring r{0, 1};
#pragma unroll 1
            for (int ph = 0; ph < 3; ++ph) {
                const int sh = ph == 1 ? 1 : 2, nst = 8 << sh;
                const uint32_t half = 16384 >> sh;
                const CUtensorMap* tm = ph == 0 ? &mp.h1h : ph == 1 ? &mp.o : &mp.h2h;
                if (ph == 1) fetch_halo(g_halo + ((m - 1) * 8 + j) * 512 + 256 + lane, m == 0, sb, 2, lane);
                const uint32_t target = ep * 8 + ST_H1 + ph;
                int a0 = 1 << sh, a1 = a0, fr = a0;
                r.skip(fr);
                uint32_t s0 = r.slot, s1 = r.slot, have = 0, n = 0;
                int k0 = j ? 0 : 128, k1 = k0;
#pragma unroll 1
                for (; fr < NSLOT; ++fr) { mbar_wait(BAR_EMPTY(sb, r.slot), r.par); r.next(); }
                uint32_t v = flag_get(fl);
                auto load = [&](int& a, uint32_t& sl, int& k, uint32_t w) {
                    const uint32_t fb = BAR_FULL(sb, sl) + (w ? 0 : AF_REL);
                    if (el) { if (!w) mbar_expect_tx(fb, half); tma_load(sb + sl * SLOT + w * half, tm, k, row0 + w * 64, fb); }
                    if (a == NSLOT - 1 && el) mbar_arrive(BAR_ONE(sb, (w ? EV_AGO : EV_FGO) + ph));
                    ++a; if (++sl == NSLOT) sl = 0;
                    k = kof(a, sh, j);
                };
                do {
                    PS(0);
                    if (fr < 9 && mbar_test(BAR_EMPTY(sb, r.slot), r.par)) { ++fr; r.next(); }
                    SPIN_GUARD(n);
                    PS(1);
                    const bool ok = (int32_t)(v - target) >= 0;
                    v = flag_get(fl);
                    have = __ballot_sync(0xffffffffu, ok);
                    PS(2);
#pragma unroll 1
                    while (a1 < fr && (have & (0x10000u << (a1 >> (sh - 1))))) {
                        if (a1 == (1 << sh)) TL(16 + ph);
                        load(a1, s1, k1, 1);
                    }
                    PS(3);
#pragma unroll 1
                    while (a0 < fr && (have & (1u << (a0 >> (sh - 1))))) load(a0, s0, k0, 0);
                    PS(4);
                } while (~have & 0x01fc01fcu);
#pragma unroll 1
                while (a0 < nst) {
                    if (a0 == 9 << (sh - 1)) while (!__all_sync(0xffffffffu, (int32_t)(flag_get(fl) - target) >= 0)) SPIN_GUARD(n);
                    mbar_wait(BAR_EMPTY(sb, r.slot), r.par);
                    r.next();
                    load(a1, s1, k1, 1); load(a0, s0, k0, 0);
                }
            }
#pragma unroll 1
            for (int p = 0; p < 4; ++p) {
                const uint32_t* f = p < 3 ? fl : g_flags + FL_AUX + m * 2 + (lane & 1);
                uint32_t n = 0;
                while (!__all_sync(0xffffffffu, (int32_t)(flag_get(f) - (ep * 8 + ST_H + p)) >= 0)) { SPIN_GUARD(n); __nanosleep(500); }
                if (el) mbar_arrive(BAR_ONE(sb, EV_H0 + p));
            }
        } else {
            const uint32_t w = warp - 9;
            const int row0 = m * 128 + w * 64;
            const uint32_t stg = sb + OFF_STG + w * 16384;
            uint32_t* const fl = g_flags + FL_PROG + (m * 32 + w * 16 + 2 * j) * FS;
            uint32_t b = 0, par = 0;
            const bool el = elect_one();
            auto store = [&](const CUtensorMap* tm, int col, bool nat = false) {
                mbar_wait(BAR_SFULL(sb, w * 2 + b), (par >> b) & 1);
                par ^= 1u << b;
                if (el) {
                    if (nat) tma_store3(tm, col, row0 >> 1, 0, stg + b * 8192); else tma_store(tm, col, row0, stg + b * 8192);
                    bulk_commit();
                }
                b ^= 1;
            };
            auto send2 = [&](const CUtensorMap* tm, int step) {
                const bool now = step == ST_O && w;
                store(tm, j * 128);
                if (!now) {
                    if (el) { bulk_wait_all(); flag_set(fl, ep * 8 + step); }
                    mbar_wait(BAR_ONE(sb, EV_FGO + step - ST_H1), 0);
                    if (step != ST_O) pause(w ? P1H : P1H + 1000);
                }
                store(tm, j * 128 + 64);
                if (el) {
                    if (now) { asm volatile("cp.async.bulk.wait_group 1;" ::: "memory"); flag_set(fl, ep * 8 + step); }
                    bulk_wait_all(); flag_set(fl + FS, ep * 8 + step);
                }
            };
            auto free2 = [&]() { if (el) { mbar_arrive(BAR_SREADY(sb, w * 2)); mbar_arrive(BAR_SREADY(sb, w * 2 + 1)); } };
            auto gate = [&](int vec, int ev) {
                uint4 v; uint32_t n = 0;
                while (true) {
                    v = ld_pkt2(g_mod + vec * 512 + j * 64 + lane * 2);
                    if (__all_sync(0xffffffffu, v.y == ep && v.w == ep)) break;
                    SPIN_GUARD(n); __nanosleep(300);
                }
                asm volatile("st.shared.v2.u32 [%0], {%1, %2};" :: "r"(sb + OFF_TAB + (ev - EV_GA) * 256 + lane * 8), "r"(v.x), "r"(v.z) : "memory");
                __syncwarp();
                if (lane == 0) mbar_arrive(BAR_ONE(sb, ev));
            };
            if (el) { prefetch_map(&mp.h1s); prefetch_map(&mp.o); prefetch_map(&mp.h2s); prefetch_map(&mp.hb); prefetch_map(&mp.out); prefetch_map(&mp.wo); }
            if (el) { flag_set(fl, ep * 8); flag_set(fl + FS, ep * 8); }
            send2(&mp.h1s, ST_H1);
            if (w == 0) TL(47);
            free2();
            if (w == 0) fetch_halo(g_halo + ((m - 1) * 8 + j) * 512 + lane, m == 0, sb, 0, lane);
            else { mbar_wait(BAR_ONE(sb, EV_KV), 0); gate(2, EV_GA); }
            send2(&mp.o, ST_O);
            if (w == 0) TL(40); else TL(38);
            mbar_wait(BAR_ONE(sb, EV_OWN + w), 0);
            if (el) {
#pragma unroll
                for (uint32_t i = 0; i < 2; ++i) {
                    mbar_expect_tx(BAR_SREADY(sb, w * 2 + i), 8192);
                    tma_load3(stg + i * 8192, &mp.x, j * 128 + i * 64, row0 >> 1, BAR_SREADY(sb, w * 2 + i));
                }
            }
            if (w == 1) {
                uint32_t n = 0;
                while ((int32_t)(flag_get(g_flags + FL_LN2) - ep * 8) < 0) { SPIN_GUARD(n); __nanosleep(200); }
                const uint4 v = __ldcg((const uint4*)(g_par2 + j * 128) + lane);
                sts128(sb + OFF_PAR + lane * 16, v.x, v.y, v.z, v.w);
                __syncwarp();
                if (lane == 0) mbar_arrive(BAR_ONE(sb, EV_LN2));
            }
            send2(&mp.h2s, ST_H2);
            if (el) { prefetch_map(&mp.hb); prefetch_map(&mp.hb3); }
            if (w == 0) TL(37);
            free2();
#pragma unroll 1
            for (int p = 0; p < 3; ++p) {
                const int col = hcol(p, j);
                mbar_wait(BAR_SFULL(sb, w * 2), par & 1);
                pause(w ? HD1 : HD0); store(&mp.hb, col);
                pause(HP); store(&mp.hb, col + 64);
                if (p == 0) {
                    pause(HP);
                    if (el) { tma_store3(&mp.hb3, 0, j, row0, sb + (w ? P3_SLOT1 : P3_SLOT0) * SLOT + 24576); bulk_commit(); }
                }
                if (el) { bulk_wait_all(); flag_set(fl, ep * 8 + ST_H + p); flag_set(fl + FS, ep * 8 + ST_H + p); }
                free2();
                if (p == 0 && w == 1) gate(5, EV_GB);
            }
            cluster_arrive_early = true;
            cluster_arrive();
            store(&mp.out, j * 128, true); store(&mp.out, j * 128 + 64, true);
            if (el) bulk_wait_read();
        }
        __syncwarp();
    }
    if (aux || (wg == 2 && !cluster_arrive_early)) cluster_arrive();
    cluster_wait();
    CS(32);
    if (KDEBUG == 5) __syncthreads();
    if (tid == 0) {
        TL(15);
        flag_add(pt.mail->flags + FL_DONE);
    }
}

typedef CUresult (*EncodeFn)(CUtensorMap*, CUtensorMapDataType, cuuint32_t, void*, const cuuint64_t*, const cuuint64_t*, const cuuint32_t*,
                             const cuuint32_t*, CUtensorMapInterleave, CUtensorMapSwizzle, CUtensorMapL2promotion, CUtensorMapFloatOOBfill);

void make_map(EncodeFn fn, CUtensorMap* m, const void* ptr, uint64_t rows, uint64_t cols, uint32_t brows, uint32_t bcols) {
    cuuint64_t dims[2] = {cols, rows}, strides[1] = {cols * 2};
    cuuint32_t box[2] = {bcols, brows}, es[2] = {1, 1};
    fn(m, CU_TENSOR_MAP_DATA_TYPE_BFLOAT16, 2, (void*)ptr, dims, strides, box, es, CU_TENSOR_MAP_INTERLEAVE_NONE,
       bcols == 64 ? CU_TENSOR_MAP_SWIZZLE_128B : bcols == 32 ? CU_TENSOR_MAP_SWIZZLE_64B : CU_TENSOR_MAP_SWIZZLE_NONE, CU_TENSOR_MAP_L2_PROMOTION_L2_256B, CU_TENSOR_MAP_FLOAT_OOB_FILL_NONE);
}

void make_map3(EncodeFn fn, CUtensorMap* m, const void* ptr) {
    cuuint64_t dims[3] = {D_, S_ / 2, 2}, strides[2] = {4 * D_, 2 * D_};
    cuuint32_t box[3] = {64, 32, 2}, es[3] = {1, 1, 1};
    fn(m, CU_TENSOR_MAP_DATA_TYPE_BFLOAT16, 3, (void*)ptr, dims, strides, box, es, CU_TENSOR_MAP_INTERLEAVE_NONE,
       CU_TENSOR_MAP_SWIZZLE_128B, CU_TENSOR_MAP_L2_PROMOTION_L2_256B, CU_TENSOR_MAP_FLOAT_OOB_FILL_NONE);
}

void make_map48(EncodeFn fn, CUtensorMap* m, const void* ptr, uint64_t rows, uint32_t brows) {
    cuuint64_t dims[3] = {48, 8, rows}, strides[2] = {96, 2 * F_};
    cuuint32_t box[3] = {64, 1, brows}, es[3] = {1, 1, 1};
    fn(m, CU_TENSOR_MAP_DATA_TYPE_BFLOAT16, 3, (void*)ptr, dims, strides, box, es, CU_TENSOR_MAP_INTERLEAVE_NONE,
       CU_TENSOR_MAP_SWIZZLE_128B, CU_TENSOR_MAP_L2_PROMOTION_L2_256B, CU_TENSOR_MAP_FLOAT_OOB_FILL_NONE);
}

}

extern "C" void kernel_launch(void* const* d_in, const int* in_sizes, int n_in, void* d_out, int out_size) {
    (void)in_sizes; (void)n_in; (void)out_size;
    void* fnp = nullptr;
    cudaDriverEntryPointQueryResult qr;
    cudaGetDriverEntryPoint("cuTensorMapEncodeTiled", &fnp, cudaEnableDefault, &qr);
    EncodeFn fn = (EncodeFn)fnp;
    void *h1, *o, *h2, *hb, *mail;
    cudaGetSymbolAddress(&h1, g_h1);
    cudaGetSymbolAddress(&mail, g_mail);
    cudaGetSymbolAddress(&o, g_o);
    cudaGetSymbolAddress(&hb, g_hb);
    h2 = H2ALIAS;
    Maps mp;
    make_map(fn, &mp.h1h, h1, S_, D_, 64, 32);
    make_map(fn, &mp.h2h, h2, S_, D_, 64, 32);
    make_map(fn, &mp.h1s, h1, S_, D_, 64, 64);
    make_map(fn, &mp.o, o, S_, D_, 64, 64);
    make_map(fn, &mp.h2l, h2, S_, D_, 128, 32);
    make_map(fn, &mp.h2s, h2, S_, D_, 64, 64);
    make_map(fn, &mp.hb, hb, S_, F_, 64, 64);
    make_map(fn, &mp.wqkv, d_in[1], D_, 3 * D_, 32, 64);
    make_map(fn, &mp.wo, d_in[2], D_, D_, 64, 64);
    make_map(fn, &mp.wg, d_in[4], D_, F_, 32, 64);
    make_map(fn, &mp.wu, d_in[5], D_, F_, 32, 64);
    make_map(fn, &mp.wd, d_in[6], F_, D_, 64, 64);
    make_map(fn, &mp.wmod, d_in[8], D_, 6 * D_, 64, 64);
    make_map(fn, &mp.wm8, d_in[8], D_ / 8, 8 * 6 * D_, 128, 16);
    make_map3(fn, &mp.x, d_in[0]);
    make_map3(fn, &mp.out, d_out);
    make_map48(fn, &mp.wg3, d_in[4], D_, 32);
    make_map48(fn, &mp.wu3, d_in[5], D_, 32);
    make_map48(fn, &mp.hb3, hb, S_, 64);
    cudaFuncSetAttribute(fused_block_kernel, cudaFuncAttributeMaxDynamicSharedMemorySize, SMEM_BYTES);
    cudaLaunchConfig_t cfg = {};
    cfg.gridDim = dim3(NCTA); cfg.blockDim = dim3(384); cfg.dynamicSmemBytes = SMEM_BYTES; cfg.stream = cudaStreamPerThread;
    cudaLaunchAttribute at[1];
    at[0].id = cudaLaunchAttributeClusterDimension; at[0].val.clusterDim.x = 2; at[0].val.clusterDim.y = 1; at[0].val.clusterDim.z = 1;
    cfg.attrs = at; cfg.numAttrs = 1;
    const Ptrs pt{(const __nv_bfloat16*)d_in[7], (Mail*)mail};
    cudaLaunchKernelEx(&cfg, fused_block_kernel, pt, mp);
}
```

```cpp
#include <cuda_runtime.h>
#include <cuda_bf16.h>
#include <cuda.h>
#include <stdint.h>
#include <stddef.h>

#define LAG 4
#define LAGS 4
#define LAGW 3
#define LAGQ 4
#define MIDW 8
#define PFWO 14
#define FLAGRED 1
#define FS 1
#define P1H 2000
#define AGW 6
#define CSW 0
#define LWAIT 2
#define BW0 0
#define BWEV EV_WIN
#define GODLY 0
#define BW1 3
#define PDLY 500
#define H2ALIAS o
#define HD1 5500
#define HD0 5500
#define HP 2200
#define LAGD 4
#define MIDD 44
#define ONOW 1
#define KDEBUG 0

namespace {

constexpr int S_ = 2048, D_ = 1024, F_ = 3584;
constexpr int NCTA = 132;
constexpr int NSLOT = 6;
constexpr uint32_t SLOT = 32768;
constexpr uint32_t OFF_STG = NSLOT * SLOT;
constexpr uint32_t OFF_BAR = OFF_STG + 32768;
constexpr uint32_t OFF_PAR = OFF_BAR + 512;
constexpr uint32_t OFF_TAB = OFF_PAR + 768;
constexpr uint32_t OFF_TL = OFF_PAR + 2048;
constexpr uint32_t SMEM_BYTES = OFF_TL + (KDEBUG ? 512 : 0);
constexpr uint32_t P3_SLOT1 = (32 + 16 + 32) % NSLOT, P3_SLOT0 = (P3_SLOT1 + 1) % NSLOT;

constexpr int ST_H1 = 1, ST_O = 2, ST_H2 = 3, ST_H = 4, FL_DONE = 0, FL_LN2 = 1, FL_AUX = 32, FL_PROG = 64;

struct Maps {
    CUtensorMap h1h, h1s, o, h2h, h2l, h2s, hb, wqkv, wo, wg, wu, wd, wmod, wm8, x, out, wg3, wu3, hb3;
};

struct Mail {
    uint32_t flags[16 * 32 * FS + 64];
    uint2 mod[6 * D_ / 2];
    uint4 mod1[8 * 512];
    uint4 st1[128 * 512];
    uint32_t par2[D_];
    uint4 halo[128 * 512];
};
struct Ptrs { const __nv_bfloat16* c; Mail* mail; };

__device__ __align__(128) Mail g_mail;
__device__ __align__(128) __nv_bfloat16 g_h1[S_ * D_];
__device__ __align__(128) __nv_bfloat16 g_o[S_ * D_];
__device__ __align__(128) __nv_bfloat16 g_hb[S_ * F_];
#define TL(i) do {} while (0)
#define TC(i) do {} while (0)
#define TS(g, which) do {} while (0)
#define CS(i) do {} while (0)

#define PS(i) do {} while (0)
__device__ __forceinline__ uint32_t smem_u32(const void* p) { return (uint32_t)__cvta_generic_to_shared(p); }
__device__ __forceinline__ void mbar_init(uint32_t bar, uint32_t cnt) { asm volatile("mbarrier.init.shared::cta.b64 [%0], %1;" :: "r"(bar), "r"(cnt) : "memory"); }
__device__ __forceinline__ void mbar_expect_tx(uint32_t bar, uint32_t bytes) { asm volatile("mbarrier.arrive.expect_tx.shared::cta.b64 _, [%0], %1;" :: "r"(bar), "r"(bytes) : "memory"); }
__device__ __forceinline__ void mbar_arrive(uint32_t bar) { asm volatile("mbarrier.arrive.shared::cta.b64 _, [%0];" :: "r"(bar) : "memory"); }
__device__ __forceinline__ void mbar_arrive_cta(uint32_t bar, uint32_t cta) {
    asm volatile("{\n.reg .b32 r;\nmapa.shared::cluster.u32 r, %0, %1;\nmbarrier.arrive.shared::cluster.b64 _, [r];\n}" :: "r"(bar), "r"(cta) : "memory");
}
__device__ __forceinline__ void mbar_wait(uint32_t bar, uint32_t parity) {
    asm volatile("{\n.reg .pred p;\n.reg .u32 n;\nmov.u32 n, 0;\n"
        "W_LOOP:\nmbarrier.try_wait.parity.shared::cta.b64 p, [%0], %1;\n@p bra W_DONE;\n"
        "add.u32 n, n, 1;\nsetp.lt.u32 p, n, 0x400000;\n@p bra W_LOOP;\ntrap;\nW_DONE:\n}" :: "r"(bar), "r"(parity) : "memory");
}
__device__ __forceinline__ void mbar_wait2(uint32_t b0, uint32_t b1, uint32_t parity) {
    asm volatile("{\n.reg .pred p, q;\n.reg .u32 n;\nmov.u32 n, 0;\n"
        "W_LOOP:\nmbarrier.try_wait.parity.shared::cta.b64 p, [%0], %2;\nmbarrier.try_wait.parity.shared::cta.b64 q, [%1], %2;\nand.pred p, p, q;\n@p bra W_DONE;\n"
        "add.u32 n, n, 1;\nsetp.lt.u32 p, n, 0x400000;\n@p bra W_LOOP;\ntrap;\nW_DONE:\n}" :: "r"(b0), "r"(b1), "r"(parity) : "memory");
}
__device__ __forceinline__ bool mbar_test(uint32_t bar, uint32_t parity) {
    uint32_t r; asm volatile("{\n.reg .pred p;\nmbarrier.test_wait.parity.shared::cta.b64 p, [%1], %2;\nselp.u32 %0, 1, 0, p;\n}" : "=r"(r) : "r"(bar), "r"(parity) : "memory"); return r;
}
__device__ __forceinline__ bool mbar_test2(uint32_t b0, uint32_t b1, uint32_t parity) {
    uint32_t r;
    asm volatile("{\n.reg .pred p, q;\nmbarrier.test_wait.parity.shared::cta.b64 p, [%1], %3;\nmbarrier.test_wait.parity.shared::cta.b64 q, [%2], %3;\n"
        "and.pred p, p, q;\nselp.u32 %0, 1, 0, p;\n}" : "=r"(r) : "r"(b0), "r"(b1), "r"(parity) : "memory");
    return r;
}
__device__ __forceinline__ void tma_load3(uint32_t dst, const CUtensorMap* m, int c0, int c1, uint32_t bar) {
    asm volatile("cp.async.bulk.tensor.3d.shared::cluster.global.mbarrier::complete_tx::bytes [%0], [%1, {%3, %4, %5}], [%2];"
        :: "r"(dst), "l"(m), "r"(bar), "r"(c0), "r"(c1), "r"(0) : "memory");
}
__device__ __forceinline__ void tma_store3(const CUtensorMap* m, int c0, int c1, int c2, uint32_t src) {
    asm volatile("cp.async.bulk.tensor.3d.global.shared::cta.bulk_group [%0, {%2, %3, %4}], [%1];" :: "l"(m), "r"(src), "r"(c0), "r"(c1), "r"(c2) : "memory");
}
__device__ __forceinline__ void tma_load3_mc(uint32_t dst, const CUtensorMap* m, int c1, int c2, uint32_t bar) {
    asm volatile("cp.async.bulk.tensor.3d.shared::cluster.global.mbarrier::complete_tx::bytes.multicast::cluster.L2::cache_hint [%0], [%1, {%3, %4, %5}], [%2], %6, %7;"
        :: "r"(dst), "l"(m), "r"(bar), "r"(0), "r"(c1), "r"(c2), "h"((uint16_t)3), "l"(0x12F0000000000000ull) : "memory");
}
__device__ __forceinline__ void tma_load(uint32_t dst, const CUtensorMap* m, int c0, int c1, uint32_t bar) {
    asm volatile("cp.async.bulk.tensor.2d.shared::cluster.global.mbarrier::complete_tx::bytes [%0], [%1, {%3, %4}], [%2];"
        :: "r"(dst), "l"(m), "r"(bar), "r"(c0), "r"(c1) : "memory");
}
__device__ __forceinline__ void tma_load_mc(uint32_t dst, const CUtensorMap* m, int c0, int c1, uint32_t bar) {
    asm volatile("cp.async.bulk.tensor.2d.shared::cluster.global.mbarrier::complete_tx::bytes.multicast::cluster.L2::cache_hint [%0], [%1, {%3, %4}], [%2], %5, %6;"
        :: "r"(dst), "l"(m), "r"(bar), "r"(c0), "r"(c1), "h"((uint16_t)3), "l"(0x12F0000000000000ull) : "memory");
}
__device__ __forceinline__ void tma_prefetch(const CUtensorMap* m, int c0, int c1) {
    asm volatile("cp.async.bulk.prefetch.tensor.2d.L2.global [%0, {%1, %2}];" :: "l"(m), "r"(c0), "r"(c1) : "memory");
}
__device__ __forceinline__ void tma_store(const CUtensorMap* m, int c0, int c1, uint32_t src) {
    asm volatile("cp.async.bulk.tensor.2d.global.shared::cta.bulk_group [%0, {%2, %3}], [%1];" :: "l"(m), "r"(src), "r"(c0), "r"(c1) : "memory");
}
__device__ __forceinline__ void bulk_commit() { asm volatile("cp.async.bulk.commit_group;" ::: "memory"); }
__device__ __forceinline__ void bulk_wait_read() { asm volatile("cp.async.bulk.wait_group.read 0;" ::: "memory"); }
__device__ __forceinline__ void bulk_wait_all() { asm volatile("cp.async.bulk.wait_group 0;" ::: "memory"); }
__device__ __forceinline__ void fence_async_smem() { asm volatile("fence.proxy.async.shared::cta;" ::: "memory"); }
__device__ __forceinline__ void prefetch_map(const CUtensorMap* m) { asm volatile("prefetch.tensormap [%0];" :: "l"(m) : "memory"); }
__device__ __forceinline__ void wg_fence() { asm volatile("wgmma.fence.sync.aligned;" ::: "memory"); }
__device__ __forceinline__ void wg_commit() { asm volatile("wgmma.commit_group.sync.aligned;" ::: "memory"); }
template <int N> __device__ __forceinline__ void wg_wait() { asm volatile("wgmma.wait_group.sync.aligned %0;" :: "n"(N) : "memory"); }
__device__ __forceinline__ void bar_sync(int id, int n) { asm volatile("bar.sync %0, %1;" :: "r"(id), "r"(n) : "memory"); }
__device__ __forceinline__ void bar_arrive(int id, int n) { asm volatile("bar.arrive %0, %1;" :: "r"(id), "r"(n) : "memory"); }
__device__ __forceinline__ void flag_add(uint32_t* f) { asm volatile("red.relaxed.gpu.global.add.u32 [%0], 1;" :: "l"(f) : "memory"); }
__device__ __forceinline__ void flag_set(uint32_t* f, uint32_t v) { asm volatile("red.relaxed.gpu.global.max.u32 [%0], %1;" :: "l"(f), "r"(v) : "memory"); }
__device__ __forceinline__ uint32_t flag_get(const uint32_t* f) { uint32_t v; asm volatile("ld.relaxed.gpu.global.u32 %0, [%1];" : "=r"(v) : "l"(f) : "memory"); return v; }
__device__ __forceinline__ uint32_t d16(uint32_t addr) { return (addr & 0x3FFFF) >> 4; }
__device__ __forceinline__ uint64_t mk_desc(uint32_t a16, uint32_t off, uint32_t lbo, uint32_t sbo, uint32_t swz) {
    const uint32_t lo = a16 + (off >> 4) + ((lbo >> 4) << 16), hi = (sbo >> 4) | (swz << 30);
    return ((uint64_t)hi << 32) | lo;
}
__device__ __forceinline__ uint32_t pack2(float lo, float hi) {
    uint32_t r; asm("cvt.rn.bf16x2.f32 %0, %1, %2;" : "=r"(r) : "f"(hi), "f"(lo)); return r;
}
__device__ __forceinline__ uint32_t hfma2_bf16(uint32_t a, uint32_t b, uint32_t c) {
    uint32_t r; asm("fma.rn.bf16x2 %0, %1, %2, %3;" : "=r"(r) : "r"(a), "r"(b), "r"(c)); return r;
}
__device__ __forceinline__ float bf_lo(uint32_t v) { return __uint_as_float(v << 16); }
__device__ __forceinline__ float bf_hi(uint32_t v) { return __uint_as_float(v & 0xFFFF0000u); }
__device__ __forceinline__ void unpack2(uint32_t v, float& lo, float& hi) {
    asm volatile("shl.b32 %0, %2, 16;\nand.b32 %1, %2, 0xffff0000;" : "=f"(lo), "=f"(hi) : "r"(v));
}
__device__ __forceinline__ float bf_round(float x) { return __bfloat162float(__float2bfloat16_rn(x)); }
__device__ __forceinline__ void stsm4(uint32_t addr, uint32_t r0, uint32_t r1, uint32_t r2, uint32_t r3) {
    asm volatile("stmatrix.sync.aligned.m8n8.x4.shared.b16 [%0], {%1, %2, %3, %4};" :: "r"(addr), "r"(r0), "r"(r1), "r"(r2), "r"(r3) : "memory");
}
__device__ __forceinline__ void stsm4t(uint32_t addr, uint32_t r0, uint32_t r1, uint32_t r2, uint32_t r3) {
    asm volatile("stmatrix.sync.aligned.m8n8.x4.trans.shared.b16 [%0], {%1, %2, %3, %4};" :: "r"(addr), "r"(r0), "r"(r1), "r"(r2), "r"(r3) : "memory");
}
__device__ __forceinline__ uint32_t movm(uint32_t a) { uint32_t d; asm volatile("movmatrix.sync.aligned.m8n8.trans.b16 %0, %1;" : "=r"(d) : "r"(a)); return d; }
__device__ __forceinline__ void ldsm4(uint32_t addr, uint32_t& r0, uint32_t& r1, uint32_t& r2, uint32_t& r3) {
    asm volatile("ldmatrix.sync.aligned.m8n8.x4.shared.b16 {%0, %1, %2, %3}, [%4];" : "=r"(r0), "=r"(r1), "=r"(r2), "=r"(r3) : "r"(addr) : "memory");
}
__device__ __forceinline__ void ldsm4t(uint32_t addr, uint32_t& r0, uint32_t& r1, uint32_t& r2, uint32_t& r3) {
    asm volatile("ldmatrix.sync.aligned.m8n8.x4.trans.shared.b16 {%0, %1, %2, %3}, [%4];" : "=r"(r0), "=r"(r1), "=r"(r2), "=r"(r3) : "r"(addr) : "memory");
}
__device__ __forceinline__ void mma16816(float (&c)[4], uint32_t a0, uint32_t a1, uint32_t a2, uint32_t a3, uint32_t b0, uint32_t b1) {
    asm("mma.sync.aligned.m16n8k16.row.col.f32.bf16.bf16.f32 {%0, %1, %2, %3}, {%4, %5, %6, %7}, {%8, %9}, {%0, %1, %2, %3};"
        : "+f"(c[0]), "+f"(c[1]), "+f"(c[2]), "+f"(c[3]) : "r"(a0), "r"(a1), "r"(a2), "r"(a3), "r"(b0), "r"(b1));
}
__device__ __forceinline__ float rcp(float x) { float r; asm("rcp.approx.ftz.f32 %0, %1;" : "=f"(r) : "f"(x)); return r; }
__device__ __forceinline__ float ex2(float x) { float r; asm("ex2.approx.ftz.f32 %0, %1;" : "=f"(r) : "f"(x)); return r; }
__device__ __forceinline__ float tanh_(float x) { float t; asm("tanh.approx.f32 %0, %1;" : "=f"(t) : "f"(x)); return t; }
__device__ __forceinline__ float silu_(float x) { return __fdividef(x, 1.f + __expf(-x)); }
__device__ __forceinline__ void st_pkt(void* p, uint32_t a, uint32_t b) {
    asm volatile("{\n.reg .b64 t;\nmov.b64 t, {%1, %2};\nst.relaxed.gpu.global.b64 [%0], t;\n}" :: "l"(p), "r"(a), "r"(b) : "memory");
}
__device__ __forceinline__ uint4 ld_pkt2(const void* p) {
    uint4 v; asm volatile("{\n.reg .b64 t, u;\nld.relaxed.gpu.global.v2.b64 {t, u}, [%4];\nmov.b64 {%0, %1}, t;\nmov.b64 {%2, %3}, u;\n}"
        : "=r"(v.x), "=r"(v.y), "=r"(v.z), "=r"(v.w) : "l"(p) : "memory"); return v;
}
__device__ __forceinline__ void st_pkt16(void* p, uint32_t a, uint32_t b, uint32_t c, uint32_t d) {
    asm volatile("{\n.reg .b64 t, u;\n.reg .b128 w;\nmov.b64 t, {%1, %2};\nmov.b64 u, {%3, %4};\nmov.b128 w, {t, u};\nst.relaxed.gpu.global.b128 [%0], w;\n}"
        :: "l"(p), "r"(a), "r"(b), "r"(c), "r"(d) : "memory");
}
__device__ __forceinline__ uint4 ld_pkt16(const void* p) {
    uint4 v; asm volatile("{\n.reg .b64 t, u;\n.reg .b128 w;\nld.relaxed.gpu.global.b128 w, [%4];\nmov.b128 {t, u}, w;\nmov.b64 {%0, %1}, t;\nmov.b64 {%2, %3}, u;\n}"
        : "=r"(v.x), "=r"(v.y), "=r"(v.z), "=r"(v.w) : "l"(p) : "memory"); return v;
}
#define SPIN_GUARD(n) do { if (++(n) > (1u << 22)) asm volatile("trap;"); } while (0)
__device__ __forceinline__ uint4 lds128(uint32_t a) { uint4 v; asm volatile("ld.shared.v4.u32 {%0, %1, %2, %3}, [%4];" : "=r"(v.x), "=r"(v.y), "=r"(v.z), "=r"(v.w) : "r"(a) : "memory"); return v; }
__device__ __forceinline__ void sts128(uint32_t a, uint32_t x, uint32_t y, uint32_t z, uint32_t w) { asm volatile("st.shared.v4.u32 [%0], {%1, %2, %3, %4};" :: "r"(a), "r"(x), "r"(y), "r"(z), "r"(w) : "memory"); }
__device__ __forceinline__ uint32_t lds32(uint32_t a) { uint32_t v; asm volatile("ld.shared.u32 %0, [%1];" : "=r"(v) : "r"(a) : "memory"); return v; }
__device__ __forceinline__ void sts32(uint32_t a, uint32_t v) { asm volatile("st.shared.u32 [%0], %1;" :: "r"(a), "r"(v) : "memory"); }
__device__ __forceinline__ bool elect_one() {
    uint32_t p; asm volatile("{\n.reg .pred q;\nelect.sync _|q, 0xffffffff;\nselp.u32 %0, 1, 0, q;\n}" : "=r"(p)); return p;
}
__device__ __forceinline__ void pause(uint32_t cycles) {
    uint32_t t0, t; asm volatile("mov.u32 %0, %%clock;" : "=r"(t0));
    do { __nanosleep(64); asm volatile("mov.u32 %0, %%clock;" : "=r"(t)); } while (t - t0 < cycles);
}
__device__ __forceinline__ void cluster_arrive() { asm volatile("barrier.cluster.arrive.relaxed.aligned;" ::: "memory"); }
__device__ __forceinline__ void cluster_wait() { asm volatile("barrier.cluster.wait.aligned;" ::: "memory"); }

__device__ __forceinline__ void wgmma_n128_z(float (&d)[64], uint64_t da, uint64_t db) {
    asm volatile("{\n.reg .pred p;\nsetp.ne.b32 p, 0, 0;\n"
        "wgmma.mma_async.sync.aligned.m64n128k16.f32.bf16.bf16 {"
        "%0, %1, %2, %3, %4, %5, %6, %7, %8, %9, %10, %11, %12, %13, %14, %15, "
        "%16, %17, %18, %19, %20, %21, %22, %23, %24, %25, %26, %27, %28, %29, %30, %31, "
        "%32, %33, %34, %35, %36, %37, %38, %39, %40, %41, %42, %43, %44, %45, %46, %47, "
        "%48, %49, %50, %51, %52, %53, %54, %55, %56, %57, %58, %59, %60, %61, %62, %63"
        "}, %64, %65, p, 1, 1, 0, 1;\n}\n"
        : "=f"(d[0]), "=f"(d[1]), "=f"(d[2]), "=f"(d[3]), "=f"(d[4]), "=f"(d[5]), "=f"(d[6]), "=f"(d[7]),
          "=f"(d[8]), "=f"(d[9]), "=f"(d[10]), "=f"(d[11]), "=f"(d[12]), "=f"(d[13]), "=f"(d[14]), "=f"(d[15]),
          "=f"(d[16]), "=f"(d[17]), "=f"(d[18]), "=f"(d[19]), "=f"(d[20]), "=f"(d[21]), "=f"(d[22]), "=f"(d[23]),
          "=f"(d[24]), "=f"(d[25]), "=f"(d[26]), "=f"(d[27]), "=f"(d[28]), "=f"(d[29]), "=f"(d[30]), "=f"(d[31]),
          "=f"(d[32]), "=f"(d[33]), "=f"(d[34]), "=f"(d[35]), "=f"(d[36]), "=f"(d[37]), "=f"(d[38]), "=f"(d[39]),
          "=f"(d[40]), "=f"(d[41]), "=f"(d[42]), "=f"(d[43]), "=f"(d[44]), "=f"(d[45]), "=f"(d[46]), "=f"(d[47]),
          "=f"(d[48]), "=f"(d[49]), "=f"(d[50]), "=f"(d[51]), "=f"(d[52]), "=f"(d[53]), "=f"(d[54]), "=f"(d[55]),
          "=f"(d[56]), "=f"(d[57]), "=f"(d[58]), "=f"(d[59]), "=f"(d[60]), "=f"(d[61]), "=f"(d[62]), "=f"(d[63])
        : "l"(da), "l"(db));
}
__device__ __forceinline__ void wgmma_n128(float (&d)[64], uint64_t da, uint64_t db) {
    asm volatile("{\n.reg .pred p;\nsetp.eq.b32 p, 0, 0;\n"
        "wgmma.mma_async.sync.aligned.m64n128k16.f32.bf16.bf16 {"
        "%0, %1, %2, %3, %4, %5, %6, %7, %8, %9, %10, %11, %12, %13, %14, %15, "
        "%16, %17, %18, %19, %20, %21, %22, %23, %24, %25, %26, %27, %28, %29, %30, %31, "
        "%32, %33, %34, %35, %36, %37, %38, %39, %40, %41, %42, %43, %44, %45, %46, %47, "
        "%48, %49, %50, %51, %52, %53, %54, %55, %56, %57, %58, %59, %60, %61, %62, %63"
        "}, %64, %65, p, 1, 1, 0, 1;\n}\n"
        : "+f"(d[0]), "+f"(d[1]), "+f"(d[2]), "+f"(d[3]), "+f"(d[4]), "+f"(d[5]), "+f"(d[6]), "+f"(d[7]),
          "+f"(d[8]), "+f"(d[9]), "+f"(d[10]), "+f"(d[11]), "+f"(d[12]), "+f"(d[13]), "+f"(d[14]), "+f"(d[15]),
          "+f"(d[16]), "+f"(d[17]), "+f"(d[18]), "+f"(d[19]), "+f"(d[20]), "+f"(d[21]), "+f"(d[22]), "+f"(d[23]),
          "+f"(d[24]), "+f"(d[25]), "+f"(d[26]), "+f"(d[27]), "+f"(d[28]), "+f"(d[29]), "+f"(d[30]), "+f"(d[31]),
          "+f"(d[32]), "+f"(d[33]), "+f"(d[34]), "+f"(d[35]), "+f"(d[36]), "+f"(d[37]), "+f"(d[38]), "+f"(d[39]),
          "+f"(d[40]), "+f"(d[41]), "+f"(d[42]), "+f"(d[43]), "+f"(d[44]), "+f"(d[45]), "+f"(d[46]), "+f"(d[47]),
          "+f"(d[48]), "+f"(d[49]), "+f"(d[50]), "+f"(d[51]), "+f"(d[52]), "+f"(d[53]), "+f"(d[54]), "+f"(d[55]),
          "+f"(d[56]), "+f"(d[57]), "+f"(d[58]), "+f"(d[59]), "+f"(d[60]), "+f"(d[61]), "+f"(d[62]), "+f"(d[63])
        : "l"(da), "l"(db));
}
__device__ __forceinline__ void wgmma_n176_z(float (&d)[88], uint64_t da, uint64_t db) {
    asm volatile("{\n.reg .pred p;\nsetp.ne.b32 p, 0, 0;\n"
        "wgmma.mma_async.sync.aligned.m64n176k16.f32.bf16.bf16 {"
        "%0, %1, %2, %3, %4, %5, %6, %7, %8, %9, %10, %11, %12, %13, %14, %15, "
        "%16, %17, %18, %19, %20, %21, %22, %23, %24, %25, %26, %27, %28, %29, %30, %31, "
        "%32, %33, %34, %35, %36, %37, %38, %39, %40, %41, %42, %43, %44, %45, %46, %47, "
        "%48, %49, %50, %51, %52, %53, %54, %55, %56, %57, %58, %59, %60, %61, %62, %63, "
        "%64, %65, %66, %67, %68, %69, %70, %71, %72, %73, %74, %75, %76, %77, %78, %79, "
        "%80, %81, %82, %83, %84, %85, %86, %87"
        "}, %88, %89, p, 1, 1, 0, 1;\n}\n"
        : "=f"(d[0]), "=f"(d[1]), "=f"(d[2]), "=f"(d[3]), "=f"(d[4]), "=f"(d[5]), "=f"(d[6]), "=f"(d[7]),
          "=f"(d[8]), "=f"(d[9]), "=f"(d[10]), "=f"(d[11]), "=f"(d[12]), "=f"(d[13]), "=f"(d[14]), "=f"(d[15]),
          "=f"(d[16]), "=f"(d[17]), "=f"(d[18]), "=f"(d[19]), "=f"(d[20]), "=f"(d[21]), "=f"(d[22]), "=f"(d[23]),
          "=f"(d[24]), "=f"(d[25]), "=f"(d[26]), "=f"(d[27]), "=f"(d[28]), "=f"(d[29]), "=f"(d[30]), "=f"(d[31]),
          "=f"(d[32]), "=f"(d[33]), "=f"(d[34]), "=f"(d[35]), "=f"(d[36]), "=f"(d[37]), "=f"(d[38]), "=f"(d[39]),
          "=f"(d[40]), "=f"(d[41]), "=f"(d[42]), "=f"(d[43]), "=f"(d[44]), "=f"(d[45]), "=f"(d[46]), "=f"(d[47]),
          "=f"(d[48]), "=f"(d[49]), "=f"(d[50]), "=f"(d[51]), "=f"(d[52]), "=f"(d[53]), "=f"(d[54]), "=f"(d[55]),
          "=f"(d[56]), "=f"(d[57]), "=f"(d[58]), "=f"(d[59]), "=f"(d[60]), "=f"(d[61]), "=f"(d[62]), "=f"(d[63]),
          "=f"(d[64]), "=f"(d[65]), "=f"(d[66]), "=f"(d[67]), "=f"(d[68]), "=f"(d[69]), "=f"(d[70]), "=f"(d[71]),
          "=f"(d[72]), "=f"(d[73]), "=f"(d[74]), "=f"(d[75]), "=f"(d[76]), "=f"(d[77]), "=f"(d[78]), "=f"(d[79]),
          "=f"(d[80]), "=f"(d[81]), "=f"(d[82]), "=f"(d[83]), "=f"(d[84]), "=f"(d[85]), "=f"(d[86]), "=f"(d[87])
        : "l"(da), "l"(db));
}
__device__ __forceinline__ void wgmma_n176(float (&d)[88], uint64_t da, uint64_t db) {
    asm volatile("{\n.reg .pred p;\nsetp.eq.b32 p, 0, 0;\n"
        "wgmma.mma_async.sync.aligned.m64n176k16.f32.bf16.bf16 {"
        "%0, %1, %2, %3, %4, %5, %6, %7, %8, %9, %10, %11, %12, %13, %14, %15, "
        "%16, %17, %18, %19, %20, %21, %22, %23, %24, %25, %26, %27, %28, %29, %30, %31, "
        "%32, %33, %34, %35, %36, %37, %38, %39, %40, %41, %42, %43, %44, %45, %46, %47, "
        "%48, %49, %50, %51, %52, %53, %54, %55, %56, %57, %58, %59, %60, %61, %62, %63, "
        "%64, %65, %66, %67, %68, %69, %70, %71, %72, %73, %74, %75, %76, %77, %78, %79, "
        "%80, %81, %82, %83, %84, %85, %86, %87"
        "}, %88, %89, p, 1, 1, 0, 1;\n}\n"
        : "+f"(d[0]), "+f"(d[1]), "+f"(d[2]), "+f"(d[3]), "+f"(d[4]), "+f"(d[5]), "+f"(d[6]), "+f"(d[7]),
          "+f"(d[8]), "+f"(d[9]), "+f"(d[10]), "+f"(d[11]), "+f"(d[12]), "+f"(d[13]), "+f"(d[14]), "+f"(d[15]),
          "+f"(d[16]), "+f"(d[17]), "+f"(d[18]), "+f"(d[19]), "+f"(d[20]), "+f"(d[21]), "+f"(d[22]), "+f"(d[23]),
          "+f"(d[24]), "+f"(d[25]), "+f"(d[26]), "+f"(d[27]), "+f"(d[28]), "+f"(d[29]), "+f"(d[30]), "+f"(d[31]),
          "+f"(d[32]), "+f"(d[33]), "+f"(d[34]), "+f"(d[35]), "+f"(d[36]), "+f"(d[37]), "+f"(d[38]), "+f"(d[39]),
          "+f"(d[40]), "+f"(d[41]), "+f"(d[42]), "+f"(d[43]), "+f"(d[44]), "+f"(d[45]), "+f"(d[46]), "+f"(d[47]),
          "+f"(d[48]), "+f"(d[49]), "+f"(d[50]), "+f"(d[51]), "+f"(d[52]), "+f"(d[53]), "+f"(d[54]), "+f"(d[55]),
          "+f"(d[56]), "+f"(d[57]), "+f"(d[58]), "+f"(d[59]), "+f"(d[60]), "+f"(d[61]), "+f"(d[62]), "+f"(d[63]),
          "+f"(d[64]), "+f"(d[65]), "+f"(d[66]), "+f"(d[67]), "+f"(d[68]), "+f"(d[69]), "+f"(d[70]), "+f"(d[71]),
          "+f"(d[72]), "+f"(d[73]), "+f"(d[74]), "+f"(d[75]), "+f"(d[76]), "+f"(d[77]), "+f"(d[78]), "+f"(d[79]),
          "+f"(d[80]), "+f"(d[81]), "+f"(d[82]), "+f"(d[83]), "+f"(d[84]), "+f"(d[85]), "+f"(d[86]), "+f"(d[87])
        : "l"(da), "l"(db));
}
__device__ __forceinline__ void wgmma_n256_z(float (&d)[128], uint64_t da, uint64_t db) {
    asm volatile("{\n.reg .pred p;\nsetp.ne.b32 p, 0, 0;\n"
        "wgmma.mma_async.sync.aligned.m64n256k16.f32.bf16.bf16 {"
        "%0, %1, %2, %3, %4, %5, %6, %7, %8, %9, %10, %11, %12, %13, %14, %15, "
        "%16, %17, %18, %19, %20, %21, %22, %23, %24, %25, %26, %27, %28, %29, %30, %31, "
        "%32, %33, %34, %35, %36, %37, %38, %39, %40, %41, %42, %43, %44, %45, %46, %47, "
        "%48, %49, %50, %51, %52, %53, %54, %55, %56, %57, %58, %59, %60, %61, %62, %63, "
        "%64, %65, %66, %67, %68, %69, %70, %71, %72, %73, %74, %75, %76, %77, %78, %79, "
        "%80, %81, %82, %83, %84, %85, %86, %87, %88, %89, %90, %91, %92, %93, %94, %95, "
        "%96, %97, %98, %99, %100, %101, %102, %103, %104, %105, %106, %107, %108, %109, %110, %111, "
        "%112, %113, %114, %115, %116, %117, %118, %119, %120, %121, %122, %123, %124, %125, %126, %127"
        "}, %128, %129, p, 1, 1, 0, 1;\n}\n"
        : "=f"(d[0]), "=f"(d[1]), "=f"(d[2]), "=f"(d[3]), "=f"(d[4]), "=f"(d[5]), "=f"(d[6]), "=f"(d[7]),
          "=f"(d[8]), "=f"(d[9]), "=f"(d[10]), "=f"(d[11]), "=f"(d[12]), "=f"(d[13]), "=f"(d[14]), "=f"(d[15]),
          "=f"(d[16]), "=f"(d[17]), "=f"(d[18]), "=f"(d[19]), "=f"(d[20]), "=f"(d[21]), "=f"(d[22]), "=f"(d[23]),
          "=f"(d[24]), "=f"(d[25]), "=f"(d[26]), "=f"(d[27]), "=f"(d[28]), "=f"(d[29]), "=f"(d[30]), "=f"(d[31]),
          "=f"(d[32]), "=f"(d[33]), "=f"(d[34]), "=f"(d[35]), "=f"(d[36]), "=f"(d[37]), "=f"(d[38]), "=f"(d[39]),
          "=f"(d[40]), "=f"(d[41]), "=f"(d[42]), "=f"(d[43]), "=f"(d[44]), "=f"(d[45]), "=f"(d[46]), "=f"(d[47]),
          "=f"(d[48]), "=f"(d[49]), "=f"(d[50]), "=f"(d[51]), "=f"(d[52]), "=f"(d[53]), "=f"(d[54]), "=f"(d[55]),
          "=f"(d[56]), "=f"(d[57]), "=f"(d[58]), "=f"(d[59]), "=f"(d[60]), "=f"(d[61]), "=f"(d[62]), "=f"(d[63]),
          "=f"(d[64]), "=f"(d[65]), "=f"(d[66]), "=f"(d[67]), "=f"(d[68]), "=f"(d[69]), "=f"(d[70]), "=f"(d[71]),
          "=f"(d[72]), "=f"(d[73]), "=f"(d[74]), "=f"(d[75]), "=f"(d[76]), "=f"(d[77]), "=f"(d[78]), "=f"(d[79]),
          "=f"(d[80]), "=f"(d[81]), "=f"(d[82]), "=f"(d[83]), "=f"(d[84]), "=f"(d[85]), "=f"(d[86]), "=f"(d[87]),
          "=f"(d[88]), "=f"(d[89]), "=f"(d[90]), "=f"(d[91]), "=f"(d[92]), "=f"(d[93]), "=f"(d[94]), "=f"(d[95]),
          "=f"(d[96]), "=f"(d[97]), "=f"(d[98]), "=f"(d[99]), "=f"(d[100]), "=f"(d[101]), "=f"(d[102]), "=f"(d[103]),
          "=f"(d[104]), "=f"(d[105]), "=f"(d[106]), "=f"(d[107]), "=f"(d[108]), "=f"(d[109]), "=f"(d[110]), "=f"(d[111]),
          "=f"(d[112]), "=f"(d[113]), "=f"(d[114]), "=f"(d[115]), "=f"(d[116]), "=f"(d[117]), "=f"(d[118]), "=f"(d[119]),
          "=f"(d[120]), "=f"(d[121]), "=f"(d[122]), "=f"(d[123]), "=f"(d[124]), "=f"(d[125]), "=f"(d[126]), "=f"(d[127])
        : "l"(da), "l"(db));
}
__device__ __forceinline__ void wgmma_n256(float (&d)[128], uint64_t da, uint64_t db) {
    asm volatile("{\n.reg .pred p;\nsetp.eq.b32 p, 0, 0;\n"
        "wgmma.mma_async.sync.aligned.m64n256k16.f32.bf16.bf16 {"
        "%0, %1, %2, %3, %4, %5, %6, %7, %8, %9, %10, %11, %12, %13, %14, %15, "
        "%16, %17, %18, %19, %20, %21, %22, %23, %24, %25, %26, %27, %28, %29, %30, %31, "
        "%32, %33, %34, %35, %36, %37, %38, %39, %40, %41, %42, %43, %44, %45, %46, %47, "
        "%48, %49, %50, %51, %52, %53, %54, %55, %56, %57, %58, %59, %60, %61, %62, %63, "
        "%64, %65, %66, %67, %68, %69, %70, %71, %72, %73, %74, %75, %76, %77, %78, %79, "
        "%80, %81, %82, %83, %84, %85, %86, %87, %88, %89, %90, %91, %92, %93, %94, %95, "
        "%96, %97, %98, %99, %100, %101, %102, %103, %104, %105, %106, %107, %108, %109, %110, %111, "
        "%112, %113, %114, %115, %116, %117, %118, %119, %120, %121, %122, %123, %124, %125, %126, %127"
        "}, %128, %129, p, 1, 1, 0, 1;\n}\n"
        : "+f"(d[0]), "+f"(d[1]), "+f"(d[2]), "+f"(d[3]), "+f"(d[4]), "+f"(d[5]), "+f"(d[6]), "+f"(d[7]),
          "+f"(d[8]), "+f"(d[9]), "+f"(d[10]), "+f"(d[11]), "+f"(d[12]), "+f"(d[13]), "+f"(d[14]), "+f"(d[15]),
          "+f"(d[16]), "+f"(d[17]), "+f"(d[18]), "+f"(d[19]), "+f"(d[20]), "+f"(d[21]), "+f"(d[22]), "+f"(d[23]),
          "+f"(d[24]), "+f"(d[25]), "+f"(d[26]), "+f"(d[27]), "+f"(d[28]), "+f"(d[29]), "+f"(d[30]), "+f"(d[31]),
          "+f"(d[32]), "+f"(d[33]), "+f"(d[34]), "+f"(d[35]), "+f"(d[36]), "+f"(d[37]), "+f"(d[38]), "+f"(d[39]),
          "+f"(d[40]), "+f"(d[41]), "+f"(d[42]), "+f"(d[43]), "+f"(d[44]), "+f"(d[45]), "+f"(d[46]), "+f"(d[47]),
          "+f"(d[48]), "+f"(d[49]), "+f"(d[50]), "+f"(d[51]), "+f"(d[52]), "+f"(d[53]), "+f"(d[54]), "+f"(d[55]),
          "+f"(d[56]), "+f"(d[57]), "+f"(d[58]), "+f"(d[59]), "+f"(d[60]), "+f"(d[61]), "+f"(d[62]), "+f"(d[63]),
          "+f"(d[64]), "+f"(d[65]), "+f"(d[66]), "+f"(d[67]), "+f"(d[68]), "+f"(d[69]), "+f"(d[70]), "+f"(d[71]),
          "+f"(d[72]), "+f"(d[73]), "+f"(d[74]), "+f"(d[75]), "+f"(d[76]), "+f"(d[77]), "+f"(d[78]), "+f"(d[79]),
          "+f"(d[80]), "+f"(d[81]), "+f"(d[82]), "+f"(d[83]), "+f"(d[84]), "+f"(d[85]), "+f"(d[86]), "+f"(d[87]),
          "+f"(d[88]), "+f"(d[89]), "+f"(d[90]), "+f"(d[91]), "+f"(d[92]), "+f"(d[93]), "+f"(d[94]), "+f"(d[95]),
          "+f"(d[96]), "+f"(d[97]), "+f"(d[98]), "+f"(d[99]), "+f"(d[100]), "+f"(d[101]), "+f"(d[102]), "+f"(d[103]),
          "+f"(d[104]), "+f"(d[105]), "+f"(d[106]), "+f"(d[107]), "+f"(d[108]), "+f"(d[109]), "+f"(d[110]), "+f"(d[111]),
          "+f"(d[112]), "+f"(d[113]), "+f"(d[114]), "+f"(d[115]), "+f"(d[116]), "+f"(d[117]), "+f"(d[118]), "+f"(d[119]),
          "+f"(d[120]), "+f"(d[121]), "+f"(d[122]), "+f"(d[123]), "+f"(d[124]), "+f"(d[125]), "+f"(d[126]), "+f"(d[127])
        : "l"(da), "l"(db));
}

struct Idx {
    uint32_t lane, warp, w4, q4, g8, prow, pan;
    __device__ __forceinline__ Idx() {
        uint32_t t; asm volatile("mov.u32 %0, %%tid.x;" : "=r"(t));
        lane = t & 31; warp = t >> 5; w4 = warp & 3; q4 = lane & 3; g8 = lane >> 2;
        prow = w4 * 16 + ((lane >> 3) & 1) * 8 + (lane & 7);
        pan = prow * 128 + (((lane >> 4) ^ (lane & 7)) << 4);
    }
};
#define IDX() const Idx ix; const uint32_t lane = ix.lane, warp = ix.warp, w4 = ix.w4, q4 = ix.q4, g8 = ix.g8, prow = ix.prow, pan_addr = ix.pan; \
    (void)lane; (void)warp; (void)w4; (void)q4; (void)g8; (void)prow; (void)pan_addr;

__device__ __forceinline__ int kof(int t, int sh, int j) {
    const int p = t >> (sh - 1), pn = p < 2 ? p : p >= 9, q = p - 2 - 7 * pn;
    return ((p < 2 ? j : q + (q >= j)) << 7) + (pn << 6) + ((t & (sh - 1)) << 5);
}
constexpr int HC0 = 8 * 48, HC3 = HC0 + 3072;
__device__ __forceinline__ int hcol(int p, int j) { return HC0 + p * 1024 + j * 128; }
struct Ring {
    uint32_t slot, par;
    __device__ __forceinline__ void next() { if (++slot == NSLOT) { slot = 0; par ^= 1; } }
    __device__ __forceinline__ void skip(uint32_t n) { slot += n; if (slot >= NSLOT) { slot -= NSLOT; par ^= 1; } }
};
__device__ __forceinline__ uint32_t BAR_FULL(uint32_t sb, uint32_t s) { return sb + OFF_BAR + 8 * s; }
constexpr uint32_t AF_REL = 48;
__device__ __forceinline__ uint32_t BAR_EMPTY(uint32_t sb, uint32_t s) { return sb + OFF_BAR + 96 + 8 * s; }
__device__ __forceinline__ uint32_t BAR_SFULL(uint32_t sb, uint32_t i) { return sb + OFF_BAR + 152 + 8 * i; }
__device__ __forceinline__ uint32_t BAR_SREADY(uint32_t sb, uint32_t i) { return sb + OFF_BAR + 184 + 8 * i; }
__device__ __forceinline__ uint32_t BAR_ONE(uint32_t sb, uint32_t i) { return sb + OFF_BAR + 216 + 8 * i; }
enum { EV_WIN, EV_WIN1, EV_WIN2, EV_WIN3, EV_P0, EV_GA, EV_GB, EV_LN2, EV_LAG0, EV_LAG1, EV_LAG2, EV_LAG3, EV_LAG4, EV_LAG5, EV_OWN, EV_OWN1, EV_KV, EV_GO, EV_PAR, EV_AGO, EV_AGO1, EV_AGO2, EV_FGO, EV_FGO1, EV_FGO2, EV_H0, EV_H1, EV_H2, EV_H3, EV_COUNT };
constexpr int NB_TAIL = 4;

struct Rel {
    uint32_t base; bool sig;
    __device__ __forceinline__ Rel(uint32_t sb, uint32_t tw) {
        uint32_t a; asm("mapa.shared::cluster.u32 %0, %1, %2;" : "=r"(a) : "r"(BAR_EMPTY(sb, 0)), "r"((tw >> 5) & 1));
        base = __shfl_sync(0xffffffffu, a, 0); sig = (tw & ~32u) == 0;
    }
    __device__ __forceinline__ void operator()(uint32_t slot) const {
        if (sig) asm volatile("mbarrier.arrive.shared::cluster.b64 _, [%0];" :: "r"(base + 8 * slot) : "memory");
    }
};
struct LnRow { float rs0, nm0, rs1, nm1; };
struct Pipe {
    Rel rel; uint32_t p1, p2;
    __device__ __forceinline__ Pipe(uint32_t sb, uint32_t tw, uint32_t first) : rel(sb, tw), p1(first), p2(NSLOT) {}
    template <bool TWO> __device__ __forceinline__ void acquire(uint32_t sb, uint32_t af, const Ring& r) {
        const uint32_t b0 = BAR_FULL(sb, r.slot), b1 = b0 + af;
        const bool ready = TWO ? mbar_test2(b0, b1, r.par) : mbar_test(b0, r.par);
        wg_wait<1>();
        rel(p2);
        if (!ready) { if (TWO) mbar_wait2(b0, b1, r.par); else mbar_wait(b0, r.par); }
    }
    __device__ __forceinline__ void issued(uint32_t slot) { p2 = p1; p1 = slot; }
    __device__ __forceinline__ void drain1() { wg_wait<1>(); rel(p2); p2 = NSLOT; }
    __device__ __forceinline__ void drain0() { wg_wait<0>(); rel(p1); p1 = NSLOT; }
    template <bool TWO, class Step> __device__ __forceinline__ void hold(int LG, uint32_t sb, uint32_t af, Ring& r, uint32_t lag_bar, Step step) {
        Ring q = r;
#pragma unroll 1
        for (int i = 0; i < LG; ++i) { if (TWO) mbar_wait2(BAR_FULL(sb, q.slot), BAR_FULL(sb, q.slot) + af, q.par); else mbar_wait(BAR_FULL(sb, q.slot), q.par); q.next(); }
        mbar_wait(lag_bar, 0);
#pragma unroll 1
        do {
            step(r.slot);
            wg_wait<2>(); rel(p2); p2 = p1; p1 = r.slot;
            if (++r.slot == NSLOT) r.slot = 0;
        } while (r.slot != q.slot);
        r.par = q.par;
    }
};
template <bool TWO, bool FIRST, int NA, int NB>
__device__ __forceinline__ void step32(float (&aa)[NA], float (&ab)[NB], uint32_t sb, uint32_t wg, uint32_t slot, int own) {
    const uint32_t st = d16(sb) + slot * (SLOT >> 4);
    const uint32_t alo = own >= 0 ? d16(sb) + OFF_STG / 16 + wg * 1024 + (own >> 1) * 512 + (own & 1) * 4 : st + wg * 256;
    const uint32_t ahi = own >= 0 ? (1024 >> 4) | (1u << 30) : (512 >> 4) | (2u << 30);
    wg_fence();
#pragma unroll
    for (int k = 0; k < 2; ++k) {
        const uint64_t da = ((uint64_t)ahi << 32) | (alo + k * 2 + 0x10000);
        if constexpr (NA == 88) {
            const uint64_t d0 = mk_desc(st, 8192 + k * 2048, 8192, 1024, 1), d1 = mk_desc(st, 12288 + k * 2048, 8192, 1024, 1);
            if (FIRST && k == 0) { wgmma_n176_z(aa, da, d0); wgmma_n176_z(ab, da, d1); }
            else { wgmma_n176(aa, da, d0); wgmma_n176(ab, da, d1); }
        } else {
            const uint64_t d0 = mk_desc(st, 8192 + k * 2048, 4096, 1024, 1), d1 = mk_desc(st, 24576 + k * 2048, 4096, 1024, 1);
            if (FIRST && k == 0) { wgmma_n256_z(aa, da, d0); if constexpr (TWO) wgmma_n128_z(ab, da, d1); }
            else { wgmma_n256(aa, da, d0); if constexpr (TWO) wgmma_n128(ab, da, d1); }
        }
    }
    wg_commit();
}
template <bool TWO, int LG, int NA, int NB, class Tail>
__device__ __forceinline__ void mainloop32(float (&aa)[NA], float (&ab)[NB], uint32_t sb, uint32_t wg, uint32_t tw, Ring& r, uint32_t lag_ev, int g0, Tail tail) {
    mbar_wait(BAR_FULL(sb, r.slot), r.par);
    step32<TWO, true>(aa, ab, sb, wg, r.slot, TWO ? 0 : -1);
    TS(g0, 0);
    Pipe pp(sb, tw, r.slot);
    r.next();
    const int end = wg ? 32 : 32 - LG;
#pragma unroll 1
    for (int it = 1; it < end; ++it) {
        pp.acquire<TWO>(sb, wg ? 0 : AF_REL, r);
        step32<TWO, false>(aa, ab, sb, wg, r.slot, TWO && it < 4 ? it : -1);
        pp.issued(r.slot);
        TS(g0 + it, 0);
        r.next();
    }
    if (wg == 0) { pp.drain1(); pp.drain0(); pp.hold<TWO>(LG, sb, AF_REL, r, BAR_ONE(sb, lag_ev), [&](uint32_t slot) { step32<TWO, false>(aa, ab, sb, 0, slot, -1); }); }
    pp.drain1();
    if (wg == 1 && tw == 0) mbar_arrive(BAR_ONE(sb, lag_ev));
    tail();
    pp.drain0();
    TS(g0 + 31, 1);
}
template <bool FIRST>
__device__ __forceinline__ void step64(float (&acc)[64], uint32_t sb, uint32_t wg, uint32_t slot, int own) {
    const uint32_t sbb = d16(sb) + slot * (SLOT >> 4), sa = own >= 0 ? d16(sb) + OFF_STG / 16 + wg * 1024 + own * 512 : sbb + wg * 512;
    wg_fence();
#pragma unroll
    for (int k = 0; k < 4; ++k) {
        const uint64_t da = mk_desc(sa, k * 32, 16, 1024, 1), db = mk_desc(sbb, 16384 + k * 2048, 8192, 1024, 1);
        if (FIRST && k == 0) wgmma_n128_z(acc, da, db); else wgmma_n128(acc, da, db);
    }
    wg_commit();
}
template <class Mid>
__device__ __forceinline__ void mainloop64(float (&acc)[64], bool wo, uint32_t sb, uint32_t wg, uint32_t tw, Ring& r, Mid mid) {
    const int g0 = wo ? 32 : 144, nst = wo ? 16 : 56, lg = wo ? LAGW : LAGD; (void)g0;
    const uint32_t lag_bar = BAR_ONE(sb, wo ? EV_LAG4 : EV_LAG5), af = wo && !wg ? AF_REL : 0;
    mbar_wait(BAR_FULL(sb, r.slot), r.par);
    if (!wo) CS(28);
    step64<true>(acc, sb, wg, r.slot, wo ? 0 : -1);
    if (!wo) CS(29);
    TS(g0, 0);
    Pipe pp(sb, tw, r.slot);
    r.next();
    int it = 1;
    auto run = [&](int end, int own) {
#pragma unroll 1
        do {
            pp.acquire<true>(sb, af, r);
            step64<false>(acc, sb, wg, r.slot, own);
            pp.issued(r.slot);
            TS(g0 + it, 0);
            r.next();
            if (own > 0) {
                own = -1;
                pp.drain1(); pp.drain0();
                TS(g0 + 1, 1);
                if (tw == 0) mbar_arrive(BAR_ONE(sb, EV_OWN + wg));
            }
        } while (++it < end);
    };
    run(wg ? (wo ? MIDW : MIDD) : nst - lg, wo ? 1 : -1);
    mid();
    if (wg) run(nst, -1);
    else { pp.drain1(); pp.drain0(); pp.hold<true>(lg, sb, af, r, lag_bar, [&](uint32_t slot) { step64<false>(acc, sb, 0, slot, -1); }); }
    pp.drain1();
    if (wg == 1 && tw == 0) mbar_arrive(lag_bar);
    pp.drain0();
    TS(g0 + nst - 1, 1);
}

struct RowAcc {
    float sm[4] = {0.f, 0.f, 0.f, 0.f}, sq[4] = {0.f, 0.f, 0.f, 0.f};
    __device__ __forceinline__ void add(int e, float x) { sm[e & 3] += x; sq[e & 3] = fmaf(x, x, sq[e & 3]); }
    __device__ __forceinline__ void publish(uint4* dst, uint32_t q4, uint32_t ep) const {
        const float s0 = sm[0] + sm[1], s1 = sm[2] + sm[3], q0 = sq[0] + sq[1], q1 = sq[2] + sq[3];
        const bool od = q4 & 1;
        float sv = (od ? s1 : s0) + __shfl_xor_sync(0xffffffffu, od ? s0 : s1, 1), qv = (od ? q1 : q0) + __shfl_xor_sync(0xffffffffu, od ? q0 : q1, 1);
        sv += __shfl_xor_sync(0xffffffffu, sv, 2); qv += __shfl_xor_sync(0xffffffffu, qv, 2);
        if (q4 < 2) st_pkt16(dst + q4 * 8, 0, __float_as_uint(sv), __float_as_uint(qv), ep);
    }
};
__device__ __forceinline__ LnRow merge_stats(const uint4* src, uint32_t q4, uint32_t ep, uint32_t sb) {
    uint4 t[4];
    uint32_t n = 0;
    while (true) {
#pragma unroll
        for (int i = 0; i < 4; ++i) t[i] = ld_pkt16(src + (q4 * 2 + (i >> 1)) * 512 + (i & 1) * 8);
        const bool ok_ = __all_sync(0xffffffffu, t[0].w == ep && t[1].w == ep && t[2].w == ep && t[3].w == ep);
        if (n < 4) CS(14 + n);
        if (ok_) break;
        SPIN_GUARD(n);
    }
    float v[4];
#pragma unroll
    for (int h = 0; h < 2; ++h) { v[h] = __uint_as_float(t[h].y) + __uint_as_float(t[2 + h].y); v[2 + h] = __uint_as_float(t[h].z) + __uint_as_float(t[2 + h].z); }
#pragma unroll
    for (int o = 1; o < 4; o <<= 1)
#pragma unroll
        for (int i = 0; i < 4; ++i) v[i] += __shfl_xor_sync(0xffffffffu, v[i], o);
    const float m0 = v[0] * (1.f / D_), m1 = v[1] * (1.f / D_);
    const float r0 = rsqrtf(fmaxf(fmaf(-m0, m0, v[2] * (1.f / D_)), 0.f) + 1e-5f), r1 = rsqrtf(fmaxf(fmaf(-m1, m1, v[3] * (1.f / D_)), 0.f) + 1e-5f);
    return LnRow{r0, -m0 * r0, r1, -m1 * r1};
}
struct Stg {
    uint32_t b, par;
    __device__ __forceinline__ uint32_t acquire2(uint32_t sb, uint32_t wg) {
        mbar_wait(BAR_SREADY(sb, wg * 2), par & 1);
        mbar_wait(BAR_SREADY(sb, wg * 2 + 1), (par >> 1) & 1);
        par ^= 3;
        return sb + OFF_STG + wg * 16384;
    }
    __device__ __forceinline__ void publish(uint32_t sb, uint32_t wg, uint32_t lane) {
        fence_async_smem();
        __syncwarp();
        if (lane == 0) mbar_arrive(BAR_SFULL(sb, wg * 2 + b));
        b ^= 1;
    }
};

struct LnPar {
    uint4 p[8];
    __device__ __forceinline__ void load(uint32_t sb, uint32_t q4) {
#pragma unroll
        for (int i = 0; i < 8; ++i) p[i] = lds128(sb + OFF_PAR + i * 64 + q4 * 16);
    }
};
__device__ __forceinline__ void ln_norm(uint32_t (&xn)[32], const float (&x)[64], const LnRow& n) {
#pragma unroll
    for (int e = 0; e < 32; ++e) {
        const float rs = (e & 1) ? n.rs1 : n.rs0, nm = (e & 1) ? n.nm1 : n.nm0;
        xn[e] = pack2(fmaf(x[2 * e], rs, nm), fmaf(x[2 * e + 1], rs, nm));
    }
}
__device__ __forceinline__ void ln_emit(const uint32_t (&xr)[32], const LnPar& lp, uint32_t sb, uint32_t wg, const Idx& ix) {
#pragma unroll
    for (int i = 0; i < 8; ++i)
        stsm4(sb + OFF_STG + wg * 16384 + (i >> 2) * 8192 + (ix.pan ^ ((i & 3) << 5)), hfma2_bf16(xr[4 * i], lp.p[i].z, lp.p[i].x), hfma2_bf16(xr[4 * i + 1], lp.p[i].z, lp.p[i].x),
              hfma2_bf16(xr[4 * i + 2], lp.p[i].w, lp.p[i].y), hfma2_bf16(xr[4 * i + 3], lp.p[i].w, lp.p[i].y));
    fence_async_smem();
    __syncwarp();
    if (ix.lane < 2) mbar_arrive(BAR_SFULL(sb, wg * 2 + ix.lane));
    bar_sync(1 + wg, 128);
}
__device__ __forceinline__ void load_slab(uint32_t (&xr)[32], uint32_t buf) {
    IDX();
#pragma unroll
    for (int i = 0; i < 8; ++i) ldsm4(buf + (i >> 2) * 8192 + (pan_addr ^ ((i & 3) << 5)), xr[4 * i], xr[4 * i + 1], xr[4 * i + 2], xr[4 * i + 3]);
}
__device__ __forceinline__ void unpack_slab(float (&x)[64], const uint32_t (&xr)[32]) {
#pragma unroll
    for (int i = 0; i < 32; ++i) unpack2(xr[i], x[2 * i], x[2 * i + 1]);
}
__device__ __forceinline__ void store_slab(const float (&x)[64], uint32_t buf, uint32_t pitch, uint32_t pan, int i0, int i1) {
#pragma unroll
    for (int i = i0; i < i1; ++i)
        stsm4(buf + (i >> 2) * pitch + (pan ^ ((i & 3) << 5)), pack2(x[8 * i], x[8 * i + 1]), pack2(x[8 * i + 2], x[8 * i + 3]), pack2(x[8 * i + 4], x[8 * i + 5]), pack2(x[8 * i + 6], x[8 * i + 7]));
}
__device__ __forceinline__ void fetch_halo(uint4* src, bool first, uint32_t sb, uint32_t W, uint32_t lane) {
    mbar_wait(BAR_ONE(sb, EV_KV), 0);
    mbar_wait2(BAR_SREADY(sb, 0), BAR_SREADY(sb, 1), 1);
    uint4 hv[8];
    uint32_t n = 0;
    while (true) {
        bool ok = true;
#pragma unroll
        for (int i = 0; i < 8; ++i) { hv[i] = first ? make_uint4(0, 0, 0, 0) : ld_pkt16(src + i * 32); ok = ok && hv[i].x != 0; }
        if (first || __all_sync(0xffffffffu, ok)) break;
        SPIN_GUARD(n);
    }
#pragma unroll
    for (int i = 0; i < 8; ++i) stsm4(sb + OFF_STG + W * 2048 + (i >> 2) * 8192 + (i & 3) * 512 + lane * 16, hv[i].x, hv[i].y, hv[i].z, hv[i].w);
    bar_arrive(NB_TAIL + W, 64);
    if (!first) {
#pragma unroll
        for (int i = 0; i < 8; ++i) src[i * 32] = make_uint4(0, 0, 0, 0);
    }
}

template <int NG, class G, class U, class Buf>
__device__ __forceinline__ void glu(uint32_t sb, uint32_t wg, G g, U u, Buf buf) {
    IDX();
#pragma unroll
    for (int k = 0; k < NG; ++k) {
        float h[8];
#pragma unroll
        for (int e = 0; e < 8; ++e) h[e] = fmaf(tanh_(g(8 * k + e)), u(8 * k + e), u(8 * k + e));
        stsm4(buf(k >> 2) + (pan_addr ^ ((k & 3) << 5)), pack2(h[0], h[1]), pack2(h[2], h[3]), pack2(h[4], h[5]), pack2(h[6], h[7]));
    }
    fence_async_smem();
    __syncwarp();
    if (lane < 2) mbar_arrive(BAR_SFULL(sb, wg * 2 + lane));
}

template <int NP>
__device__ __forceinline__ void passes128(uint32_t sb, uint32_t wg, uint32_t tw, Ring& r, Stg& stg) {
#pragma unroll 1
    for (int p = 0; p < NP; ++p) {
        float b256[128], none[1];
        mainloop32<false, LAGS>(b256, none, sb, wg, tw, r, EV_LAG2 + p, 80 + 32 * (p & 1), [&] { stg.acquire2(sb, wg); });
        if (threadIdx.x == 0) { TL(29 + 2 * p); TC(114 + 2 * p); }
        if (threadIdx.x == 128) TL(53 + 2 * (p & 1));
        CS(24 + 2 * (p & 1));
        glu<8>(sb, wg, [&](int i) { return b256[i + (i & 32)]; }, [&](int i) { return b256[i + (i & 32) + 32]; }, [&](int pn) { return sb + OFF_STG + wg * 16384 + pn * 8192; });
        if (threadIdx.x == 0) { TL(30 + 2 * p); TC(115 + 2 * p); }
        if (threadIdx.x == 128) TL(54 + 2 * (p & 1));
        CS(25 + 2 * (p & 1));
    }
}

__global__ void __launch_bounds__(384, 1)
fused_block_kernel(const __grid_constant__ Ptrs pt, const __grid_constant__ Maps mp) {
    uint32_t* const g_flags = pt.mail->flags;
    uint2* const g_mod = pt.mail->mod;
    uint4* const g_st1 = pt.mail->st1;
    uint32_t* const g_par2 = pt.mail->par2;
    uint4* const g_halo = pt.mail->halo;
    const __nv_bfloat16* __restrict__ cvec = pt.c;
    if (threadIdx.x == 224) { prefetch_map(&mp.wm8); prefetch_map(&mp.x); }
    extern __shared__ __align__(1024) uint8_t smem[];
    const uint32_t sb = smem_u32(smem);
    const uint32_t tid = threadIdx.x, tw = tid & 127, lane = tid & 31;
    const uint32_t warp = __shfl_sync(0xffffffffu, tid >> 5, 0), wg = warp >> 2;
    uint32_t rank; asm("mov.u32 %0, %%cluster_ctarank;" : "=r"(rank));
    rank = __shfl_sync(0xffffffffu, rank, 0);
    uint32_t ep;
    uint32_t smid; asm volatile("mov.u32 %0, %%smid;" : "=r"(smid));
    const int c = __shfl_sync(0xffffffffu, smid >> 1, 0);
    const int c7 = ((c - 32) * 37) >> 8;
    const int grp = c < 32 ? c & 7 : c < 60 ? c - 31 - 7 * c7 : c < 62 ? -1 : 0;
    const int j = c < 32 ? c >> 3 : c < 60 ? 4 + c7 : c < 62 ? (c - 60) * 2 + rank : c - 58;
    const bool aux = grp < 0;
    const int m = grp * 2 + rank;
    uint4* const g_st2 = g_halo + (m > 0 ? (m - 1) * 8 * 512 : 128);

    bool cluster_arrive_early = false;
    if (wg < 2) {
      if (!KDEBUG) cluster_arrive();
      ep = flag_get(g_flags + FL_DONE);
      uint16_t cw[8];
      {
          const __nv_bfloat16* cp = cvec + ((tw >> 5) * 32 + (tw & 3) * 2) * 8 + (lane >> 2);
#pragma unroll
          for (int i = 0; i < 8; ++i) asm volatile("ld.global.nc.u16 %0, [%1];" : "=h"(cw[i]) : "l"(cp + (i >> 1) * 64 + (i & 1) * 8));
      }
      asm volatile("setmaxnreg.inc.sync.aligned.u32 224;");
      if (tid == 0) TL(58);
      if (KDEBUG) cluster_arrive();
      Ring r{0, 0};
      Stg stg{0, 0};
      if (aux) {
        if (wg == 0) {
            const uint4 cv = *(const uint4*)(cvec + tw * 8);
            sts128(sb + OFF_STG + (tw >> 3) * 1024 + (tw & 7) * 16, pack2(silu_(bf_lo(cv.x)), silu_(bf_hi(cv.x))), pack2(silu_(bf_lo(cv.y)), silu_(bf_hi(cv.y))),
                   pack2(silu_(bf_lo(cv.z)), silu_(bf_hi(cv.z))), pack2(silu_(bf_lo(cv.w)), silu_(bf_hi(cv.w))));
            fence_async_smem();
        }
        cluster_wait();
        ep = __shfl_sync(0xffffffffu, ep, 0) / NCTA + 1;
        if (wg == 0) {
            if (tw == 0) {
                uint32_t n = 0;
                while (ld_pkt16(pt.mail->mod1 + 256).z != ep) { SPIN_GUARD(n); __nanosleep(200); }
                if (GODLY) __nanosleep(GODLY);
                mbar_arrive(BAR_ONE(sb, EV_GO));
            }
            bar_sync(1, 128);
#pragma unroll 1
            for (int p = 0; p < 4; ++p) {
                float acc[128];
#pragma unroll
                for (int i = 0; i < 128; ++i) acc[i] = 0.f;
                uint32_t prev = 0;
#pragma unroll 1
                for (int kc = 0; kc < 16; ++kc) {
                    mbar_wait(BAR_FULL(sb, r.slot), r.par);
                    wg_fence();
#pragma unroll
                    for (int k = 0; k < 4; ++k)
                        wgmma_n256(acc, mk_desc(d16(sb) + kc * 64, OFF_STG + k * 32, 16, 0, 1), mk_desc(d16(sb) + r.slot * (SLOT >> 4), k * 2048, 8192, 1024, 1));
                    wg_commit();
                    wg_wait<1>();
                    if (kc > 0 && tw < 4) mbar_arrive(BAR_EMPTY(sb, prev));
                    prev = r.slot;
                    r.next();
                }
                wg_wait<0>();
                if (tw < 4) mbar_arrive(BAR_EMPTY(sb, prev));
                if (tw < 4) {
#pragma unroll
                    for (int jn = 0; jn < 32; ++jn) sts32(sb + OFF_TAB + (jn * 4 + tw) * 4, pack2(acc[jn * 4], acc[jn * 4 + 1]));
                }
                bar_sync(1, 128);
                const int vec = 2 + p, blk = p * 4 + j;
                const uint32_t val = lds32(sb + OFF_TAB + tw * 4);
                if (vec == 2 || vec == 5) st_pkt(g_mod + (8 + blk) * 128 + tw, val, ep);
                else {
                    const float one = vec == 4 ? 1.f : 0.f;
                    g_par2[((blk & 3) * 16 + (tw >> 3)) * 16 + (tw & 3) * 4 + (vec - 3) * 2 + ((tw >> 2) & 1)] =
                        pack2(0.5f * bf_round(one + bf_lo(val)), 0.5f * bf_round(one + bf_hi(val)));
                }
                bar_sync(1, 128);
                if (tw == 0) {
                    if (vec == 3 || vec == 4) asm volatile("red.release.gpu.global.add.u32 [%0], 1;" :: "l"(&g_flags[FL_LN2]) : "memory");
                    TL(1 + p);
                }
            }
            if (lane < 2) mbar_arrive_cta(BAR_ONE(sb, EV_P0), lane);
        }
        r = Ring{64 % NSLOT, (64 / NSLOT) & 1};
        mbar_wait(BAR_ONE(sb, EV_P0), 0);
        passes128<4>(sb, wg, tw, r, stg);
      } else {
        float xs[64];
        uint32_t xp[32];
        {
            IDX();
            if (q4 < 2) st_pkt16(g_st1 + (m * 8 + j) * 512 + wg * 64 + w4 * 16 + g8 + q4 * 8, 0, 0, 0, 0);
            if (warp == 0) st_pkt16(pt.mail->mod1 + g8 * 512 + (m * 8 + j) * 4 + q4, 0, 0, 0, 0);
            sts128(sb + tid * 16, pack2(silu_(bf_lo(cw[0])), silu_(bf_lo(cw[1]))), pack2(silu_(bf_lo(cw[2])), silu_(bf_lo(cw[3]))),
                   pack2(silu_(bf_lo(cw[4])), silu_(bf_lo(cw[5]))), pack2(silu_(bf_lo(cw[6])), silu_(bf_lo(cw[7]))));
            cluster_wait();
            ep = __shfl_sync(0xffffffffu, ep, 0) / NCTA + 1;
            load_slab(xp, stg.acquire2(sb, wg));
            unpack_slab(xs, xp);
            if (tid == 0) TL(24);
            if (tid == 128) TL(27);
        }
#pragma unroll 1
        for (int blk = 0; ; ++blk) {
        {
            IDX();
            uint4* const st = (blk ? g_st2 : g_st1 + m * 8 * 512) + wg * 64 + w4 * 16 + g8;
            RowAcc ra;
#pragma unroll
            for (int e = 0; e < 64; ++e) ra.add(e, xs[e]);
            ra.publish(st + j * 512, q4, ep);
            uint32_t t_pub = 0; if (PDLY) asm volatile("mov.u32 %0, %%clock;" : "=r"(t_pub));
            if (tid == 0) TL(blk ? 9 : 26);
            if (tid == 128 && blk) TL(34);
            if (blk) CS(11);
            LnPar lp;
            if (blk == 0) {
            uint4* const mod_out = pt.mail->mod1 + g8 * 512 + (m * 8 + j) * 4 + q4;
            if (wg == 0) {
                uint4 af[8];
#pragma unroll
                for (int i = 0; i < 8; ++i) af[i] = lds128(sb + w4 * 512 + i * 64 + q4 * 16);
                float c[4][4] = {};
#pragma unroll
                for (int i = 0; i < 8; ++i) {
                    if (!(i & 1)) mbar_wait(BAR_ONE(sb, EV_WIN + (i >> 1)), 0);
                    if (i == 6 && tid == 0) TL(25);
#pragma unroll
                    for (int h = 0; h < 2; ++h) {
                        uint32_t b0, b1, b2, b3;
                        ldsm4t(sb + 5 * SLOT + i * 4096 + w4 * 1024 + h * 512 + (lane & 15) * 32 + (lane >> 4) * 16, b0, b1, b2, b3);
                        mma16816(c[2 * h], h ? af[i].z : af[i].x, 0u, h ? af[i].w : af[i].y, 0u, b0, b1);
                        mma16816(c[2 * h + 1], h ? af[i].z : af[i].x, 0u, h ? af[i].w : af[i].y, 0u, b2, b3);
                    }
                }
                if (lane < 4) sts128(sb + OFF_TAB + w4 * 64 + lane * 16, __float_as_uint(c[0][0] + c[2][0]), __float_as_uint(c[0][1] + c[2][1]),
                                     __float_as_uint(c[1][0] + c[3][0]), __float_as_uint(c[1][1] + c[3][1]));
                if (lane < 2) mbar_arrive_cta(BAR_ONE(sb, EV_P0), lane);
                bar_sync(1, 128);
                if (w4 == 0) {
                    float a[4] = {0.f, 0.f, 0.f, 0.f};
#pragma unroll
                    for (int i = 0; i < 4; ++i) {
                        const uint4 t = lds128(sb + OFF_TAB + i * 64 + q4 * 16);
                        a[0] += __uint_as_float(t.x); a[1] += __uint_as_float(t.y); a[2] += __uint_as_float(t.z); a[3] += __uint_as_float(t.w);
                    }
                    const float add = m >= 8 ? 1.f : 0.f;
                    st_pkt16(mod_out, pack2(bf_round(a[0]) + add, bf_round(a[1]) + add), pack2(bf_round(a[2]) + add, bf_round(a[3]) + add), ep, 0);
                    if (tid == 0) TL(3);
                }
            } else if (LWAIT >= 0) mbar_wait(BAR_ONE(sb, EV_WIN + LWAIT), 0);
            } else {
                mbar_wait(BAR_ONE(sb, EV_LN2), 0);
            }
            lp.load(sb, q4);
#pragma unroll
            for (int e = 0; e < 32; ++e) xp[e] = pack2(xs[2 * e], xs[2 * e + 1]);
            if (PDLY && blk) { uint32_t t1; do { asm volatile("mov.u32 %0, %%clock;" : "=r"(t1)); } while (t1 - t_pub < PDLY); }
            if (blk) CS(13);
            const LnRow n = merge_stats(st, q4, ep, sb);
            if (tid == 0) TL(blk ? 49 : 48);
            if (tid == 128) TL(blk ? 45 : 28);
            if (blk) CS(18);
            uint32_t xn[32];
            ln_norm(xn, xs, n);
            if (blk == 0) { mbar_wait(BAR_ONE(sb, EV_PAR), 0); lp.load(sb, q4); }
            ln_emit(xn, lp, sb, wg, ix);
            if (tid == 0) { TL(blk ? 36 : 8); TC(blk ? 109 : 103); }
            if (tid == 128) TL(blk ? 43 : 22);
            if (blk) CS(21);
        }
        if (blk == 0) {
        {
            float kv[128], qa[64];
            mbar_wait(BAR_FULL(sb, r.slot), r.par);
            step32<true, true>(kv, qa, sb, wg, r.slot, 0);
            TS(0, 0);
            Pipe pp(sb, tw, r.slot);
            r.next();
#pragma unroll 1
            for (int it = 1; it < 32 - LAGQ; ++it) {
                pp.acquire<true>(sb, wg ? 0 : AF_REL, r);
                step32<true, false>(kv, qa, sb, wg, r.slot, it < 4 ? it : -1);
                pp.issued(r.slot);
                TS(it, 0);
                r.next();
            }
            auto half = [&](uint32_t slot, bool q) {
                const uint32_t st = d16(sb) + slot * (SLOT >> 4);
#pragma unroll
                for (int k = 0; k < 2; ++k) {
                    const uint64_t da = mk_desc(st + wg * 256, k * 32, 16, 512, 2);
                    if (q) wgmma_n128(qa, da, mk_desc(st, 24576 + k * 2048, 4096, 1024, 1)); else wgmma_n256(kv, da, mk_desc(st, 8192 + k * 2048, 4096, 1024, 1));
                }
            };
            auto q_part = [&] {
                wg_fence();
#pragma unroll
                for (int it = 32 - LAGQ; it < 32; ++it) half(it % NSLOT, true);
                wg_commit();
            };
            stg.acquire2(sb, wg); mbar_wait2(BAR_SREADY(sb, 2), BAR_SREADY(sb, 3), 1);
            if (wg == 0) { pp.drain1(); pp.drain0(); mbar_wait(BAR_ONE(sb, EV_LAG0), 0); }
#pragma unroll 1
            for (int it = 32 - LAGQ; it < 32; ++it) {
                pp.acquire<true>(sb, wg ? 0 : AF_REL, r);
                wg_fence();
                half(r.slot, false);
                wg_commit();
                pp.issued(NSLOT);
                TS(it, 0);
                r.next();
            }
            if (wg == 0) { q_part(); wg_wait<1>(); }
            else { wg_wait<1>(); if (tw == 0) mbar_arrive(BAR_ONE(sb, EV_LAG0)); wg_wait<0>(); }
            CS(8);
            IDX();
            uint32_t k1[16], k2[16], v1[16], v2[16], qf[32];
#pragma unroll
            for (int i = 0; i < 128; ++i) asm volatile("" : "+f"(kv[i]) :: "memory");
#pragma unroll
            for (int t = 0; t < 16; ++t) k2[t] = pack2(kv[4 * t + 2], kv[4 * t + 3]);
#pragma unroll
            for (int t = 0; t < 16; ++t) k1[t] = pack2(kv[4 * t], kv[4 * t + 1]);
#pragma unroll
            for (int t = 0; t < 16; ++t) v2[t] = pack2(kv[64 + 4 * t + 2], kv[64 + 4 * t + 3]);
            const uint32_t nxt = warp + ((warp & 1) ? 3 : 1);
            if (nxt < 8) {
                const uint32_t dst = sb + OFF_STG + (nxt >> 2) * 16384 + (nxt & 3) * 2048 + lane * 16;
#pragma unroll
                for (int h = 0; h < 4; ++h) stsm4(dst + h * 512, k2[4 * h], k2[4 * h + 1], k2[4 * h + 2], k2[4 * h + 3]);
#pragma unroll
                for (int h = 0; h < 4; ++h) stsm4(dst + 8192 + h * 512, v2[4 * h], v2[4 * h + 1], v2[4 * h + 2], v2[4 * h + 3]);
                bar_arrive(NB_TAIL + nxt, 64);
            } else if (m < 15) {
                uint4* dst = g_halo + (m * 8 + j) * 512 + (w4 >> 1) * 256 + lane;
#pragma unroll
                for (int h = 0; h < 4; ++h) { if (!k2[4 * h]) k2[4 * h] = 0x8000u; if (!v2[4 * h]) v2[4 * h] = 0x8000u; }
#pragma unroll
                for (int h = 0; h < 4; ++h) st_pkt16(dst + h * 32, k2[4 * h], k2[4 * h + 1], k2[4 * h + 2], k2[4 * h + 3]);
#pragma unroll
                for (int h = 0; h < 4; ++h) st_pkt16(dst + 128 + h * 32, v2[4 * h], v2[4 * h + 1], v2[4 * h + 2], v2[4 * h + 3]);
            }
#pragma unroll
            for (int t = 0; t < 16; ++t) { v1[t] = movm(pack2(kv[64 + 4 * t], kv[64 + 4 * t + 1])); v2[t] = movm(v2[t]); }
            if (tid == 0) TL(33);
            CS(2);
            if (wg) q_part();
            bar_sync(NB_TAIL + warp, 64);
            CS(4);
            if (tid == 0) TL(5);
            uint32_t k0[16], v0[16];
            const uint32_t mine = sb + OFF_STG + wg * 16384 + w4 * 2048;
#pragma unroll
            for (int h = 0; h < 4; ++h) ldsm4(mine + lane * 16 + h * 512, k0[4 * h], k0[4 * h + 1], k0[4 * h + 2], k0[4 * h + 3]);
#pragma unroll
            for (int h = 0; h < 4; ++h) ldsm4t(mine + lane * 16 + 8192 + h * 512, v0[4 * h], v0[4 * h + 1], v0[4 * h + 2], v0[4 * h + 3]);
            wg_wait<0>();
#pragma unroll
            for (int it = 32 - LAGQ; it < 32; ++it) pp.rel(it % NSLOT);
            TS(31, 1);
            if (tid == 0) { TL(4); TC(104); }
            if (tid == 128) TL(50);
            CS(1);
#pragma unroll
            for (int i = 0; i < 64; ++i) asm volatile("" : "+f"(qa[i]) :: "memory");
#pragma unroll
            for (int i = 0; i < 32; ++i) qf[i] = pack2(qa[2 * i], qa[2 * i + 1]);
            float s[4][3][4];
            auto qk = [&](float (&c)[4], int h, const uint32_t* k) {
                c[0] = c[1] = c[2] = c[3] = 0.f;
                mma16816(c, qf[h * 8], qf[h * 8 + 1], qf[h * 8 + 2], qf[h * 8 + 3], k[0], k[1]);
                mma16816(c, qf[h * 8 + 4], qf[h * 8 + 5], qf[h * 8 + 6], qf[h * 8 + 7], k[2], k[3]);
            };
#pragma unroll
            for (int h = 0; h < 4; ++h) { qk(s[h][0], h, k0 + 4 * h); qk(s[h][1], h, k1 + 4 * h); qk(s[h][2], h, k2 + 4 * h); }
            CS(3);
            const bool lo0 = q4 * 2 > g8, lo1 = q4 * 2 + 1 > g8;
            const bool nopast = m == 0 && (warp & 5) == 0;
            const uint32_t lomask = (lo0 ? 0xFFFFu : 0u) | (lo1 ? 0xFFFF0000u : 0u);
            const float sl2 = 0.17677669529663687f * 1.4426950408889634f;
            float e0[8], e1[8], mx[8], sum[8], tt[8];
#pragma unroll
            for (int u = 0; u < 8; ++u) {
                const int h = u >> 1, hf = u & 1;
                e0[u] = lo0 ? ((hf == 0 && nopast) ? -INFINITY : s[h][hf][hf * 2]) : s[h][hf + 1][hf * 2];
                e1[u] = lo1 ? ((hf == 0 && nopast) ? -INFINITY : s[h][hf][hf * 2 + 1]) : s[h][hf + 1][hf * 2 + 1];
                mx[u] = fmaxf(e0[u], e1[u]);
                tt[u] = __shfl_xor_sync(0xffffffffu, mx[u], 1);
            }
#pragma unroll
            for (int u = 0; u < 8; ++u) { mx[u] = fmaxf(mx[u], tt[u]); tt[u] = __shfl_xor_sync(0xffffffffu, mx[u], 2); }
#pragma unroll
            for (int u = 0; u < 8; ++u) {
                const float c = -fmaxf(mx[u], tt[u]) * sl2;
                e0[u] = ex2(fmaf(e0[u], sl2, c)); e1[u] = ex2(fmaf(e1[u], sl2, c));
            }
#pragma unroll
            for (int u = 0; u < 8; ++u) { sum[u] = e0[u] + e1[u]; tt[u] = __shfl_xor_sync(0xffffffffu, sum[u], 1); }
#pragma unroll
            for (int u = 0; u < 8; ++u) { sum[u] += tt[u]; tt[u] = __shfl_xor_sync(0xffffffffu, sum[u], 2); }
#pragma unroll
            for (int u = 0; u < 8; ++u) sum[u] = rcp(sum[u] + tt[u]);
            CS(5);
            float o[8][2][4];
#pragma unroll
            for (int u = 0; u < 8; ++u) {
                const int h = u >> 1;
                const uint32_t p = pack2(e0[u] * sum[u], e1[u] * sum[u]);
                const uint32_t* va = ((u & 1) ? v1 : v0) + 4 * h;
                const uint32_t* vb = ((u & 1) ? v2 : v1) + 4 * h;
#pragma unroll
                for (int d = 0; d < 2; ++d) {
                    o[u][d][0] = o[u][d][1] = o[u][d][2] = o[u][d][3] = 0.f;
                    mma16816(o[u][d], va[2 * d], va[2 * d + 1], vb[2 * d], vb[2 * d + 1], p & lomask, p & ~lomask);
                }
            }
            const uint32_t orow = mine + (lane & 7) * 128 + (((lane >> 3) ^ (lane & 7)) << 4);
#pragma unroll
            for (int u = 0; u < 8; ++u)
                stsm4t((orow ^ (((u >> 1) & 1) << 6)) + (u >> 2) * 8192 + (u & 1) * 1024, pack2(o[u][0][0], o[u][0][1]), pack2(o[u][0][2], o[u][0][3]),
                       pack2(o[u][1][0], o[u][1][1]), pack2(o[u][1][2], o[u][1][3]));
            fence_async_smem();
            __syncwarp();
            if (lane < 2) mbar_arrive(BAR_SFULL(sb, wg * 2 + lane));
            CS(6);
            if (tid == 32) TL(41);
            bar_sync(1 + wg, 128);
            if (tid == 0) { TL(6); TC(106); }
            if (tid == 128) TL(44);
            CS(7);
#pragma unroll
            for (int e = 0; e < 32; ++e) xp[e] = qf[e];
        }
        } else {
        {
            float ag[88], au[88];
            mainloop32<true, LAG>(ag, au, sb, wg, tw, r, EV_LAG1, 48, [&] {
                stg.acquire2(sb, wg);
                Ring q = r; if (!wg) q.next();
                mbar_wait(BAR_EMPTY(sb, q.slot), q.par ^ 1);
            });
            if (tid == 0) { TL(10); TC(110); }
            if (tid == 128) TL(51);
            CS(22);
            glu<11>(sb, wg, [&](int i) { return ag[i]; }, [&](int i) { return au[i]; },
                    [&](int pn) { return pn < 2 ? sb + OFF_STG + wg * 16384 + pn * 8192 : sb + (wg ? P3_SLOT1 : P3_SLOT0) * SLOT + 24576; });
            if (tid == 0) { TL(11); TC(111); }
            if (tid == 128) TL(52);
            CS(23);
        }
        passes128<2>(sb, wg, tw, r, stg);
        if (tid == 0) { TL(12); TC(112); }
        }
        {
            float acc[64], gf[32];
            mainloop64(acc, blk == 0, sb, wg, tw, r, [&] {
                mbar_wait(BAR_ONE(sb, EV_GA + blk), 0);
                const uint32_t buf = stg.acquire2(sb, wg);
                if (blk == 0) load_slab(xp, buf);
                unpack_slab(xs, xp);
                uint32_t gt[16];
#pragma unroll
                for (int cg = 0; cg < 16; ++cg) gt[cg] = lds32(sb + OFF_TAB + blk * 256 + cg * 16 + (tw & 3) * 4);
#pragma unroll
                for (int i = 0; i < 16; ++i) unpack2(gt[i], gf[2 * i], gf[2 * i + 1]);
            });
            if (tid == 0) { TL(blk ? 13 : 7); TC(blk ? 113 : 107); }
            if (tid == 128) TL(blk ? 57 : 42);
            CS(blk ? 30 : 10);
#pragma unroll
            for (int e = 0; e < 64; ++e) xs[e] = fmaf(gf[(e >> 2) * 2 + (e & 1)], acc[e], xs[e]);
        }
        if (blk) break;
        }
        cluster_arrive();
        {
            IDX();
#pragma unroll
            for (int p = 0; p < 2; ++p) {
                store_slab(xs, sb + OFF_STG + wg * 16384, 8192, pan_addr, 4 * p, 4 * p + 4);
                stg.publish(sb, wg, lane);
            }
            if (tid == 0) TL(14);
            CS(31);
        }
      }
    } else {
        if (warp == 8 && !aux && elect_one()) {
#pragma unroll
            for (int i = 0; i < 4; ++i) mbar_init(BAR_SREADY(sb, i), 1);
#pragma unroll
            for (int i = 0; i < 4; ++i) mbar_init(BAR_ONE(sb, EV_WIN + i), 1);
#pragma unroll
            for (int i = 0; i < 4; ++i) {
                mbar_expect_tx(BAR_SREADY(sb, i), 8192);
                tma_load3(sb + OFF_STG + i * 8192, &mp.x, j * 128 + (i & 1) * 64, m * 64 + (i >> 1) * 32, BAR_SREADY(sb, i));
            }
#pragma unroll 1
            for (int i = 0; i < 4; ++i) {
                mbar_expect_tx(BAR_ONE(sb, EV_WIN + i), 8192);
                tma_load(sb + 5 * SLOT + i * 8192, &mp.wm8, 2 * i * 6144 + (m * 8 + j) * 16, 0, BAR_ONE(sb, EV_WIN + i));
                tma_load(sb + 5 * SLOT + i * 8192 + 4096, &mp.wm8, (2 * i + 1) * 6144 + (m * 8 + j) * 16, 0, BAR_ONE(sb, EV_WIN + i));
            }
        }
        __syncwarp();
        asm volatile("setmaxnreg.dec.sync.aligned.u32 56;");
        if (elect_one()) {
            if (warp == 8) {
                prefetch_map(&mp.wqkv); prefetch_map(&mp.wmod);
            } else if (warp < 11) {
                mbar_init(BAR_EMPTY(sb, NSLOT), 1);
#pragma unroll
                for (int i = 0; i < 2; ++i) { mbar_init(BAR_SFULL(sb, (warp - 9) * 2 + i), 4); if (aux) mbar_init(BAR_SREADY(sb, (warp - 9) * 2 + i), 1); }
#pragma unroll
                for (int i = 0; i < 3; ++i) {
                    mbar_init(BAR_EMPTY(sb, (warp - 9) * 3 + i), 4);
                    mbar_init(BAR_FULL(sb, (warp - 9) * 3 + i), 1); mbar_init(BAR_FULL(sb, (warp - 9) * 3 + i) + AF_REL, 1);
                }
            } else {
#pragma unroll
                for (int i = EV_P0; i < EV_COUNT; ++i) mbar_init(BAR_ONE(sb, i), i == EV_P0 ? 8 : 1);
            }
            asm volatile("fence.mbarrier_init.release.cluster;" ::: "memory");
        }
        __syncwarp();
        cluster_arrive();
        ep = 0;
        if (warp != 8 || aux) ep = flag_get(g_flags + FL_DONE);
        cluster_wait();
        ep = __shfl_sync(0xffffffffu, ep, 0) / NCTA + 1;
        if (warp == 8) {
            const bool el = elect_one();
            Ring r{0, 1};
            if (aux) {
                mbar_wait(BAR_ONE(sb, EV_GO), 0);
#pragma unroll 1
                for (int it = 0; it < 64; ++it) {
                    const int col = 2048 + (it >> 4) * 1024 + j * 256;
                    mbar_wait(BAR_EMPTY(sb, r.slot), r.par);
                    const uint32_t st = sb + r.slot * SLOT, fb = BAR_FULL(sb, r.slot);
                    if (el) {
                        mbar_expect_tx(fb, 32768);
#pragma unroll
                        for (int b = 0; b < 4; ++b) tma_load(st + b * 8192, &mp.wmod, col + b * 64, (it & 15) * 64, fb);
                    }
                    r.next();
                }
                mbar_wait(BAR_ONE(sb, EV_P0), 0);
                const CUtensorMap* wm = rank ? &mp.wu : &mp.wg;
#pragma unroll 1
                for (int g = 0; g < 128; ++g) {
                    const int mx = (j >> 1) * 8 + (g >> 5) * 2 + rank, k0 = (g & 31) * 32;
                    if (k0 == 0) {
                        uint32_t n = 0;
                        while (!__all_sync(0xffffffffu, (int32_t)(flag_get(g_flags + FL_PROG + (mx * 32 + lane) * FS) - (ep * 8 + ST_H2)) >= 0)) { SPIN_GUARD(n); __nanosleep(500); }
                    }
                    mbar_wait(BAR_EMPTY(sb, r.slot), r.par);
                    const uint32_t st = sb + r.slot * SLOT, fb = BAR_FULL(sb, r.slot);
                    if (el) {
                        mbar_expect_tx(fb, 24576);
                        tma_load_mc(st + 8192 + rank * 4096, wm, HC3, k0, fb);
                        tma_load_mc(st + 16384 + rank * 4096, wm, HC3 + 64, k0, fb);
                        tma_load(st, &mp.h2l, k0, mx * 128, fb);
                    }
                    r.next();
                }
            } else {
#pragma unroll 1
                for (int it = 0; it < 32; ++it) {
                    const int cb = j * 128 + rank * 64, k0 = kof(it, 2, j);
                    if (it == BW0) mbar_wait(BAR_ONE(sb, BWEV), 0);
                    if (it == BW1) mbar_wait(BAR_ONE(sb, EV_PAR), 0);
                    if (it == 5) mbar_wait(BAR_ONE(sb, EV_P0), 0);
                    if (it == 6) mbar_wait(BAR_ONE(sb, (AGW & 1) ? EV_AGO : EV_FGO), 0);
                    mbar_wait(BAR_EMPTY(sb, r.slot), r.par);
                    const uint32_t st = sb + r.slot * SLOT, fb = BAR_FULL(sb, r.slot);
                    if (el) {
                        mbar_expect_tx(fb, it < 4 ? 24576 : 28672);
                        tma_load_mc(st + 8192 + rank * 4096, &mp.wqkv, 1024 + cb, k0, fb);
                        tma_load_mc(st + 16384 + rank * 4096, &mp.wqkv, 2048 + cb, k0, fb);
                        tma_load_mc(st + 24576 + rank * 4096, &mp.wqkv, cb, k0, fb);
                        if (it < 4) mbar_arrive(fb + AF_REL);
                        if (it == PFWO + (m >> 1)) { tma_prefetch(&mp.wo, j * 128, m * 64); tma_prefetch(&mp.wo, j * 128 + 64, m * 64); }
                    }
                    r.next();
                }
                if (el) mbar_arrive(BAR_ONE(sb, EV_KV));
#pragma unroll 1
                for (int it = 0; it < 16; ++it) {
                    if (it == 6) mbar_wait(BAR_ONE(sb, (AGW & 2) ? EV_AGO1 : EV_FGO1), 0);
                    mbar_wait(BAR_EMPTY(sb, r.slot), r.par);
                    const uint32_t st = sb + r.slot * SLOT, fb = BAR_FULL(sb, r.slot);
                    if (el) {
                        mbar_expect_tx(fb, it < 2 ? 16384 : 24576);
                        tma_load_mc(st + 16384 + rank * 8192, &mp.wo, j * 128 + rank * 64, kof(it, 1, j), fb);
                        if (it < 2) mbar_arrive(fb + AF_REL);
                        if (it == 6) { prefetch_map(rank ? &mp.wu : &mp.wg); prefetch_map(rank ? &mp.wu3 : &mp.wg3); }
                    }
                    r.next();
                }
                const CUtensorMap* wm = rank ? &mp.wu : &mp.wg;
#pragma unroll 1
                for (int g = 0; g < 96; ++g) {
                    if (g == 6) mbar_wait(BAR_ONE(sb, (AGW & 4) ? EV_AGO2 : EV_FGO2), 0);
                    const int p = g >> 5, cb = hcol(p, j), k0 = p == 0 ? kof(g, 2, j) : (g & 31) * 32;
                    mbar_wait(BAR_EMPTY(sb, r.slot), r.par);
                    const uint32_t st = sb + r.slot * SLOT, fb = BAR_FULL(sb, r.slot);
                    if (el) {
                        mbar_expect_tx(fb, (g < 4 || p > 0) ? 24576 : 28672);
                        tma_load_mc(st + 8192 + rank * 4096, wm, cb, k0, fb);
                        tma_load_mc(st + 16384 + rank * 4096, wm, cb + 64, k0, fb);
                        if (p == 0) tma_load3_mc(st + 24576 + rank * 4096, rank ? &mp.wu3 : &mp.wg3, j, k0, fb);
                        else tma_load(st, &mp.h2l, k0, m * 128, fb);
                        if (g < 4) mbar_arrive(fb + AF_REL);
                        if (g == 60) prefetch_map(&mp.wd);
                    }
                    r.next();
                }
#pragma unroll 1
                for (int g = 0; g < 56; ++g) {
                    if (g == 0 || (g & 15) == 6 && g > 6) mbar_wait(BAR_ONE(sb, EV_H0 + (g >> 4)), 0);
                    const int k0 = g * 64;
                    mbar_wait(BAR_EMPTY(sb, r.slot), r.par);
                    const uint32_t st = sb + r.slot * SLOT, fb = BAR_FULL(sb, r.slot);
                    if (el) {
                        mbar_expect_tx(fb, 32768);
                        tma_load_mc(st + 16384 + rank * 8192, &mp.wd, j * 128 + rank * 64, k0, fb);
                        tma_load(st, &mp.hb, k0, m * 128, fb); tma_load(st + 8192, &mp.hb, k0, m * 128 + 64, fb);
                    }
                    r.next();
                }
            }
        } else if (aux) {
            if (warp < 11) {
                const uint32_t w = warp - 9;
                const bool el = elect_one();
#pragma unroll 1
                for (int p = 0; p < 4; ++p) {
                    const int mx = (j >> 1) * 8 + p * 2 + rank;
                    if (el) { mbar_arrive(BAR_SREADY(sb, w * 2)); mbar_arrive(BAR_SREADY(sb, w * 2 + 1)); }
                    mbar_wait2(BAR_SFULL(sb, w * 2), BAR_SFULL(sb, w * 2 + 1), p & 1);
                    if (el) {
                        tma_store(&mp.hb, HC3, mx * 128 + w * 64, sb + OFF_STG + w * 16384); tma_store(&mp.hb, HC3 + 64, mx * 128 + w * 64, sb + OFF_STG + w * 16384 + 8192);
                        bulk_commit(); bulk_wait_all(); flag_set(g_flags + FL_AUX + mx * 2 + w, ep * 8 + ST_H + 3);
                    }
                }
            }
        } else if (warp == 11) {
            const bool el = elect_one();
            const int row0 = m * 128;
            const uint32_t* const fl = g_flags + FL_PROG + (m * 32 + (lane & 16) + (kof(lane & 15, 1, j) >> 6)) * FS;
            if (el) { prefetch_map(&mp.h1h); prefetch_map(&mp.h2h); prefetch_map(&mp.h2l); }
            {
                const uint4* pk = pt.mail->mod1 + grp * 512 + j * 32 + lane;
                uint4 a, b; uint32_t n = 0;
                mbar_wait(BAR_ONE(sb, EV_WIN3), 0);
                while (true) {
                    a = ld_pkt16(pk); b = ld_pkt16(pk + 256);
                    if (__all_sync(0xffffffffu, a.z == ep && b.z == ep)) break;
                    SPIN_GUARD(n);
                }
                sts128(sb + OFF_PAR + lane * 16, a.x, a.y, b.x, b.y);
                __syncwarp();
                if (lane == 0) { mbar_arrive(BAR_ONE(sb, EV_PAR)); TL(46); }
            }
            mbar_wait(BAR_ONE(sb, EV_P0), 0);
            Ring r{0, 1};
#pragma unroll 1
            for (int ph = 0; ph < 3; ++ph) {
                const int sh = ph == 1 ? 1 : 2, nst = 8 << sh;
                const uint32_t half = 16384 >> sh;
                const CUtensorMap* tm = ph == 0 ? &mp.h1h : ph == 1 ? &mp.o : &mp.h2h;
                if (ph == 1) fetch_halo(g_halo + ((m - 1) * 8 + j) * 512 + 256 + lane, m == 0, sb, 2, lane);
                const uint32_t target = ep * 8 + ST_H1 + ph;
                int a0 = 1 << sh, a1 = a0, fr = a0;
                r.skip(fr);
                uint32_t s0 = r.slot, s1 = r.slot, have = 0, n = 0;
                int k0 = j ? 0 : 128, k1 = k0;
#pragma unroll 1
                for (; fr < NSLOT; ++fr) { mbar_wait(BAR_EMPTY(sb, r.slot), r.par); r.next(); }
                uint32_t v = flag_get(fl);
                auto load = [&](int& a, uint32_t& sl, int& k, uint32_t w) {
                    const uint32_t fb = BAR_FULL(sb, sl) + (w ? 0 : AF_REL);
                    if (el) { if (!w) mbar_expect_tx(fb, half); tma_load(sb + sl * SLOT + w * half, tm, k, row0 + w * 64, fb); }
                    if (a == NSLOT - 1 && el) mbar_arrive(BAR_ONE(sb, (w ? EV_AGO : EV_FGO) + ph));
                    ++a; if (++sl == NSLOT) sl = 0;
                    k = kof(a, sh, j);
                };
                do {
                    PS(0);
                    if (fr < 9 && mbar_test(BAR_EMPTY(sb, r.slot), r.par)) { ++fr; r.next(); }
                    SPIN_GUARD(n);
                    PS(1);
                    const bool ok = (int32_t)(v - target) >= 0;
                    v = flag_get(fl);
                    have = __ballot_sync(0xffffffffu, ok);
                    PS(2);
#pragma unroll 1
                    while (a1 < fr && (have & (0x10000u << (a1 >> (sh - 1))))) {
                        if (a1 == (1 << sh)) TL(16 + ph);
                        load(a1, s1, k1, 1);
                    }
                    PS(3);
#pragma unroll 1
                    while (a0 < fr && (have & (1u << (a0 >> (sh - 1))))) load(a0, s0, k0, 0);
                    PS(4);
                } while (~have & 0x01fc01fcu);
#pragma unroll 1
                while (a0 < nst) {
                    if (a0 == 9 << (sh - 1)) while (!__all_sync(0xffffffffu, (int32_t)(flag_get(fl) - target) >= 0)) SPIN_GUARD(n);
                    mbar_wait(BAR_EMPTY(sb, r.slot), r.par);
                    r.next();
                    load(a1, s1, k1, 1); load(a0, s0, k0, 0);
                }
            }
#pragma unroll 1
            for (int p = 0; p < 4; ++p) {
                const uint32_t* f = p < 3 ? fl : g_flags + FL_AUX + m * 2 + (lane & 1);
                uint32_t n = 0;
                while (!__all_sync(0xffffffffu, (int32_t)(flag_get(f) - (ep * 8 + ST_H + p)) >= 0)) { SPIN_GUARD(n); __nanosleep(500); }
                if (el) mbar_arrive(BAR_ONE(sb, EV_H0 + p));
            }
        } else {
            const uint32_t w = warp - 9;
            const int row0 = m * 128 + w * 64;
            const uint32_t stg = sb + OFF_STG + w * 16384;
            uint32_t* const fl = g_flags + FL_PROG + (m * 32 + w * 16 + 2 * j) * FS;
            uint32_t b = 0, par = 0;
            const bool el = elect_one();
            auto store = [&](const CUtensorMap* tm, int col, bool nat = false) {
                mbar_wait(BAR_SFULL(sb, w * 2 + b), (par >> b) & 1);
                par ^= 1u << b;
                if (el) {
                    if (nat) tma_store3(tm, col, row0 >> 1, 0, stg + b * 8192); else tma_store(tm, col, row0, stg + b * 8192);
                    bulk_commit();
                }
                b ^= 1;
            };
            auto send2 = [&](const CUtensorMap* tm, int step) {
                const bool now = step == ST_O && w && ONOW;
                store(tm, j * 128);
                if (!now) {
                    if (el) { bulk_wait_all(); flag_set(fl, ep * 8 + step); }
                    mbar_wait(BAR_ONE(sb, EV_FGO + step - ST_H1), 0);
                    if (step != ST_O) pause(w ? P1H : P1H + 1000);
                }
                store(tm, j * 128 + 64);
                if (el) {
                    if (now) { asm volatile("cp.async.bulk.wait_group 1;" ::: "memory"); flag_set(fl, ep * 8 + step); }
                    bulk_wait_all(); flag_set(fl + FS, ep * 8 + step);
                }
            };
            auto free2 = [&]() { if (el) { mbar_arrive(BAR_SREADY(sb, w * 2)); mbar_arrive(BAR_SREADY(sb, w * 2 + 1)); } };
            auto gate = [&](int vec, int ev) {
                uint4 v; uint32_t n = 0;
                while (true) {
                    v = ld_pkt2(g_mod + vec * 512 + j * 64 + lane * 2);
                    if (__all_sync(0xffffffffu, v.y == ep && v.w == ep)) break;
                    SPIN_GUARD(n); __nanosleep(300);
                }
                asm volatile("st.shared.v2.u32 [%0], {%1, %2};" :: "r"(sb + OFF_TAB + (ev - EV_GA) * 256 + lane * 8), "r"(v.x), "r"(v.z) : "memory");
                __syncwarp();
                if (lane == 0) mbar_arrive(BAR_ONE(sb, ev));
            };
            if (el) { prefetch_map(&mp.h1s); prefetch_map(&mp.o); prefetch_map(&mp.h2s); prefetch_map(&mp.hb); prefetch_map(&mp.out); prefetch_map(&mp.wo); }
            if (el) { flag_set(fl, ep * 8); flag_set(fl + FS, ep * 8); }
            send2(&mp.h1s, ST_H1);
            if (w == 0) TL(47);
            free2();
            if (w == 0) fetch_halo(g_halo + ((m - 1) * 8 + j) * 512 + lane, m == 0, sb, 0, lane);
            else { mbar_wait(BAR_ONE(sb, EV_KV), 0); gate(2, EV_GA); }
            send2(&mp.o, ST_O);
            if (w == 0) TL(40); else TL(38);
            mbar_wait(BAR_ONE(sb, EV_OWN + w), 0);
            if (el) {
#pragma unroll
                for (uint32_t i = 0; i < 2; ++i) {
                    mbar_expect_tx(BAR_SREADY(sb, w * 2 + i), 8192);
                    tma_load3(stg + i * 8192, &mp.x, j * 128 + i * 64, row0 >> 1, BAR_SREADY(sb, w * 2 + i));
                }
            }
            if (w == 1) {
                uint32_t n = 0;
                while ((int32_t)(flag_get(g_flags + FL_LN2) - ep * 8) < 0) { SPIN_GUARD(n); __nanosleep(200); }
                const uint4 v = __ldcg((const uint4*)(g_par2 + j * 128) + lane);
                sts128(sb + OFF_PAR + lane * 16, v.x, v.y, v.z, v.w);
                __syncwarp();
                if (lane == 0) mbar_arrive(BAR_ONE(sb, EV_LN2));
            }
            send2(&mp.h2s, ST_H2);
            if (el) { prefetch_map(&mp.hb); prefetch_map(&mp.hb3); }
            if (w == 0) TL(37);
            free2();
#pragma unroll 1
            for (int p = 0; p < 3; ++p) {
                const int col = hcol(p, j);
                mbar_wait(BAR_SFULL(sb, w * 2), par & 1);
                pause(w ? HD1 : HD0); store(&mp.hb, col);
                pause(HP); store(&mp.hb, col + 64);
                if (p == 0) {
                    pause(HP);
                    if (el) { tma_store3(&mp.hb3, 0, j, row0, sb + (w ? P3_SLOT1 : P3_SLOT0) * SLOT + 24576); bulk_commit(); }
                }
                if (el) { bulk_wait_all(); flag_set(fl, ep * 8 + ST_H + p); flag_set(fl + FS, ep * 8 + ST_H + p); }
                free2();
                if (p == 0 && w == 1) gate(5, EV_GB);
            }
            cluster_arrive_early = true;
            cluster_arrive();
            store(&mp.out, j * 128, true); store(&mp.out, j * 128 + 64, true);
            if (el) bulk_wait_read();
        }
        __syncwarp();
    }
    if (aux || (wg == 2 && !cluster_arrive_early)) cluster_arrive();
    cluster_wait();
    CS(32);
    if (KDEBUG == 5) __syncthreads();
    if (tid == 0) {
        TL(15);
        flag_add(pt.mail->flags + FL_DONE);
    }
}

typedef CUresult (*EncodeFn)(CUtensorMap*, CUtensorMapDataType, cuuint32_t, void*, const cuuint64_t*, const cuuint64_t*, const cuuint32_t*,
                             const cuuint32_t*, CUtensorMapInterleave, CUtensorMapSwizzle, CUtensorMapL2promotion, CUtensorMapFloatOOBfill);

void make_map(EncodeFn fn, CUtensorMap* m, const void* ptr, uint64_t rows, uint64_t cols, uint32_t brows, uint32_t bcols) {
    cuuint64_t dims[2] = {cols, rows}, strides[1] = {cols * 2};
    cuuint32_t box[2] = {bcols, brows}, es[2] = {1, 1};
    fn(m, CU_TENSOR_MAP_DATA_TYPE_BFLOAT16, 2, (void*)ptr, dims, strides, box, es, CU_TENSOR_MAP_INTERLEAVE_NONE,
       bcols == 64 ? CU_TENSOR_MAP_SWIZZLE_128B : bcols == 32 ? CU_TENSOR_MAP_SWIZZLE_64B : CU_TENSOR_MAP_SWIZZLE_NONE, CU_TENSOR_MAP_L2_PROMOTION_L2_256B, CU_TENSOR_MAP_FLOAT_OOB_FILL_NONE);
}

void make_map3(EncodeFn fn, CUtensorMap* m, const void* ptr) {
    cuuint64_t dims[3] = {D_, S_ / 2, 2}, strides[2] = {4 * D_, 2 * D_};
    cuuint32_t box[3] = {64, 32, 2}, es[3] = {1, 1, 1};
    fn(m, CU_TENSOR_MAP_DATA_TYPE_BFLOAT16, 3, (void*)ptr, dims, strides, box, es, CU_TENSOR_MAP_INTERLEAVE_NONE,
       CU_TENSOR_MAP_SWIZZLE_128B, CU_TENSOR_MAP_L2_PROMOTION_L2_256B, CU_TENSOR_MAP_FLOAT_OOB_FILL_NONE);
}

void make_map48(EncodeFn fn, CUtensorMap* m, const void* ptr, uint64_t rows, uint32_t brows) {
    cuuint64_t dims[3] = {48, 8, rows}, strides[2] = {96, 2 * F_};
    cuuint32_t box[3] = {64, 1, brows}, es[3] = {1, 1, 1};
    fn(m, CU_TENSOR_MAP_DATA_TYPE_BFLOAT16, 3, (void*)ptr, dims, strides, box, es, CU_TENSOR_MAP_INTERLEAVE_NONE,
       CU_TENSOR_MAP_SWIZZLE_128B, CU_TENSOR_MAP_L2_PROMOTION_L2_256B, CU_TENSOR_MAP_FLOAT_OOB_FILL_NONE);
}

}

extern "C" void kernel_launch(void* const* d_in, const int* in_sizes, int n_in, void* d_out, int out_size) {
    (void)in_sizes; (void)n_in; (void)out_size;
    void* fnp = nullptr;
    cudaDriverEntryPointQueryResult qr;
    cudaGetDriverEntryPoint("cuTensorMapEncodeTiled", &fnp, cudaEnableDefault, &qr);
    EncodeFn fn = (EncodeFn)fnp;
    void *h1, *o, *h2, *hb, *mail;
    cudaGetSymbolAddress(&h1, g_h1);
    cudaGetSymbolAddress(&mail, g_mail);
    cudaGetSymbolAddress(&o, g_o);
    cudaGetSymbolAddress(&hb, g_hb);
    h2 = H2ALIAS;
    Maps mp;
    make_map(fn, &mp.h1h, h1, S_, D_, 64, 32);
    make_map(fn, &mp.h2h, h2, S_, D_, 64, 32);
    make_map(fn, &mp.h1s, h1, S_, D_, 64, 64);
    make_map(fn, &mp.o, o, S_, D_, 64, 64);
    make_map(fn, &mp.h2l, h2, S_, D_, 128, 32);
    make_map(fn, &mp.h2s, h2, S_, D_, 64, 64);
    make_map(fn, &mp.hb, hb, S_, F_, 64, 64);
    make_map(fn, &mp.wqkv, d_in[1], D_, 3 * D_, 32, 64);
    make_map(fn, &mp.wo, d_in[2], D_, D_, 64, 64);
    make_map(fn, &mp.wg, d_in[4], D_, F_, 32, 64);
    make_map(fn, &mp.wu, d_in[5], D_, F_, 32, 64);
    make_map(fn, &mp.wd, d_in[6], F_, D_, 64, 64);
    make_map(fn, &mp.wmod, d_in[8], D_, 6 * D_, 64, 64);
    make_map(fn, &mp.wm8, d_in[8], D_ / 8, 8 * 6 * D_, 128, 16);
    make_map3(fn, &mp.x, d_in[0]);
    make_map3(fn, &mp.out, d_out);
    make_map48(fn, &mp.wg3, d_in[4], D_, 32);
    make_map48(fn, &mp.wu3, d_in[5], D_, 32);
    make_map48(fn, &mp.hb3, hb, S_, 64);
    cudaFuncSetAttribute(fused_block_kernel, cudaFuncAttributeMaxDynamicSharedMemorySize, SMEM_BYTES);
    cudaLaunchConfig_t cfg = {};
    cfg.gridDim = dim3(NCTA); cfg.blockDim = dim3(384); cfg.dynamicSmemBytes = SMEM_BYTES; cfg.stream = cudaStreamPerThread;
    cudaLaunchAttribute at[1];
    at[0].id = cudaLaunchAttributeClusterDimension; at[0].val.clusterDim.x = 2; at[0].val.clusterDim.y = 1; at[0].val.clusterDim.z = 1;
    cfg.attrs = at; cfg.numAttrs = 1;
    const Ptrs pt{(const __nv_bfloat16*)d_in[7], (Mail*)mail};
    cudaLaunchKernelEx(&cfg, fused_block_kernel, pt, mp);
}
```

```cpp
#include <cuda_runtime.h>
#include <cuda_bf16.h>
#include <cuda.h>
#include <stdint.h>
#include <stddef.h>

#define LAG 4
#define LAGS 4
#define LAGW 3
#define LAGQ 4
#define MIDW 8
#define PFWO 14
#define FLAGRED 1
#define FS 1
#define P1H 2000
#define AGW 6
#define CSW 0
#define LWAIT 2
#define BW0 0
#define BWEV EV_WIN
#define GODLY 0
#define BW1 3
#define PDLY 500
#define H2ALIAS o
#define HD1 5500
#define HD0 5500
#define HP 2200
#define LAGD 4
#define MIDD 44
#define PSPLIT 1
#define OMODE 1
#define KDEBUG 0

namespace {

constexpr int S_ = 2048, D_ = 1024, F_ = 3584;
constexpr int NCTA = 132;
constexpr int NSLOT = 6;
constexpr uint32_t SLOT = 32768;
constexpr uint32_t OFF_STG = NSLOT * SLOT;
constexpr uint32_t OFF_BAR = OFF_STG + 32768;
constexpr uint32_t OFF_PAR = OFF_BAR + 512;
constexpr uint32_t OFF_TAB = OFF_PAR + 768;
constexpr uint32_t OFF_TL = OFF_PAR + 2048;
constexpr uint32_t SMEM_BYTES = OFF_TL + (KDEBUG ? 512 : 0);
constexpr uint32_t P3_SLOT1 = (32 + 16 + 32) % NSLOT, P3_SLOT0 = (P3_SLOT1 + 1) % NSLOT;

constexpr int ST_H1 = 1, ST_O = 2, ST_H2 = 3, ST_H = 4, FL_DONE = 0, FL_LN2 = 1, FL_AUX = 32, FL_PROG = 64;

struct Maps {
    CUtensorMap h1h, h1s, o, h2h, h2l, h2s, hb, wqkv, wo, wg, wu, wd, wmod, wm8, x, out, wg3, wu3, hb3;
};

struct Mail {
    uint32_t flags[16 * 32 * FS + 64];
    uint2 mod[6 * D_ / 2];
    uint4 mod1[8 * 512];
    uint4 st1[128 * 512];
    uint32_t par2[D_];
    uint4 halo[128 * 512];
};
struct Ptrs { const __nv_bfloat16* c; Mail* mail; };

__device__ __align__(128) Mail g_mail;
__device__ __align__(128) __nv_bfloat16 g_h1[S_ * D_];
__device__ __align__(128) __nv_bfloat16 g_o[S_ * D_];
__device__ __align__(128) __nv_bfloat16 g_hb[S_ * F_];
#define TL(i) do {} while (0)
#define TC(i) do {} while (0)
#define TS(g, which) do {} while (0)
#define CS(i) do {} while (0)

#define PS(i) do {} while (0)
__device__ __forceinline__ uint32_t smem_u32(const void* p) { return (uint32_t)__cvta_generic_to_shared(p); }
__device__ __forceinline__ void mbar_init(uint32_t bar, uint32_t cnt) { asm volatile("mbarrier.init.shared::cta.b64 [%0], %1;" :: "r"(bar), "r"(cnt) : "memory"); }
__device__ __forceinline__ void mbar_expect_tx(uint32_t bar, uint32_t bytes) { asm volatile("mbarrier.arrive.expect_tx.shared::cta.b64 _, [%0], %1;" :: "r"(bar), "r"(bytes) : "memory"); }
__device__ __forceinline__ void mbar_arrive(uint32_t bar) { asm volatile("mbarrier.arrive.shared::cta.b64 _, [%0];" :: "r"(bar) : "memory"); }
__device__ __forceinline__ void mbar_arrive_cta(uint32_t bar, uint32_t cta) {
    asm volatile("{\n.reg .b32 r;\nmapa.shared::cluster.u32 r, %0, %1;\nmbarrier.arrive.shared::cluster.b64 _, [r];\n}" :: "r"(bar), "r"(cta) : "memory");
}
__device__ __forceinline__ void mbar_wait(uint32_t bar, uint32_t parity) {
    asm volatile("{\n.reg .pred p;\n.reg .u32 n;\nmov.u32 n, 0;\n"
        "W_LOOP:\nmbarrier.try_wait.parity.shared::cta.b64 p, [%0], %1;\n@p bra W_DONE;\n"
        "add.u32 n, n, 1;\nsetp.lt.u32 p, n, 0x400000;\n@p bra W_LOOP;\ntrap;\nW_DONE:\n}" :: "r"(bar), "r"(parity) : "memory");
}
__device__ __forceinline__ void mbar_wait2(uint32_t b0, uint32_t b1, uint32_t parity) {
    asm volatile("{\n.reg .pred p, q;\n.reg .u32 n;\nmov.u32 n, 0;\n"
        "W_LOOP:\nmbarrier.try_wait.parity.shared::cta.b64 p, [%0], %2;\nmbarrier.try_wait.parity.shared::cta.b64 q, [%1], %2;\nand.pred p, p, q;\n@p bra W_DONE;\n"
        "add.u32 n, n, 1;\nsetp.lt.u32 p, n, 0x400000;\n@p bra W_LOOP;\ntrap;\nW_DONE:\n}" :: "r"(b0), "r"(b1), "r"(parity) : "memory");
}
__device__ __forceinline__ bool mbar_test(uint32_t bar, uint32_t parity) {
    uint32_t r; asm volatile("{\n.reg .pred p;\nmbarrier.test_wait.parity.shared::cta.b64 p, [%1], %2;\nselp.u32 %0, 1, 0, p;\n}" : "=r"(r) : "r"(bar), "r"(parity) : "memory"); return r;
}
__device__ __forceinline__ bool mbar_test2(uint32_t b0, uint32_t b1, uint32_t parity) {
    uint32_t r;
    asm volatile("{\n.reg .pred p, q;\nmbarrier.test_wait.parity.shared::cta.b64 p, [%1], %3;\nmbarrier.test_wait.parity.shared::cta.b64 q, [%2], %3;\n"
        "and.pred p, p, q;\nselp.u32 %0, 1, 0, p;\n}" : "=r"(r) : "r"(b0), "r"(b1), "r"(parity) : "memory");
    return r;
}
__device__ __forceinline__ void tma_load3(uint32_t dst, const CUtensorMap* m, int c0, int c1, uint32_t bar) {
    asm volatile("cp.async.bulk.tensor.3d.shared::cluster.global.mbarrier::complete_tx::bytes [%0], [%1, {%3, %4, %5}], [%2];"
        :: "r"(dst), "l"(m), "r"(bar), "r"(c0), "r"(c1), "r"(0) : "memory");
}
__device__ __forceinline__ void tma_store3(const CUtensorMap* m, int c0, int c1, int c2, uint32_t src) {
    asm volatile("cp.async.bulk.tensor.3d.global.shared::cta.bulk_group [%0, {%2, %3, %4}], [%1];" :: "l"(m), "r"(src), "r"(c0), "r"(c1), "r"(c2) : "memory");
}
__device__ __forceinline__ void tma_load3_mc(uint32_t dst, const CUtensorMap* m, int c1, int c2, uint32_t bar) {
    asm volatile("cp.async.bulk.tensor.3d.shared::cluster.global.mbarrier::complete_tx::bytes.multicast::cluster.L2::cache_hint [%0], [%1, {%3, %4, %5}], [%2], %6, %7;"
        :: "r"(dst), "l"(m), "r"(bar), "r"(0), "r"(c1), "r"(c2), "h"((uint16_t)3), "l"(0x12F0000000000000ull) : "memory");
}
__device__ __forceinline__ void tma_load(uint32_t dst, const CUtensorMap* m, int c0, int c1, uint32_t bar) {
    asm volatile("cp.async.bulk.tensor.2d.shared::cluster.global.mbarrier::complete_tx::bytes [%0], [%1, {%3, %4}], [%2];"
        :: "r"(dst), "l"(m), "r"(bar), "r"(c0), "r"(c1) : "memory");
}
__device__ __forceinline__ void tma_load_mc(uint32_t dst, const CUtensorMap* m, int c0, int c1, uint32_t bar) {
    asm volatile("cp.async.bulk.tensor.2d.shared::cluster.global.mbarrier::complete_tx::bytes.multicast::cluster.L2::cache_hint [%0], [%1, {%3, %4}], [%2], %5, %6;"
        :: "r"(dst), "l"(m), "r"(bar), "r"(c0), "r"(c1), "h"((uint16_t)3), "l"(0x12F0000000000000ull) : "memory");
}
__device__ __forceinline__ void tma_prefetch(const CUtensorMap* m, int c0, int c1) {
    asm volatile("cp.async.bulk.prefetch.tensor.2d.L2.global [%0, {%1, %2}];" :: "l"(m), "r"(c0), "r"(c1) : "memory");
}
__device__ __forceinline__ void tma_store(const CUtensorMap* m, int c0, int c1, uint32_t src) {
    asm volatile("cp.async.bulk.tensor.2d.global.shared::cta.bulk_group [%0, {%2, %3}], [%1];" :: "l"(m), "r"(src), "r"(c0), "r"(c1) : "memory");
}
__device__ __forceinline__ void bulk_commit() { asm volatile("cp.async.bulk.commit_group;" ::: "memory"); }
__device__ __forceinline__ void bulk_wait_read() { asm volatile("cp.async.bulk.wait_group.read 0;" ::: "memory"); }
__device__ __forceinline__ void bulk_wait_all() { asm volatile("cp.async.bulk.wait_group 0;" ::: "memory"); }
__device__ __forceinline__ void fence_async_smem() { asm volatile("fence.proxy.async.shared::cta;" ::: "memory"); }
__device__ __forceinline__ void prefetch_map(const CUtensorMap* m) { asm volatile("prefetch.tensormap [%0];" :: "l"(m) : "memory"); }
__device__ __forceinline__ void wg_fence() { asm volatile("wgmma.fence.sync.aligned;" ::: "memory"); }
__device__ __forceinline__ void wg_commit() { asm volatile("wgmma.commit_group.sync.aligned;" ::: "memory"); }
template <int N> __device__ __forceinline__ void wg_wait() { asm volatile("wgmma.wait_group.sync.aligned %0;" :: "n"(N) : "memory"); }
__device__ __forceinline__ void bar_sync(int id, int n) { asm volatile("bar.sync %0, %1;" :: "r"(id), "r"(n) : "memory"); }
__device__ __forceinline__ void bar_arrive(int id, int n) { asm volatile("bar.arrive %0, %1;" :: "r"(id), "r"(n) : "memory"); }
__device__ __forceinline__ void flag_add(uint32_t* f) { asm volatile("red.relaxed.gpu.global.add.u32 [%0], 1;" :: "l"(f) : "memory"); }
__device__ __forceinline__ void flag_set(uint32_t* f, uint32_t v) { asm volatile("red.relaxed.gpu.global.max.u32 [%0], %1;" :: "l"(f), "r"(v) : "memory"); }
__device__ __forceinline__ uint32_t flag_get(const uint32_t* f) { uint32_t v; asm volatile("ld.relaxed.gpu.global.u32 %0, [%1];" : "=r"(v) : "l"(f) : "memory"); return v; }
__device__ __forceinline__ uint32_t d16(uint32_t addr) { return (addr & 0x3FFFF) >> 4; }
__device__ __forceinline__ uint64_t mk_desc(uint32_t a16, uint32_t off, uint32_t lbo, uint32_t sbo, uint32_t swz) {
    const uint32_t lo = a16 + (off >> 4) + ((lbo >> 4) << 16), hi = (sbo >> 4) | (swz << 30);
    return ((uint64_t)hi << 32) | lo;
}
__device__ __forceinline__ uint32_t pack2(float lo, float hi) {
    uint32_t r; asm("cvt.rn.bf16x2.f32 %0, %1, %2;" : "=r"(r) : "f"(hi), "f"(lo)); return r;
}
__device__ __forceinline__ uint32_t hfma2_bf16(uint32_t a, uint32_t b, uint32_t c) {
    uint32_t r; asm("fma.rn.bf16x2 %0, %1, %2, %3;" : "=r"(r) : "r"(a), "r"(b), "r"(c)); return r;
}
__device__ __forceinline__ float bf_lo(uint32_t v) { return __uint_as_float(v << 16); }
__device__ __forceinline__ float bf_hi(uint32_t v) { return __uint_as_float(v & 0xFFFF0000u); }
__device__ __forceinline__ void unpack2(uint32_t v, float& lo, float& hi) {
    asm volatile("shl.b32 %0, %2, 16;\nand.b32 %1, %2, 0xffff0000;" : "=f"(lo), "=f"(hi) : "r"(v));
}
__device__ __forceinline__ float bf_round(float x) { return __bfloat162float(__float2bfloat16_rn(x)); }
__device__ __forceinline__ void stsm4(uint32_t addr, uint32_t r0, uint32_t r1, uint32_t r2, uint32_t r3) {
    asm volatile("stmatrix.sync.aligned.m8n8.x4.shared.b16 [%0], {%1, %2, %3, %4};" :: "r"(addr), "r"(r0), "r"(r1), "r"(r2), "r"(r3) : "memory");
}
__device__ __forceinline__ void stsm4t(uint32_t addr, uint32_t r0, uint32_t r1, uint32_t r2, uint32_t r3) {
    asm volatile("stmatrix.sync.aligned.m8n8.x4.trans.shared.b16 [%0], {%1, %2, %3, %4};" :: "r"(addr), "r"(r0), "r"(r1), "r"(r2), "r"(r3) : "memory");
}
__device__ __forceinline__ uint32_t movm(uint32_t a) { uint32_t d; asm volatile("movmatrix.sync.aligned.m8n8.trans.b16 %0, %1;" : "=r"(d) : "r"(a)); return d; }
__device__ __forceinline__ void ldsm4(uint32_t addr, uint32_t& r0, uint32_t& r1, uint32_t& r2, uint32_t& r3) {
    asm volatile("ldmatrix.sync.aligned.m8n8.x4.shared.b16 {%0, %1, %2, %3}, [%4];" : "=r"(r0), "=r"(r1), "=r"(r2), "=r"(r3) : "r"(addr) : "memory");
}
__device__ __forceinline__ void ldsm4t(uint32_t addr, uint32_t& r0, uint32_t& r1, uint32_t& r2, uint32_t& r3) {
    asm volatile("ldmatrix.sync.aligned.m8n8.x4.trans.shared.b16 {%0, %1, %2, %3}, [%4];" : "=r"(r0), "=r"(r1), "=r"(r2), "=r"(r3) : "r"(addr) : "memory");
}
__device__ __forceinline__ void mma16816(float (&c)[4], uint32_t a0, uint32_t a1, uint32_t a2, uint32_t a3, uint32_t b0, uint32_t b1) {
    asm("mma.sync.aligned.m16n8k16.row.col.f32.bf16.bf16.f32 {%0, %1, %2, %3}, {%4, %5, %6, %7}, {%8, %9}, {%0, %1, %2, %3};"
        : "+f"(c[0]), "+f"(c[1]), "+f"(c[2]), "+f"(c[3]) : "r"(a0), "r"(a1), "r"(a2), "r"(a3), "r"(b0), "r"(b1));
}
__device__ __forceinline__ float rcp(float x) { float r; asm("rcp.approx.ftz.f32 %0, %1;" : "=f"(r) : "f"(x)); return r; }
__device__ __forceinline__ float ex2(float x) { float r; asm("ex2.approx.ftz.f32 %0, %1;" : "=f"(r) : "f"(x)); return r; }
__device__ __forceinline__ float tanh_(float x) { float t; asm("tanh.approx.f32 %0, %1;" : "=f"(t) : "f"(x)); return t; }
__device__ __forceinline__ void block_end(uint32_t opaque) { asm volatile("{\n.reg .pred p;\nsetp.eq.u32 p, %0, 0xffffffff;\n@p trap;\n}" :: "r"(opaque)); }
__device__ __forceinline__ float silu_(float x) { return __fdividef(x, 1.f + __expf(-x)); }
__device__ __forceinline__ void st_pkt(void* p, uint32_t a, uint32_t b) {
    asm volatile("{\n.reg .b64 t;\nmov.b64 t, {%1, %2};\nst.relaxed.gpu.global.b64 [%0], t;\n}" :: "l"(p), "r"(a), "r"(b) : "memory");
}
__device__ __forceinline__ uint4 ld_pkt2(const void* p) {
    uint4 v; asm volatile("{\n.reg .b64 t, u;\nld.relaxed.gpu.global.v2.b64 {t, u}, [%4];\nmov.b64 {%0, %1}, t;\nmov.b64 {%2, %3}, u;\n}"
        : "=r"(v.x), "=r"(v.y), "=r"(v.z), "=r"(v.w) : "l"(p) : "memory"); return v;
}
__device__ __forceinline__ void st_pkt16(void* p, uint32_t a, uint32_t b, uint32_t c, uint32_t d) {
    asm volatile("{\n.reg .b64 t, u;\n.reg .b128 w;\nmov.b64 t, {%1, %2};\nmov.b64 u, {%3, %4};\nmov.b128 w, {t, u};\nst.relaxed.gpu.global.b128 [%0], w;\n}"
        :: "l"(p), "r"(a), "r"(b), "r"(c), "r"(d) : "memory");
}
__device__ __forceinline__ uint4 ld_pkt16(const void* p) {
    uint4 v; asm volatile("{\n.reg .b64 t, u;\n.reg .b128 w;\nld.relaxed.gpu.global.b128 w, [%4];\nmov.b128 {t, u}, w;\nmov.b64 {%0, %1}, t;\nmov.b64 {%2, %3}, u;\n}"
        : "=r"(v.x), "=r"(v.y), "=r"(v.z), "=r"(v.w) : "l"(p) : "memory"); return v;
}
#define SPIN_GUARD(n) do { if (++(n) > (1u << 22)) asm volatile("trap;"); } while (0)
__device__ __forceinline__ uint4 lds128(uint32_t a) { uint4 v; asm volatile("ld.shared.v4.u32 {%0, %1, %2, %3}, [%4];" : "=r"(v.x), "=r"(v.y), "=r"(v.z), "=r"(v.w) : "r"(a) : "memory"); return v; }
__device__ __forceinline__ void sts128(uint32_t a, uint32_t x, uint32_t y, uint32_t z, uint32_t w) { asm volatile("st.shared.v4.u32 [%0], {%1, %2, %3, %4};" :: "r"(a), "r"(x), "r"(y), "r"(z), "r"(w) : "memory"); }
__device__ __forceinline__ uint32_t lds32(uint32_t a) { uint32_t v; asm volatile("ld.shared.u32 %0, [%1];" : "=r"(v) : "r"(a) : "memory"); return v; }
__device__ __forceinline__ void sts32(uint32_t a, uint32_t v) { asm volatile("st.shared.u32 [%0], %1;" :: "r"(a), "r"(v) : "memory"); }
__device__ __forceinline__ bool elect_one() {
    uint32_t p; asm volatile("{\n.reg .pred q;\nelect.sync _|q, 0xffffffff;\nselp.u32 %0, 1, 0, q;\n}" : "=r"(p)); return p;
}
__device__ __forceinline__ void pause(uint32_t cycles) {
    uint32_t t0, t; asm volatile("mov.u32 %0, %%clock;" : "=r"(t0));
    do { __nanosleep(64); asm volatile("mov.u32 %0, %%clock;" : "=r"(t)); } while (t - t0 < cycles);
}
__device__ __forceinline__ void cluster_arrive() { asm volatile("barrier.cluster.arrive.relaxed.aligned;" ::: "memory"); }
__device__ __forceinline__ void cluster_wait() { asm volatile("barrier.cluster.wait.aligned;" ::: "memory"); }

__device__ __forceinline__ void wgmma_n128_z(float (&d)[64], uint64_t da, uint64_t db) {
    asm volatile("{\n.reg .pred p;\nsetp.ne.b32 p, 0, 0;\n"
        "wgmma.mma_async.sync.aligned.m64n128k16.f32.bf16.bf16 {"
        "%0, %1, %2, %3, %4, %5, %6, %7, %8, %9, %10, %11, %12, %13, %14, %15, "
        "%16, %17, %18, %19, %20, %21, %22, %23, %24, %25, %26, %27, %28, %29, %30, %31, "
        "%32, %33, %34, %35, %36, %37, %38, %39, %40, %41, %42, %43, %44, %45, %46, %47, "
        "%48, %49, %50, %51, %52, %53, %54, %55, %56, %57, %58, %59, %60, %61, %62, %63"
        "}, %64, %65, p, 1, 1, 0, 1;\n}\n"
        : "=f"(d[0]), "=f"(d[1]), "=f"(d[2]), "=f"(d[3]), "=f"(d[4]), "=f"(d[5]), "=f"(d[6]), "=f"(d[7]),
          "=f"(d[8]), "=f"(d[9]), "=f"(d[10]), "=f"(d[11]), "=f"(d[12]), "=f"(d[13]), "=f"(d[14]), "=f"(d[15]),
          "=f"(d[16]), "=f"(d[17]), "=f"(d[18]), "=f"(d[19]), "=f"(d[20]), "=f"(d[21]), "=f"(d[22]), "=f"(d[23]),
          "=f"(d[24]), "=f"(d[25]), "=f"(d[26]), "=f"(d[27]), "=f"(d[28]), "=f"(d[29]), "=f"(d[30]), "=f"(d[31]),
          "=f"(d[32]), "=f"(d[33]), "=f"(d[34]), "=f"(d[35]), "=f"(d[36]), "=f"(d[37]), "=f"(d[38]), "=f"(d[39]),
          "=f"(d[40]), "=f"(d[41]), "=f"(d[42]), "=f"(d[43]), "=f"(d[44]), "=f"(d[45]), "=f"(d[46]), "=f"(d[47]),
          "=f"(d[48]), "=f"(d[49]), "=f"(d[50]), "=f"(d[51]), "=f"(d[52]), "=f"(d[53]), "=f"(d[54]), "=f"(d[55]),
          "=f"(d[56]), "=f"(d[57]), "=f"(d[58]), "=f"(d[59]), "=f"(d[60]), "=f"(d[61]), "=f"(d[62]), "=f"(d[63])
        : "l"(da), "l"(db));
}
__device__ __forceinline__ void wgmma_n128(float (&d)[64], uint64_t da, uint64_t db) {
    asm volatile("{\n.reg .pred p;\nsetp.eq.b32 p, 0, 0;\n"
        "wgmma.mma_async.sync.aligned.m64n128k16.f32.bf16.bf16 {"
        "%0, %1, %2, %3, %4, %5, %6, %7, %8, %9, %10, %11, %12, %13, %14, %15, "
        "%16, %17, %18, %19, %20, %21, %22, %23, %24, %25, %26, %27, %28, %29, %30, %31, "
        "%32, %33, %34, %35, %36, %37, %38, %39, %40, %41, %42, %43, %44, %45, %46, %47, "
        "%48, %49, %50, %51, %52, %53, %54, %55, %56, %57, %58, %59, %60, %61, %62, %63"
        "}, %64, %65, p, 1, 1, 0, 1;\n}\n"
        : "+f"(d[0]), "+f"(d[1]), "+f"(d[2]), "+f"(d[3]), "+f"(d[4]), "+f"(d[5]), "+f"(d[6]), "+f"(d[7]),
          "+f"(d[8]), "+f"(d[9]), "+f"(d[10]), "+f"(d[11]), "+f"(d[12]), "+f"(d[13]), "+f"(d[14]), "+f"(d[15]),
          "+f"(d[16]), "+f"(d[17]), "+f"(d[18]), "+f"(d[19]), "+f"(d[20]), "+f"(d[21]), "+f"(d[22]), "+f"(d[23]),
          "+f"(d[24]), "+f"(d[25]), "+f"(d[26]), "+f"(d[27]), "+f"(d[28]), "+f"(d[29]), "+f"(d[30]), "+f"(d[31]),
          "+f"(d[32]), "+f"(d[33]), "+f"(d[34]), "+f"(d[35]), "+f"(d[36]), "+f"(d[37]), "+f"(d[38]), "+f"(d[39]),
          "+f"(d[40]), "+f"(d[41]), "+f"(d[42]), "+f"(d[43]), "+f"(d[44]), "+f"(d[45]), "+f"(d[46]), "+f"(d[47]),
          "+f"(d[48]), "+f"(d[49]), "+f"(d[50]), "+f"(d[51]), "+f"(d[52]), "+f"(d[53]), "+f"(d[54]), "+f"(d[55]),
          "+f"(d[56]), "+f"(d[57]), "+f"(d[58]), "+f"(d[59]), "+f"(d[60]), "+f"(d[61]), "+f"(d[62]), "+f"(d[63])
        : "l"(da), "l"(db));
}
__device__ __forceinline__ void wgmma_n176_z(float (&d)[88], uint64_t da, uint64_t db) {
    asm volatile("{\n.reg .pred p;\nsetp.ne.b32 p, 0, 0;\n"
        "wgmma.mma_async.sync.aligned.m64n176k16.f32.bf16.bf16 {"
        "%0, %1, %2, %3, %4, %5, %6, %7, %8, %9, %10, %11, %12, %13, %14, %15, "
        "%16, %17, %18, %19, %20, %21, %22, %23, %24, %25, %26, %27, %28, %29, %30, %31, "
        "%32, %33, %34, %35, %36, %37, %38, %39, %40, %41, %42, %43, %44, %45, %46, %47, "
        "%48, %49, %50, %51, %52, %53, %54, %55, %56, %57, %58, %59, %60, %61, %62, %63, "
        "%64, %65, %66, %67, %68, %69, %70, %71, %72, %73, %74, %75, %76, %77, %78, %79, "
        "%80, %81, %82, %83, %84, %85, %86, %87"
        "}, %88, %89, p, 1, 1, 0, 1;\n}\n"
        : "=f"(d[0]), "=f"(d[1]), "=f"(d[2]), "=f"(d[3]), "=f"(d[4]), "=f"(d[5]), "=f"(d[6]), "=f"(d[7]),
          "=f"(d[8]), "=f"(d[9]), "=f"(d[10]), "=f"(d[11]), "=f"(d[12]), "=f"(d[13]), "=f"(d[14]), "=f"(d[15]),
          "=f"(d[16]), "=f"(d[17]), "=f"(d[18]), "=f"(d[19]), "=f"(d[20]), "=f"(d[21]), "=f"(d[22]), "=f"(d[23]),
          "=f"(d[24]), "=f"(d[25]), "=f"(d[26]), "=f"(d[27]), "=f"(d[28]), "=f"(d[29]), "=f"(d[30]), "=f"(d[31]),
          "=f"(d[32]), "=f"(d[33]), "=f"(d[34]), "=f"(d[35]), "=f"(d[36]), "=f"(d[37]), "=f"(d[38]), "=f"(d[39]),
          "=f"(d[40]), "=f"(d[41]), "=f"(d[42]), "=f"(d[43]), "=f"(d[44]), "=f"(d[45]), "=f"(d[46]), "=f"(d[47]),
          "=f"(d[48]), "=f"(d[49]), "=f"(d[50]), "=f"(d[51]), "=f"(d[52]), "=f"(d[53]), "=f"(d[54]), "=f"(d[55]),
          "=f"(d[56]), "=f"(d[57]), "=f"(d[58]), "=f"(d[59]), "=f"(d[60]), "=f"(d[61]), "=f"(d[62]), "=f"(d[63]),
          "=f"(d[64]), "=f"(d[65]), "=f"(d[66]), "=f"(d[67]), "=f"(d[68]), "=f"(d[69]), "=f"(d[70]), "=f"(d[71]),
          "=f"(d[72]), "=f"(d[73]), "=f"(d[74]), "=f"(d[75]), "=f"(d[76]), "=f"(d[77]), "=f"(d[78]), "=f"(d[79]),
          "=f"(d[80]), "=f"(d[81]), "=f"(d[82]), "=f"(d[83]), "=f"(d[84]), "=f"(d[85]), "=f"(d[86]), "=f"(d[87])
        : "l"(da), "l"(db));
}
__device__ __forceinline__ void wgmma_n176(float (&d)[88], uint64_t da, uint64_t db) {
    asm volatile("{\n.reg .pred p;\nsetp.eq.b32 p, 0, 0;\n"
        "wgmma.mma_async.sync.aligned.m64n176k16.f32.bf16.bf16 {"
        "%0, %1, %2, %3, %4, %5, %6, %7, %8, %9, %10, %11, %12, %13, %14, %15, "
        "%16, %17, %18, %19, %20, %21, %22, %23, %24, %25, %26, %27, %28, %29, %30, %31, "
        "%32, %33, %34, %35, %36, %37, %38, %39, %40, %41, %42, %43, %44, %45, %46, %47, "
        "%48, %49, %50, %51, %52, %53, %54, %55, %56, %57, %58, %59, %60, %61, %62, %63, "
        "%64, %65, %66, %67, %68, %69, %70, %71, %72, %73, %74, %75, %76, %77, %78, %79, "
        "%80, %81, %82, %83, %84, %85, %86, %87"
        "}, %88, %89, p, 1, 1, 0, 1;\n}\n"
        : "+f"(d[0]), "+f"(d[1]), "+f"(d[2]), "+f"(d[3]), "+f"(d[4]), "+f"(d[5]), "+f"(d[6]), "+f"(d[7]),
          "+f"(d[8]), "+f"(d[9]), "+f"(d[10]), "+f"(d[11]), "+f"(d[12]), "+f"(d[13]), "+f"(d[14]), "+f"(d[15]),
          "+f"(d[16]), "+f"(d[17]), "+f"(d[18]), "+f"(d[19]), "+f"(d[20]), "+f"(d[21]), "+f"(d[22]), "+f"(d[23]),
          "+f"(d[24]), "+f"(d[25]), "+f"(d[26]), "+f"(d[27]), "+f"(d[28]), "+f"(d[29]), "+f"(d[30]), "+f"(d[31]),
          "+f"(d[32]), "+f"(d[33]), "+f"(d[34]), "+f"(d[35]), "+f"(d[36]), "+f"(d[37]), "+f"(d[38]), "+f"(d[39]),
          "+f"(d[40]), "+f"(d[41]), "+f"(d[42]), "+f"(d[43]), "+f"(d[44]), "+f"(d[45]), "+f"(d[46]), "+f"(d[47]),
          "+f"(d[48]), "+f"(d[49]), "+f"(d[50]), "+f"(d[51]), "+f"(d[52]), "+f"(d[53]), "+f"(d[54]), "+f"(d[55]),
          "+f"(d[56]), "+f"(d[57]), "+f"(d[58]), "+f"(d[59]), "+f"(d[60]), "+f"(d[61]), "+f"(d[62]), "+f"(d[63]),
          "+f"(d[64]), "+f"(d[65]), "+f"(d[66]), "+f"(d[67]), "+f"(d[68]), "+f"(d[69]), "+f"(d[70]), "+f"(d[71]),
          "+f"(d[72]), "+f"(d[73]), "+f"(d[74]), "+f"(d[75]), "+f"(d[76]), "+f"(d[77]), "+f"(d[78]), "+f"(d[79]),
          "+f"(d[80]), "+f"(d[81]), "+f"(d[82]), "+f"(d[83]), "+f"(d[84]), "+f"(d[85]), "+f"(d[86]), "+f"(d[87])
        : "l"(da), "l"(db));
}
__device__ __forceinline__ void wgmma_n256_z(float (&d)[128], uint64_t da, uint64_t db) {
    asm volatile("{\n.reg .pred p;\nsetp.ne.b32 p, 0, 0;\n"
        "wgmma.mma_async.sync.aligned.m64n256k16.f32.bf16.bf16 {"
        "%0, %1, %2, %3, %4, %5, %6, %7, %8, %9, %10, %11, %12, %13, %14, %15, "
        "%16, %17, %18, %19, %20, %21, %22, %23, %24, %25, %26, %27, %28, %29, %30, %31, "
        "%32, %33, %34, %35, %36, %37, %38, %39, %40, %41, %42, %43, %44, %45, %46, %47, "
        "%48, %49, %50, %51, %52, %53, %54, %55, %56, %57, %58, %59, %60, %61, %62, %63, "
        "%64, %65, %66, %67, %68, %69, %70, %71, %72, %73, %74, %75, %76, %77, %78, %79, "
        "%80, %81, %82, %83, %84, %85, %86, %87, %88, %89, %90, %91, %92, %93, %94, %95, "
        "%96, %97, %98, %99, %100, %101, %102, %103, %104, %105, %106, %107, %108, %109, %110, %111, "
        "%112, %113, %114, %115, %116, %117, %118, %119, %120, %121, %122, %123, %124, %125, %126, %127"
        "}, %128, %129, p, 1, 1, 0, 1;\n}\n"
        : "=f"(d[0]), "=f"(d[1]), "=f"(d[2]), "=f"(d[3]), "=f"(d[4]), "=f"(d[5]), "=f"(d[6]), "=f"(d[7]),
          "=f"(d[8]), "=f"(d[9]), "=f"(d[10]), "=f"(d[11]), "=f"(d[12]), "=f"(d[13]), "=f"(d[14]), "=f"(d[15]),
          "=f"(d[16]), "=f"(d[17]), "=f"(d[18]), "=f"(d[19]), "=f"(d[20]), "=f"(d[21]), "=f"(d[22]), "=f"(d[23]),
          "=f"(d[24]), "=f"(d[25]), "=f"(d[26]), "=f"(d[27]), "=f"(d[28]), "=f"(d[29]), "=f"(d[30]), "=f"(d[31]),
          "=f"(d[32]), "=f"(d[33]), "=f"(d[34]), "=f"(d[35]), "=f"(d[36]), "=f"(d[37]), "=f"(d[38]), "=f"(d[39]),
          "=f"(d[40]), "=f"(d[41]), "=f"(d[42]), "=f"(d[43]), "=f"(d[44]), "=f"(d[45]), "=f"(d[46]), "=f"(d[47]),
          "=f"(d[48]), "=f"(d[49]), "=f"(d[50]), "=f"(d[51]), "=f"(d[52]), "=f"(d[53]), "=f"(d[54]), "=f"(d[55]),
          "=f"(d[56]), "=f"(d[57]), "=f"(d[58]), "=f"(d[59]), "=f"(d[60]), "=f"(d[61]), "=f"(d[62]), "=f"(d[63]),
          "=f"(d[64]), "=f"(d[65]), "=f"(d[66]), "=f"(d[67]), "=f"(d[68]), "=f"(d[69]), "=f"(d[70]), "=f"(d[71]),
          "=f"(d[72]), "=f"(d[73]), "=f"(d[74]), "=f"(d[75]), "=f"(d[76]), "=f"(d[77]), "=f"(d[78]), "=f"(d[79]),
          "=f"(d[80]), "=f"(d[81]), "=f"(d[82]), "=f"(d[83]), "=f"(d[84]), "=f"(d[85]), "=f"(d[86]), "=f"(d[87]),
          "=f"(d[88]), "=f"(d[89]), "=f"(d[90]), "=f"(d[91]), "=f"(d[92]), "=f"(d[93]), "=f"(d[94]), "=f"(d[95]),
          "=f"(d[96]), "=f"(d[97]), "=f"(d[98]), "=f"(d[99]), "=f"(d[100]), "=f"(d[101]), "=f"(d[102]), "=f"(d[103]),
          "=f"(d[104]), "=f"(d[105]), "=f"(d[106]), "=f"(d[107]), "=f"(d[108]), "=f"(d[109]), "=f"(d[110]), "=f"(d[111]),
          "=f"(d[112]), "=f"(d[113]), "=f"(d[114]), "=f"(d[115]), "=f"(d[116]), "=f"(d[117]), "=f"(d[118]), "=f"(d[119]),
          "=f"(d[120]), "=f"(d[121]), "=f"(d[122]), "=f"(d[123]), "=f"(d[124]), "=f"(d[125]), "=f"(d[126]), "=f"(d[127])
        : "l"(da), "l"(db));
}
__device__ __forceinline__ void wgmma_n256(float (&d)[128], uint64_t da, uint64_t db) {
    asm volatile("{\n.reg .pred p;\nsetp.eq.b32 p, 0, 0;\n"
        "wgmma.mma_async.sync.aligned.m64n256k16.f32.bf16.bf16 {"
        "%0, %1, %2, %3, %4, %5, %6, %7, %8, %9, %10, %11, %12, %13, %14, %15, "
        "%16, %17, %18, %19, %20, %21, %22, %23, %24, %25, %26, %27, %28, %29, %30, %31, "
        "%32, %33, %34, %35, %36, %37, %38, %39, %40, %41, %42, %43, %44, %45, %46, %47, "
        "%48, %49, %50, %51, %52, %53, %54, %55, %56, %57, %58, %59, %60, %61, %62, %63, "
        "%64, %65, %66, %67, %68, %69, %70, %71, %72, %73, %74, %75, %76, %77, %78, %79, "
        "%80, %81, %82, %83, %84, %85, %86, %87, %88, %89, %90, %91, %92, %93, %94, %95, "
        "%96, %97, %98, %99, %100, %101, %102, %103, %104, %105, %106, %107, %108, %109, %110, %111, "
        "%112, %113, %114, %115, %116, %117, %118, %119, %120, %121, %122, %123, %124, %125, %126, %127"
        "}, %128, %129, p, 1, 1, 0, 1;\n}\n"
        : "+f"(d[0]), "+f"(d[1]), "+f"(d[2]), "+f"(d[3]), "+f"(d[4]), "+f"(d[5]), "+f"(d[6]), "+f"(d[7]),
          "+f"(d[8]), "+f"(d[9]), "+f"(d[10]), "+f"(d[11]), "+f"(d[12]), "+f"(d[13]), "+f"(d[14]), "+f"(d[15]),
          "+f"(d[16]), "+f"(d[17]), "+f"(d[18]), "+f"(d[19]), "+f"(d[20]), "+f"(d[21]), "+f"(d[22]), "+f"(d[23]),
          "+f"(d[24]), "+f"(d[25]), "+f"(d[26]), "+f"(d[27]), "+f"(d[28]), "+f"(d[29]), "+f"(d[30]), "+f"(d[31]),
          "+f"(d[32]), "+f"(d[33]), "+f"(d[34]), "+f"(d[35]), "+f"(d[36]), "+f"(d[37]), "+f"(d[38]), "+f"(d[39]),
          "+f"(d[40]), "+f"(d[41]), "+f"(d[42]), "+f"(d[43]), "+f"(d[44]), "+f"(d[45]), "+f"(d[46]), "+f"(d[47]),
          "+f"(d[48]), "+f"(d[49]), "+f"(d[50]), "+f"(d[51]), "+f"(d[52]), "+f"(d[53]), "+f"(d[54]), "+f"(d[55]),
          "+f"(d[56]), "+f"(d[57]), "+f"(d[58]), "+f"(d[59]), "+f"(d[60]), "+f"(d[61]), "+f"(d[62]), "+f"(d[63]),
          "+f"(d[64]), "+f"(d[65]), "+f"(d[66]), "+f"(d[67]), "+f"(d[68]), "+f"(d[69]), "+f"(d[70]), "+f"(d[71]),
          "+f"(d[72]), "+f"(d[73]), "+f"(d[74]), "+f"(d[75]), "+f"(d[76]), "+f"(d[77]), "+f"(d[78]), "+f"(d[79]),
          "+f"(d[80]), "+f"(d[81]), "+f"(d[82]), "+f"(d[83]), "+f"(d[84]), "+f"(d[85]), "+f"(d[86]), "+f"(d[87]),
          "+f"(d[88]), "+f"(d[89]), "+f"(d[90]), "+f"(d[91]), "+f"(d[92]), "+f"(d[93]), "+f"(d[94]), "+f"(d[95]),
          "+f"(d[96]), "+f"(d[97]), "+f"(d[98]), "+f"(d[99]), "+f"(d[100]), "+f"(d[101]), "+f"(d[102]), "+f"(d[103]),
          "+f"(d[104]), "+f"(d[105]), "+f"(d[106]), "+f"(d[107]), "+f"(d[108]), "+f"(d[109]), "+f"(d[110]), "+f"(d[111]),
          "+f"(d[112]), "+f"(d[113]), "+f"(d[114]), "+f"(d[115]), "+f"(d[116]), "+f"(d[117]), "+f"(d[118]), "+f"(d[119]),
          "+f"(d[120]), "+f"(d[121]), "+f"(d[122]), "+f"(d[123]), "+f"(d[124]), "+f"(d[125]), "+f"(d[126]), "+f"(d[127])
        : "l"(da), "l"(db));
}

struct Idx {
    uint32_t lane, warp, w4, q4, g8, prow, pan;
    __device__ __forceinline__ Idx() {
        uint32_t t; asm volatile("mov.u32 %0, %%tid.x;" : "=r"(t));
        lane = t & 31; warp = t >> 5; w4 = warp & 3; q4 = lane & 3; g8 = lane >> 2;
        prow = w4 * 16 + ((lane >> 3) & 1) * 8 + (lane & 7);
        pan = prow * 128 + (((lane >> 4) ^ (lane & 7)) << 4);
    }
};
#define IDX() const Idx ix; const uint32_t lane = ix.lane, warp = ix.warp, w4 = ix.w4, q4 = ix.q4, g8 = ix.g8, prow = ix.prow, pan_addr = ix.pan; \
    (void)lane; (void)warp; (void)w4; (void)q4; (void)g8; (void)prow; (void)pan_addr;

__device__ __forceinline__ int kof(int t, int sh, int j) {
    const int p = t >> (sh - 1), pn = p < 2 ? p : p >= 9, q = p - 2 - 7 * pn;
    return ((p < 2 ? j : q + (q >= j)) << 7) + (pn << 6) + ((t & (sh - 1)) << 5);
}
constexpr int HC0 = 8 * 48, HC3 = HC0 + 3072;
__device__ __forceinline__ int hcol(int p, int j) { return HC0 + p * 1024 + j * 128; }
struct Ring {
    uint32_t slot, par;
    __device__ __forceinline__ void next() { if (++slot == NSLOT) { slot = 0; par ^= 1; } }
    __device__ __forceinline__ void skip(uint32_t n) { slot += n; if (slot >= NSLOT) { slot -= NSLOT; par ^= 1; } }
};
__device__ __forceinline__ uint32_t BAR_FULL(uint32_t sb, uint32_t s) { return sb + OFF_BAR + 8 * s; }
constexpr uint32_t AF_REL = 48;
__device__ __forceinline__ uint32_t BAR_EMPTY(uint32_t sb, uint32_t s) { return sb + OFF_BAR + 96 + 8 * s; }
__device__ __forceinline__ uint32_t BAR_SFULL(uint32_t sb, uint32_t i) { return sb + OFF_BAR + 152 + 8 * i; }
__device__ __forceinline__ uint32_t BAR_SREADY(uint32_t sb, uint32_t i) { return sb + OFF_BAR + 184 + 8 * i; }
__device__ __forceinline__ uint32_t BAR_ONE(uint32_t sb, uint32_t i) { return sb + OFF_BAR + 216 + 8 * i; }
enum { EV_WIN, EV_WIN1, EV_WIN2, EV_WIN3, EV_P0, EV_GA, EV_GB, EV_LN2, EV_LAG0, EV_LAG1, EV_LAG2, EV_LAG3, EV_LAG4, EV_LAG5, EV_OWN, EV_OWN1, EV_KV, EV_GO, EV_PAR, EV_AGO, EV_AGO1, EV_AGO2, EV_FGO, EV_FGO1, EV_FGO2, EV_H0, EV_H1, EV_H2, EV_H3, EV_COUNT };
constexpr int NB_TAIL = 4;

struct Rel {
    uint32_t base; bool sig;
    __device__ __forceinline__ Rel(uint32_t sb, uint32_t tw) {
        uint32_t a; asm("mapa.shared::cluster.u32 %0, %1, %2;" : "=r"(a) : "r"(BAR_EMPTY(sb, 0)), "r"((tw >> 5) & 1));
        base = __shfl_sync(0xffffffffu, a, 0); sig = (tw & ~32u) == 0;
    }
    __device__ __forceinline__ void operator()(uint32_t slot) const {
        if (sig) asm volatile("mbarrier.arrive.shared::cluster.b64 _, [%0];" :: "r"(base + 8 * slot) : "memory");
    }
};
struct LnRow { float rs0, nm0, rs1, nm1; };
struct Pipe {
    Rel rel; uint32_t p1, p2;
    __device__ __forceinline__ Pipe(uint32_t sb, uint32_t tw, uint32_t first) : rel(sb, tw), p1(first), p2(NSLOT) {}
    template <bool TWO> __device__ __forceinline__ void acquire(uint32_t sb, uint32_t af, const Ring& r) {
        const uint32_t b0 = BAR_FULL(sb, r.slot), b1 = b0 + af;
        const bool ready = TWO ? mbar_test2(b0, b1, r.par) : mbar_test(b0, r.par);
        wg_wait<1>();
        rel(p2);
        if (!ready) { if (TWO) mbar_wait2(b0, b1, r.par); else mbar_wait(b0, r.par); }
    }
    __device__ __forceinline__ void issued(uint32_t slot) { p2 = p1; p1 = slot; }
    __device__ __forceinline__ void drain1() { wg_wait<1>(); rel(p2); p2 = NSLOT; }
    __device__ __forceinline__ void drain0() { wg_wait<0>(); rel(p1); p1 = NSLOT; }
    template <bool TWO, class Step> __device__ __forceinline__ void hold(int LG, uint32_t sb, uint32_t af, Ring& r, uint32_t lag_bar, Step step) {
        Ring q = r;
#pragma unroll 1
        for (int i = 0; i < LG; ++i) { if (TWO) mbar_wait2(BAR_FULL(sb, q.slot), BAR_FULL(sb, q.slot) + af, q.par); else mbar_wait(BAR_FULL(sb, q.slot), q.par); q.next(); }
        mbar_wait(lag_bar, 0);
#pragma unroll 1
        do {
            step(r.slot);
            wg_wait<2>(); rel(p2); p2 = p1; p1 = r.slot;
            if (++r.slot == NSLOT) r.slot = 0;
        } while (r.slot != q.slot);
        r.par = q.par;
    }
};
template <bool TWO, bool FIRST, int NA, int NB>
__device__ __forceinline__ void step32(float (&aa)[NA], float (&ab)[NB], uint32_t sb, uint32_t wg, uint32_t slot, int own) {
    const uint32_t st = d16(sb) + slot * (SLOT >> 4);
    const uint32_t alo = own >= 0 ? d16(sb) + OFF_STG / 16 + wg * 1024 + (own >> 1) * 512 + (own & 1) * 4 : st + wg * 256;
    const uint32_t ahi = own >= 0 ? (1024 >> 4) | (1u << 30) : (512 >> 4) | (2u << 30);
    wg_fence();
#pragma unroll
    for (int k = 0; k < 2; ++k) {
        const uint64_t da = ((uint64_t)ahi << 32) | (alo + k * 2 + 0x10000);
        if constexpr (NA == 88) {
            const uint64_t d0 = mk_desc(st, 8192 + k * 2048, 8192, 1024, 1), d1 = mk_desc(st, 12288 + k * 2048, 8192, 1024, 1);
            if (FIRST && k == 0) { wgmma_n176_z(aa, da, d0); wgmma_n176_z(ab, da, d1); }
            else { wgmma_n176(aa, da, d0); wgmma_n176(ab, da, d1); }
        } else {
            const uint64_t d0 = mk_desc(st, 8192 + k * 2048, 4096, 1024, 1), d1 = mk_desc(st, 24576 + k * 2048, 4096, 1024, 1);
            if (FIRST && k == 0) { wgmma_n256_z(aa, da, d0); if constexpr (TWO) wgmma_n128_z(ab, da, d1); }
            else { wgmma_n256(aa, da, d0); if constexpr (TWO) wgmma_n128(ab, da, d1); }
        }
    }
    wg_commit();
}
template <bool TWO, int LG, int NA, int NB, class Tail>
__device__ __forceinline__ void mainloop32(float (&aa)[NA], float (&ab)[NB], uint32_t sb, uint32_t wg, uint32_t tw, Ring& r, uint32_t lag_ev, int g0, Tail tail) {
    mbar_wait(BAR_FULL(sb, r.slot), r.par);
    step32<TWO, true>(aa, ab, sb, wg, r.slot, TWO ? 0 : -1);
    TS(g0, 0);
    Pipe pp(sb, tw, r.slot);
    r.next();
    const int end = wg ? 32 : 32 - LG;
#pragma unroll 1
    for (int it = 1; it < end; ++it) {
        pp.acquire<TWO>(sb, wg ? 0 : AF_REL, r);
        step32<TWO, false>(aa, ab, sb, wg, r.slot, TWO && it < 4 ? it : -1);
        pp.issued(r.slot);
        TS(g0 + it, 0);
        r.next();
    }
    if (wg == 0) { pp.drain1(); pp.drain0(); pp.hold<TWO>(LG, sb, AF_REL, r, BAR_ONE(sb, lag_ev), [&](uint32_t slot) { step32<TWO, false>(aa, ab, sb, 0, slot, -1); }); }
    pp.drain1();
    if (wg == 1 && tw == 0) mbar_arrive(BAR_ONE(sb, lag_ev));
    tail();
    pp.drain0();
    TS(g0 + 31, 1);
}
template <bool FIRST>
__device__ __forceinline__ void step64(float (&acc)[64], uint32_t sb, uint32_t wg, uint32_t slot, int own) {
    const uint32_t sbb = d16(sb) + slot * (SLOT >> 4), sa = own >= 0 ? d16(sb) + OFF_STG / 16 + wg * 1024 + own * 512 : sbb + wg * 512;
    wg_fence();
#pragma unroll
    for (int k = 0; k < 4; ++k) {
        const uint64_t da = mk_desc(sa, k * 32, 16, 1024, 1), db = mk_desc(sbb, 16384 + k * 2048, 8192, 1024, 1);
        if (FIRST && k == 0) wgmma_n128_z(acc, da, db); else wgmma_n128(acc, da, db);
    }
    wg_commit();
}
template <class Mid>
__device__ __forceinline__ void mainloop64(float (&acc)[64], bool wo, uint32_t sb, uint32_t wg, uint32_t tw, Ring& r, Mid mid) {
    const int g0 = wo ? 32 : 144, nst = wo ? 16 : 56, lg = wo ? LAGW : LAGD; (void)g0;
    const uint32_t lag_bar = BAR_ONE(sb, wo ? EV_LAG4 : EV_LAG5), af = wo && !wg ? AF_REL : 0;
    mbar_wait(BAR_FULL(sb, r.slot), r.par);
    if (!wo) CS(28);
    step64<true>(acc, sb, wg, r.slot, wo ? 0 : -1);
    if (!wo) CS(29);
    TS(g0, 0);
    Pipe pp(sb, tw, r.slot);
    r.next();
    int it = 1;
    auto run = [&](int end, int own) {
#pragma unroll 1
        do {
            pp.acquire<true>(sb, af, r);
            step64<false>(acc, sb, wg, r.slot, own);
            pp.issued(r.slot);
            TS(g0 + it, 0);
            r.next();
            if (own > 0) {
                own = -1;
                pp.drain1(); pp.drain0();
                TS(g0 + 1, 1);
                if (tw == 0) mbar_arrive(BAR_ONE(sb, EV_OWN + wg));
            }
        } while (++it < end);
    };
    run(wg ? (wo ? MIDW : MIDD) : nst - lg, wo ? 1 : -1);
    mid();
    if (wg) run(nst, -1);
    else { pp.drain1(); pp.drain0(); pp.hold<true>(lg, sb, af, r, lag_bar, [&](uint32_t slot) { step64<false>(acc, sb, 0, slot, -1); }); }
    pp.drain1();
    if (wg == 1 && tw == 0) mbar_arrive(lag_bar);
    pp.drain0();
    TS(g0 + nst - 1, 1);
}

struct RowAcc {
    float sm[4] = {0.f, 0.f, 0.f, 0.f}, sq[4] = {0.f, 0.f, 0.f, 0.f};
    __device__ __forceinline__ void add(int e, float x) { sm[e & 3] += x; sq[e & 3] = fmaf(x, x, sq[e & 3]); }
    __device__ __forceinline__ void publish(uint4* dst, uint32_t q4, uint32_t ep) const {
        const float s0 = sm[0] + sm[1], s1 = sm[2] + sm[3], q0 = sq[0] + sq[1], q1 = sq[2] + sq[3];
        const bool od = q4 & 1;
        float sv = (od ? s1 : s0) + __shfl_xor_sync(0xffffffffu, od ? s0 : s1, 1), qv = (od ? q1 : q0) + __shfl_xor_sync(0xffffffffu, od ? q0 : q1, 1);
        sv += __shfl_xor_sync(0xffffffffu, sv, 2); qv += __shfl_xor_sync(0xffffffffu, qv, 2);
        if (q4 < 2) st_pkt16(dst + q4 * 8, 0, __float_as_uint(sv), __float_as_uint(qv), ep);
    }
};
__device__ __forceinline__ LnRow merge_stats(const uint4* src, uint32_t q4, uint32_t ep, uint32_t sb) {
    uint4 t[4];
    uint32_t n = 0;
    while (true) {
#pragma unroll
        for (int i = 0; i < 4; ++i) t[i] = ld_pkt16(src + (q4 * 2 + (i >> 1)) * 512 + (i & 1) * 8);
        const bool ok_ = __all_sync(0xffffffffu, t[0].w == ep && t[1].w == ep && t[2].w == ep && t[3].w == ep);
        if (n < 4) CS(14 + n);
        if (ok_) break;
        SPIN_GUARD(n);
    }
    float v[4];
#pragma unroll
    for (int h = 0; h < 2; ++h) { v[h] = __uint_as_float(t[h].y) + __uint_as_float(t[2 + h].y); v[2 + h] = __uint_as_float(t[h].z) + __uint_as_float(t[2 + h].z); }
#pragma unroll
    for (int o = 1; o < 4; o <<= 1)
#pragma unroll
        for (int i = 0; i < 4; ++i) v[i] += __shfl_xor_sync(0xffffffffu, v[i], o);
    const float m0 = v[0] * (1.f / D_), m1 = v[1] * (1.f / D_);
    const float r0 = rsqrtf(fmaxf(fmaf(-m0, m0, v[2] * (1.f / D_)), 0.f) + 1e-5f), r1 = rsqrtf(fmaxf(fmaf(-m1, m1, v[3] * (1.f / D_)), 0.f) + 1e-5f);
    return LnRow{r0, -m0 * r0, r1, -m1 * r1};
}
struct Stg {
    uint32_t b, par;
    __device__ __forceinline__ uint32_t acquire2(uint32_t sb, uint32_t wg) {
        mbar_wait(BAR_SREADY(sb, wg * 2), par & 1);
        mbar_wait(BAR_SREADY(sb, wg * 2 + 1), (par >> 1) & 1);
        par ^= 3;
        return sb + OFF_STG + wg * 16384;
    }
    __device__ __forceinline__ void publish(uint32_t sb, uint32_t wg, uint32_t lane) {
        fence_async_smem();
        __syncwarp();
        if (lane == 0) mbar_arrive(BAR_SFULL(sb, wg * 2 + b));
        b ^= 1;
    }
};

struct LnPar {
    uint4 p[8];
    __device__ __forceinline__ void load(uint32_t sb, uint32_t q4) {
#pragma unroll
        for (int i = 0; i < 8; ++i) p[i] = lds128(sb + OFF_PAR + i * 64 + q4 * 16);
    }
};
__device__ __forceinline__ void ln_norm(uint32_t (&xn)[32], const float (&x)[64], const LnRow& n) {
#pragma unroll
    for (int e = 0; e < 32; ++e) {
        const float rs = (e & 1) ? n.rs1 : n.rs0, nm = (e & 1) ? n.nm1 : n.nm0;
        xn[e] = pack2(fmaf(x[2 * e], rs, nm), fmaf(x[2 * e + 1], rs, nm));
    }
}
__device__ __forceinline__ void ln_emit(const uint32_t (&xr)[32], const LnPar& lp, uint32_t sb, uint32_t wg, const Idx& ix) {
#pragma unroll
    for (int i = 0; i < 8; ++i)
        stsm4(sb + OFF_STG + wg * 16384 + (i >> 2) * 8192 + (ix.pan ^ ((i & 3) << 5)), hfma2_bf16(xr[4 * i], lp.p[i].z, lp.p[i].x), hfma2_bf16(xr[4 * i + 1], lp.p[i].z, lp.p[i].x),
              hfma2_bf16(xr[4 * i + 2], lp.p[i].w, lp.p[i].y), hfma2_bf16(xr[4 * i + 3], lp.p[i].w, lp.p[i].y));
    fence_async_smem();
    __syncwarp();
    if (ix.lane < 2) mbar_arrive(BAR_SFULL(sb, wg * 2 + ix.lane));
    bar_sync(1 + wg, 128);
}
__device__ __forceinline__ void load_slab(uint32_t (&xr)[32], uint32_t buf) {
    IDX();
#pragma unroll
    for (int i = 0; i < 8; ++i) ldsm4(buf + (i >> 2) * 8192 + (pan_addr ^ ((i & 3) << 5)), xr[4 * i], xr[4 * i + 1], xr[4 * i + 2], xr[4 * i + 3]);
}
__device__ __forceinline__ void unpack_slab(float (&x)[64], const uint32_t (&xr)[32]) {
#pragma unroll
    for (int i = 0; i < 32; ++i) unpack2(xr[i], x[2 * i], x[2 * i + 1]);
}
__device__ __forceinline__ void store_slab(const float (&x)[64], uint32_t buf, uint32_t pitch, uint32_t pan, int i0, int i1) {
#pragma unroll
    for (int i = i0; i < i1; ++i)
        stsm4(buf + (i >> 2) * pitch + (pan ^ ((i & 3) << 5)), pack2(x[8 * i], x[8 * i + 1]), pack2(x[8 * i + 2], x[8 * i + 3]), pack2(x[8 * i + 4], x[8 * i + 5]), pack2(x[8 * i + 6], x[8 * i + 7]));
}
__device__ __forceinline__ void fetch_halo(uint4* src, bool first, uint32_t sb, uint32_t W, uint32_t lane) {
    mbar_wait(BAR_ONE(sb, EV_KV), 0);
    mbar_wait2(BAR_SREADY(sb, 0), BAR_SREADY(sb, 1), 1);
    uint4 hv[8];
    uint32_t n = 0;
    while (true) {
        bool ok = true;
#pragma unroll
        for (int i = 0; i < 8; ++i) { hv[i] = first ? make_uint4(0, 0, 0, 0) : ld_pkt16(src + i * 32); ok = ok && hv[i].x != 0; }
        if (first || __all_sync(0xffffffffu, ok)) break;
        SPIN_GUARD(n);
    }
#pragma unroll
    for (int i = 0; i < 8; ++i) stsm4(sb + OFF_STG + W * 2048 + (i >> 2) * 8192 + (i & 3) * 512 + lane * 16, hv[i].x, hv[i].y, hv[i].z, hv[i].w);
    bar_arrive(NB_TAIL + W, 64);
    if (!first) {
#pragma unroll
        for (int i = 0; i < 8; ++i) src[i * 32] = make_uint4(0, 0, 0, 0);
    }
}

template <int NG, class G, class U, class Buf>
__device__ __forceinline__ void glu(uint32_t sb, uint32_t wg, G g, U u, Buf buf) {
    IDX();
#pragma unroll
    for (int k = 0; k < NG; ++k) {
        float h[8];
#pragma unroll
        for (int e = 0; e < 8; ++e) h[e] = fmaf(tanh_(g(8 * k + e)), u(8 * k + e), u(8 * k + e));
        stsm4(buf(k >> 2) + (pan_addr ^ ((k & 3) << 5)), pack2(h[0], h[1]), pack2(h[2], h[3]), pack2(h[4], h[5]), pack2(h[6], h[7]));
    }
    fence_async_smem();
    __syncwarp();
    if (lane < 2) mbar_arrive(BAR_SFULL(sb, wg * 2 + lane));
}

template <int NP>
__device__ __forceinline__ void passes128(uint32_t sb, uint32_t wg, uint32_t tw, Ring& r, Stg& stg) {
#pragma unroll 1
    for (int p = 0; p < NP; ++p) {
        float b256[128], none[1];
        mainloop32<false, LAGS>(b256, none, sb, wg, tw, r, EV_LAG2 + p, 80 + 32 * (p & 1), [&] { stg.acquire2(sb, wg); });
        if (threadIdx.x == 0) { TL(29 + 2 * p); TC(114 + 2 * p); }
        if (threadIdx.x == 128) TL(53 + 2 * (p & 1));
        CS(24 + 2 * (p & 1));
        glu<8>(sb, wg, [&](int i) { return b256[i + (i & 32)]; }, [&](int i) { return b256[i + (i & 32) + 32]; }, [&](int pn) { return sb + OFF_STG + wg * 16384 + pn * 8192; });
        if (threadIdx.x == 0) { TL(30 + 2 * p); TC(115 + 2 * p); }
        if (threadIdx.x == 128) TL(54 + 2 * (p & 1));
        CS(25 + 2 * (p & 1));
    }
}

__global__ void __launch_bounds__(384, 1)
fused_block_kernel(const __grid_constant__ Ptrs pt, const __grid_constant__ Maps mp) {
    uint32_t* const g_flags = pt.mail->flags;
    uint2* const g_mod = pt.mail->mod;
    uint4* const g_st1 = pt.mail->st1;
    uint32_t* const g_par2 = pt.mail->par2;
    uint4* const g_halo = pt.mail->halo;
    const __nv_bfloat16* __restrict__ cvec = pt.c;
    if (threadIdx.x == 224) { prefetch_map(&mp.wm8); prefetch_map(&mp.x); }
    extern __shared__ __align__(1024) uint8_t smem[];
    const uint32_t sb = smem_u32(smem);
    const uint32_t tid = threadIdx.x, tw = tid & 127, lane = tid & 31;
    const uint32_t warp = __shfl_sync(0xffffffffu, tid >> 5, 0), wg = warp >> 2;
    uint32_t rank; asm("mov.u32 %0, %%cluster_ctarank;" : "=r"(rank));
    rank = __shfl_sync(0xffffffffu, rank, 0);
    uint32_t ep;
    uint32_t smid; asm volatile("mov.u32 %0, %%smid;" : "=r"(smid));
    const int c = __shfl_sync(0xffffffffu, smid >> 1, 0);
    const int c7 = ((c - 32) * 37) >> 8;
    const int grp = c < 32 ? c & 7 : c < 60 ? c - 31 - 7 * c7 : c < 62 ? -1 : 0;
    const int j = c < 32 ? c >> 3 : c < 60 ? 4 + c7 : c < 62 ? (c - 60) * 2 + rank : c - 58;
    const bool aux = grp < 0;
    const int m = grp * 2 + rank;
    uint4* const g_st2 = g_halo + (m > 0 ? (m - 1) * 8 * 512 : 128);

    bool cluster_arrive_early = false;
    if (wg < 2) {
      if (!KDEBUG) cluster_arrive();
      ep = flag_get(g_flags + FL_DONE);
      uint16_t cw[8];
      {
          const __nv_bfloat16* cp = cvec + ((tw >> 5) * 32 + (tw & 3) * 2) * 8 + (lane >> 2);
#pragma unroll
          for (int i = 0; i < 8; ++i) asm volatile("ld.global.nc.u16 %0, [%1];" : "=h"(cw[i]) : "l"(cp + (i >> 1) * 64 + (i & 1) * 8));
      }
      asm volatile("setmaxnreg.inc.sync.aligned.u32 224;");
      if (tid == 0) TL(58);
      if (KDEBUG) cluster_arrive();
      Ring r{0, 0};
      Stg stg{0, 0};
      if (aux) {
        if (wg == 0) {
            const uint4 cv = *(const uint4*)(cvec + tw * 8);
            sts128(sb + OFF_STG + (tw >> 3) * 1024 + (tw & 7) * 16, pack2(silu_(bf_lo(cv.x)), silu_(bf_hi(cv.x))), pack2(silu_(bf_lo(cv.y)), silu_(bf_hi(cv.y))),
                   pack2(silu_(bf_lo(cv.z)), silu_(bf_hi(cv.z))), pack2(silu_(bf_lo(cv.w)), silu_(bf_hi(cv.w))));
            fence_async_smem();
        }
        cluster_wait();
        ep = __shfl_sync(0xffffffffu, ep, 0) / NCTA + 1;
        if (wg == 0) {
            if (tw == 0) {
                uint32_t n = 0;
                while (ld_pkt16(pt.mail->mod1 + 256).z != ep) { SPIN_GUARD(n); __nanosleep(200); }
                if (GODLY) __nanosleep(GODLY);
                mbar_arrive(BAR_ONE(sb, EV_GO));
            }
            bar_sync(1, 128);
#pragma unroll 1
            for (int p = 0; p < 4; ++p) {
                float acc[128];
#pragma unroll
                for (int i = 0; i < 128; ++i) acc[i] = 0.f;
                uint32_t prev = 0;
#pragma unroll 1
                for (int kc = 0; kc < 16; ++kc) {
                    mbar_wait(BAR_FULL(sb, r.slot), r.par);
                    wg_fence();
#pragma unroll
                    for (int k = 0; k < 4; ++k)
                        wgmma_n256(acc, mk_desc(d16(sb) + kc * 64, OFF_STG + k * 32, 16, 0, 1), mk_desc(d16(sb) + r.slot * (SLOT >> 4), k * 2048, 8192, 1024, 1));
                    wg_commit();
                    wg_wait<1>();
                    if (kc > 0 && tw < 4) mbar_arrive(BAR_EMPTY(sb, prev));
                    prev = r.slot;
                    r.next();
                }
                wg_wait<0>();
                if (tw < 4) mbar_arrive(BAR_EMPTY(sb, prev));
                if (tw < 4) {
#pragma unroll
                    for (int jn = 0; jn < 32; ++jn) sts32(sb + OFF_TAB + (jn * 4 + tw) * 4, pack2(acc[jn * 4], acc[jn * 4 + 1]));
                }
                bar_sync(1, 128);
                const int vec = 2 + p, blk = p * 4 + j;
                const uint32_t val = lds32(sb + OFF_TAB + tw * 4);
                if (vec == 2 || vec == 5) st_pkt(g_mod + (8 + blk) * 128 + tw, val, ep);
                else {
                    const float one = vec == 4 ? 1.f : 0.f;
                    g_par2[((blk & 3) * 16 + (tw >> 3)) * 16 + (tw & 3) * 4 + (vec - 3) * 2 + ((tw >> 2) & 1)] =
                        pack2(0.5f * bf_round(one + bf_lo(val)), 0.5f * bf_round(one + bf_hi(val)));
                }
                bar_sync(1, 128);
                if (tw == 0) {
                    if (vec == 3 || vec == 4) asm volatile("red.release.gpu.global.add.u32 [%0], 1;" :: "l"(&g_flags[FL_LN2]) : "memory");
                    TL(1 + p);
                }
            }
            if (lane < 2) mbar_arrive_cta(BAR_ONE(sb, EV_P0), lane);
        }
        r = Ring{64 % NSLOT, (64 / NSLOT) & 1};
        mbar_wait(BAR_ONE(sb, EV_P0), 0);
        passes128<4>(sb, wg, tw, r, stg);
      } else {
        float xs[64];
        uint32_t xp[32];
        {
            IDX();
            if (q4 < 2) st_pkt16(g_st1 + (m * 8 + j) * 512 + wg * 64 + w4 * 16 + g8 + q4 * 8, 0, 0, 0, 0);
            if (warp == 0) st_pkt16(pt.mail->mod1 + g8 * 512 + (m * 8 + j) * 4 + q4, 0, 0, 0, 0);
            sts128(sb + tid * 16, pack2(silu_(bf_lo(cw[0])), silu_(bf_lo(cw[1]))), pack2(silu_(bf_lo(cw[2])), silu_(bf_lo(cw[3]))),
                   pack2(silu_(bf_lo(cw[4])), silu_(bf_lo(cw[5]))), pack2(silu_(bf_lo(cw[6])), silu_(bf_lo(cw[7]))));
            cluster_wait();
            ep = __shfl_sync(0xffffffffu, ep, 0) / NCTA + 1;
            load_slab(xp, stg.acquire2(sb, wg));
            unpack_slab(xs, xp);
            if (tid == 0) TL(24);
            if (tid == 128) TL(27);
        }
#pragma unroll 1
        for (int blk = 0; ; ++blk) {
        {
            IDX();
            uint4* const st = (blk ? g_st2 : g_st1 + m * 8 * 512) + wg * 64 + w4 * 16 + g8;
            RowAcc ra;
#pragma unroll
            for (int e = 0; e < 64; ++e) ra.add(e, xs[e]);
            ra.publish(st + j * 512, q4, ep);
            uint32_t t_pub = 0; if (PDLY) asm volatile("mov.u32 %0, %%clock;" : "=r"(t_pub));
            if (tid == 0) TL(blk ? 9 : 26);
            if (tid == 128 && blk) TL(34);
            if (blk) CS(11);
            LnPar lp;
            if (blk == 0) {
            uint4* const mod_out = pt.mail->mod1 + g8 * 512 + (m * 8 + j) * 4 + q4;
            if (wg == 0) {
                uint4 af[8];
#pragma unroll
                for (int i = 0; i < 8; ++i) af[i] = lds128(sb + w4 * 512 + i * 64 + q4 * 16);
                float c[4][4] = {};
#pragma unroll
                for (int i = 0; i < 8; ++i) {
                    if (!(i & 1)) mbar_wait(BAR_ONE(sb, EV_WIN + (i >> 1)), 0);
                    if (i == 6 && tid == 0) TL(25);
#pragma unroll
                    for (int h = 0; h < 2; ++h) {
                        uint32_t b0, b1, b2, b3;
                        ldsm4t(sb + 5 * SLOT + i * 4096 + w4 * 1024 + h * 512 + (lane & 15) * 32 + (lane >> 4) * 16, b0, b1, b2, b3);
                        mma16816(c[2 * h], h ? af[i].z : af[i].x, 0u, h ? af[i].w : af[i].y, 0u, b0, b1);
                        mma16816(c[2 * h + 1], h ? af[i].z : af[i].x, 0u, h ? af[i].w : af[i].y, 0u, b2, b3);
                    }
                }
                if (lane < 4) sts128(sb + OFF_TAB + w4 * 64 + lane * 16, __float_as_uint(c[0][0] + c[2][0]), __float_as_uint(c[0][1] + c[2][1]),
                                     __float_as_uint(c[1][0] + c[3][0]), __float_as_uint(c[1][1] + c[3][1]));
                if (lane < 2) mbar_arrive_cta(BAR_ONE(sb, EV_P0), lane);
                bar_sync(1, 128);
                if (w4 == 0) {
                    float a[4] = {0.f, 0.f, 0.f, 0.f};
#pragma unroll
                    for (int i = 0; i < 4; ++i) {
                        const uint4 t = lds128(sb + OFF_TAB + i * 64 + q4 * 16);
                        a[0] += __uint_as_float(t.x); a[1] += __uint_as_float(t.y); a[2] += __uint_as_float(t.z); a[3] += __uint_as_float(t.w);
                    }
                    const float add = m >= 8 ? 1.f : 0.f;
                    st_pkt16(mod_out, pack2(bf_round(a[0]) + add, bf_round(a[1]) + add), pack2(bf_round(a[2]) + add, bf_round(a[3]) + add), ep, 0);
                    if (tid == 0) TL(3);
                }
            } else if (LWAIT >= 0) mbar_wait(BAR_ONE(sb, EV_WIN + LWAIT), 0);
            } else {
                mbar_wait(BAR_ONE(sb, EV_LN2), 0);
            }
            lp.load(sb, q4);
#pragma unroll
            for (int e = 0; e < 32; ++e) xp[e] = pack2(xs[2 * e], xs[2 * e + 1]);
            if (PDLY && blk) { uint32_t t1; do { asm volatile("mov.u32 %0, %%clock;" : "=r"(t1)); } while (t1 - t_pub < PDLY); }
            if (blk) CS(13);
            const LnRow n = merge_stats(st, q4, ep, sb);
            if (tid == 0) TL(blk ? 49 : 48);
            if (tid == 128) TL(blk ? 45 : 28);
            if (blk) CS(18);
            uint32_t xn[32];
            ln_norm(xn, xs, n);
            if (blk == 0) { mbar_wait(BAR_ONE(sb, EV_PAR), 0); lp.load(sb, q4); }
            ln_emit(xn, lp, sb, wg, ix);
            if (tid == 0) { TL(blk ? 36 : 8); TC(blk ? 109 : 103); }
            if (tid == 128) TL(blk ? 43 : 22);
            if (blk) CS(21);
        }
        if (blk == 0) {
        {
            float kv[128], qa[64];
            mbar_wait(BAR_FULL(sb, r.slot), r.par);
            step32<true, true>(kv, qa, sb, wg, r.slot, 0);
            TS(0, 0);
            Pipe pp(sb, tw, r.slot);
            r.next();
#pragma unroll 1
            for (int it = 1; it < 32 - LAGQ; ++it) {
                pp.acquire<true>(sb, wg ? 0 : AF_REL, r);
                step32<true, false>(kv, qa, sb, wg, r.slot, it < 4 ? it : -1);
                pp.issued(r.slot);
                TS(it, 0);
                r.next();
            }
            auto half = [&](uint32_t slot, bool q) {
                const uint32_t st = d16(sb) + slot * (SLOT >> 4);
#pragma unroll
                for (int k = 0; k < 2; ++k) {
                    const uint64_t da = mk_desc(st + wg * 256, k * 32, 16, 512, 2);
                    if (q) wgmma_n128(qa, da, mk_desc(st, 24576 + k * 2048, 4096, 1024, 1)); else wgmma_n256(kv, da, mk_desc(st, 8192 + k * 2048, 4096, 1024, 1));
                }
            };
            auto part = [&](bool q) {
                wg_fence();
#pragma unroll
                for (int it = 32 - LAGQ; it < 32; ++it) half(it % NSLOT, q);
                wg_commit();
            };
            stg.acquire2(sb, wg); mbar_wait2(BAR_SREADY(sb, 2), BAR_SREADY(sb, 3), 1);
            if (wg == 0) { pp.drain1(); pp.drain0(); }
#pragma unroll 1
            for (int it = 32 - LAGQ; it < 32; ++it) {
                pp.acquire<true>(sb, wg ? 0 : AF_REL, r);
                if (wg) { wg_fence(); half(r.slot, false); wg_commit(); }
                pp.issued(NSLOT);
                TS(it, 0);
                r.next();
            }
            if (wg == 0) { mbar_wait(BAR_ONE(sb, EV_LAG0), 0); part(false); part(true); wg_wait<1>(); }
            else { wg_wait<1>(); if (tw == 0) mbar_arrive(BAR_ONE(sb, EV_LAG0)); wg_wait<0>(); }
            CS(8);
            IDX();
            uint32_t k1[16], k2[16], v1[16], v2[16], qf[32];
#pragma unroll
            for (int i = 0; i < 128; ++i) asm volatile("" : "+f"(kv[i]) :: "memory");
#pragma unroll
            for (int t = 0; t < 16; ++t) k2[t] = pack2(kv[4 * t + 2], kv[4 * t + 3]);
#pragma unroll
            for (int t = 0; t < 16; ++t) k1[t] = pack2(kv[4 * t], kv[4 * t + 1]);
#pragma unroll
            for (int t = 0; t < 16; ++t) v2[t] = pack2(kv[64 + 4 * t + 2], kv[64 + 4 * t + 3]);
            const uint32_t nxt = warp + ((warp & 1) ? 3 : 1);
            if (nxt < 8) {
                const uint32_t dst = sb + OFF_STG + (nxt >> 2) * 16384 + (nxt & 3) * 2048 + lane * 16;
#pragma unroll
                for (int h = 0; h < 4; ++h) stsm4(dst + h * 512, k2[4 * h], k2[4 * h + 1], k2[4 * h + 2], k2[4 * h + 3]);
#pragma unroll
                for (int h = 0; h < 4; ++h) stsm4(dst + 8192 + h * 512, v2[4 * h], v2[4 * h + 1], v2[4 * h + 2], v2[4 * h + 3]);
                bar_arrive(NB_TAIL + nxt, 64);
            } else if (m < 15) {
                uint4* dst = g_halo + (m * 8 + j) * 512 + (w4 >> 1) * 256 + lane;
#pragma unroll
                for (int h = 0; h < 4; ++h) { if (!k2[4 * h]) k2[4 * h] = 0x8000u; if (!v2[4 * h]) v2[4 * h] = 0x8000u; }
#pragma unroll
                for (int h = 0; h < 4; ++h) st_pkt16(dst + h * 32, k2[4 * h], k2[4 * h + 1], k2[4 * h + 2], k2[4 * h + 3]);
#pragma unroll
                for (int h = 0; h < 4; ++h) st_pkt16(dst + 128 + h * 32, v2[4 * h], v2[4 * h + 1], v2[4 * h + 2], v2[4 * h + 3]);
            }
#pragma unroll
            for (int t = 0; t < 16; ++t) { v1[t] = pack2(kv[64 + 4 * t], kv[64 + 4 * t + 1]); v1[t] = movm(v1[t]); v2[t] = movm(v2[t]); }
            if (tid == 0) TL(33);
            CS(2);
            if (wg) part(true);
            bar_sync(NB_TAIL + warp, 64);
            CS(4);
            if (tid == 0) TL(5);
            uint32_t k0[16], v0[16];
            const uint32_t mine = sb + OFF_STG + wg * 16384 + w4 * 2048;
#pragma unroll
            for (int h = 0; h < 4; ++h) ldsm4(mine + lane * 16 + h * 512, k0[4 * h], k0[4 * h + 1], k0[4 * h + 2], k0[4 * h + 3]);
#pragma unroll
            for (int h = 0; h < 4; ++h) ldsm4t(mine + lane * 16 + 8192 + h * 512, v0[4 * h], v0[4 * h + 1], v0[4 * h + 2], v0[4 * h + 3]);
            wg_wait<0>();
#pragma unroll
            for (int it = 32 - LAGQ; it < 32; ++it) pp.rel(it % NSLOT);
            TS(31, 1);
            if (tid == 0) { TL(4); TC(104); }
            if (tid == 128) TL(50);
            CS(1);
#pragma unroll
            for (int i = 0; i < 64; ++i) asm volatile("" : "+f"(qa[i]) :: "memory");
            const bool lo0 = q4 * 2 > g8, lo1 = q4 * 2 + 1 > g8;
            const bool nopast = m == 0 && (warp & 5) == 0;
            const uint32_t lomask = (lo0 ? 0xFFFFu : 0u) | (lo1 ? 0xFFFF0000u : 0u);
            const uint32_t orow = mine + (lane & 7) * 128 + (((lane >> 3) ^ (lane & 7)) << 4);
            const float sl2 = 0.17677669529663687f * 1.4426950408889634f;
#pragma unroll
            for (int pn = 0; pn < 2; ++pn) {
                float e0[4], e1[4], mx[4], sum[4];
#pragma unroll
                for (int hh = 0; hh < 2; ++hh) {
                    const int h = pn * 2 + hh;
#pragma unroll
                    for (int i = 8 * h; i < 8 * h + 8; ++i) qf[i] = pack2(qa[2 * i], qa[2 * i + 1]);
                    float s[3][4];
#pragma unroll
                    for (int t = 0; t < 3; ++t) {
                        const uint32_t* k = (t == 0 ? k0 : t == 1 ? k1 : k2) + 4 * h;
                        s[t][0] = s[t][1] = s[t][2] = s[t][3] = 0.f;
                        mma16816(s[t], qf[h * 8], qf[h * 8 + 1], qf[h * 8 + 2], qf[h * 8 + 3], k[0], k[1]);
                        mma16816(s[t], qf[h * 8 + 4], qf[h * 8 + 5], qf[h * 8 + 6], qf[h * 8 + 7], k[2], k[3]);
                    }
#pragma unroll
                    for (int hf = 0; hf < 2; ++hf) {
                        const int u = hh * 2 + hf;
                        e0[u] = lo0 ? ((hf == 0 && nopast) ? -INFINITY : s[hf][hf * 2]) : s[hf + 1][hf * 2];
                        e1[u] = lo1 ? ((hf == 0 && nopast) ? -INFINITY : s[hf][hf * 2 + 1]) : s[hf + 1][hf * 2 + 1];
                        mx[u] = fmaxf(e0[u], e1[u]);
                    }
                }
#pragma unroll
                for (int o = 1; o < 4; o <<= 1)
#pragma unroll
                    for (int u = 0; u < 4; ++u) mx[u] = fmaxf(mx[u], __shfl_xor_sync(0xffffffffu, mx[u], o));
#pragma unroll
                for (int u = 0; u < 4; ++u) {
                    const float c = -mx[u] * sl2;
                    e0[u] = ex2(fmaf(e0[u], sl2, c)); e1[u] = ex2(fmaf(e1[u], sl2, c));
                    sum[u] = e0[u] + e1[u];
                }
#pragma unroll
                for (int o = 1; o < 4; o <<= 1)
#pragma unroll
                    for (int u = 0; u < 4; ++u) sum[u] += __shfl_xor_sync(0xffffffffu, sum[u], o);
#pragma unroll
                for (int u = 0; u < 4; ++u) {
                    const int h = pn * 2 + (u >> 1);
                    const float inv = rcp(sum[u]);
                    const uint32_t p = pack2(e0[u] * inv, e1[u] * inv);
                    const uint32_t* va = ((u & 1) ? v1 : v0) + 4 * h;
                    const uint32_t* vb = ((u & 1) ? v2 : v1) + 4 * h;
                    float o[2][4] = {};
#pragma unroll
                    for (int d = 0; d < 2; ++d) mma16816(o[d], va[2 * d], va[2 * d + 1], vb[2 * d], vb[2 * d + 1], p & lomask, p & ~lomask);
                    stsm4t((orow ^ ((u >> 1) << 6)) + pn * 8192 + (u & 1) * 1024, pack2(o[0][0], o[0][1]), pack2(o[0][2], o[0][3]), pack2(o[1][0], o[1][1]), pack2(o[1][2], o[1][3]));
                }
                fence_async_smem();
                __syncwarp();
                if (lane == 0) mbar_arrive(BAR_SFULL(sb, wg * 2 + pn));
                if (pn == 0) { CS(5); if (PSPLIT) block_end(sb); }
            }
            CS(6);
            if (tid == 32) TL(41);
            bar_sync(1 + wg, 128);
            if (tid == 0) { TL(6); TC(106); }
            if (tid == 128) TL(44);
            CS(7);
#pragma unroll
            for (int e = 0; e < 32; ++e) xp[e] = qf[e];
        }
        } else {
        {
            float ag[88], au[88];
            mainloop32<true, LAG>(ag, au, sb, wg, tw, r, EV_LAG1, 48, [&] {
                stg.acquire2(sb, wg);
                Ring q = r; if (!wg) q.next();
                mbar_wait(BAR_EMPTY(sb, q.slot), q.par ^ 1);
            });
            if (tid == 0) { TL(10); TC(110); }
            if (tid == 128) TL(51);
            CS(22);
            glu<11>(sb, wg, [&](int i) { return ag[i]; }, [&](int i) { return au[i]; },
                    [&](int pn) { return pn < 2 ? sb + OFF_STG + wg * 16384 + pn * 8192 : sb + (wg ? P3_SLOT1 : P3_SLOT0) * SLOT + 24576; });
            if (tid == 0) { TL(11); TC(111); }
            if (tid == 128) TL(52);
            CS(23);
        }
        passes128<2>(sb, wg, tw, r, stg);
        if (tid == 0) { TL(12); TC(112); }
        }
        {
            float acc[64], gf[32];
            mainloop64(acc, blk == 0, sb, wg, tw, r, [&] {
                mbar_wait(BAR_ONE(sb, EV_GA + blk), 0);
                const uint32_t buf = stg.acquire2(sb, wg);
                if (blk == 0) load_slab(xp, buf);
                unpack_slab(xs, xp);
                uint32_t gt[16];
#pragma unroll
                for (int cg = 0; cg < 16; ++cg) gt[cg] = lds32(sb + OFF_TAB + blk * 256 + cg * 16 + (tw & 3) * 4);
#pragma unroll
                for (int i = 0; i < 16; ++i) unpack2(gt[i], gf[2 * i], gf[2 * i + 1]);
            });
            if (tid == 0) { TL(blk ? 13 : 7); TC(blk ? 113 : 107); }
            if (tid == 128) TL(blk ? 57 : 42);
            CS(blk ? 30 : 10);
#pragma unroll
            for (int e = 0; e < 64; ++e) xs[e] = fmaf(gf[(e >> 2) * 2 + (e & 1)], acc[e], xs[e]);
        }
        if (blk) break;
        }
        cluster_arrive();
        {
            IDX();
#pragma unroll
            for (int p = 0; p < 2; ++p) {
                store_slab(xs, sb + OFF_STG + wg * 16384, 8192, pan_addr, 4 * p, 4 * p + 4);
                stg.publish(sb, wg, lane);
            }
            if (tid == 0) TL(14);
            CS(31);
        }
      }
    } else {
        if (warp == 8 && !aux && elect_one()) {
#pragma unroll
            for (int i = 0; i < 4; ++i) mbar_init(BAR_SREADY(sb, i), 1);
#pragma unroll
            for (int i = 0; i < 4; ++i) mbar_init(BAR_ONE(sb, EV_WIN + i), 1);
#pragma unroll
            for (int i = 0; i < 4; ++i) {
                mbar_expect_tx(BAR_SREADY(sb, i), 8192);
                tma_load3(sb + OFF_STG + i * 8192, &mp.x, j * 128 + (i & 1) * 64, m * 64 + (i >> 1) * 32, BAR_SREADY(sb, i));
            }
#pragma unroll 1
            for (int i = 0; i < 4; ++i) {
                mbar_expect_tx(BAR_ONE(sb, EV_WIN + i), 8192);
                tma_load(sb + 5 * SLOT + i * 8192, &mp.wm8, 2 * i * 6144 + (m * 8 + j) * 16, 0, BAR_ONE(sb, EV_WIN + i));
                tma_load(sb + 5 * SLOT + i * 8192 + 4096, &mp.wm8, (2 * i + 1) * 6144 + (m * 8 + j) * 16, 0, BAR_ONE(sb, EV_WIN + i));
            }
        }
        __syncwarp();
        asm volatile("setmaxnreg.dec.sync.aligned.u32 56;");
        if (elect_one()) {
            if (warp == 8) {
                prefetch_map(&mp.wqkv); prefetch_map(&mp.wmod);
            } else if (warp < 11) {
                mbar_init(BAR_EMPTY(sb, NSLOT), 1);
#pragma unroll
                for (int i = 0; i < 2; ++i) { mbar_init(BAR_SFULL(sb, (warp - 9) * 2 + i), 4); if (aux) mbar_init(BAR_SREADY(sb, (warp - 9) * 2 + i), 1); }
#pragma unroll
                for (int i = 0; i < 3; ++i) {
                    mbar_init(BAR_EMPTY(sb, (warp - 9) * 3 + i), 4);
                    mbar_init(BAR_FULL(sb, (warp - 9) * 3 + i), 1); mbar_init(BAR_FULL(sb, (warp - 9) * 3 + i) + AF_REL, 1);
                }
            } else {
#pragma unroll
                for (int i = EV_P0; i < EV_COUNT; ++i) mbar_init(BAR_ONE(sb, i), i == EV_P0 ? 8 : 1);
            }
            asm volatile("fence.mbarrier_init.release.cluster;" ::: "memory");
        }
        __syncwarp();
        cluster_arrive();
        ep = 0;
        if (warp != 8 || aux) ep = flag_get(g_flags + FL_DONE);
        cluster_wait();
        ep = __shfl_sync(0xffffffffu, ep, 0) / NCTA + 1;
        if (warp == 8) {
            const bool el = elect_one();
            Ring r{0, 1};
            if (aux) {
                mbar_wait(BAR_ONE(sb, EV_GO), 0);
#pragma unroll 1
                for (int it = 0; it < 64; ++it) {
                    const int col = 2048 + (it >> 4) * 1024 + j * 256;
                    mbar_wait(BAR_EMPTY(sb, r.slot), r.par);
                    const uint32_t st = sb + r.slot * SLOT, fb = BAR_FULL(sb, r.slot);
                    if (el) {
                        mbar_expect_tx(fb, 32768);
#pragma unroll
                        for (int b = 0; b < 4; ++b) tma_load(st + b * 8192, &mp.wmod, col + b * 64, (it & 15) * 64, fb);
                    }
                    r.next();
                }
                mbar_wait(BAR_ONE(sb, EV_P0), 0);
                const CUtensorMap* wm = rank ? &mp.wu : &mp.wg;
#pragma unroll 1
                for (int g = 0; g < 128; ++g) {
                    const int mx = (j >> 1) * 8 + (g >> 5) * 2 + rank, k0 = (g & 31) * 32;
                    if (k0 == 0) {
                        uint32_t n = 0;
                        while (!__all_sync(0xffffffffu, (int32_t)(flag_get(g_flags + FL_PROG + (mx * 32 + lane) * FS) - (ep * 8 + ST_H2)) >= 0)) { SPIN_GUARD(n); __nanosleep(500); }
                    }
                    mbar_wait(BAR_EMPTY(sb, r.slot), r.par);
                    const uint32_t st = sb + r.slot * SLOT, fb = BAR_FULL(sb, r.slot);
                    if (el) {
                        mbar_expect_tx(fb, 24576);
                        tma_load_mc(st + 8192 + rank * 4096, wm, HC3, k0, fb);
                        tma_load_mc(st + 16384 + rank * 4096, wm, HC3 + 64, k0, fb);
                        tma_load(st, &mp.h2l, k0, mx * 128, fb);
                    }
                    r.next();
                }
            } else {
#pragma unroll 1
                for (int it = 0; it < 32; ++it) {
                    const int cb = j * 128 + rank * 64, k0 = kof(it, 2, j);
                    if (it == BW0) mbar_wait(BAR_ONE(sb, BWEV), 0);
                    if (it == BW1) mbar_wait(BAR_ONE(sb, EV_PAR), 0);
                    if (it == 5) mbar_wait(BAR_ONE(sb, EV_P0), 0);
                    if (it == 6) mbar_wait(BAR_ONE(sb, (AGW & 1) ? EV_AGO : EV_FGO), 0);
                    mbar_wait(BAR_EMPTY(sb, r.slot), r.par);
                    const uint32_t st = sb + r.slot * SLOT, fb = BAR_FULL(sb, r.slot);
                    if (el) {
                        mbar_expect_tx(fb, it < 4 ? 24576 : 28672);
                        tma_load_mc(st + 8192 + rank * 4096, &mp.wqkv, 1024 + cb, k0, fb);
                        tma_load_mc(st + 16384 + rank * 4096, &mp.wqkv, 2048 + cb, k0, fb);
                        tma_load_mc(st + 24576 + rank * 4096, &mp.wqkv, cb, k0, fb);
                        if (it < 4) mbar_arrive(fb + AF_REL);
                        if (it == PFWO + (m >> 1)) { tma_prefetch(&mp.wo, j * 128, m * 64); tma_prefetch(&mp.wo, j * 128 + 64, m * 64); }
                    }
                    r.next();
                }
                if (el) mbar_arrive(BAR_ONE(sb, EV_KV));
#pragma unroll 1
                for (int it = 0; it < 16; ++it) {
                    if (it == 6) mbar_wait(BAR_ONE(sb, (AGW & 2) ? EV_AGO1 : EV_FGO1), 0);
                    mbar_wait(BAR_EMPTY(sb, r.slot), r.par);
                    const uint32_t st = sb + r.slot * SLOT, fb = BAR_FULL(sb, r.slot);
                    if (el) {
                        mbar_expect_tx(fb, it < 2 ? 16384 : 24576);
                        tma_load_mc(st + 16384 + rank * 8192, &mp.wo, j * 128 + rank * 64, kof(it, 1, j), fb);
                        if (it < 2) mbar_arrive(fb + AF_REL);
                        if (it == 6) { prefetch_map(rank ? &mp.wu : &mp.wg); prefetch_map(rank ? &mp.wu3 : &mp.wg3); }
                    }
                    r.next();
                }
                const CUtensorMap* wm = rank ? &mp.wu : &mp.wg;
#pragma unroll 1
                for (int g = 0; g < 96; ++g) {
                    if (g == 6) mbar_wait(BAR_ONE(sb, (AGW & 4) ? EV_AGO2 : EV_FGO2), 0);
                    const int p = g >> 5, cb = hcol(p, j), k0 = p == 0 ? kof(g, 2, j) : (g & 31) * 32;
                    mbar_wait(BAR_EMPTY(sb, r.slot), r.par);
                    const uint32_t st = sb + r.slot * SLOT, fb = BAR_FULL(sb, r.slot);
                    if (el) {
                        mbar_expect_tx(fb, (g < 4 || p > 0) ? 24576 : 28672);
                        tma_load_mc(st + 8192 + rank * 4096, wm, cb, k0, fb);
                        tma_load_mc(st + 16384 + rank * 4096, wm, cb + 64, k0, fb);
                        if (p == 0) tma_load3_mc(st + 24576 + rank * 4096, rank ? &mp.wu3 : &mp.wg3, j, k0, fb);
                        else tma_load(st, &mp.h2l, k0, m * 128, fb);
                        if (g < 4) mbar_arrive(fb + AF_REL);
                        if (g == 60) prefetch_map(&mp.wd);
                    }
                    r.next();
                }
#pragma unroll 1
                for (int g = 0; g < 56; ++g) {
                    if (g == 0 || (g & 15) == 6 && g > 6) mbar_wait(BAR_ONE(sb, EV_H0 + (g >> 4)), 0);
                    const int k0 = g * 64;
                    mbar_wait(BAR_EMPTY(sb, r.slot), r.par);
                    const uint32_t st = sb + r.slot * SLOT, fb = BAR_FULL(sb, r.slot);
                    if (el) {
                        mbar_expect_tx(fb, 32768);
                        tma_load_mc(st + 16384 + rank * 8192, &mp.wd, j * 128 + rank * 64, k0, fb);
                        tma_load(st, &mp.hb, k0, m * 128, fb); tma_load(st + 8192, &mp.hb, k0, m * 128 + 64, fb);
                    }
                    r.next();
                }
            }
        } else if (aux) {
            if (warp < 11) {
                const uint32_t w = warp - 9;
                const bool el = elect_one();
#pragma unroll 1
                for (int p = 0; p < 4; ++p) {
                    const int mx = (j >> 1) * 8 + p * 2 + rank;
                    if (el) { mbar_arrive(BAR_SREADY(sb, w * 2)); mbar_arrive(BAR_SREADY(sb, w * 2 + 1)); }
                    mbar_wait2(BAR_SFULL(sb, w * 2), BAR_SFULL(sb, w * 2 + 1), p & 1);
                    if (el) {
                        tma_store(&mp.hb, HC3, mx * 128 + w * 64, sb + OFF_STG + w * 16384); tma_store(&mp.hb, HC3 + 64, mx * 128 + w * 64, sb + OFF_STG + w * 16384 + 8192);
                        bulk_commit(); bulk_wait_all(); flag_set(g_flags + FL_AUX + mx * 2 + w, ep * 8 + ST_H + 3);
                    }
                }
            }
        } else if (warp == 11) {
            const bool el = elect_one();
            const int row0 = m * 128;
            const uint32_t* const fl = g_flags + FL_PROG + (m * 32 + (lane & 16) + (kof(lane & 15, 1, j) >> 6)) * FS;
            if (el) { prefetch_map(&mp.h1h); prefetch_map(&mp.h2h); prefetch_map(&mp.h2l); }
            {
                const uint4* pk = pt.mail->mod1 + grp * 512 + j * 32 + lane;
                uint4 a, b; uint32_t n = 0;
                mbar_wait(BAR_ONE(sb, EV_WIN3), 0);
                while (true) {
                    a = ld_pkt16(pk); b = ld_pkt16(pk + 256);
                    if (__all_sync(0xffffffffu, a.z == ep && b.z == ep)) break;
                    SPIN_GUARD(n);
                }
                sts128(sb + OFF_PAR + lane * 16, a.x, a.y, b.x, b.y);
                __syncwarp();
                if (lane == 0) { mbar_arrive(BAR_ONE(sb, EV_PAR)); TL(46); }
            }
            mbar_wait(BAR_ONE(sb, EV_P0), 0);
            Ring r{0, 1};
#pragma unroll 1
            for (int ph = 0; ph < 3; ++ph) {
                const int sh = ph == 1 ? 1 : 2, nst = 8 << sh;
                const uint32_t half = 16384 >> sh;
                const CUtensorMap* tm = ph == 0 ? &mp.h1h : ph == 1 ? &mp.o : &mp.h2h;
                if (ph == 1) fetch_halo(g_halo + ((m - 1) * 8 + j) * 512 + 256 + lane, m == 0, sb, 2, lane);
                const uint32_t target = ep * 8 + ST_H1 + ph;
                int a0 = 1 << sh, a1 = a0, fr = a0;
                r.skip(fr);
                uint32_t s0 = r.slot, s1 = r.slot, have = 0, n = 0;
                int k0 = j ? 0 : 128, k1 = k0;
#pragma unroll 1
                for (; fr < NSLOT; ++fr) { mbar_wait(BAR_EMPTY(sb, r.slot), r.par); r.next(); }
                uint32_t v = flag_get(fl);
                auto load = [&](int& a, uint32_t& sl, int& k, uint32_t w) {
                    const uint32_t fb = BAR_FULL(sb, sl) + (w ? 0 : AF_REL);
                    if (el) { if (!w) mbar_expect_tx(fb, half); tma_load(sb + sl * SLOT + w * half, tm, k, row0 + w * 64, fb); }
                    if (a == NSLOT - 1 && el) mbar_arrive(BAR_ONE(sb, (w ? EV_AGO : EV_FGO) + ph));
                    ++a; if (++sl == NSLOT) sl = 0;
                    k = kof(a, sh, j);
                };
                do {
                    PS(0);
                    if (fr < 9 && mbar_test(BAR_EMPTY(sb, r.slot), r.par)) { ++fr; r.next(); }
                    SPIN_GUARD(n);
                    PS(1);
                    const bool ok = (int32_t)(v - target) >= 0;
                    v = flag_get(fl);
                    have = __ballot_sync(0xffffffffu, ok);
                    PS(2);
#pragma unroll 1
                    while (a1 < fr && (have & (0x10000u << (a1 >> (sh - 1))))) {
                        if (a1 == (1 << sh)) TL(16 + ph);
                        load(a1, s1, k1, 1);
                    }
                    PS(3);
#pragma unroll 1
                    while (a0 < fr && (have & (1u << (a0 >> (sh - 1))))) load(a0, s0, k0, 0);
                    PS(4);
                } while (~have & 0x01fc01fcu);
#pragma unroll 1
                while (a0 < nst) {
                    if (a0 == 9 << (sh - 1)) while (!__all_sync(0xffffffffu, (int32_t)(flag_get(fl) - target) >= 0)) SPIN_GUARD(n);
                    mbar_wait(BAR_EMPTY(sb, r.slot), r.par);
                    r.next();
                    load(a1, s1, k1, 1); load(a0, s0, k0, 0);
                }
            }
#pragma unroll 1
            for (int p = 0; p < 4; ++p) {
                const uint32_t* f = p < 3 ? fl : g_flags + FL_AUX + m * 2 + (lane & 1);
                uint32_t n = 0;
                while (!__all_sync(0xffffffffu, (int32_t)(flag_get(f) - (ep * 8 + ST_H + p)) >= 0)) { SPIN_GUARD(n); __nanosleep(500); }
                if (el) mbar_arrive(BAR_ONE(sb, EV_H0 + p));
            }
        } else {
            const uint32_t w = warp - 9;
            const int row0 = m * 128 + w * 64;
            const uint32_t stg = sb + OFF_STG + w * 16384;
            uint32_t* const fl = g_flags + FL_PROG + (m * 32 + w * 16 + 2 * j) * FS;
            uint32_t b = 0, par = 0;
            const bool el = elect_one();
            auto store = [&](const CUtensorMap* tm, int col, bool nat = false) {
                mbar_wait(BAR_SFULL(sb, w * 2 + b), (par >> b) & 1);
                par ^= 1u << b;
                if (el) {
                    if (nat) tma_store3(tm, col, row0 >> 1, 0, stg + b * 8192); else tma_store(tm, col, row0, stg + b * 8192);
                    bulk_commit();
                }
                b ^= 1;
            };
            auto send2 = [&](const CUtensorMap* tm, int step) {
                store(tm, j * 128);
                if (el) { bulk_wait_all(); flag_set(fl, ep * 8 + step); }
                if (step != ST_O) { mbar_wait(BAR_ONE(sb, EV_FGO + step - ST_H1), 0); pause(w ? P1H : P1H + 1000); }
                else if ((OMODE >> (2 * w)) & 3) mbar_wait(BAR_ONE(sb, ((OMODE >> (2 * w)) & 1) ? EV_FGO1 : EV_AGO1), 0);
                store(tm, j * 128 + 64);
                if (el) { bulk_wait_all(); flag_set(fl + FS, ep * 8 + step); }
            };
            auto free2 = [&]() { if (el) { mbar_arrive(BAR_SREADY(sb, w * 2)); mbar_arrive(BAR_SREADY(sb, w * 2 + 1)); } };
            auto gate = [&](int vec, int ev) {
                uint4 v; uint32_t n = 0;
                while (true) {
                    v = ld_pkt2(g_mod + vec * 512 + j * 64 + lane * 2);
                    if (__all_sync(0xffffffffu, v.y == ep && v.w == ep)) break;
                    SPIN_GUARD(n); __nanosleep(300);
                }
                asm volatile("st.shared.v2.u32 [%0], {%1, %2};" :: "r"(sb + OFF_TAB + (ev - EV_GA) * 256 + lane * 8), "r"(v.x), "r"(v.z) : "memory");
                __syncwarp();
                if (lane == 0) mbar_arrive(BAR_ONE(sb, ev));
            };
            if (el) { prefetch_map(&mp.h1s); prefetch_map(&mp.o); prefetch_map(&mp.h2s); prefetch_map(&mp.hb); prefetch_map(&mp.out); prefetch_map(&mp.wo); }
            if (el) { flag_set(fl, ep * 8); flag_set(fl + FS, ep * 8); }
            send2(&mp.h1s, ST_H1);
            if (w == 0) TL(47);
            free2();
            if (w == 0) fetch_halo(g_halo + ((m - 1) * 8 + j) * 512 + lane, m == 0, sb, 0, lane);
            else { mbar_wait(BAR_ONE(sb, EV_KV), 0); gate(2, EV_GA); }
            send2(&mp.o, ST_O);
            if (w == 0) TL(40); else TL(38);
            mbar_wait(BAR_ONE(sb, EV_OWN + w), 0);
            if (el) {
#pragma unroll
                for (uint32_t i = 0; i < 2; ++i) {
                    mbar_expect_tx(BAR_SREADY(sb, w * 2 + i), 8192);
                    tma_load3(stg + i * 8192, &mp.x, j * 128 + i * 64, row0 >> 1, BAR_SREADY(sb, w * 2 + i));
                }
            }
            if (w == 1) {
                uint32_t n = 0;
                while ((int32_t)(flag_get(g_flags + FL_LN2) - ep * 8) < 0) { SPIN_GUARD(n); __nanosleep(200); }
                const uint4 v = __ldcg((const uint4*)(g_par2 + j * 128) + lane);
                sts128(sb + OFF_PAR + lane * 16, v.x, v.y, v.z, v.w);
                __syncwarp();
                if (lane == 0) mbar_arrive(BAR_ONE(sb, EV_LN2));
            }
            send2(&mp.h2s, ST_H2);
            if (el) { prefetch_map(&mp.hb); prefetch_map(&mp.hb3); }
            if (w == 0) TL(37);
            free2();
#pragma unroll 1
            for (int p = 0; p < 3; ++p) {
                const int col = hcol(p, j);
                mbar_wait(BAR_SFULL(sb, w * 2), par & 1);
                pause(w ? HD1 : HD0); store(&mp.hb, col);
                pause(HP); store(&mp.hb, col + 64);
                if (p == 0) {
                    pause(HP);
                    if (el) { tma_store3(&mp.hb3, 0, j, row0, sb + (w ? P3_SLOT1 : P3_SLOT0) * SLOT + 24576); bulk_commit(); }
                }
                if (el) { bulk_wait_all(); flag_set(fl, ep * 8 + ST_H + p); flag_set(fl + FS, ep * 8 + ST_H + p); }
                free2();
                if (p == 0 && w == 1) gate(5, EV_GB);
            }
            cluster_arrive_early = true;
            cluster_arrive();
            store(&mp.out, j * 128, true); store(&mp.out, j * 128 + 64, true);
            if (el) bulk_wait_read();
        }
        __syncwarp();
    }
    if (aux || (wg == 2 && !cluster_arrive_early)) cluster_arrive();
    cluster_wait();
    CS(32);
    if (KDEBUG == 5) __syncthreads();
    if (tid == 0) {
        TL(15);
        flag_add(pt.mail->flags + FL_DONE);
    }
}

typedef CUresult (*EncodeFn)(CUtensorMap*, CUtensorMapDataType, cuuint32_t, void*, const cuuint64_t*, const cuuint64_t*, const cuuint32_t*,
                             const cuuint32_t*, CUtensorMapInterleave, CUtensorMapSwizzle, CUtensorMapL2promotion, CUtensorMapFloatOOBfill);

void make_map(EncodeFn fn, CUtensorMap* m, const void* ptr, uint64_t rows, uint64_t cols, uint32_t brows, uint32_t bcols) {
    cuuint64_t dims[2] = {cols, rows}, strides[1] = {cols * 2};
    cuuint32_t box[2] = {bcols, brows}, es[2] = {1, 1};
    fn(m, CU_TENSOR_MAP_DATA_TYPE_BFLOAT16, 2, (void*)ptr, dims, strides, box, es, CU_TENSOR_MAP_INTERLEAVE_NONE,
       bcols == 64 ? CU_TENSOR_MAP_SWIZZLE_128B : bcols == 32 ? CU_TENSOR_MAP_SWIZZLE_64B : CU_TENSOR_MAP_SWIZZLE_NONE, CU_TENSOR_MAP_L2_PROMOTION_L2_256B, CU_TENSOR_MAP_FLOAT_OOB_FILL_NONE);
}

void make_map3(EncodeFn fn, CUtensorMap* m, const void* ptr) {
    cuuint64_t dims[3] = {D_, S_ / 2, 2}, strides[2] = {4 * D_, 2 * D_};
    cuuint32_t box[3] = {64, 32, 2}, es[3] = {1, 1, 1};
    fn(m, CU_TENSOR_MAP_DATA_TYPE_BFLOAT16, 3, (void*)ptr, dims, strides, box, es, CU_TENSOR_MAP_INTERLEAVE_NONE,
       CU_TENSOR_MAP_SWIZZLE_128B, CU_TENSOR_MAP_L2_PROMOTION_L2_256B, CU_TENSOR_MAP_FLOAT_OOB_FILL_NONE);
}

void make_map48(EncodeFn fn, CUtensorMap* m, const void* ptr, uint64_t rows, uint32_t brows) {
    cuuint64_t dims[3] = {48, 8, rows}, strides[2] = {96, 2 * F_};
    cuuint32_t box[3] = {64, 1, brows}, es[3] = {1, 1, 1};
    fn(m, CU_TENSOR_MAP_DATA_TYPE_BFLOAT16, 3, (void*)ptr, dims, strides, box, es, CU_TENSOR_MAP_INTERLEAVE_NONE,
       CU_TENSOR_MAP_SWIZZLE_128B, CU_TENSOR_MAP_L2_PROMOTION_L2_256B, CU_TENSOR_MAP_FLOAT_OOB_FILL_NONE);
}

}

extern "C" void kernel_launch(void* const* d_in, const int* in_sizes, int n_in, void* d_out, int out_size) {
    (void)in_sizes; (void)n_in; (void)out_size;
    void* fnp = nullptr;
    cudaDriverEntryPointQueryResult qr;
    cudaGetDriverEntryPoint("cuTensorMapEncodeTiled", &fnp, cudaEnableDefault, &qr);
    EncodeFn fn = (EncodeFn)fnp;
    void *h1, *o, *h2, *hb, *mail;
    cudaGetSymbolAddress(&h1, g_h1);
    cudaGetSymbolAddress(&mail, g_mail);
    cudaGetSymbolAddress(&o, g_o);
    cudaGetSymbolAddress(&hb, g_hb);
    h2 = H2ALIAS;
    Maps mp;
    make_map(fn, &mp.h1h, h1, S_, D_, 64, 32);
    make_map(fn, &mp.h2h, h2, S_, D_, 64, 32);
    make_map(fn, &mp.h1s, h1, S_, D_, 64, 64);
    make_map(fn, &mp.o, o, S_, D_, 64, 64);
    make_map(fn, &mp.h2l, h2, S_, D_, 128, 32);
    make_map(fn, &mp.h2s, h2, S_, D_, 64, 64);
    make_map(fn, &mp.hb, hb, S_, F_, 64, 64);
    make_map(fn, &mp.wqkv, d_in[1], D_, 3 * D_, 32, 64);
    make_map(fn, &mp.wo, d_in[2], D_, D_, 64, 64);
    make_map(fn, &mp.wg, d_in[4], D_, F_, 32, 64);
    make_map(fn, &mp.wu, d_in[5], D_, F_, 32, 64);
    make_map(fn, &mp.wd, d_in[6], F_, D_, 64, 64);
    make_map(fn, &mp.wmod, d_in[8], D_, 6 * D_, 64, 64);
    make_map(fn, &mp.wm8, d_in[8], D_ / 8, 8 * 6 * D_, 128, 16);
    make_map3(fn, &mp.x, d_in[0]);
    make_map3(fn, &mp.out, d_out);
    make_map48(fn, &mp.wg3, d_in[4], D_, 32);
    make_map48(fn, &mp.wu3, d_in[5], D_, 32);
    make_map48(fn, &mp.hb3, hb, S_, 64);
    cudaFuncSetAttribute(fused_block_kernel, cudaFuncAttributeMaxDynamicSharedMemorySize, SMEM_BYTES);
    cudaLaunchConfig_t cfg = {};
    cfg.gridDim = dim3(NCTA); cfg.blockDim = dim3(384); cfg.dynamicSmemBytes = SMEM_BYTES; cfg.stream = cudaStreamPerThread;
    cudaLaunchAttribute at[1];
    at[0].id = cudaLaunchAttributeClusterDimension; at[0].val.clusterDim.x = 2; at[0].val.clusterDim.y = 1; at[0].val.clusterDim.z = 1;
    cfg.attrs = at; cfg.numAttrs = 1;
    const Ptrs pt{(const __nv_bfloat16*)d_in[7], (Mail*)mail};
    cudaLaunchKernelEx(&cfg, fused_block_kernel, pt, mp);
}
```

```cpp
#include <cuda_runtime.h>
#include <cuda_bf16.h>
#include <cuda.h>
#include <stdint.h>
#include <stddef.h>

#define LAG 4
#define LAGS 4
#define LAGW 3
#define LAGQ 4
#define MIDW 2
#define PFWO 14
#define FLAGRED 1
#define FLAY 0
#define PMASK 1
#define PGAP 0
#define PWAIT 0
#define P1H 2000
#define AGW 6
#define CSW 0
#define LWAIT 2
#define BW0 0
#define BWEV EV_WIN
#define GODLY 0
#define BW1 3
#define PDLY 500
#define H2ALIAS o
#define HD1 5500
#define HD0 5500
#define HP 2200
#define LAGD 4
#define MIDD 44
#define PSPLIT 1
#define OMODE 1
#define XST ST_O
#define P1AT 8
#define P1S 0
#define P1G 0
#define KDEBUG 0

namespace {

constexpr int S_ = 2048, D_ = 1024, F_ = 3584;
constexpr int NCTA = 132;
constexpr int NSLOT = 6;
constexpr uint32_t SLOT = 32768;
constexpr uint32_t OFF_STG = NSLOT * SLOT;
constexpr uint32_t OFF_BAR = OFF_STG + 32768;
constexpr uint32_t OFF_PAR = OFF_BAR + 512;
constexpr uint32_t OFF_TAB = OFF_PAR + 768;
constexpr uint32_t OFF_TL = OFF_PAR + 2048;
constexpr uint32_t SMEM_BYTES = OFF_TL + (KDEBUG ? 512 : 0);
constexpr uint32_t P3_SLOT1 = (32 + 16 + 32) % NSLOT, P3_SLOT0 = (P3_SLOT1 + 1) % NSLOT;

constexpr int ST_H1 = 1, ST_O = 2, ST_H2 = 3, ST_H = 4, FL_DONE = 0, FL_LN2 = 1, FL_AUX = 32, FL_PROG = 64;

struct Maps {
    CUtensorMap h1h, h1s, o, h2h, h2l, h2s, hb, wqkv, wo, wg, wu, wd, wmod, wm8, x, out, wg3, wu3, hb3;
};

struct Mail {
    uint32_t flags[16 * 32 * 32 + 64];
    uint2 mod[6 * D_ / 2];
    uint4 mod1[8 * 512];
    uint4 st1[128 * 512];
    uint32_t par2[D_];
    uint4 halo[128 * 512];
};
struct Ptrs { const __nv_bfloat16* c; Mail* mail; };

__device__ __align__(128) Mail g_mail;
__device__ __align__(128) __nv_bfloat16 g_h1[S_ * D_];
__device__ __align__(128) __nv_bfloat16 g_o[S_ * D_];
__device__ __align__(128) __nv_bfloat16 g_hb[S_ * F_];
#define TL(i) do {} while (0)
#define TC(i) do {} while (0)
#define TS(g, which) do {} while (0)
#define CS(i) do {} while (0)

__device__ __forceinline__ uint32_t smem_u32(const void* p) { return (uint32_t)__cvta_generic_to_shared(p); }
__device__ __forceinline__ void mbar_init(uint32_t bar, uint32_t cnt) { asm volatile("mbarrier.init.shared::cta.b64 [%0], %1;" :: "r"(bar), "r"(cnt) : "memory"); }
__device__ __forceinline__ void mbar_expect_tx(uint32_t bar, uint32_t bytes) { asm volatile("mbarrier.arrive.expect_tx.shared::cta.b64 _, [%0], %1;" :: "r"(bar), "r"(bytes) : "memory"); }
__device__ __forceinline__ void mbar_arrive(uint32_t bar) { asm volatile("mbarrier.arrive.shared::cta.b64 _, [%0];" :: "r"(bar) : "memory"); }
__device__ __forceinline__ void mbar_arrive_cta(uint32_t bar, uint32_t cta) {
    asm volatile("{\n.reg .b32 r;\nmapa.shared::cluster.u32 r, %0, %1;\nmbarrier.arrive.shared::cluster.b64 _, [r];\n}" :: "r"(bar), "r"(cta) : "memory");
}
__device__ __forceinline__ void mbar_wait(uint32_t bar, uint32_t parity) {
    asm volatile("{\n.reg .pred p;\n.reg .u32 n;\nmov.u32 n, 0;\n"
        "W_LOOP:\nmbarrier.try_wait.parity.shared::cta.b64 p, [%0], %1;\n@p bra W_DONE;\n"
        "add.u32 n, n, 1;\nsetp.lt.u32 p, n, 0x400000;\n@p bra W_LOOP;\ntrap;\nW_DONE:\n}" :: "r"(bar), "r"(parity) : "memory");
}
__device__ __forceinline__ void mbar_wait2(uint32_t b0, uint32_t b1, uint32_t parity) {
    asm volatile("{\n.reg .pred p, q;\n.reg .u32 n;\nmov.u32 n, 0;\n"
        "W_LOOP:\nmbarrier.try_wait.parity.shared::cta.b64 p, [%0], %2;\nmbarrier.try_wait.parity.shared::cta.b64 q, [%1], %2;\nand.pred p, p, q;\n@p bra W_DONE;\n"
        "add.u32 n, n, 1;\nsetp.lt.u32 p, n, 0x400000;\n@p bra W_LOOP;\ntrap;\nW_DONE:\n}" :: "r"(b0), "r"(b1), "r"(parity) : "memory");
}
__device__ __forceinline__ bool mbar_test(uint32_t bar, uint32_t parity) {
    uint32_t r; asm volatile("{\n.reg .pred p;\nmbarrier.test_wait.parity.shared::cta.b64 p, [%1], %2;\nselp.u32 %0, 1, 0, p;\n}" : "=r"(r) : "r"(bar), "r"(parity) : "memory"); return r;
}
__device__ __forceinline__ bool mbar_test2(uint32_t b0, uint32_t b1, uint32_t parity) {
    uint32_t r;
    asm volatile("{\n.reg .pred p, q;\nmbarrier.test_wait.parity.shared::cta.b64 p, [%1], %3;\nmbarrier.test_wait.parity.shared::cta.b64 q, [%2], %3;\n"
        "and.pred p, p, q;\nselp.u32 %0, 1, 0, p;\n}" : "=r"(r) : "r"(b0), "r"(b1), "r"(parity) : "memory");
    return r;
}
__device__ __forceinline__ void tma_load3(uint32_t dst, const CUtensorMap* m, int c0, int c1, uint32_t bar) {
    asm volatile("cp.async.bulk.tensor.3d.shared::cluster.global.mbarrier::complete_tx::bytes [%0], [%1, {%3, %4, %5}], [%2];"
        :: "r"(dst), "l"(m), "r"(bar), "r"(c0), "r"(c1), "r"(0) : "memory");
}
__device__ __forceinline__ void tma_store3(const CUtensorMap* m, int c0, int c1, int c2, uint32_t src) {
    asm volatile("cp.async.bulk.tensor.3d.global.shared::cta.bulk_group [%0, {%2, %3, %4}], [%1];" :: "l"(m), "r"(src), "r"(c0), "r"(c1), "r"(c2) : "memory");
}
__device__ __forceinline__ void tma_load3_mc(uint32_t dst, const CUtensorMap* m, int c1, int c2, uint32_t bar) {
    asm volatile("cp.async.bulk.tensor.3d.shared::cluster.global.mbarrier::complete_tx::bytes.multicast::cluster.L2::cache_hint [%0], [%1, {%3, %4, %5}], [%2], %6, %7;"
        :: "r"(dst), "l"(m), "r"(bar), "r"(0), "r"(c1), "r"(c2), "h"((uint16_t)3), "l"(0x12F0000000000000ull) : "memory");
}
__device__ __forceinline__ void tma_load(uint32_t dst, const CUtensorMap* m, int c0, int c1, uint32_t bar) {
    asm volatile("cp.async.bulk.tensor.2d.shared::cluster.global.mbarrier::complete_tx::bytes [%0], [%1, {%3, %4}], [%2];"
        :: "r"(dst), "l"(m), "r"(bar), "r"(c0), "r"(c1) : "memory");
}
__device__ __forceinline__ void tma_load_mc(uint32_t dst, const CUtensorMap* m, int c0, int c1, uint32_t bar) {
    asm volatile("cp.async.bulk.tensor.2d.shared::cluster.global.mbarrier::complete_tx::bytes.multicast::cluster.L2::cache_hint [%0], [%1, {%3, %4}], [%2], %5, %6;"
        :: "r"(dst), "l"(m), "r"(bar), "r"(c0), "r"(c1), "h"((uint16_t)3), "l"(0x12F0000000000000ull) : "memory");
}
__device__ __forceinline__ void tma_prefetch(const CUtensorMap* m, int c0, int c1) {
    asm volatile("cp.async.bulk.prefetch.tensor.2d.L2.global [%0, {%1, %2}];" :: "l"(m), "r"(c0), "r"(c1) : "memory");
}
__device__ __forceinline__ void tma_store(const CUtensorMap* m, int c0, int c1, uint32_t src) {
    asm volatile("cp.async.bulk.tensor.2d.global.shared::cta.bulk_group [%0, {%2, %3}], [%1];" :: "l"(m), "r"(src), "r"(c0), "r"(c1) : "memory");
}
__device__ __forceinline__ void bulk_commit() { asm volatile("cp.async.bulk.commit_group;" ::: "memory"); }
__device__ __forceinline__ void bulk_wait_read() { asm volatile("cp.async.bulk.wait_group.read 0;" ::: "memory"); }
__device__ __forceinline__ void bulk_wait_all() { asm volatile("cp.async.bulk.wait_group 0;" ::: "memory"); }
__device__ __forceinline__ void fence_async_smem() { asm volatile("fence.proxy.async.shared::cta;" ::: "memory"); }
__device__ __forceinline__ void prefetch_map(const CUtensorMap* m) { asm volatile("prefetch.tensormap [%0];" :: "l"(m) : "memory"); }
__device__ __forceinline__ void wg_fence() { asm volatile("wgmma.fence.sync.aligned;" ::: "memory"); }
__device__ __forceinline__ void wg_commit() { asm volatile("wgmma.commit_group.sync.aligned;" ::: "memory"); }
template <int N> __device__ __forceinline__ void wg_wait() { asm volatile("wgmma.wait_group.sync.aligned %0;" :: "n"(N) : "memory"); }
__device__ __forceinline__ void bar_sync(int id, int n) { asm volatile("bar.sync %0, %1;" :: "r"(id), "r"(n) : "memory"); }
__device__ __forceinline__ void bar_arrive(int id, int n) { asm volatile("bar.arrive %0, %1;" :: "r"(id), "r"(n) : "memory"); }
__device__ __forceinline__ void flag_add(uint32_t* f) { asm volatile("red.relaxed.gpu.global.add.u32 [%0], 1;" :: "l"(f) : "memory"); }
__device__ __forceinline__ void flag_set(uint32_t* f, uint32_t v) { asm volatile("red.relaxed.gpu.global.max.u32 [%0], %1;" :: "l"(f), "r"(v) : "memory"); }
__device__ __forceinline__ uint32_t flag_get(const uint32_t* f) { uint32_t v; asm volatile("ld.relaxed.gpu.global.u32 %0, [%1];" : "=r"(v) : "l"(f) : "memory"); return v; }
__device__ __forceinline__ uint32_t d16(uint32_t addr) { return (addr & 0x3FFFF) >> 4; }
__device__ __forceinline__ uint64_t mk_desc(uint32_t a16, uint32_t off, uint32_t lbo, uint32_t sbo, uint32_t swz) {
    const uint32_t lo = a16 + (off >> 4) + ((lbo >> 4) << 16), hi = (sbo >> 4) | (swz << 30);
    return ((uint64_t)hi << 32) | lo;
}
__device__ __forceinline__ uint32_t pack2(float lo, float hi) {
    uint32_t r; asm("cvt.rn.bf16x2.f32 %0, %1, %2;" : "=r"(r) : "f"(hi), "f"(lo)); return r;
}
__device__ __forceinline__ uint32_t hfma2_bf16(uint32_t a, uint32_t b, uint32_t c) {
    uint32_t r; asm("fma.rn.bf16x2 %0, %1, %2, %3;" : "=r"(r) : "r"(a), "r"(b), "r"(c)); return r;
}
__device__ __forceinline__ float bf_lo(uint32_t v) { return __uint_as_float(v << 16); }
__device__ __forceinline__ float bf_hi(uint32_t v) { return __uint_as_float(v & 0xFFFF0000u); }
__device__ __forceinline__ void unpack2(uint32_t v, float& lo, float& hi) {
    asm volatile("shl.b32 %0, %2, 16;\nand.b32 %1, %2, 0xffff0000;" : "=f"(lo), "=f"(hi) : "r"(v));
}
__device__ __forceinline__ float bf_round(float x) { return __bfloat162float(__float2bfloat16_rn(x)); }
__device__ __forceinline__ void stsm4(uint32_t addr, uint32_t r0, uint32_t r1, uint32_t r2, uint32_t r3) {
    asm volatile("stmatrix.sync.aligned.m8n8.x4.shared.b16 [%0], {%1, %2, %3, %4};" :: "r"(addr), "r"(r0), "r"(r1), "r"(r2), "r"(r3) : "memory");
}
__device__ __forceinline__ void stsm4t(uint32_t addr, uint32_t r0, uint32_t r1, uint32_t r2, uint32_t r3) {
    asm volatile("stmatrix.sync.aligned.m8n8.x4.trans.shared.b16 [%0], {%1, %2, %3, %4};" :: "r"(addr), "r"(r0), "r"(r1), "r"(r2), "r"(r3) : "memory");
}
__device__ __forceinline__ uint32_t movm(uint32_t a) { uint32_t d; asm volatile("movmatrix.sync.aligned.m8n8.trans.b16 %0, %1;" : "=r"(d) : "r"(a)); return d; }
__device__ __forceinline__ void ldsm4(uint32_t addr, uint32_t& r0, uint32_t& r1, uint32_t& r2, uint32_t& r3) {
    asm volatile("ldmatrix.sync.aligned.m8n8.x4.shared.b16 {%0, %1, %2, %3}, [%4];" : "=r"(r0), "=r"(r1), "=r"(r2), "=r"(r3) : "r"(addr) : "memory");
}
__device__ __forceinline__ void ldsm4t(uint32_t addr, uint32_t& r0, uint32_t& r1, uint32_t& r2, uint32_t& r3) {
    asm volatile("ldmatrix.sync.aligned.m8n8.x4.trans.shared.b16 {%0, %1, %2, %3}, [%4];" : "=r"(r0), "=r"(r1), "=r"(r2), "=r"(r3) : "r"(addr) : "memory");
}
__device__ __forceinline__ void mma16816(float (&c)[4], uint32_t a0, uint32_t a1, uint32_t a2, uint32_t a3, uint32_t b0, uint32_t b1) {
    asm("mma.sync.aligned.m16n8k16.row.col.f32.bf16.bf16.f32 {%0, %1, %2, %3}, {%4, %5, %6, %7}, {%8, %9}, {%0, %1, %2, %3};"
        : "+f"(c[0]), "+f"(c[1]), "+f"(c[2]), "+f"(c[3]) : "r"(a0), "r"(a1), "r"(a2), "r"(a3), "r"(b0), "r"(b1));
}
__device__ __forceinline__ float rcp(float x) { float r; asm("rcp.approx.ftz.f32 %0, %1;" : "=f"(r) : "f"(x)); return r; }
__device__ __forceinline__ float ex2(float x) { float r; asm("ex2.approx.ftz.f32 %0, %1;" : "=f"(r) : "f"(x)); return r; }
__device__ __forceinline__ float tanh_(float x) { float t; asm("tanh.approx.f32 %0, %1;" : "=f"(t) : "f"(x)); return t; }
__device__ __forceinline__ void block_end(uint32_t opaque) { asm volatile("{\n.reg .pred p;\nsetp.eq.u32 p, %0, 0xffffffff;\n@p trap;\n}" :: "r"(opaque)); }
__device__ __forceinline__ float silu_(float x) { return __fdividef(x, 1.f + __expf(-x)); }
__device__ __forceinline__ void st_pkt(void* p, uint32_t a, uint32_t b) {
    asm volatile("{\n.reg .b64 t;\nmov.b64 t, {%1, %2};\nst.relaxed.gpu.global.b64 [%0], t;\n}" :: "l"(p), "r"(a), "r"(b) : "memory");
}
__device__ __forceinline__ uint4 ld_pkt2(const void* p) {
    uint4 v; asm volatile("{\n.reg .b64 t, u;\nld.relaxed.gpu.global.v2.b64 {t, u}, [%4];\nmov.b64 {%0, %1}, t;\nmov.b64 {%2, %3}, u;\n}"
        : "=r"(v.x), "=r"(v.y), "=r"(v.z), "=r"(v.w) : "l"(p) : "memory"); return v;
}
__device__ __forceinline__ void st_pkt16(void* p, uint32_t a, uint32_t b, uint32_t c, uint32_t d) {
    asm volatile("{\n.reg .b64 t, u;\n.reg .b128 w;\nmov.b64 t, {%1, %2};\nmov.b64 u, {%3, %4};\nmov.b128 w, {t, u};\nst.relaxed.gpu.global.b128 [%0], w;\n}"
        :: "l"(p), "r"(a), "r"(b), "r"(c), "r"(d) : "memory");
}
__device__ __forceinline__ uint4 ld_pkt16(const void* p) {
    uint4 v; asm volatile("{\n.reg .b64 t, u;\n.reg .b128 w;\nld.relaxed.gpu.global.b128 w, [%4];\nmov.b128 {t, u}, w;\nmov.b64 {%0, %1}, t;\nmov.b64 {%2, %3}, u;\n}"
        : "=r"(v.x), "=r"(v.y), "=r"(v.z), "=r"(v.w) : "l"(p) : "memory"); return v;
}
#define SPIN_GUARD(n) do { if (++(n) > (1u << 22)) asm volatile("trap;"); } while (0)
__device__ __forceinline__ uint4 lds128(uint32_t a) { uint4 v; asm volatile("ld.shared.v4.u32 {%0, %1, %2, %3}, [%4];" : "=r"(v.x), "=r"(v.y), "=r"(v.z), "=r"(v.w) : "r"(a) : "memory"); return v; }
__device__ __forceinline__ void sts128(uint32_t a, uint32_t x, uint32_t y, uint32_t z, uint32_t w) { asm volatile("st.shared.v4.u32 [%0], {%1, %2, %3, %4};" :: "r"(a), "r"(x), "r"(y), "r"(z), "r"(w) : "memory"); }
__device__ __forceinline__ uint32_t lds32(uint32_t a) { uint32_t v; asm volatile("ld.shared.u32 %0, [%1];" : "=r"(v) : "r"(a) : "memory"); return v; }
__device__ __forceinline__ void sts32(uint32_t a, uint32_t v) { asm volatile("st.shared.u32 [%0], %1;" :: "r"(a), "r"(v) : "memory"); }
__device__ __forceinline__ bool elect_one() {
    uint32_t p; asm volatile("{\n.reg .pred q;\nelect.sync _|q, 0xffffffff;\nselp.u32 %0, 1, 0, q;\n}" : "=r"(p)); return p;
}
__device__ __forceinline__ void pause(uint32_t cycles) {
    uint32_t t0, t; asm volatile("mov.u32 %0, %%clock;" : "=r"(t0));
    do { __nanosleep(64); asm volatile("mov.u32 %0, %%clock;" : "=r"(t)); } while (t - t0 < cycles);
}
__device__ __forceinline__ void spin(uint32_t cycles) {
    uint32_t t0, t; asm volatile("mov.u32 %0, %%clock;" : "=r"(t0));
    do { asm volatile("mov.u32 %0, %%clock;" : "=r"(t)); } while (t - t0 < cycles);
}
__device__ __forceinline__ void cluster_arrive() { asm volatile("barrier.cluster.arrive.relaxed.aligned;" ::: "memory"); }
__device__ __forceinline__ void cluster_wait() { asm volatile("barrier.cluster.wait.aligned;" ::: "memory"); }

__device__ __forceinline__ void wgmma_n128_z(float (&d)[64], uint64_t da, uint64_t db) {
    asm volatile("{\n.reg .pred p;\nsetp.ne.b32 p, 0, 0;\n"
        "wgmma.mma_async.sync.aligned.m64n128k16.f32.bf16.bf16 {"
        "%0, %1, %2, %3, %4, %5, %6, %7, %8, %9, %10, %11, %12, %13, %14, %15, "
        "%16, %17, %18, %19, %20, %21, %22, %23, %24, %25, %26, %27, %28, %29, %30, %31, "
        "%32, %33, %34, %35, %36, %37, %38, %39, %40, %41, %42, %43, %44, %45, %46, %47, "
        "%48, %49, %50, %51, %52, %53, %54, %55, %56, %57, %58, %59, %60, %61, %62, %63"
        "}, %64, %65, p, 1, 1, 0, 1;\n}\n"
        : "=f"(d[0]), "=f"(d[1]), "=f"(d[2]), "=f"(d[3]), "=f"(d[4]), "=f"(d[5]), "=f"(d[6]), "=f"(d[7]),
          "=f"(d[8]), "=f"(d[9]), "=f"(d[10]), "=f"(d[11]), "=f"(d[12]), "=f"(d[13]), "=f"(d[14]), "=f"(d[15]),
          "=f"(d[16]), "=f"(d[17]), "=f"(d[18]), "=f"(d[19]), "=f"(d[20]), "=f"(d[21]), "=f"(d[22]), "=f"(d[23]),
          "=f"(d[24]), "=f"(d[25]), "=f"(d[26]), "=f"(d[27]), "=f"(d[28]), "=f"(d[29]), "=f"(d[30]), "=f"(d[31]),
          "=f"(d[32]), "=f"(d[33]), "=f"(d[34]), "=f"(d[35]), "=f"(d[36]), "=f"(d[37]), "=f"(d[38]), "=f"(d[39]),
          "=f"(d[40]), "=f"(d[41]), "=f"(d[42]), "=f"(d[43]), "=f"(d[44]), "=f"(d[45]), "=f"(d[46]), "=f"(d[47]),
          "=f"(d[48]), "=f"(d[49]), "=f"(d[50]), "=f"(d[51]), "=f"(d[52]), "=f"(d[53]), "=f"(d[54]), "=f"(d[55]),
          "=f"(d[56]), "=f"(d[57]), "=f"(d[58]), "=f"(d[59]), "=f"(d[60]), "=f"(d[61]), "=f"(d[62]), "=f"(d[63])
        : "l"(da), "l"(db));
}
__device__ __forceinline__ void wgmma_n128(float (&d)[64], uint64_t da, uint64_t db) {
    asm volatile("{\n.reg .pred p;\nsetp.eq.b32 p, 0, 0;\n"
        "wgmma.mma_async.sync.aligned.m64n128k16.f32.bf16.bf16 {"
        "%0, %1, %2, %3, %4, %5, %6, %7, %8, %9, %10, %11, %12, %13, %14, %15, "
        "%16, %17, %18, %19, %20, %21, %22, %23, %24, %25, %26, %27, %28, %29, %30, %31, "
        "%32, %33, %34, %35, %36, %37, %38, %39, %40, %41, %42, %43, %44, %45, %46, %47, "
        "%48, %49, %50, %51, %52, %53, %54, %55, %56, %57, %58, %59, %60, %61, %62, %63"
        "}, %64, %65, p, 1, 1, 0, 1;\n}\n"
        : "+f"(d[0]), "+f"(d[1]), "+f"(d[2]), "+f"(d[3]), "+f"(d[4]), "+f"(d[5]), "+f"(d[6]), "+f"(d[7]),
          "+f"(d[8]), "+f"(d[9]), "+f"(d[10]), "+f"(d[11]), "+f"(d[12]), "+f"(d[13]), "+f"(d[14]), "+f"(d[15]),
          "+f"(d[16]), "+f"(d[17]), "+f"(d[18]), "+f"(d[19]), "+f"(d[20]), "+f"(d[21]), "+f"(d[22]), "+f"(d[23]),
          "+f"(d[24]), "+f"(d[25]), "+f"(d[26]), "+f"(d[27]), "+f"(d[28]), "+f"(d[29]), "+f"(d[30]), "+f"(d[31]),
          "+f"(d[32]), "+f"(d[33]), "+f"(d[34]), "+f"(d[35]), "+f"(d[36]), "+f"(d[37]), "+f"(d[38]), "+f"(d[39]),
          "+f"(d[40]), "+f"(d[41]), "+f"(d[42]), "+f"(d[43]), "+f"(d[44]), "+f"(d[45]), "+f"(d[46]), "+f"(d[47]),
          "+f"(d[48]), "+f"(d[49]), "+f"(d[50]), "+f"(d[51]), "+f"(d[52]), "+f"(d[53]), "+f"(d[54]), "+f"(d[55]),
          "+f"(d[56]), "+f"(d[57]), "+f"(d[58]), "+f"(d[59]), "+f"(d[60]), "+f"(d[61]), "+f"(d[62]), "+f"(d[63])
        : "l"(da), "l"(db));
}
__device__ __forceinline__ void wgmma_n176_z(float (&d)[88], uint64_t da, uint64_t db) {
    asm volatile("{\n.reg .pred p;\nsetp.ne.b32 p, 0, 0;\n"
        "wgmma.mma_async.sync.aligned.m64n176k16.f32.bf16.bf16 {"
        "%0, %1, %2, %3, %4, %5, %6, %7, %8, %9, %10, %11, %12, %13, %14, %15, "
        "%16, %17, %18, %19, %20, %21, %22, %23, %24, %25, %26, %27, %28, %29, %30, %31, "
        "%32, %33, %34, %35, %36, %37, %38, %39, %40, %41, %42, %43, %44, %45, %46, %47, "
        "%48, %49, %50, %51, %52, %53, %54, %55, %56, %57, %58, %59, %60, %61, %62, %63, "
        "%64, %65, %66, %67, %68, %69, %70, %71, %72, %73, %74, %75, %76, %77, %78, %79, "
        "%80, %81, %82, %83, %84, %85, %86, %87"
        "}, %88, %89, p, 1, 1, 0, 1;\n}\n"
        : "=f"(d[0]), "=f"(d[1]), "=f"(d[2]), "=f"(d[3]), "=f"(d[4]), "=f"(d[5]), "=f"(d[6]), "=f"(d[7]),
          "=f"(d[8]), "=f"(d[9]), "=f"(d[10]), "=f"(d[11]), "=f"(d[12]), "=f"(d[13]), "=f"(d[14]), "=f"(d[15]),
          "=f"(d[16]), "=f"(d[17]), "=f"(d[18]), "=f"(d[19]), "=f"(d[20]), "=f"(d[21]), "=f"(d[22]), "=f"(d[23]),
          "=f"(d[24]), "=f"(d[25]), "=f"(d[26]), "=f"(d[27]), "=f"(d[28]), "=f"(d[29]), "=f"(d[30]), "=f"(d[31]),
          "=f"(d[32]), "=f"(d[33]), "=f"(d[34]), "=f"(d[35]), "=f"(d[36]), "=f"(d[37]), "=f"(d[38]), "=f"(d[39]),
          "=f"(d[40]), "=f"(d[41]), "=f"(d[42]), "=f"(d[43]), "=f"(d[44]), "=f"(d[45]), "=f"(d[46]), "=f"(d[47]),
          "=f"(d[48]), "=f"(d[49]), "=f"(d[50]), "=f"(d[51]), "=f"(d[52]), "=f"(d[53]), "=f"(d[54]), "=f"(d[55]),
          "=f"(d[56]), "=f"(d[57]), "=f"(d[58]), "=f"(d[59]), "=f"(d[60]), "=f"(d[61]), "=f"(d[62]), "=f"(d[63]),
          "=f"(d[64]), "=f"(d[65]), "=f"(d[66]), "=f"(d[67]), "=f"(d[68]), "=f"(d[69]), "=f"(d[70]), "=f"(d[71]),
          "=f"(d[72]), "=f"(d[73]), "=f"(d[74]), "=f"(d[75]), "=f"(d[76]), "=f"(d[77]), "=f"(d[78]), "=f"(d[79]),
          "=f"(d[80]), "=f"(d[81]), "=f"(d[82]), "=f"(d[83]), "=f"(d[84]), "=f"(d[85]), "=f"(d[86]), "=f"(d[87])
        : "l"(da), "l"(db));
}
__device__ __forceinline__ void wgmma_n176(float (&d)[88], uint64_t da, uint64_t db) {
    asm volatile("{\n.reg .pred p;\nsetp.eq.b32 p, 0, 0;\n"
        "wgmma.mma_async.sync.aligned.m64n176k16.f32.bf16.bf16 {"
        "%0, %1, %2, %3, %4, %5, %6, %7, %8, %9, %10, %11, %12, %13, %14, %15, "
        "%16, %17, %18, %19, %20, %21, %22, %23, %24, %25, %26, %27, %28, %29, %30, %31, "
        "%32, %33, %34, %35, %36, %37, %38, %39, %40, %41, %42, %43, %44, %45, %46, %47, "
        "%48, %49, %50, %51, %52, %53, %54, %55, %56, %57, %58, %59, %60, %61, %62, %63, "
        "%64, %65, %66, %67, %68, %69, %70, %71, %72, %73, %74, %75, %76, %77, %78, %79, "
        "%80, %81, %82, %83, %84, %85, %86, %87"
        "}, %88, %89, p, 1, 1, 0, 1;\n}\n"
        : "+f"(d[0]), "+f"(d[1]), "+f"(d[2]), "+f"(d[3]), "+f"(d[4]), "+f"(d[5]), "+f"(d[6]), "+f"(d[7]),
          "+f"(d[8]), "+f"(d[9]), "+f"(d[10]), "+f"(d[11]), "+f"(d[12]), "+f"(d[13]), "+f"(d[14]), "+f"(d[15]),
          "+f"(d[16]), "+f"(d[17]), "+f"(d[18]), "+f"(d[19]), "+f"(d[20]), "+f"(d[21]), "+f"(d[22]), "+f"(d[23]),
          "+f"(d[24]), "+f"(d[25]), "+f"(d[26]), "+f"(d[27]), "+f"(d[28]), "+f"(d[29]), "+f"(d[30]), "+f"(d[31]),
          "+f"(d[32]), "+f"(d[33]), "+f"(d[34]), "+f"(d[35]), "+f"(d[36]), "+f"(d[37]), "+f"(d[38]), "+f"(d[39]),
          "+f"(d[40]), "+f"(d[41]), "+f"(d[42]), "+f"(d[43]), "+f"(d[44]), "+f"(d[45]), "+f"(d[46]), "+f"(d[47]),
          "+f"(d[48]), "+f"(d[49]), "+f"(d[50]), "+f"(d[51]), "+f"(d[52]), "+f"(d[53]), "+f"(d[54]), "+f"(d[55]),
          "+f"(d[56]), "+f"(d[57]), "+f"(d[58]), "+f"(d[59]), "+f"(d[60]), "+f"(d[61]), "+f"(d[62]), "+f"(d[63]),
          "+f"(d[64]), "+f"(d[65]), "+f"(d[66]), "+f"(d[67]), "+f"(d[68]), "+f"(d[69]), "+f"(d[70]), "+f"(d[71]),
          "+f"(d[72]), "+f"(d[73]), "+f"(d[74]), "+f"(d[75]), "+f"(d[76]), "+f"(d[77]), "+f"(d[78]), "+f"(d[79]),
          "+f"(d[80]), "+f"(d[81]), "+f"(d[82]), "+f"(d[83]), "+f"(d[84]), "+f"(d[85]), "+f"(d[86]), "+f"(d[87])
        : "l"(da), "l"(db));
}
__device__ __forceinline__ void wgmma_n256_z(float (&d)[128], uint64_t da, uint64_t db) {
    asm volatile("{\n.reg .pred p;\nsetp.ne.b32 p, 0, 0;\n"
        "wgmma.mma_async.sync.aligned.m64n256k16.f32.bf16.bf16 {"
        "%0, %1, %2, %3, %4, %5, %6, %7, %8, %9, %10, %11, %12, %13, %14, %15, "
        "%16, %17, %18, %19, %20, %21, %22, %23, %24, %25, %26, %27, %28, %29, %30, %31, "
        "%32, %33, %34, %35, %36, %37, %38, %39, %40, %41, %42, %43, %44, %45, %46, %47, "
        "%48, %49, %50, %51, %52, %53, %54, %55, %56, %57, %58, %59, %60, %61, %62, %63, "
        "%64, %65, %66, %67, %68, %69, %70, %71, %72, %73, %74, %75, %76, %77, %78, %79, "
        "%80, %81, %82, %83, %84, %85, %86, %87, %88, %89, %90, %91, %92, %93, %94, %95, "
        "%96, %97, %98, %99, %100, %101, %102, %103, %104, %105, %106, %107, %108, %109, %110, %111, "
        "%112, %113, %114, %115, %116, %117, %118, %119, %120, %121, %122, %123, %124, %125, %126, %127"
        "}, %128, %129, p, 1, 1, 0, 1;\n}\n"
        : "=f"(d[0]), "=f"(d[1]), "=f"(d[2]), "=f"(d[3]), "=f"(d[4]), "=f"(d[5]), "=f"(d[6]), "=f"(d[7]),
          "=f"(d[8]), "=f"(d[9]), "=f"(d[10]), "=f"(d[11]), "=f"(d[12]), "=f"(d[13]), "=f"(d[14]), "=f"(d[15]),
          "=f"(d[16]), "=f"(d[17]), "=f"(d[18]), "=f"(d[19]), "=f"(d[20]), "=f"(d[21]), "=f"(d[22]), "=f"(d[23]),
          "=f"(d[24]), "=f"(d[25]), "=f"(d[26]), "=f"(d[27]), "=f"(d[28]), "=f"(d[29]), "=f"(d[30]), "=f"(d[31]),
          "=f"(d[32]), "=f"(d[33]), "=f"(d[34]), "=f"(d[35]), "=f"(d[36]), "=f"(d[37]), "=f"(d[38]), "=f"(d[39]),
          "=f"(d[40]), "=f"(d[41]), "=f"(d[42]), "=f"(d[43]), "=f"(d[44]), "=f"(d[45]), "=f"(d[46]), "=f"(d[47]),
          "=f"(d[48]), "=f"(d[49]), "=f"(d[50]), "=f"(d[51]), "=f"(d[52]), "=f"(d[53]), "=f"(d[54]), "=f"(d[55]),
          "=f"(d[56]), "=f"(d[57]), "=f"(d[58]), "=f"(d[59]), "=f"(d[60]), "=f"(d[61]), "=f"(d[62]), "=f"(d[63]),
          "=f"(d[64]), "=f"(d[65]), "=f"(d[66]), "=f"(d[67]), "=f"(d[68]), "=f"(d[69]), "=f"(d[70]), "=f"(d[71]),
          "=f"(d[72]), "=f"(d[73]), "=f"(d[74]), "=f"(d[75]), "=f"(d[76]), "=f"(d[77]), "=f"(d[78]), "=f"(d[79]),
          "=f"(d[80]), "=f"(d[81]), "=f"(d[82]), "=f"(d[83]), "=f"(d[84]), "=f"(d[85]), "=f"(d[86]), "=f"(d[87]),
          "=f"(d[88]), "=f"(d[89]), "=f"(d[90]), "=f"(d[91]), "=f"(d[92]), "=f"(d[93]), "=f"(d[94]), "=f"(d[95]),
          "=f"(d[96]), "=f"(d[97]), "=f"(d[98]), "=f"(d[99]), "=f"(d[100]), "=f"(d[101]), "=f"(d[102]), "=f"(d[103]),
          "=f"(d[104]), "=f"(d[105]), "=f"(d[106]), "=f"(d[107]), "=f"(d[108]), "=f"(d[109]), "=f"(d[110]), "=f"(d[111]),
          "=f"(d[112]), "=f"(d[113]), "=f"(d[114]), "=f"(d[115]), "=f"(d[116]), "=f"(d[117]), "=f"(d[118]), "=f"(d[119]),
          "=f"(d[120]), "=f"(d[121]), "=f"(d[122]), "=f"(d[123]), "=f"(d[124]), "=f"(d[125]), "=f"(d[126]), "=f"(d[127])
        : "l"(da), "l"(db));
}
__device__ __forceinline__ void wgmma_n256(float (&d)[128], uint64_t da, uint64_t db) {
    asm volatile("{\n.reg .pred p;\nsetp.eq.b32 p, 0, 0;\n"
        "wgmma.mma_async.sync.aligned.m64n256k16.f32.bf16.bf16 {"
        "%0, %1, %2, %3, %4, %5, %6, %7, %8, %9, %10, %11, %12, %13, %14, %15, "
        "%16, %17, %18, %19, %20, %21, %22, %23, %24, %25, %26, %27, %28, %29, %30, %31, "
        "%32, %33, %34, %35, %36, %37, %38, %39, %40, %41, %42, %43, %44, %45, %46, %47, "
        "%48, %49, %50, %51, %52, %53, %54, %55, %56, %57, %58, %59, %60, %61, %62, %63, "
        "%64, %65, %66, %67, %68, %69, %70, %71, %72, %73, %74, %75, %76, %77, %78, %79, "
        "%80, %81, %82, %83, %84, %85, %86, %87, %88, %89, %90, %91, %92, %93, %94, %95, "
        "%96, %97, %98, %99, %100, %101, %102, %103, %104, %105, %106, %107, %108, %109, %110, %111, "
        "%112, %113, %114, %115, %116, %117, %118, %119, %120, %121, %122, %123, %124, %125, %126, %127"
        "}, %128, %129, p, 1, 1, 0, 1;\n}\n"
        : "+f"(d[0]), "+f"(d[1]), "+f"(d[2]), "+f"(d[3]), "+f"(d[4]), "+f"(d[5]), "+f"(d[6]), "+f"(d[7]),
          "+f"(d[8]), "+f"(d[9]), "+f"(d[10]), "+f"(d[11]), "+f"(d[12]), "+f"(d[13]), "+f"(d[14]), "+f"(d[15]),
          "+f"(d[16]), "+f"(d[17]), "+f"(d[18]), "+f"(d[19]), "+f"(d[20]), "+f"(d[21]), "+f"(d[22]), "+f"(d[23]),
          "+f"(d[24]), "+f"(d[25]), "+f"(d[26]), "+f"(d[27]), "+f"(d[28]), "+f"(d[29]), "+f"(d[30]), "+f"(d[31]),
          "+f"(d[32]), "+f"(d[33]), "+f"(d[34]), "+f"(d[35]), "+f"(d[36]), "+f"(d[37]), "+f"(d[38]), "+f"(d[39]),
          "+f"(d[40]), "+f"(d[41]), "+f"(d[42]), "+f"(d[43]), "+f"(d[44]), "+f"(d[45]), "+f"(d[46]), "+f"(d[47]),
          "+f"(d[48]), "+f"(d[49]), "+f"(d[50]), "+f"(d[51]), "+f"(d[52]), "+f"(d[53]), "+f"(d[54]), "+f"(d[55]),
          "+f"(d[56]), "+f"(d[57]), "+f"(d[58]), "+f"(d[59]), "+f"(d[60]), "+f"(d[61]), "+f"(d[62]), "+f"(d[63]),
          "+f"(d[64]), "+f"(d[65]), "+f"(d[66]), "+f"(d[67]), "+f"(d[68]), "+f"(d[69]), "+f"(d[70]), "+f"(d[71]),
          "+f"(d[72]), "+f"(d[73]), "+f"(d[74]), "+f"(d[75]), "+f"(d[76]), "+f"(d[77]), "+f"(d[78]), "+f"(d[79]),
          "+f"(d[80]), "+f"(d[81]), "+f"(d[82]), "+f"(d[83]), "+f"(d[84]), "+f"(d[85]), "+f"(d[86]), "+f"(d[87]),
          "+f"(d[88]), "+f"(d[89]), "+f"(d[90]), "+f"(d[91]), "+f"(d[92]), "+f"(d[93]), "+f"(d[94]), "+f"(d[95]),
          "+f"(d[96]), "+f"(d[97]), "+f"(d[98]), "+f"(d[99]), "+f"(d[100]), "+f"(d[101]), "+f"(d[102]), "+f"(d[103]),
          "+f"(d[104]), "+f"(d[105]), "+f"(d[106]), "+f"(d[107]), "+f"(d[108]), "+f"(d[109]), "+f"(d[110]), "+f"(d[111]),
          "+f"(d[112]), "+f"(d[113]), "+f"(d[114]), "+f"(d[115]), "+f"(d[116]), "+f"(d[117]), "+f"(d[118]), "+f"(d[119]),
          "+f"(d[120]), "+f"(d[121]), "+f"(d[122]), "+f"(d[123]), "+f"(d[124]), "+f"(d[125]), "+f"(d[126]), "+f"(d[127])
        : "l"(da), "l"(db));
}

struct Idx {
    uint32_t lane, warp, w4, q4, g8, prow, pan;
    __device__ __forceinline__ Idx() {
        uint32_t t; asm volatile("mov.u32 %0, %%tid.x;" : "=r"(t));
        lane = t & 31; warp = t >> 5; w4 = warp & 3; q4 = lane & 3; g8 = lane >> 2;
        prow = w4 * 16 + ((lane >> 3) & 1) * 8 + (lane & 7);
        pan = prow * 128 + (((lane >> 4) ^ (lane & 7)) << 4);
    }
};
#define IDX() const Idx ix; const uint32_t lane = ix.lane, warp = ix.warp, w4 = ix.w4, q4 = ix.q4, g8 = ix.g8, prow = ix.prow, pan_addr = ix.pan; \
    (void)lane; (void)warp; (void)w4; (void)q4; (void)g8; (void)prow; (void)pan_addr;

__device__ __forceinline__ int kof(int t, int sh, int j) {
    const int p = t >> (sh - 1), pn = p < 2 ? p : p >= 9, q = p - 2 - 7 * pn;
    return ((p < 2 ? j : q + (q >= j)) << 7) + (pn << 6) + ((t & (sh - 1)) << 5);
}
__device__ __forceinline__ uint32_t fidx(uint32_t m, uint32_t w, uint32_t pn) {
    return FLAY == 0 ? m * 32 + w * 16 + pn : FLAY == 1 ? (m * 4 + w * 2 + (pn & 1)) * 32 + (pn >> 1) : FLAY == 2 ? (m * 32 + w * 16 + pn) * 32 : (m * 4 + w * 2 + (pn & 1)) * 64 + (pn >> 1) * 8;
}
constexpr int HC0 = 8 * 48, HC3 = HC0 + 3072;
__device__ __forceinline__ int hcol(int p, int j) { return HC0 + p * 1024 + j * 128; }
struct Ring {
    uint32_t slot, par;
    __device__ __forceinline__ void next() { if (++slot == NSLOT) { slot = 0; par ^= 1; } }
    __device__ __forceinline__ void skip(uint32_t n) { slot += n; if (slot >= NSLOT) { slot -= NSLOT; par ^= 1; } }
};
__device__ __forceinline__ uint32_t BAR_FULL(uint32_t sb, uint32_t s) { return sb + OFF_BAR + 8 * s; }
constexpr uint32_t AF_REL = 48;
__device__ __forceinline__ uint32_t BAR_EMPTY(uint32_t sb, uint32_t s) { return sb + OFF_BAR + 96 + 8 * s; }
__device__ __forceinline__ uint32_t BAR_SFULL(uint32_t sb, uint32_t i) { return sb + OFF_BAR + 152 + 8 * i; }
__device__ __forceinline__ uint32_t BAR_SREADY(uint32_t sb, uint32_t i) { return sb + OFF_BAR + 184 + 8 * i; }
__device__ __forceinline__ uint32_t BAR_ONE(uint32_t sb, uint32_t i) { return sb + OFF_BAR + 216 + 8 * i; }
enum { EV_WIN, EV_WIN1, EV_WIN2, EV_WIN3, EV_P0, EV_GA, EV_GB, EV_LN2, EV_LAG0, EV_LAG1, EV_LAG2, EV_LAG3, EV_LAG4, EV_LAG5, EV_KV, EV_P1, EV_GO, EV_PAR, EV_AGO, EV_AGO1, EV_AGO2, EV_FGO, EV_FGO1, EV_FGO2, EV_H0, EV_H1, EV_H2, EV_H3, EV_COUNT };
constexpr int NB_TAIL = 4;

struct Rel {
    uint32_t base; bool sig;
    __device__ __forceinline__ Rel(uint32_t sb, uint32_t tw) {
        uint32_t a; asm("mapa.shared::cluster.u32 %0, %1, %2;" : "=r"(a) : "r"(BAR_EMPTY(sb, 0)), "r"((tw >> 5) & 1));
        base = __shfl_sync(0xffffffffu, a, 0); sig = (tw & ~32u) == 0;
    }
    __device__ __forceinline__ void operator()(uint32_t slot) const {
        if (sig) asm volatile("mbarrier.arrive.shared::cluster.b64 _, [%0];" :: "r"(base + 8 * slot) : "memory");
    }
};
struct LnRow { float rs0, nm0, rs1, nm1; };
struct Pipe {
    Rel rel; uint32_t p1, p2;
    __device__ __forceinline__ Pipe(uint32_t sb, uint32_t tw, uint32_t first) : rel(sb, tw), p1(first), p2(NSLOT) {}
    template <bool TWO> __device__ __forceinline__ void acquire(uint32_t sb, uint32_t af, const Ring& r) {
        const uint32_t b0 = BAR_FULL(sb, r.slot), b1 = b0 + af;
        const bool ready = TWO ? mbar_test2(b0, b1, r.par) : mbar_test(b0, r.par);
        wg_wait<1>();
        rel(p2);
        if (!ready) { if (TWO) mbar_wait2(b0, b1, r.par); else mbar_wait(b0, r.par); }
    }
    __device__ __forceinline__ void issued(uint32_t slot) { p2 = p1; p1 = slot; }
    __device__ __forceinline__ void drain1() { wg_wait<1>(); rel(p2); p2 = NSLOT; }
    __device__ __forceinline__ void drain0() { wg_wait<0>(); rel(p1); p1 = NSLOT; }
    template <bool TWO, class Step> __device__ __forceinline__ void hold(int LG, uint32_t sb, uint32_t af, Ring& r, uint32_t lag_bar, Step step) {
        Ring q = r;
#pragma unroll 1
        for (int i = 0; i < LG; ++i) { if (TWO) mbar_wait2(BAR_FULL(sb, q.slot), BAR_FULL(sb, q.slot) + af, q.par); else mbar_wait(BAR_FULL(sb, q.slot), q.par); q.next(); }
        mbar_wait(lag_bar, 0);
#pragma unroll 1
        do {
            step(r.slot);
            wg_wait<2>(); rel(p2); p2 = p1; p1 = r.slot;
            if (++r.slot == NSLOT) r.slot = 0;
        } while (r.slot != q.slot);
        r.par = q.par;
    }
};
template <bool TWO, bool FIRST, int NA, int NB>
__device__ __forceinline__ void step32(float (&aa)[NA], float (&ab)[NB], uint32_t sb, uint32_t wg, uint32_t slot, int own) {
    const uint32_t st = d16(sb) + slot * (SLOT >> 4);
    const uint32_t alo = own >= 0 ? d16(sb) + OFF_STG / 16 + wg * 1024 + (own >> 1) * 512 + (own & 1) * 4 : st + wg * 256;
    const uint32_t ahi = own >= 0 ? (1024 >> 4) | (1u << 30) : (512 >> 4) | (2u << 30);
    wg_fence();
#pragma unroll
    for (int k = 0; k < 2; ++k) {
        const uint64_t da = ((uint64_t)ahi << 32) | (alo + k * 2 + 0x10000);
        if constexpr (NA == 88) {
            const uint64_t d0 = mk_desc(st, 8192 + k * 2048, 8192, 1024, 1), d1 = mk_desc(st, 12288 + k * 2048, 8192, 1024, 1);
            if (FIRST && k == 0) { wgmma_n176_z(aa, da, d0); wgmma_n176_z(ab, da, d1); }
            else { wgmma_n176(aa, da, d0); wgmma_n176(ab, da, d1); }
        } else {
            const uint64_t d0 = mk_desc(st, 8192 + k * 2048, 4096, 1024, 1), d1 = mk_desc(st, 24576 + k * 2048, 4096, 1024, 1);
            if (FIRST && k == 0) { wgmma_n256_z(aa, da, d0); if constexpr (TWO) wgmma_n128_z(ab, da, d1); }
            else { wgmma_n256(aa, da, d0); if constexpr (TWO) wgmma_n128(ab, da, d1); }
        }
    }
    wg_commit();
}
template <bool TWO, int LG, int NA, int NB, class Tail>
__device__ __forceinline__ void mainloop32(float (&aa)[NA], float (&ab)[NB], uint32_t sb, uint32_t wg, uint32_t tw, Ring& r, uint32_t lag_ev, int g0, Tail tail) {
    mbar_wait(BAR_FULL(sb, r.slot), r.par);
    step32<TWO, true>(aa, ab, sb, wg, r.slot, TWO ? 0 : -1);
    TS(g0, 0);
    Pipe pp(sb, tw, r.slot);
    r.next();
    const int end = wg ? 32 : 32 - LG;
#pragma unroll 1
    for (int it = 1; it < end; ++it) {
        pp.acquire<TWO>(sb, wg ? 0 : AF_REL, r);
        step32<TWO, false>(aa, ab, sb, wg, r.slot, TWO && it < 4 ? it : -1);
        pp.issued(r.slot);
        TS(g0 + it, 0);
        r.next();
    }
    if (wg == 0) { pp.drain1(); pp.drain0(); pp.hold<TWO>(LG, sb, AF_REL, r, BAR_ONE(sb, lag_ev), [&](uint32_t slot) { step32<TWO, false>(aa, ab, sb, 0, slot, -1); }); }
    pp.drain1();
    if (wg == 1 && tw == 0) mbar_arrive(BAR_ONE(sb, lag_ev));
    tail();
    pp.drain0();
    TS(g0 + 31, 1);
}
template <bool FIRST>
__device__ __forceinline__ void step64(float (&acc)[64], uint32_t sb, uint32_t wg, uint32_t slot, int own) {
    const uint32_t sbb = d16(sb) + slot * (SLOT >> 4), sa = own >= 0 ? d16(sb) + OFF_STG / 16 + wg * 1024 + own * 512 : sbb + wg * 512;
    wg_fence();
#pragma unroll
    for (int k = 0; k < 4; ++k) {
        const uint64_t da = mk_desc(sa, k * 32, 16, 1024, 1), db = mk_desc(sbb, 16384 + k * 2048, 8192, 1024, 1);
        if (FIRST && k == 0) wgmma_n128_z(acc, da, db); else wgmma_n128(acc, da, db);
    }
    wg_commit();
}
template <class Mid>
__device__ __forceinline__ void mainloop64(float (&acc)[64], bool wo, uint32_t sb, uint32_t wg, uint32_t tw, Ring& r, Mid mid) {
    const int g0 = wo ? 32 : 144, nst = wo ? 16 : 56, lg = wo ? LAGW : LAGD; (void)g0;
    const uint32_t lag_bar = BAR_ONE(sb, wo ? EV_LAG4 : EV_LAG5), af = wo && !wg ? AF_REL : 0;
    mbar_wait(BAR_FULL(sb, r.slot), r.par);
    if (!wo) CS(28);
    step64<true>(acc, sb, wg, r.slot, wo ? 0 : -1);
    if (!wo) CS(29);
    TS(g0, 0);
    Pipe pp(sb, tw, r.slot);
    r.next();
    int it = 1;
    auto run = [&](int end, int own) {
#pragma unroll 1
        do {
            pp.acquire<true>(sb, af, r);
            step64<false>(acc, sb, wg, r.slot, own);
            pp.issued(r.slot);
            TS(g0 + it, 0);
            if (wo && it == 2) CS(9);
            r.next();
            if (own > 0) {
                own = -1;
                pp.drain1(); pp.drain0();
                TS(g0 + 1, 1);
            }
        } while (++it < end);
    };
    const int end = wg ? nst : nst - lg;
    run(wo ? MIDW : wg ? MIDD : end, wo ? 1 : -1);
    mid();
    if (it < end) run(end, -1);
    if (wg == 0) { pp.drain1(); pp.drain0(); pp.hold<true>(lg, sb, af, r, lag_bar, [&](uint32_t slot) { step64<false>(acc, sb, 0, slot, -1); }); }
    pp.drain1();
    if (wg == 1 && tw == 0) mbar_arrive(lag_bar);
    pp.drain0();
    TS(g0 + nst - 1, 1);
}

struct RowAcc {
    float sm[4] = {0.f, 0.f, 0.f, 0.f}, sq[4] = {0.f, 0.f, 0.f, 0.f};
    __device__ __forceinline__ void add(int e, float x) { sm[e & 3] += x; sq[e & 3] = fmaf(x, x, sq[e & 3]); }
    __device__ __forceinline__ void publish(uint4* dst, uint32_t q4, uint32_t ep) const {
        const float s0 = sm[0] + sm[1], s1 = sm[2] + sm[3], q0 = sq[0] + sq[1], q1 = sq[2] + sq[3];
        const bool od = q4 & 1;
        float sv = (od ? s1 : s0) + __shfl_xor_sync(0xffffffffu, od ? s0 : s1, 1), qv = (od ? q1 : q0) + __shfl_xor_sync(0xffffffffu, od ? q0 : q1, 1);
        sv += __shfl_xor_sync(0xffffffffu, sv, 2); qv += __shfl_xor_sync(0xffffffffu, qv, 2);
        if (q4 < 2) st_pkt16(dst + q4 * 8, 0, __float_as_uint(sv), __float_as_uint(qv), ep);
    }
};
__device__ __forceinline__ LnRow merge_stats(const uint4* src, uint32_t q4, uint32_t ep, uint32_t sb) {
    uint4 t[4];
    uint32_t n = 0;
    while (true) {
#pragma unroll
        for (int i = 0; i < 4; ++i) t[i] = ld_pkt16(src + (q4 * 2 + (i >> 1)) * 512 + (i & 1) * 8);
        const bool ok_ = __all_sync(0xffffffffu, t[0].w == ep && t[1].w == ep && t[2].w == ep && t[3].w == ep);
        if (n < 4) CS(14 + n);
        if (ok_) break;
        SPIN_GUARD(n);
    }
    float v[4];
#pragma unroll
    for (int h = 0; h < 2; ++h) { v[h] = __uint_as_float(t[h].y) + __uint_as_float(t[2 + h].y); v[2 + h] = __uint_as_float(t[h].z) + __uint_as_float(t[2 + h].z); }
#pragma unroll
    for (int o = 1; o < 4; o <<= 1)
#pragma unroll
        for (int i = 0; i < 4; ++i) v[i] += __shfl_xor_sync(0xffffffffu, v[i], o);
    const float m0 = v[0] * (1.f / D_), m1 = v[1] * (1.f / D_);
    const float r0 = rsqrtf(fmaxf(fmaf(-m0, m0, v[2] * (1.f / D_)), 0.f) + 1e-5f), r1 = rsqrtf(fmaxf(fmaf(-m1, m1, v[3] * (1.f / D_)), 0.f) + 1e-5f);
    return LnRow{r0, -m0 * r0, r1, -m1 * r1};
}
struct Stg {
    uint32_t b, par;
    __device__ __forceinline__ uint32_t acquire2(uint32_t sb, uint32_t wg) {
        mbar_wait2(BAR_SREADY(sb, wg * 2), BAR_SREADY(sb, wg * 2 + 1), par);
        par ^= 1;
        return sb + OFF_STG + wg * 16384;
    }
    __device__ __forceinline__ void publish(uint32_t sb, uint32_t wg, uint32_t lane) {
        fence_async_smem();
        __syncwarp();
        if (lane == 0) mbar_arrive(BAR_SFULL(sb, wg * 2 + b));
        b ^= 1;
    }
};

struct LnPar {
    uint4 p[8];
    __device__ __forceinline__ void load(uint32_t sb, uint32_t q4) {
#pragma unroll
        for (int i = 0; i < 8; ++i) p[i] = lds128(sb + OFF_PAR + i * 64 + q4 * 16);
    }
};
__device__ __forceinline__ void ln_norm(uint32_t (&xn)[32], const float (&x)[64], const LnRow& n) {
#pragma unroll
    for (int e = 0; e < 32; ++e) {
        const float rs = (e & 1) ? n.rs1 : n.rs0, nm = (e & 1) ? n.nm1 : n.nm0;
        xn[e] = pack2(fmaf(x[2 * e], rs, nm), fmaf(x[2 * e + 1], rs, nm));
    }
}
__device__ __forceinline__ void ln_emit(const uint32_t (&xr)[32], const LnPar& lp, uint32_t sb, uint32_t wg, const Idx& ix) {
#pragma unroll
    for (int i = 0; i < 8; ++i)
        stsm4(sb + OFF_STG + wg * 16384 + (i >> 2) * 8192 + (ix.pan ^ ((i & 3) << 5)), hfma2_bf16(xr[4 * i], lp.p[i].z, lp.p[i].x), hfma2_bf16(xr[4 * i + 1], lp.p[i].z, lp.p[i].x),
              hfma2_bf16(xr[4 * i + 2], lp.p[i].w, lp.p[i].y), hfma2_bf16(xr[4 * i + 3], lp.p[i].w, lp.p[i].y));
    fence_async_smem();
    __syncwarp();
    if (ix.lane < 2) mbar_arrive(BAR_SFULL(sb, wg * 2 + ix.lane));
    bar_sync(1 + wg, 128);
}
__device__ __forceinline__ void load_slab(uint32_t (&xr)[32], uint32_t buf) {
    IDX();
#pragma unroll
    for (int i = 0; i < 8; ++i) ldsm4(buf + (i >> 2) * 8192 + (pan_addr ^ ((i & 3) << 5)), xr[4 * i], xr[4 * i + 1], xr[4 * i + 2], xr[4 * i + 3]);
}
__device__ __forceinline__ void unpack_slab(float (&x)[64], const uint32_t (&xr)[32]) {
#pragma unroll
    for (int i = 0; i < 32; ++i) unpack2(xr[i], x[2 * i], x[2 * i + 1]);
}
__device__ __forceinline__ void store_slab(const float (&x)[64], uint32_t buf, uint32_t pitch, uint32_t pan, int i0, int i1) {
#pragma unroll
    for (int i = i0; i < i1; ++i)
        stsm4(buf + (i >> 2) * pitch + (pan ^ ((i & 3) << 5)), pack2(x[8 * i], x[8 * i + 1]), pack2(x[8 * i + 2], x[8 * i + 3]), pack2(x[8 * i + 4], x[8 * i + 5]), pack2(x[8 * i + 6], x[8 * i + 7]));
}
__device__ __forceinline__ void fetch_halo(uint4* src, bool first, uint32_t sb, uint32_t W, uint32_t lane) {
    mbar_wait(BAR_ONE(sb, EV_KV), 0);
    mbar_wait2(BAR_SREADY(sb, 0), BAR_SREADY(sb, 1), 1);
    uint4 hv[8];
    uint32_t n = 0;
    while (true) {
        bool ok = true;
#pragma unroll
        for (int i = 0; i < 8; ++i) { hv[i] = first ? make_uint4(0, 0, 0, 0) : ld_pkt16(src + i * 32); ok = ok && hv[i].x != 0; }
        if (first || __all_sync(0xffffffffu, ok)) break;
        SPIN_GUARD(n);
    }
#pragma unroll
    for (int i = 0; i < 8; ++i) stsm4(sb + OFF_STG + W * 2048 + (i >> 2) * 8192 + (i & 3) * 512 + lane * 16, hv[i].x, hv[i].y, hv[i].z, hv[i].w);
    bar_arrive(NB_TAIL + W, 64);
    if (!first) {
#pragma unroll
        for (int i = 0; i < 8; ++i) src[i * 32] = make_uint4(0, 0, 0, 0);
    }
}

template <int NG, class G, class U, class Buf>
__device__ __forceinline__ void glu(uint32_t sb, uint32_t wg, G g, U u, Buf buf) {
    IDX();
#pragma unroll
    for (int k = 0; k < NG; ++k) {
        float h[8];
#pragma unroll
        for (int e = 0; e < 8; ++e) h[e] = fmaf(tanh_(g(8 * k + e)), u(8 * k + e), u(8 * k + e));
        stsm4(buf(k >> 2) + (pan_addr ^ ((k & 3) << 5)), pack2(h[0], h[1]), pack2(h[2], h[3]), pack2(h[4], h[5]), pack2(h[6], h[7]));
    }
    fence_async_smem();
    __syncwarp();
    if (lane < 2) mbar_arrive(BAR_SFULL(sb, wg * 2 + lane));
}

template <int NP>
__device__ __forceinline__ void passes128(uint32_t sb, uint32_t wg, uint32_t tw, Ring& r, Stg& stg) {
#pragma unroll 1
    for (int p = 0; p < NP; ++p) {
        float b256[128], none[1];
        mainloop32<false, LAGS>(b256, none, sb, wg, tw, r, EV_LAG2 + p, 80 + 32 * (p & 1), [&] { stg.acquire2(sb, wg); });
        if (threadIdx.x == 0) { TL(29 + 2 * p); TC(114 + 2 * p); }
        if (threadIdx.x == 128) TL(53 + 2 * (p & 1));
        CS(24 + 2 * (p & 1));
        glu<8>(sb, wg, [&](int i) { return b256[i + (i & 32)]; }, [&](int i) { return b256[i + (i & 32) + 32]; }, [&](int pn) { return sb + OFF_STG + wg * 16384 + pn * 8192; });
        if (threadIdx.x == 0) { TL(30 + 2 * p); TC(115 + 2 * p); }
        if (threadIdx.x == 128) TL(54 + 2 * (p & 1));
        CS(25 + 2 * (p & 1));
    }
}

__global__ void __launch_bounds__(384, 1)
fused_block_kernel(const __grid_constant__ Ptrs pt, const __grid_constant__ Maps mp) {
    uint32_t* const g_flags = pt.mail->flags;
    uint2* const g_mod = pt.mail->mod;
    uint4* const g_st1 = pt.mail->st1;
    uint32_t* const g_par2 = pt.mail->par2;
    uint4* const g_halo = pt.mail->halo;
    const __nv_bfloat16* __restrict__ cvec = pt.c;
    if (threadIdx.x == 224) { prefetch_map(&mp.wm8); prefetch_map(&mp.x); }
    extern __shared__ __align__(1024) uint8_t smem[];
    const uint32_t sb = smem_u32(smem);
    const uint32_t tid = threadIdx.x, tw = tid & 127, lane = tid & 31;
    const uint32_t warp = __shfl_sync(0xffffffffu, tid >> 5, 0), wg = warp >> 2;
    uint32_t rank; asm("mov.u32 %0, %%cluster_ctarank;" : "=r"(rank));
    rank = __shfl_sync(0xffffffffu, rank, 0);
    uint32_t ep;
    uint32_t smid; asm volatile("mov.u32 %0, %%smid;" : "=r"(smid));
    const int c = __shfl_sync(0xffffffffu, smid >> 1, 0);
    const int c7 = ((c - 32) * 37) >> 8;
    const int grp = c < 32 ? c & 7 : c < 60 ? c - 31 - 7 * c7 : c < 62 ? -1 : 0;
    const int j = c < 32 ? c >> 3 : c < 60 ? 4 + c7 : c < 62 ? (c - 60) * 2 + rank : c - 58;
    const bool aux = grp < 0;
    const int m = grp * 2 + rank;
    uint4* const g_st2 = g_halo + (m > 0 ? (m - 1) * 8 * 512 : 128);

    bool cluster_arrive_early = false;
    if (wg < 2) {
      if (!KDEBUG) cluster_arrive();
      ep = flag_get(g_flags + FL_DONE);
      uint16_t cw[8];
      {
          const __nv_bfloat16* cp = cvec + ((tw >> 5) * 32 + (tw & 3) * 2) * 8 + (lane >> 2);
#pragma unroll
          for (int i = 0; i < 8; ++i) asm volatile("ld.global.nc.u16 %0, [%1];" : "=h"(cw[i]) : "l"(cp + (i >> 1) * 64 + (i & 1) * 8));
      }
      asm volatile("setmaxnreg.inc.sync.aligned.u32 224;");
      if (tid == 0) TL(58);
      if (KDEBUG) cluster_arrive();
      Ring r{0, 0};
      Stg stg{0, 0};
      if (aux) {
        if (wg == 0) {
            const uint4 cv = *(const uint4*)(cvec + tw * 8);
            sts128(sb + OFF_STG + (tw >> 3) * 1024 + (tw & 7) * 16, pack2(silu_(bf_lo(cv.x)), silu_(bf_hi(cv.x))), pack2(silu_(bf_lo(cv.y)), silu_(bf_hi(cv.y))),
                   pack2(silu_(bf_lo(cv.z)), silu_(bf_hi(cv.z))), pack2(silu_(bf_lo(cv.w)), silu_(bf_hi(cv.w))));
            fence_async_smem();
        }
        cluster_wait();
        ep = __shfl_sync(0xffffffffu, ep, 0) / NCTA + 1;
        if (wg == 0) {
            if (tw == 0) {
                uint32_t n = 0;
                while (ld_pkt16(pt.mail->mod1 + 256).z != ep) { SPIN_GUARD(n); __nanosleep(200); }
                if (GODLY) __nanosleep(GODLY);
                mbar_arrive(BAR_ONE(sb, EV_GO));
            }
            bar_sync(1, 128);
#pragma unroll 1
            for (int p = 0; p < 4; ++p) {
                float acc[128];
#pragma unroll
                for (int i = 0; i < 128; ++i) acc[i] = 0.f;
                uint32_t prev = 0;
#pragma unroll 1
                for (int kc = 0; kc < 16; ++kc) {
                    mbar_wait(BAR_FULL(sb, r.slot), r.par);
                    wg_fence();
#pragma unroll
                    for (int k = 0; k < 4; ++k)
                        wgmma_n256(acc, mk_desc(d16(sb) + kc * 64, OFF_STG + k * 32, 16, 0, 1), mk_desc(d16(sb) + r.slot * (SLOT >> 4), k * 2048, 8192, 1024, 1));
                    wg_commit();
                    wg_wait<1>();
                    if (kc > 0 && tw < 4) mbar_arrive(BAR_EMPTY(sb, prev));
                    prev = r.slot;
                    r.next();
                }
                wg_wait<0>();
                if (tw < 4) mbar_arrive(BAR_EMPTY(sb, prev));
                if (tw < 4) {
#pragma unroll
                    for (int jn = 0; jn < 32; ++jn) sts32(sb + OFF_TAB + (jn * 4 + tw) * 4, pack2(acc[jn * 4], acc[jn * 4 + 1]));
                }
                bar_sync(1, 128);
                const int vec = 2 + p, blk = p * 4 + j;
                const uint32_t val = lds32(sb + OFF_TAB + tw * 4);
                if (vec == 2 || vec == 5) st_pkt(g_mod + (8 + blk) * 128 + tw, val, ep);
                else {
                    const float one = vec == 4 ? 1.f : 0.f;
                    g_par2[((blk & 3) * 16 + (tw >> 3)) * 16 + (tw & 3) * 4 + (vec - 3) * 2 + ((tw >> 2) & 1)] =
                        pack2(0.5f * bf_round(one + bf_lo(val)), 0.5f * bf_round(one + bf_hi(val)));
                }
                bar_sync(1, 128);
                if (tw == 0) {
                    if (vec == 3 || vec == 4) asm volatile("red.release.gpu.global.add.u32 [%0], 1;" :: "l"(&g_flags[FL_LN2]) : "memory");
                    TL(1 + p);
                }
            }
            if (lane < 2) mbar_arrive_cta(BAR_ONE(sb, EV_P0), lane);
        }
        r = Ring{64 % NSLOT, (64 / NSLOT) & 1};
        mbar_wait(BAR_ONE(sb, EV_P0), 0);
        passes128<4>(sb, wg, tw, r, stg);
      } else {
        float xs[64];
        uint32_t xp[32];
        {
            IDX();
            if (q4 < 2) st_pkt16(g_st1 + (m * 8 + j) * 512 + wg * 64 + w4 * 16 + g8 + q4 * 8, 0, 0, 0, 0);
            if (warp == 0) st_pkt16(pt.mail->mod1 + g8 * 512 + (m * 8 + j) * 4 + q4, 0, 0, 0, 0);
            sts128(sb + tid * 16, pack2(silu_(bf_lo(cw[0])), silu_(bf_lo(cw[1]))), pack2(silu_(bf_lo(cw[2])), silu_(bf_lo(cw[3]))),
                   pack2(silu_(bf_lo(cw[4])), silu_(bf_lo(cw[5]))), pack2(silu_(bf_lo(cw[6])), silu_(bf_lo(cw[7]))));
            cluster_wait();
            ep = __shfl_sync(0xffffffffu, ep, 0) / NCTA + 1;
            load_slab(xp, stg.acquire2(sb, wg));
            unpack_slab(xs, xp);
            if (tid == 0) TL(24);
            if (tid == 128) TL(27);
        }
#pragma unroll 1
        for (int blk = 0; ; ++blk) {
        {
            IDX();
            uint4* const st = (blk ? g_st2 : g_st1 + m * 8 * 512) + wg * 64 + w4 * 16 + g8;
            RowAcc ra;
#pragma unroll
            for (int e = 0; e < 64; ++e) ra.add(e, xs[e]);
            ra.publish(st + j * 512, q4, ep);
            uint32_t t_pub = 0; if (PDLY) asm volatile("mov.u32 %0, %%clock;" : "=r"(t_pub));
            if (tid == 0) TL(blk ? 9 : 26);
            if (tid == 128 && blk) TL(34);
            if (blk) CS(11);
            LnPar lp;
            if (blk == 0) {
            uint4* const mod_out = pt.mail->mod1 + g8 * 512 + (m * 8 + j) * 4 + q4;
            if (wg == 0) {
                uint4 af[8];
#pragma unroll
                for (int i = 0; i < 8; ++i) af[i] = lds128(sb + w4 * 512 + i * 64 + q4 * 16);
                float c[4][4] = {};
#pragma unroll
                for (int i = 0; i < 8; ++i) {
                    if (!(i & 1)) mbar_wait(BAR_ONE(sb, EV_WIN + (i >> 1)), 0);
                    if (i == 6 && tid == 0) TL(25);
#pragma unroll
                    for (int h = 0; h < 2; ++h) {
                        uint32_t b0, b1, b2, b3;
                        ldsm4t(sb + 5 * SLOT + i * 4096 + w4 * 1024 + h * 512 + (lane & 15) * 32 + (lane >> 4) * 16, b0, b1, b2, b3);
                        mma16816(c[2 * h], h ? af[i].z : af[i].x, 0u, h ? af[i].w : af[i].y, 0u, b0, b1);
                        mma16816(c[2 * h + 1], h ? af[i].z : af[i].x, 0u, h ? af[i].w : af[i].y, 0u, b2, b3);
                    }
                }
                if (lane < 4) sts128(sb + OFF_TAB + w4 * 64 + lane * 16, __float_as_uint(c[0][0] + c[2][0]), __float_as_uint(c[0][1] + c[2][1]),
                                     __float_as_uint(c[1][0] + c[3][0]), __float_as_uint(c[1][1] + c[3][1]));
                if (lane < 2) mbar_arrive_cta(BAR_ONE(sb, EV_P0), lane);
                bar_sync(1, 128);
                if (w4 == 0) {
                    float a[4] = {0.f, 0.f, 0.f, 0.f};
#pragma unroll
                    for (int i = 0; i < 4; ++i) {
                        const uint4 t = lds128(sb + OFF_TAB + i * 64 + q4 * 16);
                        a[0] += __uint_as_float(t.x); a[1] += __uint_as_float(t.y); a[2] += __uint_as_float(t.z); a[3] += __uint_as_float(t.w);
                    }
                    const float add = m >= 8 ? 1.f : 0.f;
                    st_pkt16(mod_out, pack2(bf_round(a[0]) + add, bf_round(a[1]) + add), pack2(bf_round(a[2]) + add, bf_round(a[3]) + add), ep, 0);
                    if (tid == 0) TL(3);
                }
            } else if (LWAIT >= 0) mbar_wait(BAR_ONE(sb, EV_WIN + LWAIT), 0);
            } else {
                mbar_wait(BAR_ONE(sb, EV_LN2), 0);
                stg.acquire2(sb, wg);
            }
            lp.load(sb, q4);
#pragma unroll
            for (int e = 0; e < 32; ++e) xp[e] = pack2(xs[2 * e], xs[2 * e + 1]);
            if (PDLY && blk) { uint32_t t1; do { asm volatile("mov.u32 %0, %%clock;" : "=r"(t1)); } while (t1 - t_pub < PDLY); }
            if (blk) CS(13);
            const LnRow n = merge_stats(st, q4, ep, sb);
            if (tid == 0) TL(blk ? 49 : 48);
            if (tid == 128) TL(blk ? 45 : 28);
            if (blk) CS(18);
            uint32_t xn[32];
            ln_norm(xn, xs, n);
            if (blk == 0) { mbar_wait(BAR_ONE(sb, EV_PAR), 0); lp.load(sb, q4); }
            ln_emit(xn, lp, sb, wg, ix);
            if (tid == 0) { TL(blk ? 36 : 8); TC(blk ? 109 : 103); }
            if (tid == 128) TL(blk ? 43 : 22);
            if (blk) CS(21);
        }
        if (blk == 0) {
        {
            float kv[128], qa[64];
            mbar_wait(BAR_FULL(sb, r.slot), r.par);
            step32<true, true>(kv, qa, sb, wg, r.slot, 0);
            TS(0, 0);
            Pipe pp(sb, tw, r.slot);
            r.next();
#pragma unroll 1
            for (int it = 1; it < 32 - LAGQ; ++it) {
                pp.acquire<true>(sb, wg ? 0 : AF_REL, r);
                step32<true, false>(kv, qa, sb, wg, r.slot, it < 4 ? it : -1);
                pp.issued(r.slot);
                TS(it, 0);
                r.next();
            }
            auto half = [&](uint32_t slot, bool q) {
                const uint32_t st = d16(sb) + slot * (SLOT >> 4);
#pragma unroll
                for (int k = 0; k < 2; ++k) {
                    const uint64_t da = mk_desc(st + wg * 256, k * 32, 16, 512, 2);
                    if (q) wgmma_n128(qa, da, mk_desc(st, 24576 + k * 2048, 4096, 1024, 1)); else wgmma_n256(kv, da, mk_desc(st, 8192 + k * 2048, 4096, 1024, 1));
                }
            };
            auto part = [&](bool q) {
                wg_fence();
#pragma unroll
                for (int it = 32 - LAGQ; it < 32; ++it) half(it % NSLOT, q);
                wg_commit();
            };
            stg.acquire2(sb, wg); mbar_wait2(BAR_SREADY(sb, 2), BAR_SREADY(sb, 3), 1);
            if (wg == 0) { pp.drain1(); pp.drain0(); }
#pragma unroll 1
            for (int it = 32 - LAGQ; it < 32; ++it) {
                pp.acquire<true>(sb, wg ? 0 : AF_REL, r);
                if (wg) { wg_fence(); half(r.slot, false); wg_commit(); }
                pp.issued(NSLOT);
                TS(it, 0);
                r.next();
            }
            if (wg == 0) { mbar_wait(BAR_ONE(sb, EV_LAG0), 0); part(false); part(true); wg_wait<1>(); }
            else { wg_wait<1>(); if (tw == 0) mbar_arrive(BAR_ONE(sb, EV_LAG0)); wg_wait<0>(); }
            CS(8);
            IDX();
            uint32_t k1[16], k2[16], v1[16], v2[16], qf[32];
#pragma unroll
            for (int i = 0; i < 128; ++i) asm volatile("" : "+f"(kv[i]) :: "memory");
#pragma unroll
            for (int t = 0; t < 16; ++t) k2[t] = pack2(kv[4 * t + 2], kv[4 * t + 3]);
#pragma unroll
            for (int t = 0; t < 16; ++t) k1[t] = pack2(kv[4 * t], kv[4 * t + 1]);
#pragma unroll
            for (int t = 0; t < 16; ++t) v2[t] = pack2(kv[64 + 4 * t + 2], kv[64 + 4 * t + 3]);
            const uint32_t nxt = warp + ((warp & 1) ? 3 : 1);
            if (nxt < 8) {
                const uint32_t dst = sb + OFF_STG + (nxt >> 2) * 16384 + (nxt & 3) * 2048 + lane * 16;
#pragma unroll
                for (int h = 0; h < 4; ++h) stsm4(dst + h * 512, k2[4 * h], k2[4 * h + 1], k2[4 * h + 2], k2[4 * h + 3]);
#pragma unroll
                for (int h = 0; h < 4; ++h) stsm4(dst + 8192 + h * 512, v2[4 * h], v2[4 * h + 1], v2[4 * h + 2], v2[4 * h + 3]);
                bar_arrive(NB_TAIL + nxt, 64);
            } else if (m < 15) {
                uint4* dst = g_halo + (m * 8 + j) * 512 + (w4 >> 1) * 256 + lane;
#pragma unroll
                for (int h = 0; h < 4; ++h) { if (!k2[4 * h]) k2[4 * h] = 0x8000u; if (!v2[4 * h]) v2[4 * h] = 0x8000u; }
#pragma unroll
                for (int h = 0; h < 4; ++h) st_pkt16(dst + h * 32, k2[4 * h], k2[4 * h + 1], k2[4 * h + 2], k2[4 * h + 3]);
#pragma unroll
                for (int h = 0; h < 4; ++h) st_pkt16(dst + 128 + h * 32, v2[4 * h], v2[4 * h + 1], v2[4 * h + 2], v2[4 * h + 3]);
            }
#pragma unroll
            for (int t = 0; t < 16; ++t) { v1[t] = pack2(kv[64 + 4 * t], kv[64 + 4 * t + 1]); v1[t] = movm(v1[t]); v2[t] = movm(v2[t]); }
            if (tid == 0) TL(33);
            CS(2);
            if (wg) part(true);
            bar_sync(NB_TAIL + warp, 64);
            CS(4);
            if (tid == 0) TL(5);
            uint32_t k0[16], v0[16];
            const uint32_t mine = sb + OFF_STG + wg * 16384 + w4 * 2048;
#pragma unroll
            for (int h = 0; h < 4; ++h) ldsm4(mine + lane * 16 + h * 512, k0[4 * h], k0[4 * h + 1], k0[4 * h + 2], k0[4 * h + 3]);
#pragma unroll
            for (int h = 0; h < 4; ++h) ldsm4t(mine + lane * 16 + 8192 + h * 512, v0[4 * h], v0[4 * h + 1], v0[4 * h + 2], v0[4 * h + 3]);
            wg_wait<0>();
#pragma unroll
            for (int it = 32 - LAGQ; it < 32; ++it) pp.rel(it % NSLOT);
            TS(31, 1);
            if (tid == 0) { TL(4); TC(104); }
            if (tid == 128) TL(50);
            CS(1);
#pragma unroll
            for (int i = 0; i < 64; ++i) asm volatile("" : "+f"(qa[i]) :: "memory");
            const bool lo0 = q4 * 2 > g8, lo1 = q4 * 2 + 1 > g8;
            const bool nopast = m == 0 && (warp & 5) == 0;
            const uint32_t lomask = (lo0 ? 0xFFFFu : 0u) | (lo1 ? 0xFFFF0000u : 0u);
            const uint32_t orow = mine + (lane & 7) * 128 + (((lane >> 3) ^ (lane & 7)) << 4);
            const float sl2 = 0.17677669529663687f * 1.4426950408889634f;
#pragma unroll
            for (int pn = 0; pn < 2; ++pn) {
                float e0[4], e1[4], mx[4], sum[4];
#pragma unroll
                for (int hh = 0; hh < 2; ++hh) {
                    const int h = pn * 2 + hh;
#pragma unroll
                    for (int i = 8 * h; i < 8 * h + 8; ++i) qf[i] = pack2(qa[2 * i], qa[2 * i + 1]);
                    float s[3][4];
#pragma unroll
                    for (int t = 0; t < 3; ++t) {
                        const uint32_t* k = (t == 0 ? k0 : t == 1 ? k1 : k2) + 4 * h;
                        s[t][0] = s[t][1] = s[t][2] = s[t][3] = 0.f;
                        mma16816(s[t], qf[h * 8], qf[h * 8 + 1], qf[h * 8 + 2], qf[h * 8 + 3], k[0], k[1]);
                        mma16816(s[t], qf[h * 8 + 4], qf[h * 8 + 5], qf[h * 8 + 6], qf[h * 8 + 7], k[2], k[3]);
                    }
#pragma unroll
                    for (int hf = 0; hf < 2; ++hf) {
                        const int u = hh * 2 + hf;
                        e0[u] = lo0 ? ((hf == 0 && nopast) ? -INFINITY : s[hf][hf * 2]) : s[hf + 1][hf * 2];
                        e1[u] = lo1 ? ((hf == 0 && nopast) ? -INFINITY : s[hf][hf * 2 + 1]) : s[hf + 1][hf * 2 + 1];
                        mx[u] = fmaxf(e0[u], e1[u]);
                    }
                }
#pragma unroll
                for (int o = 1; o < 4; o <<= 1)
#pragma unroll
                    for (int u = 0; u < 4; ++u) mx[u] = fmaxf(mx[u], __shfl_xor_sync(0xffffffffu, mx[u], o));
#pragma unroll
                for (int u = 0; u < 4; ++u) {
                    const float c = -mx[u] * sl2;
                    e0[u] = ex2(fmaf(e0[u], sl2, c)); e1[u] = ex2(fmaf(e1[u], sl2, c));
                    sum[u] = e0[u] + e1[u];
                }
#pragma unroll
                for (int o = 1; o < 4; o <<= 1)
#pragma unroll
                    for (int u = 0; u < 4; ++u) sum[u] += __shfl_xor_sync(0xffffffffu, sum[u], o);
#pragma unroll
                for (int u = 0; u < 4; ++u) {
                    const int h = pn * 2 + (u >> 1);
                    const float inv = rcp(sum[u]);
                    const uint32_t p = pack2(e0[u] * inv, e1[u] * inv);
                    const uint32_t* va = ((u & 1) ? v1 : v0) + 4 * h;
                    const uint32_t* vb = ((u & 1) ? v2 : v1) + 4 * h;
                    float o[2][4] = {};
#pragma unroll
                    for (int d = 0; d < 2; ++d) mma16816(o[d], va[2 * d], va[2 * d + 1], vb[2 * d], vb[2 * d + 1], p & lomask, p & ~lomask);
                    stsm4t((orow ^ ((u >> 1) << 6)) + pn * 8192 + (u & 1) * 1024, pack2(o[0][0], o[0][1]), pack2(o[0][2], o[0][3]), pack2(o[1][0], o[1][1]), pack2(o[1][2], o[1][3]));
                }
                fence_async_smem();
                __syncwarp();
                if (lane == 0) mbar_arrive(BAR_SFULL(sb, wg * 2 + pn));
                if (pn == 0) { CS(5); if (PSPLIT) block_end(sb); }
            }
            CS(6);
            if (tid == 32) TL(41);
            mbar_wait(BAR_FULL(sb, 32 % NSLOT + wg), (32 / NSLOT) & 1);
            load_slab(xp, sb + (32 % NSLOT + wg) * SLOT);
            bar_sync(1 + wg, 128);
            if (tid == 0) { TL(6); TC(106); }
            if (tid == 128) TL(44);
            CS(7);
        }
        } else {
        {
            float ag[88], au[88];
            mainloop32<true, LAG>(ag, au, sb, wg, tw, r, EV_LAG1, 48, [&] {
                stg.acquire2(sb, wg);
                Ring q = r; if (!wg) q.next();
                mbar_wait(BAR_EMPTY(sb, q.slot), q.par ^ 1);
            });
            if (tid == 0) { TL(10); TC(110); }
            if (tid == 128) TL(51);
            CS(22);
            glu<11>(sb, wg, [&](int i) { return ag[i]; }, [&](int i) { return au[i]; },
                    [&](int pn) { return pn < 2 ? sb + OFF_STG + wg * 16384 + pn * 8192 : sb + (wg ? P3_SLOT1 : P3_SLOT0) * SLOT + 24576; });
            if (tid == 0) { TL(11); TC(111); }
            if (tid == 128) TL(52);
            CS(23);
        }
        passes128<2>(sb, wg, tw, r, stg);
        if (tid == 0) { TL(12); TC(112); }
        }
        {
            float acc[64], gf[32];
            mainloop64(acc, blk == 0, sb, wg, tw, r, [&] {
                mbar_wait(BAR_ONE(sb, EV_GA + blk), 0);
                if (blk) stg.acquire2(sb, wg);
                unpack_slab(xs, xp);
                uint32_t gt[16];
#pragma unroll
                for (int cg = 0; cg < 16; ++cg) gt[cg] = lds32(sb + OFF_TAB + blk * 256 + cg * 16 + (tw & 3) * 4);
#pragma unroll
                for (int i = 0; i < 16; ++i) unpack2(gt[i], gf[2 * i], gf[2 * i + 1]);
            });
            if (tid == 0) { TL(blk ? 13 : 7); TC(blk ? 113 : 107); }
            if (tid == 128) TL(blk ? 57 : 42);
            CS(blk ? 30 : 10);
#pragma unroll
            for (int e = 0; e < 64; ++e) xs[e] = fmaf(gf[(e >> 2) * 2 + (e & 1)], acc[e], xs[e]);
        }
        if (blk) break;
        }
        cluster_arrive();
        {
            IDX();
#pragma unroll
            for (int p = 0; p < 2; ++p) {
                store_slab(xs, sb + OFF_STG + wg * 16384, 8192, pan_addr, 4 * p, 4 * p + 4);
                stg.publish(sb, wg, lane);
            }
            if (tid == 0) TL(14);
            CS(31);
        }
      }
    } else {
        if (warp == 8 && !aux && elect_one()) {
#pragma unroll
            for (int i = 0; i < 4; ++i) mbar_init(BAR_SREADY(sb, i), 1);
#pragma unroll
            for (int i = 0; i < 4; ++i) mbar_init(BAR_ONE(sb, EV_WIN + i), 1);
#pragma unroll
            for (int i = 0; i < 4; ++i) {
                mbar_expect_tx(BAR_SREADY(sb, i), 8192);
                tma_load3(sb + OFF_STG + i * 8192, &mp.x, j * 128 + (i & 1) * 64, m * 64 + (i >> 1) * 32, BAR_SREADY(sb, i));
            }
#pragma unroll 1
            for (int i = 0; i < 4; ++i) {
                mbar_expect_tx(BAR_ONE(sb, EV_WIN + i), 8192);
                tma_load(sb + 5 * SLOT + i * 8192, &mp.wm8, 2 * i * 6144 + (m * 8 + j) * 16, 0, BAR_ONE(sb, EV_WIN + i));
                tma_load(sb + 5 * SLOT + i * 8192 + 4096, &mp.wm8, (2 * i + 1) * 6144 + (m * 8 + j) * 16, 0, BAR_ONE(sb, EV_WIN + i));
            }
        }
        __syncwarp();
        asm volatile("setmaxnreg.dec.sync.aligned.u32 56;");
        if (elect_one()) {
            if (warp == 8) {
                prefetch_map(&mp.wqkv); prefetch_map(&mp.wmod);
            } else if (warp < 11) {
                mbar_init(BAR_EMPTY(sb, NSLOT), 1);
#pragma unroll
                for (int i = 0; i < 2; ++i) { mbar_init(BAR_SFULL(sb, (warp - 9) * 2 + i), 4); if (aux) mbar_init(BAR_SREADY(sb, (warp - 9) * 2 + i), 1); }
#pragma unroll
                for (int i = 0; i < 3; ++i) {
                    mbar_init(BAR_EMPTY(sb, (warp - 9) * 3 + i), 4);
                    mbar_init(BAR_FULL(sb, (warp - 9) * 3 + i), 1); mbar_init(BAR_FULL(sb, (warp - 9) * 3 + i) + AF_REL, 1);
                }
            } else {
#pragma unroll
                for (int i = EV_P0; i < EV_COUNT; ++i) mbar_init(BAR_ONE(sb, i), i == EV_P0 ? 8 : 1);
            }
            asm volatile("fence.mbarrier_init.release.cluster;" ::: "memory");
        }
        __syncwarp();
        cluster_arrive();
        ep = 0;
        if (warp != 8 || aux) ep = flag_get(g_flags + FL_DONE);
        cluster_wait();
        ep = __shfl_sync(0xffffffffu, ep, 0) / NCTA + 1;
        if (warp == 8) {
            const bool el = elect_one();
            Ring r{0, 1};
            if (aux) {
                mbar_wait(BAR_ONE(sb, EV_GO), 0);
#pragma unroll 1
                for (int it = 0; it < 64; ++it) {
                    const int col = 2048 + (it >> 4) * 1024 + j * 256;
                    mbar_wait(BAR_EMPTY(sb, r.slot), r.par);
                    const uint32_t st = sb + r.slot * SLOT, fb = BAR_FULL(sb, r.slot);
                    if (el) {
                        mbar_expect_tx(fb, 32768);
#pragma unroll
                        for (int b = 0; b < 4; ++b) tma_load(st + b * 8192, &mp.wmod, col + b * 64, (it & 15) * 64, fb);
                    }
                    r.next();
                }
                mbar_wait(BAR_ONE(sb, EV_P0), 0);
                const CUtensorMap* wm = rank ? &mp.wu : &mp.wg;
#pragma unroll 1
                for (int g = 0; g < 128; ++g) {
                    const int mx = (j >> 1) * 8 + (g >> 5) * 2 + rank, k0 = (g & 31) * 32;
                    if (k0 == 0) {
                        uint32_t n = 0;
                        while (!__all_sync(0xffffffffu, (int32_t)(flag_get(g_flags + FL_PROG + fidx(mx, lane >> 4, lane & 15)) - (ep * 8 + ST_H2)) >= 0)) { SPIN_GUARD(n); __nanosleep(500); }
                    }
                    mbar_wait(BAR_EMPTY(sb, r.slot), r.par);
                    const uint32_t st = sb + r.slot * SLOT, fb = BAR_FULL(sb, r.slot);
                    if (el) {
                        mbar_expect_tx(fb, 24576);
                        tma_load_mc(st + 8192 + rank * 4096, wm, HC3, k0, fb);
                        tma_load_mc(st + 16384 + rank * 4096, wm, HC3 + 64, k0, fb);
                        tma_load(st, &mp.h2l, k0, mx * 128, fb);
                    }
                    r.next();
                }
            } else {
#pragma unroll 1
                for (int it = 0; it < 32; ++it) {
                    const int cb = j * 128 + rank * 64, k0 = kof(it, 2, j);
                    if (it == BW0) mbar_wait(BAR_ONE(sb, BWEV), 0);
                    if (it == BW1) mbar_wait(BAR_ONE(sb, EV_PAR), 0);
                    if (it == 5) mbar_wait(BAR_ONE(sb, EV_P0), 0);
                    if (it == 6) mbar_wait(BAR_ONE(sb, (AGW & 1) ? EV_AGO : EV_FGO), 0);
                    mbar_wait(BAR_EMPTY(sb, r.slot), r.par);
                    const uint32_t st = sb + r.slot * SLOT, fb = BAR_FULL(sb, r.slot);
                    if (el) {
                        mbar_expect_tx(fb, it < 4 ? 24576 : 28672);
                        tma_load_mc(st + 8192 + rank * 4096, &mp.wqkv, 1024 + cb, k0, fb);
                        tma_load_mc(st + 16384 + rank * 4096, &mp.wqkv, 2048 + cb, k0, fb);
                        tma_load_mc(st + 24576 + rank * 4096, &mp.wqkv, cb, k0, fb);
                        if (it < 4) mbar_arrive(fb + AF_REL);
                        if (it == PFWO + (m >> 1)) { tma_prefetch(&mp.wo, j * 128, m * 64); tma_prefetch(&mp.wo, j * 128 + 64, m * 64); }
                    }
                    r.next();
                }
                if (el) mbar_arrive(BAR_ONE(sb, EV_KV));
#pragma unroll 1
                for (int it = 0; it < 16; ++it) {
                    const int k0 = kof(it, 1, j);
                    if (it == 6) mbar_wait(BAR_ONE(sb, (AGW & 2) ? EV_AGO1 : EV_FGO1), 0);
                    mbar_wait(BAR_EMPTY(sb, r.slot), r.par);
                    const uint32_t st = sb + r.slot * SLOT, fb = BAR_FULL(sb, r.slot);
                    if (el) {
                        mbar_expect_tx(fb, it < 2 ? 32768 : 24576);
                        tma_load_mc(st + 16384 + rank * 8192, &mp.wo, j * 128 + rank * 64, k0, fb);
                        if (it < 2) {
                            tma_load3(st, &mp.x, j * 128, m * 64 + it * 32, fb); tma_load3(st + 8192, &mp.x, j * 128 + 64, m * 64 + it * 32, fb);
                            mbar_arrive(fb + AF_REL);
                        }
                        if (it == 6) { prefetch_map(rank ? &mp.wu : &mp.wg); prefetch_map(rank ? &mp.wu3 : &mp.wg3); }
                    }
                    r.next();
                }
                const CUtensorMap* wm = rank ? &mp.wu : &mp.wg;
#pragma unroll 1
                for (int g = 0; g < 96; ++g) {
                    if (g == 6) mbar_wait(BAR_ONE(sb, (AGW & 4) ? EV_AGO2 : EV_FGO2), 0);
                    const int p = g >> 5, cb = hcol(p, j), k0 = p == 0 ? kof(g, 2, j) : (g & 31) * 32;
                    mbar_wait(BAR_EMPTY(sb, r.slot), r.par);
                    const uint32_t st = sb + r.slot * SLOT, fb = BAR_FULL(sb, r.slot);
                    if (el) {
                        mbar_expect_tx(fb, (g < 4 || p > 0) ? 24576 : 28672);
                        tma_load_mc(st + 8192 + rank * 4096, wm, cb, k0, fb);
                        tma_load_mc(st + 16384 + rank * 4096, wm, cb + 64, k0, fb);
                        if (p == 0) tma_load3_mc(st + 24576 + rank * 4096, rank ? &mp.wu3 : &mp.wg3, j, k0, fb);
                        else tma_load(st, &mp.h2l, k0, m * 128, fb);
                        if (g < 4) mbar_arrive(fb + AF_REL);
                        if (g == 60) prefetch_map(&mp.wd);
                    }
                    r.next();
                }
#pragma unroll 1
                for (int g = 0; g < 56; ++g) {
                    if (g == 0 || (g & 15) == 6 && g > 6) mbar_wait(BAR_ONE(sb, EV_H0 + (g >> 4)), 0);
                    const int k0 = g * 64;
                    mbar_wait(BAR_EMPTY(sb, r.slot), r.par);
                    const uint32_t st = sb + r.slot * SLOT, fb = BAR_FULL(sb, r.slot);
                    if (el) {
                        mbar_expect_tx(fb, 32768);
                        tma_load_mc(st + 16384 + rank * 8192, &mp.wd, j * 128 + rank * 64, k0, fb);
                        tma_load(st, &mp.hb, k0, m * 128, fb); tma_load(st + 8192, &mp.hb, k0, m * 128 + 64, fb);
                    }
                    r.next();
                }
            }
        } else if (aux) {
            if (warp < 11) {
                const uint32_t w = warp - 9;
                const bool el = elect_one();
#pragma unroll 1
                for (int p = 0; p < 4; ++p) {
                    const int mx = (j >> 1) * 8 + p * 2 + rank;
                    if (el) { mbar_arrive(BAR_SREADY(sb, w * 2)); mbar_arrive(BAR_SREADY(sb, w * 2 + 1)); }
                    mbar_wait2(BAR_SFULL(sb, w * 2), BAR_SFULL(sb, w * 2 + 1), p & 1);
                    if (el) {
                        tma_store(&mp.hb, HC3, mx * 128 + w * 64, sb + OFF_STG + w * 16384); tma_store(&mp.hb, HC3 + 64, mx * 128 + w * 64, sb + OFF_STG + w * 16384 + 8192);
                        bulk_commit(); bulk_wait_all(); flag_set(g_flags + FL_AUX + mx * 2 + w, ep * 8 + ST_H + 3);
                    }
                }
            }
        } else if (warp == 11) {
            const bool el = elect_one();
            const int row0 = m * 128;
            const uint32_t* const fl = g_flags + FL_PROG + fidx(m, lane >> 4, kof(lane & 15, 1, j) >> 6);
            if (el) { prefetch_map(&mp.h1h); prefetch_map(&mp.h2h); prefetch_map(&mp.h2l); }
            auto gate = [&](int vec, int ev) {
                uint4 v; uint32_t n = 0;
                while (true) {
                    v = ld_pkt2(g_mod + vec * 512 + j * 64 + lane * 2);
                    if (__all_sync(0xffffffffu, v.y == ep && v.w == ep)) break;
                    SPIN_GUARD(n); __nanosleep(300);
                }
                asm volatile("st.shared.v2.u32 [%0], {%1, %2};" :: "r"(sb + OFF_TAB + (ev - EV_GA) * 256 + lane * 8), "r"(v.x), "r"(v.z) : "memory");
                __syncwarp();
                if (lane == 0) mbar_arrive(BAR_ONE(sb, ev));
            };
            {
                const uint4* pk = pt.mail->mod1 + grp * 512 + j * 32 + lane;
                uint4 a, b; uint32_t n = 0;
                mbar_wait(BAR_ONE(sb, EV_WIN3), 0);
                while (true) {
                    a = ld_pkt16(pk); b = ld_pkt16(pk + 256);
                    if (__all_sync(0xffffffffu, a.z == ep && b.z == ep)) break;
                    SPIN_GUARD(n);
                }
                sts128(sb + OFF_PAR + lane * 16, a.x, a.y, b.x, b.y);
                __syncwarp();
                if (lane == 0) { mbar_arrive(BAR_ONE(sb, EV_PAR)); TL(46); }
            }
            mbar_wait(BAR_ONE(sb, EV_P0), 0);
            Ring r{0, 1};
#pragma unroll 1
            for (int ph = 0; ph < 3; ++ph) {
                const int sh = ph == 1 ? 1 : 2, nst = 8 << sh;
                const uint32_t half = 16384 >> sh, target = ep * 8 + ST_H1 + ph;
                const CUtensorMap* tm = ph == 0 ? &mp.h1h : ph == 1 ? &mp.o : &mp.h2h;
                if (ph == 1) gate(2, EV_GA);
                if (ph == 2) {
                    uint32_t n = 0;
                    while ((int32_t)(flag_get(g_flags + FL_LN2) - ep * 8) < 0) { SPIN_GUARD(n); __nanosleep(200); }
                    const uint4 v = __ldcg((const uint4*)(g_par2 + j * 128) + lane);
                    sts128(sb + OFF_PAR + lane * 16, v.x, v.y, v.z, v.w);
                    __syncwarp();
                    if (lane == 0) mbar_arrive(BAR_ONE(sb, EV_LN2));
                }
                const uint32_t lw = ~lane & 1, lt = lane >> 1, ls = (r.slot + lt) % NSLOT, lk = kof(lt, sh, j), lb = BAR_FULL(sb, ls) + (lw ? 0 : AF_REL);
                const uint32_t* const lf = g_flags + FL_PROG + fidx(m, lw, lk >> 6);
                int fr = 1 << sh;
                uint32_t todo = 0x3ffffu >> (2 * fr) << (2 * fr), have = ~todo, n = 0, v = 0;
                r.skip(fr);
#pragma unroll 1
                for (; fr < NSLOT; ++fr) { mbar_wait(BAR_EMPTY(sb, r.slot), r.par); r.next(); }
                if (PWAIT) mbar_wait(BAR_SFULL(sb, 2), ph & 1);
                if (PWAIT > 1) spin(PWAIT);
                if (ph == XST - 1) CS(33);
                do {
                    if (!PMASK || !((have >> lane) & 1)) v = flag_get(lf);
                    if (fr < P1AT && mbar_test(BAR_EMPTY(sb, r.slot), r.par)) { ++fr; r.next(); }
                    SPIN_GUARD(n);
                    have |= __ballot_sync(0xffffffffu, (int32_t)(v - target) >= 0);
                    const uint32_t go = have & todo & ((1u << (2 * fr)) - 1);
                    if ((go >> lane) & 1) {
                        if (!lw) mbar_expect_tx(lb, half);
                        tma_load(sb + ls * SLOT + lw * half, tm, lk, row0 + lw * 64, lb);
                    }
                    __syncwarp();
                    if (lane < 2 && (todo & (0x555u << lane)) && !(todo & ~go & (0x555u << lane))) mbar_arrive(BAR_ONE(sb, (lane ? EV_FGO : EV_AGO) + ph));
                    if (ph == XST - 1) { if (go & (1u << (2 << sh))) CS(34); if (go & (2u << (2 << sh))) CS(35); if (todo & 0x555u) CS(36); if (todo & 0xaaau) CS(37); }
                    todo &= ~go;
                    if (PGAP && !go) spin(PGAP);
                } while (~have);
                if (ph == XST - 1) CS(38);
#pragma unroll 1
                for (; fr < nst; ++fr) {
                    if (fr == P1AT && ph == 1 && el) mbar_arrive(BAR_ONE(sb, EV_P1));
                    if (fr == 9 || fr == 18) {
                        const uint32_t skip = fr == 9 << (sh - 1) ? 0 : ~0x01fc01fcu;
                        while (~(__ballot_sync(0xffffffffu, (int32_t)(flag_get(fl) - target) >= 0) | skip)) { SPIN_GUARD(n); if (PGAP) spin(PGAP); }
                    }
                    const int k = kof(fr, sh, j);
                    const uint32_t st = sb + r.slot * SLOT, fb = BAR_FULL(sb, r.slot);
                    mbar_wait(BAR_EMPTY(sb, r.slot), r.par);
                    if (el) {
                        tma_load(st + half, tm, k, row0 + 64, fb);
                        mbar_expect_tx(fb + AF_REL, half);
                        tma_load(st, tm, k, row0, fb + AF_REL);
                    }
                    if (ph == XST - 1 && fr == 9) CS(39);
                    r.next();
                }
            }
#pragma unroll 1
            for (int p = 0; p < 4; ++p) {
                const uint32_t* f = p < 3 ? fl : g_flags + FL_AUX + m * 2 + (lane & 1);
                uint32_t n = 0;
                while (!__all_sync(0xffffffffu, (int32_t)(flag_get(f) - (ep * 8 + ST_H + p)) >= 0)) { SPIN_GUARD(n); __nanosleep(500); }
                if (el) mbar_arrive(BAR_ONE(sb, EV_H0 + p));
                if (p == 0) gate(5, EV_GB);
            }
        } else {
            const uint32_t w = warp - 9;
            const int row0 = m * 128 + w * 64;
            const uint32_t stg = sb + OFF_STG + w * 16384;
            uint32_t* const fl = g_flags + FL_PROG + fidx(m, w, 2 * j);
            const uint32_t FS = fidx(0, 0, 1);
            uint32_t b = 0, par = 0;
            const bool el = elect_one();
            auto store = [&](const CUtensorMap* tm, int col, bool nat = false) {
                mbar_wait(BAR_SFULL(sb, w * 2 + b), (par >> b) & 1);
                par ^= 1u << b;
                if (el) {
                    if (nat) tma_store3(tm, col, row0 >> 1, 0, stg + b * 8192); else tma_store(tm, col, row0, stg + b * 8192);
                    bulk_commit();
                }
                b ^= 1;
            };
            auto send2 = [&](const CUtensorMap* tm, int step) {
                store(tm, j * 128);
                if (step == XST) CS(33);
                if (el) { bulk_wait_all(); flag_set(fl, ep * 8 + step); }
                if (step == XST) CS(34);
                if (step != ST_O) { mbar_wait(BAR_ONE(sb, EV_FGO + step - ST_H1), 0); pause(w ? P1H : P1H + 1000); }
                else if ((OMODE >> (2 * w)) & 3) { const int md = (OMODE >> (2 * w)) & 3; mbar_wait(BAR_ONE(sb, md == 3 ? EV_P1 : md == 1 ? EV_FGO1 : EV_AGO1), 0); if (P1S) spin(w ? P1S : P1S + P1G); }
                store(tm, j * 128 + 64);
                if (step == XST) CS(35);
                if (el) { bulk_wait_all(); flag_set(fl + FS, ep * 8 + step); }
                if (step == XST) CS(36);
            };
            auto free2 = [&]() { if (el) { mbar_arrive(BAR_SREADY(sb, w * 2)); mbar_arrive(BAR_SREADY(sb, w * 2 + 1)); } };
            if (el) { prefetch_map(&mp.h1s); prefetch_map(&mp.o); prefetch_map(&mp.h2s); prefetch_map(&mp.hb); prefetch_map(&mp.out); prefetch_map(&mp.wo); }
            if (el) { flag_set(fl, ep * 8); flag_set(fl + FS, ep * 8); }
            send2(&mp.h1s, ST_H1);
            if (w == 0) TL(47);
            free2();
            fetch_halo(g_halo + ((m - 1) * 8 + j) * 512 + w * 256 + lane, m == 0, sb, 2 * w, lane);
            send2(&mp.o, ST_O);
            if (w == 0) TL(40); else TL(38);
            free2();
            send2(&mp.h2s, ST_H2);
            if (el) { prefetch_map(&mp.hb); prefetch_map(&mp.hb3); }
            if (w == 0) TL(37);
            free2();
#pragma unroll 1
            for (int p = 0; p < 3; ++p) {
                const int col = hcol(p, j);
                mbar_wait(BAR_SFULL(sb, w * 2), par & 1);
                pause(w ? HD1 : HD0); store(&mp.hb, col);
                pause(HP); store(&mp.hb, col + 64);
                if (p == 0) {
                    pause(HP);
                    if (el) { tma_store3(&mp.hb3, 0, j, row0, sb + (w ? P3_SLOT1 : P3_SLOT0) * SLOT + 24576); bulk_commit(); }
                }
                if (el) { bulk_wait_all(); flag_set(fl, ep * 8 + ST_H + p); flag_set(fl + FS, ep * 8 + ST_H + p); }
                free2();
            }
            cluster_arrive_early = true;
            cluster_arrive();
            store(&mp.out, j * 128, true); store(&mp.out, j * 128 + 64, true);
            if (el) bulk_wait_read();
        }
        __syncwarp();
    }
    if (aux || (wg == 2 && !cluster_arrive_early)) cluster_arrive();
    cluster_wait();
    CS(32);
    if (KDEBUG == 5) __syncthreads();
    if (tid == 0) {
        TL(15);
        flag_add(pt.mail->flags + FL_DONE);
    }
}

typedef CUresult (*EncodeFn)(CUtensorMap*, CUtensorMapDataType, cuuint32_t, void*, const cuuint64_t*, const cuuint64_t*, const cuuint32_t*,
                             const cuuint32_t*, CUtensorMapInterleave, CUtensorMapSwizzle, CUtensorMapL2promotion, CUtensorMapFloatOOBfill);

void make_map(EncodeFn fn, CUtensorMap* m, const void* ptr, uint64_t rows, uint64_t cols, uint32_t brows, uint32_t bcols) {
    cuuint64_t dims[2] = {cols, rows}, strides[1] = {cols * 2};
    cuuint32_t box[2] = {bcols, brows}, es[2] = {1, 1};
    fn(m, CU_TENSOR_MAP_DATA_TYPE_BFLOAT16, 2, (void*)ptr, dims, strides, box, es, CU_TENSOR_MAP_INTERLEAVE_NONE,
       bcols == 64 ? CU_TENSOR_MAP_SWIZZLE_128B : bcols == 32 ? CU_TENSOR_MAP_SWIZZLE_64B : CU_TENSOR_MAP_SWIZZLE_NONE, CU_TENSOR_MAP_L2_PROMOTION_L2_256B, CU_TENSOR_MAP_FLOAT_OOB_FILL_NONE);
}

void make_map3(EncodeFn fn, CUtensorMap* m, const void* ptr) {
    cuuint64_t dims[3] = {D_, S_ / 2, 2}, strides[2] = {4 * D_, 2 * D_};
    cuuint32_t box[3] = {64, 32, 2}, es[3] = {1, 1, 1};
    fn(m, CU_TENSOR_MAP_DATA_TYPE_BFLOAT16, 3, (void*)ptr, dims, strides, box, es, CU_TENSOR_MAP_INTERLEAVE_NONE,
       CU_TENSOR_MAP_SWIZZLE_128B, CU_TENSOR_MAP_L2_PROMOTION_L2_256B, CU_TENSOR_MAP_FLOAT_OOB_FILL_NONE);
}

void make_map48(EncodeFn fn, CUtensorMap* m, const void* ptr, uint64_t rows, uint32_t brows) {
    cuuint64_t dims[3] = {48, 8, rows}, strides[2] = {96, 2 * F_};
    cuuint32_t box[3] = {64, 1, brows}, es[3] = {1, 1, 1};
    fn(m, CU_TENSOR_MAP_DATA_TYPE_BFLOAT16, 3, (void*)ptr, dims, strides, box, es, CU_TENSOR_MAP_INTERLEAVE_NONE,
       CU_TENSOR_MAP_SWIZZLE_128B, CU_TENSOR_MAP_L2_PROMOTION_L2_256B, CU_TENSOR_MAP_FLOAT_OOB_FILL_NONE);
}

}

extern "C" void kernel_launch(void* const* d_in, const int* in_sizes, int n_in, void* d_out, int out_size) {
    (void)in_sizes; (void)n_in; (void)out_size;
    void* fnp = nullptr;
    cudaDriverEntryPointQueryResult qr;
    cudaGetDriverEntryPoint("cuTensorMapEncodeTiled", &fnp, cudaEnableDefault, &qr);
    EncodeFn fn = (EncodeFn)fnp;
    void *h1, *o, *h2, *hb, *mail;
    cudaGetSymbolAddress(&h1, g_h1);
    cudaGetSymbolAddress(&mail, g_mail);
    cudaGetSymbolAddress(&o, g_o);
    cudaGetSymbolAddress(&hb, g_hb);
    h2 = H2ALIAS;
    Maps mp;
    make_map(fn, &mp.h1h, h1, S_, D_, 64, 32);
    make_map(fn, &mp.h2h, h2, S_, D_, 64, 32);
    make_map(fn, &mp.h1s, h1, S_, D_, 64, 64);
    make_map(fn, &mp.o, o, S_, D_, 64, 64);
    make_map(fn, &mp.h2l, h2, S_, D_, 128, 32);
    make_map(fn, &mp.h2s, h2, S_, D_, 64, 64);
    make_map(fn, &mp.hb, hb, S_, F_, 64, 64);
    make_map(fn, &mp.wqkv, d_in[1], D_, 3 * D_, 32, 64);
    make_map(fn, &mp.wo, d_in[2], D_, D_, 64, 64);
    make_map(fn, &mp.wg, d_in[4], D_, F_, 32, 64);
    make_map(fn, &mp.wu, d_in[5], D_, F_, 32, 64);
    make_map(fn, &mp.wd, d_in[6], F_, D_, 64, 64);
    make_map(fn, &mp.wmod, d_in[8], D_, 6 * D_, 64, 64);
    make_map(fn, &mp.wm8, d_in[8], D_ / 8, 8 * 6 * D_, 128, 16);
    make_map3(fn, &mp.x, d_in[0]);
    make_map3(fn, &mp.out, d_out);
    make_map48(fn, &mp.wg3, d_in[4], D_, 32);
    make_map48(fn, &mp.wu3, d_in[5], D_, 32);
    make_map48(fn, &mp.hb3, hb, S_, 64);
    cudaFuncSetAttribute(fused_block_kernel, cudaFuncAttributeMaxDynamicSharedMemorySize, SMEM_BYTES);
    cudaLaunchConfig_t cfg = {};
    cfg.gridDim = dim3(NCTA); cfg.blockDim = dim3(384); cfg.dynamicSmemBytes = SMEM_BYTES; cfg.stream = cudaStreamPerThread;
    cudaLaunchAttribute at[1];
    at[0].id = cudaLaunchAttributeClusterDimension; at[0].val.clusterDim.x = 2; at[0].val.clusterDim.y = 1; at[0].val.clusterDim.z = 1;
    cfg.attrs = at; cfg.numAttrs = 1;
    const Ptrs pt{(const __nv_bfloat16*)d_in[7], (Mail*)mail};
    cudaLaunchKernelEx(&cfg, fused_block_kernel, pt, mp);
}
```

```cpp
#include <cuda_runtime.h>
#include <cuda_bf16.h>
#include <cuda.h>
#include <stdint.h>
#include <stddef.h>

#define LAG 4
#define LAGS 4
#define LAGW 3
#define LAGQ 4
#define MIDW 2
#define PFWO 14
#define PMASK 1
#define PWAIT 0
#define P1H 2000
#define AGW 6
#define CSW 0
#define LWAIT 2
#define BW0 0
#define BWEV EV_WIN
#define BW1 3
#define PDLY 500
#define HD1 5500
#define HD0 5500
#define HP 2200
#define LAGD 4
#define MIDD 44
#define XST ST_O
#define AG0 6
#define AG1 6
#define AG2 6
#define KDEBUG 0

namespace {

constexpr int S_ = 2048, D_ = 1024, F_ = 3584;
constexpr int NCTA = 132;
constexpr int NSLOT = 6;
constexpr uint32_t SLOT = 32768;
constexpr uint32_t OFF_STG = NSLOT * SLOT;
constexpr uint32_t OFF_BAR = OFF_STG + 32768;
constexpr uint32_t OFF_PAR = OFF_BAR + 512;
constexpr uint32_t OFF_TAB = OFF_PAR + 768;
constexpr uint32_t OFF_TL = OFF_PAR + 2048;
constexpr uint32_t SMEM_BYTES = OFF_TL + (KDEBUG ? 512 : 0);
constexpr uint32_t P3_SLOT1 = (32 + 16 + 32) % NSLOT, P3_SLOT0 = (P3_SLOT1 + 1) % NSLOT;

constexpr int ST_H1 = 1, ST_O = 2, ST_H2 = 3, ST_H = 4, FL_DONE = 0, FL_LN2 = 1, FL_AUX = 32, FL_PROG = 64;

struct Maps {
    CUtensorMap h1h, h1s, o, h2h, h2l, h2s, hb, wqkv, wo, wg, wu, wd, wmod, wm8, x, out, wg3, wu3, hb3;
};

struct Mail {
    uint32_t flags[16 * 32 + 64];
    uint2 mod[6 * D_ / 2];
    uint4 mod1[8 * 512];
    uint4 st1[128 * 512];
    uint32_t par2[D_];
    uint4 halo[128 * 512];
};
struct Ptrs { const __nv_bfloat16* c; Mail* mail; const uint32_t *h1, *o; uint32_t zero; };

__device__ __align__(128) Mail g_mail;
__device__ __align__(128) __nv_bfloat16 g_h1[S_ * D_];
__device__ __align__(128) __nv_bfloat16 g_o[S_ * D_];
__device__ __align__(128) __nv_bfloat16 g_hb[S_ * F_];
#define TL(i) do {} while (0)
#define TC(i) do {} while (0)
#define TS(g, which) do {} while (0)
#define CS(i) do {} while (0)

__device__ __forceinline__ uint32_t smem_u32(const void* p) { return (uint32_t)__cvta_generic_to_shared(p); }
__device__ __forceinline__ void mbar_init(uint32_t bar, uint32_t cnt) { asm volatile("mbarrier.init.shared::cta.b64 [%0], %1;" :: "r"(bar), "r"(cnt) : "memory"); }
__device__ __forceinline__ void mbar_expect_tx(uint32_t bar, uint32_t bytes) { asm volatile("mbarrier.arrive.expect_tx.shared::cta.b64 _, [%0], %1;" :: "r"(bar), "r"(bytes) : "memory"); }
__device__ __forceinline__ void mbar_arrive(uint32_t bar) { asm volatile("mbarrier.arrive.shared::cta.b64 _, [%0];" :: "r"(bar) : "memory"); }
__device__ __forceinline__ void mbar_arrive_cta(uint32_t bar, uint32_t cta) {
    asm volatile("{\n.reg .b32 r;\nmapa.shared::cluster.u32 r, %0, %1;\nmbarrier.arrive.shared::cluster.b64 _, [r];\n}" :: "r"(bar), "r"(cta) : "memory");
}
__device__ __forceinline__ void mbar_wait(uint32_t bar, uint32_t parity) {
    asm volatile("{\n.reg .pred p;\n.reg .u32 n;\nmov.u32 n, 0;\n"
        "W_LOOP:\nmbarrier.try_wait.parity.shared::cta.b64 p, [%0], %1;\n@p bra W_DONE;\n"
        "add.u32 n, n, 1;\nsetp.lt.u32 p, n, 0x400000;\n@p bra W_LOOP;\ntrap;\nW_DONE:\n}" :: "r"(bar), "r"(parity) : "memory");
}
__device__ __forceinline__ void mbar_wait2(uint32_t b0, uint32_t b1, uint32_t parity) {
    asm volatile("{\n.reg .pred p, q;\n.reg .u32 n;\nmov.u32 n, 0;\n"
        "W_LOOP:\nmbarrier.try_wait.parity.shared::cta.b64 p, [%0], %2;\nmbarrier.try_wait.parity.shared::cta.b64 q, [%1], %2;\nand.pred p, p, q;\n@p bra W_DONE;\n"
        "add.u32 n, n, 1;\nsetp.lt.u32 p, n, 0x400000;\n@p bra W_LOOP;\ntrap;\nW_DONE:\n}" :: "r"(b0), "r"(b1), "r"(parity) : "memory");
}
__device__ __forceinline__ bool mbar_test(uint32_t bar, uint32_t parity) {
    uint32_t r; asm volatile("{\n.reg .pred p;\nmbarrier.test_wait.parity.shared::cta.b64 p, [%1], %2;\nselp.u32 %0, 1, 0, p;\n}" : "=r"(r) : "r"(bar), "r"(parity) : "memory"); return r;
}
__device__ __forceinline__ bool mbar_test2(uint32_t b0, uint32_t b1, uint32_t parity) {
    uint32_t r;
    asm volatile("{\n.reg .pred p, q;\nmbarrier.test_wait.parity.shared::cta.b64 p, [%1], %3;\nmbarrier.test_wait.parity.shared::cta.b64 q, [%2], %3;\n"
        "and.pred p, p, q;\nselp.u32 %0, 1, 0, p;\n}" : "=r"(r) : "r"(b0), "r"(b1), "r"(parity) : "memory");
    return r;
}
__device__ __forceinline__ void tma_load3(uint32_t dst, const CUtensorMap* m, int c0, int c1, uint32_t bar) {
    asm volatile("cp.async.bulk.tensor.3d.shared::cluster.global.mbarrier::complete_tx::bytes [%0], [%1, {%3, %4, %5}], [%2];"
        :: "r"(dst), "l"(m), "r"(bar), "r"(c0), "r"(c1), "r"(0) : "memory");
}
__device__ __forceinline__ void tma_store3(const CUtensorMap* m, int c0, int c1, int c2, uint32_t src) {
    asm volatile("cp.async.bulk.tensor.3d.global.shared::cta.bulk_group [%0, {%2, %3, %4}], [%1];" :: "l"(m), "r"(src), "r"(c0), "r"(c1), "r"(c2) : "memory");
}
__device__ __forceinline__ void tma_load3_mc(uint32_t dst, const CUtensorMap* m, int c1, int c2, uint32_t bar) {
    asm volatile("cp.async.bulk.tensor.3d.shared::cluster.global.mbarrier::complete_tx::bytes.multicast::cluster.L2::cache_hint [%0], [%1, {%3, %4, %5}], [%2], %6, %7;"
        :: "r"(dst), "l"(m), "r"(bar), "r"(0), "r"(c1), "r"(c2), "h"((uint16_t)3), "l"(0x12F0000000000000ull) : "memory");
}
__device__ __forceinline__ void tma_load(uint32_t dst, const CUtensorMap* m, int c0, int c1, uint32_t bar) {
    asm volatile("cp.async.bulk.tensor.2d.shared::cluster.global.mbarrier::complete_tx::bytes [%0], [%1, {%3, %4}], [%2];"
        :: "r"(dst), "l"(m), "r"(bar), "r"(c0), "r"(c1) : "memory");
}
__device__ __forceinline__ void tma_load_mc(uint32_t dst, const CUtensorMap* m, int c0, int c1, uint32_t bar) {
    asm volatile("cp.async.bulk.tensor.2d.shared::cluster.global.mbarrier::complete_tx::bytes.multicast::cluster.L2::cache_hint [%0], [%1, {%3, %4}], [%2], %5, %6;"
        :: "r"(dst), "l"(m), "r"(bar), "r"(c0), "r"(c1), "h"((uint16_t)3), "l"(0x12F0000000000000ull) : "memory");
}
__device__ __forceinline__ void tma_prefetch(const CUtensorMap* m, int c0, int c1) {
    asm volatile("cp.async.bulk.prefetch.tensor.2d.L2.global [%0, {%1, %2}];" :: "l"(m), "r"(c0), "r"(c1) : "memory");
}
__device__ __forceinline__ void tma_store(const CUtensorMap* m, int c0, int c1, uint32_t src) {
    asm volatile("cp.async.bulk.tensor.2d.global.shared::cta.bulk_group [%0, {%2, %3}], [%1];" :: "l"(m), "r"(src), "r"(c0), "r"(c1) : "memory");
}
__device__ __forceinline__ void bulk_commit() { asm volatile("cp.async.bulk.commit_group;" ::: "memory"); }
__device__ __forceinline__ void bulk_wait_read() { asm volatile("cp.async.bulk.wait_group.read 0;" ::: "memory"); }
__device__ __forceinline__ void fence_async_smem() { asm volatile("fence.proxy.async.shared::cta;" ::: "memory"); }
__device__ __forceinline__ void prefetch_map(const CUtensorMap* m) { asm volatile("prefetch.tensormap [%0];" :: "l"(m) : "memory"); }
__device__ __forceinline__ void wg_fence() { asm volatile("wgmma.fence.sync.aligned;" ::: "memory"); }
__device__ __forceinline__ void wg_commit() { asm volatile("wgmma.commit_group.sync.aligned;" ::: "memory"); }
template <int N> __device__ __forceinline__ void wg_wait() { asm volatile("wgmma.wait_group.sync.aligned %0;" :: "n"(N) : "memory"); }
__device__ __forceinline__ void bar_sync(int id, int n) { asm volatile("bar.sync %0, %1;" :: "r"(id), "r"(n) : "memory"); }
__device__ __forceinline__ void bar_arrive(int id, int n) { asm volatile("bar.arrive %0, %1;" :: "r"(id), "r"(n) : "memory"); }
__device__ __forceinline__ void flag_add(uint32_t* f) { asm volatile("red.relaxed.gpu.global.add.u32 [%0], 1;" :: "l"(f) : "memory"); }
__device__ __forceinline__ void flag_set(uint32_t* f, uint32_t v) { asm volatile("red.relaxed.gpu.global.max.u32 [%0], %1;" :: "l"(f), "r"(v) : "memory"); }
__device__ __forceinline__ uint32_t flag_get(const uint32_t* f) { uint32_t v; asm volatile("ld.relaxed.gpu.global.u32 %0, [%1];" : "=r"(v) : "l"(f) : "memory"); return v; }
__device__ __forceinline__ void bulk_wait_fence() { asm volatile("cp.async.bulk.wait_group 0;\nfence.proxy.async.global;\nfence.acq_rel.gpu;" ::: "memory"); }
__device__ __forceinline__ uint32_t landed(bool el, const uint32_t* p, uint32_t pitch, uint32_t zero) {
    if (el) asm volatile("cp.async.bulk.wait_group 0;" ::: "memory");
    __syncwarp();
    const uint32_t a = flag_get(p), b = flag_get(p + 32 * pitch);
    return __reduce_or_sync(0xffffffffu, (a | b) & zero);
}
__device__ __forceinline__ uint32_t d16(uint32_t addr) { return (addr & 0x3FFFF) >> 4; }
__device__ __forceinline__ uint64_t mk_desc(uint32_t a16, uint32_t off, uint32_t lbo, uint32_t sbo, uint32_t swz) {
    const uint32_t lo = a16 + (off >> 4) + ((lbo >> 4) << 16), hi = (sbo >> 4) | (swz << 30);
    return ((uint64_t)hi << 32) | lo;
}
__device__ __forceinline__ uint32_t pack2(float lo, float hi) {
    uint32_t r; asm("cvt.rn.bf16x2.f32 %0, %1, %2;" : "=r"(r) : "f"(hi), "f"(lo)); return r;
}
__device__ __forceinline__ uint32_t hfma2_bf16(uint32_t a, uint32_t b, uint32_t c) {
    uint32_t r; asm("fma.rn.bf16x2 %0, %1, %2, %3;" : "=r"(r) : "r"(a), "r"(b), "r"(c)); return r;
}
__device__ __forceinline__ float bf_lo(uint32_t v) { return __uint_as_float(v << 16); }
__device__ __forceinline__ float bf_hi(uint32_t v) { return __uint_as_float(v & 0xFFFF0000u); }
__device__ __forceinline__ void unpack2(uint32_t v, float& lo, float& hi) {
    asm volatile("shl.b32 %0, %2, 16;\nand.b32 %1, %2, 0xffff0000;" : "=f"(lo), "=f"(hi) : "r"(v));
}
__device__ __forceinline__ float bf_round(float x) { return __bfloat162float(__float2bfloat16_rn(x)); }
__device__ __forceinline__ void stsm4(uint32_t addr, uint32_t r0, uint32_t r1, uint32_t r2, uint32_t r3) {
    asm volatile("stmatrix.sync.aligned.m8n8.x4.shared.b16 [%0], {%1, %2, %3, %4};" :: "r"(addr), "r"(r0), "r"(r1), "r"(r2), "r"(r3) : "memory");
}
__device__ __forceinline__ void stsm4t(uint32_t addr, uint32_t r0, uint32_t r1, uint32_t r2, uint32_t r3) {
    asm volatile("stmatrix.sync.aligned.m8n8.x4.trans.shared.b16 [%0], {%1, %2, %3, %4};" :: "r"(addr), "r"(r0), "r"(r1), "r"(r2), "r"(r3) : "memory");
}
__device__ __forceinline__ uint32_t movm(uint32_t a) { uint32_t d; asm volatile("movmatrix.sync.aligned.m8n8.trans.b16 %0, %1;" : "=r"(d) : "r"(a)); return d; }
__device__ __forceinline__ void ldsm4(uint32_t addr, uint32_t& r0, uint32_t& r1, uint32_t& r2, uint32_t& r3) {
    asm volatile("ldmatrix.sync.aligned.m8n8.x4.shared.b16 {%0, %1, %2, %3}, [%4];" : "=r"(r0), "=r"(r1), "=r"(r2), "=r"(r3) : "r"(addr) : "memory");
}
__device__ __forceinline__ void ldsm4t(uint32_t addr, uint32_t& r0, uint32_t& r1, uint32_t& r2, uint32_t& r3) {
    asm volatile("ldmatrix.sync.aligned.m8n8.x4.trans.shared.b16 {%0, %1, %2, %3}, [%4];" : "=r"(r0), "=r"(r1), "=r"(r2), "=r"(r3) : "r"(addr) : "memory");
}
__device__ __forceinline__ void mma16816(float (&c)[4], uint32_t a0, uint32_t a1, uint32_t a2, uint32_t a3, uint32_t b0, uint32_t b1) {
    asm("mma.sync.aligned.m16n8k16.row.col.f32.bf16.bf16.f32 {%0, %1, %2, %3}, {%4, %5, %6, %7}, {%8, %9}, {%0, %1, %2, %3};"
        : "+f"(c[0]), "+f"(c[1]), "+f"(c[2]), "+f"(c[3]) : "r"(a0), "r"(a1), "r"(a2), "r"(a3), "r"(b0), "r"(b1));
}
__device__ __forceinline__ float rcp(float x) { float r; asm("rcp.approx.ftz.f32 %0, %1;" : "=f"(r) : "f"(x)); return r; }
__device__ __forceinline__ float ex2(float x) { float r; asm("ex2.approx.ftz.f32 %0, %1;" : "=f"(r) : "f"(x)); return r; }
__device__ __forceinline__ float tanh_(float x) { float t; asm("tanh.approx.f32 %0, %1;" : "=f"(t) : "f"(x)); return t; }
__device__ __forceinline__ void block_end(uint32_t opaque) { asm volatile("{\n.reg .pred p;\nsetp.eq.u32 p, %0, 0xffffffff;\n@p trap;\n}" :: "r"(opaque)); }
__device__ __forceinline__ float silu_(float x) { return __fdividef(x, 1.f + __expf(-x)); }
__device__ __forceinline__ void st_pkt(void* p, uint32_t a, uint32_t b) {
    asm volatile("{\n.reg .b64 t;\nmov.b64 t, {%1, %2};\nst.relaxed.gpu.global.b64 [%0], t;\n}" :: "l"(p), "r"(a), "r"(b) : "memory");
}
__device__ __forceinline__ uint4 ld_pkt2(const void* p) {
    uint4 v; asm volatile("{\n.reg .b64 t, u;\nld.relaxed.gpu.global.v2.b64 {t, u}, [%4];\nmov.b64 {%0, %1}, t;\nmov.b64 {%2, %3}, u;\n}"
        : "=r"(v.x), "=r"(v.y), "=r"(v.z), "=r"(v.w) : "l"(p) : "memory"); return v;
}
__device__ __forceinline__ void st_pkt16(void* p, uint32_t a, uint32_t b, uint32_t c, uint32_t d) {
    asm volatile("{\n.reg .b64 t, u;\n.reg .b128 w;\nmov.b64 t, {%1, %2};\nmov.b64 u, {%3, %4};\nmov.b128 w, {t, u};\nst.relaxed.gpu.global.b128 [%0], w;\n}"
        :: "l"(p), "r"(a), "r"(b), "r"(c), "r"(d) : "memory");
}
__device__ __forceinline__ uint4 ld_pkt16(const void* p) {
    uint4 v; asm volatile("{\n.reg .b64 t, u;\n.reg .b128 w;\nld.relaxed.gpu.global.b128 w, [%4];\nmov.b128 {t, u}, w;\nmov.b64 {%0, %1}, t;\nmov.b64 {%2, %3}, u;\n}"
        : "=r"(v.x), "=r"(v.y), "=r"(v.z), "=r"(v.w) : "l"(p) : "memory"); return v;
}
#define SPIN_GUARD(n) do { if (++(n) > (1u << 22)) asm volatile("trap;"); } while (0)
__device__ __forceinline__ uint4 lds128(uint32_t a) { uint4 v; asm volatile("ld.shared.v4.u32 {%0, %1, %2, %3}, [%4];" : "=r"(v.x), "=r"(v.y), "=r"(v.z), "=r"(v.w) : "r"(a) : "memory"); return v; }
__device__ __forceinline__ void sts128(uint32_t a, uint32_t x, uint32_t y, uint32_t z, uint32_t w) { asm volatile("st.shared.v4.u32 [%0], {%1, %2, %3, %4};" :: "r"(a), "r"(x), "r"(y), "r"(z), "r"(w) : "memory"); }
__device__ __forceinline__ uint32_t lds32(uint32_t a) { uint32_t v; asm volatile("ld.shared.u32 %0, [%1];" : "=r"(v) : "r"(a) : "memory"); return v; }
__device__ __forceinline__ void sts32(uint32_t a, uint32_t v) { asm volatile("st.shared.u32 [%0], %1;" :: "r"(a), "r"(v) : "memory"); }
__device__ __forceinline__ bool elect_one() {
    uint32_t p; asm volatile("{\n.reg .pred q;\nelect.sync _|q, 0xffffffff;\nselp.u32 %0, 1, 0, q;\n}" : "=r"(p)); return p;
}
__device__ __forceinline__ void pause(uint32_t cycles) {
    uint32_t t0, t; asm volatile("mov.u32 %0, %%clock;" : "=r"(t0));
    do { __nanosleep(64); asm volatile("mov.u32 %0, %%clock;" : "=r"(t)); } while (t - t0 < cycles);
}
__device__ __forceinline__ void spin(uint32_t cycles) {
    uint32_t t0, t; asm volatile("mov.u32 %0, %%clock;" : "=r"(t0));
    do { asm volatile("mov.u32 %0, %%clock;" : "=r"(t)); } while (t - t0 < cycles);
}
__device__ __forceinline__ void cluster_arrive() { asm volatile("barrier.cluster.arrive.relaxed.aligned;" ::: "memory"); }
__device__ __forceinline__ void cluster_wait() { asm volatile("barrier.cluster.wait.aligned;" ::: "memory"); }

__device__ __forceinline__ void wgmma_n128_z(float (&d)[64], uint64_t da, uint64_t db) {
    asm volatile("{\n.reg .pred p;\nsetp.ne.b32 p, 0, 0;\n"
        "wgmma.mma_async.sync.aligned.m64n128k16.f32.bf16.bf16 {"
        "%0, %1, %2, %3, %4, %5, %6, %7, %8, %9, %10, %11, %12, %13, %14, %15, "
        "%16, %17, %18, %19, %20, %21, %22, %23, %24, %25, %26, %27, %28, %29, %30, %31, "
        "%32, %33, %34, %35, %36, %37, %38, %39, %40, %41, %42, %43, %44, %45, %46, %47, "
        "%48, %49, %50, %51, %52, %53, %54, %55, %56, %57, %58, %59, %60, %61, %62, %63"
        "}, %64, %65, p, 1, 1, 0, 1;\n}\n"
        : "=f"(d[0]), "=f"(d[1]), "=f"(d[2]), "=f"(d[3]), "=f"(d[4]), "=f"(d[5]), "=f"(d[6]), "=f"(d[7]),
          "=f"(d[8]), "=f"(d[9]), "=f"(d[10]), "=f"(d[11]), "=f"(d[12]), "=f"(d[13]), "=f"(d[14]), "=f"(d[15]),
          "=f"(d[16]), "=f"(d[17]), "=f"(d[18]), "=f"(d[19]), "=f"(d[20]), "=f"(d[21]), "=f"(d[22]), "=f"(d[23]),
          "=f"(d[24]), "=f"(d[25]), "=f"(d[26]), "=f"(d[27]), "=f"(d[28]), "=f"(d[29]), "=f"(d[30]), "=f"(d[31]),
          "=f"(d[32]), "=f"(d[33]), "=f"(d[34]), "=f"(d[35]), "=f"(d[36]), "=f"(d[37]), "=f"(d[38]), "=f"(d[39]),
          "=f"(d[40]), "=f"(d[41]), "=f"(d[42]), "=f"(d[43]), "=f"(d[44]), "=f"(d[45]), "=f"(d[46]), "=f"(d[47]),
          "=f"(d[48]), "=f"(d[49]), "=f"(d[50]), "=f"(d[51]), "=f"(d[52]), "=f"(d[53]), "=f"(d[54]), "=f"(d[55]),
          "=f"(d[56]), "=f"(d[57]), "=f"(d[58]), "=f"(d[59]), "=f"(d[60]), "=f"(d[61]), "=f"(d[62]), "=f"(d[63])
        : "l"(da), "l"(db));
}
__device__ __forceinline__ void wgmma_n128(float (&d)[64], uint64_t da, uint64_t db) {
    asm volatile("{\n.reg .pred p;\nsetp.eq.b32 p, 0, 0;\n"
        "wgmma.mma_async.sync.aligned.m64n128k16.f32.bf16.bf16 {"
        "%0, %1, %2, %3, %4, %5, %6, %7, %8, %9, %10, %11, %12, %13, %14, %15, "
        "%16, %17, %18, %19, %20, %21, %22, %23, %24, %25, %26, %27, %28, %29, %30, %31, "
        "%32, %33, %34, %35, %36, %37, %38, %39, %40, %41, %42, %43, %44, %45, %46, %47, "
        "%48, %49, %50, %51, %52, %53, %54, %55, %56, %57, %58, %59, %60, %61, %62, %63"
        "}, %64, %65, p, 1, 1, 0, 1;\n}\n"
        : "+f"(d[0]), "+f"(d[1]), "+f"(d[2]), "+f"(d[3]), "+f"(d[4]), "+f"(d[5]), "+f"(d[6]), "+f"(d[7]),
          "+f"(d[8]), "+f"(d[9]), "+f"(d[10]), "+f"(d[11]), "+f"(d[12]), "+f"(d[13]), "+f"(d[14]), "+f"(d[15]),
          "+f"(d[16]), "+f"(d[17]), "+f"(d[18]), "+f"(d[19]), "+f"(d[20]), "+f"(d[21]), "+f"(d[22]), "+f"(d[23]),
          "+f"(d[24]), "+f"(d[25]), "+f"(d[26]), "+f"(d[27]), "+f"(d[28]), "+f"(d[29]), "+f"(d[30]), "+f"(d[31]),
          "+f"(d[32]), "+f"(d[33]), "+f"(d[34]), "+f"(d[35]), "+f"(d[36]), "+f"(d[37]), "+f"(d[38]), "+f"(d[39]),
          "+f"(d[40]), "+f"(d[41]), "+f"(d[42]), "+f"(d[43]), "+f"(d[44]), "+f"(d[45]), "+f"(d[46]), "+f"(d[47]),
          "+f"(d[48]), "+f"(d[49]), "+f"(d[50]), "+f"(d[51]), "+f"(d[52]), "+f"(d[53]), "+f"(d[54]), "+f"(d[55]),
          "+f"(d[56]), "+f"(d[57]), "+f"(d[58]), "+f"(d[59]), "+f"(d[60]), "+f"(d[61]), "+f"(d[62]), "+f"(d[63])
        : "l"(da), "l"(db));
}
__device__ __forceinline__ void wgmma_n176_z(float (&d)[88], uint64_t da, uint64_t db) {
    asm volatile("{\n.reg .pred p;\nsetp.ne.b32 p, 0, 0;\n"
        "wgmma.mma_async.sync.aligned.m64n176k16.f32.bf16.bf16 {"
        "%0, %1, %2, %3, %4, %5, %6, %7, %8, %9, %10, %11, %12, %13, %14, %15, "
        "%16, %17, %18, %19, %20, %21, %22, %23, %24, %25, %26, %27, %28, %29, %30, %31, "
        "%32, %33, %34, %35, %36, %37, %38, %39, %40, %41, %42, %43, %44, %45, %46, %47, "
        "%48, %49, %50, %51, %52, %53, %54, %55, %56, %57, %58, %59, %60, %61, %62, %63, "
        "%64, %65, %66, %67, %68, %69, %70, %71, %72, %73, %74, %75, %76, %77, %78, %79, "
        "%80, %81, %82, %83, %84, %85, %86, %87"
        "}, %88, %89, p, 1, 1, 0, 1;\n}\n"
        : "=f"(d[0]), "=f"(d[1]), "=f"(d[2]), "=f"(d[3]), "=f"(d[4]), "=f"(d[5]), "=f"(d[6]), "=f"(d[7]),
          "=f"(d[8]), "=f"(d[9]), "=f"(d[10]), "=f"(d[11]), "=f"(d[12]), "=f"(d[13]), "=f"(d[14]), "=f"(d[15]),
          "=f"(d[16]), "=f"(d[17]), "=f"(d[18]), "=f"(d[19]), "=f"(d[20]), "=f"(d[21]), "=f"(d[22]), "=f"(d[23]),
          "=f"(d[24]), "=f"(d[25]), "=f"(d[26]), "=f"(d[27]), "=f"(d[28]), "=f"(d[29]), "=f"(d[30]), "=f"(d[31]),
          "=f"(d[32]), "=f"(d[33]), "=f"(d[34]), "=f"(d[35]), "=f"(d[36]), "=f"(d[37]), "=f"(d[38]), "=f"(d[39]),
          "=f"(d[40]), "=f"(d[41]), "=f"(d[42]), "=f"(d[43]), "=f"(d[44]), "=f"(d[45]), "=f"(d[46]), "=f"(d[47]),
          "=f"(d[48]), "=f"(d[49]), "=f"(d[50]), "=f"(d[51]), "=f"(d[52]), "=f"(d[53]), "=f"(d[54]), "=f"(d[55]),
          "=f"(d[56]), "=f"(d[57]), "=f"(d[58]), "=f"(d[59]), "=f"(d[60]), "=f"(d[61]), "=f"(d[62]), "=f"(d[63]),
          "=f"(d[64]), "=f"(d[65]), "=f"(d[66]), "=f"(d[67]), "=f"(d[68]), "=f"(d[69]), "=f"(d[70]), "=f"(d[71]),
          "=f"(d[72]), "=f"(d[73]), "=f"(d[74]), "=f"(d[75]), "=f"(d[76]), "=f"(d[77]), "=f"(d[78]), "=f"(d[79]),
          "=f"(d[80]), "=f"(d[81]), "=f"(d[82]), "=f"(d[83]), "=f"(d[84]), "=f"(d[85]), "=f"(d[86]), "=f"(d[87])
        : "l"(da), "l"(db));
}
__device__ __forceinline__ void wgmma_n176(float (&d)[88], uint64_t da, uint64_t db) {
    asm volatile("{\n.reg .pred p;\nsetp.eq.b32 p, 0, 0;\n"
        "wgmma.mma_async.sync.aligned.m64n176k16.f32.bf16.bf16 {"
        "%0, %1, %2, %3, %4, %5, %6, %7, %8, %9, %10, %11, %12, %13, %14, %15, "
        "%16, %17, %18, %19, %20, %21, %22, %23, %24, %25, %26, %27, %28, %29, %30, %31, "
        "%32, %33, %34, %35, %36, %37, %38, %39, %40, %41, %42, %43, %44, %45, %46, %47, "
        "%48, %49, %50, %51, %52, %53, %54, %55, %56, %57, %58, %59, %60, %61, %62, %63, "
        "%64, %65, %66, %67, %68, %69, %70, %71, %72, %73, %74, %75, %76, %77, %78, %79, "
        "%80, %81, %82, %83, %84, %85, %86, %87"
        "}, %88, %89, p, 1, 1, 0, 1;\n}\n"
        : "+f"(d[0]), "+f"(d[1]), "+f"(d[2]), "+f"(d[3]), "+f"(d[4]), "+f"(d[5]), "+f"(d[6]), "+f"(d[7]),
          "+f"(d[8]), "+f"(d[9]), "+f"(d[10]), "+f"(d[11]), "+f"(d[12]), "+f"(d[13]), "+f"(d[14]), "+f"(d[15]),
          "+f"(d[16]), "+f"(d[17]), "+f"(d[18]), "+f"(d[19]), "+f"(d[20]), "+f"(d[21]), "+f"(d[22]), "+f"(d[23]),
          "+f"(d[24]), "+f"(d[25]), "+f"(d[26]), "+f"(d[27]), "+f"(d[28]), "+f"(d[29]), "+f"(d[30]), "+f"(d[31]),
          "+f"(d[32]), "+f"(d[33]), "+f"(d[34]), "+f"(d[35]), "+f"(d[36]), "+f"(d[37]), "+f"(d[38]), "+f"(d[39]),
          "+f"(d[40]), "+f"(d[41]), "+f"(d[42]), "+f"(d[43]), "+f"(d[44]), "+f"(d[45]), "+f"(d[46]), "+f"(d[47]),
          "+f"(d[48]), "+f"(d[49]), "+f"(d[50]), "+f"(d[51]), "+f"(d[52]), "+f"(d[53]), "+f"(d[54]), "+f"(d[55]),
          "+f"(d[56]), "+f"(d[57]), "+f"(d[58]), "+f"(d[59]), "+f"(d[60]), "+f"(d[61]), "+f"(d[62]), "+f"(d[63]),
          "+f"(d[64]), "+f"(d[65]), "+f"(d[66]), "+f"(d[67]), "+f"(d[68]), "+f"(d[69]), "+f"(d[70]), "+f"(d[71]),
          "+f"(d[72]), "+f"(d[73]), "+f"(d[74]), "+f"(d[75]), "+f"(d[76]), "+f"(d[77]), "+f"(d[78]), "+f"(d[79]),
          "+f"(d[80]), "+f"(d[81]), "+f"(d[82]), "+f"(d[83]), "+f"(d[84]), "+f"(d[85]), "+f"(d[86]), "+f"(d[87])
        : "l"(da), "l"(db));
}
__device__ __forceinline__ void wgmma_n256_z(float (&d)[128], uint64_t da, uint64_t db) {
    asm volatile("{\n.reg .pred p;\nsetp.ne.b32 p, 0, 0;\n"
        "wgmma.mma_async.sync.aligned.m64n256k16.f32.bf16.bf16 {"
        "%0, %1, %2, %3, %4, %5, %6, %7, %8, %9, %10, %11, %12, %13, %14, %15, "
        "%16, %17, %18, %19, %20, %21, %22, %23, %24, %25, %26, %27, %28, %29, %30, %31, "
        "%32, %33, %34, %35, %36, %37, %38, %39, %40, %41, %42, %43, %44, %45, %46, %47, "
        "%48, %49, %50, %51, %52, %53, %54, %55, %56, %57, %58, %59, %60, %61, %62, %63, "
        "%64, %65, %66, %67, %68, %69, %70, %71, %72, %73, %74, %75, %76, %77, %78, %79, "
        "%80, %81, %82, %83, %84, %85, %86, %87, %88, %89, %90, %91, %92, %93, %94, %95, "
        "%96, %97, %98, %99, %100, %101, %102, %103, %104, %105, %106, %107, %108, %109, %110, %111, "
        "%112, %113, %114, %115, %116, %117, %118, %119, %120, %121, %122, %123, %124, %125, %126, %127"
        "}, %128, %129, p, 1, 1, 0, 1;\n}\n"
        : "=f"(d[0]), "=f"(d[1]), "=f"(d[2]), "=f"(d[3]), "=f"(d[4]), "=f"(d[5]), "=f"(d[6]), "=f"(d[7]),
          "=f"(d[8]), "=f"(d[9]), "=f"(d[10]), "=f"(d[11]), "=f"(d[12]), "=f"(d[13]), "=f"(d[14]), "=f"(d[15]),
          "=f"(d[16]), "=f"(d[17]), "=f"(d[18]), "=f"(d[19]), "=f"(d[20]), "=f"(d[21]), "=f"(d[22]), "=f"(d[23]),
          "=f"(d[24]), "=f"(d[25]), "=f"(d[26]), "=f"(d[27]), "=f"(d[28]), "=f"(d[29]), "=f"(d[30]), "=f"(d[31]),
          "=f"(d[32]), "=f"(d[33]), "=f"(d[34]), "=f"(d[35]), "=f"(d[36]), "=f"(d[37]), "=f"(d[38]), "=f"(d[39]),
          "=f"(d[40]), "=f"(d[41]), "=f"(d[42]), "=f"(d[43]), "=f"(d[44]), "=f"(d[45]), "=f"(d[46]), "=f"(d[47]),
          "=f"(d[48]), "=f"(d[49]), "=f"(d[50]), "=f"(d[51]), "=f"(d[52]), "=f"(d[53]), "=f"(d[54]), "=f"(d[55]),
          "=f"(d[56]), "=f"(d[57]), "=f"(d[58]), "=f"(d[59]), "=f"(d[60]), "=f"(d[61]), "=f"(d[62]), "=f"(d[63]),
          "=f"(d[64]), "=f"(d[65]), "=f"(d[66]), "=f"(d[67]), "=f"(d[68]), "=f"(d[69]), "=f"(d[70]), "=f"(d[71]),
          "=f"(d[72]), "=f"(d[73]), "=f"(d[74]), "=f"(d[75]), "=f"(d[76]), "=f"(d[77]), "=f"(d[78]), "=f"(d[79]),
          "=f"(d[80]), "=f"(d[81]), "=f"(d[82]), "=f"(d[83]), "=f"(d[84]), "=f"(d[85]), "=f"(d[86]), "=f"(d[87]),
          "=f"(d[88]), "=f"(d[89]), "=f"(d[90]), "=f"(d[91]), "=f"(d[92]), "=f"(d[93]), "=f"(d[94]), "=f"(d[95]),
          "=f"(d[96]), "=f"(d[97]), "=f"(d[98]), "=f"(d[99]), "=f"(d[100]), "=f"(d[101]), "=f"(d[102]), "=f"(d[103]),
          "=f"(d[104]), "=f"(d[105]), "=f"(d[106]), "=f"(d[107]), "=f"(d[108]), "=f"(d[109]), "=f"(d[110]), "=f"(d[111]),
          "=f"(d[112]), "=f"(d[113]), "=f"(d[114]), "=f"(d[115]), "=f"(d[116]), "=f"(d[117]), "=f"(d[118]), "=f"(d[119]),
          "=f"(d[120]), "=f"(d[121]), "=f"(d[122]), "=f"(d[123]), "=f"(d[124]), "=f"(d[125]), "=f"(d[126]), "=f"(d[127])
        : "l"(da), "l"(db));
}
__device__ __forceinline__ void wgmma_n256(float (&d)[128], uint64_t da, uint64_t db) {
    asm volatile("{\n.reg .pred p;\nsetp.eq.b32 p, 0, 0;\n"
        "wgmma.mma_async.sync.aligned.m64n256k16.f32.bf16.bf16 {"
        "%0, %1, %2, %3, %4, %5, %6, %7, %8, %9, %10, %11, %12, %13, %14, %15, "
        "%16, %17, %18, %19, %20, %21, %22, %23, %24, %25, %26, %27, %28, %29, %30, %31, "
        "%32, %33, %34, %35, %36, %37, %38, %39, %40, %41, %42, %43, %44, %45, %46, %47, "
        "%48, %49, %50, %51, %52, %53, %54, %55, %56, %57, %58, %59, %60, %61, %62, %63, "
        "%64, %65, %66, %67, %68, %69, %70, %71, %72, %73, %74, %75, %76, %77, %78, %79, "
        "%80, %81, %82, %83, %84, %85, %86, %87, %88, %89, %90, %91, %92, %93, %94, %95, "
        "%96, %97, %98, %99, %100, %101, %102, %103, %104, %105, %106, %107, %108, %109, %110, %111, "
        "%112, %113, %114, %115, %116, %117, %118, %119, %120, %121, %122, %123, %124, %125, %126, %127"
        "}, %128, %129, p, 1, 1, 0, 1;\n}\n"
        : "+f"(d[0]), "+f"(d[1]), "+f"(d[2]), "+f"(d[3]), "+f"(d[4]), "+f"(d[5]), "+f"(d[6]), "+f"(d[7]),
          "+f"(d[8]), "+f"(d[9]), "+f"(d[10]), "+f"(d[11]), "+f"(d[12]), "+f"(d[13]), "+f"(d[14]), "+f"(d[15]),
          "+f"(d[16]), "+f"(d[17]), "+f"(d[18]), "+f"(d[19]), "+f"(d[20]), "+f"(d[21]), "+f"(d[22]), "+f"(d[23]),
          "+f"(d[24]), "+f"(d[25]), "+f"(d[26]), "+f"(d[27]), "+f"(d[28]), "+f"(d[29]), "+f"(d[30]), "+f"(d[31]),
          "+f"(d[32]), "+f"(d[33]), "+f"(d[34]), "+f"(d[35]), "+f"(d[36]), "+f"(d[37]), "+f"(d[38]), "+f"(d[39]),
          "+f"(d[40]), "+f"(d[41]), "+f"(d[42]), "+f"(d[43]), "+f"(d[44]), "+f"(d[45]), "+f"(d[46]), "+f"(d[47]),
          "+f"(d[48]), "+f"(d[49]), "+f"(d[50]), "+f"(d[51]), "+f"(d[52]), "+f"(d[53]), "+f"(d[54]), "+f"(d[55]),
          "+f"(d[56]), "+f"(d[57]), "+f"(d[58]), "+f"(d[59]), "+f"(d[60]), "+f"(d[61]), "+f"(d[62]), "+f"(d[63]),
          "+f"(d[64]), "+f"(d[65]), "+f"(d[66]), "+f"(d[67]), "+f"(d[68]), "+f"(d[69]), "+f"(d[70]), "+f"(d[71]),
          "+f"(d[72]), "+f"(d[73]), "+f"(d[74]), "+f"(d[75]), "+f"(d[76]), "+f"(d[77]), "+f"(d[78]), "+f"(d[79]),
          "+f"(d[80]), "+f"(d[81]), "+f"(d[82]), "+f"(d[83]), "+f"(d[84]), "+f"(d[85]), "+f"(d[86]), "+f"(d[87]),
          "+f"(d[88]), "+f"(d[89]), "+f"(d[90]), "+f"(d[91]), "+f"(d[92]), "+f"(d[93]), "+f"(d[94]), "+f"(d[95]),
          "+f"(d[96]), "+f"(d[97]), "+f"(d[98]), "+f"(d[99]), "+f"(d[100]), "+f"(d[101]), "+f"(d[102]), "+f"(d[103]),
          "+f"(d[104]), "+f"(d[105]), "+f"(d[106]), "+f"(d[107]), "+f"(d[108]), "+f"(d[109]), "+f"(d[110]), "+f"(d[111]),
          "+f"(d[112]), "+f"(d[113]), "+f"(d[114]), "+f"(d[115]), "+f"(d[116]), "+f"(d[117]), "+f"(d[118]), "+f"(d[119]),
          "+f"(d[120]), "+f"(d[121]), "+f"(d[122]), "+f"(d[123]), "+f"(d[124]), "+f"(d[125]), "+f"(d[126]), "+f"(d[127])
        : "l"(da), "l"(db));
}

struct Idx {
    uint32_t lane, warp, w4, q4, g8, prow, pan;
    __device__ __forceinline__ Idx() {
        uint32_t t; asm volatile("mov.u32 %0, %%tid.x;" : "=r"(t));
        lane = t & 31; warp = t >> 5; w4 = warp & 3; q4 = lane & 3; g8 = lane >> 2;
        prow = w4 * 16 + ((lane >> 3) & 1) * 8 + (lane & 7);
        pan = prow * 128 + (((lane >> 4) ^ (lane & 7)) << 4);
    }
};
#define IDX() const Idx ix; const uint32_t lane = ix.lane, warp = ix.warp, w4 = ix.w4, q4 = ix.q4, g8 = ix.g8, prow = ix.prow, pan_addr = ix.pan; \
    (void)lane; (void)warp; (void)w4; (void)q4; (void)g8; (void)prow; (void)pan_addr;

__device__ __forceinline__ int kof(int t, int sh, int j) {
    const int p = t >> (sh - 1), pn = p < 2 ? p : p >= 9, q = p - 2 - 7 * pn;
    return ((p < 2 ? j : q + (q >= j)) << 7) + (pn << 6) + ((t & (sh - 1)) << 5);
}
__device__ __forceinline__ uint32_t fidx(uint32_t m, uint32_t w, uint32_t pn) {
    return m * 32 + w * 16 + pn;
}
constexpr int HC0 = 8 * 48, HC3 = HC0 + 3072;
__device__ __forceinline__ int hcol(int p, int j) { return HC0 + p * 1024 + j * 128; }
struct Ring {
    uint32_t slot, par;
    __device__ __forceinline__ void next() { if (++slot == NSLOT) { slot = 0; par ^= 1; } }
    __device__ __forceinline__ void skip(uint32_t n) { slot += n; if (slot >= NSLOT) { slot -= NSLOT; par ^= 1; } }
};
__device__ __forceinline__ uint32_t BAR_FULL(uint32_t sb, uint32_t s) { return sb + OFF_BAR + 8 * s; }
constexpr uint32_t AF_REL = 48;
__device__ __forceinline__ uint32_t BAR_EMPTY(uint32_t sb, uint32_t s) { return sb + OFF_BAR + 96 + 8 * s; }
__device__ __forceinline__ uint32_t BAR_SFULL(uint32_t sb, uint32_t i) { return sb + OFF_BAR + 152 + 8 * i; }
__device__ __forceinline__ uint32_t BAR_SREADY(uint32_t sb, uint32_t i) { return sb + OFF_BAR + 184 + 8 * i; }
__device__ __forceinline__ uint32_t BAR_ONE(uint32_t sb, uint32_t i) { return sb + OFF_BAR + 216 + 8 * i; }
enum { EV_WIN, EV_WIN1, EV_WIN2, EV_WIN3, EV_P0, EV_GA, EV_GB, EV_LN2, EV_LAG0, EV_LAG1, EV_LAG2, EV_LAG3, EV_LAG4, EV_LAG5, EV_KV, EV_GO, EV_PAR, EV_AGO, EV_AGO1, EV_AGO2, EV_FGO, EV_FGO1, EV_FGO2, EV_H0, EV_H1, EV_H2, EV_H3, EV_COUNT };
constexpr int NB_TAIL = 4;

struct Rel {
    uint32_t base; bool sig;
    __device__ __forceinline__ Rel(uint32_t sb, uint32_t tw) {
        uint32_t a; asm("mapa.shared::cluster.u32 %0, %1, %2;" : "=r"(a) : "r"(BAR_EMPTY(sb, 0)), "r"((tw >> 5) & 1));
        base = __shfl_sync(0xffffffffu, a, 0); sig = (tw & ~32u) == 0;
    }
    __device__ __forceinline__ void operator()(uint32_t slot) const {
        if (sig) asm volatile("mbarrier.arrive.shared::cluster.b64 _, [%0];" :: "r"(base + 8 * slot) : "memory");
    }
};
struct LnRow { float rs0, nm0, rs1, nm1; };
struct Pipe {
    Rel rel; uint32_t p1, p2;
    __device__ __forceinline__ Pipe(uint32_t sb, uint32_t tw, uint32_t first) : rel(sb, tw), p1(first), p2(NSLOT) {}
    template <bool TWO> __device__ __forceinline__ void acquire(uint32_t sb, uint32_t af, const Ring& r) {
        const uint32_t b0 = BAR_FULL(sb, r.slot), b1 = b0 + af;
        const bool ready = TWO ? mbar_test2(b0, b1, r.par) : mbar_test(b0, r.par);
        wg_wait<1>();
        rel(p2);
        if (!ready) { if (TWO) mbar_wait2(b0, b1, r.par); else mbar_wait(b0, r.par); }
    }
    __device__ __forceinline__ void issued(uint32_t slot) { p2 = p1; p1 = slot; }
    __device__ __forceinline__ void drain1() { wg_wait<1>(); rel(p2); p2 = NSLOT; }
    __device__ __forceinline__ void drain0() { wg_wait<0>(); rel(p1); p1 = NSLOT; }
    template <bool TWO, class Step> __device__ __forceinline__ void hold(int LG, uint32_t sb, uint32_t af, Ring& r, uint32_t lag_bar, Step step) {
        Ring q = r;
#pragma unroll 1
        for (int i = 0; i < LG; ++i) { if (TWO) mbar_wait2(BAR_FULL(sb, q.slot), BAR_FULL(sb, q.slot) + af, q.par); else mbar_wait(BAR_FULL(sb, q.slot), q.par); q.next(); }
        mbar_wait(lag_bar, 0);
#pragma unroll 1
        do {
            step(r.slot);
            wg_wait<2>(); rel(p2); p2 = p1; p1 = r.slot;
            if (++r.slot == NSLOT) r.slot = 0;
        } while (r.slot != q.slot);
        r.par = q.par;
    }
};
template <bool TWO, bool FIRST, int NA, int NB>
__device__ __forceinline__ void step32(float (&aa)[NA], float (&ab)[NB], uint32_t sb, uint32_t wg, uint32_t slot, int own) {
    const uint32_t st = d16(sb) + slot * (SLOT >> 4);
    const uint32_t alo = own >= 0 ? d16(sb) + OFF_STG / 16 + wg * 1024 + (own >> 1) * 512 + (own & 1) * 4 : st + wg * 256;
    const uint32_t ahi = own >= 0 ? (1024 >> 4) | (1u << 30) : (512 >> 4) | (2u << 30);
    wg_fence();
#pragma unroll
    for (int k = 0; k < 2; ++k) {
        const uint64_t da = ((uint64_t)ahi << 32) | (alo + k * 2 + 0x10000);
        if constexpr (NA == 88) {
            const uint64_t d0 = mk_desc(st, 8192 + k * 2048, 8192, 1024, 1), d1 = mk_desc(st, 12288 + k * 2048, 8192, 1024, 1);
            if (FIRST && k == 0) { wgmma_n176_z(aa, da, d0); wgmma_n176_z(ab, da, d1); }
            else { wgmma_n176(aa, da, d0); wgmma_n176(ab, da, d1); }
        } else {
            const uint64_t d0 = mk_desc(st, 8192 + k * 2048, 4096, 1024, 1), d1 = mk_desc(st, 24576 + k * 2048, 4096, 1024, 1);
            if (FIRST && k == 0) { wgmma_n256_z(aa, da, d0); if constexpr (TWO) wgmma_n128_z(ab, da, d1); }
            else { wgmma_n256(aa, da, d0); if constexpr (TWO) wgmma_n128(ab, da, d1); }
        }
    }
    wg_commit();
}
template <bool TWO, int LG, int NA, int NB, class Tail>
__device__ __forceinline__ void mainloop32(float (&aa)[NA], float (&ab)[NB], uint32_t sb, uint32_t wg, uint32_t tw, Ring& r, uint32_t lag_ev, int g0, Tail tail) {
    mbar_wait(BAR_FULL(sb, r.slot), r.par);
    step32<TWO, true>(aa, ab, sb, wg, r.slot, TWO ? 0 : -1);
    TS(g0, 0);
    Pipe pp(sb, tw, r.slot);
    r.next();
    const int end = wg ? 32 : 32 - LG;
#pragma unroll 1
    for (int it = 1; it < end; ++it) {
        pp.acquire<TWO>(sb, wg ? 0 : AF_REL, r);
        step32<TWO, false>(aa, ab, sb, wg, r.slot, TWO && it < 4 ? it : -1);
        pp.issued(r.slot);
        TS(g0 + it, 0);
        r.next();
    }
    if (wg == 0) { pp.drain1(); pp.drain0(); pp.hold<TWO>(LG, sb, AF_REL, r, BAR_ONE(sb, lag_ev), [&](uint32_t slot) { step32<TWO, false>(aa, ab, sb, 0, slot, -1); }); }
    pp.drain1();
    if (wg == 1 && tw == 0) mbar_arrive(BAR_ONE(sb, lag_ev));
    tail();
    pp.drain0();
    TS(g0 + 31, 1);
}
template <bool FIRST>
__device__ __forceinline__ void step64(float (&acc)[64], uint32_t sb, uint32_t wg, uint32_t slot, int own) {
    const uint32_t sbb = d16(sb) + slot * (SLOT >> 4), sa = own >= 0 ? d16(sb) + OFF_STG / 16 + wg * 1024 + own * 512 : sbb + wg * 512;
    wg_fence();
#pragma unroll
    for (int k = 0; k < 4; ++k) {
        const uint64_t da = mk_desc(sa, k * 32, 16, 1024, 1), db = mk_desc(sbb, 16384 + k * 2048, 8192, 1024, 1);
        if (FIRST && k == 0) wgmma_n128_z(acc, da, db); else wgmma_n128(acc, da, db);
    }
    wg_commit();
}
template <class Mid>
__device__ __forceinline__ void mainloop64(float (&acc)[64], bool wo, uint32_t sb, uint32_t wg, uint32_t tw, Ring& r, Mid mid) {
    const int g0 = wo ? 32 : 144, nst = wo ? 16 : 56, lg = wo ? LAGW : LAGD; (void)g0;
    const uint32_t lag_bar = BAR_ONE(sb, wo ? EV_LAG4 : EV_LAG5), af = wo && !wg ? AF_REL : 0;
    mbar_wait(BAR_FULL(sb, r.slot), r.par);
    if (!wo) CS(28);
    step64<true>(acc, sb, wg, r.slot, wo ? 0 : -1);
    if (!wo) CS(29);
    TS(g0, 0);
    Pipe pp(sb, tw, r.slot);
    r.next();
    int it = 1;
    auto run = [&](int end, int own) {
#pragma unroll 1
        do {
            pp.acquire<true>(sb, af, r);
            step64<false>(acc, sb, wg, r.slot, own);
            pp.issued(r.slot);
            TS(g0 + it, 0);
            if (wo && it == 2) CS(9);
            r.next();
            if (own > 0) {
                own = -1;
                pp.drain1(); pp.drain0();
                TS(g0 + 1, 1);
            }
        } while (++it < end);
    };
    const int end = wg ? nst : nst - lg;
    run(wo ? MIDW : wg ? MIDD : end, wo ? 1 : -1);
    mid();
    if (it < end) run(end, -1);
    if (wg == 0) { pp.drain1(); pp.drain0(); pp.hold<true>(lg, sb, af, r, lag_bar, [&](uint32_t slot) { step64<false>(acc, sb, 0, slot, -1); }); }
    pp.drain1();
    if (wg == 1 && tw == 0) mbar_arrive(lag_bar);
    pp.drain0();
    TS(g0 + nst - 1, 1);
}

struct RowAcc {
    float sm[4] = {0.f, 0.f, 0.f, 0.f}, sq[4] = {0.f, 0.f, 0.f, 0.f};
    __device__ __forceinline__ void add(int e, float x) { sm[e & 3] += x; sq[e & 3] = fmaf(x, x, sq[e & 3]); }
    __device__ __forceinline__ void publish(uint4* dst, uint32_t q4, uint32_t ep) const {
        const float s0 = sm[0] + sm[1], s1 = sm[2] + sm[3], q0 = sq[0] + sq[1], q1 = sq[2] + sq[3];
        const bool od = q4 & 1;
        float sv = (od ? s1 : s0) + __shfl_xor_sync(0xffffffffu, od ? s0 : s1, 1), qv = (od ? q1 : q0) + __shfl_xor_sync(0xffffffffu, od ? q0 : q1, 1);
        sv += __shfl_xor_sync(0xffffffffu, sv, 2); qv += __shfl_xor_sync(0xffffffffu, qv, 2);
        if (q4 < 2) st_pkt16(dst + q4 * 8, 0, __float_as_uint(sv), __float_as_uint(qv), ep);
    }
};
__device__ __forceinline__ LnRow merge_stats(const uint4* src, uint32_t q4, uint32_t ep, uint32_t sb) {
    uint4 t[4];
    uint32_t n = 0;
    while (true) {
#pragma unroll
        for (int i = 0; i < 4; ++i) t[i] = ld_pkt16(src + (q4 * 2 + (i >> 1)) * 512 + (i & 1) * 8);
        const bool ok_ = __all_sync(0xffffffffu, t[0].w == ep && t[1].w == ep && t[2].w == ep && t[3].w == ep);
        if (n < 4) CS(14 + n);
        if (ok_) break;
        SPIN_GUARD(n);
    }
    float v[4];
#pragma unroll
    for (int h = 0; h < 2; ++h) { v[h] = __uint_as_float(t[h].y) + __uint_as_float(t[2 + h].y); v[2 + h] = __uint_as_float(t[h].z) + __uint_as_float(t[2 + h].z); }
#pragma unroll
    for (int o = 1; o < 4; o <<= 1)
#pragma unroll
        for (int i = 0; i < 4; ++i) v[i] += __shfl_xor_sync(0xffffffffu, v[i], o);
    const float m0 = v[0] * (1.f / D_), m1 = v[1] * (1.f / D_);
    const float r0 = rsqrtf(fmaxf(fmaf(-m0, m0, v[2] * (1.f / D_)), 0.f) + 1e-5f), r1 = rsqrtf(fmaxf(fmaf(-m1, m1, v[3] * (1.f / D_)), 0.f) + 1e-5f);
    return LnRow{r0, -m0 * r0, r1, -m1 * r1};
}
struct Stg {
    uint32_t b, par;
    __device__ __forceinline__ uint32_t acquire2(uint32_t sb, uint32_t wg) {
        mbar_wait2(BAR_SREADY(sb, wg * 2), BAR_SREADY(sb, wg * 2 + 1), par);
        par ^= 1;
        return sb + OFF_STG + wg * 16384;
    }
    __device__ __forceinline__ void publish(uint32_t sb, uint32_t wg, uint32_t lane) {
        fence_async_smem();
        __syncwarp();
        if (lane == 0) mbar_arrive(BAR_SFULL(sb, wg * 2 + b));
        b ^= 1;
    }
};

struct LnPar {
    uint4 p[8];
    __device__ __forceinline__ void load(uint32_t sb, uint32_t q4) {
#pragma unroll
        for (int i = 0; i < 8; ++i) p[i] = lds128(sb + OFF_PAR + i * 64 + q4 * 16);
    }
};
__device__ __forceinline__ void ln_norm(uint32_t (&xn)[32], const float (&x)[64], const LnRow& n) {
#pragma unroll
    for (int e = 0; e < 32; ++e) {
        const float rs = (e & 1) ? n.rs1 : n.rs0, nm = (e & 1) ? n.nm1 : n.nm0;
        xn[e] = pack2(fmaf(x[2 * e], rs, nm), fmaf(x[2 * e + 1], rs, nm));
    }
}
__device__ __forceinline__ void ln_emit(const uint32_t (&xr)[32], const LnPar& lp, uint32_t sb, uint32_t wg, const Idx& ix) {
#pragma unroll
    for (int i = 0; i < 8; ++i)
        stsm4(sb + OFF_STG + wg * 16384 + (i >> 2) * 8192 + (ix.pan ^ ((i & 3) << 5)), hfma2_bf16(xr[4 * i], lp.p[i].z, lp.p[i].x), hfma2_bf16(xr[4 * i + 1], lp.p[i].z, lp.p[i].x),
              hfma2_bf16(xr[4 * i + 2], lp.p[i].w, lp.p[i].y), hfma2_bf16(xr[4 * i + 3], lp.p[i].w, lp.p[i].y));
    fence_async_smem();
    __syncwarp();
    if (ix.lane < 2) mbar_arrive(BAR_SFULL(sb, wg * 2 + ix.lane));
    bar_sync(1 + wg, 128);
}
__device__ __forceinline__ void load_slab(uint32_t (&xr)[32], uint32_t buf) {
    IDX();
#pragma unroll
    for (int i = 0; i < 8; ++i) ldsm4(buf + (i >> 2) * 8192 + (pan_addr ^ ((i & 3) << 5)), xr[4 * i], xr[4 * i + 1], xr[4 * i + 2], xr[4 * i + 3]);
}
__device__ __forceinline__ void unpack_slab(float (&x)[64], const uint32_t (&xr)[32]) {
#pragma unroll
    for (int i = 0; i < 32; ++i) unpack2(xr[i], x[2 * i], x[2 * i + 1]);
}
__device__ __forceinline__ void store_slab(const float (&x)[64], uint32_t buf, uint32_t pitch, uint32_t pan, int i0, int i1) {
#pragma unroll
    for (int i = i0; i < i1; ++i)
        stsm4(buf + (i >> 2) * pitch + (pan ^ ((i & 3) << 5)), pack2(x[8 * i], x[8 * i + 1]), pack2(x[8 * i + 2], x[8 * i + 3]), pack2(x[8 * i + 4], x[8 * i + 5]), pack2(x[8 * i + 6], x[8 * i + 7]));
}
__device__ __forceinline__ void fetch_halo(uint4* src, bool first, uint32_t sb, uint32_t W, uint32_t lane) {
    mbar_wait(BAR_ONE(sb, EV_KV), 0);
    mbar_wait2(BAR_SREADY(sb, 0), BAR_SREADY(sb, 1), 1);
    uint4 hv[8];
    uint32_t n = 0;
    while (true) {
        bool ok = true;
#pragma unroll
        for (int i = 0; i < 8; ++i) { hv[i] = first ? make_uint4(0, 0, 0, 0) : ld_pkt16(src + i * 32); ok = ok && hv[i].x != 0; }
        if (first || __all_sync(0xffffffffu, ok)) break;
        SPIN_GUARD(n);
    }
#pragma unroll
    for (int i = 0; i < 8; ++i) stsm4(sb + OFF_STG + W * 2048 + (i >> 2) * 8192 + (i & 3) * 512 + lane * 16, hv[i].x, hv[i].y, hv[i].z, hv[i].w);
    bar_arrive(NB_TAIL + W, 64);
    if (!first) {
#pragma unroll
        for (int i = 0; i < 8; ++i) src[i * 32] = make_uint4(0, 0, 0, 0);
    }
}

template <int NG, class G, class U, class Buf>
__device__ __forceinline__ void glu(uint32_t sb, uint32_t wg, G g, U u, Buf buf) {
    IDX();
#pragma unroll
    for (int k = 0; k < NG; ++k) {
        float h[8];
#pragma unroll
        for (int e = 0; e < 8; ++e) h[e] = fmaf(tanh_(g(8 * k + e)), u(8 * k + e), u(8 * k + e));
        stsm4(buf(k >> 2) + (pan_addr ^ ((k & 3) << 5)), pack2(h[0], h[1]), pack2(h[2], h[3]), pack2(h[4], h[5]), pack2(h[6], h[7]));
    }
    fence_async_smem();
    __syncwarp();
    if (lane < 2) mbar_arrive(BAR_SFULL(sb, wg * 2 + lane));
}

template <int NP>
__device__ __forceinline__ void passes128(uint32_t sb, uint32_t wg, uint32_t tw, Ring& r, Stg& stg) {
#pragma unroll 1
    for (int p = 0; p < NP; ++p) {
        float b256[128], none[1];
        mainloop32<false, LAGS>(b256, none, sb, wg, tw, r, EV_LAG2 + p, 80 + 32 * (p & 1), [&] { stg.acquire2(sb, wg); });
        if (threadIdx.x == 0) { TL(29 + 2 * p); TC(114 + 2 * p); }
        if (threadIdx.x == 128) TL(53 + 2 * (p & 1));
        CS(24 + 2 * (p & 1));
        glu<8>(sb, wg, [&](int i) { return b256[i + (i & 32)]; }, [&](int i) { return b256[i + (i & 32) + 32]; }, [&](int pn) { return sb + OFF_STG + wg * 16384 + pn * 8192; });
        if (threadIdx.x == 0) { TL(30 + 2 * p); TC(115 + 2 * p); }
        if (threadIdx.x == 128) TL(54 + 2 * (p & 1));
        CS(25 + 2 * (p & 1));
    }
}

__global__ void __launch_bounds__(384, 1)
fused_block_kernel(const __grid_constant__ Ptrs pt, const __grid_constant__ Maps mp) {
    uint32_t* const g_flags = pt.mail->flags;
    uint2* const g_mod = pt.mail->mod;
    uint4* const g_st1 = pt.mail->st1;
    uint32_t* const g_par2 = pt.mail->par2;
    uint4* const g_halo = pt.mail->halo;
    const __nv_bfloat16* __restrict__ cvec = pt.c;
    if (threadIdx.x == 224) { prefetch_map(&mp.wm8); prefetch_map(&mp.x); }
    extern __shared__ __align__(1024) uint8_t smem[];
    const uint32_t sb = smem_u32(smem);
    const uint32_t tid = threadIdx.x, tw = tid & 127, lane = tid & 31;
    const uint32_t warp = __shfl_sync(0xffffffffu, tid >> 5, 0), wg = warp >> 2;
    uint32_t rank; asm("mov.u32 %0, %%cluster_ctarank;" : "=r"(rank));
    rank = __shfl_sync(0xffffffffu, rank, 0);
    uint32_t ep;
    uint32_t smid; asm volatile("mov.u32 %0, %%smid;" : "=r"(smid));
    const int c = __shfl_sync(0xffffffffu, smid >> 1, 0);
    const int c7 = ((c - 32) * 37) >> 8;
    int grp = c < 32 ? c & 7 : c < 60 ? c - 31 - 7 * c7 : c < 62 ? -1 : 0;
    const int j = c < 32 ? c >> 3 : c < 60 ? 4 + c7 : c < 62 ? (c - 60) * 2 + rank : c - 58;
    const bool aux = grp < 0;
    const int m = grp * 2 + rank;
    uint4* const g_st2 = g_halo + (m > 0 ? (m - 1) * 8 * 512 : 128);

    bool cluster_arrive_early = false;
    if (wg < 2) {
      if (!KDEBUG) cluster_arrive();
      ep = flag_get(g_flags + FL_DONE);
      uint16_t cw[8];
      {
          const __nv_bfloat16* cp = cvec + ((tw >> 5) * 32 + (tw & 3) * 2) * 8 + (lane >> 2);
#pragma unroll
          for (int i = 0; i < 8; ++i) asm volatile("ld.global.nc.u16 %0, [%1];" : "=h"(cw[i]) : "l"(cp + (i >> 1) * 64 + (i & 1) * 8));
      }
      asm volatile("setmaxnreg.inc.sync.aligned.u32 224;");
      if (tid == 0) TL(58);
      if (KDEBUG) cluster_arrive();
      Ring r{0, 0};
      Stg stg{0, 0};
      if (aux) {
        if (wg == 0) {
            const uint4 cv = *(const uint4*)(cvec + tw * 8);
            sts128(sb + OFF_STG + (tw >> 3) * 1024 + (tw & 7) * 16, pack2(silu_(bf_lo(cv.x)), silu_(bf_hi(cv.x))), pack2(silu_(bf_lo(cv.y)), silu_(bf_hi(cv.y))),
                   pack2(silu_(bf_lo(cv.z)), silu_(bf_hi(cv.z))), pack2(silu_(bf_lo(cv.w)), silu_(bf_hi(cv.w))));
            fence_async_smem();
        }
        cluster_wait();
        ep = __shfl_sync(0xffffffffu, ep, 0) / NCTA + 1;
        if (wg == 0) {
            if (tw == 0) {
                uint32_t n = 0;
                while (ld_pkt16(pt.mail->mod1 + 256).z != ep) { SPIN_GUARD(n); __nanosleep(200); }
                mbar_arrive(BAR_ONE(sb, EV_GO));
            }
            bar_sync(1, 128);
#pragma unroll 1
            for (int p = 0; p < 4; ++p) {
                float acc[128];
#pragma unroll
                for (int i = 0; i < 128; ++i) acc[i] = 0.f;
                uint32_t prev = 0;
#pragma unroll 1
                for (int kc = 0; kc < 16; ++kc) {
                    mbar_wait(BAR_FULL(sb, r.slot), r.par);
                    wg_fence();
#pragma unroll
                    for (int k = 0; k < 4; ++k)
                        wgmma_n256(acc, mk_desc(d16(sb) + kc * 64, OFF_STG + k * 32, 16, 0, 1), mk_desc(d16(sb) + r.slot * (SLOT >> 4), k * 2048, 8192, 1024, 1));
                    wg_commit();
                    wg_wait<1>();
                    if (kc > 0 && tw < 4) mbar_arrive(BAR_EMPTY(sb, prev));
                    prev = r.slot;
                    r.next();
                }
                wg_wait<0>();
                if (tw < 4) mbar_arrive(BAR_EMPTY(sb, prev));
                if (tw < 4) {
#pragma unroll
                    for (int jn = 0; jn < 32; ++jn) sts32(sb + OFF_TAB + (jn * 4 + tw) * 4, pack2(acc[jn * 4], acc[jn * 4 + 1]));
                }
                bar_sync(1, 128);
                const int vec = 2 + p, blk = p * 4 + j;
                const uint32_t val = lds32(sb + OFF_TAB + tw * 4);
                if (vec == 2 || vec == 5) st_pkt(g_mod + (8 + blk) * 128 + tw, val, ep);
                else {
                    const float one = vec == 4 ? 1.f : 0.f;
                    g_par2[((blk & 3) * 16 + (tw >> 3)) * 16 + (tw & 3) * 4 + (vec - 3) * 2 + ((tw >> 2) & 1)] =
                        pack2(0.5f * bf_round(one + bf_lo(val)), 0.5f * bf_round(one + bf_hi(val)));
                }
                bar_sync(1, 128);
                if (tw == 0) {
                    if (vec == 3 || vec == 4) asm volatile("red.release.gpu.global.add.u32 [%0], 1;" :: "l"(&g_flags[FL_LN2]) : "memory");
                    TL(1 + p);
                }
            }
            if (lane < 2) mbar_arrive_cta(BAR_ONE(sb, EV_P0), lane);
        }
        r = Ring{64 % NSLOT, (64 / NSLOT) & 1};
        mbar_wait(BAR_ONE(sb, EV_P0), 0);
        passes128<4>(sb, wg, tw, r, stg);
      } else {
        float xs[64];
        uint32_t xp[32];
        {
            IDX();
            if (q4 < 2) st_pkt16(g_st1 + (m * 8 + j) * 512 + wg * 64 + w4 * 16 + g8 + q4 * 8, 0, 0, 0, 0);
            if (warp == 0) st_pkt16(pt.mail->mod1 + g8 * 512 + (m * 8 + j) * 4 + q4, 0, 0, 0, 0);
            sts128(sb + tid * 16, pack2(silu_(bf_lo(cw[0])), silu_(bf_lo(cw[1]))), pack2(silu_(bf_lo(cw[2])), silu_(bf_lo(cw[3]))),
                   pack2(silu_(bf_lo(cw[4])), silu_(bf_lo(cw[5]))), pack2(silu_(bf_lo(cw[6])), silu_(bf_lo(cw[7]))));
            cluster_wait();
            ep = __shfl_sync(0xffffffffu, ep, 0) / NCTA + 1;
            load_slab(xp, stg.acquire2(sb, wg));
            unpack_slab(xs, xp);
            if (tid == 0) TL(24);
            if (tid == 128) TL(27);
        }
#pragma unroll 1
        for (int blk = 0; ; ++blk) {
        {
            IDX();
            uint4* const st = (blk ? g_st2 : g_st1 + m * 8 * 512) + wg * 64 + w4 * 16 + g8;
            RowAcc ra;
#pragma unroll
            for (int e = 0; e < 64; ++e) ra.add(e, xs[e]);
            ra.publish(st + j * 512, q4, ep);
            uint32_t t_pub = 0; if (PDLY) asm volatile("mov.u32 %0, %%clock;" : "=r"(t_pub));
            if (tid == 0) TL(blk ? 9 : 26);
            if (tid == 128 && blk) TL(34);
            if (blk) CS(11);
            LnPar lp;
            if (blk == 0) {
            uint4* const mod_out = pt.mail->mod1 + g8 * 512 + (m * 8 + j) * 4 + q4;
            if (wg == 0) {
                uint4 af[8];
#pragma unroll
                for (int i = 0; i < 8; ++i) af[i] = lds128(sb + w4 * 512 + i * 64 + q4 * 16);
                float c[4][4] = {};
#pragma unroll
                for (int i = 0; i < 8; ++i) {
                    if (!(i & 1)) mbar_wait(BAR_ONE(sb, EV_WIN + (i >> 1)), 0);
                    if (i == 6 && tid == 0) TL(25);
#pragma unroll
                    for (int h = 0; h < 2; ++h) {
                        uint32_t b0, b1, b2, b3;
                        ldsm4t(sb + 5 * SLOT + i * 4096 + w4 * 1024 + h * 512 + (lane & 15) * 32 + (lane >> 4) * 16, b0, b1, b2, b3);
                        mma16816(c[2 * h], h ? af[i].z : af[i].x, 0u, h ? af[i].w : af[i].y, 0u, b0, b1);
                        mma16816(c[2 * h + 1], h ? af[i].z : af[i].x, 0u, h ? af[i].w : af[i].y, 0u, b2, b3);
                    }
                }
                if (lane < 4) sts128(sb + OFF_TAB + w4 * 64 + lane * 16, __float_as_uint(c[0][0] + c[2][0]), __float_as_uint(c[0][1] + c[2][1]),
                                     __float_as_uint(c[1][0] + c[3][0]), __float_as_uint(c[1][1] + c[3][1]));
                if (lane < 2) mbar_arrive_cta(BAR_ONE(sb, EV_P0), lane);
                bar_sync(1, 128);
                if (w4 == 0) {
                    float a[4] = {0.f, 0.f, 0.f, 0.f};
#pragma unroll
                    for (int i = 0; i < 4; ++i) {
                        const uint4 t = lds128(sb + OFF_TAB + i * 64 + q4 * 16);
                        a[0] += __uint_as_float(t.x); a[1] += __uint_as_float(t.y); a[2] += __uint_as_float(t.z); a[3] += __uint_as_float(t.w);
                    }
                    const float add = m >= 8 ? 1.f : 0.f;
                    st_pkt16(mod_out, pack2(bf_round(a[0]) + add, bf_round(a[1]) + add), pack2(bf_round(a[2]) + add, bf_round(a[3]) + add), ep, 0);
                    if (tid == 0) TL(3);
                }
            } else if (LWAIT >= 0) mbar_wait(BAR_ONE(sb, EV_WIN + LWAIT), 0);
            } else {
                mbar_wait(BAR_ONE(sb, EV_LN2), 0);
                stg.acquire2(sb, wg);
            }
            lp.load(sb, q4);
#pragma unroll
            for (int e = 0; e < 32; ++e) xp[e] = pack2(xs[2 * e], xs[2 * e + 1]);
            if (PDLY && blk) { uint32_t t1; do { asm volatile("mov.u32 %0, %%clock;" : "=r"(t1)); } while (t1 - t_pub < PDLY); }
            if (blk) CS(13);
            const LnRow n = merge_stats(st, q4, ep, sb);
            if (tid == 0) TL(blk ? 49 : 48);
            if (tid == 128) TL(blk ? 45 : 28);
            if (blk) CS(18);
            uint32_t xn[32];
            ln_norm(xn, xs, n);
            if (blk == 0) { mbar_wait(BAR_ONE(sb, EV_PAR), 0); lp.load(sb, q4); }
            ln_emit(xn, lp, sb, wg, ix);
            if (tid == 0) { TL(blk ? 36 : 8); TC(blk ? 109 : 103); }
            if (tid == 128) TL(blk ? 43 : 22);
            if (blk) CS(21);
        }
        if (blk == 0) {
        {
            float kv[128], qa[64];
            mbar_wait(BAR_FULL(sb, r.slot), r.par);
            step32<true, true>(kv, qa, sb, wg, r.slot, 0);
            TS(0, 0);
            Pipe pp(sb, tw, r.slot);
            r.next();
#pragma unroll 1
            for (int it = 1; it < 32 - LAGQ; ++it) {
                pp.acquire<true>(sb, wg ? 0 : AF_REL, r);
                step32<true, false>(kv, qa, sb, wg, r.slot, it < 4 ? it : -1);
                pp.issued(r.slot);
                TS(it, 0);
                r.next();
            }
            auto half = [&](uint32_t slot, bool q) {
                const uint32_t st = d16(sb) + slot * (SLOT >> 4);
#pragma unroll
                for (int k = 0; k < 2; ++k) {
                    const uint64_t da = mk_desc(st + wg * 256, k * 32, 16, 512, 2);
                    if (q) wgmma_n128(qa, da, mk_desc(st, 24576 + k * 2048, 4096, 1024, 1)); else wgmma_n256(kv, da, mk_desc(st, 8192 + k * 2048, 4096, 1024, 1));
                }
            };
            auto part = [&](bool q) {
                wg_fence();
#pragma unroll
                for (int it = 32 - LAGQ; it < 32; ++it) half(it % NSLOT, q);
                wg_commit();
            };
            stg.acquire2(sb, wg); mbar_wait2(BAR_SREADY(sb, 2), BAR_SREADY(sb, 3), 1);
            if (wg == 0) { pp.drain1(); pp.drain0(); }
#pragma unroll 1
            for (int it = 32 - LAGQ; it < 32; ++it) {
                pp.acquire<true>(sb, wg ? 0 : AF_REL, r);
                if (wg) { wg_fence(); half(r.slot, false); wg_commit(); }
                pp.issued(NSLOT);
                TS(it, 0);
                r.next();
            }
            if (wg == 0) { mbar_wait(BAR_ONE(sb, EV_LAG0), 0); part(false); part(true); wg_wait<1>(); }
            else { wg_wait<1>(); if (tw == 0) mbar_arrive(BAR_ONE(sb, EV_LAG0)); wg_wait<0>(); }
            CS(8);
            IDX();
            uint32_t k1[16], k2[16], v1[16], v2[16], qf[32];
#pragma unroll
            for (int i = 0; i < 128; ++i) asm volatile("" : "+f"(kv[i]) :: "memory");
#pragma unroll
            for (int t = 0; t < 16; ++t) k2[t] = pack2(kv[4 * t + 2], kv[4 * t + 3]);
#pragma unroll
            for (int t = 0; t < 16; ++t) k1[t] = pack2(kv[4 * t], kv[4 * t + 1]);
#pragma unroll
            for (int t = 0; t < 16; ++t) v2[t] = pack2(kv[64 + 4 * t + 2], kv[64 + 4 * t + 3]);
            const uint32_t nxt = warp + ((warp & 1) ? 3 : 1);
            if (nxt < 8) {
                const uint32_t dst = sb + OFF_STG + (nxt >> 2) * 16384 + (nxt & 3) * 2048 + lane * 16;
#pragma unroll
                for (int h = 0; h < 4; ++h) stsm4(dst + h * 512, k2[4 * h], k2[4 * h + 1], k2[4 * h + 2], k2[4 * h + 3]);
#pragma unroll
                for (int h = 0; h < 4; ++h) stsm4(dst + 8192 + h * 512, v2[4 * h], v2[4 * h + 1], v2[4 * h + 2], v2[4 * h + 3]);
                bar_arrive(NB_TAIL + nxt, 64);
            } else if (m < 15) {
                uint4* dst = g_halo + (m * 8 + j) * 512 + (w4 >> 1) * 256 + lane;
#pragma unroll
                for (int h = 0; h < 4; ++h) { if (!k2[4 * h]) k2[4 * h] = 0x8000u; if (!v2[4 * h]) v2[4 * h] = 0x8000u; }
#pragma unroll
                for (int h = 0; h < 4; ++h) st_pkt16(dst + h * 32, k2[4 * h], k2[4 * h + 1], k2[4 * h + 2], k2[4 * h + 3]);
#pragma unroll
                for (int h = 0; h < 4; ++h) st_pkt16(dst + 128 + h * 32, v2[4 * h], v2[4 * h + 1], v2[4 * h + 2], v2[4 * h + 3]);
            }
#pragma unroll
            for (int t = 0; t < 16; ++t) { v1[t] = pack2(kv[64 + 4 * t], kv[64 + 4 * t + 1]); v1[t] = movm(v1[t]); v2[t] = movm(v2[t]); }
            if (tid == 0) TL(33);
            CS(2);
            if (wg) part(true);
            bar_sync(NB_TAIL + warp, 64);
            CS(4);
            if (tid == 0) TL(5);
            uint32_t k0[16], v0[16];
            const uint32_t mine = sb + OFF_STG + wg * 16384 + w4 * 2048;
#pragma unroll
            for (int h = 0; h < 4; ++h) ldsm4(mine + lane * 16 + h * 512, k0[4 * h], k0[4 * h + 1], k0[4 * h + 2], k0[4 * h + 3]);
#pragma unroll
            for (int h = 0; h < 4; ++h) ldsm4t(mine + lane * 16 + 8192 + h * 512, v0[4 * h], v0[4 * h + 1], v0[4 * h + 2], v0[4 * h + 3]);
            wg_wait<0>();
#pragma unroll
            for (int it = 32 - LAGQ; it < 32; ++it) pp.rel(it % NSLOT);
            TS(31, 1);
            if (tid == 0) { TL(4); TC(104); }
            if (tid == 128) TL(50);
            CS(1);
#pragma unroll
            for (int i = 0; i < 64; ++i) asm volatile("" : "+f"(qa[i]) :: "memory");
            const bool lo0 = q4 * 2 > g8, lo1 = q4 * 2 + 1 > g8;
            const bool nopast = m == 0 && (warp & 5) == 0;
            const uint32_t lomask = (lo0 ? 0xFFFFu : 0u) | (lo1 ? 0xFFFF0000u : 0u);
            const uint32_t orow = mine + (lane & 7) * 128 + (((lane >> 3) ^ (lane & 7)) << 4);
            const float sl2 = 0.17677669529663687f * 1.4426950408889634f;
#pragma unroll
            for (int pn = 0; pn < 2; ++pn) {
                float e0[4], e1[4], mx[4], sum[4];
#pragma unroll
                for (int hh = 0; hh < 2; ++hh) {
                    const int h = pn * 2 + hh;
#pragma unroll
                    for (int i = 8 * h; i < 8 * h + 8; ++i) qf[i] = pack2(qa[2 * i], qa[2 * i + 1]);
                    float s[3][4];
#pragma unroll
                    for (int t = 0; t < 3; ++t) {
                        const uint32_t* k = (t == 0 ? k0 : t == 1 ? k1 : k2) + 4 * h;
                        s[t][0] = s[t][1] = s[t][2] = s[t][3] = 0.f;
                        mma16816(s[t], qf[h * 8], qf[h * 8 + 1], qf[h * 8 + 2], qf[h * 8 + 3], k[0], k[1]);
                        mma16816(s[t], qf[h * 8 + 4], qf[h * 8 + 5], qf[h * 8 + 6], qf[h * 8 + 7], k[2], k[3]);
                    }
#pragma unroll
                    for (int hf = 0; hf < 2; ++hf) {
                        const int u = hh * 2 + hf;
                        e0[u] = lo0 ? ((hf == 0 && nopast) ? -INFINITY : s[hf][hf * 2]) : s[hf + 1][hf * 2];
                        e1[u] = lo1 ? ((hf == 0 && nopast) ? -INFINITY : s[hf][hf * 2 + 1]) : s[hf + 1][hf * 2 + 1];
                        mx[u] = fmaxf(e0[u], e1[u]);
                    }
                }
#pragma unroll
                for (int o = 1; o < 4; o <<= 1)
#pragma unroll
                    for (int u = 0; u < 4; ++u) mx[u] = fmaxf(mx[u], __shfl_xor_sync(0xffffffffu, mx[u], o));
#pragma unroll
                for (int u = 0; u < 4; ++u) {
                    const float c = -mx[u] * sl2;
                    e0[u] = ex2(fmaf(e0[u], sl2, c)); e1[u] = ex2(fmaf(e1[u], sl2, c));
                    sum[u] = e0[u] + e1[u];
                }
#pragma unroll
                for (int o = 1; o < 4; o <<= 1)
#pragma unroll
                    for (int u = 0; u < 4; ++u) sum[u] += __shfl_xor_sync(0xffffffffu, sum[u], o);
#pragma unroll
                for (int u = 0; u < 4; ++u) {
                    const int h = pn * 2 + (u >> 1);
                    const float inv = rcp(sum[u]);
                    const uint32_t p = pack2(e0[u] * inv, e1[u] * inv);
                    const uint32_t* va = ((u & 1) ? v1 : v0) + 4 * h;
                    const uint32_t* vb = ((u & 1) ? v2 : v1) + 4 * h;
                    float o[2][4] = {};
#pragma unroll
                    for (int d = 0; d < 2; ++d) mma16816(o[d], va[2 * d], va[2 * d + 1], vb[2 * d], vb[2 * d + 1], p & lomask, p & ~lomask);
                    stsm4t((orow ^ ((u >> 1) << 6)) + pn * 8192 + (u & 1) * 1024, pack2(o[0][0], o[0][1]), pack2(o[0][2], o[0][3]), pack2(o[1][0], o[1][1]), pack2(o[1][2], o[1][3]));
                }
                fence_async_smem();
                __syncwarp();
                if (lane == 0) mbar_arrive(BAR_SFULL(sb, wg * 2 + pn));
                if (pn == 0) { CS(5); block_end(sb); }
            }
            CS(6);
            if (tid == 32) TL(41);
            mbar_wait(BAR_FULL(sb, 32 % NSLOT + wg), (32 / NSLOT) & 1);
            load_slab(xp, sb + (32 % NSLOT + wg) * SLOT);
            bar_sync(1 + wg, 128);
            if (tid == 0) { TL(6); TC(106); }
            if (tid == 128) TL(44);
            CS(7);
        }
        } else {
        {
            float ag[88], au[88];
            mainloop32<true, LAG>(ag, au, sb, wg, tw, r, EV_LAG1, 48, [&] {
                stg.acquire2(sb, wg);
                Ring q = r; if (!wg) q.next();
                mbar_wait(BAR_EMPTY(sb, q.slot), q.par ^ 1);
            });
            if (tid == 0) { TL(10); TC(110); }
            if (tid == 128) TL(51);
            CS(22);
            glu<11>(sb, wg, [&](int i) { return ag[i]; }, [&](int i) { return au[i]; },
                    [&](int pn) { return pn < 2 ? sb + OFF_STG + wg * 16384 + pn * 8192 : sb + (wg ? P3_SLOT1 : P3_SLOT0) * SLOT + 24576; });
            if (tid == 0) { TL(11); TC(111); }
            if (tid == 128) TL(52);
            CS(23);
        }
        passes128<2>(sb, wg, tw, r, stg);
        if (tid == 0) { TL(12); TC(112); }
        }
        {
            float acc[64], gf[32];
            mainloop64(acc, blk == 0, sb, wg, tw, r, [&] {
                mbar_wait(BAR_ONE(sb, EV_GA + blk), 0);
                if (blk) stg.acquire2(sb, wg);
                unpack_slab(xs, xp);
                uint32_t gt[16];
#pragma unroll
                for (int cg = 0; cg < 16; ++cg) gt[cg] = lds32(sb + OFF_TAB + blk * 256 + cg * 16 + (tw & 3) * 4);
#pragma unroll
                for (int i = 0; i < 16; ++i) unpack2(gt[i], gf[2 * i], gf[2 * i + 1]);
            });
            if (tid == 0) { TL(blk ? 13 : 7); TC(blk ? 113 : 107); }
            if (tid == 128) TL(blk ? 57 : 42);
            CS(blk ? 30 : 10);
#pragma unroll
            for (int e = 0; e < 64; ++e) xs[e] = fmaf(gf[(e >> 2) * 2 + (e & 1)], acc[e], xs[e]);
        }
        if (blk) break;
        }
        cluster_arrive();
        {
            IDX();
#pragma unroll
            for (int p = 0; p < 2; ++p) {
                store_slab(xs, sb + OFF_STG + wg * 16384, 8192, pan_addr, 4 * p, 4 * p + 4);
                stg.publish(sb, wg, lane);
            }
            if (tid == 0) TL(14);
            CS(31);
        }
      }
    } else {
        if (warp == 8 && !aux && elect_one()) {
#pragma unroll
            for (int i = 0; i < 4; ++i) mbar_init(BAR_SREADY(sb, i), 1);
#pragma unroll
            for (int i = 0; i < 4; ++i) mbar_init(BAR_ONE(sb, EV_WIN + i), 1);
#pragma unroll
            for (int i = 0; i < 4; ++i) {
                mbar_expect_tx(BAR_SREADY(sb, i), 8192);
                tma_load3(sb + OFF_STG + i * 8192, &mp.x, j * 128 + (i & 1) * 64, m * 64 + (i >> 1) * 32, BAR_SREADY(sb, i));
            }
#pragma unroll 1
            for (int i = 0; i < 4; ++i) {
                mbar_expect_tx(BAR_ONE(sb, EV_WIN + i), 8192);
                tma_load(sb + 5 * SLOT + i * 8192, &mp.wm8, 2 * i * 6144 + (m * 8 + j) * 16, 0, BAR_ONE(sb, EV_WIN + i));
                tma_load(sb + 5 * SLOT + i * 8192 + 4096, &mp.wm8, (2 * i + 1) * 6144 + (m * 8 + j) * 16, 0, BAR_ONE(sb, EV_WIN + i));
            }
        }
        __syncwarp();
        asm volatile("setmaxnreg.dec.sync.aligned.u32 56;");
        if (elect_one()) {
            if (warp == 8) {
                prefetch_map(&mp.wqkv); prefetch_map(&mp.wmod);
            } else if (warp < 11) {
                mbar_init(BAR_EMPTY(sb, NSLOT), 1);
#pragma unroll
                for (int i = 0; i < 2; ++i) { mbar_init(BAR_SFULL(sb, (warp - 9) * 2 + i), 4); if (aux) mbar_init(BAR_SREADY(sb, (warp - 9) * 2 + i), 1); }
#pragma unroll
                for (int i = 0; i < 3; ++i) {
                    mbar_init(BAR_EMPTY(sb, (warp - 9) * 3 + i), 4);
                    mbar_init(BAR_FULL(sb, (warp - 9) * 3 + i), 1); mbar_init(BAR_FULL(sb, (warp - 9) * 3 + i) + AF_REL, 1);
                }
            } else {
#pragma unroll
                for (int i = EV_P0; i < EV_COUNT; ++i) mbar_init(BAR_ONE(sb, i), i == EV_P0 ? 8 : 1);
            }
            asm volatile("fence.mbarrier_init.release.cluster;" ::: "memory");
        }
        __syncwarp();
        cluster_arrive();
        ep = 0;
        if (warp != 8 || aux) ep = flag_get(g_flags + FL_DONE);
        cluster_wait();
        ep = __shfl_sync(0xffffffffu, ep, 0) / NCTA + 1;
        if (warp == 8) {
            const bool el = elect_one();
            Ring r{0, 1};
            if (aux) {
                mbar_wait(BAR_ONE(sb, EV_GO), 0);
#pragma unroll 1
                for (int it = 0; it < 64; ++it) {
                    const int col = 2048 + (it >> 4) * 1024 + j * 256;
                    mbar_wait(BAR_EMPTY(sb, r.slot), r.par);
                    const uint32_t st = sb + r.slot * SLOT, fb = BAR_FULL(sb, r.slot);
                    if (el) {
                        mbar_expect_tx(fb, 32768);
#pragma unroll
                        for (int b = 0; b < 4; ++b) tma_load(st + b * 8192, &mp.wmod, col + b * 64, (it & 15) * 64, fb);
                    }
                    r.next();
                }
                mbar_wait(BAR_ONE(sb, EV_P0), 0);
                const CUtensorMap* wm = rank ? &mp.wu : &mp.wg;
#pragma unroll 1
                for (int g = 0; g < 128; ++g) {
                    const int mx = (j >> 1) * 8 + (g >> 5) * 2 + rank, k0 = (g & 31) * 32;
                    if (k0 == 0) {
                        uint32_t n = 0;
                        while (!__all_sync(0xffffffffu, (int32_t)(flag_get(g_flags + FL_PROG + fidx(mx, lane >> 4, lane & 15)) - (ep * 8 + ST_H2)) >= 0)) { SPIN_GUARD(n); __nanosleep(500); }
                    }
                    mbar_wait(BAR_EMPTY(sb, r.slot), r.par);
                    const uint32_t st = sb + r.slot * SLOT, fb = BAR_FULL(sb, r.slot);
                    if (el) {
                        mbar_expect_tx(fb, 24576);
                        tma_load_mc(st + 8192 + rank * 4096, wm, HC3, k0, fb);
                        tma_load_mc(st + 16384 + rank * 4096, wm, HC3 + 64, k0, fb);
                        tma_load(st, &mp.h2l, k0, mx * 128, fb);
                    }
                    r.next();
                }
            } else {
#pragma unroll 1
                for (int it = 0; it < 32; ++it) {
                    const int cb = j * 128 + rank * 64, k0 = kof(it, 2, j);
                    if (it == BW0) mbar_wait(BAR_ONE(sb, BWEV), 0);
                    if (it == BW1) mbar_wait(BAR_ONE(sb, EV_PAR), 0);
                    if (it == 5) mbar_wait(BAR_ONE(sb, EV_P0), 0);
                    if (it == AG0) mbar_wait(BAR_ONE(sb, (AGW & 1) ? EV_AGO : EV_FGO), 0);
                    mbar_wait(BAR_EMPTY(sb, r.slot), r.par);
                    const uint32_t st = sb + r.slot * SLOT, fb = BAR_FULL(sb, r.slot);
                    if (el) {
                        mbar_expect_tx(fb, it < 4 ? 24576 : 28672);
                        tma_load_mc(st + 8192 + rank * 4096, &mp.wqkv, 1024 + cb, k0, fb);
                        tma_load_mc(st + 16384 + rank * 4096, &mp.wqkv, 2048 + cb, k0, fb);
                        tma_load_mc(st + 24576 + rank * 4096, &mp.wqkv, cb, k0, fb);
                        if (it < 4) mbar_arrive(fb + AF_REL);
                        if (it == PFWO + (m >> 1)) { tma_prefetch(&mp.wo, j * 128, m * 64); tma_prefetch(&mp.wo, j * 128 + 64, m * 64); }
                    }
                    r.next();
                }
                if (el) mbar_arrive(BAR_ONE(sb, EV_KV));
#pragma unroll 1
                for (int it = 0; it < 16; ++it) {
                    const int k0 = kof(it, 1, j);
                    if (it == AG1) mbar_wait(BAR_ONE(sb, (AGW & 2) ? EV_AGO1 : EV_FGO1), 0);
                    mbar_wait(BAR_EMPTY(sb, r.slot), r.par);
                    const uint32_t st = sb + r.slot * SLOT, fb = BAR_FULL(sb, r.slot);
                    if (el) {
                        mbar_expect_tx(fb, it < 2 ? 32768 : 24576);
                        tma_load_mc(st + 16384 + rank * 8192, &mp.wo, j * 128 + rank * 64, k0, fb);
                        if (it < 2) {
                            tma_load3(st, &mp.x, j * 128, m * 64 + it * 32, fb); tma_load3(st + 8192, &mp.x, j * 128 + 64, m * 64 + it * 32, fb);
                            mbar_arrive(fb + AF_REL);
                        }
                        if (it == 6) { prefetch_map(rank ? &mp.wu : &mp.wg); prefetch_map(rank ? &mp.wu3 : &mp.wg3); }
                    }
                    r.next();
                }
                const CUtensorMap* wm = rank ? &mp.wu : &mp.wg;
#pragma unroll 1
                for (int g = 0; g < 96; ++g) {
                    if (g == AG2) mbar_wait(BAR_ONE(sb, (AGW & 4) ? EV_AGO2 : EV_FGO2), 0);
                    const int p = g >> 5, cb = hcol(p, j), k0 = p == 0 ? kof(g, 2, j) : (g & 31) * 32;
                    mbar_wait(BAR_EMPTY(sb, r.slot), r.par);
                    const uint32_t st = sb + r.slot * SLOT, fb = BAR_FULL(sb, r.slot);
                    if (el) {
                        mbar_expect_tx(fb, (g < 4 || p > 0) ? 24576 : 28672);
                        tma_load_mc(st + 8192 + rank * 4096, wm, cb, k0, fb);
                        tma_load_mc(st + 16384 + rank * 4096, wm, cb + 64, k0, fb);
                        if (p == 0) tma_load3_mc(st + 24576 + rank * 4096, rank ? &mp.wu3 : &mp.wg3, j, k0, fb);
                        else tma_load(st, &mp.h2l, k0, m * 128, fb);
                        if (g < 4) mbar_arrive(fb + AF_REL);
                        if (g == 60) prefetch_map(&mp.wd);
                    }
                    r.next();
                }
#pragma unroll 1
                for (int g = 0; g < 56; ++g) {
                    if (g == 0 || (g & 15) == 6 && g > 6) mbar_wait(BAR_ONE(sb, EV_H0 + (g >> 4)), 0);
                    const int k0 = g * 64;
                    mbar_wait(BAR_EMPTY(sb, r.slot), r.par);
                    const uint32_t st = sb + r.slot * SLOT, fb = BAR_FULL(sb, r.slot);
                    if (el) {
                        mbar_expect_tx(fb, 32768);
                        tma_load_mc(st + 16384 + rank * 8192, &mp.wd, j * 128 + rank * 64, k0, fb);
                        tma_load(st, &mp.hb, k0, m * 128, fb); tma_load(st + 8192, &mp.hb, k0, m * 128 + 64, fb);
                    }
                    r.next();
                }
            }
        } else if (aux) {
            if (warp < 11) {
                const uint32_t w = warp - 9;
                const bool el = elect_one();
#pragma unroll 1
                for (int p = 0; p < 4; ++p) {
                    const int mx = (j >> 1) * 8 + p * 2 + rank;
                    if (el) { mbar_arrive(BAR_SREADY(sb, w * 2)); mbar_arrive(BAR_SREADY(sb, w * 2 + 1)); }
                    mbar_wait2(BAR_SFULL(sb, w * 2), BAR_SFULL(sb, w * 2 + 1), p & 1);
                    if (el) {
                        tma_store(&mp.hb, HC3, mx * 128 + w * 64, sb + OFF_STG + w * 16384); tma_store(&mp.hb, HC3 + 64, mx * 128 + w * 64, sb + OFF_STG + w * 16384 + 8192);
                        bulk_commit(); bulk_wait_fence(); flag_set(g_flags + FL_AUX + mx * 2 + w, ep * 8 + ST_H + 3);
                    }
                }
            }
        } else if (warp == 11) {
            const bool el = elect_one();
            const int row0 = m * 128;
            const uint32_t* const fl = g_flags + FL_PROG + fidx(m, lane >> 4, kof(lane & 15, 1, j) >> 6);
            if (el) { prefetch_map(&mp.h1h); prefetch_map(&mp.h2h); prefetch_map(&mp.h2l); }
            auto gate = [&](int vec, int ev) {
                uint4 v; uint32_t n = 0;
                while (true) {
                    v = ld_pkt2(g_mod + vec * 512 + j * 64 + lane * 2);
                    if (__all_sync(0xffffffffu, v.y == ep && v.w == ep)) break;
                    SPIN_GUARD(n); __nanosleep(300);
                }
                asm volatile("st.shared.v2.u32 [%0], {%1, %2};" :: "r"(sb + OFF_TAB + (ev - EV_GA) * 256 + lane * 8), "r"(v.x), "r"(v.z) : "memory");
                __syncwarp();
                if (lane == 0) mbar_arrive(BAR_ONE(sb, ev));
            };
            {
                const uint4* pk = pt.mail->mod1 + grp * 512 + j * 32 + lane;
                uint4 a, b; uint32_t n = 0;
                mbar_wait(BAR_ONE(sb, EV_WIN3), 0);
                while (true) {
                    a = ld_pkt16(pk); b = ld_pkt16(pk + 256);
                    if (__all_sync(0xffffffffu, a.z == ep && b.z == ep)) break;
                    SPIN_GUARD(n);
                }
                sts128(sb + OFF_PAR + lane * 16, a.x, a.y, b.x, b.y);
                __syncwarp();
                if (lane == 0) { mbar_arrive(BAR_ONE(sb, EV_PAR)); TL(46); }
            }
            mbar_wait(BAR_ONE(sb, EV_P0), 0);
            Ring r{0, 1};
#pragma unroll 1
            for (int ph = 0; ph < 3; ++ph) {
                const int sh = ph == 1 ? 1 : 2, nst = 8 << sh;
                const uint32_t half = 16384 >> sh, target = ep * 8 + ST_H1 + ph;
                const CUtensorMap* tm = ph == 0 ? &mp.h1h : ph == 1 ? &mp.o : &mp.h2h;
                if (ph == 1) gate(2, EV_GA);
                if (ph == 2) {
                    uint32_t n = 0;
                    while ((int32_t)(flag_get(g_flags + FL_LN2) - ep * 8) < 0) { SPIN_GUARD(n); __nanosleep(200); }
                    const uint4 v = __ldcg((const uint4*)(g_par2 + j * 128) + lane);
                    sts128(sb + OFF_PAR + lane * 16, v.x, v.y, v.z, v.w);
                    __syncwarp();
                    if (lane == 0) mbar_arrive(BAR_ONE(sb, EV_LN2));
                }
                const uint32_t lw = ~lane & 1, lt = lane >> 1, ls = (r.slot + lt) % NSLOT, lk = kof(lt, sh, j), lb = BAR_FULL(sb, ls) + (lw ? 0 : AF_REL);
                const uint32_t* const lf = g_flags + FL_PROG + fidx(m, lw, lk >> 6);
                int fr = 1 << sh;
                uint32_t todo = 0x3ffffu >> (2 * fr) << (2 * fr), have = ~todo, n = 0, v = 0;
                r.skip(fr);
#pragma unroll 1
                for (; fr < NSLOT; ++fr) { mbar_wait(BAR_EMPTY(sb, r.slot), r.par); r.next(); }
                if (PWAIT) mbar_wait(BAR_SFULL(sb, 2), ph & 1);
                if (PWAIT > 1) spin(PWAIT);
                if (ph == XST - 1) CS(33);
                do {
                    if (!PMASK || !((have >> lane) & 1)) v = flag_get(lf);
                    if (fr < 9 && mbar_test(BAR_EMPTY(sb, r.slot), r.par)) { ++fr; r.next(); }
                    SPIN_GUARD(n);
                    have |= __ballot_sync(0xffffffffu, (int32_t)(v - target) >= 0);
                    const uint32_t go = have & todo & ((1u << (2 * fr)) - 1);
                    if ((go >> lane) & 1) {
                        if (!lw) mbar_expect_tx(lb, half);
                        tma_load(sb + ls * SLOT + lw * half, tm, lk, row0 + lw * 64, lb);
                    }
                    __syncwarp();
                    if (lane < 2 && (todo & (0x555u << lane)) && !(todo & ~go & (0x555u << lane))) mbar_arrive(BAR_ONE(sb, (lane ? EV_FGO : EV_AGO) + ph));
                    if (ph == XST - 1) { if (go & (1u << (2 << sh))) CS(34); if (go & (2u << (2 << sh))) CS(35); if (todo & 0x555u) CS(36); if (todo & 0xaaau) CS(37); }
                    todo &= ~go;
                } while (~have);
                if (ph == XST - 1) CS(38);
                int k = kof(fr, sh, j);
#pragma unroll 1
                for (; fr < nst; ++fr) {
                    if (fr == 9 || fr == 18) {
                        const uint32_t skip = fr == 9 << (sh - 1) ? 0 : ~0x01fc01fcu;
                        while (~(__ballot_sync(0xffffffffu, (int32_t)(flag_get(fl) - target) >= 0) | skip)) SPIN_GUARD(n);
                    }
                    const uint32_t st = sb + r.slot * SLOT, fb = BAR_FULL(sb, r.slot);
                    mbar_wait(BAR_EMPTY(sb, r.slot), r.par);
                    if (el) {
                        tma_load(st + half, tm, k, row0 + 64, fb);
                        mbar_expect_tx(fb + AF_REL, half);
                        tma_load(st, tm, k, row0, fb + AF_REL);
                    }
                    if (ph == XST - 1 && fr == 9) CS(39);
                    r.next();
                    k = kof(fr + 1, sh, j);
                }
            }
#pragma unroll 1
            for (int p = 0; p < 4; ++p) {
                const uint32_t* f = p < 3 ? fl : g_flags + FL_AUX + m * 2 + (lane & 1);
                uint32_t n = 0;
                while (!__all_sync(0xffffffffu, (int32_t)(flag_get(f) - (ep * 8 + ST_H + p)) >= 0)) { SPIN_GUARD(n); __nanosleep(500); }
                if (el) mbar_arrive(BAR_ONE(sb, EV_H0 + p));
                if (p == 0) gate(5, EV_GB);
            }
        } else {
            const uint32_t w = warp - 9;
            const int row0 = m * 128 + w * 64;
            const uint32_t stg = sb + OFF_STG + w * 16384;
            uint32_t* const fl = g_flags + FL_PROG + fidx(m, w, 2 * j);
            uint32_t b = 0, par = 0;
            const bool el = elect_one();
            auto store = [&](const CUtensorMap* tm, int col, bool nat = false) {
                mbar_wait(BAR_SFULL(sb, w * 2 + b), (par >> b) & 1);
                par ^= 1u << b;
                if (el) {
                    if (nat) tma_store3(tm, col, row0 >> 1, 0, stg + b * 8192); else tma_store(tm, col, row0, stg + b * 8192);
                    bulk_commit();
                }
                b ^= 1;
            };
            auto send2 = [&](const CUtensorMap* tm, const uint32_t* buf, int step) {
                const uint32_t* const q = buf + (size_t)((row0 + lane) * (D_ / 2) + j * 64 + 31);
                store(tm, j * 128);
                if (step == XST) CS(33);
                uint32_t z = landed(el, q, D_ / 2, pt.zero);
                if (el) flag_set(fl, ep * 8 + step + z);
                if (step == XST) CS(34);
                if (step != ST_O) { mbar_wait(BAR_ONE(sb, EV_FGO + step - ST_H1), 0); pause(w ? P1H : P1H + 1000); }
                store(tm, j * 128 + 64);
                if (step == XST) CS(35);
                if (step == ST_O) z = landed(el, q + 32, D_ / 2, pt.zero); else if (el) bulk_wait_fence();
                if (el) flag_set(fl + 1, ep * 8 + step + z);
                if (step == XST) CS(36);
            };
            auto free2 = [&]() { if (el) { mbar_arrive(BAR_SREADY(sb, w * 2)); mbar_arrive(BAR_SREADY(sb, w * 2 + 1)); } };
            if (el) { prefetch_map(&mp.h1s); prefetch_map(&mp.o); prefetch_map(&mp.h2s); prefetch_map(&mp.hb); prefetch_map(&mp.out); prefetch_map(&mp.wo); }
            if (el) { flag_set(fl, ep * 8); flag_set(fl + 1, ep * 8); }
            send2(&mp.h1s, pt.h1, ST_H1);
            if (w == 0) TL(47);
            free2();
            fetch_halo(g_halo + ((m - 1) * 8 + j) * 512 + w * 256 + lane, m == 0, sb, 2 * w, lane);
            send2(&mp.o, pt.o, ST_O);
            if (w == 0) TL(40); else TL(38);
            free2();
            send2(&mp.h2s, pt.o, ST_H2);
            if (el) { prefetch_map(&mp.hb); prefetch_map(&mp.hb3); }
            if (w == 0) TL(37);
            free2();
#pragma unroll 1
            for (int p = 0; p < 3; ++p) {
                const int col = hcol(p, j);
                mbar_wait(BAR_SFULL(sb, w * 2), par & 1);
                pause(w ? HD1 : HD0); store(&mp.hb, col);
                pause(HP); store(&mp.hb, col + 64);
                if (p == 0) {
                    pause(HP);
                    if (el) { tma_store3(&mp.hb3, 0, j, row0, sb + (w ? P3_SLOT1 : P3_SLOT0) * SLOT + 24576); bulk_commit(); }
                }
                if (el) bulk_wait_read();
                free2();
                if (el) { bulk_wait_fence(); flag_set(fl, ep * 8 + ST_H + p); flag_set(fl + 1, ep * 8 + ST_H + p); }
            }
            cluster_arrive_early = true;
            cluster_arrive();
            store(&mp.out, j * 128, true); store(&mp.out, j * 128 + 64, true);
            if (el) bulk_wait_read();
        }
        __syncwarp();
    }
    if (aux || (wg == 2 && !cluster_arrive_early)) cluster_arrive();
    cluster_wait();
    CS(32);
    if (KDEBUG == 5) __syncthreads();
    if (tid == 0) {
        TL(15);
        flag_add(pt.mail->flags + FL_DONE);
    }
}

typedef CUresult (*EncodeFn)(CUtensorMap*, CUtensorMapDataType, cuuint32_t, void*, const cuuint64_t*, const cuuint64_t*, const cuuint32_t*,
                             const cuuint32_t*, CUtensorMapInterleave, CUtensorMapSwizzle, CUtensorMapL2promotion, CUtensorMapFloatOOBfill);

void make_map(EncodeFn fn, CUtensorMap* m, const void* ptr, uint64_t rows, uint64_t cols, uint32_t brows, uint32_t bcols) {
    cuuint64_t dims[2] = {cols, rows}, strides[1] = {cols * 2};
    cuuint32_t box[2] = {bcols, brows}, es[2] = {1, 1};
    fn(m, CU_TENSOR_MAP_DATA_TYPE_BFLOAT16, 2, (void*)ptr, dims, strides, box, es, CU_TENSOR_MAP_INTERLEAVE_NONE,
       bcols == 64 ? CU_TENSOR_MAP_SWIZZLE_128B : bcols == 32 ? CU_TENSOR_MAP_SWIZZLE_64B : CU_TENSOR_MAP_SWIZZLE_NONE, CU_TENSOR_MAP_L2_PROMOTION_L2_256B, CU_TENSOR_MAP_FLOAT_OOB_FILL_NONE);
}

void make_map3(EncodeFn fn, CUtensorMap* m, const void* ptr) {
    cuuint64_t dims[3] = {D_, S_ / 2, 2}, strides[2] = {4 * D_, 2 * D_};
    cuuint32_t box[3] = {64, 32, 2}, es[3] = {1, 1, 1};
    fn(m, CU_TENSOR_MAP_DATA_TYPE_BFLOAT16, 3, (void*)ptr, dims, strides, box, es, CU_TENSOR_MAP_INTERLEAVE_NONE,
       CU_TENSOR_MAP_SWIZZLE_128B, CU_TENSOR_MAP_L2_PROMOTION_L2_256B, CU_TENSOR_MAP_FLOAT_OOB_FILL_NONE);
}

void make_map48(EncodeFn fn, CUtensorMap* m, const void* ptr, uint64_t rows, uint32_t brows) {
    cuuint64_t dims[3] = {48, 8, rows}, strides[2] = {96, 2 * F_};
    cuuint32_t box[3] = {64, 1, brows}, es[3] = {1, 1, 1};
    fn(m, CU_TENSOR_MAP_DATA_TYPE_BFLOAT16, 3, (void*)ptr, dims, strides, box, es, CU_TENSOR_MAP_INTERLEAVE_NONE,
       CU_TENSOR_MAP_SWIZZLE_128B, CU_TENSOR_MAP_L2_PROMOTION_L2_256B, CU_TENSOR_MAP_FLOAT_OOB_FILL_NONE);
}

}

extern "C" void kernel_launch(void* const* d_in, const int* in_sizes, int n_in, void* d_out, int out_size) {
    (void)in_sizes; (void)n_in; (void)out_size;
    void* fnp = nullptr;
    cudaDriverEntryPointQueryResult qr;
    cudaGetDriverEntryPoint("cuTensorMapEncodeTiled", &fnp, cudaEnableDefault, &qr);
    EncodeFn fn = (EncodeFn)fnp;
    void *h1, *o, *h2, *hb, *mail;
    cudaGetSymbolAddress(&h1, g_h1);
    cudaGetSymbolAddress(&mail, g_mail);
    cudaGetSymbolAddress(&o, g_o);
    cudaGetSymbolAddress(&hb, g_hb);
    h2 = o;
    Maps mp;
    make_map(fn, &mp.h1h, h1, S_, D_, 64, 32);
    make_map(fn, &mp.h2h, h2, S_, D_, 64, 32);
    make_map(fn, &mp.h1s, h1, S_, D_, 64, 64);
    make_map(fn, &mp.o, o, S_, D_, 64, 64);
    make_map(fn, &mp.h2l, h2, S_, D_, 128, 32);
    make_map(fn, &mp.h2s, h2, S_, D_, 64, 64);
    make_map(fn, &mp.hb, hb, S_, F_, 64, 64);
    make_map(fn, &mp.wqkv, d_in[1], D_, 3 * D_, 32, 64);
    make_map(fn, &mp.wo, d_in[2], D_, D_, 64, 64);
    make_map(fn, &mp.wg, d_in[4], D_, F_, 32, 64);
    make_map(fn, &mp.wu, d_in[5], D_, F_, 32, 64);
    make_map(fn, &mp.wd, d_in[6], F_, D_, 64, 64);
    make_map(fn, &mp.wmod, d_in[8], D_, 6 * D_, 64, 64);
    make_map(fn, &mp.wm8, d_in[8], D_ / 8, 8 * 6 * D_, 128, 16);
    make_map3(fn, &mp.x, d_in[0]);
    make_map3(fn, &mp.out, d_out);
    make_map48(fn, &mp.wg3, d_in[4], D_, 32);
    make_map48(fn, &mp.wu3, d_in[5], D_, 32);
    make_map48(fn, &mp.hb3, hb, S_, 64);
    cudaFuncSetAttribute(fused_block_kernel, cudaFuncAttributeMaxDynamicSharedMemorySize, SMEM_BYTES);
    cudaLaunchConfig_t cfg = {};
    cfg.gridDim = dim3(NCTA); cfg.blockDim = dim3(384); cfg.dynamicSmemBytes = SMEM_BYTES; cfg.stream = cudaStreamPerThread;
    cudaLaunchAttribute at[1];
    at[0].id = cudaLaunchAttributeClusterDimension; at[0].val.clusterDim.x = 2; at[0].val.clusterDim.y = 1; at[0].val.clusterDim.z = 1;
    cfg.attrs = at; cfg.numAttrs = 1;
    const Ptrs pt{(const __nv_bfloat16*)d_in[7], (Mail*)mail, (const uint32_t*)h1, (const uint32_t*)o, 0};
    cudaLaunchKernelEx(&cfg, fused_block_kernel, pt, mp);
}
```

```cpp
#include <cuda_runtime.h>
#include <cuda_bf16.h>
#include <cuda.h>
#include <stdint.h>
#include <stddef.h>

#define LAG 4
#define LAGS 4
#define LAGW 3
#define LAGQ 4
#define MIDW 2
#define PFWO 12
#define PMASK 1
#define PWAIT 0
#define P1H 4000
#define AGW 6
#define CSW 0
#define LWAIT 2
#define BW0 0
#define BWEV EV_WIN
#define BW1 3
#define PDLY 500
#define HD1 5500
#define HD0 5500
#define HP 2200
#define LAGD 4
#define MIDD 44
#define XST ST_O
#define AG0 6
#define AG1 6
#define AG2 8
#define SKIPRB 0
#define OFGO 0
#define PFG 20
#define PFN 12
#define PFO 0
#define MULTI 1
#define LATET 0
#define KDEBUG 0

namespace {

constexpr int S_ = 2048, D_ = 1024, F_ = 3584;
constexpr int NCTA = 132;
constexpr int NSLOT = 6;
constexpr uint32_t SLOT = 32768;
constexpr uint32_t OFF_STG = NSLOT * SLOT;
constexpr uint32_t OFF_BAR = OFF_STG + 32768;
constexpr uint32_t OFF_PAR = OFF_BAR + 512;
constexpr uint32_t OFF_TAB = OFF_PAR + 768;
constexpr uint32_t OFF_TL = OFF_PAR + 2048;
constexpr uint32_t SMEM_BYTES = OFF_TL + (KDEBUG ? 512 : 0);
constexpr uint32_t P3_SLOT1 = (32 + 16 + 32) % NSLOT, P3_SLOT0 = (P3_SLOT1 + 1) % NSLOT;

constexpr int ST_H1 = 1, ST_O = 2, ST_H2 = 3, ST_H = 4, FL_DONE = 0, FL_LN2 = 1, FL_AUX = 32, FL_PROG = 64;

struct Maps {
    CUtensorMap h1h, h1s, o, h2h, h2l, h2s, hb, wqkv, wo, wg, wu, wd, wmod, wm8, x, out, wg3, wu3, hb3;
};

struct Mail {
    uint32_t flags[16 * 32 + 64];
    uint2 mod[6 * D_ / 2];
    uint4 mod1[8 * 512];
    uint4 st1[128 * 512];
    uint32_t par2[D_];
    uint4 halo[128 * 512];
};
struct Ptrs { const __nv_bfloat16* c; Mail* mail; const uint32_t *h1, *o; uint32_t zero; };

__device__ __align__(128) Mail g_mail;
__device__ __align__(128) __nv_bfloat16 g_h1[S_ * D_];
__device__ __align__(128) __nv_bfloat16 g_o[S_ * D_];
__device__ __align__(128) __nv_bfloat16 g_hb[S_ * F_];
#define TL(i) do {} while (0)
#define TC(i) do {} while (0)
#define TS(g, which) do {} while (0)
#define CS(i) do {} while (0)

__device__ __forceinline__ uint32_t smem_u32(const void* p) { return (uint32_t)__cvta_generic_to_shared(p); }
__device__ __forceinline__ void mbar_init(uint32_t bar, uint32_t cnt) { asm volatile("mbarrier.init.shared::cta.b64 [%0], %1;" :: "r"(bar), "r"(cnt) : "memory"); }
__device__ __forceinline__ void mbar_expect_tx(uint32_t bar, uint32_t bytes) { asm volatile("mbarrier.arrive.expect_tx.shared::cta.b64 _, [%0], %1;" :: "r"(bar), "r"(bytes) : "memory"); }
__device__ __forceinline__ void mbar_arrive(uint32_t bar) { asm volatile("mbarrier.arrive.shared::cta.b64 _, [%0];" :: "r"(bar) : "memory"); }
__device__ __forceinline__ void mbar_arrive_cta(uint32_t bar, uint32_t cta) {
    asm volatile("{\n.reg .b32 r;\nmapa.shared::cluster.u32 r, %0, %1;\nmbarrier.arrive.shared::cluster.b64 _, [r];\n}" :: "r"(bar), "r"(cta) : "memory");
}
__device__ __forceinline__ void mbar_wait(uint32_t bar, uint32_t parity) {
    asm volatile("{\n.reg .pred p;\n.reg .u32 n;\nmov.u32 n, 0;\n"
        "W_LOOP:\nmbarrier.try_wait.parity.shared::cta.b64 p, [%0], %1;\n@p bra W_DONE;\n"
        "add.u32 n, n, 1;\nsetp.lt.u32 p, n, 0x400000;\n@p bra W_LOOP;\ntrap;\nW_DONE:\n}" :: "r"(bar), "r"(parity) : "memory");
}
__device__ __forceinline__ void mbar_wait2(uint32_t b0, uint32_t b1, uint32_t parity) {
    asm volatile("{\n.reg .pred p, q;\n.reg .u32 n;\nmov.u32 n, 0;\n"
        "W_LOOP:\nmbarrier.try_wait.parity.shared::cta.b64 p, [%0], %2;\nmbarrier.try_wait.parity.shared::cta.b64 q, [%1], %2;\nand.pred p, p, q;\n@p bra W_DONE;\n"
        "add.u32 n, n, 1;\nsetp.lt.u32 p, n, 0x400000;\n@p bra W_LOOP;\ntrap;\nW_DONE:\n}" :: "r"(b0), "r"(b1), "r"(parity) : "memory");
}
__device__ __forceinline__ bool mbar_test(uint32_t bar, uint32_t parity) {
    uint32_t r; asm volatile("{\n.reg .pred p;\nmbarrier.test_wait.parity.shared::cta.b64 p, [%1], %2;\nselp.u32 %0, 1, 0, p;\n}" : "=r"(r) : "r"(bar), "r"(parity) : "memory"); return r;
}
__device__ __forceinline__ bool mbar_test2(uint32_t b0, uint32_t b1, uint32_t parity) {
    uint32_t r;
    asm volatile("{\n.reg .pred p, q;\nmbarrier.test_wait.parity.shared::cta.b64 p, [%1], %3;\nmbarrier.test_wait.parity.shared::cta.b64 q, [%2], %3;\n"
        "and.pred p, p, q;\nselp.u32 %0, 1, 0, p;\n}" : "=r"(r) : "r"(b0), "r"(b1), "r"(parity) : "memory");
    return r;
}
__device__ __forceinline__ void tma_load3(uint32_t dst, const CUtensorMap* m, int c0, int c1, uint32_t bar) {
    asm volatile("cp.async.bulk.tensor.3d.shared::cluster.global.mbarrier::complete_tx::bytes [%0], [%1, {%3, %4, %5}], [%2];"
        :: "r"(dst), "l"(m), "r"(bar), "r"(c0), "r"(c1), "r"(0) : "memory");
}
__device__ __forceinline__ void tma_store3(const CUtensorMap* m, int c0, int c1, int c2, uint32_t src) {
    asm volatile("cp.async.bulk.tensor.3d.global.shared::cta.bulk_group [%0, {%2, %3, %4}], [%1];" :: "l"(m), "r"(src), "r"(c0), "r"(c1), "r"(c2) : "memory");
}
__device__ __forceinline__ void tma_load3_mc(uint32_t dst, const CUtensorMap* m, int c1, int c2, uint32_t bar) {
    asm volatile("cp.async.bulk.tensor.3d.shared::cluster.global.mbarrier::complete_tx::bytes.multicast::cluster.L2::cache_hint [%0], [%1, {%3, %4, %5}], [%2], %6, %7;"
        :: "r"(dst), "l"(m), "r"(bar), "r"(0), "r"(c1), "r"(c2), "h"((uint16_t)3), "l"(0x12F0000000000000ull) : "memory");
}
__device__ __forceinline__ void tma_load(uint32_t dst, const CUtensorMap* m, int c0, int c1, uint32_t bar) {
    asm volatile("cp.async.bulk.tensor.2d.shared::cluster.global.mbarrier::complete_tx::bytes [%0], [%1, {%3, %4}], [%2];"
        :: "r"(dst), "l"(m), "r"(bar), "r"(c0), "r"(c1) : "memory");
}
__device__ __forceinline__ void tma_load_mc(uint32_t dst, const CUtensorMap* m, int c0, int c1, uint32_t bar) {
    asm volatile("cp.async.bulk.tensor.2d.shared::cluster.global.mbarrier::complete_tx::bytes.multicast::cluster.L2::cache_hint [%0], [%1, {%3, %4}], [%2], %5, %6;"
        :: "r"(dst), "l"(m), "r"(bar), "r"(c0), "r"(c1), "h"((uint16_t)3), "l"(0x12F0000000000000ull) : "memory");
}
__device__ __forceinline__ void tma_prefetch(const CUtensorMap* m, int c0, int c1) {
    asm volatile("cp.async.bulk.prefetch.tensor.2d.L2.global [%0, {%1, %2}];" :: "l"(m), "r"(c0), "r"(c1) : "memory");
}
__device__ __forceinline__ void tma_store(const CUtensorMap* m, int c0, int c1, uint32_t src) {
    asm volatile("cp.async.bulk.tensor.2d.global.shared::cta.bulk_group [%0, {%2, %3}], [%1];" :: "l"(m), "r"(src), "r"(c0), "r"(c1) : "memory");
}
__device__ __forceinline__ void bulk_commit() { asm volatile("cp.async.bulk.commit_group;" ::: "memory"); }
__device__ __forceinline__ void bulk_wait_read() { asm volatile("cp.async.bulk.wait_group.read 0;" ::: "memory"); }
__device__ __forceinline__ void fence_async_smem() { asm volatile("fence.proxy.async.shared::cta;" ::: "memory"); }
__device__ __forceinline__ void prefetch_map(const CUtensorMap* m) { asm volatile("prefetch.tensormap [%0];" :: "l"(m) : "memory"); }
__device__ __forceinline__ void wg_fence() { asm volatile("wgmma.fence.sync.aligned;" ::: "memory"); }
__device__ __forceinline__ void wg_commit() { asm volatile("wgmma.commit_group.sync.aligned;" ::: "memory"); }
template <int N> __device__ __forceinline__ void wg_wait() { asm volatile("wgmma.wait_group.sync.aligned %0;" :: "n"(N) : "memory"); }
__device__ __forceinline__ void bar_sync(int id, int n) { asm volatile("bar.sync %0, %1;" :: "r"(id), "r"(n) : "memory"); }
__device__ __forceinline__ void bar_arrive(int id, int n) { asm volatile("bar.arrive %0, %1;" :: "r"(id), "r"(n) : "memory"); }
__device__ __forceinline__ void flag_add(uint32_t* f) { asm volatile("red.relaxed.gpu.global.add.u32 [%0], 1;" :: "l"(f) : "memory"); }
__device__ __forceinline__ void flag_set(uint32_t* f, uint32_t v) { asm volatile("red.relaxed.gpu.global.max.u32 [%0], %1;" :: "l"(f), "r"(v) : "memory"); }
__device__ __forceinline__ uint32_t flag_get(const uint32_t* f) { uint32_t v; asm volatile("ld.relaxed.gpu.global.u32 %0, [%1];" : "=r"(v) : "l"(f) : "memory"); return v; }
__device__ __forceinline__ void bulk_wait_fence() { asm volatile("cp.async.bulk.wait_group 0;\nfence.proxy.async.global;\nfence.acq_rel.gpu;" ::: "memory"); }
__device__ __forceinline__ uint32_t landed(bool el, const uint32_t* p, uint32_t pitch, uint32_t zero, bool skip = false) {
    if (el) asm volatile("cp.async.bulk.wait_group 0;" ::: "memory");
    if (skip) return 0;
    __syncwarp();
    const uint32_t a = flag_get(p), b = flag_get(p + 32 * pitch);
    return __reduce_or_sync(0xffffffffu, (a | b) & zero);
}
__device__ __forceinline__ uint32_t d16(uint32_t addr) { return (addr & 0x3FFFF) >> 4; }
__device__ __forceinline__ uint64_t mk_desc(uint32_t a16, uint32_t off, uint32_t lbo, uint32_t sbo, uint32_t swz) {
    const uint32_t lo = a16 + (off >> 4) + ((lbo >> 4) << 16), hi = (sbo >> 4) | (swz << 30);
    return ((uint64_t)hi << 32) | lo;
}
__device__ __forceinline__ uint32_t pack2(float lo, float hi) {
    uint32_t r; asm("cvt.rn.bf16x2.f32 %0, %1, %2;" : "=r"(r) : "f"(hi), "f"(lo)); return r;
}
__device__ __forceinline__ uint32_t hfma2_bf16(uint32_t a, uint32_t b, uint32_t c) {
    uint32_t r; asm("fma.rn.bf16x2 %0, %1, %2, %3;" : "=r"(r) : "r"(a), "r"(b), "r"(c)); return r;
}
__device__ __forceinline__ float bf_lo(uint32_t v) { return __uint_as_float(v << 16); }
__device__ __forceinline__ float bf_hi(uint32_t v) { return __uint_as_float(v & 0xFFFF0000u); }
__device__ __forceinline__ void unpack2(uint32_t v, float& lo, float& hi) {
    asm volatile("shl.b32 %0, %2, 16;\nand.b32 %1, %2, 0xffff0000;" : "=f"(lo), "=f"(hi) : "r"(v));
}
__device__ __forceinline__ float bf_round(float x) { return __bfloat162float(__float2bfloat16_rn(x)); }
__device__ __forceinline__ void stsm4(uint32_t addr, uint32_t r0, uint32_t r1, uint32_t r2, uint32_t r3) {
    asm volatile("stmatrix.sync.aligned.m8n8.x4.shared.b16 [%0], {%1, %2, %3, %4};" :: "r"(addr), "r"(r0), "r"(r1), "r"(r2), "r"(r3) : "memory");
}
__device__ __forceinline__ void stsm4t(uint32_t addr, uint32_t r0, uint32_t r1, uint32_t r2, uint32_t r3) {
    asm volatile("stmatrix.sync.aligned.m8n8.x4.trans.shared.b16 [%0], {%1, %2, %3, %4};" :: "r"(addr), "r"(r0), "r"(r1), "r"(r2), "r"(r3) : "memory");
}
__device__ __forceinline__ uint32_t movm(uint32_t a) { uint32_t d; asm volatile("movmatrix.sync.aligned.m8n8.trans.b16 %0, %1;" : "=r"(d) : "r"(a)); return d; }
__device__ __forceinline__ void ldsm4(uint32_t addr, uint32_t& r0, uint32_t& r1, uint32_t& r2, uint32_t& r3) {
    asm volatile("ldmatrix.sync.aligned.m8n8.x4.shared.b16 {%0, %1, %2, %3}, [%4];" : "=r"(r0), "=r"(r1), "=r"(r2), "=r"(r3) : "r"(addr) : "memory");
}
__device__ __forceinline__ void ldsm4t(uint32_t addr, uint32_t& r0, uint32_t& r1, uint32_t& r2, uint32_t& r3) {
    asm volatile("ldmatrix.sync.aligned.m8n8.x4.trans.shared.b16 {%0, %1, %2, %3}, [%4];" : "=r"(r0), "=r"(r1), "=r"(r2), "=r"(r3) : "r"(addr) : "memory");
}
__device__ __forceinline__ void mma16816(float (&c)[4], uint32_t a0, uint32_t a1, uint32_t a2, uint32_t a3, uint32_t b0, uint32_t b1) {
    asm("mma.sync.aligned.m16n8k16.row.col.f32.bf16.bf16.f32 {%0, %1, %2, %3}, {%4, %5, %6, %7}, {%8, %9}, {%0, %1, %2, %3};"
        : "+f"(c[0]), "+f"(c[1]), "+f"(c[2]), "+f"(c[3]) : "r"(a0), "r"(a1), "r"(a2), "r"(a3), "r"(b0), "r"(b1));
}
__device__ __forceinline__ float rcp(float x) { float r; asm("rcp.approx.ftz.f32 %0, %1;" : "=f"(r) : "f"(x)); return r; }
__device__ __forceinline__ float ex2(float x) { float r; asm("ex2.approx.ftz.f32 %0, %1;" : "=f"(r) : "f"(x)); return r; }
__device__ __forceinline__ float tanh_(float x) { float t; asm("tanh.approx.f32 %0, %1;" : "=f"(t) : "f"(x)); return t; }
__device__ __forceinline__ void block_end(uint32_t opaque) { asm volatile("{\n.reg .pred p;\nsetp.eq.u32 p, %0, 0xffffffff;\n@p trap;\n}" :: "r"(opaque)); }
__device__ __forceinline__ float silu_(float x) { return __fdividef(x, 1.f + __expf(-x)); }
__device__ __forceinline__ void st_pkt(void* p, uint32_t a, uint32_t b) {
    asm volatile("{\n.reg .b64 t;\nmov.b64 t, {%1, %2};\nst.relaxed.gpu.global.b64 [%0], t;\n}" :: "l"(p), "r"(a), "r"(b) : "memory");
}
__device__ __forceinline__ uint4 ld_pkt2(const void* p) {
    uint4 v; asm volatile("{\n.reg .b64 t, u;\nld.relaxed.gpu.global.v2.b64 {t, u}, [%4];\nmov.b64 {%0, %1}, t;\nmov.b64 {%2, %3}, u;\n}"
        : "=r"(v.x), "=r"(v.y), "=r"(v.z), "=r"(v.w) : "l"(p) : "memory"); return v;
}
__device__ __forceinline__ void st_pkt16(void* p, uint32_t a, uint32_t b, uint32_t c, uint32_t d) {
    asm volatile("{\n.reg .b64 t, u;\n.reg .b128 w;\nmov.b64 t, {%1, %2};\nmov.b64 u, {%3, %4};\nmov.b128 w, {t, u};\nst.relaxed.gpu.global.b128 [%0], w;\n}"
        :: "l"(p), "r"(a), "r"(b), "r"(c), "r"(d) : "memory");
}
__device__ __forceinline__ uint4 ld_pkt16(const void* p) {
    uint4 v; asm volatile("{\n.reg .b64 t, u;\n.reg .b128 w;\nld.relaxed.gpu.global.b128 w, [%4];\nmov.b128 {t, u}, w;\nmov.b64 {%0, %1}, t;\nmov.b64 {%2, %3}, u;\n}"
        : "=r"(v.x), "=r"(v.y), "=r"(v.z), "=r"(v.w) : "l"(p) : "memory"); return v;
}
#define SPIN_GUARD(n) do { if (++(n) > (1u << 22)) asm volatile("trap;"); } while (0)
__device__ __forceinline__ uint4 lds128(uint32_t a) { uint4 v; asm volatile("ld.shared.v4.u32 {%0, %1, %2, %3}, [%4];" : "=r"(v.x), "=r"(v.y), "=r"(v.z), "=r"(v.w) : "r"(a) : "memory"); return v; }
__device__ __forceinline__ void sts128(uint32_t a, uint32_t x, uint32_t y, uint32_t z, uint32_t w) { asm volatile("st.shared.v4.u32 [%0], {%1, %2, %3, %4};" :: "r"(a), "r"(x), "r"(y), "r"(z), "r"(w) : "memory"); }
__device__ __forceinline__ uint32_t lds32(uint32_t a) { uint32_t v; asm volatile("ld.shared.u32 %0, [%1];" : "=r"(v) : "r"(a) : "memory"); return v; }
__device__ __forceinline__ void sts32(uint32_t a, uint32_t v) { asm volatile("st.shared.u32 [%0], %1;" :: "r"(a), "r"(v) : "memory"); }
__device__ __forceinline__ bool elect_one() {
    uint32_t p; asm volatile("{\n.reg .pred q;\nelect.sync _|q, 0xffffffff;\nselp.u32 %0, 1, 0, q;\n}" : "=r"(p)); return p;
}
__device__ __forceinline__ void pause(uint32_t cycles) {
    uint32_t t0, t; asm volatile("mov.u32 %0, %%clock;" : "=r"(t0));
    do { __nanosleep(64); asm volatile("mov.u32 %0, %%clock;" : "=r"(t)); } while (t - t0 < cycles);
}
__device__ __forceinline__ void spin(uint32_t cycles) {
    uint32_t t0, t; asm volatile("mov.u32 %0, %%clock;" : "=r"(t0));
    do { asm volatile("mov.u32 %0, %%clock;" : "=r"(t)); } while (t - t0 < cycles);
}
__device__ __forceinline__ void cluster_arrive() { asm volatile("barrier.cluster.arrive.relaxed.aligned;" ::: "memory"); }
__device__ __forceinline__ void cluster_wait() { asm volatile("barrier.cluster.wait.aligned;" ::: "memory"); }

__device__ __forceinline__ void wgmma_n128_z(float (&d)[64], uint64_t da, uint64_t db) {
    asm volatile("{\n.reg .pred p;\nsetp.ne.b32 p, 0, 0;\n"
        "wgmma.mma_async.sync.aligned.m64n128k16.f32.bf16.bf16 {"
        "%0, %1, %2, %3, %4, %5, %6, %7, %8, %9, %10, %11, %12, %13, %14, %15, "
        "%16, %17, %18, %19, %20, %21, %22, %23, %24, %25, %26, %27, %28, %29, %30, %31, "
        "%32, %33, %34, %35, %36, %37, %38, %39, %40, %41, %42, %43, %44, %45, %46, %47, "
        "%48, %49, %50, %51, %52, %53, %54, %55, %56, %57, %58, %59, %60, %61, %62, %63"
        "}, %64, %65, p, 1, 1, 0, 1;\n}\n"
        : "=f"(d[0]), "=f"(d[1]), "=f"(d[2]), "=f"(d[3]), "=f"(d[4]), "=f"(d[5]), "=f"(d[6]), "=f"(d[7]),
          "=f"(d[8]), "=f"(d[9]), "=f"(d[10]), "=f"(d[11]), "=f"(d[12]), "=f"(d[13]), "=f"(d[14]), "=f"(d[15]),
          "=f"(d[16]), "=f"(d[17]), "=f"(d[18]), "=f"(d[19]), "=f"(d[20]), "=f"(d[21]), "=f"(d[22]), "=f"(d[23]),
          "=f"(d[24]), "=f"(d[25]), "=f"(d[26]), "=f"(d[27]), "=f"(d[28]), "=f"(d[29]), "=f"(d[30]), "=f"(d[31]),
          "=f"(d[32]), "=f"(d[33]), "=f"(d[34]), "=f"(d[35]), "=f"(d[36]), "=f"(d[37]), "=f"(d[38]), "=f"(d[39]),
          "=f"(d[40]), "=f"(d[41]), "=f"(d[42]), "=f"(d[43]), "=f"(d[44]), "=f"(d[45]), "=f"(d[46]), "=f"(d[47]),
          "=f"(d[48]), "=f"(d[49]), "=f"(d[50]), "=f"(d[51]), "=f"(d[52]), "=f"(d[53]), "=f"(d[54]), "=f"(d[55]),
          "=f"(d[56]), "=f"(d[57]), "=f"(d[58]), "=f"(d[59]), "=f"(d[60]), "=f"(d[61]), "=f"(d[62]), "=f"(d[63])
        : "l"(da), "l"(db));
}
__device__ __forceinline__ void wgmma_n128(float (&d)[64], uint64_t da, uint64_t db) {
    asm volatile("{\n.reg .pred p;\nsetp.eq.b32 p, 0, 0;\n"
        "wgmma.mma_async.sync.aligned.m64n128k16.f32.bf16.bf16 {"
        "%0, %1, %2, %3, %4, %5, %6, %7, %8, %9, %10, %11, %12, %13, %14, %15, "
        "%16, %17, %18, %19, %20, %21, %22, %23, %24, %25, %26, %27, %28, %29, %30, %31, "
        "%32, %33, %34, %35, %36, %37, %38, %39, %40, %41, %42, %43, %44, %45, %46, %47, "
        "%48, %49, %50, %51, %52, %53, %54, %55, %56, %57, %58, %59, %60, %61, %62, %63"
        "}, %64, %65, p, 1, 1, 0, 1;\n}\n"
        : "+f"(d[0]), "+f"(d[1]), "+f"(d[2]), "+f"(d[3]), "+f"(d[4]), "+f"(d[5]), "+f"(d[6]), "+f"(d[7]),
          "+f"(d[8]), "+f"(d[9]), "+f"(d[10]), "+f"(d[11]), "+f"(d[12]), "+f"(d[13]), "+f"(d[14]), "+f"(d[15]),
          "+f"(d[16]), "+f"(d[17]), "+f"(d[18]), "+f"(d[19]), "+f"(d[20]), "+f"(d[21]), "+f"(d[22]), "+f"(d[23]),
          "+f"(d[24]), "+f"(d[25]), "+f"(d[26]), "+f"(d[27]), "+f"(d[28]), "+f"(d[29]), "+f"(d[30]), "+f"(d[31]),
          "+f"(d[32]), "+f"(d[33]), "+f"(d[34]), "+f"(d[35]), "+f"(d[36]), "+f"(d[37]), "+f"(d[38]), "+f"(d[39]),
          "+f"(d[40]), "+f"(d[41]), "+f"(d[42]), "+f"(d[43]), "+f"(d[44]), "+f"(d[45]), "+f"(d[46]), "+f"(d[47]),
          "+f"(d[48]), "+f"(d[49]), "+f"(d[50]), "+f"(d[51]), "+f"(d[52]), "+f"(d[53]), "+f"(d[54]), "+f"(d[55]),
          "+f"(d[56]), "+f"(d[57]), "+f"(d[58]), "+f"(d[59]), "+f"(d[60]), "+f"(d[61]), "+f"(d[62]), "+f"(d[63])
        : "l"(da), "l"(db));
}
__device__ __forceinline__ void wgmma_n176_z(float (&d)[88], uint64_t da, uint64_t db) {
    asm volatile("{\n.reg .pred p;\nsetp.ne.b32 p, 0, 0;\n"
        "wgmma.mma_async.sync.aligned.m64n176k16.f32.bf16.bf16 {"
        "%0, %1, %2, %3, %4, %5, %6, %7, %8, %9, %10, %11, %12, %13, %14, %15, "
        "%16, %17, %18, %19, %20, %21, %22, %23, %24, %25, %26, %27, %28, %29, %30, %31, "
        "%32, %33, %34, %35, %36, %37, %38, %39, %40, %41, %42, %43, %44, %45, %46, %47, "
        "%48, %49, %50, %51, %52, %53, %54, %55, %56, %57, %58, %59, %60, %61, %62, %63, "
        "%64, %65, %66, %67, %68, %69, %70, %71, %72, %73, %74, %75, %76, %77, %78, %79, "
        "%80, %81, %82, %83, %84, %85, %86, %87"
        "}, %88, %89, p, 1, 1, 0, 1;\n}\n"
        : "=f"(d[0]), "=f"(d[1]), "=f"(d[2]), "=f"(d[3]), "=f"(d[4]), "=f"(d[5]), "=f"(d[6]), "=f"(d[7]),
          "=f"(d[8]), "=f"(d[9]), "=f"(d[10]), "=f"(d[11]), "=f"(d[12]), "=f"(d[13]), "=f"(d[14]), "=f"(d[15]),
          "=f"(d[16]), "=f"(d[17]), "=f"(d[18]), "=f"(d[19]), "=f"(d[20]), "=f"(d[21]), "=f"(d[22]), "=f"(d[23]),
          "=f"(d[24]), "=f"(d[25]), "=f"(d[26]), "=f"(d[27]), "=f"(d[28]), "=f"(d[29]), "=f"(d[30]), "=f"(d[31]),
          "=f"(d[32]), "=f"(d[33]), "=f"(d[34]), "=f"(d[35]), "=f"(d[36]), "=f"(d[37]), "=f"(d[38]), "=f"(d[39]),
          "=f"(d[40]), "=f"(d[41]), "=f"(d[42]), "=f"(d[43]), "=f"(d[44]), "=f"(d[45]), "=f"(d[46]), "=f"(d[47]),
          "=f"(d[48]), "=f"(d[49]), "=f"(d[50]), "=f"(d[51]), "=f"(d[52]), "=f"(d[53]), "=f"(d[54]), "=f"(d[55]),
          "=f"(d[56]), "=f"(d[57]), "=f"(d[58]), "=f"(d[59]), "=f"(d[60]), "=f"(d[61]), "=f"(d[62]), "=f"(d[63]),
          "=f"(d[64]), "=f"(d[65]), "=f"(d[66]), "=f"(d[67]), "=f"(d[68]), "=f"(d[69]), "=f"(d[70]), "=f"(d[71]),
          "=f"(d[72]), "=f"(d[73]), "=f"(d[74]), "=f"(d[75]), "=f"(d[76]), "=f"(d[77]), "=f"(d[78]), "=f"(d[79]),
          "=f"(d[80]), "=f"(d[81]), "=f"(d[82]), "=f"(d[83]), "=f"(d[84]), "=f"(d[85]), "=f"(d[86]), "=f"(d[87])
        : "l"(da), "l"(db));
}
__device__ __forceinline__ void wgmma_n176(float (&d)[88], uint64_t da, uint64_t db) {
    asm volatile("{\n.reg .pred p;\nsetp.eq.b32 p, 0, 0;\n"
        "wgmma.mma_async.sync.aligned.m64n176k16.f32.bf16.bf16 {"
        "%0, %1, %2, %3, %4, %5, %6, %7, %8, %9, %10, %11, %12, %13, %14, %15, "
        "%16, %17, %18, %19, %20, %21, %22, %23, %24, %25, %26, %27, %28, %29, %30, %31, "
        "%32, %33, %34, %35, %36, %37, %38, %39, %40, %41, %42, %43, %44, %45, %46, %47, "
        "%48, %49, %50, %51, %52, %53, %54, %55, %56, %57, %58, %59, %60, %61, %62, %63, "
        "%64, %65, %66, %67, %68, %69, %70, %71, %72, %73, %74, %75, %76, %77, %78, %79, "
        "%80, %81, %82, %83, %84, %85, %86, %87"
        "}, %88, %89, p, 1, 1, 0, 1;\n}\n"
        : "+f"(d[0]), "+f"(d[1]), "+f"(d[2]), "+f"(d[3]), "+f"(d[4]), "+f"(d[5]), "+f"(d[6]), "+f"(d[7]),
          "+f"(d[8]), "+f"(d[9]), "+f"(d[10]), "+f"(d[11]), "+f"(d[12]), "+f"(d[13]), "+f"(d[14]), "+f"(d[15]),
          "+f"(d[16]), "+f"(d[17]), "+f"(d[18]), "+f"(d[19]), "+f"(d[20]), "+f"(d[21]), "+f"(d[22]), "+f"(d[23]),
          "+f"(d[24]), "+f"(d[25]), "+f"(d[26]), "+f"(d[27]), "+f"(d[28]), "+f"(d[29]), "+f"(d[30]), "+f"(d[31]),
          "+f"(d[32]), "+f"(d[33]), "+f"(d[34]), "+f"(d[35]), "+f"(d[36]), "+f"(d[37]), "+f"(d[38]), "+f"(d[39]),
          "+f"(d[40]), "+f"(d[41]), "+f"(d[42]), "+f"(d[43]), "+f"(d[44]), "+f"(d[45]), "+f"(d[46]), "+f"(d[47]),
          "+f"(d[48]), "+f"(d[49]), "+f"(d[50]), "+f"(d[51]), "+f"(d[52]), "+f"(d[53]), "+f"(d[54]), "+f"(d[55]),
          "+f"(d[56]), "+f"(d[57]), "+f"(d[58]), "+f"(d[59]), "+f"(d[60]), "+f"(d[61]), "+f"(d[62]), "+f"(d[63]),
          "+f"(d[64]), "+f"(d[65]), "+f"(d[66]), "+f"(d[67]), "+f"(d[68]), "+f"(d[69]), "+f"(d[70]), "+f"(d[71]),
          "+f"(d[72]), "+f"(d[73]), "+f"(d[74]), "+f"(d[75]), "+f"(d[76]), "+f"(d[77]), "+f"(d[78]), "+f"(d[79]),
          "+f"(d[80]), "+f"(d[81]), "+f"(d[82]), "+f"(d[83]), "+f"(d[84]), "+f"(d[85]), "+f"(d[86]), "+f"(d[87])
        : "l"(da), "l"(db));
}
__device__ __forceinline__ void wgmma_n256_z(float (&d)[128], uint64_t da, uint64_t db) {
    asm volatile("{\n.reg .pred p;\nsetp.ne.b32 p, 0, 0;\n"
        "wgmma.mma_async.sync.aligned.m64n256k16.f32.bf16.bf16 {"
        "%0, %1, %2, %3, %4, %5, %6, %7, %8, %9, %10, %11, %12, %13, %14, %15, "
        "%16, %17, %18, %19, %20, %21, %22, %23, %24, %25, %26, %27, %28, %29, %30, %31, "
        "%32, %33, %34, %35, %36, %37, %38, %39, %40, %41, %42, %43, %44, %45, %46, %47, "
        "%48, %49, %50, %51, %52, %53, %54, %55, %56, %57, %58, %59, %60, %61, %62, %63, "
        "%64, %65, %66, %67, %68, %69, %70, %71, %72, %73, %74, %75, %76, %77, %78, %79, "
        "%80, %81, %82, %83, %84, %85, %86, %87, %88, %89, %90, %91, %92, %93, %94, %95, "
        "%96, %97, %98, %99, %100, %101, %102, %103, %104, %105, %106, %107, %108, %109, %110, %111, "
        "%112, %113, %114, %115, %116, %117, %118, %119, %120, %121, %122, %123, %124, %125, %126, %127"
        "}, %128, %129, p, 1, 1, 0, 1;\n}\n"
        : "=f"(d[0]), "=f"(d[1]), "=f"(d[2]), "=f"(d[3]), "=f"(d[4]), "=f"(d[5]), "=f"(d[6]), "=f"(d[7]),
          "=f"(d[8]), "=f"(d[9]), "=f"(d[10]), "=f"(d[11]), "=f"(d[12]), "=f"(d[13]), "=f"(d[14]), "=f"(d[15]),
          "=f"(d[16]), "=f"(d[17]), "=f"(d[18]), "=f"(d[19]), "=f"(d[20]), "=f"(d[21]), "=f"(d[22]), "=f"(d[23]),
          "=f"(d[24]), "=f"(d[25]), "=f"(d[26]), "=f"(d[27]), "=f"(d[28]), "=f"(d[29]), "=f"(d[30]), "=f"(d[31]),
          "=f"(d[32]), "=f"(d[33]), "=f"(d[34]), "=f"(d[35]), "=f"(d[36]), "=f"(d[37]), "=f"(d[38]), "=f"(d[39]),
          "=f"(d[40]), "=f"(d[41]), "=f"(d[42]), "=f"(d[43]), "=f"(d[44]), "=f"(d[45]), "=f"(d[46]), "=f"(d[47]),
          "=f"(d[48]), "=f"(d[49]), "=f"(d[50]), "=f"(d[51]), "=f"(d[52]), "=f"(d[53]), "=f"(d[54]), "=f"(d[55]),
          "=f"(d[56]), "=f"(d[57]), "=f"(d[58]), "=f"(d[59]), "=f"(d[60]), "=f"(d[61]), "=f"(d[62]), "=f"(d[63]),
          "=f"(d[64]), "=f"(d[65]), "=f"(d[66]), "=f"(d[67]), "=f"(d[68]), "=f"(d[69]), "=f"(d[70]), "=f"(d[71]),
          "=f"(d[72]), "=f"(d[73]), "=f"(d[74]), "=f"(d[75]), "=f"(d[76]), "=f"(d[77]), "=f"(d[78]), "=f"(d[79]),
          "=f"(d[80]), "=f"(d[81]), "=f"(d[82]), "=f"(d[83]), "=f"(d[84]), "=f"(d[85]), "=f"(d[86]), "=f"(d[87]),
          "=f"(d[88]), "=f"(d[89]), "=f"(d[90]), "=f"(d[91]), "=f"(d[92]), "=f"(d[93]), "=f"(d[94]), "=f"(d[95]),
          "=f"(d[96]), "=f"(d[97]), "=f"(d[98]), "=f"(d[99]), "=f"(d[100]), "=f"(d[101]), "=f"(d[102]), "=f"(d[103]),
          "=f"(d[104]), "=f"(d[105]), "=f"(d[106]), "=f"(d[107]), "=f"(d[108]), "=f"(d[109]), "=f"(d[110]), "=f"(d[111]),
          "=f"(d[112]), "=f"(d[113]), "=f"(d[114]), "=f"(d[115]), "=f"(d[116]), "=f"(d[117]), "=f"(d[118]), "=f"(d[119]),
          "=f"(d[120]), "=f"(d[121]), "=f"(d[122]), "=f"(d[123]), "=f"(d[124]), "=f"(d[125]), "=f"(d[126]), "=f"(d[127])
        : "l"(da), "l"(db));
}
__device__ __forceinline__ void wgmma_n256(float (&d)[128], uint64_t da, uint64_t db) {
    asm volatile("{\n.reg .pred p;\nsetp.eq.b32 p, 0, 0;\n"
        "wgmma.mma_async.sync.aligned.m64n256k16.f32.bf16.bf16 {"
        "%0, %1, %2, %3, %4, %5, %6, %7, %8, %9, %10, %11, %12, %13, %14, %15, "
        "%16, %17, %18, %19, %20, %21, %22, %23, %24, %25, %26, %27, %28, %29, %30, %31, "
        "%32, %33, %34, %35, %36, %37, %38, %39, %40, %41, %42, %43, %44, %45, %46, %47, "
        "%48, %49, %50, %51, %52, %53, %54, %55, %56, %57, %58, %59, %60, %61, %62, %63, "
        "%64, %65, %66, %67, %68, %69, %70, %71, %72, %73, %74, %75, %76, %77, %78, %79, "
        "%80, %81, %82, %83, %84, %85, %86, %87, %88, %89, %90, %91, %92, %93, %94, %95, "
        "%96, %97, %98, %99, %100, %101, %102, %103, %104, %105, %106, %107, %108, %109, %110, %111, "
        "%112, %113, %114, %115, %116, %117, %118, %119, %120, %121, %122, %123, %124, %125, %126, %127"
        "}, %128, %129, p, 1, 1, 0, 1;\n}\n"
        : "+f"(d[0]), "+f"(d[1]), "+f"(d[2]), "+f"(d[3]), "+f"(d[4]), "+f"(d[5]), "+f"(d[6]), "+f"(d[7]),
          "+f"(d[8]), "+f"(d[9]), "+f"(d[10]), "+f"(d[11]), "+f"(d[12]), "+f"(d[13]), "+f"(d[14]), "+f"(d[15]),
          "+f"(d[16]), "+f"(d[17]), "+f"(d[18]), "+f"(d[19]), "+f"(d[20]), "+f"(d[21]), "+f"(d[22]), "+f"(d[23]),
          "+f"(d[24]), "+f"(d[25]), "+f"(d[26]), "+f"(d[27]), "+f"(d[28]), "+f"(d[29]), "+f"(d[30]), "+f"(d[31]),
          "+f"(d[32]), "+f"(d[33]), "+f"(d[34]), "+f"(d[35]), "+f"(d[36]), "+f"(d[37]), "+f"(d[38]), "+f"(d[39]),
          "+f"(d[40]), "+f"(d[41]), "+f"(d[42]), "+f"(d[43]), "+f"(d[44]), "+f"(d[45]), "+f"(d[46]), "+f"(d[47]),
          "+f"(d[48]), "+f"(d[49]), "+f"(d[50]), "+f"(d[51]), "+f"(d[52]), "+f"(d[53]), "+f"(d[54]), "+f"(d[55]),
          "+f"(d[56]), "+f"(d[57]), "+f"(d[58]), "+f"(d[59]), "+f"(d[60]), "+f"(d[61]), "+f"(d[62]), "+f"(d[63]),
          "+f"(d[64]), "+f"(d[65]), "+f"(d[66]), "+f"(d[67]), "+f"(d[68]), "+f"(d[69]), "+f"(d[70]), "+f"(d[71]),
          "+f"(d[72]), "+f"(d[73]), "+f"(d[74]), "+f"(d[75]), "+f"(d[76]), "+f"(d[77]), "+f"(d[78]), "+f"(d[79]),
          "+f"(d[80]), "+f"(d[81]), "+f"(d[82]), "+f"(d[83]), "+f"(d[84]), "+f"(d[85]), "+f"(d[86]), "+f"(d[87]),
          "+f"(d[88]), "+f"(d[89]), "+f"(d[90]), "+f"(d[91]), "+f"(d[92]), "+f"(d[93]), "+f"(d[94]), "+f"(d[95]),
          "+f"(d[96]), "+f"(d[97]), "+f"(d[98]), "+f"(d[99]), "+f"(d[100]), "+f"(d[101]), "+f"(d[102]), "+f"(d[103]),
          "+f"(d[104]), "+f"(d[105]), "+f"(d[106]), "+f"(d[107]), "+f"(d[108]), "+f"(d[109]), "+f"(d[110]), "+f"(d[111]),
          "+f"(d[112]), "+f"(d[113]), "+f"(d[114]), "+f"(d[115]), "+f"(d[116]), "+f"(d[117]), "+f"(d[118]), "+f"(d[119]),
          "+f"(d[120]), "+f"(d[121]), "+f"(d[122]), "+f"(d[123]), "+f"(d[124]), "+f"(d[125]), "+f"(d[126]), "+f"(d[127])
        : "l"(da), "l"(db));
}

struct Idx {
    uint32_t lane, warp, w4, q4, g8, prow, pan;
    __device__ __forceinline__ Idx() {
        uint32_t t; asm volatile("mov.u32 %0, %%tid.x;" : "=r"(t));
        lane = t & 31; warp = t >> 5; w4 = warp & 3; q4 = lane & 3; g8 = lane >> 2;
        prow = w4 * 16 + ((lane >> 3) & 1) * 8 + (lane & 7);
        pan = prow * 128 + (((lane >> 4) ^ (lane & 7)) << 4);
    }
};
#define IDX() const Idx ix; const uint32_t lane = ix.lane, warp = ix.warp, w4 = ix.w4, q4 = ix.q4, g8 = ix.g8, prow = ix.prow, pan_addr = ix.pan; \
    (void)lane; (void)warp; (void)w4; (void)q4; (void)g8; (void)prow; (void)pan_addr;

__device__ __forceinline__ int kof(int t, int sh, int j) {
    const int p = t >> (sh - 1), pn = p < 2 ? p : p >= 9, q = p - 2 - 7 * pn;
    return ((p < 2 ? j : q + (q >= j)) << 7) + (pn << 6) + ((t & (sh - 1)) << 5);
}
__device__ __forceinline__ uint32_t fidx(uint32_t m, uint32_t w, uint32_t pn) {
    return m * 32 + w * 16 + pn;
}
constexpr int HC0 = 8 * 48, HC3 = HC0 + 3072;
__device__ __forceinline__ int hcol(int p, int j) { return HC0 + p * 1024 + j * 128; }
struct Ring {
    uint32_t slot, par;
    __device__ __forceinline__ void next() { if (++slot == NSLOT) { slot = 0; par ^= 1; } }
    __device__ __forceinline__ void skip(uint32_t n) { slot += n; if (slot >= NSLOT) { slot -= NSLOT; par ^= 1; } }
};
__device__ __forceinline__ uint32_t BAR_FULL(uint32_t sb, uint32_t s) { return sb + OFF_BAR + 8 * s; }
constexpr uint32_t AF_REL = 48;
__device__ __forceinline__ uint32_t BAR_EMPTY(uint32_t sb, uint32_t s) { return sb + OFF_BAR + 96 + 8 * s; }
__device__ __forceinline__ uint32_t BAR_SFULL(uint32_t sb, uint32_t i) { return sb + OFF_BAR + 152 + 8 * i; }
__device__ __forceinline__ uint32_t BAR_SREADY(uint32_t sb, uint32_t i) { return sb + OFF_BAR + 184 + 8 * i; }
__device__ __forceinline__ uint32_t BAR_ONE(uint32_t sb, uint32_t i) { return sb + OFF_BAR + 216 + 8 * i; }
enum { EV_WIN, EV_WIN1, EV_WIN2, EV_WIN3, EV_P0, EV_GA, EV_GB, EV_LN2, EV_LAG0, EV_LAG1, EV_LAG2, EV_LAG3, EV_LAG4, EV_LAG5, EV_KV, EV_PAR, EV_AGO, EV_AGO1, EV_AGO2, EV_FGO, EV_FGO1, EV_FGO2, EV_H0, EV_H1, EV_H2, EV_H3, EV_COUNT };
constexpr int NB_TAIL = 4;

struct Rel {
    uint32_t base; bool sig;
    __device__ __forceinline__ Rel(uint32_t sb, uint32_t tw) {
        uint32_t a; asm("mapa.shared::cluster.u32 %0, %1, %2;" : "=r"(a) : "r"(BAR_EMPTY(sb, 0)), "r"((tw >> 5) & 1));
        base = __shfl_sync(0xffffffffu, a, 0); sig = (tw & ~32u) == 0;
    }
    __device__ __forceinline__ void operator()(uint32_t slot) const {
        if (sig) asm volatile("mbarrier.arrive.shared::cluster.b64 _, [%0];" :: "r"(base + 8 * slot) : "memory");
    }
};
struct LnRow { float rs0, nm0, rs1, nm1; };
struct Pipe {
    Rel rel; uint32_t p1, p2;
    __device__ __forceinline__ Pipe(uint32_t sb, uint32_t tw, uint32_t first) : rel(sb, tw), p1(first), p2(NSLOT) {}
    template <bool TWO> __device__ __forceinline__ void acquire(uint32_t sb, uint32_t af, const Ring& r) {
        const uint32_t b0 = BAR_FULL(sb, r.slot), b1 = b0 + af;
        const bool ready = TWO ? mbar_test2(b0, b1, r.par) : mbar_test(b0, r.par);
        wg_wait<1>();
        rel(p2);
        if (!ready) { if (TWO) mbar_wait2(b0, b1, r.par); else mbar_wait(b0, r.par); }
    }
    __device__ __forceinline__ void issued(uint32_t slot) { p2 = p1; p1 = slot; }
    __device__ __forceinline__ void drain1() { wg_wait<1>(); rel(p2); p2 = NSLOT; }
    __device__ __forceinline__ void drain0() { wg_wait<0>(); rel(p1); p1 = NSLOT; }
    template <bool TWO, class Step> __device__ __forceinline__ void hold(int LG, uint32_t sb, uint32_t af, Ring& r, uint32_t lag_bar, Step step) {
        Ring q = r;
#pragma unroll 1
        for (int i = 0; i < LG; ++i) { if (TWO) mbar_wait2(BAR_FULL(sb, q.slot), BAR_FULL(sb, q.slot) + af, q.par); else mbar_wait(BAR_FULL(sb, q.slot), q.par); q.next(); }
        mbar_wait(lag_bar, 0);
#pragma unroll 1
        do {
            step(r.slot);
            wg_wait<2>(); rel(p2); p2 = p1; p1 = r.slot;
            if (++r.slot == NSLOT) r.slot = 0;
        } while (r.slot != q.slot);
        r.par = q.par;
    }
};
template <bool TWO, bool FIRST, int NA, int NB>
__device__ __forceinline__ void step32(float (&aa)[NA], float (&ab)[NB], uint32_t sb, uint32_t wg, uint32_t slot, int own) {
    const uint32_t st = d16(sb) + slot * (SLOT >> 4);
    const uint32_t alo = own >= 0 ? d16(sb) + OFF_STG / 16 + wg * 1024 + (own >> 1) * 512 + (own & 1) * 4 : st + wg * 256;
    const uint32_t ahi = own >= 0 ? (1024 >> 4) | (1u << 30) : (512 >> 4) | (2u << 30);
    wg_fence();
#pragma unroll
    for (int k = 0; k < 2; ++k) {
        const uint64_t da = ((uint64_t)ahi << 32) | (alo + k * 2 + 0x10000);
        if constexpr (NA == 88) {
            const uint64_t d0 = mk_desc(st, 8192 + k * 2048, 8192, 1024, 1), d1 = mk_desc(st, 12288 + k * 2048, 8192, 1024, 1);
            if (FIRST && k == 0) { wgmma_n176_z(aa, da, d0); wgmma_n176_z(ab, da, d1); }
            else { wgmma_n176(aa, da, d0); wgmma_n176(ab, da, d1); }
        } else {
            const uint64_t d0 = mk_desc(st, 8192 + k * 2048, 4096, 1024, 1), d1 = mk_desc(st, 24576 + k * 2048, 4096, 1024, 1);
            if (FIRST && k == 0) { wgmma_n256_z(aa, da, d0); if constexpr (TWO) wgmma_n128_z(ab, da, d1); }
            else { wgmma_n256(aa, da, d0); if constexpr (TWO) wgmma_n128(ab, da, d1); }
        }
    }
    wg_commit();
}
template <bool TWO, int LG, int NA, int NB, class Tail>
__device__ __forceinline__ void mainloop32(float (&aa)[NA], float (&ab)[NB], uint32_t sb, uint32_t wg, uint32_t tw, Ring& r, uint32_t lag_ev, int g0, Tail tail) {
    mbar_wait(BAR_FULL(sb, r.slot), r.par);
    step32<TWO, true>(aa, ab, sb, wg, r.slot, TWO ? 0 : -1);
    TS(g0, 0);
    Pipe pp(sb, tw, r.slot);
    r.next();
    const int end = wg ? 32 : 32 - LG;
#pragma unroll 1
    for (int it = 1; it < end; ++it) {
        pp.acquire<TWO>(sb, wg ? 0 : AF_REL, r);
        step32<TWO, false>(aa, ab, sb, wg, r.slot, TWO && it < 4 ? it : -1);
        pp.issued(r.slot);
        TS(g0 + it, 0);
        r.next();
    }
    if (wg == 0) { pp.drain1(); pp.drain0(); pp.hold<TWO>(LG, sb, AF_REL, r, BAR_ONE(sb, lag_ev), [&](uint32_t slot) { step32<TWO, false>(aa, ab, sb, 0, slot, -1); }); }
    pp.drain1();
    if (wg == 1 && tw == 0) mbar_arrive(BAR_ONE(sb, lag_ev));
    tail();
    pp.drain0();
    TS(g0 + 31, 1);
}
template <bool FIRST>
__device__ __forceinline__ void step64(float (&acc)[64], uint32_t sb, uint32_t wg, uint32_t slot, int own) {
    const uint32_t sbb = d16(sb) + slot * (SLOT >> 4), sa = own >= 0 ? d16(sb) + OFF_STG / 16 + wg * 1024 + own * 512 : sbb + wg * 512;
    wg_fence();
#pragma unroll
    for (int k = 0; k < 4; ++k) {
        const uint64_t da = mk_desc(sa, k * 32, 16, 1024, 1), db = mk_desc(sbb, 16384 + k * 2048, 8192, 1024, 1);
        if (FIRST && k == 0) wgmma_n128_z(acc, da, db); else wgmma_n128(acc, da, db);
    }
    wg_commit();
}
template <class Mid>
__device__ __forceinline__ void mainloop64(float (&acc)[64], bool wo, uint32_t sb, uint32_t wg, uint32_t tw, Ring& r, Mid mid) {
    const int g0 = wo ? 32 : 144, nst = wo ? 16 : 56, lg = wo ? LAGW : LAGD; (void)g0;
    const uint32_t lag_bar = BAR_ONE(sb, wo ? EV_LAG4 : EV_LAG5), af = wo && !wg ? AF_REL : 0;
    mbar_wait(BAR_FULL(sb, r.slot), r.par);
    if (!wo) CS(28);
    step64<true>(acc, sb, wg, r.slot, wo ? 0 : -1);
    if (!wo) CS(29);
    TS(g0, 0);
    Pipe pp(sb, tw, r.slot);
    r.next();
    int it = 1;
    auto run = [&](int end, int own) {
#pragma unroll 1
        do {
            pp.acquire<true>(sb, af, r);
            step64<false>(acc, sb, wg, r.slot, own);
            pp.issued(r.slot);
            TS(g0 + it, 0);
            if (wo && it == 2) CS(9);
            r.next();
            if (own > 0) {
                own = -1;
                pp.drain1(); pp.drain0();
                TS(g0 + 1, 1);
            }
        } while (++it < end);
    };
    const int end = wg ? nst : nst - lg;
    run(wo ? MIDW : wg ? MIDD : end, wo ? 1 : -1);
    mid();
    if (it < end) run(end, -1);
    if (wg == 0) { pp.drain1(); pp.drain0(); pp.hold<true>(lg, sb, af, r, lag_bar, [&](uint32_t slot) { step64<false>(acc, sb, 0, slot, -1); }); }
    pp.drain1();
    if (wg == 1 && tw == 0) mbar_arrive(lag_bar);
    pp.drain0();
    TS(g0 + nst - 1, 1);
}

struct RowAcc {
    float sm[4] = {0.f, 0.f, 0.f, 0.f}, sq[4] = {0.f, 0.f, 0.f, 0.f};
    __device__ __forceinline__ void add(int e, float x) { sm[e & 3] += x; sq[e & 3] = fmaf(x, x, sq[e & 3]); }
    __device__ __forceinline__ void publish(uint4* dst, uint32_t q4, uint32_t ep) const {
        const float s0 = sm[0] + sm[1], s1 = sm[2] + sm[3], q0 = sq[0] + sq[1], q1 = sq[2] + sq[3];
        const bool od = q4 & 1;
        float sv = (od ? s1 : s0) + __shfl_xor_sync(0xffffffffu, od ? s0 : s1, 1), qv = (od ? q1 : q0) + __shfl_xor_sync(0xffffffffu, od ? q0 : q1, 1);
        sv += __shfl_xor_sync(0xffffffffu, sv, 2); qv += __shfl_xor_sync(0xffffffffu, qv, 2);
        if (q4 < 2) st_pkt16(dst + q4 * 8, 0, __float_as_uint(sv), __float_as_uint(qv), ep);
    }
};
__device__ __forceinline__ LnRow merge_stats(const uint4* src, uint32_t q4, uint32_t ep, uint32_t sb) {
    uint4 t[4];
    uint32_t n = 0;
    while (true) {
#pragma unroll
        for (int i = 0; i < 4; ++i) t[i] = ld_pkt16(src + (q4 * 2 + (i >> 1)) * 512 + (i & 1) * 8);
        const bool ok_ = __all_sync(0xffffffffu, t[0].w == ep && t[1].w == ep && t[2].w == ep && t[3].w == ep);
        if (n < 4) CS(14 + n);
        if (ok_) break;
        SPIN_GUARD(n);
    }
    float v[4];
#pragma unroll
    for (int h = 0; h < 2; ++h) { v[h] = __uint_as_float(t[h].y) + __uint_as_float(t[2 + h].y); v[2 + h] = __uint_as_float(t[h].z) + __uint_as_float(t[2 + h].z); }
#pragma unroll
    for (int o = 1; o < 4; o <<= 1)
#pragma unroll
        for (int i = 0; i < 4; ++i) v[i] += __shfl_xor_sync(0xffffffffu, v[i], o);
    const float m0 = v[0] * (1.f / D_), m1 = v[1] * (1.f / D_);
    const float r0 = rsqrtf(fmaxf(fmaf(-m0, m0, v[2] * (1.f / D_)), 0.f) + 1e-5f), r1 = rsqrtf(fmaxf(fmaf(-m1, m1, v[3] * (1.f / D_)), 0.f) + 1e-5f);
    return LnRow{r0, -m0 * r0, r1, -m1 * r1};
}
struct Stg {
    uint32_t b, par;
    __device__ __forceinline__ uint32_t acquire2(uint32_t sb, uint32_t wg) {
        mbar_wait2(BAR_SREADY(sb, wg * 2), BAR_SREADY(sb, wg * 2 + 1), par);
        par ^= 1;
        return sb + OFF_STG + wg * 16384;
    }
    __device__ __forceinline__ void publish(uint32_t sb, uint32_t wg, uint32_t lane) {
        fence_async_smem();
        __syncwarp();
        if (lane == 0) mbar_arrive(BAR_SFULL(sb, wg * 2 + b));
        b ^= 1;
    }
};

struct LnPar {
    uint4 p[8];
    __device__ __forceinline__ void load(uint32_t sb, uint32_t q4) {
#pragma unroll
        for (int i = 0; i < 8; ++i) p[i] = lds128(sb + OFF_PAR + i * 64 + q4 * 16);
    }
};
__device__ __forceinline__ void ln_norm(uint32_t (&xn)[32], const float (&x)[64], const LnRow& n) {
#pragma unroll
    for (int e = 0; e < 32; ++e) {
        const float rs = (e & 1) ? n.rs1 : n.rs0, nm = (e & 1) ? n.nm1 : n.nm0;
        xn[e] = pack2(fmaf(x[2 * e], rs, nm), fmaf(x[2 * e + 1], rs, nm));
    }
}
__device__ __forceinline__ void ln_emit(const uint32_t (&xr)[32], const LnPar& lp, uint32_t sb, uint32_t wg, const Idx& ix) {
#pragma unroll
    for (int i = 0; i < 8; ++i)
        stsm4(sb + OFF_STG + wg * 16384 + (i >> 2) * 8192 + (ix.pan ^ ((i & 3) << 5)), hfma2_bf16(xr[4 * i], lp.p[i].z, lp.p[i].x), hfma2_bf16(xr[4 * i + 1], lp.p[i].z, lp.p[i].x),
              hfma2_bf16(xr[4 * i + 2], lp.p[i].w, lp.p[i].y), hfma2_bf16(xr[4 * i + 3], lp.p[i].w, lp.p[i].y));
    fence_async_smem();
    __syncwarp();
    if (ix.lane < 2) mbar_arrive(BAR_SFULL(sb, wg * 2 + ix.lane));
    bar_sync(1 + wg, 128);
}
__device__ __forceinline__ void load_slab(uint32_t (&xr)[32], uint32_t buf) {
    IDX();
#pragma unroll
    for (int i = 0; i < 8; ++i) ldsm4(buf + (i >> 2) * 8192 + (pan_addr ^ ((i & 3) << 5)), xr[4 * i], xr[4 * i + 1], xr[4 * i + 2], xr[4 * i + 3]);
}
__device__ __forceinline__ void unpack_slab(float (&x)[64], const uint32_t (&xr)[32]) {
#pragma unroll
    for (int i = 0; i < 32; ++i) unpack2(xr[i], x[2 * i], x[2 * i + 1]);
}
__device__ __forceinline__ void store_slab(const float (&x)[64], uint32_t buf, uint32_t pitch, uint32_t pan, int i0, int i1) {
#pragma unroll
    for (int i = i0; i < i1; ++i)
        stsm4(buf + (i >> 2) * pitch + (pan ^ ((i & 3) << 5)), pack2(x[8 * i], x[8 * i + 1]), pack2(x[8 * i + 2], x[8 * i + 3]), pack2(x[8 * i + 4], x[8 * i + 5]), pack2(x[8 * i + 6], x[8 * i + 7]));
}
__device__ __forceinline__ void fetch_halo(uint4* src, bool first, uint32_t sb, uint32_t W, uint32_t lane) {
    mbar_wait(BAR_ONE(sb, EV_KV), 0);
    mbar_wait2(BAR_SREADY(sb, 0), BAR_SREADY(sb, 1), 1);
    uint4 hv[8];
    uint32_t n = 0;
    while (true) {
        bool ok = true;
#pragma unroll
        for (int i = 0; i < 8; ++i) { hv[i] = first ? make_uint4(0, 0, 0, 0) : ld_pkt16(src + i * 32); ok = ok && hv[i].x != 0; }
        if (first || __all_sync(0xffffffffu, ok)) break;
        SPIN_GUARD(n);
    }
#pragma unroll
    for (int i = 0; i < 8; ++i) stsm4(sb + OFF_STG + W * 2048 + (i >> 2) * 8192 + (i & 3) * 512 + lane * 16, hv[i].x, hv[i].y, hv[i].z, hv[i].w);
    bar_arrive(NB_TAIL + W, 64);
    if (!first) {
#pragma unroll
        for (int i = 0; i < 8; ++i) src[i * 32] = make_uint4(0, 0, 0, 0);
    }
}

template <int NG, class G, class U, class Buf>
__device__ __forceinline__ void glu(uint32_t sb, uint32_t wg, G g, U u, Buf buf) {
    IDX();
#pragma unroll
    for (int k = 0; k < NG; ++k) {
        float h[8];
#pragma unroll
        for (int e = 0; e < 8; ++e) h[e] = fmaf(tanh_(g(8 * k + e)), u(8 * k + e), u(8 * k + e));
        stsm4(buf(k >> 2) + (pan_addr ^ ((k & 3) << 5)), pack2(h[0], h[1]), pack2(h[2], h[3]), pack2(h[4], h[5]), pack2(h[6], h[7]));
    }
    fence_async_smem();
    __syncwarp();
    if (lane < 2) mbar_arrive(BAR_SFULL(sb, wg * 2 + lane));
}

template <int NP>
__device__ __forceinline__ void passes128(uint32_t sb, uint32_t wg, uint32_t tw, Ring& r, Stg& stg) {
#pragma unroll 1
    for (int p = 0; p < NP; ++p) {
        float b256[128], none[1];
        mainloop32<false, LAGS>(b256, none, sb, wg, tw, r, EV_LAG2 + p, 80 + 32 * (p & 1), [&] { stg.acquire2(sb, wg); });
        if (threadIdx.x == 0) { TL(29 + 2 * p); TC(114 + 2 * p); }
        if (threadIdx.x == 128) TL(53 + 2 * (p & 1));
        CS(24 + 2 * (p & 1));
        glu<8>(sb, wg, [&](int i) { return b256[i + (i & 32)]; }, [&](int i) { return b256[i + (i & 32) + 32]; }, [&](int pn) { return sb + OFF_STG + wg * 16384 + pn * 8192; });
        if (threadIdx.x == 0) { TL(30 + 2 * p); TC(115 + 2 * p); }
        if (threadIdx.x == 128) TL(54 + 2 * (p & 1));
        CS(25 + 2 * (p & 1));
    }
}

__global__ void __launch_bounds__(384, 1)
fused_block_kernel(const __grid_constant__ Ptrs pt, const __grid_constant__ Maps mp) {
    uint32_t* const g_flags = pt.mail->flags;
    uint2* const g_mod = pt.mail->mod;
    uint4* const g_st1 = pt.mail->st1;
    uint32_t* const g_par2 = pt.mail->par2;
    uint4* const g_halo = pt.mail->halo;
    const __nv_bfloat16* __restrict__ cvec = pt.c;
    if (threadIdx.x == 224) { prefetch_map(&mp.wm8); prefetch_map(&mp.x); }
    extern __shared__ __align__(1024) uint8_t smem[];
    const uint32_t sb = smem_u32(smem);
    const uint32_t tid = threadIdx.x, tw = tid & 127, lane = tid & 31;
    const uint32_t warp = __shfl_sync(0xffffffffu, tid >> 5, 0), wg = warp >> 2;
    uint32_t rank; asm("mov.u32 %0, %%cluster_ctarank;" : "=r"(rank));
    rank = __shfl_sync(0xffffffffu, rank, 0);
    uint32_t ep;
    uint32_t smid; asm volatile("mov.u32 %0, %%smid;" : "=r"(smid));
    const int c = __shfl_sync(0xffffffffu, smid >> 1, 0);
    const int c7 = ((c - 32) * 37) >> 8;
    int grp = c < 32 ? c & 7 : c < 60 ? c - 31 - 7 * c7 : c < 62 ? -1 : 0;
    const int j = c < 32 ? c >> 3 : c < 60 ? 4 + c7 : c < 62 ? (c - 60) * 2 + rank : c - 58;
    const bool aux = grp < 0;
    const int m = grp * 2 + rank;
    uint4* const g_st2 = g_halo + (m > 0 ? (m - 1) * 8 * 512 : 128);

    bool cluster_arrive_early = false;
    if (wg < 2) {
      if (!KDEBUG) cluster_arrive();
      ep = flag_get(g_flags + FL_DONE);
      uint16_t cw[8];
      {
          const __nv_bfloat16* cp = cvec + ((tw >> 5) * 32 + (tw & 3) * 2) * 8 + (lane >> 2);
#pragma unroll
          for (int i = 0; i < 8; ++i) asm volatile("ld.global.nc.u16 %0, [%1];" : "=h"(cw[i]) : "l"(cp + (i >> 1) * 64 + (i & 1) * 8));
      }
      asm volatile("setmaxnreg.inc.sync.aligned.u32 224;");
      if (tid == 0) TL(58);
      if (KDEBUG) cluster_arrive();
      Ring r{0, 0};
      Stg stg{0, 0};
      if (aux) {
        if (wg == 0) {
            const uint4 cv = *(const uint4*)(cvec + tw * 8);
            sts128(sb + OFF_STG + (tw >> 3) * 1024 + (tw & 7) * 16, pack2(silu_(bf_lo(cv.x)), silu_(bf_hi(cv.x))), pack2(silu_(bf_lo(cv.y)), silu_(bf_hi(cv.y))),
                   pack2(silu_(bf_lo(cv.z)), silu_(bf_hi(cv.z))), pack2(silu_(bf_lo(cv.w)), silu_(bf_hi(cv.w))));
            fence_async_smem();
        }
        cluster_wait();
        ep = __shfl_sync(0xffffffffu, ep, 0) / NCTA + 1;
        if (wg == 0) {
            bar_sync(1, 128);
#pragma unroll 1
            for (int p = 0; p < 4; ++p) {
                float acc[128];
#pragma unroll
                for (int i = 0; i < 128; ++i) acc[i] = 0.f;
                uint32_t prev = 0;
#pragma unroll 1
                for (int kc = 0; kc < 16; ++kc) {
                    mbar_wait(BAR_FULL(sb, r.slot), r.par);
                    wg_fence();
#pragma unroll
                    for (int k = 0; k < 4; ++k)
                        wgmma_n256(acc, mk_desc(d16(sb) + kc * 64, OFF_STG + k * 32, 16, 0, 1), mk_desc(d16(sb) + r.slot * (SLOT >> 4), k * 2048, 8192, 1024, 1));
                    wg_commit();
                    wg_wait<1>();
                    if (kc > 0 && tw < 4) mbar_arrive(BAR_EMPTY(sb, prev));
                    prev = r.slot;
                    r.next();
                }
                wg_wait<0>();
                if (tw < 4) mbar_arrive(BAR_EMPTY(sb, prev));
                if (tw < 4) {
#pragma unroll
                    for (int jn = 0; jn < 32; ++jn) sts32(sb + OFF_TAB + (jn * 4 + tw) * 4, pack2(acc[jn * 4], acc[jn * 4 + 1]));
                }
                bar_sync(1, 128);
                const int vec = 2 + p, blk = p * 4 + j;
                const uint32_t val = lds32(sb + OFF_TAB + tw * 4);
                if (vec == 2 || vec == 5) st_pkt(g_mod + (8 + blk) * 128 + tw, val, ep);
                else {
                    const float one = vec == 4 ? 1.f : 0.f;
                    g_par2[((blk & 3) * 16 + (tw >> 3)) * 16 + (tw & 3) * 4 + (vec - 3) * 2 + ((tw >> 2) & 1)] =
                        pack2(0.5f * bf_round(one + bf_lo(val)), 0.5f * bf_round(one + bf_hi(val)));
                }
                bar_sync(1, 128);
                if (tw == 0) {
                    if (vec == 3 || vec == 4) asm volatile("red.release.gpu.global.add.u32 [%0], 1;" :: "l"(&g_flags[FL_LN2]) : "memory");
                    TL(1 + p);
                }
            }
            if (lane < 2) mbar_arrive_cta(BAR_ONE(sb, EV_P0), lane);
        }
        r = Ring{64 % NSLOT, (64 / NSLOT) & 1};
        mbar_wait(BAR_ONE(sb, EV_P0), 0);
        passes128<4>(sb, wg, tw, r, stg);
      } else {
        float xs[64];
        uint32_t xp[32];
        {
            IDX();
            if (q4 < 2) st_pkt16(g_st1 + (m * 8 + j) * 512 + wg * 64 + w4 * 16 + g8 + q4 * 8, 0, 0, 0, 0);
            if (warp == 0) st_pkt16(pt.mail->mod1 + g8 * 512 + (m * 8 + j) * 4 + q4, 0, 0, 0, 0);
            sts128(sb + tid * 16, pack2(silu_(bf_lo(cw[0])), silu_(bf_lo(cw[1]))), pack2(silu_(bf_lo(cw[2])), silu_(bf_lo(cw[3]))),
                   pack2(silu_(bf_lo(cw[4])), silu_(bf_lo(cw[5]))), pack2(silu_(bf_lo(cw[6])), silu_(bf_lo(cw[7]))));
            cluster_wait();
            ep = __shfl_sync(0xffffffffu, ep, 0) / NCTA + 1;
            load_slab(xp, stg.acquire2(sb, wg));
            unpack_slab(xs, xp);
            if (tid == 0) TL(24);
            if (tid == 128) TL(27);
        }
#pragma unroll 1
        for (int blk = 0; ; ++blk) {
        {
            IDX();
            uint4* const st = (blk ? g_st2 : g_st1 + m * 8 * 512) + wg * 64 + w4 * 16 + g8;
            RowAcc ra;
#pragma unroll
            for (int e = 0; e < 64; ++e) ra.add(e, xs[e]);
            ra.publish(st + j * 512, q4, ep);
            uint32_t t_pub = 0; if (PDLY) asm volatile("mov.u32 %0, %%clock;" : "=r"(t_pub));
            if (tid == 0) TL(blk ? 9 : 26);
            if (tid == 128 && blk) TL(34);
            if (blk) CS(11);
            LnPar lp;
            if (blk == 0) {
            uint4* const mod_out = pt.mail->mod1 + g8 * 512 + (m * 8 + j) * 4 + q4;
            if (wg == 0) {
                uint4 af[8];
#pragma unroll
                for (int i = 0; i < 8; ++i) af[i] = lds128(sb + w4 * 512 + i * 64 + q4 * 16);
                float c[4][4] = {};
#pragma unroll
                for (int i = 0; i < 8; ++i) {
                    if (!(i & 1)) mbar_wait(BAR_ONE(sb, EV_WIN + (i >> 1)), 0);
                    if (i == 6 && tid == 0) TL(25);
#pragma unroll
                    for (int h = 0; h < 2; ++h) {
                        uint32_t b0, b1, b2, b3;
                        ldsm4t(sb + 5 * SLOT + i * 4096 + w4 * 1024 + h * 512 + (lane & 15) * 32 + (lane >> 4) * 16, b0, b1, b2, b3);
                        mma16816(c[2 * h], h ? af[i].z : af[i].x, 0u, h ? af[i].w : af[i].y, 0u, b0, b1);
                        mma16816(c[2 * h + 1], h ? af[i].z : af[i].x, 0u, h ? af[i].w : af[i].y, 0u, b2, b3);
                    }
                }
                if (lane < 4) sts128(sb + OFF_TAB + w4 * 64 + lane * 16, __float_as_uint(c[0][0] + c[2][0]), __float_as_uint(c[0][1] + c[2][1]),
                                     __float_as_uint(c[1][0] + c[3][0]), __float_as_uint(c[1][1] + c[3][1]));
                if (lane < 2) mbar_arrive_cta(BAR_ONE(sb, EV_P0), lane);
                bar_sync(1, 128);
                if (w4 == 0) {
                    float a[4] = {0.f, 0.f, 0.f, 0.f};
#pragma unroll
                    for (int i = 0; i < 4; ++i) {
                        const uint4 t = lds128(sb + OFF_TAB + i * 64 + q4 * 16);
                        a[0] += __uint_as_float(t.x); a[1] += __uint_as_float(t.y); a[2] += __uint_as_float(t.z); a[3] += __uint_as_float(t.w);
                    }
                    const float add = m >= 8 ? 1.f : 0.f;
                    st_pkt16(mod_out, pack2(bf_round(a[0]) + add, bf_round(a[1]) + add), pack2(bf_round(a[2]) + add, bf_round(a[3]) + add), ep, 0);
                    if (tid == 0) TL(3);
                }
            } else if (LWAIT >= 0) mbar_wait(BAR_ONE(sb, EV_WIN + LWAIT), 0);
            } else {
                mbar_wait(BAR_ONE(sb, EV_LN2), 0);
                stg.acquire2(sb, wg);
            }
            lp.load(sb, q4);
#pragma unroll
            for (int e = 0; e < 32; ++e) xp[e] = pack2(xs[2 * e], xs[2 * e + 1]);
            if (PDLY && blk) { uint32_t t1; do { asm volatile("mov.u32 %0, %%clock;" : "=r"(t1)); } while (t1 - t_pub < PDLY); }
            if (blk) CS(13);
            const LnRow n = merge_stats(st, q4, ep, sb);
            if (tid == 0) TL(blk ? 49 : 48);
            if (tid == 128) TL(blk ? 45 : 28);
            if (blk) CS(18);
            uint32_t xn[32];
            ln_norm(xn, xs, n);
            if (blk == 0) { mbar_wait(BAR_ONE(sb, EV_PAR), 0); lp.load(sb, q4); }
            ln_emit(xn, lp, sb, wg, ix);
            if (tid == 0) { TL(blk ? 36 : 8); TC(blk ? 109 : 103); }
            if (tid == 128) TL(blk ? 43 : 22);
            if (blk) CS(21);
        }
        if (blk == 0) {
        {
            float kv[128], qa[64];
            mbar_wait(BAR_FULL(sb, r.slot), r.par);
            step32<true, true>(kv, qa, sb, wg, r.slot, 0);
            TS(0, 0);
            Pipe pp(sb, tw, r.slot);
            r.next();
#pragma unroll 1
            for (int it = 1; it < 32 - LAGQ; ++it) {
                pp.acquire<true>(sb, wg ? 0 : AF_REL, r);
                step32<true, false>(kv, qa, sb, wg, r.slot, it < 4 ? it : -1);
                pp.issued(r.slot);
                TS(it, 0);
                r.next();
            }
            auto half = [&](uint32_t slot, bool q) {
                const uint32_t st = d16(sb) + slot * (SLOT >> 4);
#pragma unroll
                for (int k = 0; k < 2; ++k) {
                    const uint64_t da = mk_desc(st + wg * 256, k * 32, 16, 512, 2);
                    if (q) wgmma_n128(qa, da, mk_desc(st, 24576 + k * 2048, 4096, 1024, 1)); else wgmma_n256(kv, da, mk_desc(st, 8192 + k * 2048, 4096, 1024, 1));
                }
            };
            auto part = [&](bool q) {
                wg_fence();
#pragma unroll
                for (int it = 32 - LAGQ; it < 32; ++it) half(it % NSLOT, q);
                wg_commit();
            };
            stg.acquire2(sb, wg); mbar_wait2(BAR_SREADY(sb, 2), BAR_SREADY(sb, 3), 1);
            if (wg == 0) { pp.drain1(); pp.drain0(); }
#pragma unroll 1
            for (int it = 32 - LAGQ; it < 32; ++it) {
                pp.acquire<true>(sb, wg ? 0 : AF_REL, r);
                if (wg) { wg_fence(); half(r.slot, false); wg_commit(); }
                pp.issued(NSLOT);
                TS(it, 0);
                r.next();
            }
            if (wg == 0) { mbar_wait(BAR_ONE(sb, EV_LAG0), 0); part(false); part(true); wg_wait<1>(); }
            else { wg_wait<1>(); if (tw == 0) mbar_arrive(BAR_ONE(sb, EV_LAG0)); wg_wait<0>(); }
            CS(8);
            IDX();
            uint32_t k1[16], k2[16], v1[16], v2[16], qf[32];
#pragma unroll
            for (int i = 0; i < 128; ++i) asm volatile("" : "+f"(kv[i]) :: "memory");
#pragma unroll
            for (int t = 0; t < 16; ++t) k2[t] = pack2(kv[4 * t + 2], kv[4 * t + 3]);
#pragma unroll
            for (int t = 0; t < 16; ++t) k1[t] = pack2(kv[4 * t], kv[4 * t + 1]);
#pragma unroll
            for (int t = 0; t < 16; ++t) v2[t] = pack2(kv[64 + 4 * t + 2], kv[64 + 4 * t + 3]);
            const uint32_t nxt = warp + ((warp & 1) ? 3 : 1);
            if (nxt < 8) {
                const uint32_t dst = sb + OFF_STG + (nxt >> 2) * 16384 + (nxt & 3) * 2048 + lane * 16;
#pragma unroll
                for (int h = 0; h < 4; ++h) stsm4(dst + h * 512, k2[4 * h], k2[4 * h + 1], k2[4 * h + 2], k2[4 * h + 3]);
#pragma unroll
                for (int h = 0; h < 4; ++h) stsm4(dst + 8192 + h * 512, v2[4 * h], v2[4 * h + 1], v2[4 * h + 2], v2[4 * h + 3]);
                bar_arrive(NB_TAIL + nxt, 64);
            } else if (m < 15) {
                uint4* dst = g_halo + (m * 8 + j) * 512 + (w4 >> 1) * 256 + lane;
#pragma unroll
                for (int h = 0; h < 4; ++h) { if (!k2[4 * h]) k2[4 * h] = 0x8000u; if (!v2[4 * h]) v2[4 * h] = 0x8000u; }
#pragma unroll
                for (int h = 0; h < 4; ++h) st_pkt16(dst + h * 32, k2[4 * h], k2[4 * h + 1], k2[4 * h + 2], k2[4 * h + 3]);
#pragma unroll
                for (int h = 0; h < 4; ++h) st_pkt16(dst + 128 + h * 32, v2[4 * h], v2[4 * h + 1], v2[4 * h + 2], v2[4 * h + 3]);
            }
#pragma unroll
            for (int t = 0; t < 16; ++t) { v1[t] = pack2(kv[64 + 4 * t], kv[64 + 4 * t + 1]); v1[t] = movm(v1[t]); v2[t] = movm(v2[t]); }
            if (tid == 0) TL(33);
            CS(2);
            if (wg) part(true);
            bar_sync(NB_TAIL + warp, 64);
            CS(4);
            if (tid == 0) TL(5);
            uint32_t k0[16], v0[16];
            const uint32_t mine = sb + OFF_STG + wg * 16384 + w4 * 2048;
#pragma unroll
            for (int h = 0; h < 4; ++h) ldsm4(mine + lane * 16 + h * 512, k0[4 * h], k0[4 * h + 1], k0[4 * h + 2], k0[4 * h + 3]);
#pragma unroll
            for (int h = 0; h < 4; ++h) ldsm4t(mine + lane * 16 + 8192 + h * 512, v0[4 * h], v0[4 * h + 1], v0[4 * h + 2], v0[4 * h + 3]);
            wg_wait<0>();
#pragma unroll
            for (int it = 32 - LAGQ; it < 32; ++it) pp.rel(it % NSLOT);
            TS(31, 1);
            if (tid == 0) { TL(4); TC(104); }
            if (tid == 128) TL(50);
            CS(1);
#pragma unroll
            for (int i = 0; i < 64; ++i) asm volatile("" : "+f"(qa[i]) :: "memory");
            const bool lo0 = q4 * 2 > g8, lo1 = q4 * 2 + 1 > g8;
            const bool nopast = m == 0 && (warp & 5) == 0;
            const uint32_t lomask = (lo0 ? 0xFFFFu : 0u) | (lo1 ? 0xFFFF0000u : 0u);
            const uint32_t orow = mine + (lane & 7) * 128 + (((lane >> 3) ^ (lane & 7)) << 4);
            const float sl2 = 0.17677669529663687f * 1.4426950408889634f;
#pragma unroll
            for (int pn = 0; pn < 2; ++pn) {
                float e0[4], e1[4], mx[4], sum[4];
#pragma unroll
                for (int hh = 0; hh < 2; ++hh) {
                    const int h = pn * 2 + hh;
#pragma unroll
                    for (int i = 8 * h; i < 8 * h + 8; ++i) qf[i] = pack2(qa[2 * i], qa[2 * i + 1]);
                    float s[3][4];
#pragma unroll
                    for (int t = 0; t < 3; ++t) {
                        const uint32_t* k = (t == 0 ? k0 : t == 1 ? k1 : k2) + 4 * h;
                        s[t][0] = s[t][1] = s[t][2] = s[t][3] = 0.f;
                        mma16816(s[t], qf[h * 8], qf[h * 8 + 1], qf[h * 8 + 2], qf[h * 8 + 3], k[0], k[1]);
                        mma16816(s[t], qf[h * 8 + 4], qf[h * 8 + 5], qf[h * 8 + 6], qf[h * 8 + 7], k[2], k[3]);
                    }
#pragma unroll
                    for (int hf = 0; hf < 2; ++hf) {
                        const int u = hh * 2 + hf;
                        e0[u] = lo0 ? ((hf == 0 && nopast) ? -INFINITY : s[hf][hf * 2]) : s[hf + 1][hf * 2];
                        e1[u] = lo1 ? ((hf == 0 && nopast) ? -INFINITY : s[hf][hf * 2 + 1]) : s[hf + 1][hf * 2 + 1];
                        mx[u] = fmaxf(e0[u], e1[u]);
                    }
                }
#pragma unroll
                for (int o = 1; o < 4; o <<= 1)
#pragma unroll
                    for (int u = 0; u < 4; ++u) mx[u] = fmaxf(mx[u], __shfl_xor_sync(0xffffffffu, mx[u], o));
#pragma unroll
                for (int u = 0; u < 4; ++u) {
                    const float c = -mx[u] * sl2;
                    e0[u] = ex2(fmaf(e0[u], sl2, c)); e1[u] = ex2(fmaf(e1[u], sl2, c));
                    sum[u] = e0[u] + e1[u];
                }
#pragma unroll
                for (int o = 1; o < 4; o <<= 1)
#pragma unroll
                    for (int u = 0; u < 4; ++u) sum[u] += __shfl_xor_sync(0xffffffffu, sum[u], o);
#pragma unroll
                for (int u = 0; u < 4; ++u) {
                    const int h = pn * 2 + (u >> 1);
                    const float inv = rcp(sum[u]);
                    const uint32_t p = pack2(e0[u] * inv, e1[u] * inv);
                    const uint32_t* va = ((u & 1) ? v1 : v0) + 4 * h;
                    const uint32_t* vb = ((u & 1) ? v2 : v1) + 4 * h;
                    float o[2][4] = {};
#pragma unroll
                    for (int d = 0; d < 2; ++d) mma16816(o[d], va[2 * d], va[2 * d + 1], vb[2 * d], vb[2 * d + 1], p & lomask, p & ~lomask);
                    stsm4t((orow ^ ((u >> 1) << 6)) + pn * 8192 + (u & 1) * 1024, pack2(o[0][0], o[0][1]), pack2(o[0][2], o[0][3]), pack2(o[1][0], o[1][1]), pack2(o[1][2], o[1][3]));
                }
                fence_async_smem();
                __syncwarp();
                if (lane == 0) mbar_arrive(BAR_SFULL(sb, wg * 2 + pn));
                if (pn == 0) { CS(5); block_end(sb); }
            }
            CS(6);
            if (tid == 32) TL(41);
            mbar_wait(BAR_FULL(sb, 32 % NSLOT + wg), (32 / NSLOT) & 1);
            load_slab(xp, sb + (32 % NSLOT + wg) * SLOT);
            bar_sync(1 + wg, 128);
            if (tid == 0) { TL(6); TC(106); }
            if (tid == 128) TL(44);
            CS(7);
        }
        } else {
        {
            float ag[88], au[88];
            mainloop32<true, LAG>(ag, au, sb, wg, tw, r, EV_LAG1, 48, [&] {
                stg.acquire2(sb, wg);
                Ring q = r; if (!wg) q.next();
                mbar_wait(BAR_EMPTY(sb, q.slot), q.par ^ 1);
            });
            if (tid == 0) { TL(10); TC(110); }
            if (tid == 128) TL(51);
            CS(22);
            glu<11>(sb, wg, [&](int i) { return ag[i]; }, [&](int i) { return au[i]; },
                    [&](int pn) { return pn < 2 ? sb + OFF_STG + wg * 16384 + pn * 8192 : sb + (wg ? P3_SLOT1 : P3_SLOT0) * SLOT + 24576; });
            if (tid == 0) { TL(11); TC(111); }
            if (tid == 128) TL(52);
            CS(23);
        }
        passes128<2>(sb, wg, tw, r, stg);
        if (tid == 0) { TL(12); TC(112); }
        }
        {
            float acc[64], gf[32];
            mainloop64(acc, blk == 0, sb, wg, tw, r, [&] {
                mbar_wait(BAR_ONE(sb, EV_GA + blk), 0);
                if (blk) stg.acquire2(sb, wg);
                unpack_slab(xs, xp);
                uint32_t gt[16];
#pragma unroll
                for (int cg = 0; cg < 16; ++cg) gt[cg] = lds32(sb + OFF_TAB + blk * 256 + cg * 16 + (tw & 3) * 4);
#pragma unroll
                for (int i = 0; i < 16; ++i) unpack2(gt[i], gf[2 * i], gf[2 * i + 1]);
            });
            if (tid == 0) { TL(blk ? 13 : 7); TC(blk ? 113 : 107); }
            if (tid == 128) TL(blk ? 57 : 42);
            CS(blk ? 30 : 10);
#pragma unroll
            for (int e = 0; e < 64; ++e) xs[e] = fmaf(gf[(e >> 2) * 2 + (e & 1)], acc[e], xs[e]);
        }
        if (blk) break;
        }
        cluster_arrive();
        {
            IDX();
#pragma unroll
            for (int p = 0; p < 2; ++p) {
                store_slab(xs, sb + OFF_STG + wg * 16384, 8192, pan_addr, 4 * p, 4 * p + 4);
                stg.publish(sb, wg, lane);
            }
            if (tid == 0) TL(14);
            CS(31);
        }
      }
    } else {
        if (warp == 8 && !aux && elect_one()) {
#pragma unroll
            for (int i = 0; i < 4; ++i) mbar_init(BAR_SREADY(sb, i), 1);
#pragma unroll
            for (int i = 0; i < 4; ++i) mbar_init(BAR_ONE(sb, EV_WIN + i), 1);
#pragma unroll
            for (int i = 0; i < 4; ++i) {
                mbar_expect_tx(BAR_SREADY(sb, i), 8192);
                tma_load3(sb + OFF_STG + i * 8192, &mp.x, j * 128 + (i & 1) * 64, m * 64 + (i >> 1) * 32, BAR_SREADY(sb, i));
            }
#pragma unroll 1
            for (int i = 0; i < 4; ++i) {
                mbar_expect_tx(BAR_ONE(sb, EV_WIN + i), 8192);
                tma_load(sb + 5 * SLOT + i * 8192, &mp.wm8, 2 * i * 6144 + (m * 8 + j) * 16, 0, BAR_ONE(sb, EV_WIN + i));
                tma_load(sb + 5 * SLOT + i * 8192 + 4096, &mp.wm8, (2 * i + 1) * 6144 + (m * 8 + j) * 16, 0, BAR_ONE(sb, EV_WIN + i));
            }
        }
        __syncwarp();
        asm volatile("setmaxnreg.dec.sync.aligned.u32 56;");
        if (elect_one()) {
            if (warp == 8) {
                prefetch_map(&mp.wqkv); prefetch_map(&mp.wmod);
            } else if (warp < 11) {
                mbar_init(BAR_EMPTY(sb, NSLOT), 1);
#pragma unroll
                for (int i = 0; i < 2; ++i) { mbar_init(BAR_SFULL(sb, (warp - 9) * 2 + i), 4); if (aux) mbar_init(BAR_SREADY(sb, (warp - 9) * 2 + i), 1); }
#pragma unroll
                for (int i = 0; i < 3; ++i) {
                    mbar_init(BAR_EMPTY(sb, (warp - 9) * 3 + i), 4);
                    mbar_init(BAR_FULL(sb, (warp - 9) * 3 + i), 1); mbar_init(BAR_FULL(sb, (warp - 9) * 3 + i) + AF_REL, 1);
                }
            } else {
#pragma unroll
                for (int i = EV_P0; i < EV_COUNT; ++i) mbar_init(BAR_ONE(sb, i), i == EV_P0 ? 8 : 1);
            }
            asm volatile("fence.mbarrier_init.release.cluster;" ::: "memory");
        }
        __syncwarp();
        cluster_arrive();
        ep = 0;
        if (warp != 8 || aux) ep = flag_get(g_flags + FL_DONE);
        cluster_wait();
        ep = __shfl_sync(0xffffffffu, ep, 0) / NCTA + 1;
        if (warp == 8) {
            const bool el = elect_one();
            Ring r{0, 1};
            if (aux) {
                {
                    uint32_t n = 0;
                    while (!__all_sync(0xffffffffu, ld_pkt16(pt.mail->mod1 + 256).z == ep)) { SPIN_GUARD(n); __nanosleep(200); }
                }
#pragma unroll 1
                for (int it = 0; it < 64; ++it) {
                    const int col = 2048 + (it >> 4) * 1024 + j * 256;
                    mbar_wait(BAR_EMPTY(sb, r.slot), r.par);
                    const uint32_t st = sb + r.slot * SLOT, fb = BAR_FULL(sb, r.slot);
                    if (el) {
                        mbar_expect_tx(fb, 32768);
#pragma unroll
                        for (int b = 0; b < 4; ++b) tma_load(st + b * 8192, &mp.wmod, col + b * 64, (it & 15) * 64, fb);
                    }
                    r.next();
                }
                mbar_wait(BAR_ONE(sb, EV_P0), 0);
                const CUtensorMap* wm = rank ? &mp.wu : &mp.wg;
#pragma unroll 1
                for (int g = 0; g < 128; ++g) {
                    const int mx = (j >> 1) * 8 + (g >> 5) * 2 + rank, k0 = ((g & 14) << 6) + ((g & 16) << 2) + ((g & 1) << 5);
                    if (!(g & 15)) {
                        uint32_t n = 0;
                        while (!__all_sync(0xffffffffu, (int32_t)(flag_get(g_flags + FL_PROG + fidx(mx, lane >> 4, (lane & 14) | ((g >> 4) & 1))) - (ep * 8 + ST_H2)) >= 0)) { SPIN_GUARD(n); __nanosleep(300); }
                    }
                    mbar_wait(BAR_EMPTY(sb, r.slot), r.par);
                    const uint32_t st = sb + r.slot * SLOT, fb = BAR_FULL(sb, r.slot);
                    if (el) {
                        mbar_expect_tx(fb, 24576);
                        tma_load_mc(st + 8192 + rank * 4096, wm, HC3, k0, fb);
                        tma_load_mc(st + 16384 + rank * 4096, wm, HC3 + 64, k0, fb);
                        tma_load(st, &mp.h2l, k0, mx * 128, fb);
                    }
                    r.next();
                }
            } else {
#pragma unroll 1
                for (int it = 0; it < 32; ++it) {
                    const int cb = j * 128 + rank * 64, k0 = kof(it, 2, j);
                    if (it == BW0) mbar_wait(BAR_ONE(sb, BWEV), 0);
                    if (it == BW1) mbar_wait(BAR_ONE(sb, EV_PAR), 0);
                    if (it == 5) mbar_wait(BAR_ONE(sb, EV_P0), 0);
                    if (it == AG0) mbar_wait(BAR_ONE(sb, (AGW & 1) ? EV_AGO : EV_FGO), 0);
                    mbar_wait(BAR_EMPTY(sb, r.slot), r.par);
                    const uint32_t st = sb + r.slot * SLOT, fb = BAR_FULL(sb, r.slot);
                    if (el) {
                        mbar_expect_tx(fb, it < 4 ? 24576 : 28672);
                        tma_load_mc(st + 8192 + rank * 4096, &mp.wqkv, 1024 + cb, k0, fb);
                        tma_load_mc(st + 16384 + rank * 4096, &mp.wqkv, 2048 + cb, k0, fb);
                        tma_load_mc(st + 24576 + rank * 4096, &mp.wqkv, cb, k0, fb);
                        if (it < 4) mbar_arrive(fb + AF_REL);
                        if (it == PFWO + (m >> 1)) { tma_prefetch(&mp.wo, j * 128, m * 64); tma_prefetch(&mp.wo, j * 128 + 64, m * 64); }
                        if (it >= PFG && it < PFG + PFN && (it & 7) == grp) {
                            const int kp = kof(it - PFG + PFO, 2, j);
                            tma_prefetch(rank ? &mp.wu : &mp.wg, hcol(0, j), kp); tma_prefetch(rank ? &mp.wu : &mp.wg, hcol(0, j) + 64, kp);
                            asm volatile("cp.async.bulk.prefetch.tensor.3d.L2.global [%0, {%1, %2, %3}];" :: "l"(rank ? &mp.wu3 : &mp.wg3), "r"(0), "r"(j), "r"(kp) : "memory");
                        }
                    }
                    r.next();
                }
                if (el) mbar_arrive(BAR_ONE(sb, EV_KV));
#pragma unroll 1
                for (int it = 0; it < 16; ++it) {
                    const int k0 = kof(it, 1, j);
                    if (it == AG1) mbar_wait(BAR_ONE(sb, (AGW & 2) ? EV_AGO1 : EV_FGO1), 0);
                    mbar_wait(BAR_EMPTY(sb, r.slot), r.par);
                    const uint32_t st = sb + r.slot * SLOT, fb = BAR_FULL(sb, r.slot);
                    if (el) {
                        mbar_expect_tx(fb, it < 2 ? 32768 : 24576);
                        tma_load_mc(st + 16384 + rank * 8192, &mp.wo, j * 128 + rank * 64, k0, fb);
                        if (it < 2) {
                            tma_load3(st, &mp.x, j * 128, m * 64 + it * 32, fb); tma_load3(st + 8192, &mp.x, j * 128 + 64, m * 64 + it * 32, fb);
                            mbar_arrive(fb + AF_REL);
                        }
                        if (it == 6) { prefetch_map(rank ? &mp.wu : &mp.wg); prefetch_map(rank ? &mp.wu3 : &mp.wg3); }
                    }
                    r.next();
                }
                const CUtensorMap* wm = rank ? &mp.wu : &mp.wg;
#pragma unroll 1
                for (int g = 0; g < 96; ++g) {
                    if (g == AG2) mbar_wait(BAR_ONE(sb, (AGW & 4) ? EV_AGO2 : EV_FGO2), 0);
                    const int p = g >> 5, cb = hcol(p, j), k0 = p == 0 ? kof(g, 2, j) : (g & 31) * 32;
                    mbar_wait(BAR_EMPTY(sb, r.slot), r.par);
                    const uint32_t st = sb + r.slot * SLOT, fb = BAR_FULL(sb, r.slot);
                    if (el) {
                        mbar_expect_tx(fb, (g < 4 || p > 0) ? 24576 : 28672);
                        tma_load_mc(st + 8192 + rank * 4096, wm, cb, k0, fb);
                        tma_load_mc(st + 16384 + rank * 4096, wm, cb + 64, k0, fb);
                        if (p == 0) tma_load3_mc(st + 24576 + rank * 4096, rank ? &mp.wu3 : &mp.wg3, j, k0, fb);
                        else tma_load(st, &mp.h2l, k0, m * 128, fb);
                        if (g < 4) mbar_arrive(fb + AF_REL);
                        if (g == 60) prefetch_map(&mp.wd);
                    }
                    r.next();
                }
#pragma unroll 1
                for (int g = 0; g < 56; ++g) {
                    if (g == 0 || (g & 15) == 6 && g > 6) mbar_wait(BAR_ONE(sb, EV_H0 + (g >> 4)), 0);
                    const int k0 = g * 64;
                    mbar_wait(BAR_EMPTY(sb, r.slot), r.par);
                    const uint32_t st = sb + r.slot * SLOT, fb = BAR_FULL(sb, r.slot);
                    if (el) {
                        mbar_expect_tx(fb, 32768);
                        tma_load_mc(st + 16384 + rank * 8192, &mp.wd, j * 128 + rank * 64, k0, fb);
                        tma_load(st, &mp.hb, k0, m * 128, fb); tma_load(st + 8192, &mp.hb, k0, m * 128 + 64, fb);
                    }
                    r.next();
                }
            }
        } else if (aux) {
            if (warp < 11) {
                const uint32_t w = warp - 9;
                const bool el = elect_one();
#pragma unroll 1
                for (int p = 0; p < 4; ++p) {
                    const int mx = (j >> 1) * 8 + p * 2 + rank;
                    if (el) { mbar_arrive(BAR_SREADY(sb, w * 2)); mbar_arrive(BAR_SREADY(sb, w * 2 + 1)); }
                    mbar_wait2(BAR_SFULL(sb, w * 2), BAR_SFULL(sb, w * 2 + 1), p & 1);
                    if (p < 3) pause(HD0);
                    if (el) tma_store(&mp.hb, HC3, mx * 128 + w * 64, sb + OFF_STG + w * 16384);
                    if (p < 3) pause(HP);
                    if (el) {
                        tma_store(&mp.hb, HC3 + 64, mx * 128 + w * 64, sb + OFF_STG + w * 16384 + 8192);
                        bulk_commit(); bulk_wait_fence(); flag_set(g_flags + FL_AUX + mx * 2 + w, ep * 8 + ST_H + 3);
                    }
                }
            }
        } else if (warp == 11) {
            const bool el = elect_one();
            const int row0 = m * 128;
            const uint32_t* const fl = g_flags + FL_PROG + fidx(m, lane >> 4, kof(lane & 15, 1, j) >> 6);
            if (el) { prefetch_map(&mp.h1h); prefetch_map(&mp.h2h); prefetch_map(&mp.h2l); }
            auto gate = [&](int vec, int ev) {
                uint4 v; uint32_t n = 0;
                while (true) {
                    v = ld_pkt2(g_mod + vec * 512 + j * 64 + lane * 2);
                    if (__all_sync(0xffffffffu, v.y == ep && v.w == ep)) break;
                    SPIN_GUARD(n); __nanosleep(300);
                }
                asm volatile("st.shared.v2.u32 [%0], {%1, %2};" :: "r"(sb + OFF_TAB + (ev - EV_GA) * 256 + lane * 8), "r"(v.x), "r"(v.z) : "memory");
                __syncwarp();
                if (lane == 0) mbar_arrive(BAR_ONE(sb, ev));
            };
            {
                const uint4* pk = pt.mail->mod1 + grp * 512 + j * 32 + lane;
                uint4 a, b; uint32_t n = 0;
                mbar_wait(BAR_ONE(sb, EV_WIN3), 0);
                while (true) {
                    a = ld_pkt16(pk); b = ld_pkt16(pk + 256);
                    if (__all_sync(0xffffffffu, a.z == ep && b.z == ep)) break;
                    SPIN_GUARD(n);
                }
                sts128(sb + OFF_PAR + lane * 16, a.x, a.y, b.x, b.y);
                __syncwarp();
                if (lane == 0) { mbar_arrive(BAR_ONE(sb, EV_PAR)); TL(46); }
            }
            mbar_wait(BAR_ONE(sb, EV_P0), 0);
            Ring r{0, 1};
#pragma unroll 1
            for (int ph = 0; ph < 3; ++ph) {
                const int sh = ph == 1 ? 1 : 2, nst = 8 << sh;
                const uint32_t half = 16384 >> sh, target = ep * 8 + ST_H1 + ph;
                const CUtensorMap* tm = ph == 0 ? &mp.h1h : ph == 1 ? &mp.o : &mp.h2h;
                if (ph == 1) gate(2, EV_GA);
                if (ph == 2) {
                    uint32_t n = 0;
                    while ((int32_t)(flag_get(g_flags + FL_LN2) - ep * 8) < 0) { SPIN_GUARD(n); __nanosleep(200); }
                    const uint4 v = __ldcg((const uint4*)(g_par2 + j * 128) + lane);
                    sts128(sb + OFF_PAR + lane * 16, v.x, v.y, v.z, v.w);
                    __syncwarp();
                    if (lane == 0) mbar_arrive(BAR_ONE(sb, EV_LN2));
                }
                const uint32_t lw = ~lane & 1, lt = lane >> 1, ls = (r.slot + lt) % NSLOT, lk = kof(lt, sh, j), lb = BAR_FULL(sb, ls) + (lw ? 0 : AF_REL);
                const uint32_t* const lf = g_flags + FL_PROG + fidx(m, lw, lk >> 6);
                int fr = 1 << sh;
                uint32_t todo = 0x3ffffu >> (2 * fr) << (2 * fr), have = ~todo, n = 0, v = 0;
                r.skip(fr);
#pragma unroll 1
                for (; fr < NSLOT; ++fr) { mbar_wait(BAR_EMPTY(sb, r.slot), r.par); r.next(); }
                if (PWAIT) mbar_wait(BAR_SFULL(sb, 2), ph & 1);
                if (PWAIT > 1) spin(PWAIT);
                if (ph == XST - 1) CS(33);
                do {
                    if (!PMASK || !((have >> lane) & 1)) v = flag_get(lf);
                    if (!LATET) while (fr < 9 && mbar_test(BAR_EMPTY(sb, r.slot), r.par)) { ++fr; r.next(); if (!MULTI) break; }
                    SPIN_GUARD(n);
                    have |= __ballot_sync(0xffffffffu, (int32_t)(v - target) >= 0);
                    if (LATET) while (fr < 9 && mbar_test(BAR_EMPTY(sb, r.slot), r.par)) { ++fr; r.next(); }
                    const uint32_t go = have & todo & ((1u << (2 * fr)) - 1);
                    if ((go >> lane) & 1) {
                        if (!lw) mbar_expect_tx(lb, half);
                        tma_load(sb + ls * SLOT + lw * half, tm, lk, row0 + lw * 64, lb);
                    }
                    __syncwarp();
                    if (lane < 2 && (todo & (0x555u << lane)) && !(todo & ~go & (0x555u << lane))) mbar_arrive(BAR_ONE(sb, (lane ? EV_FGO : EV_AGO) + ph));
                    if (ph == XST - 1) { if (go & (1u << (2 << sh))) CS(34); if (go & (2u << (2 << sh))) CS(35); if (todo & 0x555u) CS(36); if (todo & 0xaaau) CS(37); }
                    todo &= ~go;
                } while (~have);
                if (ph == XST - 1) CS(38);
                int k = kof(fr, sh, j);
#pragma unroll 1
                for (; fr < nst; ++fr) {
                    if (fr == 9 || fr == 18) {
                        const uint32_t skip = fr == 9 << (sh - 1) ? 0 : ~0x01fc01fcu;
                        while (~(__ballot_sync(0xffffffffu, (int32_t)(flag_get(fl) - target) >= 0) | skip)) SPIN_GUARD(n);
                    }
                    const uint32_t st = sb + r.slot * SLOT, fb = BAR_FULL(sb, r.slot);
                    mbar_wait(BAR_EMPTY(sb, r.slot), r.par);
                    if (el) {
                        tma_load(st + half, tm, k, row0 + 64, fb);
                        mbar_expect_tx(fb + AF_REL, half);
                        tma_load(st, tm, k, row0, fb + AF_REL);
                    }
                    if (ph == XST - 1 && fr == 9) CS(39);
                    r.next();
                    k = kof(fr + 1, sh, j);
                }
            }
#pragma unroll 1
            for (int p = 0; p < 4; ++p) {
                const uint32_t* f = p < 3 ? fl : g_flags + FL_AUX + m * 2 + (lane & 1);
                uint32_t n = 0;
                while (!__all_sync(0xffffffffu, (int32_t)(flag_get(f) - (ep * 8 + ST_H + p)) >= 0)) { SPIN_GUARD(n); __nanosleep(300); }
                if (el) mbar_arrive(BAR_ONE(sb, EV_H0 + p));
                if (p == 0) gate(5, EV_GB);
            }
        } else {
            const uint32_t w = warp - 9;
            const int row0 = m * 128 + w * 64;
            const uint32_t stg = sb + OFF_STG + w * 16384;
            uint32_t* const fl = g_flags + FL_PROG + fidx(m, w, 2 * j);
            uint32_t b = 0, par = 0;
            const bool el = elect_one();
            auto store = [&](const CUtensorMap* tm, int col, bool nat = false) {
                mbar_wait(BAR_SFULL(sb, w * 2 + b), (par >> b) & 1);
                par ^= 1u << b;
                if (el) {
                    if (nat) tma_store3(tm, col, row0 >> 1, 0, stg + b * 8192); else tma_store(tm, col, row0, stg + b * 8192);
                    bulk_commit();
                }
                b ^= 1;
            };
            auto send2 = [&](const CUtensorMap* tm, const uint32_t* buf, int step) {
                const uint32_t* const q = buf + (size_t)((row0 + lane) * (D_ / 2) + j * 64 + 31);
                store(tm, j * 128);
                if (step == XST) CS(33);
                uint32_t z = landed(el, q, D_ / 2, pt.zero, (SKIPRB >> (2 * (step - ST_H1))) & 1);
                if (el) flag_set(fl, ep * 8 + step + z);
                if (step == XST) CS(34);
                if (step != ST_O) { mbar_wait(BAR_ONE(sb, EV_FGO + step - ST_H1), 0); pause(w ? P1H : P1H + 1000); }
                else if (OFGO && w == 0) mbar_wait(BAR_ONE(sb, EV_FGO1), 0);
                store(tm, j * 128 + 64);
                if (step == XST) CS(35);
                z = landed(el, q + 32, D_ / 2, pt.zero, (SKIPRB >> (2 * (step - ST_H1) + 1)) & 1);
                if (el) flag_set(fl + 1, ep * 8 + step + z);
                if (step == XST) CS(36);
            };
            auto free2 = [&]() { if (el) { mbar_arrive(BAR_SREADY(sb, w * 2)); mbar_arrive(BAR_SREADY(sb, w * 2 + 1)); } };
            if (el) { prefetch_map(&mp.h1s); prefetch_map(&mp.o); prefetch_map(&mp.h2s); prefetch_map(&mp.hb); prefetch_map(&mp.out); prefetch_map(&mp.wo); }
            if (el) { flag_set(fl, ep * 8); flag_set(fl + 1, ep * 8); }
            send2(&mp.h1s, pt.h1, ST_H1);
            if (w == 0) TL(47);
            free2();
            fetch_halo(g_halo + ((m - 1) * 8 + j) * 512 + w * 256 + lane, m == 0, sb, 2 * w, lane);
            send2(&mp.o, pt.o, ST_O);
            if (w == 0) TL(40); else TL(38);
            free2();
            send2(&mp.h2s, pt.o, ST_H2);
            if (el) { prefetch_map(&mp.hb); prefetch_map(&mp.hb3); }
            if (w == 0) TL(37);
            free2();
#pragma unroll 1
            for (int p = 0; p < 3; ++p) {
                const int col = hcol(p, j);
                mbar_wait(BAR_SFULL(sb, w * 2), par & 1);
                pause(w ? HD1 : HD0); store(&mp.hb, col);
                pause(HP); store(&mp.hb, col + 64);
                if (p == 0) {
                    pause(HP);
                    if (el) { tma_store3(&mp.hb3, 0, j, row0, sb + (w ? P3_SLOT1 : P3_SLOT0) * SLOT + 24576); bulk_commit(); }
                }
                if (el) bulk_wait_read();
                free2();
                if (el) { bulk_wait_fence(); flag_set(fl, ep * 8 + ST_H + p); flag_set(fl + 1, ep * 8 + ST_H + p); }
            }
            cluster_arrive_early = true;
            cluster_arrive();
            store(&mp.out, j * 128, true); store(&mp.out, j * 128 + 64, true);
            if (el) bulk_wait_read();
        }
        __syncwarp();
    }
    if (aux || (wg == 2 && !cluster_arrive_early)) cluster_arrive();
    cluster_wait();
    CS(32);
    if (KDEBUG == 5) __syncthreads();
    if (tid == 0) {
        TL(15);
        flag_add(pt.mail->flags + FL_DONE);
    }
}

typedef CUresult (*EncodeFn)(CUtensorMap*, CUtensorMapDataType, cuuint32_t, void*, const cuuint64_t*, const cuuint64_t*, const cuuint32_t*,
                             const cuuint32_t*, CUtensorMapInterleave, CUtensorMapSwizzle, CUtensorMapL2promotion, CUtensorMapFloatOOBfill);

void make_map(EncodeFn fn, CUtensorMap* m, const void* ptr, uint64_t rows, uint64_t cols, uint32_t brows, uint32_t bcols) {
    cuuint64_t dims[2] = {cols, rows}, strides[1] = {cols * 2};
    cuuint32_t box[2] = {bcols, brows}, es[2] = {1, 1};
    fn(m, CU_TENSOR_MAP_DATA_TYPE_BFLOAT16, 2, (void*)ptr, dims, strides, box, es, CU_TENSOR_MAP_INTERLEAVE_NONE,
       bcols == 64 ? CU_TENSOR_MAP_SWIZZLE_128B : bcols == 32 ? CU_TENSOR_MAP_SWIZZLE_64B : CU_TENSOR_MAP_SWIZZLE_NONE, CU_TENSOR_MAP_L2_PROMOTION_L2_256B, CU_TENSOR_MAP_FLOAT_OOB_FILL_NONE);
}

void make_map3(EncodeFn fn, CUtensorMap* m, const void* ptr) {
    cuuint64_t dims[3] = {D_, S_ / 2, 2}, strides[2] = {4 * D_, 2 * D_};
    cuuint32_t box[3] = {64, 32, 2}, es[3] = {1, 1, 1};
    fn(m, CU_TENSOR_MAP_DATA_TYPE_BFLOAT16, 3, (void*)ptr, dims, strides, box, es, CU_TENSOR_MAP_INTERLEAVE_NONE,
       CU_TENSOR_MAP_SWIZZLE_128B, CU_TENSOR_MAP_L2_PROMOTION_L2_256B, CU_TENSOR_MAP_FLOAT_OOB_FILL_NONE);
}

void make_map48(EncodeFn fn, CUtensorMap* m, const void* ptr, uint64_t rows, uint32_t brows) {
    cuuint64_t dims[3] = {48, 8, rows}, strides[2] = {96, 2 * F_};
    cuuint32_t box[3] = {64, 1, brows}, es[3] = {1, 1, 1};
    fn(m, CU_TENSOR_MAP_DATA_TYPE_BFLOAT16, 3, (void*)ptr, dims, strides, box, es, CU_TENSOR_MAP_INTERLEAVE_NONE,
       CU_TENSOR_MAP_SWIZZLE_128B, CU_TENSOR_MAP_L2_PROMOTION_L2_256B, CU_TENSOR_MAP_FLOAT_OOB_FILL_NONE);
}

}

extern "C" void kernel_launch(void* const* d_in, const int* in_sizes, int n_in, void* d_out, int out_size) {
    (void)in_sizes; (void)n_in; (void)out_size;
    void* fnp = nullptr;
    cudaDriverEntryPointQueryResult qr;
    cudaGetDriverEntryPoint("cuTensorMapEncodeTiled", &fnp, cudaEnableDefault, &qr);
    EncodeFn fn = (EncodeFn)fnp;
    void *h1, *o, *h2, *hb, *mail;
    cudaGetSymbolAddress(&h1, g_h1);
    cudaGetSymbolAddress(&mail, g_mail);
    cudaGetSymbolAddress(&o, g_o);
    cudaGetSymbolAddress(&hb, g_hb);
    h2 = o;
    Maps mp;
    make_map(fn, &mp.h1h, h1, S_, D_, 64, 32);
    make_map(fn, &mp.h2h, h2, S_, D_, 64, 32);
    make_map(fn, &mp.h1s, h1, S_, D_, 64, 64);
    make_map(fn, &mp.o, o, S_, D_, 64, 64);
    make_map(fn, &mp.h2l, h2, S_, D_, 128, 32);
    make_map(fn, &mp.h2s, h2, S_, D_, 64, 64);
    make_map(fn, &mp.hb, hb, S_, F_, 64, 64);
    make_map(fn, &mp.wqkv, d_in[1], D_, 3 * D_, 32, 64);
    make_map(fn, &mp.wo, d_in[2], D_, D_, 64, 64);
    make_map(fn, &mp.wg, d_in[4], D_, F_, 32, 64);
    make_map(fn, &mp.wu, d_in[5], D_, F_, 32, 64);
    make_map(fn, &mp.wd, d_in[6], F_, D_, 64, 64);
    make_map(fn, &mp.wmod, d_in[8], D_, 6 * D_, 64, 64);
    make_map(fn, &mp.wm8, d_in[8], D_ / 8, 8 * 6 * D_, 128, 16);
    make_map3(fn, &mp.x, d_in[0]);
    make_map3(fn, &mp.out, d_out);
    make_map48(fn, &mp.wg3, d_in[4], D_, 32);
    make_map48(fn, &mp.wu3, d_in[5], D_, 32);
    make_map48(fn, &mp.hb3, hb, S_, 64);
    cudaFuncSetAttribute(fused_block_kernel, cudaFuncAttributeMaxDynamicSharedMemorySize, SMEM_BYTES);
    cudaLaunchConfig_t cfg = {};
    cfg.gridDim = dim3(NCTA); cfg.blockDim = dim3(384); cfg.dynamicSmemBytes = SMEM_BYTES; cfg.stream = cudaStreamPerThread;
    cudaLaunchAttribute at[1];
    at[0].id = cudaLaunchAttributeClusterDimension; at[0].val.clusterDim.x = 2; at[0].val.clusterDim.y = 1; at[0].val.clusterDim.z = 1;
    cfg.attrs = at; cfg.numAttrs = 1;
    const Ptrs pt{(const __nv_bfloat16*)d_in[7], (Mail*)mail, (const uint32_t*)h1, (const uint32_t*)o, 0};
    cudaLaunchKernelEx(&cfg, fused_block_kernel, pt, mp);
}
```

```cpp
#include <cuda_runtime.h>
#include <cuda_bf16.h>
#include <cuda.h>
#include <stdint.h>
#include <stddef.h>

#define LAG 4
#define LAGS 4
#define LAGW 3
#define LAGQ 4
#define MIDW 2
#define PFWO 12
#define P1H 4000
#define AGW 6
#define CSW 0
#define LWAIT 2
#define BW0 0
#define BWEV EV_WIN
#define BW1 3
#define PDLY 500
#define HD1 5500
#define HD0 5500
#define HP 2200
#define LAGD 4
#define MIDD 44
#define XST ST_O
#define AG0 6
#define AG1 6
#define AG2 8
#define PFG 20
#define PFN 12
#define PFO 0
#define KDEBUG 0

namespace {

constexpr int S_ = 2048, D_ = 1024, F_ = 3584;
constexpr int NCTA = 132;
constexpr int NSLOT = 6;
constexpr uint32_t SLOT = 32768;
constexpr uint32_t OFF_STG = NSLOT * SLOT;
constexpr uint32_t OFF_BAR = OFF_STG + 32768;
constexpr uint32_t OFF_PAR = OFF_BAR + 512;
constexpr uint32_t OFF_TAB = OFF_PAR + 768;
constexpr uint32_t OFF_TL = OFF_PAR + 2048;
constexpr uint32_t SMEM_BYTES = OFF_TL + (KDEBUG ? 512 : 0);
constexpr uint32_t P3_SLOT1 = (32 + 16 + 32) % NSLOT, P3_SLOT0 = (P3_SLOT1 + 1) % NSLOT;

constexpr int ST_H1 = 1, ST_O = 2, ST_H2 = 3, ST_H = 4, FL_DONE = 0, FL_LN2 = 1, FL_AUX = 32, FL_PROG = 64;

struct Maps {
    CUtensorMap h1h, h1s, o, h2h, h2l, h2s, hb, wqkv, wo, wg, wu, wd, wmod, wm8, x, out, wg3, wu3, hb3;
};

struct Mail {
    uint32_t flags[16 * 32 + 64];
    uint2 mod[6 * D_ / 2];
    uint4 mod1[8 * 512];
    uint4 st1[128 * 512];
    uint32_t par2[D_];
    uint4 halo[128 * 512];
};
struct Ptrs { const __nv_bfloat16* c; Mail* mail; const uint32_t *h1, *o; uint32_t zero; };

__device__ __align__(128) Mail g_mail;
__device__ __align__(128) __nv_bfloat16 g_h1[S_ * D_];
__device__ __align__(128) __nv_bfloat16 g_o[S_ * D_];
__device__ __align__(128) __nv_bfloat16 g_hb[S_ * F_];
#define TL(i) do {} while (0)
#define TC(i) do {} while (0)
#define TS(g, which) do {} while (0)
#define CS(i) do {} while (0)

__device__ __forceinline__ uint32_t smem_u32(const void* p) { return (uint32_t)__cvta_generic_to_shared(p); }
__device__ __forceinline__ void mbar_init(uint32_t bar, uint32_t cnt) { asm volatile("mbarrier.init.shared::cta.b64 [%0], %1;" :: "r"(bar), "r"(cnt) : "memory"); }
__device__ __forceinline__ void mbar_expect_tx(uint32_t bar, uint32_t bytes) { asm volatile("mbarrier.arrive.expect_tx.shared::cta.b64 _, [%0], %1;" :: "r"(bar), "r"(bytes) : "memory"); }
__device__ __forceinline__ void mbar_arrive(uint32_t bar) { asm volatile("mbarrier.arrive.shared::cta.b64 _, [%0];" :: "r"(bar) : "memory"); }
__device__ __forceinline__ void mbar_arrive_cta(uint32_t bar, uint32_t cta) {
    asm volatile("{\n.reg .b32 r;\nmapa.shared::cluster.u32 r, %0, %1;\nmbarrier.arrive.shared::cluster.b64 _, [r];\n}" :: "r"(bar), "r"(cta) : "memory");
}
__device__ __forceinline__ void mbar_wait(uint32_t bar, uint32_t parity) {
    asm volatile("{\n.reg .pred p;\n.reg .u32 n;\nmov.u32 n, 0;\n"
        "W_LOOP:\nmbarrier.try_wait.parity.shared::cta.b64 p, [%0], %1;\n@p bra W_DONE;\n"
        "add.u32 n, n, 1;\nsetp.lt.u32 p, n, 0x400000;\n@p bra W_LOOP;\ntrap;\nW_DONE:\n}" :: "r"(bar), "r"(parity) : "memory");
}
__device__ __forceinline__ void mbar_wait2(uint32_t b0, uint32_t b1, uint32_t parity) {
    asm volatile("{\n.reg .pred p, q;\n.reg .u32 n;\nmov.u32 n, 0;\n"
        "W_LOOP:\nmbarrier.try_wait.parity.shared::cta.b64 p, [%0], %2;\nmbarrier.try_wait.parity.shared::cta.b64 q, [%1], %2;\nand.pred p, p, q;\n@p bra W_DONE;\n"
        "add.u32 n, n, 1;\nsetp.lt.u32 p, n, 0x400000;\n@p bra W_LOOP;\ntrap;\nW_DONE:\n}" :: "r"(b0), "r"(b1), "r"(parity) : "memory");
}
__device__ __forceinline__ bool mbar_test(uint32_t bar, uint32_t parity) {
    uint32_t r; asm volatile("{\n.reg .pred p;\nmbarrier.test_wait.parity.shared::cta.b64 p, [%1], %2;\nselp.u32 %0, 1, 0, p;\n}" : "=r"(r) : "r"(bar), "r"(parity) : "memory"); return r;
}
__device__ __forceinline__ bool mbar_test2(uint32_t b0, uint32_t b1, uint32_t parity) {
    uint32_t r;
    asm volatile("{\n.reg .pred p, q;\nmbarrier.test_wait.parity.shared::cta.b64 p, [%1], %3;\nmbarrier.test_wait.parity.shared::cta.b64 q, [%2], %3;\n"
        "and.pred p, p, q;\nselp.u32 %0, 1, 0, p;\n}" : "=r"(r) : "r"(b0), "r"(b1), "r"(parity) : "memory");
    return r;
}
__device__ __forceinline__ void tma_load3(uint32_t dst, const CUtensorMap* m, int c0, int c1, uint32_t bar) {
    asm volatile("cp.async.bulk.tensor.3d.shared::cluster.global.mbarrier::complete_tx::bytes [%0], [%1, {%3, %4, %5}], [%2];"
        :: "r"(dst), "l"(m), "r"(bar), "r"(c0), "r"(c1), "r"(0) : "memory");
}
__device__ __forceinline__ void tma_store3(const CUtensorMap* m, int c0, int c1, int c2, uint32_t src) {
    asm volatile("cp.async.bulk.tensor.3d.global.shared::cta.bulk_group [%0, {%2, %3, %4}], [%1];" :: "l"(m), "r"(src), "r"(c0), "r"(c1), "r"(c2) : "memory");
}
__device__ __forceinline__ void tma_load3_mc(uint32_t dst, const CUtensorMap* m, int c1, int c2, uint32_t bar) {
    asm volatile("cp.async.bulk.tensor.3d.shared::cluster.global.mbarrier::complete_tx::bytes.multicast::cluster.L2::cache_hint [%0], [%1, {%3, %4, %5}], [%2], %6, %7;"
        :: "r"(dst), "l"(m), "r"(bar), "r"(0), "r"(c1), "r"(c2), "h"((uint16_t)3), "l"(0x12F0000000000000ull) : "memory");
}
__device__ __forceinline__ void tma_load(uint32_t dst, const CUtensorMap* m, int c0, int c1, uint32_t bar) {
    asm volatile("cp.async.bulk.tensor.2d.shared::cluster.global.mbarrier::complete_tx::bytes [%0], [%1, {%3, %4}], [%2];"
        :: "r"(dst), "l"(m), "r"(bar), "r"(c0), "r"(c1) : "memory");
}
__device__ __forceinline__ void tma_load_mc(uint32_t dst, const CUtensorMap* m, int c0, int c1, uint32_t bar) {
    asm volatile("cp.async.bulk.tensor.2d.shared::cluster.global.mbarrier::complete_tx::bytes.multicast::cluster.L2::cache_hint [%0], [%1, {%3, %4}], [%2], %5, %6;"
        :: "r"(dst), "l"(m), "r"(bar), "r"(c0), "r"(c1), "h"((uint16_t)3), "l"(0x12F0000000000000ull) : "memory");
}
__device__ __forceinline__ void tma_prefetch(const CUtensorMap* m, int c0, int c1) {
    asm volatile("cp.async.bulk.prefetch.tensor.2d.L2.global [%0, {%1, %2}];" :: "l"(m), "r"(c0), "r"(c1) : "memory");
}
__device__ __forceinline__ void tma_store(const CUtensorMap* m, int c0, int c1, uint32_t src) {
    asm volatile("cp.async.bulk.tensor.2d.global.shared::cta.bulk_group [%0, {%2, %3}], [%1];" :: "l"(m), "r"(src), "r"(c0), "r"(c1) : "memory");
}
__device__ __forceinline__ void bulk_commit() { asm volatile("cp.async.bulk.commit_group;" ::: "memory"); }
__device__ __forceinline__ void bulk_wait_read() { asm volatile("cp.async.bulk.wait_group.read 0;" ::: "memory"); }
__device__ __forceinline__ void fence_async_smem() { asm volatile("fence.proxy.async.shared::cta;" ::: "memory"); }
__device__ __forceinline__ void prefetch_map(const CUtensorMap* m) { asm volatile("prefetch.tensormap [%0];" :: "l"(m) : "memory"); }
__device__ __forceinline__ void wg_fence() { asm volatile("wgmma.fence.sync.aligned;" ::: "memory"); }
__device__ __forceinline__ void wg_commit() { asm volatile("wgmma.commit_group.sync.aligned;" ::: "memory"); }
template <int N> __device__ __forceinline__ void wg_wait() { asm volatile("wgmma.wait_group.sync.aligned %0;" :: "n"(N) : "memory"); }
__device__ __forceinline__ void bar_sync(int id, int n) { asm volatile("bar.sync %0, %1;" :: "r"(id), "r"(n) : "memory"); }
__device__ __forceinline__ void bar_arrive(int id, int n) { asm volatile("bar.arrive %0, %1;" :: "r"(id), "r"(n) : "memory"); }
__device__ __forceinline__ void flag_add(uint32_t* f) { asm volatile("red.relaxed.gpu.global.add.u32 [%0], 1;" :: "l"(f) : "memory"); }
__device__ __forceinline__ void flag_set(uint32_t* f, uint32_t v) { asm volatile("red.relaxed.gpu.global.max.u32 [%0], %1;" :: "l"(f), "r"(v) : "memory"); }
__device__ __forceinline__ uint32_t flag_get(const uint32_t* f) { uint32_t v; asm volatile("ld.relaxed.gpu.global.u32 %0, [%1];" : "=r"(v) : "l"(f) : "memory"); return v; }
__device__ __forceinline__ void bulk_wait_fence() { asm volatile("cp.async.bulk.wait_group 0;\nfence.proxy.async.global;\nfence.acq_rel.gpu;" ::: "memory"); }
__device__ __forceinline__ uint32_t landed(bool el, const uint32_t* p, uint32_t pitch, uint32_t zero) {
    if (el) asm volatile("cp.async.bulk.wait_group 0;" ::: "memory");
    __syncwarp();
    const uint32_t a = flag_get(p), b = flag_get(p + 32 * pitch);
    return __reduce_or_sync(0xffffffffu, (a | b) & zero);
}
__device__ __forceinline__ uint32_t d16(uint32_t addr) { return (addr & 0x3FFFF) >> 4; }
__device__ __forceinline__ uint64_t mk_desc(uint32_t a16, uint32_t off, uint32_t lbo, uint32_t sbo, uint32_t swz) {
    const uint32_t lo = a16 + (off >> 4) + ((lbo >> 4) << 16), hi = (sbo >> 4) | (swz << 30);
    return ((uint64_t)hi << 32) | lo;
}
__device__ __forceinline__ uint32_t pack2(float lo, float hi) {
    uint32_t r; asm("cvt.rn.bf16x2.f32 %0, %1, %2;" : "=r"(r) : "f"(hi), "f"(lo)); return r;
}
__device__ __forceinline__ uint32_t hfma2_bf16(uint32_t a, uint32_t b, uint32_t c) {
    uint32_t r; asm("fma.rn.bf16x2 %0, %1, %2, %3;" : "=r"(r) : "r"(a), "r"(b), "r"(c)); return r;
}
__device__ __forceinline__ float bf_lo(uint32_t v) { return __uint_as_float(v << 16); }
__device__ __forceinline__ float bf_hi(uint32_t v) { return __uint_as_float(v & 0xFFFF0000u); }
__device__ __forceinline__ void unpack2(uint32_t v, float& lo, float& hi) {
    asm volatile("shl.b32 %0, %2, 16;\nand.b32 %1, %2, 0xffff0000;" : "=f"(lo), "=f"(hi) : "r"(v));
}
__device__ __forceinline__ float bf_round(float x) { return __bfloat162float(__float2bfloat16_rn(x)); }
__device__ __forceinline__ void stsm4(uint32_t addr, uint32_t r0, uint32_t r1, uint32_t r2, uint32_t r3) {
    asm volatile("stmatrix.sync.aligned.m8n8.x4.shared.b16 [%0], {%1, %2, %3, %4};" :: "r"(addr), "r"(r0), "r"(r1), "r"(r2), "r"(r3) : "memory");
}
__device__ __forceinline__ void stsm4t(uint32_t addr, uint32_t r0, uint32_t r1, uint32_t r2, uint32_t r3) {
    asm volatile("stmatrix.sync.aligned.m8n8.x4.trans.shared.b16 [%0], {%1, %2, %3, %4};" :: "r"(addr), "r"(r0), "r"(r1), "r"(r2), "r"(r3) : "memory");
}
__device__ __forceinline__ uint32_t movm(uint32_t a) { uint32_t d; asm volatile("movmatrix.sync.aligned.m8n8.trans.b16 %0, %1;" : "=r"(d) : "r"(a)); return d; }
__device__ __forceinline__ void ldsm4(uint32_t addr, uint32_t& r0, uint32_t& r1, uint32_t& r2, uint32_t& r3) {
    asm volatile("ldmatrix.sync.aligned.m8n8.x4.shared.b16 {%0, %1, %2, %3}, [%4];" : "=r"(r0), "=r"(r1), "=r"(r2), "=r"(r3) : "r"(addr) : "memory");
}
__device__ __forceinline__ void ldsm4t(uint32_t addr, uint32_t& r0, uint32_t& r1, uint32_t& r2, uint32_t& r3) {
    asm volatile("ldmatrix.sync.aligned.m8n8.x4.trans.shared.b16 {%0, %1, %2, %3}, [%4];" : "=r"(r0), "=r"(r1), "=r"(r2), "=r"(r3) : "r"(addr) : "memory");
}
__device__ __forceinline__ void mma16816(float (&c)[4], uint32_t a0, uint32_t a1, uint32_t a2, uint32_t a3, uint32_t b0, uint32_t b1) {
    asm("mma.sync.aligned.m16n8k16.row.col.f32.bf16.bf16.f32 {%0, %1, %2, %3}, {%4, %5, %6, %7}, {%8, %9}, {%0, %1, %2, %3};"
        : "+f"(c[0]), "+f"(c[1]), "+f"(c[2]), "+f"(c[3]) : "r"(a0), "r"(a1), "r"(a2), "r"(a3), "r"(b0), "r"(b1));
}
__device__ __forceinline__ float rcp(float x) { float r; asm("rcp.approx.ftz.f32 %0, %1;" : "=f"(r) : "f"(x)); return r; }
__device__ __forceinline__ float ex2(float x) { float r; asm("ex2.approx.ftz.f32 %0, %1;" : "=f"(r) : "f"(x)); return r; }
__device__ __forceinline__ float tanh_(float x) { float t; asm("tanh.approx.f32 %0, %1;" : "=f"(t) : "f"(x)); return t; }
__device__ __forceinline__ void block_end(uint32_t opaque) { asm volatile("{\n.reg .pred p;\nsetp.eq.u32 p, %0, 0xffffffff;\n@p trap;\n}" :: "r"(opaque)); }
__device__ __forceinline__ float silu_(float x) { return __fdividef(x, 1.f + __expf(-x)); }
__device__ __forceinline__ void st_pkt(void* p, uint32_t a, uint32_t b) {
    asm volatile("{\n.reg .b64 t;\nmov.b64 t, {%1, %2};\nst.relaxed.gpu.global.b64 [%0], t;\n}" :: "l"(p), "r"(a), "r"(b) : "memory");
}
__device__ __forceinline__ uint4 ld_pkt2(const void* p) {
    uint4 v; asm volatile("{\n.reg .b64 t, u;\nld.relaxed.gpu.global.v2.b64 {t, u}, [%4];\nmov.b64 {%0, %1}, t;\nmov.b64 {%2, %3}, u;\n}"
        : "=r"(v.x), "=r"(v.y), "=r"(v.z), "=r"(v.w) : "l"(p) : "memory"); return v;
}
__device__ __forceinline__ void st_pkt16(void* p, uint32_t a, uint32_t b, uint32_t c, uint32_t d) {
    asm volatile("{\n.reg .b64 t, u;\n.reg .b128 w;\nmov.b64 t, {%1, %2};\nmov.b64 u, {%3, %4};\nmov.b128 w, {t, u};\nst.relaxed.gpu.global.b128 [%0], w;\n}"
        :: "l"(p), "r"(a), "r"(b), "r"(c), "r"(d) : "memory");
}
__device__ __forceinline__ uint4 ld_pkt16(const void* p) {
    uint4 v; asm volatile("{\n.reg .b64 t, u;\n.reg .b128 w;\nld.relaxed.gpu.global.b128 w, [%4];\nmov.b128 {t, u}, w;\nmov.b64 {%0, %1}, t;\nmov.b64 {%2, %3}, u;\n}"
        : "=r"(v.x), "=r"(v.y), "=r"(v.z), "=r"(v.w) : "l"(p) : "memory"); return v;
}
#define SPIN_GUARD(n) do { if (++(n) > (1u << 22)) asm volatile("trap;"); } while (0)
__device__ __forceinline__ uint4 lds128(uint32_t a) { uint4 v; asm volatile("ld.shared.v4.u32 {%0, %1, %2, %3}, [%4];" : "=r"(v.x), "=r"(v.y), "=r"(v.z), "=r"(v.w) : "r"(a) : "memory"); return v; }
__device__ __forceinline__ void sts128(uint32_t a, uint32_t x, uint32_t y, uint32_t z, uint32_t w) { asm volatile("st.shared.v4.u32 [%0], {%1, %2, %3, %4};" :: "r"(a), "r"(x), "r"(y), "r"(z), "r"(w) : "memory"); }
__device__ __forceinline__ uint32_t lds32(uint32_t a) { uint32_t v; asm volatile("ld.shared.u32 %0, [%1];" : "=r"(v) : "r"(a) : "memory"); return v; }
__device__ __forceinline__ void sts32(uint32_t a, uint32_t v) { asm volatile("st.shared.u32 [%0], %1;" :: "r"(a), "r"(v) : "memory"); }
__device__ __forceinline__ bool elect_one() {
    uint32_t p; asm volatile("{\n.reg .pred q;\nelect.sync _|q, 0xffffffff;\nselp.u32 %0, 1, 0, q;\n}" : "=r"(p)); return p;
}
__device__ __forceinline__ void pause(uint32_t cycles) {
    uint32_t t0, t; asm volatile("mov.u32 %0, %%clock;" : "=r"(t0));
    do { __nanosleep(64); asm volatile("mov.u32 %0, %%clock;" : "=r"(t)); } while (t - t0 < cycles);
}
__device__ __forceinline__ void cluster_arrive() { asm volatile("barrier.cluster.arrive.relaxed.aligned;" ::: "memory"); }
__device__ __forceinline__ void cluster_wait() { asm volatile("barrier.cluster.wait.aligned;" ::: "memory"); }

__device__ __forceinline__ void wgmma_n128_z(float (&d)[64], uint64_t da, uint64_t db) {
    asm volatile("{\n.reg .pred p;\nsetp.ne.b32 p, 0, 0;\n"
        "wgmma.mma_async.sync.aligned.m64n128k16.f32.bf16.bf16 {"
        "%0, %1, %2, %3, %4, %5, %6, %7, %8, %9, %10, %11, %12, %13, %14, %15, "
        "%16, %17, %18, %19, %20, %21, %22, %23, %24, %25, %26, %27, %28, %29, %30, %31, "
        "%32, %33, %34, %35, %36, %37, %38, %39, %40, %41, %42, %43, %44, %45, %46, %47, "
        "%48, %49, %50, %51, %52, %53, %54, %55, %56, %57, %58, %59, %60, %61, %62, %63"
        "}, %64, %65, p, 1, 1, 0, 1;\n}\n"
        : "=f"(d[0]), "=f"(d[1]), "=f"(d[2]), "=f"(d[3]), "=f"(d[4]), "=f"(d[5]), "=f"(d[6]), "=f"(d[7]),
          "=f"(d[8]), "=f"(d[9]), "=f"(d[10]), "=f"(d[11]), "=f"(d[12]), "=f"(d[13]), "=f"(d[14]), "=f"(d[15]),
          "=f"(d[16]), "=f"(d[17]), "=f"(d[18]), "=f"(d[19]), "=f"(d[20]), "=f"(d[21]), "=f"(d[22]), "=f"(d[23]),
          "=f"(d[24]), "=f"(d[25]), "=f"(d[26]), "=f"(d[27]), "=f"(d[28]), "=f"(d[29]), "=f"(d[30]), "=f"(d[31]),
          "=f"(d[32]), "=f"(d[33]), "=f"(d[34]), "=f"(d[35]), "=f"(d[36]), "=f"(d[37]), "=f"(d[38]), "=f"(d[39]),
          "=f"(d[40]), "=f"(d[41]), "=f"(d[42]), "=f"(d[43]), "=f"(d[44]), "=f"(d[45]), "=f"(d[46]), "=f"(d[47]),
          "=f"(d[48]), "=f"(d[49]), "=f"(d[50]), "=f"(d[51]), "=f"(d[52]), "=f"(d[53]), "=f"(d[54]), "=f"(d[55]),
          "=f"(d[56]), "=f"(d[57]), "=f"(d[58]), "=f"(d[59]), "=f"(d[60]), "=f"(d[61]), "=f"(d[62]), "=f"(d[63])
        : "l"(da), "l"(db));
}
__device__ __forceinline__ void wgmma_n128(float (&d)[64], uint64_t da, uint64_t db) {
    asm volatile("{\n.reg .pred p;\nsetp.eq.b32 p, 0, 0;\n"
        "wgmma.mma_async.sync.aligned.m64n128k16.f32.bf16.bf16 {"
        "%0, %1, %2, %3, %4, %5, %6, %7, %8, %9, %10, %11, %12, %13, %14, %15, "
        "%16, %17, %18, %19, %20, %21, %22, %23, %24, %25, %26, %27, %28, %29, %30, %31, "
        "%32, %33, %34, %35, %36, %37, %38, %39, %40, %41, %42, %43, %44, %45, %46, %47, "
        "%48, %49, %50, %51, %52, %53, %54, %55, %56, %57, %58, %59, %60, %61, %62, %63"
        "}, %64, %65, p, 1, 1, 0, 1;\n}\n"
        : "+f"(d[0]), "+f"(d[1]), "+f"(d[2]), "+f"(d[3]), "+f"(d[4]), "+f"(d[5]), "+f"(d[6]), "+f"(d[7]),
          "+f"(d[8]), "+f"(d[9]), "+f"(d[10]), "+f"(d[11]), "+f"(d[12]), "+f"(d[13]), "+f"(d[14]), "+f"(d[15]),
          "+f"(d[16]), "+f"(d[17]), "+f"(d[18]), "+f"(d[19]), "+f"(d[20]), "+f"(d[21]), "+f"(d[22]), "+f"(d[23]),
          "+f"(d[24]), "+f"(d[25]), "+f"(d[26]), "+f"(d[27]), "+f"(d[28]), "+f"(d[29]), "+f"(d[30]), "+f"(d[31]),
          "+f"(d[32]), "+f"(d[33]), "+f"(d[34]), "+f"(d[35]), "+f"(d[36]), "+f"(d[37]), "+f"(d[38]), "+f"(d[39]),
          "+f"(d[40]), "+f"(d[41]), "+f"(d[42]), "+f"(d[43]), "+f"(d[44]), "+f"(d[45]), "+f"(d[46]), "+f"(d[47]),
          "+f"(d[48]), "+f"(d[49]), "+f"(d[50]), "+f"(d[51]), "+f"(d[52]), "+f"(d[53]), "+f"(d[54]), "+f"(d[55]),
          "+f"(d[56]), "+f"(d[57]), "+f"(d[58]), "+f"(d[59]), "+f"(d[60]), "+f"(d[61]), "+f"(d[62]), "+f"(d[63])
        : "l"(da), "l"(db));
}
__device__ __forceinline__ void wgmma_n176_z(float (&d)[88], uint64_t da, uint64_t db) {
    asm volatile("{\n.reg .pred p;\nsetp.ne.b32 p, 0, 0;\n"
        "wgmma.mma_async.sync.aligned.m64n176k16.f32.bf16.bf16 {"
        "%0, %1, %2, %3, %4, %5, %6, %7, %8, %9, %10, %11, %12, %13, %14, %15, "
        "%16, %17, %18, %19, %20, %21, %22, %23, %24, %25, %26, %27, %28, %29, %30, %31, "
        "%32, %33, %34, %35, %36, %37, %38, %39, %40, %41, %42, %43, %44, %45, %46, %47, "
        "%48, %49, %50, %51, %52, %53, %54, %55, %56, %57, %58, %59, %60, %61, %62, %63, "
        "%64, %65, %66, %67, %68, %69, %70, %71, %72, %73, %74, %75, %76, %77, %78, %79, "
        "%80, %81, %82, %83, %84, %85, %86, %87"
        "}, %88, %89, p, 1, 1, 0, 1;\n}\n"
        : "=f"(d[0]), "=f"(d[1]), "=f"(d[2]), "=f"(d[3]), "=f"(d[4]), "=f"(d[5]), "=f"(d[6]), "=f"(d[7]),
          "=f"(d[8]), "=f"(d[9]), "=f"(d[10]), "=f"(d[11]), "=f"(d[12]), "=f"(d[13]), "=f"(d[14]), "=f"(d[15]),
          "=f"(d[16]), "=f"(d[17]), "=f"(d[18]), "=f"(d[19]), "=f"(d[20]), "=f"(d[21]), "=f"(d[22]), "=f"(d[23]),
          "=f"(d[24]), "=f"(d[25]), "=f"(d[26]), "=f"(d[27]), "=f"(d[28]), "=f"(d[29]), "=f"(d[30]), "=f"(d[31]),
          "=f"(d[32]), "=f"(d[33]), "=f"(d[34]), "=f"(d[35]), "=f"(d[36]), "=f"(d[37]), "=f"(d[38]), "=f"(d[39]),
          "=f"(d[40]), "=f"(d[41]), "=f"(d[42]), "=f"(d[43]), "=f"(d[44]), "=f"(d[45]), "=f"(d[46]), "=f"(d[47]),
          "=f"(d[48]), "=f"(d[49]), "=f"(d[50]), "=f"(d[51]), "=f"(d[52]), "=f"(d[53]), "=f"(d[54]), "=f"(d[55]),
          "=f"(d[56]), "=f"(d[57]), "=f"(d[58]), "=f"(d[59]), "=f"(d[60]), "=f"(d[61]), "=f"(d[62]), "=f"(d[63]),
          "=f"(d[64]), "=f"(d[65]), "=f"(d[66]), "=f"(d[67]), "=f"(d[68]), "=f"(d[69]), "=f"(d[70]), "=f"(d[71]),
          "=f"(d[72]), "=f"(d[73]), "=f"(d[74]), "=f"(d[75]), "=f"(d[76]), "=f"(d[77]), "=f"(d[78]), "=f"(d[79]),
          "=f"(d[80]), "=f"(d[81]), "=f"(d[82]), "=f"(d[83]), "=f"(d[84]), "=f"(d[85]), "=f"(d[86]), "=f"(d[87])
        : "l"(da), "l"(db));
}
__device__ __forceinline__ void wgmma_n176(float (&d)[88], uint64_t da, uint64_t db) {
    asm volatile("{\n.reg .pred p;\nsetp.eq.b32 p, 0, 0;\n"
        "wgmma.mma_async.sync.aligned.m64n176k16.f32.bf16.bf16 {"
        "%0, %1, %2, %3, %4, %5, %6, %7, %8, %9, %10, %11, %12, %13, %14, %15, "
        "%16, %17, %18, %19, %20, %21, %22, %23, %24, %25, %26, %27, %28, %29, %30, %31, "
        "%32, %33, %34, %35, %36, %37, %38, %39, %40, %41, %42, %43, %44, %45, %46, %47, "
        "%48, %49, %50, %51, %52, %53, %54, %55, %56, %57, %58, %59, %60, %61, %62, %63, "
        "%64, %65, %66, %67, %68, %69, %70, %71, %72, %73, %74, %75, %76, %77, %78, %79, "
        "%80, %81, %82, %83, %84, %85, %86, %87"
        "}, %88, %89, p, 1, 1, 0, 1;\n}\n"
        : "+f"(d[0]), "+f"(d[1]), "+f"(d[2]), "+f"(d[3]), "+f"(d[4]), "+f"(d[5]), "+f"(d[6]), "+f"(d[7]),
          "+f"(d[8]), "+f"(d[9]), "+f"(d[10]), "+f"(d[11]), "+f"(d[12]), "+f"(d[13]), "+f"(d[14]), "+f"(d[15]),
          "+f"(d[16]), "+f"(d[17]), "+f"(d[18]), "+f"(d[19]), "+f"(d[20]), "+f"(d[21]), "+f"(d[22]), "+f"(d[23]),
          "+f"(d[24]), "+f"(d[25]), "+f"(d[26]), "+f"(d[27]), "+f"(d[28]), "+f"(d[29]), "+f"(d[30]), "+f"(d[31]),
          "+f"(d[32]), "+f"(d[33]), "+f"(d[34]), "+f"(d[35]), "+f"(d[36]), "+f"(d[37]), "+f"(d[38]), "+f"(d[39]),
          "+f"(d[40]), "+f"(d[41]), "+f"(d[42]), "+f"(d[43]), "+f"(d[44]), "+f"(d[45]), "+f"(d[46]), "+f"(d[47]),
          "+f"(d[48]), "+f"(d[49]), "+f"(d[50]), "+f"(d[51]), "+f"(d[52]), "+f"(d[53]), "+f"(d[54]), "+f"(d[55]),
          "+f"(d[56]), "+f"(d[57]), "+f"(d[58]), "+f"(d[59]), "+f"(d[60]), "+f"(d[61]), "+f"(d[62]), "+f"(d[63]),
          "+f"(d[64]), "+f"(d[65]), "+f"(d[66]), "+f"(d[67]), "+f"(d[68]), "+f"(d[69]), "+f"(d[70]), "+f"(d[71]),
          "+f"(d[72]), "+f"(d[73]), "+f"(d[74]), "+f"(d[75]), "+f"(d[76]), "+f"(d[77]), "+f"(d[78]), "+f"(d[79]),
          "+f"(d[80]), "+f"(d[81]), "+f"(d[82]), "+f"(d[83]), "+f"(d[84]), "+f"(d[85]), "+f"(d[86]), "+f"(d[87])
        : "l"(da), "l"(db));
}
__device__ __forceinline__ void wgmma_n256_z(float (&d)[128], uint64_t da, uint64_t db) {
    asm volatile("{\n.reg .pred p;\nsetp.ne.b32 p, 0, 0;\n"
        "wgmma.mma_async.sync.aligned.m64n256k16.f32.bf16.bf16 {"
        "%0, %1, %2, %3, %4, %5, %6, %7, %8, %9, %10, %11, %12, %13, %14, %15, "
        "%16, %17, %18, %19, %20, %21, %22, %23, %24, %25, %26, %27, %28, %29, %30, %31, "
        "%32, %33, %34, %35, %36, %37, %38, %39, %40, %41, %42, %43, %44, %45, %46, %47, "
        "%48, %49, %50, %51, %52, %53, %54, %55, %56, %57, %58, %59, %60, %61, %62, %63, "
        "%64, %65, %66, %67, %68, %69, %70, %71, %72, %73, %74, %75, %76, %77, %78, %79, "
        "%80, %81, %82, %83, %84, %85, %86, %87, %88, %89, %90, %91, %92, %93, %94, %95, "
        "%96, %97, %98, %99, %100, %101, %102, %103, %104, %105, %106, %107, %108, %109, %110, %111, "
        "%112, %113, %114, %115, %116, %117, %118, %119, %120, %121, %122, %123, %124, %125, %126, %127"
        "}, %128, %129, p, 1, 1, 0, 1;\n}\n"
        : "=f"(d[0]), "=f"(d[1]), "=f"(d[2]), "=f"(d[3]), "=f"(d[4]), "=f"(d[5]), "=f"(d[6]), "=f"(d[7]),
          "=f"(d[8]), "=f"(d[9]), "=f"(d[10]), "=f"(d[11]), "=f"(d[12]), "=f"(d[13]), "=f"(d[14]), "=f"(d[15]),
          "=f"(d[16]), "=f"(d[17]), "=f"(d[18]), "=f"(d[19]), "=f"(d[20]), "=f"(d[21]), "=f"(d[22]), "=f"(d[23]),
          "=f"(d[24]), "=f"(d[25]), "=f"(d[26]), "=f"(d[27]), "=f"(d[28]), "=f"(d[29]), "=f"(d[30]), "=f"(d[31]),
          "=f"(d[32]), "=f"(d[33]), "=f"(d[34]), "=f"(d[35]), "=f"(d[36]), "=f"(d[37]), "=f"(d[38]), "=f"(d[39]),
          "=f"(d[40]), "=f"(d[41]), "=f"(d[42]), "=f"(d[43]), "=f"(d[44]), "=f"(d[45]), "=f"(d[46]), "=f"(d[47]),
          "=f"(d[48]), "=f"(d[49]), "=f"(d[50]), "=f"(d[51]), "=f"(d[52]), "=f"(d[53]), "=f"(d[54]), "=f"(d[55]),
          "=f"(d[56]), "=f"(d[57]), "=f"(d[58]), "=f"(d[59]), "=f"(d[60]), "=f"(d[61]), "=f"(d[62]), "=f"(d[63]),
          "=f"(d[64]), "=f"(d[65]), "=f"(d[66]), "=f"(d[67]), "=f"(d[68]), "=f"(d[69]), "=f"(d[70]), "=f"(d[71]),
          "=f"(d[72]), "=f"(d[73]), "=f"(d[74]), "=f"(d[75]), "=f"(d[76]), "=f"(d[77]), "=f"(d[78]), "=f"(d[79]),
          "=f"(d[80]), "=f"(d[81]), "=f"(d[82]), "=f"(d[83]), "=f"(d[84]), "=f"(d[85]), "=f"(d[86]), "=f"(d[87]),
          "=f"(d[88]), "=f"(d[89]), "=f"(d[90]), "=f"(d[91]), "=f"(d[92]), "=f"(d[93]), "=f"(d[94]), "=f"(d[95]),
          "=f"(d[96]), "=f"(d[97]), "=f"(d[98]), "=f"(d[99]), "=f"(d[100]), "=f"(d[101]), "=f"(d[102]), "=f"(d[103]),
          "=f"(d[104]), "=f"(d[105]), "=f"(d[106]), "=f"(d[107]), "=f"(d[108]), "=f"(d[109]), "=f"(d[110]), "=f"(d[111]),
          "=f"(d[112]), "=f"(d[113]), "=f"(d[114]), "=f"(d[115]), "=f"(d[116]), "=f"(d[117]), "=f"(d[118]), "=f"(d[119]),
          "=f"(d[120]), "=f"(d[121]), "=f"(d[122]), "=f"(d[123]), "=f"(d[124]), "=f"(d[125]), "=f"(d[126]), "=f"(d[127])
        : "l"(da), "l"(db));
}
__device__ __forceinline__ void wgmma_n256(float (&d)[128], uint64_t da, uint64_t db) {
    asm volatile("{\n.reg .pred p;\nsetp.eq.b32 p, 0, 0;\n"
        "wgmma.mma_async.sync.aligned.m64n256k16.f32.bf16.bf16 {"
        "%0, %1, %2, %3, %4, %5, %6, %7, %8, %9, %10, %11, %12, %13, %14, %15, "
        "%16, %17, %18, %19, %20, %21, %22, %23, %24, %25, %26, %27, %28, %29, %30, %31, "
        "%32, %33, %34, %35, %36, %37, %38, %39, %40, %41, %42, %43, %44, %45, %46, %47, "
        "%48, %49, %50, %51, %52, %53, %54, %55, %56, %57, %58, %59, %60, %61, %62, %63, "
        "%64, %65, %66, %67, %68, %69, %70, %71, %72, %73, %74, %75, %76, %77, %78, %79, "
        "%80, %81, %82, %83, %84, %85, %86, %87, %88, %89, %90, %91, %92, %93, %94, %95, "
        "%96, %97, %98, %99, %100, %101, %102, %103, %104, %105, %106, %107, %108, %109, %110, %111, "
        "%112, %113, %114, %115, %116, %117, %118, %119, %120, %121, %122, %123, %124, %125, %126, %127"
        "}, %128, %129, p, 1, 1, 0, 1;\n}\n"
        : "+f"(d[0]), "+f"(d[1]), "+f"(d[2]), "+f"(d[3]), "+f"(d[4]), "+f"(d[5]), "+f"(d[6]), "+f"(d[7]),
          "+f"(d[8]), "+f"(d[9]), "+f"(d[10]), "+f"(d[11]), "+f"(d[12]), "+f"(d[13]), "+f"(d[14]), "+f"(d[15]),
          "+f"(d[16]), "+f"(d[17]), "+f"(d[18]), "+f"(d[19]), "+f"(d[20]), "+f"(d[21]), "+f"(d[22]), "+f"(d[23]),
          "+f"(d[24]), "+f"(d[25]), "+f"(d[26]), "+f"(d[27]), "+f"(d[28]), "+f"(d[29]), "+f"(d[30]), "+f"(d[31]),
          "+f"(d[32]), "+f"(d[33]), "+f"(d[34]), "+f"(d[35]), "+f"(d[36]), "+f"(d[37]), "+f"(d[38]), "+f"(d[39]),
          "+f"(d[40]), "+f"(d[41]), "+f"(d[42]), "+f"(d[43]), "+f"(d[44]), "+f"(d[45]), "+f"(d[46]), "+f"(d[47]),
          "+f"(d[48]), "+f"(d[49]), "+f"(d[50]), "+f"(d[51]), "+f"(d[52]), "+f"(d[53]), "+f"(d[54]), "+f"(d[55]),
          "+f"(d[56]), "+f"(d[57]), "+f"(d[58]), "+f"(d[59]), "+f"(d[60]), "+f"(d[61]), "+f"(d[62]), "+f"(d[63]),
          "+f"(d[64]), "+f"(d[65]), "+f"(d[66]), "+f"(d[67]), "+f"(d[68]), "+f"(d[69]), "+f"(d[70]), "+f"(d[71]),
          "+f"(d[72]), "+f"(d[73]), "+f"(d[74]), "+f"(d[75]), "+f"(d[76]), "+f"(d[77]), "+f"(d[78]), "+f"(d[79]),
          "+f"(d[80]), "+f"(d[81]), "+f"(d[82]), "+f"(d[83]), "+f"(d[84]), "+f"(d[85]), "+f"(d[86]), "+f"(d[87]),
          "+f"(d[88]), "+f"(d[89]), "+f"(d[90]), "+f"(d[91]), "+f"(d[92]), "+f"(d[93]), "+f"(d[94]), "+f"(d[95]),
          "+f"(d[96]), "+f"(d[97]), "+f"(d[98]), "+f"(d[99]), "+f"(d[100]), "+f"(d[101]), "+f"(d[102]), "+f"(d[103]),
          "+f"(d[104]), "+f"(d[105]), "+f"(d[106]), "+f"(d[107]), "+f"(d[108]), "+f"(d[109]), "+f"(d[110]), "+f"(d[111]),
          "+f"(d[112]), "+f"(d[113]), "+f"(d[114]), "+f"(d[115]), "+f"(d[116]), "+f"(d[117]), "+f"(d[118]), "+f"(d[119]),
          "+f"(d[120]), "+f"(d[121]), "+f"(d[122]), "+f"(d[123]), "+f"(d[124]), "+f"(d[125]), "+f"(d[126]), "+f"(d[127])
        : "l"(da), "l"(db));
}

struct Idx {
    uint32_t lane, warp, w4, q4, g8, prow, pan;
    __device__ __forceinline__ Idx() {
        uint32_t t; asm volatile("mov.u32 %0, %%tid.x;" : "=r"(t));
        lane = t & 31; warp = t >> 5; w4 = warp & 3; q4 = lane & 3; g8 = lane >> 2;
        prow = w4 * 16 + ((lane >> 3) & 1) * 8 + (lane & 7);
        pan = prow * 128 + (((lane >> 4) ^ (lane & 7)) << 4);
    }
};
#define IDX() const Idx ix; const uint32_t lane = ix.lane, warp = ix.warp, w4 = ix.w4, q4 = ix.q4, g8 = ix.g8, prow = ix.prow, pan_addr = ix.pan; \
    (void)lane; (void)warp; (void)w4; (void)q4; (void)g8; (void)prow; (void)pan_addr;

__device__ __forceinline__ int kof(int t, int sh, int j) {
    const int p = t >> (sh - 1), pn = p < 2 ? p : p >= 9, q = p - 2 - 7 * pn;
    return ((p < 2 ? j : q + (q >= j)) << 7) + (pn << 6) + ((t & (sh - 1)) << 5);
}
__device__ __forceinline__ uint32_t fidx(uint32_t m, uint32_t w, uint32_t pn) {
    return m * 32 + w * 16 + pn;
}
constexpr int HC0 = 8 * 48, HC3 = HC0 + 3072;
__device__ __forceinline__ int hcol(int p, int j) { return HC0 + p * 1024 + j * 128; }
struct Ring {
    uint32_t slot, par;
    __device__ __forceinline__ void next() { if (++slot == NSLOT) { slot = 0; par ^= 1; } }
    __device__ __forceinline__ void skip(uint32_t n) { slot += n; if (slot >= NSLOT) { slot -= NSLOT; par ^= 1; } }
};
__device__ __forceinline__ uint32_t BAR_FULL(uint32_t sb, uint32_t s) { return sb + OFF_BAR + 8 * s; }
constexpr uint32_t AF_REL = 48;
__device__ __forceinline__ uint32_t BAR_EMPTY(uint32_t sb, uint32_t s) { return sb + OFF_BAR + 96 + 8 * s; }
__device__ __forceinline__ uint32_t BAR_SFULL(uint32_t sb, uint32_t i) { return sb + OFF_BAR + 152 + 8 * i; }
__device__ __forceinline__ uint32_t BAR_SREADY(uint32_t sb, uint32_t i) { return sb + OFF_BAR + 184 + 8 * i; }
__device__ __forceinline__ uint32_t BAR_ONE(uint32_t sb, uint32_t i) { return sb + OFF_BAR + 216 + 8 * i; }
enum { EV_WIN, EV_WIN1, EV_WIN2, EV_WIN3, EV_P0, EV_GA, EV_GB, EV_LN2, EV_LAG0, EV_LAG1, EV_LAG2, EV_LAG3, EV_LAG4, EV_LAG5, EV_KV, EV_PAR, EV_AGO, EV_AGO1, EV_AGO2, EV_FGO, EV_FGO1, EV_FGO2, EV_H0, EV_H1, EV_H2, EV_H3, EV_COUNT };
constexpr int NB_TAIL = 4;

struct Rel {
    uint32_t base; bool sig;
    __device__ __forceinline__ Rel(uint32_t sb, uint32_t tw) {
        uint32_t a; asm("mapa.shared::cluster.u32 %0, %1, %2;" : "=r"(a) : "r"(BAR_EMPTY(sb, 0)), "r"((tw >> 5) & 1));
        base = __shfl_sync(0xffffffffu, a, 0); sig = (tw & ~32u) == 0;
    }
    __device__ __forceinline__ void operator()(uint32_t slot) const {
        if (sig) asm volatile("mbarrier.arrive.shared::cluster.b64 _, [%0];" :: "r"(base + 8 * slot) : "memory");
    }
};
struct LnRow { float rs0, nm0, rs1, nm1; };
struct Pipe {
    Rel rel; uint32_t p1, p2;
    __device__ __forceinline__ Pipe(uint32_t sb, uint32_t tw, uint32_t first) : rel(sb, tw), p1(first), p2(NSLOT) {}
    template <bool TWO> __device__ __forceinline__ void acquire(uint32_t sb, uint32_t af, const Ring& r) {
        const uint32_t b0 = BAR_FULL(sb, r.slot), b1 = b0 + af;
        const bool ready = TWO ? mbar_test2(b0, b1, r.par) : mbar_test(b0, r.par);
        wg_wait<1>();
        rel(p2);
        if (!ready) { if (TWO) mbar_wait2(b0, b1, r.par); else mbar_wait(b0, r.par); }
    }
    __device__ __forceinline__ void issued(uint32_t slot) { p2 = p1; p1 = slot; }
    __device__ __forceinline__ void drain1() { wg_wait<1>(); rel(p2); p2 = NSLOT; }
    __device__ __forceinline__ void drain0() { wg_wait<0>(); rel(p1); p1 = NSLOT; }
    template <bool TWO, class Step> __device__ __forceinline__ void hold(int LG, uint32_t sb, uint32_t af, Ring& r, uint32_t lag_bar, Step step) {
        Ring q = r;
#pragma unroll 1
        for (int i = 0; i < LG; ++i) { if (TWO) mbar_wait2(BAR_FULL(sb, q.slot), BAR_FULL(sb, q.slot) + af, q.par); else mbar_wait(BAR_FULL(sb, q.slot), q.par); q.next(); }
        mbar_wait(lag_bar, 0);
#pragma unroll 1
        do {
            step(r.slot);
            wg_wait<2>(); rel(p2); p2 = p1; p1 = r.slot;
            if (++r.slot == NSLOT) r.slot = 0;
        } while (r.slot != q.slot);
        r.par = q.par;
    }
};
template <bool TWO, bool FIRST, int NA, int NB>
__device__ __forceinline__ void step32(float (&aa)[NA], float (&ab)[NB], uint32_t sb, uint32_t wg, uint32_t slot, int own) {
    const uint32_t st = d16(sb) + slot * (SLOT >> 4);
    const uint32_t alo = own >= 0 ? d16(sb) + OFF_STG / 16 + wg * 1024 + (own >> 1) * 512 + (own & 1) * 4 : st + wg * 256;
    const uint32_t ahi = own >= 0 ? (1024 >> 4) | (1u << 30) : (512 >> 4) | (2u << 30);
    wg_fence();
#pragma unroll
    for (int k = 0; k < 2; ++k) {
        const uint64_t da = ((uint64_t)ahi << 32) | (alo + k * 2 + 0x10000);
        if constexpr (NA == 88) {
            const uint64_t d0 = mk_desc(st, 8192 + k * 2048, 8192, 1024, 1), d1 = mk_desc(st, 12288 + k * 2048, 8192, 1024, 1);
            if (FIRST && k == 0) { wgmma_n176_z(aa, da, d0); wgmma_n176_z(ab, da, d1); }
            else { wgmma_n176(aa, da, d0); wgmma_n176(ab, da, d1); }
        } else {
            const uint64_t d0 = mk_desc(st, 8192 + k * 2048, 4096, 1024, 1), d1 = mk_desc(st, 24576 + k * 2048, 4096, 1024, 1);
            if (FIRST && k == 0) { wgmma_n256_z(aa, da, d0); if constexpr (TWO) wgmma_n128_z(ab, da, d1); }
            else { wgmma_n256(aa, da, d0); if constexpr (TWO) wgmma_n128(ab, da, d1); }
        }
    }
    wg_commit();
}
template <bool TWO, int LG, int NA, int NB, class Tail>
__device__ __forceinline__ void mainloop32(float (&aa)[NA], float (&ab)[NB], uint32_t sb, uint32_t wg, uint32_t tw, Ring& r, uint32_t lag_ev, int g0, Tail tail) {
    if (!TWO) mbar_wait(BAR_FULL(sb, r.slot), r.par);
    step32<TWO, true>(aa, ab, sb, wg, r.slot, TWO ? 0 : -1);
    TS(g0, 0);
    Pipe pp(sb, tw, r.slot);
    r.next();
    const int end = wg ? 32 : 32 - LG;
#pragma unroll 1
    for (int it = 1; it < end; ++it) {
        pp.acquire<TWO>(sb, wg ? 0 : AF_REL, r);
        step32<TWO, false>(aa, ab, sb, wg, r.slot, TWO && it < 4 ? it : -1);
        pp.issued(r.slot);
        TS(g0 + it, 0);
        r.next();
    }
    if (wg == 0) { pp.drain1(); pp.drain0(); pp.hold<TWO>(LG, sb, AF_REL, r, BAR_ONE(sb, lag_ev), [&](uint32_t slot) { step32<TWO, false>(aa, ab, sb, 0, slot, -1); }); }
    pp.drain1();
    if (wg == 1 && tw == 0) mbar_arrive(BAR_ONE(sb, lag_ev));
    tail();
    pp.drain0();
    TS(g0 + 31, 1);
}
template <bool FIRST>
__device__ __forceinline__ void step64(float (&acc)[64], uint32_t sb, uint32_t wg, uint32_t slot, int own) {
    const uint32_t sbb = d16(sb) + slot * (SLOT >> 4), sa = own >= 0 ? d16(sb) + OFF_STG / 16 + wg * 1024 + own * 512 : sbb + wg * 512;
    wg_fence();
#pragma unroll
    for (int k = 0; k < 4; ++k) {
        const uint64_t da = mk_desc(sa, k * 32, 16, 1024, 1), db = mk_desc(sbb, 16384 + k * 2048, 8192, 1024, 1);
        if (FIRST && k == 0) wgmma_n128_z(acc, da, db); else wgmma_n128(acc, da, db);
    }
    wg_commit();
}
template <class Mid>
__device__ __forceinline__ void mainloop64(float (&acc)[64], bool wo, uint32_t sb, uint32_t wg, uint32_t tw, Ring& r, Mid mid) {
    const int g0 = wo ? 32 : 144, nst = wo ? 16 : 56, lg = wo ? LAGW : LAGD; (void)g0;
    const uint32_t lag_bar = BAR_ONE(sb, wo ? EV_LAG4 : EV_LAG5), af = wo && !wg ? AF_REL : 0;
    mbar_wait(BAR_FULL(sb, r.slot), r.par);
    if (!wo) CS(28);
    step64<true>(acc, sb, wg, r.slot, wo ? 0 : -1);
    if (!wo) CS(29);
    TS(g0, 0);
    Pipe pp(sb, tw, r.slot);
    r.next();
    int it = 1;
    auto run = [&](int end, int own) {
#pragma unroll 1
        do {
            pp.acquire<true>(sb, af, r);
            step64<false>(acc, sb, wg, r.slot, own);
            pp.issued(r.slot);
            TS(g0 + it, 0);
            if (wo && it == 2) CS(9);
            r.next();
            if (own > 0) {
                own = -1;
                pp.drain1(); pp.drain0();
                TS(g0 + 1, 1);
            }
        } while (++it < end);
    };
    const int end = wg ? nst : nst - lg;
    run(wo ? MIDW : wg ? MIDD : end, wo ? 1 : -1);
    mid();
    if (it < end) run(end, -1);
    if (wg == 0) { pp.drain1(); pp.drain0(); pp.hold<true>(lg, sb, af, r, lag_bar, [&](uint32_t slot) { step64<false>(acc, sb, 0, slot, -1); }); }
    pp.drain1();
    if (wg == 1 && tw == 0) mbar_arrive(lag_bar);
    pp.drain0();
    TS(g0 + nst - 1, 1);
}

struct RowAcc {
    float sm[4] = {0.f, 0.f, 0.f, 0.f}, sq[4] = {0.f, 0.f, 0.f, 0.f};
    __device__ __forceinline__ void add(int e, float x) { sm[e & 3] += x; sq[e & 3] = fmaf(x, x, sq[e & 3]); }
    __device__ __forceinline__ void publish(uint4* dst, uint32_t q4, uint32_t ep) const {
        const float s0 = sm[0] + sm[1], s1 = sm[2] + sm[3], q0 = sq[0] + sq[1], q1 = sq[2] + sq[3];
        const bool od = q4 & 1;
        float sv = (od ? s1 : s0) + __shfl_xor_sync(0xffffffffu, od ? s0 : s1, 1), qv = (od ? q1 : q0) + __shfl_xor_sync(0xffffffffu, od ? q0 : q1, 1);
        sv += __shfl_xor_sync(0xffffffffu, sv, 2); qv += __shfl_xor_sync(0xffffffffu, qv, 2);
        if (q4 < 2) st_pkt16(dst + q4 * 8, 0, __float_as_uint(sv), __float_as_uint(qv), ep);
    }
};
__device__ __forceinline__ LnRow merge_stats(const uint4* src, uint32_t q4, uint32_t ep, uint32_t sb) {
    uint4 t[4];
    uint32_t n = 0;
    while (true) {
#pragma unroll
        for (int i = 0; i < 4; ++i) t[i] = ld_pkt16(src + (q4 * 2 + (i >> 1)) * 512 + (i & 1) * 8);
        const bool ok_ = __all_sync(0xffffffffu, t[0].w == ep && t[1].w == ep && t[2].w == ep && t[3].w == ep);
        if (n < 4) CS(14 + n);
        if (ok_) break;
        SPIN_GUARD(n);
    }
    float v[4];
#pragma unroll
    for (int h = 0; h < 2; ++h) { v[h] = __uint_as_float(t[h].y) + __uint_as_float(t[2 + h].y); v[2 + h] = __uint_as_float(t[h].z) + __uint_as_float(t[2 + h].z); }
#pragma unroll
    for (int o = 1; o < 4; o <<= 1)
#pragma unroll
        for (int i = 0; i < 4; ++i) v[i] += __shfl_xor_sync(0xffffffffu, v[i], o);
    const float m0 = v[0] * (1.f / D_), m1 = v[1] * (1.f / D_);
    const float r0 = rsqrtf(fmaxf(fmaf(-m0, m0, v[2] * (1.f / D_)), 0.f) + 1e-5f), r1 = rsqrtf(fmaxf(fmaf(-m1, m1, v[3] * (1.f / D_)), 0.f) + 1e-5f);
    return LnRow{r0, -m0 * r0, r1, -m1 * r1};
}
struct Stg {
    uint32_t b, par;
    __device__ __forceinline__ uint32_t acquire2(uint32_t sb, uint32_t wg) {
        mbar_wait2(BAR_SREADY(sb, wg * 2), BAR_SREADY(sb, wg * 2 + 1), par);
        par ^= 1;
        return sb + OFF_STG + wg * 16384;
    }
    __device__ __forceinline__ void publish(uint32_t sb, uint32_t wg, uint32_t lane) {
        fence_async_smem();
        __syncwarp();
        if (lane == 0) mbar_arrive(BAR_SFULL(sb, wg * 2 + b));
        b ^= 1;
    }
};

struct LnPar {
    uint4 p[8];
    __device__ __forceinline__ void load(uint32_t sb, uint32_t q4) {
#pragma unroll
        for (int i = 0; i < 8; ++i) p[i] = lds128(sb + OFF_PAR + i * 64 + q4 * 16);
    }
};
__device__ __forceinline__ void ln_norm(uint32_t (&xn)[32], const float (&x)[64], const LnRow& n) {
#pragma unroll
    for (int e = 0; e < 32; ++e) {
        const float rs = (e & 1) ? n.rs1 : n.rs0, nm = (e & 1) ? n.nm1 : n.nm0;
        xn[e] = pack2(fmaf(x[2 * e], rs, nm), fmaf(x[2 * e + 1], rs, nm));
    }
}
__device__ __forceinline__ void ln_emit(const uint32_t (&xr)[32], const LnPar& lp, uint32_t sb, uint32_t wg, const Idx& ix) {
#pragma unroll
    for (int i = 0; i < 8; ++i)
        stsm4(sb + OFF_STG + wg * 16384 + (i >> 2) * 8192 + (ix.pan ^ ((i & 3) << 5)), hfma2_bf16(xr[4 * i], lp.p[i].z, lp.p[i].x), hfma2_bf16(xr[4 * i + 1], lp.p[i].z, lp.p[i].x),
              hfma2_bf16(xr[4 * i + 2], lp.p[i].w, lp.p[i].y), hfma2_bf16(xr[4 * i + 3], lp.p[i].w, lp.p[i].y));
    fence_async_smem();
    __syncwarp();
    if (ix.lane < 2) mbar_arrive(BAR_SFULL(sb, wg * 2 + ix.lane));
    bar_sync(1 + wg, 128);
}
__device__ __forceinline__ void load_slab(uint32_t (&xr)[32], uint32_t buf) {
    IDX();
#pragma unroll
    for (int i = 0; i < 8; ++i) ldsm4(buf + (i >> 2) * 8192 + (pan_addr ^ ((i & 3) << 5)), xr[4 * i], xr[4 * i + 1], xr[4 * i + 2], xr[4 * i + 3]);
}
__device__ __forceinline__ void unpack_slab(float (&x)[64], const uint32_t (&xr)[32]) {
#pragma unroll
    for (int i = 0; i < 32; ++i) unpack2(xr[i], x[2 * i], x[2 * i + 1]);
}
__device__ __forceinline__ void store_slab(const float (&x)[64], uint32_t buf, uint32_t pitch, uint32_t pan, int i0, int i1) {
#pragma unroll
    for (int i = i0; i < i1; ++i)
        stsm4(buf + (i >> 2) * pitch + (pan ^ ((i & 3) << 5)), pack2(x[8 * i], x[8 * i + 1]), pack2(x[8 * i + 2], x[8 * i + 3]), pack2(x[8 * i + 4], x[8 * i + 5]), pack2(x[8 * i + 6], x[8 * i + 7]));
}
__device__ __forceinline__ void fetch_halo(uint4* src, bool first, uint32_t sb, uint32_t W, uint32_t lane) {
    mbar_wait(BAR_ONE(sb, EV_KV), 0);
    mbar_wait2(BAR_SREADY(sb, 0), BAR_SREADY(sb, 1), 1);
    uint4 hv[8];
    uint32_t n = 0;
    while (true) {
        bool ok = true;
#pragma unroll
        for (int i = 0; i < 8; ++i) { hv[i] = first ? make_uint4(0, 0, 0, 0) : ld_pkt16(src + i * 32); ok = ok && hv[i].x != 0; }
        if (first || __all_sync(0xffffffffu, ok)) break;
        SPIN_GUARD(n);
    }
#pragma unroll
    for (int i = 0; i < 8; ++i) stsm4(sb + OFF_STG + W * 2048 + (i >> 2) * 8192 + (i & 3) * 512 + lane * 16, hv[i].x, hv[i].y, hv[i].z, hv[i].w);
    bar_arrive(NB_TAIL + W, 64);
    if (!first) {
#pragma unroll
        for (int i = 0; i < 8; ++i) src[i * 32] = make_uint4(0, 0, 0, 0);
    }
}

template <int NG, class G, class U, class Buf>
__device__ __forceinline__ void glu(uint32_t sb, uint32_t wg, G g, U u, Buf buf) {
    IDX();
#pragma unroll
    for (int k = 0; k < NG; ++k) {
        float h[8];
#pragma unroll
        for (int e = 0; e < 8; ++e) h[e] = fmaf(tanh_(g(8 * k + e)), u(8 * k + e), u(8 * k + e));
        stsm4(buf(k >> 2) + (pan_addr ^ ((k & 3) << 5)), pack2(h[0], h[1]), pack2(h[2], h[3]), pack2(h[4], h[5]), pack2(h[6], h[7]));
    }
    fence_async_smem();
    __syncwarp();
    if (lane < 2) mbar_arrive(BAR_SFULL(sb, wg * 2 + lane));
}

template <int NP>
__device__ __forceinline__ void passes128(uint32_t sb, uint32_t wg, uint32_t tw, Ring& r, Stg& stg) {
#pragma unroll 1
    for (int p = 0; p < NP; ++p) {
        float b256[128], none[1];
        mainloop32<false, LAGS>(b256, none, sb, wg, tw, r, EV_LAG2 + p, 80 + 32 * (p & 1), [&] { stg.acquire2(sb, wg); });
        if (threadIdx.x == 0) { TL(29 + 2 * p); TC(114 + 2 * p); }
        if (threadIdx.x == 128) TL(53 + 2 * (p & 1));
        CS(24 + 2 * (p & 1));
        glu<8>(sb, wg, [&](int i) { return b256[i + (i & 32)]; }, [&](int i) { return b256[i + (i & 32) + 32]; }, [&](int pn) { return sb + OFF_STG + wg * 16384 + pn * 8192; });
        if (threadIdx.x == 0) { TL(30 + 2 * p); TC(115 + 2 * p); }
        if (threadIdx.x == 128) TL(54 + 2 * (p & 1));
        CS(25 + 2 * (p & 1));
    }
}

__global__ void __launch_bounds__(384, 1)
fused_block_kernel(const __grid_constant__ Ptrs pt, const __grid_constant__ Maps mp) {
    uint32_t* const g_flags = pt.mail->flags;
    uint2* const g_mod = pt.mail->mod;
    uint4* const g_st1 = pt.mail->st1;
    uint32_t* const g_par2 = pt.mail->par2;
    uint4* const g_halo = pt.mail->halo;
    const __nv_bfloat16* __restrict__ cvec = pt.c;
    if (threadIdx.x == 224) { prefetch_map(&mp.wm8); prefetch_map(&mp.x); }
    extern __shared__ __align__(1024) uint8_t smem[];
    const uint32_t sb = smem_u32(smem);
    const uint32_t tid = threadIdx.x, tw = tid & 127, lane = tid & 31;
    const uint32_t warp = __shfl_sync(0xffffffffu, tid >> 5, 0), wg = warp >> 2;
    uint32_t rank; asm("mov.u32 %0, %%cluster_ctarank;" : "=r"(rank));
    rank = __shfl_sync(0xffffffffu, rank, 0);
    uint32_t ep;
    uint32_t smid; asm volatile("mov.u32 %0, %%smid;" : "=r"(smid));
    const int c = __shfl_sync(0xffffffffu, smid >> 1, 0);
    const int c7 = ((c - 32) * 37) >> 8;
    int grp = c < 32 ? c & 7 : c < 60 ? c - 31 - 7 * c7 : c < 62 ? -1 : 0;
    const int j = c < 32 ? c >> 3 : c < 60 ? 4 + c7 : c < 62 ? (c - 60) * 2 + rank : c - 58;
    const bool aux = grp < 0;
    const int m = grp * 2 + rank;
    uint4* const g_st2 = g_halo + (m > 0 ? (m - 1) * 8 * 512 : 128);

    bool cluster_arrive_early = false;
    if (wg < 2) {
      if (!KDEBUG) cluster_arrive();
      ep = flag_get(g_flags + FL_DONE);
      uint16_t cw[8];
      {
          const __nv_bfloat16* cp = cvec + ((tw >> 5) * 32 + (tw & 3) * 2) * 8 + (lane >> 2);
#pragma unroll
          for (int i = 0; i < 8; ++i) asm volatile("ld.global.nc.u16 %0, [%1];" : "=h"(cw[i]) : "l"(cp + (i >> 1) * 64 + (i & 1) * 8));
      }
      asm volatile("setmaxnreg.inc.sync.aligned.u32 224;");
      if (tid == 0) TL(58);
      if (KDEBUG) cluster_arrive();
      Ring r{0, 0};
      Stg stg{0, 0};
      if (aux) {
        if (wg == 0) {
            const uint4 cv = *(const uint4*)(cvec + tw * 8);
            sts128(sb + OFF_STG + (tw >> 3) * 1024 + (tw & 7) * 16, pack2(silu_(bf_lo(cv.x)), silu_(bf_hi(cv.x))), pack2(silu_(bf_lo(cv.y)), silu_(bf_hi(cv.y))),
                   pack2(silu_(bf_lo(cv.z)), silu_(bf_hi(cv.z))), pack2(silu_(bf_lo(cv.w)), silu_(bf_hi(cv.w))));
            fence_async_smem();
        }
        cluster_wait();
        ep = __shfl_sync(0xffffffffu, ep, 0) / NCTA + 1;
        if (wg == 0) {
            bar_sync(1, 128);
#pragma unroll 1
            for (int p = 0; p < 4; ++p) {
                float acc[128];
#pragma unroll
                for (int i = 0; i < 128; ++i) acc[i] = 0.f;
                uint32_t prev = 0;
#pragma unroll 1
                for (int kc = 0; kc < 16; ++kc) {
                    mbar_wait(BAR_FULL(sb, r.slot), r.par);
                    wg_fence();
#pragma unroll
                    for (int k = 0; k < 4; ++k)
                        wgmma_n256(acc, mk_desc(d16(sb) + kc * 64, OFF_STG + k * 32, 16, 0, 1), mk_desc(d16(sb) + r.slot * (SLOT >> 4), k * 2048, 8192, 1024, 1));
                    wg_commit();
                    wg_wait<1>();
                    if (kc > 0 && tw < 4) mbar_arrive(BAR_EMPTY(sb, prev));
                    prev = r.slot;
                    r.next();
                }
                wg_wait<0>();
                if (tw < 4) mbar_arrive(BAR_EMPTY(sb, prev));
                if (tw < 4) {
#pragma unroll
                    for (int jn = 0; jn < 32; ++jn) sts32(sb + OFF_TAB + (jn * 4 + tw) * 4, pack2(acc[jn * 4], acc[jn * 4 + 1]));
                }
                bar_sync(1, 128);
                const int vec = 2 + p, blk = p * 4 + j;
                const uint32_t val = lds32(sb + OFF_TAB + tw * 4);
                if (vec == 2 || vec == 5) st_pkt(g_mod + (8 + blk) * 128 + tw, val, ep);
                else {
                    const float one = vec == 4 ? 1.f : 0.f;
                    g_par2[((blk & 3) * 16 + (tw >> 3)) * 16 + (tw & 3) * 4 + (vec - 3) * 2 + ((tw >> 2) & 1)] =
                        pack2(0.5f * bf_round(one + bf_lo(val)), 0.5f * bf_round(one + bf_hi(val)));
                }
                bar_sync(1, 128);
                if (tw == 0) {
                    if (vec == 3 || vec == 4) asm volatile("red.release.gpu.global.add.u32 [%0], 1;" :: "l"(&g_flags[FL_LN2]) : "memory");
                    TL(1 + p);
                }
            }
            if (lane < 2) mbar_arrive_cta(BAR_ONE(sb, EV_P0), lane);
        }
        r = Ring{64 % NSLOT, (64 / NSLOT) & 1};
        mbar_wait(BAR_ONE(sb, EV_P0), 0);
        passes128<4>(sb, wg, tw, r, stg);
      } else {
        float xs[64];
        uint32_t xp[32];
        {
            IDX();
            if (q4 < 2) st_pkt16(g_st1 + (m * 8 + j) * 512 + wg * 64 + w4 * 16 + g8 + q4 * 8, 0, 0, 0, 0);
            if (warp == 0) st_pkt16(pt.mail->mod1 + g8 * 512 + (m * 8 + j) * 4 + q4, 0, 0, 0, 0);
            sts128(sb + tid * 16, pack2(silu_(bf_lo(cw[0])), silu_(bf_lo(cw[1]))), pack2(silu_(bf_lo(cw[2])), silu_(bf_lo(cw[3]))),
                   pack2(silu_(bf_lo(cw[4])), silu_(bf_lo(cw[5]))), pack2(silu_(bf_lo(cw[6])), silu_(bf_lo(cw[7]))));
            cluster_wait();
            ep = __shfl_sync(0xffffffffu, ep, 0) / NCTA + 1;
            load_slab(xp, stg.acquire2(sb, wg));
            unpack_slab(xs, xp);
            if (tid == 0) TL(24);
            if (tid == 128) TL(27);
        }
#pragma unroll 1
        for (int blk = 0; ; ++blk) {
        {
            IDX();
            uint4* const st = (blk ? g_st2 : g_st1 + m * 8 * 512) + wg * 64 + w4 * 16 + g8;
            RowAcc ra;
#pragma unroll
            for (int e = 0; e < 64; ++e) ra.add(e, xs[e]);
            ra.publish(st + j * 512, q4, ep);
            uint32_t t_pub = 0; if (PDLY) asm volatile("mov.u32 %0, %%clock;" : "=r"(t_pub));
            if (tid == 0) TL(blk ? 9 : 26);
            if (tid == 128 && blk) TL(34);
            if (blk) CS(11);
            LnPar lp;
            if (blk == 0) {
            uint4* const mod_out = pt.mail->mod1 + g8 * 512 + (m * 8 + j) * 4 + q4;
            if (wg == 0) {
                uint4 af[8];
#pragma unroll
                for (int i = 0; i < 8; ++i) af[i] = lds128(sb + w4 * 512 + i * 64 + q4 * 16);
                float c[4][4] = {};
#pragma unroll
                for (int i = 0; i < 8; ++i) {
                    if (!(i & 1)) mbar_wait(BAR_ONE(sb, EV_WIN + (i >> 1)), 0);
                    if (i == 6 && tid == 0) TL(25);
#pragma unroll
                    for (int h = 0; h < 2; ++h) {
                        uint32_t b0, b1, b2, b3;
                        ldsm4t(sb + 5 * SLOT + i * 4096 + w4 * 1024 + h * 512 + (lane & 15) * 32 + (lane >> 4) * 16, b0, b1, b2, b3);
                        mma16816(c[2 * h], h ? af[i].z : af[i].x, 0u, h ? af[i].w : af[i].y, 0u, b0, b1);
                        mma16816(c[2 * h + 1], h ? af[i].z : af[i].x, 0u, h ? af[i].w : af[i].y, 0u, b2, b3);
                    }
                }
                if (lane < 4) sts128(sb + OFF_TAB + w4 * 64 + lane * 16, __float_as_uint(c[0][0] + c[2][0]), __float_as_uint(c[0][1] + c[2][1]),
                                     __float_as_uint(c[1][0] + c[3][0]), __float_as_uint(c[1][1] + c[3][1]));
                if (lane < 2) mbar_arrive_cta(BAR_ONE(sb, EV_P0), lane);
                bar_sync(1, 128);
                if (w4 == 0) {
                    float a[4] = {0.f, 0.f, 0.f, 0.f};
#pragma unroll
                    for (int i = 0; i < 4; ++i) {
                        const uint4 t = lds128(sb + OFF_TAB + i * 64 + q4 * 16);
                        a[0] += __uint_as_float(t.x); a[1] += __uint_as_float(t.y); a[2] += __uint_as_float(t.z); a[3] += __uint_as_float(t.w);
                    }
                    const float add = m >= 8 ? 1.f : 0.f;
                    st_pkt16(mod_out, pack2(bf_round(a[0]) + add, bf_round(a[1]) + add), pack2(bf_round(a[2]) + add, bf_round(a[3]) + add), ep, 0);
                    if (tid == 0) TL(3);
                }
            } else if (LWAIT >= 0) mbar_wait(BAR_ONE(sb, EV_WIN + LWAIT), 0);
            } else {
                mbar_wait2(BAR_ONE(sb, EV_LN2), BAR_FULL(sb, 0), 0);
                stg.acquire2(sb, wg);
            }
            lp.load(sb, q4);
#pragma unroll
            for (int e = 0; e < 32; ++e) xp[e] = pack2(xs[2 * e], xs[2 * e + 1]);
            if (PDLY && blk) { uint32_t t1; do { asm volatile("mov.u32 %0, %%clock;" : "=r"(t1)); } while (t1 - t_pub < PDLY); }
            if (blk) CS(13);
            const LnRow n = merge_stats(st, q4, ep, sb);
            if (tid == 0) TL(blk ? 49 : 48);
            if (tid == 128) TL(blk ? 45 : 28);
            if (blk) CS(18);
            uint32_t xn[32];
            ln_norm(xn, xs, n);
            if (blk == 0) { mbar_wait2(BAR_FULL(sb, 0), BAR_ONE(sb, EV_PAR), 0); lp.load(sb, q4); }
            ln_emit(xn, lp, sb, wg, ix);
            if (tid == 0) { TL(blk ? 36 : 8); TC(blk ? 109 : 103); }
            if (tid == 128) TL(blk ? 43 : 22);
            if (blk) CS(21);
        }
        if (blk == 0) {
        {
            float kv[128], qa[64];
            step32<true, true>(kv, qa, sb, wg, r.slot, 0);
            TS(0, 0);
            Pipe pp(sb, tw, r.slot);
            r.next();
#pragma unroll 1
            for (int it = 1; it < 32 - LAGQ; ++it) {
                pp.acquire<true>(sb, wg ? 0 : AF_REL, r);
                step32<true, false>(kv, qa, sb, wg, r.slot, it < 4 ? it : -1);
                pp.issued(r.slot);
                TS(it, 0);
                r.next();
            }
            auto half = [&](uint32_t slot, bool q) {
                const uint32_t st = d16(sb) + slot * (SLOT >> 4);
#pragma unroll
                for (int k = 0; k < 2; ++k) {
                    const uint64_t da = mk_desc(st + wg * 256, k * 32, 16, 512, 2);
                    if (q) wgmma_n128(qa, da, mk_desc(st, 24576 + k * 2048, 4096, 1024, 1)); else wgmma_n256(kv, da, mk_desc(st, 8192 + k * 2048, 4096, 1024, 1));
                }
            };
            auto part = [&](bool q) {
                wg_fence();
#pragma unroll
                for (int it = 32 - LAGQ; it < 32; ++it) half(it % NSLOT, q);
                wg_commit();
            };
            stg.acquire2(sb, wg); mbar_wait2(BAR_SREADY(sb, 2), BAR_SREADY(sb, 3), 1);
            if (wg == 0) { pp.drain1(); pp.drain0(); }
#pragma unroll 1
            for (int it = 32 - LAGQ; it < 32; ++it) {
                pp.acquire<true>(sb, wg ? 0 : AF_REL, r);
                if (wg) { wg_fence(); half(r.slot, false); wg_commit(); }
                pp.issued(NSLOT);
                TS(it, 0);
                r.next();
            }
            if (wg == 0) { mbar_wait(BAR_ONE(sb, EV_LAG0), 0); part(false); part(true); wg_wait<1>(); }
            else { wg_wait<1>(); if (tw == 0) mbar_arrive(BAR_ONE(sb, EV_LAG0)); wg_wait<0>(); }
            CS(8);
            IDX();
            uint32_t k1[16], k2[16], v1[16], v2[16], qf[32];
#pragma unroll
            for (int i = 0; i < 128; ++i) asm volatile("" : "+f"(kv[i]) :: "memory");
#pragma unroll
            for (int t = 0; t < 16; ++t) k2[t] = pack2(kv[4 * t + 2], kv[4 * t + 3]);
#pragma unroll
            for (int t = 0; t < 16; ++t) k1[t] = pack2(kv[4 * t], kv[4 * t + 1]);
#pragma unroll
            for (int t = 0; t < 16; ++t) v2[t] = pack2(kv[64 + 4 * t + 2], kv[64 + 4 * t + 3]);
            const uint32_t nxt = warp + ((warp & 1) ? 3 : 1);
            if (nxt < 8) {
                const uint32_t dst = sb + OFF_STG + (nxt >> 2) * 16384 + (nxt & 3) * 2048 + lane * 16;
#pragma unroll
                for (int h = 0; h < 4; ++h) stsm4(dst + h * 512, k2[4 * h], k2[4 * h + 1], k2[4 * h + 2], k2[4 * h + 3]);
#pragma unroll
                for (int h = 0; h < 4; ++h) stsm4(dst + 8192 + h * 512, v2[4 * h], v2[4 * h + 1], v2[4 * h + 2], v2[4 * h + 3]);
                bar_arrive(NB_TAIL + nxt, 64);
            } else if (m < 15) {
                uint4* dst = g_halo + (m * 8 + j) * 512 + (w4 >> 1) * 256 + lane;
#pragma unroll
                for (int h = 0; h < 4; ++h) { if (!k2[4 * h]) k2[4 * h] = 0x8000u; if (!v2[4 * h]) v2[4 * h] = 0x8000u; }
#pragma unroll
                for (int h = 0; h < 4; ++h) st_pkt16(dst + h * 32, k2[4 * h], k2[4 * h + 1], k2[4 * h + 2], k2[4 * h + 3]);
#pragma unroll
                for (int h = 0; h < 4; ++h) st_pkt16(dst + 128 + h * 32, v2[4 * h], v2[4 * h + 1], v2[4 * h + 2], v2[4 * h + 3]);
            }
#pragma unroll
            for (int t = 0; t < 16; ++t) { v1[t] = pack2(kv[64 + 4 * t], kv[64 + 4 * t + 1]); v1[t] = movm(v1[t]); v2[t] = movm(v2[t]); }
            if (tid == 0) TL(33);
            CS(2);
            if (wg) part(true);
            bar_sync(NB_TAIL + warp, 64);
            CS(4);
            if (tid == 0) TL(5);
            uint32_t k0[16], v0[16];
            const uint32_t mine = sb + OFF_STG + wg * 16384 + w4 * 2048;
#pragma unroll
            for (int h = 0; h < 4; ++h) ldsm4(mine + lane * 16 + h * 512, k0[4 * h], k0[4 * h + 1], k0[4 * h + 2], k0[4 * h + 3]);
#pragma unroll
            for (int h = 0; h < 4; ++h) ldsm4t(mine + lane * 16 + 8192 + h * 512, v0[4 * h], v0[4 * h + 1], v0[4 * h + 2], v0[4 * h + 3]);
            wg_wait<0>();
#pragma unroll
            for (int it = 32 - LAGQ; it < 32; ++it) pp.rel(it % NSLOT);
            TS(31, 1);
            if (tid == 0) { TL(4); TC(104); }
            if (tid == 128) TL(50);
            CS(1);
#pragma unroll
            for (int i = 0; i < 64; ++i) asm volatile("" : "+f"(qa[i]) :: "memory");
            const bool lo0 = q4 * 2 > g8, lo1 = q4 * 2 + 1 > g8;
            const bool nopast = m == 0 && (warp & 5) == 0;
            const uint32_t lomask = (lo0 ? 0xFFFFu : 0u) | (lo1 ? 0xFFFF0000u : 0u);
            const uint32_t orow = mine + (lane & 7) * 128 + (((lane >> 3) ^ (lane & 7)) << 4);
            const float sl2 = 0.17677669529663687f * 1.4426950408889634f;
#pragma unroll
            for (int pn = 0; pn < 2; ++pn) {
                float e0[4], e1[4], mx[4], sum[4];
#pragma unroll
                for (int hh = 0; hh < 2; ++hh) {
                    const int h = pn * 2 + hh;
#pragma unroll
                    for (int i = 8 * h; i < 8 * h + 8; ++i) qf[i] = pack2(qa[2 * i], qa[2 * i + 1]);
                    float s[3][4];
#pragma unroll
                    for (int t = 0; t < 3; ++t) {
                        const uint32_t* k = (t == 0 ? k0 : t == 1 ? k1 : k2) + 4 * h;
                        s[t][0] = s[t][1] = s[t][2] = s[t][3] = 0.f;
                        mma16816(s[t], qf[h * 8], qf[h * 8 + 1], qf[h * 8 + 2], qf[h * 8 + 3], k[0], k[1]);
                        mma16816(s[t], qf[h * 8 + 4], qf[h * 8 + 5], qf[h * 8 + 6], qf[h * 8 + 7], k[2], k[3]);
                    }
#pragma unroll
                    for (int hf = 0; hf < 2; ++hf) {
                        const int u = hh * 2 + hf;
                        e0[u] = lo0 ? ((hf == 0 && nopast) ? -INFINITY : s[hf][hf * 2]) : s[hf + 1][hf * 2];
                        e1[u] = lo1 ? ((hf == 0 && nopast) ? -INFINITY : s[hf][hf * 2 + 1]) : s[hf + 1][hf * 2 + 1];
                        mx[u] = fmaxf(e0[u], e1[u]);
                    }
                }
#pragma unroll
                for (int o = 1; o < 4; o <<= 1)
#pragma unroll
                    for (int u = 0; u < 4; ++u) mx[u] = fmaxf(mx[u], __shfl_xor_sync(0xffffffffu, mx[u], o));
#pragma unroll
                for (int u = 0; u < 4; ++u) {
                    const float c = -mx[u] * sl2;
                    e0[u] = ex2(fmaf(e0[u], sl2, c)); e1[u] = ex2(fmaf(e1[u], sl2, c));
                    sum[u] = e0[u] + e1[u];
                }
#pragma unroll
                for (int o = 1; o < 4; o <<= 1)
#pragma unroll
                    for (int u = 0; u < 4; ++u) sum[u] += __shfl_xor_sync(0xffffffffu, sum[u], o);
#pragma unroll
                for (int u = 0; u < 4; ++u) {
                    const int h = pn * 2 + (u >> 1);
                    const float inv = rcp(sum[u]);
                    const uint32_t p = pack2(e0[u] * inv, e1[u] * inv);
                    const uint32_t* va = ((u & 1) ? v1 : v0) + 4 * h;
                    const uint32_t* vb = ((u & 1) ? v2 : v1) + 4 * h;
                    float o[2][4] = {};
#pragma unroll
                    for (int d = 0; d < 2; ++d) mma16816(o[d], va[2 * d], va[2 * d + 1], vb[2 * d], vb[2 * d + 1], p & lomask, p & ~lomask);
                    stsm4t((orow ^ ((u >> 1) << 6)) + pn * 8192 + (u & 1) * 1024, pack2(o[0][0], o[0][1]), pack2(o[0][2], o[0][3]), pack2(o[1][0], o[1][1]), pack2(o[1][2], o[1][3]));
                }
                fence_async_smem();
                __syncwarp();
                if (lane == 0) mbar_arrive(BAR_SFULL(sb, wg * 2 + pn));
                if (pn == 0) { CS(5); block_end(sb); }
            }
            CS(6);
            if (tid == 32) TL(41);
            mbar_wait(BAR_FULL(sb, 32 % NSLOT + wg), (32 / NSLOT) & 1);
            load_slab(xp, sb + (32 % NSLOT + wg) * SLOT);
            bar_sync(1 + wg, 128);
            if (tid == 0) { TL(6); TC(106); }
            if (tid == 128) TL(44);
            CS(7);
        }
        } else {
        {
            float ag[88], au[88];
            mainloop32<true, LAG>(ag, au, sb, wg, tw, r, EV_LAG1, 48, [&] {
                stg.acquire2(sb, wg);
                Ring q = r; if (!wg) q.next();
                mbar_wait(BAR_EMPTY(sb, q.slot), q.par ^ 1);
            });
            if (tid == 0) { TL(10); TC(110); }
            if (tid == 128) TL(51);
            CS(22);
            glu<11>(sb, wg, [&](int i) { return ag[i]; }, [&](int i) { return au[i]; },
                    [&](int pn) { return pn < 2 ? sb + OFF_STG + wg * 16384 + pn * 8192 : sb + (wg ? P3_SLOT1 : P3_SLOT0) * SLOT + 24576; });
            if (tid == 0) { TL(11); TC(111); }
            if (tid == 128) TL(52);
            CS(23);
        }
        passes128<2>(sb, wg, tw, r, stg);
        if (tid == 0) { TL(12); TC(112); }
        }
        {
            float acc[64], gf[32];
            mainloop64(acc, blk == 0, sb, wg, tw, r, [&] {
                mbar_wait(BAR_ONE(sb, EV_GA + blk), 0);
                if (blk) stg.acquire2(sb, wg);
                unpack_slab(xs, xp);
                uint32_t gt[16];
#pragma unroll
                for (int cg = 0; cg < 16; ++cg) gt[cg] = lds32(sb + OFF_TAB + blk * 256 + cg * 16 + (tw & 3) * 4);
#pragma unroll
                for (int i = 0; i < 16; ++i) unpack2(gt[i], gf[2 * i], gf[2 * i + 1]);
            });
            if (tid == 0) { TL(blk ? 13 : 7); TC(blk ? 113 : 107); }
            if (tid == 128) TL(blk ? 57 : 42);
            CS(blk ? 30 : 10);
#pragma unroll
            for (int e = 0; e < 64; ++e) xs[e] = fmaf(gf[(e >> 2) * 2 + (e & 1)], acc[e], xs[e]);
        }
        if (blk) break;
        }
        cluster_arrive();
        {
            IDX();
#pragma unroll
            for (int p = 0; p < 2; ++p) {
                store_slab(xs, sb + OFF_STG + wg * 16384, 8192, pan_addr, 4 * p, 4 * p + 4);
                stg.publish(sb, wg, lane);
            }
            if (tid == 0) TL(14);
            CS(31);
        }
      }
    } else {
        if (warp == 8 && !aux && elect_one()) {
#pragma unroll
            for (int i = 0; i < 4; ++i) mbar_init(BAR_SREADY(sb, i), 1);
#pragma unroll
            for (int i = 0; i < 4; ++i) mbar_init(BAR_ONE(sb, EV_WIN + i), 1);
#pragma unroll
            for (int i = 0; i < 4; ++i) {
                mbar_expect_tx(BAR_SREADY(sb, i), 8192);
                tma_load3(sb + OFF_STG + i * 8192, &mp.x, j * 128 + (i & 1) * 64, m * 64 + (i >> 1) * 32, BAR_SREADY(sb, i));
            }
#pragma unroll 1
            for (int i = 0; i < 4; ++i) {
                mbar_expect_tx(BAR_ONE(sb, EV_WIN + i), 8192);
                tma_load(sb + 5 * SLOT + i * 8192, &mp.wm8, 2 * i * 6144 + (m * 8 + j) * 16, 0, BAR_ONE(sb, EV_WIN + i));
                tma_load(sb + 5 * SLOT + i * 8192 + 4096, &mp.wm8, (2 * i + 1) * 6144 + (m * 8 + j) * 16, 0, BAR_ONE(sb, EV_WIN + i));
            }
        }
        __syncwarp();
        asm volatile("setmaxnreg.dec.sync.aligned.u32 56;");
        if (elect_one()) {
            if (warp == 8) {
                prefetch_map(&mp.wqkv); prefetch_map(&mp.wmod);
            } else if (warp < 11) {
                mbar_init(BAR_EMPTY(sb, NSLOT), 1);
#pragma unroll
                for (int i = 0; i < 2; ++i) { mbar_init(BAR_SFULL(sb, (warp - 9) * 2 + i), 4); if (aux) mbar_init(BAR_SREADY(sb, (warp - 9) * 2 + i), 1); }
#pragma unroll
                for (int i = 0; i < 3; ++i) {
                    mbar_init(BAR_EMPTY(sb, (warp - 9) * 3 + i), 4);
                    mbar_init(BAR_FULL(sb, (warp - 9) * 3 + i), 1); mbar_init(BAR_FULL(sb, (warp - 9) * 3 + i) + AF_REL, 1);
                }
            } else {
#pragma unroll
                for (int i = EV_P0; i < EV_COUNT; ++i) mbar_init(BAR_ONE(sb, i), i == EV_P0 ? 8 : 1);
            }
            asm volatile("fence.mbarrier_init.release.cluster;" ::: "memory");
        }
        __syncwarp();
        cluster_arrive();
        ep = 0;
        if (warp != 8 || aux) ep = flag_get(g_flags + FL_DONE);
        cluster_wait();
        ep = __shfl_sync(0xffffffffu, ep, 0) / NCTA + 1;
        if (warp == 8) {
            const bool el = elect_one();
            Ring r{0, 1};
            if (aux) {
                {
                    uint32_t n = 0;
                    while (!__all_sync(0xffffffffu, ld_pkt16(pt.mail->mod1 + 256).z == ep)) { SPIN_GUARD(n); __nanosleep(200); }
                }
#pragma unroll 1
                for (int it = 0; it < 64; ++it) {
                    const int col = 2048 + (it >> 4) * 1024 + j * 256;
                    mbar_wait(BAR_EMPTY(sb, r.slot), r.par);
                    const uint32_t st = sb + r.slot * SLOT, fb = BAR_FULL(sb, r.slot);
                    if (el) {
                        mbar_expect_tx(fb, 32768);
#pragma unroll
                        for (int b = 0; b < 4; ++b) tma_load(st + b * 8192, &mp.wmod, col + b * 64, (it & 15) * 64, fb);
                    }
                    r.next();
                }
                mbar_wait(BAR_ONE(sb, EV_P0), 0);
                const CUtensorMap* wm = rank ? &mp.wu : &mp.wg;
#pragma unroll 1
                for (int g = 0; g < 128; ++g) {
                    const int mx = (j >> 1) * 8 + (g >> 5) * 2 + rank, k0 = ((g & 14) << 6) + ((g & 16) << 2) + ((g & 1) << 5);
                    if (!(g & 15)) {
                        uint32_t n = 0;
                        while (!__all_sync(0xffffffffu, (int32_t)(flag_get(g_flags + FL_PROG + fidx(mx, lane >> 4, (lane & 14) | ((g >> 4) & 1))) - (ep * 8 + ST_H2)) >= 0)) { SPIN_GUARD(n); __nanosleep(300); }
                    }
                    mbar_wait(BAR_EMPTY(sb, r.slot), r.par);
                    const uint32_t st = sb + r.slot * SLOT, fb = BAR_FULL(sb, r.slot);
                    if (el) {
                        mbar_expect_tx(fb, 24576);
                        tma_load_mc(st + 8192 + rank * 4096, wm, HC3, k0, fb);
                        tma_load_mc(st + 16384 + rank * 4096, wm, HC3 + 64, k0, fb);
                        tma_load(st, &mp.h2l, k0, mx * 128, fb);
                    }
                    r.next();
                }
            } else {
#pragma unroll 1
                for (int it = 0; it < 32; ++it) {
                    const int cb = j * 128 + rank * 64, k0 = kof(it, 2, j);
                    if (it == BW0) mbar_wait(BAR_ONE(sb, BWEV), 0);
                    if (it == BW1) mbar_wait(BAR_ONE(sb, EV_PAR), 0);
                    if (it == 5) mbar_wait(BAR_ONE(sb, EV_P0), 0);
                    if (it == AG0) mbar_wait(BAR_ONE(sb, (AGW & 1) ? EV_AGO : EV_FGO), 0);
                    mbar_wait(BAR_EMPTY(sb, r.slot), r.par);
                    const uint32_t st = sb + r.slot * SLOT, fb = BAR_FULL(sb, r.slot);
                    if (el) {
                        mbar_expect_tx(fb, it < 4 ? 24576 : 28672);
                        tma_load_mc(st + 8192 + rank * 4096, &mp.wqkv, 1024 + cb, k0, fb);
                        tma_load_mc(st + 16384 + rank * 4096, &mp.wqkv, 2048 + cb, k0, fb);
                        tma_load_mc(st + 24576 + rank * 4096, &mp.wqkv, cb, k0, fb);
                        if (it < 4) mbar_arrive(fb + AF_REL);
                        if (it == PFWO + (m >> 1)) { tma_prefetch(&mp.wo, j * 128, m * 64); tma_prefetch(&mp.wo, j * 128 + 64, m * 64); }
                        if (it >= PFG && it < PFG + PFN && (it & 7) == grp) {
                            const int kp = kof(it - PFG + PFO, 2, j);
                            tma_prefetch(rank ? &mp.wu : &mp.wg, hcol(0, j), kp); tma_prefetch(rank ? &mp.wu : &mp.wg, hcol(0, j) + 64, kp);
                            asm volatile("cp.async.bulk.prefetch.tensor.3d.L2.global [%0, {%1, %2, %3}];" :: "l"(rank ? &mp.wu3 : &mp.wg3), "r"(0), "r"(j), "r"(kp) : "memory");
                        }
                    }
                    r.next();
                }
                if (el) mbar_arrive(BAR_ONE(sb, EV_KV));
#pragma unroll 1
                for (int it = 0; it < 16; ++it) {
                    const int k0 = kof(it, 1, j);
                    if (it == AG1) mbar_wait(BAR_ONE(sb, (AGW & 2) ? EV_AGO1 : EV_FGO1), 0);
                    mbar_wait(BAR_EMPTY(sb, r.slot), r.par);
                    const uint32_t st = sb + r.slot * SLOT, fb = BAR_FULL(sb, r.slot);
                    if (el) {
                        mbar_expect_tx(fb, it < 2 ? 32768 : 24576);
                        tma_load_mc(st + 16384 + rank * 8192, &mp.wo, j * 128 + rank * 64, k0, fb);
                        if (it < 2) {
                            tma_load3(st, &mp.x, j * 128, m * 64 + it * 32, fb); tma_load3(st + 8192, &mp.x, j * 128 + 64, m * 64 + it * 32, fb);
                            mbar_arrive(fb + AF_REL);
                        }
                        if (it == 6) { prefetch_map(rank ? &mp.wu : &mp.wg); prefetch_map(rank ? &mp.wu3 : &mp.wg3); }
                    }
                    r.next();
                }
                const CUtensorMap* wm = rank ? &mp.wu : &mp.wg;
#pragma unroll 1
                for (int g = 0; g < 96; ++g) {
                    if (g == AG2) mbar_wait(BAR_ONE(sb, (AGW & 4) ? EV_AGO2 : EV_FGO2), 0);
                    const int p = g >> 5, cb = hcol(p, j), k0 = p == 0 ? kof(g, 2, j) : (g & 31) * 32;
                    mbar_wait(BAR_EMPTY(sb, r.slot), r.par);
                    const uint32_t st = sb + r.slot * SLOT, fb = BAR_FULL(sb, r.slot);
                    if (el) {
                        mbar_expect_tx(fb, (g < 4 || p > 0) ? 24576 : 28672);
                        tma_load_mc(st + 8192 + rank * 4096, wm, cb, k0, fb);
                        tma_load_mc(st + 16384 + rank * 4096, wm, cb + 64, k0, fb);
                        if (p == 0) tma_load3_mc(st + 24576 + rank * 4096, rank ? &mp.wu3 : &mp.wg3, j, k0, fb);
                        else tma_load(st, &mp.h2l, k0, m * 128, fb);
                        if (g < 4) mbar_arrive(fb + AF_REL);
                        if (g == 60) prefetch_map(&mp.wd);
                    }
                    r.next();
                }
#pragma unroll 1
                for (int g = 0; g < 56; ++g) {
                    if (g == 0 || (g & 15) == 6 && g > 6) mbar_wait(BAR_ONE(sb, EV_H0 + (g >> 4)), 0);
                    const int k0 = g * 64;
                    mbar_wait(BAR_EMPTY(sb, r.slot), r.par);
                    const uint32_t st = sb + r.slot * SLOT, fb = BAR_FULL(sb, r.slot);
                    if (el) {
                        mbar_expect_tx(fb, 32768);
                        tma_load_mc(st + 16384 + rank * 8192, &mp.wd, j * 128 + rank * 64, k0, fb);
                        tma_load(st, &mp.hb, k0, m * 128, fb); tma_load(st + 8192, &mp.hb, k0, m * 128 + 64, fb);
                    }
                    r.next();
                }
            }
        } else if (aux) {
            if (warp < 11) {
                const uint32_t w = warp - 9;
                const bool el = elect_one();
#pragma unroll 1
                for (int p = 0; p < 4; ++p) {
                    const int mx = (j >> 1) * 8 + p * 2 + rank;
                    if (el) { mbar_arrive(BAR_SREADY(sb, w * 2)); mbar_arrive(BAR_SREADY(sb, w * 2 + 1)); }
                    mbar_wait2(BAR_SFULL(sb, w * 2), BAR_SFULL(sb, w * 2 + 1), p & 1);
                    if (p < 3) pause(HD0);
                    if (el) tma_store(&mp.hb, HC3, mx * 128 + w * 64, sb + OFF_STG + w * 16384);
                    if (p < 3) pause(HP);
                    if (el) {
                        tma_store(&mp.hb, HC3 + 64, mx * 128 + w * 64, sb + OFF_STG + w * 16384 + 8192);
                        bulk_commit(); bulk_wait_fence(); flag_set(g_flags + FL_AUX + mx * 2 + w, ep * 8 + ST_H + 3);
                    }
                }
            }
        } else if (warp == 11) {
            const bool el = elect_one();
            const int row0 = m * 128;
            const uint32_t* const fl = g_flags + FL_PROG + fidx(m, lane >> 4, kof(lane & 15, 1, j) >> 6);
            if (el) { prefetch_map(&mp.h1h); prefetch_map(&mp.h2h); prefetch_map(&mp.h2l); }
            auto gate = [&](int vec, int ev) {
                uint4 v; uint32_t n = 0;
                while (true) {
                    v = ld_pkt2(g_mod + vec * 512 + j * 64 + lane * 2);
                    if (__all_sync(0xffffffffu, v.y == ep && v.w == ep)) break;
                    SPIN_GUARD(n); __nanosleep(300);
                }
                asm volatile("st.shared.v2.u32 [%0], {%1, %2};" :: "r"(sb + OFF_TAB + (ev - EV_GA) * 256 + lane * 8), "r"(v.x), "r"(v.z) : "memory");
                __syncwarp();
                if (lane == 0) mbar_arrive(BAR_ONE(sb, ev));
            };
            {
                const uint4* pk = pt.mail->mod1 + grp * 512 + j * 32 + lane;
                uint4 a, b; uint32_t n = 0;
                mbar_wait(BAR_ONE(sb, EV_WIN3), 0);
                while (true) {
                    a = ld_pkt16(pk); b = ld_pkt16(pk + 256);
                    if (__all_sync(0xffffffffu, a.z == ep && b.z == ep)) break;
                    SPIN_GUARD(n);
                }
                sts128(sb + OFF_PAR + lane * 16, a.x, a.y, b.x, b.y);
                __syncwarp();
                if (lane == 0) { mbar_arrive(BAR_ONE(sb, EV_PAR)); TL(46); }
            }
            mbar_wait(BAR_ONE(sb, EV_P0), 0);
            Ring r{0, 1};
#pragma unroll 1
            for (int ph = 0; ph < 3; ++ph) {
                const int sh = ph == 1 ? 1 : 2, nst = 8 << sh;
                const uint32_t half = 16384 >> sh, target = ep * 8 + ST_H1 + ph;
                const CUtensorMap* tm = ph == 0 ? &mp.h1h : ph == 1 ? &mp.o : &mp.h2h;
                if (ph == 1) gate(2, EV_GA);
                if (ph == 2) {
                    uint32_t n = 0;
                    while ((int32_t)(flag_get(g_flags + FL_LN2) - ep * 8) < 0) { SPIN_GUARD(n); __nanosleep(200); }
                    const uint4 v = __ldcg((const uint4*)(g_par2 + j * 128) + lane);
                    sts128(sb + OFF_PAR + lane * 16, v.x, v.y, v.z, v.w);
                    __syncwarp();
                    if (lane == 0) mbar_arrive(BAR_ONE(sb, EV_LN2));
                }
                const uint32_t lw = ~lane & 1, lt = lane >> 1, ls = (r.slot + lt) % NSLOT, lk = kof(lt, sh, j), lb = BAR_FULL(sb, ls) + (lw ? 0 : AF_REL);
                const uint32_t* const lf = g_flags + FL_PROG + fidx(m, lw, lk >> 6);
                int fr = 1 << sh;
                uint32_t todo = 0x3ffffu >> (2 * fr) << (2 * fr), have = ~todo, n = 0, v = 0;
                r.skip(fr);
#pragma unroll 1
                for (; fr < NSLOT; ++fr) { mbar_wait(BAR_EMPTY(sb, r.slot), r.par); r.next(); }
                if (ph == XST - 1) CS(33);
                do {
                    if (!((have >> lane) & 1)) v = flag_get(lf);
                    while (fr < 9 && mbar_test(BAR_EMPTY(sb, r.slot), r.par)) { ++fr; r.next(); }
                    SPIN_GUARD(n);
                    have |= __ballot_sync(0xffffffffu, (int32_t)(v - target) >= 0);
                    const uint32_t go = have & todo & ((1u << (2 * fr)) - 1);
                    if ((go >> lane) & 1) {
                        if (!lw) mbar_expect_tx(lb, half);
                        tma_load(sb + ls * SLOT + lw * half, tm, lk, row0 + lw * 64, lb);
                    }
                    __syncwarp();
                    if (lane < 2 && (todo & (0x555u << lane)) && !(todo & ~go & (0x555u << lane))) mbar_arrive(BAR_ONE(sb, (lane ? EV_FGO : EV_AGO) + ph));
                    if (ph == XST - 1) { if (go & (1u << (2 << sh))) CS(34); if (go & (2u << (2 << sh))) CS(35); if (todo & 0x555u) CS(36); if (todo & 0xaaau) CS(37); }
                    todo &= ~go;
                } while (~have);
                if (ph == XST - 1) CS(38);
                int k = kof(fr, sh, j);
#pragma unroll 1
                for (; fr < nst; ++fr) {
                    if (fr == 9 || fr == 18) {
                        const uint32_t skip = fr == 9 << (sh - 1) ? 0 : ~0x01fc01fcu;
                        while (~(__ballot_sync(0xffffffffu, (int32_t)(flag_get(fl) - target) >= 0) | skip)) SPIN_GUARD(n);
                    }
                    const uint32_t st = sb + r.slot * SLOT, fb = BAR_FULL(sb, r.slot);
                    mbar_wait(BAR_EMPTY(sb, r.slot), r.par);
                    if (el) {
                        tma_load(st + half, tm, k, row0 + 64, fb);
                        mbar_expect_tx(fb + AF_REL, half);
                        tma_load(st, tm, k, row0, fb + AF_REL);
                    }
                    if (ph == XST - 1 && fr == 9) CS(39);
                    r.next();
                    k = kof(fr + 1, sh, j);
                }
            }
#pragma unroll 1
            for (int p = 0; p < 4; ++p) {
                const uint32_t* f = p < 3 ? fl : g_flags + FL_AUX + m * 2 + (lane & 1);
                uint32_t n = 0;
                while (!__all_sync(0xffffffffu, (int32_t)(flag_get(f) - (ep * 8 + ST_H + p)) >= 0)) { SPIN_GUARD(n); __nanosleep(300); }
                if (el) mbar_arrive(BAR_ONE(sb, EV_H0 + p));
                if (p == 0) gate(5, EV_GB);
            }
        } else {
            const uint32_t w = warp - 9;
            const int row0 = m * 128 + w * 64;
            const uint32_t stg = sb + OFF_STG + w * 16384;
            uint32_t* const fl = g_flags + FL_PROG + fidx(m, w, 2 * j);
            uint32_t b = 0, par = 0;
            const bool el = elect_one();
            auto store = [&](const CUtensorMap* tm, int col, bool nat = false) {
                mbar_wait(BAR_SFULL(sb, w * 2 + b), (par >> b) & 1);
                par ^= 1u << b;
                if (el) {
                    if (nat) tma_store3(tm, col, row0 >> 1, 0, stg + b * 8192); else tma_store(tm, col, row0, stg + b * 8192);
                    bulk_commit();
                }
                b ^= 1;
            };
            auto send2 = [&](const CUtensorMap* tm, const uint32_t* buf, int step) {
                const uint32_t* const q = buf + (size_t)((row0 + lane) * (D_ / 2) + j * 64 + 31);
                store(tm, j * 128);
                if (step == XST) CS(33);
                uint32_t z = landed(el, q, D_ / 2, pt.zero);
                if (el) flag_set(fl, ep * 8 + step + z);
                if (step == XST) CS(34);
                if (step != ST_O) { mbar_wait(BAR_ONE(sb, EV_FGO + step - ST_H1), 0); pause(w ? P1H : P1H + 1000); }
                store(tm, j * 128 + 64);
                if (step == XST) CS(35);
                z = landed(el, q + 32, D_ / 2, pt.zero);
                if (el) flag_set(fl + 1, ep * 8 + step + z);
                if (step == XST) CS(36);
            };
            auto free2 = [&]() { if (el) { mbar_arrive(BAR_SREADY(sb, w * 2)); mbar_arrive(BAR_SREADY(sb, w * 2 + 1)); } };
            if (el) { prefetch_map(&mp.h1s); prefetch_map(&mp.o); prefetch_map(&mp.h2s); prefetch_map(&mp.hb); prefetch_map(&mp.out); prefetch_map(&mp.wo); }
            if (el) { flag_set(fl, ep * 8); flag_set(fl + 1, ep * 8); }
            send2(&mp.h1s, pt.h1, ST_H1);
            if (w == 0) TL(47);
            free2();
            fetch_halo(g_halo + ((m - 1) * 8 + j) * 512 + w * 256 + lane, m == 0, sb, 2 * w, lane);
            send2(&mp.o, pt.o, ST_O);
            if (w == 0) TL(40); else TL(38);
            free2();
            send2(&mp.h2s, pt.o, ST_H2);
            if (el) { prefetch_map(&mp.hb); prefetch_map(&mp.hb3); }
            if (w == 0) TL(37);
            free2();
#pragma unroll 1
            for (int p = 0; p < 3; ++p) {
                const int col = hcol(p, j);
                mbar_wait(BAR_SFULL(sb, w * 2), par & 1);
                pause(w ? HD1 : HD0); store(&mp.hb, col);
                pause(HP); store(&mp.hb, col + 64);
                if (p == 0) {
                    pause(HP);
                    if (el) { tma_store3(&mp.hb3, 0, j, row0, sb + (w ? P3_SLOT1 : P3_SLOT0) * SLOT + 24576); bulk_commit(); }
                }
                if (el) bulk_wait_read();
                free2();
                if (el) { bulk_wait_fence(); flag_set(fl, ep * 8 + ST_H + p); flag_set(fl + 1, ep * 8 + ST_H + p); }
            }
            cluster_arrive_early = true;
            cluster_arrive();
            store(&mp.out, j * 128, true); store(&mp.out, j * 128 + 64, true);
            if (el) bulk_wait_read();
        }
        __syncwarp();
    }
    if (aux || (wg == 2 && !cluster_arrive_early)) cluster_arrive();
    cluster_wait();
    CS(32);
    if (KDEBUG == 5) __syncthreads();
    if (tid == 0) {
        TL(15);
        flag_add(pt.mail->flags + FL_DONE);
    }
}

typedef CUresult (*EncodeFn)(CUtensorMap*, CUtensorMapDataType, cuuint32_t, void*, const cuuint64_t*, const cuuint64_t*, const cuuint32_t*,
                             const cuuint32_t*, CUtensorMapInterleave, CUtensorMapSwizzle, CUtensorMapL2promotion, CUtensorMapFloatOOBfill);

void make_map(EncodeFn fn, CUtensorMap* m, const void* ptr, uint64_t rows, uint64_t cols, uint32_t brows, uint32_t bcols) {
    cuuint64_t dims[2] = {cols, rows}, strides[1] = {cols * 2};
    cuuint32_t box[2] = {bcols, brows}, es[2] = {1, 1};
    fn(m, CU_TENSOR_MAP_DATA_TYPE_BFLOAT16, 2, (void*)ptr, dims, strides, box, es, CU_TENSOR_MAP_INTERLEAVE_NONE,
       bcols == 64 ? CU_TENSOR_MAP_SWIZZLE_128B : bcols == 32 ? CU_TENSOR_MAP_SWIZZLE_64B : CU_TENSOR_MAP_SWIZZLE_NONE, CU_TENSOR_MAP_L2_PROMOTION_L2_256B, CU_TENSOR_MAP_FLOAT_OOB_FILL_NONE);
}

void make_map3(EncodeFn fn, CUtensorMap* m, const void* ptr) {
    cuuint64_t dims[3] = {D_, S_ / 2, 2}, strides[2] = {4 * D_, 2 * D_};
    cuuint32_t box[3] = {64, 32, 2}, es[3] = {1, 1, 1};
    fn(m, CU_TENSOR_MAP_DATA_TYPE_BFLOAT16, 3, (void*)ptr, dims, strides, box, es, CU_TENSOR_MAP_INTERLEAVE_NONE,
       CU_TENSOR_MAP_SWIZZLE_128B, CU_TENSOR_MAP_L2_PROMOTION_L2_256B, CU_TENSOR_MAP_FLOAT_OOB_FILL_NONE);
}

void make_map48(EncodeFn fn, CUtensorMap* m, const void* ptr, uint64_t rows, uint32_t brows) {
    cuuint64_t dims[3] = {48, 8, rows}, strides[2] = {96, 2 * F_};
    cuuint32_t box[3] = {64, 1, brows}, es[3] = {1, 1, 1};
    fn(m, CU_TENSOR_MAP_DATA_TYPE_BFLOAT16, 3, (void*)ptr, dims, strides, box, es, CU_TENSOR_MAP_INTERLEAVE_NONE,
       CU_TENSOR_MAP_SWIZZLE_128B, CU_TENSOR_MAP_L2_PROMOTION_L2_256B, CU_TENSOR_MAP_FLOAT_OOB_FILL_NONE);
}

}

extern "C" void kernel_launch(void* const* d_in, const int* in_sizes, int n_in, void* d_out, int out_size) {
    (void)in_sizes; (void)n_in; (void)out_size;
    void* fnp = nullptr;
    cudaDriverEntryPointQueryResult qr;
    cudaGetDriverEntryPoint("cuTensorMapEncodeTiled", &fnp, cudaEnableDefault, &qr);
    EncodeFn fn = (EncodeFn)fnp;
    void *h1, *o, *h2, *hb, *mail;
    cudaGetSymbolAddress(&h1, g_h1);
    cudaGetSymbolAddress(&mail, g_mail);
    cudaGetSymbolAddress(&o, g_o);
    cudaGetSymbolAddress(&hb, g_hb);
    h2 = o;
    Maps mp;
    make_map(fn, &mp.h1h, h1, S_, D_, 64, 32);
    make_map(fn, &mp.h2h, h2, S_, D_, 64, 32);
    make_map(fn, &mp.h1s, h1, S_, D_, 64, 64);
    make_map(fn, &mp.o, o, S_, D_, 64, 64);
    make_map(fn, &mp.h2l, h2, S_, D_, 128, 32);
    make_map(fn, &mp.h2s, h2, S_, D_, 64, 64);
    make_map(fn, &mp.hb, hb, S_, F_, 64, 64);
    make_map(fn, &mp.wqkv, d_in[1], D_, 3 * D_, 32, 64);
    make_map(fn, &mp.wo, d_in[2], D_, D_, 64, 64);
    make_map(fn, &mp.wg, d_in[4], D_, F_, 32, 64);
    make_map(fn, &mp.wu, d_in[5], D_, F_, 32, 64);
    make_map(fn, &mp.wd, d_in[6], F_, D_, 64, 64);
    make_map(fn, &mp.wmod, d_in[8], D_, 6 * D_, 64, 64);
    make_map(fn, &mp.wm8, d_in[8], D_ / 8, 8 * 6 * D_, 128, 16);
    make_map3(fn, &mp.x, d_in[0]);
    make_map3(fn, &mp.out, d_out);
    make_map48(fn, &mp.wg3, d_in[4], D_, 32);
    make_map48(fn, &mp.wu3, d_in[5], D_, 32);
    make_map48(fn, &mp.hb3, hb, S_, 64);
    cudaFuncSetAttribute(fused_block_kernel, cudaFuncAttributeMaxDynamicSharedMemorySize, SMEM_BYTES);
    cudaLaunchConfig_t cfg = {};
    cfg.gridDim = dim3(NCTA); cfg.blockDim = dim3(384); cfg.dynamicSmemBytes = SMEM_BYTES; cfg.stream = cudaStreamPerThread;
    cudaLaunchAttribute at[1];
    at[0].id = cudaLaunchAttributeClusterDimension; at[0].val.clusterDim.x = 2; at[0].val.clusterDim.y = 1; at[0].val.clusterDim.z = 1;
    cfg.attrs = at; cfg.numAttrs = 1;
    const Ptrs pt{(const __nv_bfloat16*)d_in[7], (Mail*)mail, (const uint32_t*)h1, (const uint32_t*)o, 0};
    cudaLaunchKernelEx(&cfg, fused_block_kernel, pt, mp);
}
```

```cpp
#include <cuda_runtime.h>
#include <cuda_bf16.h>
#include <cuda.h>
#include <stdint.h>
#include <stddef.h>

#define LAG 4
#define LAGS 4
#define LAGW 3
#define LAGQ 4
#define MIDW 2
#define PFWO 12
#define P1H 4000
#define AGW 6
#define CSW 0
#define LWAIT 2
#define BW0 0
#define BWEV EV_WIN
#define BW1 3
#define PDLY 500
#define HD1 5500
#define HD0 5500
#define HP 2200
#define LAGD 4
#define MIDD 5
#define XST ST_O
#define AG0 6
#define AG1 6
#define AG2 8
#define PFG 20
#define PFN 12
#define PFO 0
#define MVE 8
#define KDEBUG 0

namespace {

constexpr int S_ = 2048, D_ = 1024, F_ = 3584;
constexpr int NCTA = 132;
constexpr int NSLOT = 6;
constexpr uint32_t SLOT = 32768;
constexpr uint32_t OFF_STG = NSLOT * SLOT;
constexpr uint32_t OFF_BAR = OFF_STG + 32768;
constexpr uint32_t OFF_PAR = OFF_BAR + 512;
constexpr uint32_t OFF_TAB = OFF_PAR + 768;
constexpr uint32_t OFF_TL = OFF_PAR + 2048;
constexpr uint32_t SMEM_BYTES = OFF_TL + (KDEBUG ? 512 : 0);
constexpr uint32_t P3_SLOT1 = (32 + 16 + 32) % NSLOT, P3_SLOT0 = (P3_SLOT1 + 1) % NSLOT;

constexpr int ST_H1 = 1, ST_O = 2, ST_H2 = 3, ST_H = 4, FL_DONE = 0, FL_LN2 = 1, FL_AUX = 32, FL_PROG = 64;

struct Maps {
    CUtensorMap h1h, h1s, o, h2h, h2l, h2s, hb, wqkv, wo, wg, wu, wd, wmod, wm8, x, out, wg3, wu3, hb3;
};

struct Mail {
    uint32_t flags[16 * 32 + 64];
    uint2 mod[6 * D_ / 2];
    uint4 mod1[8 * 512];
    uint4 st1[128 * 512];
    uint32_t par2[D_];
    uint4 halo[128 * 512];
};
struct Ptrs { const __nv_bfloat16* c; Mail* mail; const uint32_t *h1, *o; uint32_t zero; };

__device__ __align__(128) Mail g_mail;
__device__ __align__(128) __nv_bfloat16 g_h1[S_ * D_];
__device__ __align__(128) __nv_bfloat16 g_o[S_ * D_];
__device__ __align__(128) __nv_bfloat16 g_hb[S_ * F_];
#define TL(i) do {} while (0)
#define TC(i) do {} while (0)
#define TS(g, which) do {} while (0)
#define CS(i) do {} while (0)

__device__ __forceinline__ uint32_t smem_u32(const void* p) { return (uint32_t)__cvta_generic_to_shared(p); }
__device__ __forceinline__ void mbar_init(uint32_t bar, uint32_t cnt) { asm volatile("mbarrier.init.shared::cta.b64 [%0], %1;" :: "r"(bar), "r"(cnt) : "memory"); }
__device__ __forceinline__ void mbar_expect_tx(uint32_t bar, uint32_t bytes) { asm volatile("mbarrier.arrive.expect_tx.shared::cta.b64 _, [%0], %1;" :: "r"(bar), "r"(bytes) : "memory"); }
__device__ __forceinline__ void mbar_arrive(uint32_t bar) { asm volatile("mbarrier.arrive.shared::cta.b64 _, [%0];" :: "r"(bar) : "memory"); }
__device__ __forceinline__ void mbar_arrive_cta(uint32_t bar, uint32_t cta) {
    asm volatile("{\n.reg .b32 r;\nmapa.shared::cluster.u32 r, %0, %1;\nmbarrier.arrive.shared::cluster.b64 _, [r];\n}" :: "r"(bar), "r"(cta) : "memory");
}
__device__ __forceinline__ void mbar_wait(uint32_t bar, uint32_t parity) {
    asm volatile("{\n.reg .pred p;\n.reg .u32 n;\nmov.u32 n, 0;\n"
        "W_LOOP:\nmbarrier.try_wait.parity.shared::cta.b64 p, [%0], %1;\n@p bra W_DONE;\n"
        "add.u32 n, n, 1;\nsetp.lt.u32 p, n, 0x400000;\n@p bra W_LOOP;\ntrap;\nW_DONE:\n}" :: "r"(bar), "r"(parity) : "memory");
}
__device__ __forceinline__ void mbar_wait2(uint32_t b0, uint32_t b1, uint32_t parity) {
    asm volatile("{\n.reg .pred p, q;\n.reg .u32 n;\nmov.u32 n, 0;\n"
        "W_LOOP:\nmbarrier.try_wait.parity.shared::cta.b64 p, [%0], %2;\nmbarrier.try_wait.parity.shared::cta.b64 q, [%1], %2;\nand.pred p, p, q;\n@p bra W_DONE;\n"
        "add.u32 n, n, 1;\nsetp.lt.u32 p, n, 0x400000;\n@p bra W_LOOP;\ntrap;\nW_DONE:\n}" :: "r"(b0), "r"(b1), "r"(parity) : "memory");
}
__device__ __forceinline__ bool mbar_test(uint32_t bar, uint32_t parity) {
    uint32_t r; asm volatile("{\n.reg .pred p;\nmbarrier.test_wait.parity.shared::cta.b64 p, [%1], %2;\nselp.u32 %0, 1, 0, p;\n}" : "=r"(r) : "r"(bar), "r"(parity) : "memory"); return r;
}
__device__ __forceinline__ bool mbar_test2(uint32_t b0, uint32_t b1, uint32_t parity) {
    uint32_t r;
    asm volatile("{\n.reg .pred p, q;\nmbarrier.test_wait.parity.shared::cta.b64 p, [%1], %3;\nmbarrier.test_wait.parity.shared::cta.b64 q, [%2], %3;\n"
        "and.pred p, p, q;\nselp.u32 %0, 1, 0, p;\n}" : "=r"(r) : "r"(b0), "r"(b1), "r"(parity) : "memory");
    return r;
}
__device__ __forceinline__ void tma_load3(uint32_t dst, const CUtensorMap* m, int c0, int c1, uint32_t bar) {
    asm volatile("cp.async.bulk.tensor.3d.shared::cluster.global.mbarrier::complete_tx::bytes [%0], [%1, {%3, %4, %5}], [%2];"
        :: "r"(dst), "l"(m), "r"(bar), "r"(c0), "r"(c1), "r"(0) : "memory");
}
__device__ __forceinline__ void tma_store3(const CUtensorMap* m, int c0, int c1, int c2, uint32_t src) {
    asm volatile("cp.async.bulk.tensor.3d.global.shared::cta.bulk_group [%0, {%2, %3, %4}], [%1];" :: "l"(m), "r"(src), "r"(c0), "r"(c1), "r"(c2) : "memory");
}
__device__ __forceinline__ void tma_load3_mc(uint32_t dst, const CUtensorMap* m, int c1, int c2, uint32_t bar) {
    asm volatile("cp.async.bulk.tensor.3d.shared::cluster.global.mbarrier::complete_tx::bytes.multicast::cluster.L2::cache_hint [%0], [%1, {%3, %4, %5}], [%2], %6, %7;"
        :: "r"(dst), "l"(m), "r"(bar), "r"(0), "r"(c1), "r"(c2), "h"((uint16_t)3), "l"(0x12F0000000000000ull) : "memory");
}
__device__ __forceinline__ void tma_load(uint32_t dst, const CUtensorMap* m, int c0, int c1, uint32_t bar) {
    asm volatile("cp.async.bulk.tensor.2d.shared::cluster.global.mbarrier::complete_tx::bytes [%0], [%1, {%3, %4}], [%2];"
        :: "r"(dst), "l"(m), "r"(bar), "r"(c0), "r"(c1) : "memory");
}
__device__ __forceinline__ void tma_load_mc(uint32_t dst, const CUtensorMap* m, int c0, int c1, uint32_t bar) {
    asm volatile("cp.async.bulk.tensor.2d.shared::cluster.global.mbarrier::complete_tx::bytes.multicast::cluster.L2::cache_hint [%0], [%1, {%3, %4}], [%2], %5, %6;"
        :: "r"(dst), "l"(m), "r"(bar), "r"(c0), "r"(c1), "h"((uint16_t)3), "l"(0x12F0000000000000ull) : "memory");
}
__device__ __forceinline__ void tma_prefetch(const CUtensorMap* m, int c0, int c1) {
    asm volatile("cp.async.bulk.prefetch.tensor.2d.L2.global [%0, {%1, %2}];" :: "l"(m), "r"(c0), "r"(c1) : "memory");
}
__device__ __forceinline__ void tma_store(const CUtensorMap* m, int c0, int c1, uint32_t src) {
    asm volatile("cp.async.bulk.tensor.2d.global.shared::cta.bulk_group [%0, {%2, %3}], [%1];" :: "l"(m), "r"(src), "r"(c0), "r"(c1) : "memory");
}
__device__ __forceinline__ void bulk_commit() { asm volatile("cp.async.bulk.commit_group;" ::: "memory"); }
__device__ __forceinline__ void bulk_wait_read() { asm volatile("cp.async.bulk.wait_group.read 0;" ::: "memory"); }
__device__ __forceinline__ void fence_async_smem() { asm volatile("fence.proxy.async.shared::cta;" ::: "memory"); }
__device__ __forceinline__ void prefetch_map(const CUtensorMap* m) { asm volatile("prefetch.tensormap [%0];" :: "l"(m) : "memory"); }
__device__ __forceinline__ void wg_fence() { asm volatile("wgmma.fence.sync.aligned;" ::: "memory"); }
__device__ __forceinline__ void wg_commit() { asm volatile("wgmma.commit_group.sync.aligned;" ::: "memory"); }
template <int N> __device__ __forceinline__ void wg_wait() { asm volatile("wgmma.wait_group.sync.aligned %0;" :: "n"(N) : "memory"); }
__device__ __forceinline__ void bar_sync(int id, int n) { asm volatile("bar.sync %0, %1;" :: "r"(id), "r"(n) : "memory"); }
__device__ __forceinline__ void bar_arrive(int id, int n) { asm volatile("bar.arrive %0, %1;" :: "r"(id), "r"(n) : "memory"); }
__device__ __forceinline__ void flag_add(uint32_t* f) { asm volatile("red.relaxed.gpu.global.add.u32 [%0], 1;" :: "l"(f) : "memory"); }
__device__ __forceinline__ void flag_set(uint32_t* f, uint32_t v) { asm volatile("red.relaxed.gpu.global.max.u32 [%0], %1;" :: "l"(f), "r"(v) : "memory"); }
__device__ __forceinline__ uint32_t flag_get(const uint32_t* f) { uint32_t v; asm volatile("ld.relaxed.gpu.global.u32 %0, [%1];" : "=r"(v) : "l"(f) : "memory"); return v; }
__device__ __forceinline__ void bulk_wait_fence() { asm volatile("cp.async.bulk.wait_group 0;\nfence.proxy.async.global;\nfence.acq_rel.gpu;" ::: "memory"); }
__device__ __forceinline__ uint32_t landed(bool el, const uint32_t* p, uint32_t pitch, uint32_t zero) {
    if (el) asm volatile("cp.async.bulk.wait_group 0;" ::: "memory");
    __syncwarp();
    const uint32_t a = flag_get(p), b = flag_get(p + 32 * pitch);
    return __reduce_or_sync(0xffffffffu, (a | b) & zero);
}
__device__ __forceinline__ uint32_t d16(uint32_t addr) { return (addr & 0x3FFFF) >> 4; }
__device__ __forceinline__ uint64_t mk_desc(uint32_t a16, uint32_t off, uint32_t lbo, uint32_t sbo, uint32_t swz) {
    const uint32_t lo = a16 + (off >> 4) + ((lbo >> 4) << 16), hi = (sbo >> 4) | (swz << 30);
    return ((uint64_t)hi << 32) | lo;
}
__device__ __forceinline__ uint32_t pack2(float lo, float hi) {
    uint32_t r; asm("cvt.rn.bf16x2.f32 %0, %1, %2;" : "=r"(r) : "f"(hi), "f"(lo)); return r;
}
__device__ __forceinline__ uint32_t hfma2_bf16(uint32_t a, uint32_t b, uint32_t c) {
    uint32_t r; asm("fma.rn.bf16x2 %0, %1, %2, %3;" : "=r"(r) : "r"(a), "r"(b), "r"(c)); return r;
}
__device__ __forceinline__ float bf_lo(uint32_t v) { return __uint_as_float(v << 16); }
__device__ __forceinline__ float bf_hi(uint32_t v) { return __uint_as_float(v & 0xFFFF0000u); }
__device__ __forceinline__ void unpack2(uint32_t v, float& lo, float& hi) {
    asm volatile("shl.b32 %0, %2, 16;\nand.b32 %1, %2, 0xffff0000;" : "=f"(lo), "=f"(hi) : "r"(v));
}
__device__ __forceinline__ float bf_round(float x) { return __bfloat162float(__float2bfloat16_rn(x)); }
__device__ __forceinline__ void stsm4(uint32_t addr, uint32_t r0, uint32_t r1, uint32_t r2, uint32_t r3) {
    asm volatile("stmatrix.sync.aligned.m8n8.x4.shared.b16 [%0], {%1, %2, %3, %4};" :: "r"(addr), "r"(r0), "r"(r1), "r"(r2), "r"(r3) : "memory");
}
__device__ __forceinline__ void stsm4t(uint32_t addr, uint32_t r0, uint32_t r1, uint32_t r2, uint32_t r3) {
    asm volatile("stmatrix.sync.aligned.m8n8.x4.trans.shared.b16 [%0], {%1, %2, %3, %4};" :: "r"(addr), "r"(r0), "r"(r1), "r"(r2), "r"(r3) : "memory");
}
__device__ __forceinline__ uint32_t movm(uint32_t a) { uint32_t d; asm volatile("movmatrix.sync.aligned.m8n8.trans.b16 %0, %1;" : "=r"(d) : "r"(a)); return d; }
__device__ __forceinline__ void ldsm4(uint32_t addr, uint32_t& r0, uint32_t& r1, uint32_t& r2, uint32_t& r3) {
    asm volatile("ldmatrix.sync.aligned.m8n8.x4.shared.b16 {%0, %1, %2, %3}, [%4];" : "=r"(r0), "=r"(r1), "=r"(r2), "=r"(r3) : "r"(addr) : "memory");
}
__device__ __forceinline__ void ldsm4t(uint32_t addr, uint32_t& r0, uint32_t& r1, uint32_t& r2, uint32_t& r3) {
    asm volatile("ldmatrix.sync.aligned.m8n8.x4.trans.shared.b16 {%0, %1, %2, %3}, [%4];" : "=r"(r0), "=r"(r1), "=r"(r2), "=r"(r3) : "r"(addr) : "memory");
}
__device__ __forceinline__ void mma16816(float (&c)[4], uint32_t a0, uint32_t a1, uint32_t a2, uint32_t a3, uint32_t b0, uint32_t b1) {
    asm("mma.sync.aligned.m16n8k16.row.col.f32.bf16.bf16.f32 {%0, %1, %2, %3}, {%4, %5, %6, %7}, {%8, %9}, {%0, %1, %2, %3};"
        : "+f"(c[0]), "+f"(c[1]), "+f"(c[2]), "+f"(c[3]) : "r"(a0), "r"(a1), "r"(a2), "r"(a3), "r"(b0), "r"(b1));
}
__device__ __forceinline__ float rcp(float x) { float r; asm("rcp.approx.ftz.f32 %0, %1;" : "=f"(r) : "f"(x)); return r; }
__device__ __forceinline__ float ex2(float x) { float r; asm("ex2.approx.ftz.f32 %0, %1;" : "=f"(r) : "f"(x)); return r; }
__device__ __forceinline__ float tanh_(float x) { float t; asm("tanh.approx.f32 %0, %1;" : "=f"(t) : "f"(x)); return t; }
__device__ __forceinline__ void block_end(uint32_t opaque, uint32_t id) { asm volatile("{\n.reg .pred p;\nsetp.eq.u32 p, %0, %1;\n@p trap;\n}" :: "r"(opaque), "r"(0xffffff00u + id)); }
__device__ __forceinline__ float silu_(float x) { return __fdividef(x, 1.f + __expf(-x)); }
__device__ __forceinline__ void st_pkt(void* p, uint32_t a, uint32_t b) {
    asm volatile("{\n.reg .b64 t;\nmov.b64 t, {%1, %2};\nst.relaxed.gpu.global.b64 [%0], t;\n}" :: "l"(p), "r"(a), "r"(b) : "memory");
}
__device__ __forceinline__ uint4 ld_pkt2(const void* p) {
    uint4 v; asm volatile("{\n.reg .b64 t, u;\nld.relaxed.gpu.global.v2.b64 {t, u}, [%4];\nmov.b64 {%0, %1}, t;\nmov.b64 {%2, %3}, u;\n}"
        : "=r"(v.x), "=r"(v.y), "=r"(v.z), "=r"(v.w) : "l"(p) : "memory"); return v;
}
__device__ __forceinline__ void st_pkt16(void* p, uint32_t a, uint32_t b, uint32_t c, uint32_t d) {
    asm volatile("{\n.reg .b64 t, u;\n.reg .b128 w;\nmov.b64 t, {%1, %2};\nmov.b64 u, {%3, %4};\nmov.b128 w, {t, u};\nst.relaxed.gpu.global.b128 [%0], w;\n}"
        :: "l"(p), "r"(a), "r"(b), "r"(c), "r"(d) : "memory");
}
__device__ __forceinline__ uint4 ld_pkt16(const void* p) {
    uint4 v; asm volatile("{\n.reg .b64 t, u;\n.reg .b128 w;\nld.relaxed.gpu.global.b128 w, [%4];\nmov.b128 {t, u}, w;\nmov.b64 {%0, %1}, t;\nmov.b64 {%2, %3}, u;\n}"
        : "=r"(v.x), "=r"(v.y), "=r"(v.z), "=r"(v.w) : "l"(p) : "memory"); return v;
}
#define SPIN_GUARD(n) do { if (++(n) > (1u << 22)) asm volatile("trap;"); } while (0)
__device__ __forceinline__ uint4 lds128(uint32_t a) { uint4 v; asm volatile("ld.shared.v4.u32 {%0, %1, %2, %3}, [%4];" : "=r"(v.x), "=r"(v.y), "=r"(v.z), "=r"(v.w) : "r"(a) : "memory"); return v; }
__device__ __forceinline__ void sts128(uint32_t a, uint32_t x, uint32_t y, uint32_t z, uint32_t w) { asm volatile("st.shared.v4.u32 [%0], {%1, %2, %3, %4};" :: "r"(a), "r"(x), "r"(y), "r"(z), "r"(w) : "memory"); }
__device__ __forceinline__ uint32_t lds32(uint32_t a) { uint32_t v; asm volatile("ld.shared.u32 %0, [%1];" : "=r"(v) : "r"(a) : "memory"); return v; }
__device__ __forceinline__ void sts32(uint32_t a, uint32_t v) { asm volatile("st.shared.u32 [%0], %1;" :: "r"(a), "r"(v) : "memory"); }
__device__ __forceinline__ bool elect_one() {
    uint32_t p; asm volatile("{\n.reg .pred q;\nelect.sync _|q, 0xffffffff;\nselp.u32 %0, 1, 0, q;\n}" : "=r"(p)); return p;
}
__device__ __forceinline__ void pause(uint32_t cycles) {
    uint32_t t0, t; asm volatile("mov.u32 %0, %%clock;" : "=r"(t0));
    do { __nanosleep(64); asm volatile("mov.u32 %0, %%clock;" : "=r"(t)); } while (t - t0 < cycles);
}
__device__ __forceinline__ void cluster_arrive() { asm volatile("barrier.cluster.arrive.relaxed.aligned;" ::: "memory"); }
__device__ __forceinline__ void cluster_wait() { asm volatile("barrier.cluster.wait.aligned;" ::: "memory"); }

__device__ __forceinline__ void wgmma_n128_z(float (&d)[64], uint64_t da, uint64_t db) {
    asm volatile("{\n.reg .pred p;\nsetp.ne.b32 p, 0, 0;\n"
        "wgmma.mma_async.sync.aligned.m64n128k16.f32.bf16.bf16 {"
        "%0, %1, %2, %3, %4, %5, %6, %7, %8, %9, %10, %11, %12, %13, %14, %15, "
        "%16, %17, %18, %19, %20, %21, %22, %23, %24, %25, %26, %27, %28, %29, %30, %31, "
        "%32, %33, %34, %35, %36, %37, %38, %39, %40, %41, %42, %43, %44, %45, %46, %47, "
        "%48, %49, %50, %51, %52, %53, %54, %55, %56, %57, %58, %59, %60, %61, %62, %63"
        "}, %64, %65, p, 1, 1, 0, 1;\n}\n"
        : "=f"(d[0]), "=f"(d[1]), "=f"(d[2]), "=f"(d[3]), "=f"(d[4]), "=f"(d[5]), "=f"(d[6]), "=f"(d[7]),
          "=f"(d[8]), "=f"(d[9]), "=f"(d[10]), "=f"(d[11]), "=f"(d[12]), "=f"(d[13]), "=f"(d[14]), "=f"(d[15]),
          "=f"(d[16]), "=f"(d[17]), "=f"(d[18]), "=f"(d[19]), "=f"(d[20]), "=f"(d[21]), "=f"(d[22]), "=f"(d[23]),
          "=f"(d[24]), "=f"(d[25]), "=f"(d[26]), "=f"(d[27]), "=f"(d[28]), "=f"(d[29]), "=f"(d[30]), "=f"(d[31]),
          "=f"(d[32]), "=f"(d[33]), "=f"(d[34]), "=f"(d[35]), "=f"(d[36]), "=f"(d[37]), "=f"(d[38]), "=f"(d[39]),
          "=f"(d[40]), "=f"(d[41]), "=f"(d[42]), "=f"(d[43]), "=f"(d[44]), "=f"(d[45]), "=f"(d[46]), "=f"(d[47]),
          "=f"(d[48]), "=f"(d[49]), "=f"(d[50]), "=f"(d[51]), "=f"(d[52]), "=f"(d[53]), "=f"(d[54]), "=f"(d[55]),
          "=f"(d[56]), "=f"(d[57]), "=f"(d[58]), "=f"(d[59]), "=f"(d[60]), "=f"(d[61]), "=f"(d[62]), "=f"(d[63])
        : "l"(da), "l"(db));
}
__device__ __forceinline__ void wgmma_n128(float (&d)[64], uint64_t da, uint64_t db) {
    asm volatile("{\n.reg .pred p;\nsetp.eq.b32 p, 0, 0;\n"
        "wgmma.mma_async.sync.aligned.m64n128k16.f32.bf16.bf16 {"
        "%0, %1, %2, %3, %4, %5, %6, %7, %8, %9, %10, %11, %12, %13, %14, %15, "
        "%16, %17, %18, %19, %20, %21, %22, %23, %24, %25, %26, %27, %28, %29, %30, %31, "
        "%32, %33, %34, %35, %36, %37, %38, %39, %40, %41, %42, %43, %44, %45, %46, %47, "
        "%48, %49, %50, %51, %52, %53, %54, %55, %56, %57, %58, %59, %60, %61, %62, %63"
        "}, %64, %65, p, 1, 1, 0, 1;\n}\n"
        : "+f"(d[0]), "+f"(d[1]), "+f"(d[2]), "+f"(d[3]), "+f"(d[4]), "+f"(d[5]), "+f"(d[6]), "+f"(d[7]),
          "+f"(d[8]), "+f"(d[9]), "+f"(d[10]), "+f"(d[11]), "+f"(d[12]), "+f"(d[13]), "+f"(d[14]), "+f"(d[15]),
          "+f"(d[16]), "+f"(d[17]), "+f"(d[18]), "+f"(d[19]), "+f"(d[20]), "+f"(d[21]), "+f"(d[22]), "+f"(d[23]),
          "+f"(d[24]), "+f"(d[25]), "+f"(d[26]), "+f"(d[27]), "+f"(d[28]), "+f"(d[29]), "+f"(d[30]), "+f"(d[31]),
          "+f"(d[32]), "+f"(d[33]), "+f"(d[34]), "+f"(d[35]), "+f"(d[36]), "+f"(d[37]), "+f"(d[38]), "+f"(d[39]),
          "+f"(d[40]), "+f"(d[41]), "+f"(d[42]), "+f"(d[43]), "+f"(d[44]), "+f"(d[45]), "+f"(d[46]), "+f"(d[47]),
          "+f"(d[48]), "+f"(d[49]), "+f"(d[50]), "+f"(d[51]), "+f"(d[52]), "+f"(d[53]), "+f"(d[54]), "+f"(d[55]),
          "+f"(d[56]), "+f"(d[57]), "+f"(d[58]), "+f"(d[59]), "+f"(d[60]), "+f"(d[61]), "+f"(d[62]), "+f"(d[63])
        : "l"(da), "l"(db));
}
__device__ __forceinline__ void wgmma_n176_z(float (&d)[88], uint64_t da, uint64_t db) {
    asm volatile("{\n.reg .pred p;\nsetp.ne.b32 p, 0, 0;\n"
        "wgmma.mma_async.sync.aligned.m64n176k16.f32.bf16.bf16 {"
        "%0, %1, %2, %3, %4, %5, %6, %7, %8, %9, %10, %11, %12, %13, %14, %15, "
        "%16, %17, %18, %19, %20, %21, %22, %23, %24, %25, %26, %27, %28, %29, %30, %31, "
        "%32, %33, %34, %35, %36, %37, %38, %39, %40, %41, %42, %43, %44, %45, %46, %47, "
        "%48, %49, %50, %51, %52, %53, %54, %55, %56, %57, %58, %59, %60, %61, %62, %63, "
        "%64, %65, %66, %67, %68, %69, %70, %71, %72, %73, %74, %75, %76, %77, %78, %79, "
        "%80, %81, %82, %83, %84, %85, %86, %87"
        "}, %88, %89, p, 1, 1, 0, 1;\n}\n"
        : "=f"(d[0]), "=f"(d[1]), "=f"(d[2]), "=f"(d[3]), "=f"(d[4]), "=f"(d[5]), "=f"(d[6]), "=f"(d[7]),
          "=f"(d[8]), "=f"(d[9]), "=f"(d[10]), "=f"(d[11]), "=f"(d[12]), "=f"(d[13]), "=f"(d[14]), "=f"(d[15]),
          "=f"(d[16]), "=f"(d[17]), "=f"(d[18]), "=f"(d[19]), "=f"(d[20]), "=f"(d[21]), "=f"(d[22]), "=f"(d[23]),
          "=f"(d[24]), "=f"(d[25]), "=f"(d[26]), "=f"(d[27]), "=f"(d[28]), "=f"(d[29]), "=f"(d[30]), "=f"(d[31]),
          "=f"(d[32]), "=f"(d[33]), "=f"(d[34]), "=f"(d[35]), "=f"(d[36]), "=f"(d[37]), "=f"(d[38]), "=f"(d[39]),
          "=f"(d[40]), "=f"(d[41]), "=f"(d[42]), "=f"(d[43]), "=f"(d[44]), "=f"(d[45]), "=f"(d[46]), "=f"(d[47]),
          "=f"(d[48]), "=f"(d[49]), "=f"(d[50]), "=f"(d[51]), "=f"(d[52]), "=f"(d[53]), "=f"(d[54]), "=f"(d[55]),
          "=f"(d[56]), "=f"(d[57]), "=f"(d[58]), "=f"(d[59]), "=f"(d[60]), "=f"(d[61]), "=f"(d[62]), "=f"(d[63]),
          "=f"(d[64]), "=f"(d[65]), "=f"(d[66]), "=f"(d[67]), "=f"(d[68]), "=f"(d[69]), "=f"(d[70]), "=f"(d[71]),
          "=f"(d[72]), "=f"(d[73]), "=f"(d[74]), "=f"(d[75]), "=f"(d[76]), "=f"(d[77]), "=f"(d[78]), "=f"(d[79]),
          "=f"(d[80]), "=f"(d[81]), "=f"(d[82]), "=f"(d[83]), "=f"(d[84]), "=f"(d[85]), "=f"(d[86]), "=f"(d[87])
        : "l"(da), "l"(db));
}
__device__ __forceinline__ void wgmma_n176(float (&d)[88], uint64_t da, uint64_t db) {
    asm volatile("{\n.reg .pred p;\nsetp.eq.b32 p, 0, 0;\n"
        "wgmma.mma_async.sync.aligned.m64n176k16.f32.bf16.bf16 {"
        "%0, %1, %2, %3, %4, %5, %6, %7, %8, %9, %10, %11, %12, %13, %14, %15, "
        "%16, %17, %18, %19, %20, %21, %22, %23, %24, %25, %26, %27, %28, %29, %30, %31, "
        "%32, %33, %34, %35, %36, %37, %38, %39, %40, %41, %42, %43, %44, %45, %46, %47, "
        "%48, %49, %50, %51, %52, %53, %54, %55, %56, %57, %58, %59, %60, %61, %62, %63, "
        "%64, %65, %66, %67, %68, %69, %70, %71, %72, %73, %74, %75, %76, %77, %78, %79, "
        "%80, %81, %82, %83, %84, %85, %86, %87"
        "}, %88, %89, p, 1, 1, 0, 1;\n}\n"
        : "+f"(d[0]), "+f"(d[1]), "+f"(d[2]), "+f"(d[3]), "+f"(d[4]), "+f"(d[5]), "+f"(d[6]), "+f"(d[7]),
          "+f"(d[8]), "+f"(d[9]), "+f"(d[10]), "+f"(d[11]), "+f"(d[12]), "+f"(d[13]), "+f"(d[14]), "+f"(d[15]),
          "+f"(d[16]), "+f"(d[17]), "+f"(d[18]), "+f"(d[19]), "+f"(d[20]), "+f"(d[21]), "+f"(d[22]), "+f"(d[23]),
          "+f"(d[24]), "+f"(d[25]), "+f"(d[26]), "+f"(d[27]), "+f"(d[28]), "+f"(d[29]), "+f"(d[30]), "+f"(d[31]),
          "+f"(d[32]), "+f"(d[33]), "+f"(d[34]), "+f"(d[35]), "+f"(d[36]), "+f"(d[37]), "+f"(d[38]), "+f"(d[39]),
          "+f"(d[40]), "+f"(d[41]), "+f"(d[42]), "+f"(d[43]), "+f"(d[44]), "+f"(d[45]), "+f"(d[46]), "+f"(d[47]),
          "+f"(d[48]), "+f"(d[49]), "+f"(d[50]), "+f"(d[51]), "+f"(d[52]), "+f"(d[53]), "+f"(d[54]), "+f"(d[55]),
          "+f"(d[56]), "+f"(d[57]), "+f"(d[58]), "+f"(d[59]), "+f"(d[60]), "+f"(d[61]), "+f"(d[62]), "+f"(d[63]),
          "+f"(d[64]), "+f"(d[65]), "+f"(d[66]), "+f"(d[67]), "+f"(d[68]), "+f"(d[69]), "+f"(d[70]), "+f"(d[71]),
          "+f"(d[72]), "+f"(d[73]), "+f"(d[74]), "+f"(d[75]), "+f"(d[76]), "+f"(d[77]), "+f"(d[78]), "+f"(d[79]),
          "+f"(d[80]), "+f"(d[81]), "+f"(d[82]), "+f"(d[83]), "+f"(d[84]), "+f"(d[85]), "+f"(d[86]), "+f"(d[87])
        : "l"(da), "l"(db));
}
__device__ __forceinline__ void wgmma_n256_z(float (&d)[128], uint64_t da, uint64_t db) {
    asm volatile("{\n.reg .pred p;\nsetp.ne.b32 p, 0, 0;\n"
        "wgmma.mma_async.sync.aligned.m64n256k16.f32.bf16.bf16 {"
        "%0, %1, %2, %3, %4, %5, %6, %7, %8, %9, %10, %11, %12, %13, %14, %15, "
        "%16, %17, %18, %19, %20, %21, %22, %23, %24, %25, %26, %27, %28, %29, %30, %31, "
        "%32, %33, %34, %35, %36, %37, %38, %39, %40, %41, %42, %43, %44, %45, %46, %47, "
        "%48, %49, %50, %51, %52, %53, %54, %55, %56, %57, %58, %59, %60, %61, %62, %63, "
        "%64, %65, %66, %67, %68, %69, %70, %71, %72, %73, %74, %75, %76, %77, %78, %79, "
        "%80, %81, %82, %83, %84, %85, %86, %87, %88, %89, %90, %91, %92, %93, %94, %95, "
        "%96, %97, %98, %99, %100, %101, %102, %103, %104, %105, %106, %107, %108, %109, %110, %111, "
        "%112, %113, %114, %115, %116, %117, %118, %119, %120, %121, %122, %123, %124, %125, %126, %127"
        "}, %128, %129, p, 1, 1, 0, 1;\n}\n"
        : "=f"(d[0]), "=f"(d[1]), "=f"(d[2]), "=f"(d[3]), "=f"(d[4]), "=f"(d[5]), "=f"(d[6]), "=f"(d[7]),
          "=f"(d[8]), "=f"(d[9]), "=f"(d[10]), "=f"(d[11]), "=f"(d[12]), "=f"(d[13]), "=f"(d[14]), "=f"(d[15]),
          "=f"(d[16]), "=f"(d[17]), "=f"(d[18]), "=f"(d[19]), "=f"(d[20]), "=f"(d[21]), "=f"(d[22]), "=f"(d[23]),
          "=f"(d[24]), "=f"(d[25]), "=f"(d[26]), "=f"(d[27]), "=f"(d[28]), "=f"(d[29]), "=f"(d[30]), "=f"(d[31]),
          "=f"(d[32]), "=f"(d[33]), "=f"(d[34]), "=f"(d[35]), "=f"(d[36]), "=f"(d[37]), "=f"(d[38]), "=f"(d[39]),
          "=f"(d[40]), "=f"(d[41]), "=f"(d[42]), "=f"(d[43]), "=f"(d[44]), "=f"(d[45]), "=f"(d[46]), "=f"(d[47]),
          "=f"(d[48]), "=f"(d[49]), "=f"(d[50]), "=f"(d[51]), "=f"(d[52]), "=f"(d[53]), "=f"(d[54]), "=f"(d[55]),
          "=f"(d[56]), "=f"(d[57]), "=f"(d[58]), "=f"(d[59]), "=f"(d[60]), "=f"(d[61]), "=f"(d[62]), "=f"(d[63]),
          "=f"(d[64]), "=f"(d[65]), "=f"(d[66]), "=f"(d[67]), "=f"(d[68]), "=f"(d[69]), "=f"(d[70]), "=f"(d[71]),
          "=f"(d[72]), "=f"(d[73]), "=f"(d[74]), "=f"(d[75]), "=f"(d[76]), "=f"(d[77]), "=f"(d[78]), "=f"(d[79]),
          "=f"(d[80]), "=f"(d[81]), "=f"(d[82]), "=f"(d[83]), "=f"(d[84]), "=f"(d[85]), "=f"(d[86]), "=f"(d[87]),
          "=f"(d[88]), "=f"(d[89]), "=f"(d[90]), "=f"(d[91]), "=f"(d[92]), "=f"(d[93]), "=f"(d[94]), "=f"(d[95]),
          "=f"(d[96]), "=f"(d[97]), "=f"(d[98]), "=f"(d[99]), "=f"(d[100]), "=f"(d[101]), "=f"(d[102]), "=f"(d[103]),
          "=f"(d[104]), "=f"(d[105]), "=f"(d[106]), "=f"(d[107]), "=f"(d[108]), "=f"(d[109]), "=f"(d[110]), "=f"(d[111]),
          "=f"(d[112]), "=f"(d[113]), "=f"(d[114]), "=f"(d[115]), "=f"(d[116]), "=f"(d[117]), "=f"(d[118]), "=f"(d[119]),
          "=f"(d[120]), "=f"(d[121]), "=f"(d[122]), "=f"(d[123]), "=f"(d[124]), "=f"(d[125]), "=f"(d[126]), "=f"(d[127])
        : "l"(da), "l"(db));
}
__device__ __forceinline__ void wgmma_n256(float (&d)[128], uint64_t da, uint64_t db) {
    asm volatile("{\n.reg .pred p;\nsetp.eq.b32 p, 0, 0;\n"
        "wgmma.mma_async.sync.aligned.m64n256k16.f32.bf16.bf16 {"
        "%0, %1, %2, %3, %4, %5, %6, %7, %8, %9, %10, %11, %12, %13, %14, %15, "
        "%16, %17, %18, %19, %20, %21, %22, %23, %24, %25, %26, %27, %28, %29, %30, %31, "
        "%32, %33, %34, %35, %36, %37, %38, %39, %40, %41, %42, %43, %44, %45, %46, %47, "
        "%48, %49, %50, %51, %52, %53, %54, %55, %56, %57, %58, %59, %60, %61, %62, %63, "
        "%64, %65, %66, %67, %68, %69, %70, %71, %72, %73, %74, %75, %76, %77, %78, %79, "
        "%80, %81, %82, %83, %84, %85, %86, %87, %88, %89, %90, %91, %92, %93, %94, %95, "
        "%96, %97, %98, %99, %100, %101, %102, %103, %104, %105, %106, %107, %108, %109, %110, %111, "
        "%112, %113, %114, %115, %116, %117, %118, %119, %120, %121, %122, %123, %124, %125, %126, %127"
        "}, %128, %129, p, 1, 1, 0, 1;\n}\n"
        : "+f"(d[0]), "+f"(d[1]), "+f"(d[2]), "+f"(d[3]), "+f"(d[4]), "+f"(d[5]), "+f"(d[6]), "+f"(d[7]),
          "+f"(d[8]), "+f"(d[9]), "+f"(d[10]), "+f"(d[11]), "+f"(d[12]), "+f"(d[13]), "+f"(d[14]), "+f"(d[15]),
          "+f"(d[16]), "+f"(d[17]), "+f"(d[18]), "+f"(d[19]), "+f"(d[20]), "+f"(d[21]), "+f"(d[22]), "+f"(d[23]),
          "+f"(d[24]), "+f"(d[25]), "+f"(d[26]), "+f"(d[27]), "+f"(d[28]), "+f"(d[29]), "+f"(d[30]), "+f"(d[31]),
          "+f"(d[32]), "+f"(d[33]), "+f"(d[34]), "+f"(d[35]), "+f"(d[36]), "+f"(d[37]), "+f"(d[38]), "+f"(d[39]),
          "+f"(d[40]), "+f"(d[41]), "+f"(d[42]), "+f"(d[43]), "+f"(d[44]), "+f"(d[45]), "+f"(d[46]), "+f"(d[47]),
          "+f"(d[48]), "+f"(d[49]), "+f"(d[50]), "+f"(d[51]), "+f"(d[52]), "+f"(d[53]), "+f"(d[54]), "+f"(d[55]),
          "+f"(d[56]), "+f"(d[57]), "+f"(d[58]), "+f"(d[59]), "+f"(d[60]), "+f"(d[61]), "+f"(d[62]), "+f"(d[63]),
          "+f"(d[64]), "+f"(d[65]), "+f"(d[66]), "+f"(d[67]), "+f"(d[68]), "+f"(d[69]), "+f"(d[70]), "+f"(d[71]),
          "+f"(d[72]), "+f"(d[73]), "+f"(d[74]), "+f"(d[75]), "+f"(d[76]), "+f"(d[77]), "+f"(d[78]), "+f"(d[79]),
          "+f"(d[80]), "+f"(d[81]), "+f"(d[82]), "+f"(d[83]), "+f"(d[84]), "+f"(d[85]), "+f"(d[86]), "+f"(d[87]),
          "+f"(d[88]), "+f"(d[89]), "+f"(d[90]), "+f"(d[91]), "+f"(d[92]), "+f"(d[93]), "+f"(d[94]), "+f"(d[95]),
          "+f"(d[96]), "+f"(d[97]), "+f"(d[98]), "+f"(d[99]), "+f"(d[100]), "+f"(d[101]), "+f"(d[102]), "+f"(d[103]),
          "+f"(d[104]), "+f"(d[105]), "+f"(d[106]), "+f"(d[107]), "+f"(d[108]), "+f"(d[109]), "+f"(d[110]), "+f"(d[111]),
          "+f"(d[112]), "+f"(d[113]), "+f"(d[114]), "+f"(d[115]), "+f"(d[116]), "+f"(d[117]), "+f"(d[118]), "+f"(d[119]),
          "+f"(d[120]), "+f"(d[121]), "+f"(d[122]), "+f"(d[123]), "+f"(d[124]), "+f"(d[125]), "+f"(d[126]), "+f"(d[127])
        : "l"(da), "l"(db));
}

struct Idx {
    uint32_t lane, warp, w4, q4, g8, prow, pan;
    __device__ __forceinline__ Idx() {
        uint32_t t; asm volatile("mov.u32 %0, %%tid.x;" : "=r"(t));
        lane = t & 31; warp = t >> 5; w4 = warp & 3; q4 = lane & 3; g8 = lane >> 2;
        prow = w4 * 16 + ((lane >> 3) & 1) * 8 + (lane & 7);
        pan = prow * 128 + (((lane >> 4) ^ (lane & 7)) << 4);
    }
};
#define IDX() const Idx ix; const uint32_t lane = ix.lane, warp = ix.warp, w4 = ix.w4, q4 = ix.q4, g8 = ix.g8, prow = ix.prow, pan_addr = ix.pan; \
    (void)lane; (void)warp; (void)w4; (void)q4; (void)g8; (void)prow; (void)pan_addr;

__device__ __forceinline__ int kof(int t, int sh, int j) {
    const int p = t >> (sh - 1), pn = p < 2 ? p : p >= 9, q = p - 2 - 7 * pn;
    return ((p < 2 ? j : q + (q >= j)) << 7) + (pn << 6) + ((t & (sh - 1)) << 5);
}
__device__ __forceinline__ uint32_t fidx(uint32_t m, uint32_t w, uint32_t pn) {
    return m * 32 + w * 16 + pn;
}
constexpr int HC0 = 8 * 48, HC3 = HC0 + 3072;
__device__ __forceinline__ int hcol(int p, int j) { return HC0 + p * 1024 + j * 128; }
struct Ring {
    uint32_t slot, par;
    __device__ __forceinline__ void next() { if (++slot == NSLOT) { slot = 0; par ^= 1; } }
    __device__ __forceinline__ void skip(uint32_t n) { slot += n; if (slot >= NSLOT) { slot -= NSLOT; par ^= 1; } }
};
__device__ __forceinline__ uint32_t BAR_FULL(uint32_t sb, uint32_t s) { return sb + OFF_BAR + 8 * s; }
constexpr uint32_t AF_REL = 48;
__device__ __forceinline__ uint32_t BAR_EMPTY(uint32_t sb, uint32_t s) { return sb + OFF_BAR + 96 + 8 * s; }
__device__ __forceinline__ uint32_t BAR_SFULL(uint32_t sb, uint32_t i) { return sb + OFF_BAR + 152 + 8 * i; }
__device__ __forceinline__ uint32_t BAR_SREADY(uint32_t sb, uint32_t i) { return sb + OFF_BAR + 184 + 8 * i; }
__device__ __forceinline__ uint32_t BAR_ONE(uint32_t sb, uint32_t i) { return sb + OFF_BAR + 216 + 8 * i; }
enum { EV_WIN, EV_WIN1, EV_WIN2, EV_WIN3, EV_P0, EV_GA, EV_GB, EV_LN2, EV_LAG0, EV_LAG1, EV_LAG2, EV_LAG3, EV_LAG4, EV_LAG5, EV_KV, EV_PAR, EV_AGO, EV_AGO1, EV_AGO2, EV_FGO, EV_FGO1, EV_FGO2, EV_H0, EV_H1, EV_H2, EV_H3, EV_COUNT };
constexpr int NB_TAIL = 4;

struct Rel {
    uint32_t base; bool sig;
    __device__ __forceinline__ Rel(uint32_t sb, uint32_t tw) {
        uint32_t a; asm("mapa.shared::cluster.u32 %0, %1, %2;" : "=r"(a) : "r"(BAR_EMPTY(sb, 0)), "r"((tw >> 5) & 1));
        base = __shfl_sync(0xffffffffu, a, 0); sig = (tw & ~32u) == 0;
    }
    __device__ __forceinline__ void operator()(uint32_t slot) const {
        if (sig) asm volatile("mbarrier.arrive.shared::cluster.b64 _, [%0];" :: "r"(base + 8 * slot) : "memory");
    }
};
struct LnRow { float rs0, nm0, rs1, nm1; };
struct Pipe {
    Rel rel; uint32_t p1, p2;
    __device__ __forceinline__ Pipe(uint32_t sb, uint32_t tw, uint32_t first) : rel(sb, tw), p1(first), p2(NSLOT) {}
    template <bool TWO> __device__ __forceinline__ void acquire(uint32_t sb, uint32_t af, const Ring& r) {
        const uint32_t b0 = BAR_FULL(sb, r.slot), b1 = b0 + af;
        const bool ready = TWO ? mbar_test2(b0, b1, r.par) : mbar_test(b0, r.par);
        wg_wait<1>();
        rel(p2);
        if (!ready) { if (TWO) mbar_wait2(b0, b1, r.par); else mbar_wait(b0, r.par); }
    }
    __device__ __forceinline__ void issued(uint32_t slot) { p2 = p1; p1 = slot; }
    __device__ __forceinline__ void drain1() { wg_wait<1>(); rel(p2); p2 = NSLOT; }
    __device__ __forceinline__ void drain0() { wg_wait<0>(); rel(p1); p1 = NSLOT; }
    template <bool TWO, class Step> __device__ __forceinline__ void hold(int LG, uint32_t sb, uint32_t af, Ring& r, uint32_t lag_bar, Step step) {
        Ring q = r;
#pragma unroll 1
        for (int i = 0; i < LG; ++i) { if (TWO) mbar_wait2(BAR_FULL(sb, q.slot), BAR_FULL(sb, q.slot) + af, q.par); else mbar_wait(BAR_FULL(sb, q.slot), q.par); q.next(); }
        mbar_wait(lag_bar, 0);
#pragma unroll 1
        do {
            step(r.slot);
            wg_wait<2>(); rel(p2); p2 = p1; p1 = r.slot;
            if (++r.slot == NSLOT) r.slot = 0;
        } while (r.slot != q.slot);
        r.par = q.par;
    }
};
template <bool TWO, bool FIRST, int NA, int NB>
__device__ __forceinline__ void step32(float (&aa)[NA], float (&ab)[NB], uint32_t sb, uint32_t wg, uint32_t slot, int own) {
    const uint32_t st = d16(sb) + slot * (SLOT >> 4);
    const uint32_t alo = own >= 0 ? d16(sb) + OFF_STG / 16 + wg * 1024 + (own >> 1) * 512 + (own & 1) * 4 : st + wg * 256;
    const uint32_t ahi = own >= 0 ? (1024 >> 4) | (1u << 30) : (512 >> 4) | (2u << 30);
    wg_fence();
#pragma unroll
    for (int k = 0; k < 2; ++k) {
        const uint64_t da = ((uint64_t)ahi << 32) | (alo + k * 2 + 0x10000);
        if constexpr (NA == 88) {
            const uint64_t d0 = mk_desc(st, 8192 + k * 2048, 8192, 1024, 1), d1 = mk_desc(st, 12288 + k * 2048, 8192, 1024, 1);
            if (FIRST && k == 0) { wgmma_n176_z(aa, da, d0); wgmma_n176_z(ab, da, d1); }
            else { wgmma_n176(aa, da, d0); wgmma_n176(ab, da, d1); }
        } else {
            const uint64_t d0 = mk_desc(st, 8192 + k * 2048, 4096, 1024, 1), d1 = mk_desc(st, 24576 + k * 2048, 4096, 1024, 1);
            if (FIRST && k == 0) { wgmma_n256_z(aa, da, d0); if constexpr (TWO) wgmma_n128_z(ab, da, d1); }
            else { wgmma_n256(aa, da, d0); if constexpr (TWO) wgmma_n128(ab, da, d1); }
        }
    }
    wg_commit();
}
template <bool TWO, int LG, int NA, int NB, class Tail>
__device__ __forceinline__ void mainloop32(float (&aa)[NA], float (&ab)[NB], uint32_t sb, uint32_t wg, uint32_t tw, Ring& r, uint32_t lag_ev, int g0, Tail tail) {
    if (!TWO) mbar_wait(BAR_FULL(sb, r.slot), r.par);
    step32<TWO, true>(aa, ab, sb, wg, r.slot, TWO ? 0 : -1);
    TS(g0, 0);
    Pipe pp(sb, tw, r.slot);
    r.next();
    const int end = wg ? 32 : 32 - LG;
#pragma unroll 1
    for (int it = 1; it < end; ++it) {
        pp.acquire<TWO>(sb, wg ? 0 : AF_REL, r);
        step32<TWO, false>(aa, ab, sb, wg, r.slot, TWO && it < 4 ? it : -1);
        pp.issued(r.slot);
        TS(g0 + it, 0);
        r.next();
    }
    if (wg == 0) { pp.drain1(); pp.drain0(); pp.hold<TWO>(LG, sb, AF_REL, r, BAR_ONE(sb, lag_ev), [&](uint32_t slot) { step32<TWO, false>(aa, ab, sb, 0, slot, -1); }); }
    pp.drain1();
    if (wg == 1 && tw == 0) mbar_arrive(BAR_ONE(sb, lag_ev));
    tail();
    pp.drain0();
    TS(g0 + 31, 1);
}
template <bool FIRST>
__device__ __forceinline__ void step64(float (&acc)[64], uint32_t sb, uint32_t wg, uint32_t slot, int own) {
    const uint32_t sbb = d16(sb) + slot * (SLOT >> 4), sa = own >= 0 ? d16(sb) + OFF_STG / 16 + wg * 1024 + own * 512 : sbb + wg * 512;
    wg_fence();
#pragma unroll
    for (int k = 0; k < 4; ++k) {
        const uint64_t da = mk_desc(sa, k * 32, 16, 1024, 1), db = mk_desc(sbb, 16384 + k * 2048, 8192, 1024, 1);
        if (FIRST && k == 0) wgmma_n128_z(acc, da, db); else wgmma_n128(acc, da, db);
    }
    wg_commit();
}
template <class Mid, class Tail>
__device__ __forceinline__ void mainloop64(float (&acc)[64], bool wo, uint32_t sb, uint32_t wg, uint32_t tw, Ring& r, Mid mid, Tail tail) {
    const int g0 = wo ? 32 : 144, nst = wo ? 16 : 56, lg = wo ? LAGW : LAGD; (void)g0;
    const uint32_t lag_bar = BAR_ONE(sb, wo ? EV_LAG4 : EV_LAG5), af = wo && !wg ? AF_REL : 0;
    mbar_wait(BAR_FULL(sb, r.slot), r.par);
    if (!wo) CS(28);
    step64<true>(acc, sb, wg, r.slot, wo ? 0 : -1);
    if (!wo) CS(29);
    TS(g0, 0);
    Pipe pp(sb, tw, r.slot);
    r.next();
    int it = 1;
    auto run = [&](int end, int own) {
#pragma unroll 1
        do {
            pp.acquire<true>(sb, af, r);
            step64<false>(acc, sb, wg, r.slot, own);
            pp.issued(r.slot);
            TS(g0 + it, 0);
            if (wo && it == 2) CS(9);
            r.next();
            if (own > 0) {
                own = -1;
                pp.drain1(); pp.drain0();
                TS(g0 + 1, 1);
            }
        } while (++it < end);
    };
    const int end = wg ? nst : nst - lg;
    run(wo ? MIDW : wg ? MIDD : end, wo ? 1 : -1);
    mid();
    if (it < end) run(end, -1);
    if (wg == 0) { pp.drain1(); pp.drain0(); pp.hold<true>(lg, sb, af, r, lag_bar, [&](uint32_t slot) { step64<false>(acc, sb, 0, slot, -1); }); }
    pp.drain1();
    if (wg == 1 && tw == 0) mbar_arrive(lag_bar);
    tail();
    pp.drain0();
    TS(g0 + nst - 1, 1);
}

struct RowAcc {
    float sm[4] = {0.f, 0.f, 0.f, 0.f}, sq[4] = {0.f, 0.f, 0.f, 0.f};
    __device__ __forceinline__ void add(int e, float x) { sm[e & 3] += x; sq[e & 3] = fmaf(x, x, sq[e & 3]); }
    __device__ __forceinline__ void publish(uint4* dst, uint32_t q4, uint32_t ep) const {
        const float s0 = sm[0] + sm[1], s1 = sm[2] + sm[3], q0 = sq[0] + sq[1], q1 = sq[2] + sq[3];
        const bool od = q4 & 1;
        float sv = (od ? s1 : s0) + __shfl_xor_sync(0xffffffffu, od ? s0 : s1, 1), qv = (od ? q1 : q0) + __shfl_xor_sync(0xffffffffu, od ? q0 : q1, 1);
        sv += __shfl_xor_sync(0xffffffffu, sv, 2); qv += __shfl_xor_sync(0xffffffffu, qv, 2);
        st_pkt16(dst + (q4 & 1) * 8, 0, __float_as_uint(sv), __float_as_uint(qv), ep);
    }
};
__device__ __forceinline__ LnRow merge_stats(const uint4* src, uint32_t q4, uint32_t ep, uint32_t sb) {
    uint4 t[4];
    uint32_t n = 0;
    while (true) {
#pragma unroll
        for (int i = 0; i < 4; ++i) t[i] = ld_pkt16(src + (q4 * 2 + (i >> 1)) * 512 + (i & 1) * 8);
        const bool ok_ = __all_sync(0xffffffffu, t[0].w == ep && t[1].w == ep && t[2].w == ep && t[3].w == ep);
        if (n < 4) CS(14 + n);
        if (ok_) break;
        SPIN_GUARD(n);
    }
    float v[4];
#pragma unroll
    for (int h = 0; h < 2; ++h) { v[h] = __uint_as_float(t[h].y) + __uint_as_float(t[2 + h].y); v[2 + h] = __uint_as_float(t[h].z) + __uint_as_float(t[2 + h].z); }
#pragma unroll
    for (int o = 1; o < 4; o <<= 1)
#pragma unroll
        for (int i = 0; i < 4; ++i) v[i] += __shfl_xor_sync(0xffffffffu, v[i], o);
    const float m0 = v[0] * (1.f / D_), m1 = v[1] * (1.f / D_);
    const float r0 = rsqrtf(fmaxf(fmaf(-m0, m0, v[2] * (1.f / D_)), 0.f) + 1e-5f), r1 = rsqrtf(fmaxf(fmaf(-m1, m1, v[3] * (1.f / D_)), 0.f) + 1e-5f);
    return LnRow{r0, -m0 * r0, r1, -m1 * r1};
}
struct Stg {
    uint32_t b, par;
    __device__ __forceinline__ uint32_t acquire2(uint32_t sb, uint32_t wg) {
        mbar_wait2(BAR_SREADY(sb, wg * 2), BAR_SREADY(sb, wg * 2 + 1), par);
        par ^= 1;
        return sb + OFF_STG + wg * 16384;
    }
    __device__ __forceinline__ void publish(uint32_t sb, uint32_t wg, uint32_t lane) {
        fence_async_smem();
        __syncwarp();
        if (lane == 0) mbar_arrive(BAR_SFULL(sb, wg * 2 + b));
        b ^= 1;
    }
};

struct LnPar {
    uint4 p[8];
    __device__ __forceinline__ void load(uint32_t sb, uint32_t q4) {
#pragma unroll
        for (int i = 0; i < 8; ++i) p[i] = lds128(sb + OFF_PAR + i * 64 + q4 * 16);
    }
};
__device__ __forceinline__ void ln_norm(uint32_t (&xn)[32], const float (&x)[64], const LnRow& n) {
#pragma unroll
    for (int e = 0; e < 32; ++e) {
        const float rs = (e & 1) ? n.rs1 : n.rs0, nm = (e & 1) ? n.nm1 : n.nm0;
        xn[e] = pack2(fmaf(x[2 * e], rs, nm), fmaf(x[2 * e + 1], rs, nm));
    }
}
__device__ __forceinline__ void ln_emit(const uint32_t (&xr)[32], const LnPar& lp, uint32_t sb, uint32_t wg, const Idx& ix) {
#pragma unroll
    for (int i = 0; i < 8; ++i)
        stsm4(sb + OFF_STG + wg * 16384 + (i >> 2) * 8192 + (ix.pan ^ ((i & 3) << 5)), hfma2_bf16(xr[4 * i], lp.p[i].z, lp.p[i].x), hfma2_bf16(xr[4 * i + 1], lp.p[i].z, lp.p[i].x),
              hfma2_bf16(xr[4 * i + 2], lp.p[i].w, lp.p[i].y), hfma2_bf16(xr[4 * i + 3], lp.p[i].w, lp.p[i].y));
    fence_async_smem();
    __syncwarp();
    if (ix.lane < 2) mbar_arrive(BAR_SFULL(sb, wg * 2 + ix.lane));
    bar_sync(1 + wg, 128);
}
__device__ __forceinline__ void load_slab(uint32_t (&xr)[32], uint32_t buf) {
    IDX();
#pragma unroll
    for (int i = 0; i < 8; ++i) ldsm4(buf + (i >> 2) * 8192 + (pan_addr ^ ((i & 3) << 5)), xr[4 * i], xr[4 * i + 1], xr[4 * i + 2], xr[4 * i + 3]);
}
__device__ __forceinline__ void unpack_slab(float (&x)[64], const uint32_t (&xr)[32]) {
#pragma unroll
    for (int i = 0; i < 32; ++i) unpack2(xr[i], x[2 * i], x[2 * i + 1]);
}
__device__ __forceinline__ void store_slab(const float (&x)[64], uint32_t buf, uint32_t pitch, uint32_t pan, int i0, int i1) {
#pragma unroll
    for (int i = i0; i < i1; ++i)
        stsm4(buf + (i >> 2) * pitch + (pan ^ ((i & 3) << 5)), pack2(x[8 * i], x[8 * i + 1]), pack2(x[8 * i + 2], x[8 * i + 3]), pack2(x[8 * i + 4], x[8 * i + 5]), pack2(x[8 * i + 6], x[8 * i + 7]));
}
__device__ __forceinline__ void fetch_halo(uint4* src, bool first, uint32_t sb, uint32_t W, uint32_t lane) {
    mbar_wait(BAR_ONE(sb, EV_KV), 0);
    mbar_wait2(BAR_SREADY(sb, 0), BAR_SREADY(sb, 1), 1);
    uint4 hv[8];
    uint32_t n = 0;
    while (true) {
        bool ok = true;
#pragma unroll
        for (int i = 0; i < 8; ++i) { hv[i] = first ? make_uint4(0, 0, 0, 0) : ld_pkt16(src + i * 32); ok = ok && hv[i].x != 0; }
        if (first || __all_sync(0xffffffffu, ok)) break;
        SPIN_GUARD(n);
    }
#pragma unroll
    for (int i = 0; i < 8; ++i) stsm4(sb + OFF_STG + W * 2048 + (i >> 2) * 8192 + (i & 3) * 512 + lane * 16, hv[i].x, hv[i].y, hv[i].z, hv[i].w);
    bar_arrive(NB_TAIL + W, 64);
    if (!first) {
#pragma unroll
        for (int i = 0; i < 8; ++i) src[i * 32] = make_uint4(0, 0, 0, 0);
    }
}

template <int NG, class G, class U, class Buf>
__device__ __forceinline__ void glu(uint32_t sb, uint32_t wg, G g, U u, Buf buf) {
    IDX();
#pragma unroll
    for (int k = 0; k < NG; ++k) {
        float h[8];
#pragma unroll
        for (int e = 0; e < 8; ++e) h[e] = fmaf(tanh_(g(8 * k + e)), u(8 * k + e), u(8 * k + e));
        stsm4(buf(k >> 2) + (pan_addr ^ ((k & 3) << 5)), pack2(h[0], h[1]), pack2(h[2], h[3]), pack2(h[4], h[5]), pack2(h[6], h[7]));
    }
    fence_async_smem();
    __syncwarp();
    if (lane < 2) mbar_arrive(BAR_SFULL(sb, wg * 2 + lane));
}

template <int NP>
__device__ __forceinline__ void passes128(uint32_t sb, uint32_t wg, uint32_t tw, Ring& r, Stg& stg) {
#pragma unroll 1
    for (int p = 0; p < NP; ++p) {
        float b256[128], none[1];
        mainloop32<false, LAGS>(b256, none, sb, wg, tw, r, EV_LAG2 + p, 80 + 32 * (p & 1), [&] { stg.acquire2(sb, wg); });
        if (threadIdx.x == 0) { TL(29 + 2 * p); TC(114 + 2 * p); }
        if (threadIdx.x == 128) TL(53 + 2 * (p & 1));
        CS(24 + 2 * (p & 1));
        glu<8>(sb, wg, [&](int i) { return b256[i + (i & 32)]; }, [&](int i) { return b256[i + (i & 32) + 32]; }, [&](int pn) { return sb + OFF_STG + wg * 16384 + pn * 8192; });
        if (threadIdx.x == 0) { TL(30 + 2 * p); TC(115 + 2 * p); }
        if (threadIdx.x == 128) TL(54 + 2 * (p & 1));
        CS(25 + 2 * (p & 1));
    }
}

__global__ void __launch_bounds__(384, 1)
fused_block_kernel(const __grid_constant__ Ptrs pt, const __grid_constant__ Maps mp) {
    uint32_t* const g_flags = pt.mail->flags;
    uint2* const g_mod = pt.mail->mod;
    uint4* const g_st1 = pt.mail->st1;
    uint32_t* const g_par2 = pt.mail->par2;
    uint4* const g_halo = pt.mail->halo;
    const __nv_bfloat16* __restrict__ cvec = pt.c;
    if (threadIdx.x == 224) { prefetch_map(&mp.wm8); prefetch_map(&mp.x); }
    extern __shared__ __align__(1024) uint8_t smem[];
    const uint32_t sb = smem_u32(smem);
    const uint32_t tid = threadIdx.x, tw = tid & 127, lane = tid & 31;
    const uint32_t warp = __shfl_sync(0xffffffffu, tid >> 5, 0), wg = warp >> 2;
    uint32_t rank; asm("mov.u32 %0, %%cluster_ctarank;" : "=r"(rank));
    rank = __shfl_sync(0xffffffffu, rank, 0);
    uint32_t ep;
    uint32_t smid; asm volatile("mov.u32 %0, %%smid;" : "=r"(smid));
    const int c = __shfl_sync(0xffffffffu, smid >> 1, 0);
    const int c7 = ((c - 32) * 37) >> 8;
    int grp = c < 32 ? c & 7 : c < 60 ? c - 31 - 7 * c7 : c < 62 ? -1 : 0;
    const int j = c < 32 ? c >> 3 : c < 60 ? 4 + c7 : c < 62 ? (c - 60) * 2 + rank : c - 58;
    const bool aux = grp < 0;
    const int m = grp * 2 + rank;
    uint4* const g_st2 = g_halo + (m > 0 ? (m - 1) * 8 * 512 : 128);

    bool cluster_arrive_early = false;
    if (wg < 2) {
      if (!KDEBUG) cluster_arrive();
      ep = flag_get(g_flags + FL_DONE);
      uint16_t cw[8];
      {
          const __nv_bfloat16* cp = cvec + ((tw >> 5) * 32 + (tw & 3) * 2) * 8 + (lane >> 2);
#pragma unroll
          for (int i = 0; i < 8; ++i) asm volatile("ld.global.nc.u16 %0, [%1];" : "=h"(cw[i]) : "l"(cp + (i >> 1) * 64 + (i & 1) * 8));
      }
      asm volatile("setmaxnreg.inc.sync.aligned.u32 224;");
      if (tid == 0) TL(58);
      if (KDEBUG) cluster_arrive();
      Ring r{0, 0};
      Stg stg{0, 0};
      if (aux) {
        if (wg == 0) {
            const uint4 cv = *(const uint4*)(cvec + tw * 8);
            sts128(sb + OFF_STG + (tw >> 3) * 1024 + (tw & 7) * 16, pack2(silu_(bf_lo(cv.x)), silu_(bf_hi(cv.x))), pack2(silu_(bf_lo(cv.y)), silu_(bf_hi(cv.y))),
                   pack2(silu_(bf_lo(cv.z)), silu_(bf_hi(cv.z))), pack2(silu_(bf_lo(cv.w)), silu_(bf_hi(cv.w))));
            fence_async_smem();
        }
        cluster_wait();
        ep = __shfl_sync(0xffffffffu, ep, 0) / NCTA + 1;
        if (wg == 0) {
            bar_sync(1, 128);
#pragma unroll 1
            for (int p = 0; p < 4; ++p) {
                float acc[128];
#pragma unroll
                for (int i = 0; i < 128; ++i) acc[i] = 0.f;
                uint32_t prev = 0;
#pragma unroll 1
                for (int kc = 0; kc < 16; ++kc) {
                    mbar_wait(BAR_FULL(sb, r.slot), r.par);
                    wg_fence();
#pragma unroll
                    for (int k = 0; k < 4; ++k)
                        wgmma_n256(acc, mk_desc(d16(sb) + kc * 64, OFF_STG + k * 32, 16, 0, 1), mk_desc(d16(sb) + r.slot * (SLOT >> 4), k * 2048, 8192, 1024, 1));
                    wg_commit();
                    wg_wait<1>();
                    if (kc > 0 && tw < 4) mbar_arrive(BAR_EMPTY(sb, prev));
                    prev = r.slot;
                    r.next();
                }
                wg_wait<0>();
                if (tw < 4) mbar_arrive(BAR_EMPTY(sb, prev));
                if (tw < 4) {
#pragma unroll
                    for (int jn = 0; jn < 32; ++jn) sts32(sb + OFF_TAB + (jn * 4 + tw) * 4, pack2(acc[jn * 4], acc[jn * 4 + 1]));
                }
                bar_sync(1, 128);
                const int vec = 2 + p, blk = p * 4 + j;
                const uint32_t val = lds32(sb + OFF_TAB + tw * 4);
                if (vec == 2 || vec == 5) st_pkt(g_mod + (8 + blk) * 128 + tw, val, ep);
                else {
                    const float one = vec == 4 ? 1.f : 0.f;
                    g_par2[((blk & 3) * 16 + (tw >> 3)) * 16 + (tw & 3) * 4 + (vec - 3) * 2 + ((tw >> 2) & 1)] =
                        pack2(0.5f * bf_round(one + bf_lo(val)), 0.5f * bf_round(one + bf_hi(val)));
                }
                bar_sync(1, 128);
                if (tw == 0) {
                    if (vec == 3 || vec == 4) asm volatile("red.release.gpu.global.add.u32 [%0], 1;" :: "l"(&g_flags[FL_LN2]) : "memory");
                    TL(1 + p);
                }
            }
            if (lane < 2) mbar_arrive_cta(BAR_ONE(sb, EV_P0), lane);
        }
        r = Ring{64 % NSLOT, (64 / NSLOT) & 1};
        mbar_wait(BAR_ONE(sb, EV_P0), 0);
        passes128<4>(sb, wg, tw, r, stg);
      } else {
        float xs[64];
        uint32_t xp[32];
        {
            IDX();
            if (q4 < 2) st_pkt16(g_st1 + (m * 8 + j) * 512 + wg * 64 + w4 * 16 + g8 + q4 * 8, 0, 0, 0, 0);
            if (warp == 0) st_pkt16(pt.mail->mod1 + g8 * 512 + (m * 8 + j) * 4 + q4, 0, 0, 0, 0);
            sts128(sb + tid * 16, pack2(silu_(bf_lo(cw[0])), silu_(bf_lo(cw[1]))), pack2(silu_(bf_lo(cw[2])), silu_(bf_lo(cw[3]))),
                   pack2(silu_(bf_lo(cw[4])), silu_(bf_lo(cw[5]))), pack2(silu_(bf_lo(cw[6])), silu_(bf_lo(cw[7]))));
            cluster_wait();
            ep = __shfl_sync(0xffffffffu, ep, 0) / NCTA + 1;
            load_slab(xp, stg.acquire2(sb, wg));
            unpack_slab(xs, xp);
            if (tid == 0) TL(24);
            if (tid == 128) TL(27);
        }
#pragma unroll 1
        for (int blk = 0; ; ++blk) {
        {
            IDX();
            uint4* const st = (blk ? g_st2 : g_st1 + m * 8 * 512) + wg * 64 + w4 * 16 + g8;
            RowAcc ra;
#pragma unroll
            for (int e = 0; e < 64; ++e) ra.add(e, xs[e]);
            ra.publish(st + j * 512, q4, ep);
            uint32_t t_pub = 0; if (PDLY) asm volatile("mov.u32 %0, %%clock;" : "=r"(t_pub));
            if (tid == 0) TL(blk ? 9 : 26);
            if (tid == 128 && blk) TL(34);
            if (blk) CS(11);
            LnPar lp;
            if (blk == 0) {
            uint4* const mod_out = pt.mail->mod1 + g8 * 512 + (m * 8 + j) * 4 + q4;
            if (wg == 0) {
                uint4 af[8];
#pragma unroll
                for (int i = 0; i < 8; ++i) af[i] = lds128(sb + w4 * 512 + i * 64 + q4 * 16);
                float c[4][4] = {};
#pragma unroll
                for (int i = 0; i < 8; ++i) {
                    if (!(i & 1)) mbar_wait(BAR_ONE(sb, EV_WIN + (i >> 1)), 0);
                    if (i == 6 && tid == 0) TL(25);
#pragma unroll
                    for (int h = 0; h < 2; ++h) {
                        uint32_t b0, b1, b2, b3;
                        ldsm4t(sb + 5 * SLOT + i * 4096 + w4 * 1024 + h * 512 + (lane & 15) * 32 + (lane >> 4) * 16, b0, b1, b2, b3);
                        mma16816(c[2 * h], h ? af[i].z : af[i].x, 0u, h ? af[i].w : af[i].y, 0u, b0, b1);
                        mma16816(c[2 * h + 1], h ? af[i].z : af[i].x, 0u, h ? af[i].w : af[i].y, 0u, b2, b3);
                    }
                }
                if (lane < 4) sts128(sb + OFF_TAB + w4 * 64 + lane * 16, __float_as_uint(c[0][0] + c[2][0]), __float_as_uint(c[0][1] + c[2][1]),
                                     __float_as_uint(c[1][0] + c[3][0]), __float_as_uint(c[1][1] + c[3][1]));
                if (lane < 2) mbar_arrive_cta(BAR_ONE(sb, EV_P0), lane);
                bar_sync(1, 128);
                if (w4 == 0) {
                    float a[4] = {0.f, 0.f, 0.f, 0.f};
#pragma unroll
                    for (int i = 0; i < 4; ++i) {
                        const uint4 t = lds128(sb + OFF_TAB + i * 64 + q4 * 16);
                        a[0] += __uint_as_float(t.x); a[1] += __uint_as_float(t.y); a[2] += __uint_as_float(t.z); a[3] += __uint_as_float(t.w);
                    }
                    const float add = m >= 8 ? 1.f : 0.f;
                    st_pkt16(mod_out, pack2(bf_round(a[0]) + add, bf_round(a[1]) + add), pack2(bf_round(a[2]) + add, bf_round(a[3]) + add), ep, 0);
                    if (tid == 0) TL(3);
                }
            } else if (LWAIT >= 0) mbar_wait(BAR_ONE(sb, EV_WIN + LWAIT), 0);
            } else {
                mbar_wait2(BAR_ONE(sb, EV_LN2), BAR_FULL(sb, 0), 0);
            }
            lp.load(sb, q4);
#pragma unroll
            for (int e = 0; e < 32; ++e) xp[e] = pack2(xs[2 * e], xs[2 * e + 1]);
            if (PDLY && blk) { uint32_t t1; do { asm volatile("mov.u32 %0, %%clock;" : "=r"(t1)); } while (t1 - t_pub < PDLY); }
            if (blk) CS(13);
            const LnRow n = merge_stats(st, q4, ep, sb);
            if (tid == 0) TL(blk ? 49 : 48);
            if (tid == 128) TL(blk ? 45 : 28);
            if (blk) CS(18);
            uint32_t xn[32];
            ln_norm(xn, xs, n);
            if (blk == 0) { mbar_wait2(BAR_FULL(sb, 0), BAR_ONE(sb, EV_PAR), 0); lp.load(sb, q4); }
            ln_emit(xn, lp, sb, wg, ix);
            if (tid == 0) { TL(blk ? 36 : 8); TC(blk ? 109 : 103); }
            if (tid == 128) TL(blk ? 43 : 22);
            if (blk) CS(21);
        }
        if (blk == 0) {
        {
            float kv[128], qa[64];
            step32<true, true>(kv, qa, sb, wg, r.slot, 0);
            TS(0, 0);
            Pipe pp(sb, tw, r.slot);
            r.next();
#pragma unroll 1
            for (int it = 1; it < 32 - LAGQ; ++it) {
                pp.acquire<true>(sb, wg ? 0 : AF_REL, r);
                step32<true, false>(kv, qa, sb, wg, r.slot, it < 4 ? it : -1);
                pp.issued(r.slot);
                TS(it, 0);
                r.next();
            }
            auto half = [&](uint32_t slot, bool q) {
                const uint32_t st = d16(sb) + slot * (SLOT >> 4);
#pragma unroll
                for (int k = 0; k < 2; ++k) {
                    const uint64_t da = mk_desc(st + wg * 256, k * 32, 16, 512, 2);
                    if (q) wgmma_n128(qa, da, mk_desc(st, 24576 + k * 2048, 4096, 1024, 1)); else wgmma_n256(kv, da, mk_desc(st, 8192 + k * 2048, 4096, 1024, 1));
                }
            };
            auto part = [&](bool q) {
                wg_fence();
#pragma unroll
                for (int it = 32 - LAGQ; it < 32; ++it) half(it % NSLOT, q);
                wg_commit();
            };
            stg.acquire2(sb, wg); mbar_wait2(BAR_SREADY(sb, 2), BAR_SREADY(sb, 3), 1);
            if (wg == 0) { pp.drain1(); pp.drain0(); }
#pragma unroll 1
            for (int it = 32 - LAGQ; it < 32; ++it) {
                pp.acquire<true>(sb, wg ? 0 : AF_REL, r);
                if (wg) { wg_fence(); half(r.slot, false); wg_commit(); }
                pp.issued(NSLOT);
                TS(it, 0);
                r.next();
            }
            if (wg == 0) { mbar_wait(BAR_ONE(sb, EV_LAG0), 0); part(false); part(true); wg_wait<1>(); }
            else { wg_wait<1>(); if (tw == 0) mbar_arrive(BAR_ONE(sb, EV_LAG0)); wg_wait<0>(); }
            CS(8);
            IDX();
            uint32_t k1[16], k2[16], v1[16], v2[16], qf[32];
#pragma unroll
            for (int i = 0; i < 128; ++i) asm volatile("" : "+f"(kv[i]) :: "memory");
#pragma unroll
            for (int t = 0; t < 16; ++t) k2[t] = pack2(kv[4 * t + 2], kv[4 * t + 3]);
#pragma unroll
            for (int t = 0; t < 16; ++t) k1[t] = pack2(kv[4 * t], kv[4 * t + 1]);
#pragma unroll
            for (int t = 0; t < 16; ++t) v2[t] = pack2(kv[64 + 4 * t + 2], kv[64 + 4 * t + 3]);
            const uint32_t nxt = warp + ((warp & 1) ? 3 : 1);
            if (nxt < 8) {
                const uint32_t dst = sb + OFF_STG + (nxt >> 2) * 16384 + (nxt & 3) * 2048 + lane * 16;
#pragma unroll
                for (int h = 0; h < 4; ++h) stsm4(dst + h * 512, k2[4 * h], k2[4 * h + 1], k2[4 * h + 2], k2[4 * h + 3]);
#pragma unroll
                for (int h = 0; h < 4; ++h) stsm4(dst + 8192 + h * 512, v2[4 * h], v2[4 * h + 1], v2[4 * h + 2], v2[4 * h + 3]);
                bar_arrive(NB_TAIL + nxt, 64);
            } else if (m < 15) {
                uint4* dst = g_halo + (m * 8 + j) * 512 + (w4 >> 1) * 256 + lane;
#pragma unroll
                for (int h = 0; h < 4; ++h) { if (!k2[4 * h]) k2[4 * h] = 0x8000u; if (!v2[4 * h]) v2[4 * h] = 0x8000u; }
#pragma unroll
                for (int h = 0; h < 4; ++h) st_pkt16(dst + h * 32, k2[4 * h], k2[4 * h + 1], k2[4 * h + 2], k2[4 * h + 3]);
#pragma unroll
                for (int h = 0; h < 4; ++h) st_pkt16(dst + 128 + h * 32, v2[4 * h], v2[4 * h + 1], v2[4 * h + 2], v2[4 * h + 3]);
            }
#pragma unroll
            for (int t = 0; t < 16; ++t) { v1[t] = pack2(kv[64 + 4 * t], kv[64 + 4 * t + 1]); if (t < MVE) { v1[t] = movm(v1[t]); v2[t] = movm(v2[t]); } }
            if (tid == 0) TL(33);
            CS(2);
            if (wg) part(true);
            bar_sync(NB_TAIL + warp, 64);
            CS(4);
            if (tid == 0) TL(5);
            uint32_t k0[16], v0[16];
            const uint32_t mine = sb + OFF_STG + wg * 16384 + w4 * 2048;
#pragma unroll
            for (int h = 0; h < 4; ++h) ldsm4(mine + lane * 16 + h * 512, k0[4 * h], k0[4 * h + 1], k0[4 * h + 2], k0[4 * h + 3]);
#pragma unroll
            for (int h = 0; h < 4; ++h) ldsm4t(mine + lane * 16 + 8192 + h * 512, v0[4 * h], v0[4 * h + 1], v0[4 * h + 2], v0[4 * h + 3]);
            wg_wait<0>();
#pragma unroll
            for (int it = 32 - LAGQ; it < 32; ++it) pp.rel(it % NSLOT);
            TS(31, 1);
            if (tid == 0) { TL(4); TC(104); }
            if (tid == 128) TL(50);
            CS(1);
#pragma unroll
            for (int i = 0; i < 64; ++i) asm volatile("" : "+f"(qa[i]) :: "memory");
            const bool lo0 = q4 * 2 > g8, lo1 = q4 * 2 + 1 > g8;
            const bool nopast = m == 0 && (warp & 5) == 0;
            const uint32_t lomask = (lo0 ? 0xFFFFu : 0u) | (lo1 ? 0xFFFF0000u : 0u);
            const uint32_t orow = mine + (lane & 7) * 128 + (((lane >> 3) ^ (lane & 7)) << 4);
            const float sl2 = 0.17677669529663687f * 1.4426950408889634f;
#pragma unroll
            for (int pn = 0; pn < 2; ++pn) {
                float e0[4], e1[4], mx[4], sum[4];
#pragma unroll
                for (int hh = 0; hh < 2; ++hh) {
                    const int h = pn * 2 + hh;
#pragma unroll
                    for (int i = 8 * h; i < 8 * h + 8; ++i) qf[i] = pack2(qa[2 * i], qa[2 * i + 1]);
                    float s[3][4];
#pragma unroll
                    for (int t = 0; t < 3; ++t) {
                        const uint32_t* k = (t == 0 ? k0 : t == 1 ? k1 : k2) + 4 * h;
                        s[t][0] = s[t][1] = s[t][2] = s[t][3] = 0.f;
                        mma16816(s[t], qf[h * 8], qf[h * 8 + 1], qf[h * 8 + 2], qf[h * 8 + 3], k[0], k[1]);
                        mma16816(s[t], qf[h * 8 + 4], qf[h * 8 + 5], qf[h * 8 + 6], qf[h * 8 + 7], k[2], k[3]);
                    }
#pragma unroll
                    for (int hf = 0; hf < 2; ++hf) {
                        const int u = hh * 2 + hf;
                        e0[u] = lo0 ? ((hf == 0 && nopast) ? -INFINITY : s[hf][hf * 2]) : s[hf + 1][hf * 2];
                        e1[u] = lo1 ? ((hf == 0 && nopast) ? -INFINITY : s[hf][hf * 2 + 1]) : s[hf + 1][hf * 2 + 1];
                        mx[u] = fmaxf(e0[u], e1[u]);
                    }
                }
#pragma unroll
                for (int o = 1; o < 4; o <<= 1)
#pragma unroll
                    for (int u = 0; u < 4; ++u) mx[u] = fmaxf(mx[u], __shfl_xor_sync(0xffffffffu, mx[u], o));
#pragma unroll
                for (int u = 0; u < 4; ++u) {
                    const float c = -mx[u] * sl2;
                    e0[u] = ex2(fmaf(e0[u], sl2, c)); e1[u] = ex2(fmaf(e1[u], sl2, c));
                    sum[u] = e0[u] + e1[u];
                }
#pragma unroll
                for (int o = 1; o < 4; o <<= 1)
#pragma unroll
                    for (int u = 0; u < 4; ++u) sum[u] += __shfl_xor_sync(0xffffffffu, sum[u], o);
#pragma unroll
                for (int u = 0; u < 4; ++u) {
                    const int h = pn * 2 + (u >> 1);
                    const float inv = rcp(sum[u]);
                    const uint32_t p = pack2(e0[u] * inv, e1[u] * inv);
                    const uint32_t* va = ((u & 1) ? v1 : v0) + 4 * h;
                    const uint32_t* vb = ((u & 1) ? v2 : v1) + 4 * h;
                    float o[2][4] = {};
#pragma unroll
                    for (int d = 0; d < 2; ++d) mma16816(o[d], va[2 * d], va[2 * d + 1], vb[2 * d], vb[2 * d + 1], p & lomask, p & ~lomask);
                    stsm4t((orow ^ ((u >> 1) << 6)) + pn * 8192 + (u & 1) * 1024, pack2(o[0][0], o[0][1]), pack2(o[0][2], o[0][3]), pack2(o[1][0], o[1][1]), pack2(o[1][2], o[1][3]));
                }
                fence_async_smem();
                __syncwarp();
                if (lane == 0) mbar_arrive(BAR_SFULL(sb, wg * 2 + pn));
                if (pn == 0) {
                    CS(5); block_end(sb, 0);
#pragma unroll
                    for (int t = MVE; t < 16; ++t) { v1[t] = movm(v1[t]); v2[t] = movm(v2[t]); }
                }
            }
            CS(6);
            if (tid == 32) TL(41);
            mbar_wait(BAR_FULL(sb, 32 % NSLOT + wg), (32 / NSLOT) & 1);
            load_slab(xp, sb + (32 % NSLOT + wg) * SLOT);
            bar_sync(1 + wg, 128);
            if (tid == 0) { TL(6); TC(106); }
            if (tid == 128) TL(44);
            CS(7);
        }
        } else {
        {
            float ag[88], au[88];
            mainloop32<true, LAG>(ag, au, sb, wg, tw, r, EV_LAG1, 48, [&] {
                stg.acquire2(sb, wg);
                Ring q = r; if (!wg) q.next();
                mbar_wait(BAR_EMPTY(sb, q.slot), q.par ^ 1);
            });
            if (tid == 0) { TL(10); TC(110); }
            if (tid == 128) TL(51);
            CS(22);
            glu<11>(sb, wg, [&](int i) { return ag[i]; }, [&](int i) { return au[i]; },
                    [&](int pn) { return pn < 2 ? sb + OFF_STG + wg * 16384 + pn * 8192 : sb + (wg ? P3_SLOT1 : P3_SLOT0) * SLOT + 24576; });
            if (tid == 0) { TL(11); TC(111); }
            if (tid == 128) TL(52);
            CS(23);
        }
        passes128<2>(sb, wg, tw, r, stg);
        if (tid == 0) { TL(12); TC(112); }
        }
        {
            float acc[64], gf[32];
            mainloop64(acc, blk == 0, sb, wg, tw, r, [&] {
                mbar_wait(BAR_ONE(sb, EV_GA + blk), 0);
                unpack_slab(xs, xp);
                uint32_t gt[16];
#pragma unroll
                for (int cg = 0; cg < 16; ++cg) gt[cg] = lds32(sb + OFF_TAB + blk * 256 + cg * 16 + (tw & 3) * 4);
#pragma unroll
                for (int i = 0; i < 16; ++i) unpack2(gt[i], gf[2 * i], gf[2 * i + 1]);
            }, [&] { stg.acquire2(sb, wg); });
            if (tid == 0) { TL(blk ? 13 : 7); TC(blk ? 113 : 107); }
            if (tid == 128) TL(blk ? 57 : 42);
            CS(blk ? 30 : 10);
#pragma unroll
            for (int e = 0; e < 64; ++e) xs[e] = fmaf(gf[(e >> 2) * 2 + (e & 1)], acc[e], xs[e]);
        }
        if (blk) break;
        }
        {
            IDX();
#pragma unroll
            for (int p = 0; p < 2; ++p) {
                store_slab(xs, sb + OFF_STG + wg * 16384, 8192, pan_addr, 4 * p, 4 * p + 4);
                stg.publish(sb, wg, lane);
            }
            cluster_arrive();
            if (tid == 0) TL(14);
            CS(31);
        }
      }
    } else {
        if (warp == 8 && !aux && elect_one()) {
#pragma unroll
            for (int i = 0; i < 4; ++i) mbar_init(BAR_SREADY(sb, i), 1);
#pragma unroll
            for (int i = 0; i < 4; ++i) mbar_init(BAR_ONE(sb, EV_WIN + i), 1);
#pragma unroll
            for (int i = 0; i < 4; ++i) {
                mbar_expect_tx(BAR_SREADY(sb, i), 8192);
                tma_load3(sb + OFF_STG + i * 8192, &mp.x, j * 128 + (i & 1) * 64, m * 64 + (i >> 1) * 32, BAR_SREADY(sb, i));
            }
#pragma unroll 1
            for (int i = 0; i < 4; ++i) {
                mbar_expect_tx(BAR_ONE(sb, EV_WIN + i), 8192);
                tma_load(sb + 5 * SLOT + i * 8192, &mp.wm8, 2 * i * 6144 + (m * 8 + j) * 16, 0, BAR_ONE(sb, EV_WIN + i));
                tma_load(sb + 5 * SLOT + i * 8192 + 4096, &mp.wm8, (2 * i + 1) * 6144 + (m * 8 + j) * 16, 0, BAR_ONE(sb, EV_WIN + i));
            }
        }
        __syncwarp();
        asm volatile("setmaxnreg.dec.sync.aligned.u32 56;");
        if (elect_one()) {
            if (warp == 8) {
                prefetch_map(&mp.wqkv); prefetch_map(&mp.wmod);
            } else if (warp < 11) {
                mbar_init(BAR_EMPTY(sb, NSLOT), 1);
#pragma unroll
                for (int i = 0; i < 2; ++i) { mbar_init(BAR_SFULL(sb, (warp - 9) * 2 + i), 4); if (aux) mbar_init(BAR_SREADY(sb, (warp - 9) * 2 + i), 1); }
#pragma unroll
                for (int i = 0; i < 3; ++i) {
                    mbar_init(BAR_EMPTY(sb, (warp - 9) * 3 + i), 4);
                    mbar_init(BAR_FULL(sb, (warp - 9) * 3 + i), 1); mbar_init(BAR_FULL(sb, (warp - 9) * 3 + i) + AF_REL, 1);
                }
            } else {
#pragma unroll
                for (int i = EV_P0; i < EV_COUNT; ++i) mbar_init(BAR_ONE(sb, i), i == EV_P0 ? 8 : 1);
            }
            asm volatile("fence.mbarrier_init.release.cluster;" ::: "memory");
        }
        __syncwarp();
        cluster_arrive();
        ep = 0;
        if (warp != 8 || aux) ep = flag_get(g_flags + FL_DONE);
        cluster_wait();
        ep = __shfl_sync(0xffffffffu, ep, 0) / NCTA + 1;
        if (warp == 8) {
            const bool el = elect_one();
            Ring r{0, 1};
            if (aux) {
                {
                    uint32_t n = 0;
                    while (!__all_sync(0xffffffffu, ld_pkt16(pt.mail->mod1 + 256).z == ep)) { SPIN_GUARD(n); __nanosleep(200); }
                }
#pragma unroll 1
                for (int it = 0; it < 64; ++it) {
                    const int col = 2048 + (it >> 4) * 1024 + j * 256;
                    mbar_wait(BAR_EMPTY(sb, r.slot), r.par);
                    const uint32_t st = sb + r.slot * SLOT, fb = BAR_FULL(sb, r.slot);
                    if (el) {
                        mbar_expect_tx(fb, 32768);
#pragma unroll
                        for (int b = 0; b < 4; ++b) tma_load(st + b * 8192, &mp.wmod, col + b * 64, (it & 15) * 64, fb);
                    }
                    r.next();
                }
                mbar_wait(BAR_ONE(sb, EV_P0), 0);
                const CUtensorMap* wm = rank ? &mp.wu : &mp.wg;
#pragma unroll 1
                for (int g = 0; g < 128; ++g) {
                    const int mx = (j >> 1) * 8 + (g >> 5) * 2 + rank, k0 = ((g & 14) << 6) + ((g & 16) << 2) + ((g & 1) << 5);
                    if (!(g & 15)) {
                        uint32_t n = 0;
                        while (!__all_sync(0xffffffffu, (int32_t)(flag_get(g_flags + FL_PROG + fidx(mx, lane >> 4, (lane & 14) | ((g >> 4) & 1))) - (ep * 8 + ST_H2)) >= 0)) { SPIN_GUARD(n); __nanosleep(300); }
                    }
                    mbar_wait(BAR_EMPTY(sb, r.slot), r.par);
                    const uint32_t st = sb + r.slot * SLOT, fb = BAR_FULL(sb, r.slot);
                    if (el) {
                        mbar_expect_tx(fb, 24576);
                        tma_load_mc(st + 8192 + rank * 4096, wm, HC3, k0, fb);
                        tma_load_mc(st + 16384 + rank * 4096, wm, HC3 + 64, k0, fb);
                        tma_load(st, &mp.h2l, k0, mx * 128, fb);
                    }
                    r.next();
                }
            } else {
#pragma unroll 1
                for (int it = 0; it < 32; ++it) {
                    const int cb = j * 128 + rank * 64, k0 = kof(it, 2, j);
                    if (it == BW0) mbar_wait(BAR_ONE(sb, BWEV), 0);
                    if (it == BW1) mbar_wait(BAR_ONE(sb, EV_PAR), 0);
                    if (it == 5) mbar_wait(BAR_ONE(sb, EV_P0), 0);
                    if (it == AG0) mbar_wait(BAR_ONE(sb, (AGW & 1) ? EV_AGO : EV_FGO), 0);
                    mbar_wait(BAR_EMPTY(sb, r.slot), r.par);
                    const uint32_t st = sb + r.slot * SLOT, fb = BAR_FULL(sb, r.slot);
                    if (el) {
                        mbar_expect_tx(fb, it < 4 ? 24576 : 28672);
                        tma_load_mc(st + 8192 + rank * 4096, &mp.wqkv, 1024 + cb, k0, fb);
                        tma_load_mc(st + 16384 + rank * 4096, &mp.wqkv, 2048 + cb, k0, fb);
                        tma_load_mc(st + 24576 + rank * 4096, &mp.wqkv, cb, k0, fb);
                        if (it < 4) mbar_arrive(fb + AF_REL);
                        if (it == PFWO + (m >> 1)) { tma_prefetch(&mp.wo, j * 128, m * 64); tma_prefetch(&mp.wo, j * 128 + 64, m * 64); }
                        if (it >= PFG && it < PFG + PFN && (it & 7) == grp) {
                            const int kp = kof(it - PFG + PFO, 2, j);
                            tma_prefetch(rank ? &mp.wu : &mp.wg, hcol(0, j), kp); tma_prefetch(rank ? &mp.wu : &mp.wg, hcol(0, j) + 64, kp);
                            asm volatile("cp.async.bulk.prefetch.tensor.3d.L2.global [%0, {%1, %2, %3}];" :: "l"(rank ? &mp.wu3 : &mp.wg3), "r"(0), "r"(j), "r"(kp) : "memory");
                        }
                    }
                    r.next();
                }
                if (el) mbar_arrive(BAR_ONE(sb, EV_KV));
#pragma unroll 1
                for (int it = 0; it < 16; ++it) {
                    const int k0 = kof(it, 1, j);
                    if (it == AG1) mbar_wait(BAR_ONE(sb, (AGW & 2) ? EV_AGO1 : EV_FGO1), 0);
                    mbar_wait(BAR_EMPTY(sb, r.slot), r.par);
                    const uint32_t st = sb + r.slot * SLOT, fb = BAR_FULL(sb, r.slot);
                    if (el) {
                        mbar_expect_tx(fb, it < 2 ? 32768 : 24576);
                        tma_load_mc(st + 16384 + rank * 8192, &mp.wo, j * 128 + rank * 64, k0, fb);
                        if (it < 2) {
                            tma_load3(st, &mp.x, j * 128, m * 64 + it * 32, fb); tma_load3(st + 8192, &mp.x, j * 128 + 64, m * 64 + it * 32, fb);
                            mbar_arrive(fb + AF_REL);
                        }
                        if (it == 6) { prefetch_map(rank ? &mp.wu : &mp.wg); prefetch_map(rank ? &mp.wu3 : &mp.wg3); }
                    }
                    r.next();
                }
                const CUtensorMap* wm = rank ? &mp.wu : &mp.wg;
#pragma unroll 1
                for (int g = 0; g < 96; ++g) {
                    if (g == AG2) mbar_wait(BAR_ONE(sb, (AGW & 4) ? EV_AGO2 : EV_FGO2), 0);
                    const int p = g >> 5, cb = hcol(p, j), k0 = p == 0 ? kof(g, 2, j) : (g & 31) * 32;
                    mbar_wait(BAR_EMPTY(sb, r.slot), r.par);
                    const uint32_t st = sb + r.slot * SLOT, fb = BAR_FULL(sb, r.slot);
                    if (el) {
                        mbar_expect_tx(fb, (g < 4 || p > 0) ? 24576 : 28672);
                        tma_load_mc(st + 8192 + rank * 4096, wm, cb, k0, fb);
                        tma_load_mc(st + 16384 + rank * 4096, wm, cb + 64, k0, fb);
                        if (p == 0) tma_load3_mc(st + 24576 + rank * 4096, rank ? &mp.wu3 : &mp.wg3, j, k0, fb);
                        else tma_load(st, &mp.h2l, k0, m * 128, fb);
                        if (g < 4) mbar_arrive(fb + AF_REL);
                        if (g == 60) prefetch_map(&mp.wd);
                    }
                    r.next();
                }
#pragma unroll 1
                for (int g = 0; g < 56; ++g) {
                    if (g == 0 || (g & 15) == 6 && g > 6) mbar_wait(BAR_ONE(sb, EV_H0 + (g >> 4)), 0);
                    const int k0 = g * 64;
                    mbar_wait(BAR_EMPTY(sb, r.slot), r.par);
                    const uint32_t st = sb + r.slot * SLOT, fb = BAR_FULL(sb, r.slot);
                    if (el) {
                        mbar_expect_tx(fb, 32768);
                        tma_load_mc(st + 16384 + rank * 8192, &mp.wd, j * 128 + rank * 64, k0, fb);
                        tma_load(st, &mp.hb, k0, m * 128, fb); tma_load(st + 8192, &mp.hb, k0, m * 128 + 64, fb);
                    }
                    r.next();
                }
            }
        } else if (aux) {
            if (warp < 11) {
                const uint32_t w = warp - 9;
                const bool el = elect_one();
#pragma unroll 1
                for (int p = 0; p < 4; ++p) {
                    const int mx = (j >> 1) * 8 + p * 2 + rank;
                    if (el) { mbar_arrive(BAR_SREADY(sb, w * 2)); mbar_arrive(BAR_SREADY(sb, w * 2 + 1)); }
                    mbar_wait2(BAR_SFULL(sb, w * 2), BAR_SFULL(sb, w * 2 + 1), p & 1);
                    if (p < 3) pause(HD0);
                    if (el) tma_store(&mp.hb, HC3, mx * 128 + w * 64, sb + OFF_STG + w * 16384);
                    if (p < 3) pause(HP);
                    if (el) {
                        tma_store(&mp.hb, HC3 + 64, mx * 128 + w * 64, sb + OFF_STG + w * 16384 + 8192);
                        bulk_commit(); bulk_wait_fence(); flag_set(g_flags + FL_AUX + mx * 2 + w, ep * 8 + ST_H + 3);
                    }
                }
            }
        } else if (warp == 11) {
            const bool el = elect_one();
            const int row0 = m * 128;
            const uint32_t* const fl = g_flags + FL_PROG + fidx(m, lane >> 4, kof(lane & 15, 1, j) >> 6);
            if (el) { prefetch_map(&mp.h1h); prefetch_map(&mp.h2h); prefetch_map(&mp.h2l); }
            auto gate = [&](int vec, int ev) {
                uint4 v; uint32_t n = 0;
                while (true) {
                    v = ld_pkt2(g_mod + vec * 512 + j * 64 + lane * 2);
                    if (__all_sync(0xffffffffu, v.y == ep && v.w == ep)) break;
                    SPIN_GUARD(n); __nanosleep(300);
                }
                asm volatile("st.shared.v2.u32 [%0], {%1, %2};" :: "r"(sb + OFF_TAB + (ev - EV_GA) * 256 + lane * 8), "r"(v.x), "r"(v.z) : "memory");
                __syncwarp();
                if (lane == 0) mbar_arrive(BAR_ONE(sb, ev));
            };
            {
                const uint4* pk = pt.mail->mod1 + grp * 512 + j * 32 + lane;
                uint4 a, b; uint32_t n = 0;
                mbar_wait(BAR_ONE(sb, EV_WIN3), 0);
                while (true) {
                    a = ld_pkt16(pk); b = ld_pkt16(pk + 256);
                    if (__all_sync(0xffffffffu, a.z == ep && b.z == ep)) break;
                    SPIN_GUARD(n);
                }
                sts128(sb + OFF_PAR + lane * 16, a.x, a.y, b.x, b.y);
                __syncwarp();
                if (lane == 0) { mbar_arrive(BAR_ONE(sb, EV_PAR)); TL(46); }
            }
            mbar_wait(BAR_ONE(sb, EV_P0), 0);
            Ring r{0, 1};
#pragma unroll 1
            for (int ph = 0; ph < 3; ++ph) {
                const int sh = ph == 1 ? 1 : 2, nst = 8 << sh;
                const uint32_t half = 16384 >> sh, target = ep * 8 + ST_H1 + ph;
                const CUtensorMap* tm = ph == 0 ? &mp.h1h : ph == 1 ? &mp.o : &mp.h2h;
                if (ph == 1) gate(2, EV_GA);
                if (ph == 2) {
                    uint32_t n = 0;
                    while ((int32_t)(flag_get(g_flags + FL_LN2) - ep * 8) < 0) { SPIN_GUARD(n); __nanosleep(200); }
                    const uint4 v = __ldcg((const uint4*)(g_par2 + j * 128) + lane);
                    sts128(sb + OFF_PAR + lane * 16, v.x, v.y, v.z, v.w);
                    __syncwarp();
                    if (lane == 0) mbar_arrive(BAR_ONE(sb, EV_LN2));
                }
                const uint32_t lw = ~lane & 1, lt = lane >> 1, ls = (r.slot + lt) % NSLOT, lk = kof(lt, sh, j), lb = BAR_FULL(sb, ls) + (lw ? 0 : AF_REL);
                const uint32_t* const lf = g_flags + FL_PROG + fidx(m, lw, lk >> 6);
                int fr = 1 << sh;
                uint32_t todo = 0x3ffffu >> (2 * fr) << (2 * fr), have = ~todo, n = 0, v = 0;
                r.skip(fr);
#pragma unroll 1
                for (; fr < NSLOT; ++fr) { mbar_wait(BAR_EMPTY(sb, r.slot), r.par); r.next(); }
                if (ph == XST - 1) CS(33);
                do {
                    if (!((have >> lane) & 1)) v = flag_get(lf);
                    while (fr < 9 && mbar_test(BAR_EMPTY(sb, r.slot), r.par)) { ++fr; r.next(); }
                    SPIN_GUARD(n);
                    have |= __ballot_sync(0xffffffffu, (int32_t)(v - target) >= 0);
                    const uint32_t go = have & todo & ((1u << (2 * fr)) - 1);
                    if ((go >> lane) & 1) {
                        if (!lw) mbar_expect_tx(lb, half);
                        tma_load(sb + ls * SLOT + lw * half, tm, lk, row0 + lw * 64, lb);
                    }
                    __syncwarp();
                    if (lane < 2 && (todo & (0x555u << lane)) && !(todo & ~go & (0x555u << lane))) mbar_arrive(BAR_ONE(sb, (lane ? EV_FGO : EV_AGO) + ph));
                    if (ph == XST - 1) { if (go & (1u << (2 << sh))) CS(34); if (go & (2u << (2 << sh))) CS(35); if (todo & 0x555u) CS(36); if (todo & 0xaaau) CS(37); }
                    todo &= ~go;
                } while (~have);
                if (ph == XST - 1) CS(38);
                int k = kof(fr, sh, j);
#pragma unroll 1
                for (; fr < nst; ++fr) {
                    if (fr == 9 || fr == 18) {
                        const uint32_t skip = fr == 9 << (sh - 1) ? 0 : ~0x01fc01fcu;
                        while (~(__ballot_sync(0xffffffffu, (int32_t)(flag_get(fl) - target) >= 0) | skip)) SPIN_GUARD(n);
                    }
                    const uint32_t st = sb + r.slot * SLOT, fb = BAR_FULL(sb, r.slot);
                    mbar_wait(BAR_EMPTY(sb, r.slot), r.par);
                    if (el) {
                        tma_load(st + half, tm, k, row0 + 64, fb);
                        mbar_expect_tx(fb + AF_REL, half);
                        tma_load(st, tm, k, row0, fb + AF_REL);
                    }
                    if (ph == XST - 1 && fr == 9) CS(39);
                    r.next();
                    k = kof(fr + 1, sh, j);
                }
            }
#pragma unroll 1
            for (int p = 0; p < 4; ++p) {
                const uint32_t* f = p < 3 ? fl : g_flags + FL_AUX + m * 2 + (lane & 1);
                uint32_t n = 0;
                while (!__all_sync(0xffffffffu, (int32_t)(flag_get(f) - (ep * 8 + ST_H + p)) >= 0)) { SPIN_GUARD(n); __nanosleep(300); }
                if (el) mbar_arrive(BAR_ONE(sb, EV_H0 + p));
                if (p == 0) gate(5, EV_GB);
            }
        } else {
            const uint32_t w = warp - 9;
            const int row0 = m * 128 + w * 64;
            const uint32_t stg = sb + OFF_STG + w * 16384;
            uint32_t* const fl = g_flags + FL_PROG + fidx(m, w, 2 * j);
            uint32_t b = 0, par = 0;
            const bool el = elect_one();
            auto store = [&](const CUtensorMap* tm, int col, bool nat = false) {
                mbar_wait(BAR_SFULL(sb, w * 2 + b), (par >> b) & 1);
                par ^= 1u << b;
                if (el) {
                    if (nat) tma_store3(tm, col, row0 >> 1, 0, stg + b * 8192); else tma_store(tm, col, row0, stg + b * 8192);
                    bulk_commit();
                }
                b ^= 1;
            };
            auto send2 = [&](const CUtensorMap* tm, const uint32_t* buf, int step) {
                const uint32_t* const q = buf + (size_t)((row0 + lane) * (D_ / 2) + j * 64 + 31);
                store(tm, j * 128);
                if (step == XST) CS(33);
                uint32_t z = landed(el, q, D_ / 2, pt.zero);
                if (el) flag_set(fl, ep * 8 + step + z);
                if (step == XST) CS(34);
                if (step != ST_O) { mbar_wait(BAR_ONE(sb, EV_FGO + step - ST_H1), 0); pause(w ? P1H : P1H + 1000); }
                store(tm, j * 128 + 64);
                if (step == XST) CS(35);
                z = landed(el, q + 32, D_ / 2, pt.zero);
                if (el) flag_set(fl + 1, ep * 8 + step + z);
                if (step == XST) CS(36);
            };
            auto free2 = [&]() { if (el) { mbar_arrive(BAR_SREADY(sb, w * 2)); mbar_arrive(BAR_SREADY(sb, w * 2 + 1)); } };
            if (el) { prefetch_map(&mp.h1s); prefetch_map(&mp.o); prefetch_map(&mp.h2s); prefetch_map(&mp.hb); prefetch_map(&mp.out); prefetch_map(&mp.wo); }
            if (el) { flag_set(fl, ep * 8); flag_set(fl + 1, ep * 8); }
            send2(&mp.h1s, pt.h1, ST_H1);
            if (w == 0) TL(47);
            free2();
            fetch_halo(g_halo + ((m - 1) * 8 + j) * 512 + w * 256 + lane, m == 0, sb, 2 * w, lane);
            send2(&mp.o, pt.o, ST_O);
            if (w == 0) TL(40); else TL(38);
            free2();
            send2(&mp.h2s, pt.o, ST_H2);
            if (el) { prefetch_map(&mp.hb); prefetch_map(&mp.hb3); }
            if (w == 0) TL(37);
            free2();
#pragma unroll 1
            for (int p = 0; p < 3; ++p) {
                const int col = hcol(p, j);
                mbar_wait(BAR_SFULL(sb, w * 2), par & 1);
                pause(w ? HD1 : HD0); store(&mp.hb, col);
                pause(HP); store(&mp.hb, col + 64);
                if (p == 0) {
                    pause(HP);
                    if (el) { tma_store3(&mp.hb3, 0, j, row0, sb + (w ? P3_SLOT1 : P3_SLOT0) * SLOT + 24576); bulk_commit(); }
                }
                if (el) bulk_wait_read();
                free2();
                if (el) { bulk_wait_fence(); flag_set(fl, ep * 8 + ST_H + p); flag_set(fl + 1, ep * 8 + ST_H + p); }
            }
            cluster_arrive_early = true;
            cluster_arrive();
            store(&mp.out, j * 128, true); store(&mp.out, j * 128 + 64, true);
            if (el) bulk_wait_read();
        }
        __syncwarp();
    }
    if (aux || (wg == 2 && !cluster_arrive_early)) cluster_arrive();
    cluster_wait();
    CS(32);
    if (KDEBUG == 5) __syncthreads();
    if (tid == 0) {
        TL(15);
        flag_add(pt.mail->flags + FL_DONE);
    }
}

typedef CUresult (*EncodeFn)(CUtensorMap*, CUtensorMapDataType, cuuint32_t, void*, const cuuint64_t*, const cuuint64_t*, const cuuint32_t*,
                             const cuuint32_t*, CUtensorMapInterleave, CUtensorMapSwizzle, CUtensorMapL2promotion, CUtensorMapFloatOOBfill);

void make_map(EncodeFn fn, CUtensorMap* m, const void* ptr, uint64_t rows, uint64_t cols, uint32_t brows, uint32_t bcols) {
    cuuint64_t dims[2] = {cols, rows}, strides[1] = {cols * 2};
    cuuint32_t box[2] = {bcols, brows}, es[2] = {1, 1};
    fn(m, CU_TENSOR_MAP_DATA_TYPE_BFLOAT16, 2, (void*)ptr, dims, strides, box, es, CU_TENSOR_MAP_INTERLEAVE_NONE,
       bcols == 64 ? CU_TENSOR_MAP_SWIZZLE_128B : bcols == 32 ? CU_TENSOR_MAP_SWIZZLE_64B : CU_TENSOR_MAP_SWIZZLE_NONE, CU_TENSOR_MAP_L2_PROMOTION_L2_256B, CU_TENSOR_MAP_FLOAT_OOB_FILL_NONE);
}

void make_map3(EncodeFn fn, CUtensorMap* m, const void* ptr) {
    cuuint64_t dims[3] = {D_, S_ / 2, 2}, strides[2] = {4 * D_, 2 * D_};
    cuuint32_t box[3] = {64, 32, 2}, es[3] = {1, 1, 1};
    fn(m, CU_TENSOR_MAP_DATA_TYPE_BFLOAT16, 3, (void*)ptr, dims, strides, box, es, CU_TENSOR_MAP_INTERLEAVE_NONE,
       CU_TENSOR_MAP_SWIZZLE_128B, CU_TENSOR_MAP_L2_PROMOTION_L2_256B, CU_TENSOR_MAP_FLOAT_OOB_FILL_NONE);
}

void make_map48(EncodeFn fn, CUtensorMap* m, const void* ptr, uint64_t rows, uint32_t brows) {
    cuuint64_t dims[3] = {48, 8, rows}, strides[2] = {96, 2 * F_};
    cuuint32_t box[3] = {64, 1, brows}, es[3] = {1, 1, 1};
    fn(m, CU_TENSOR_MAP_DATA_TYPE_BFLOAT16, 3, (void*)ptr, dims, strides, box, es, CU_TENSOR_MAP_INTERLEAVE_NONE,
       CU_TENSOR_MAP_SWIZZLE_128B, CU_TENSOR_MAP_L2_PROMOTION_L2_256B, CU_TENSOR_MAP_FLOAT_OOB_FILL_NONE);
}

}

extern "C" void kernel_launch(void* const* d_in, const int* in_sizes, int n_in, void* d_out, int out_size) {
    (void)in_sizes; (void)n_in; (void)out_size;
    void* fnp = nullptr;
    cudaDriverEntryPointQueryResult qr;
    cudaGetDriverEntryPoint("cuTensorMapEncodeTiled", &fnp, cudaEnableDefault, &qr);
    EncodeFn fn = (EncodeFn)fnp;
    void *h1, *o, *h2, *hb, *mail;
    cudaGetSymbolAddress(&h1, g_h1);
    cudaGetSymbolAddress(&mail, g_mail);
    cudaGetSymbolAddress(&o, g_o);
    cudaGetSymbolAddress(&hb, g_hb);
    h2 = o;
    Maps mp;
    make_map(fn, &mp.h1h, h1, S_, D_, 64, 32);
    make_map(fn, &mp.h2h, h2, S_, D_, 64, 32);
    make_map(fn, &mp.h1s, h1, S_, D_, 64, 64);
    make_map(fn, &mp.o, o, S_, D_, 64, 64);
    make_map(fn, &mp.h2l, h2, S_, D_, 128, 32);
    make_map(fn, &mp.h2s, h2, S_, D_, 64, 64);
    make_map(fn, &mp.hb, hb, S_, F_, 64, 64);
    make_map(fn, &mp.wqkv, d_in[1], D_, 3 * D_, 32, 64);
    make_map(fn, &mp.wo, d_in[2], D_, D_, 64, 64);
    make_map(fn, &mp.wg, d_in[4], D_, F_, 32, 64);
    make_map(fn, &mp.wu, d_in[5], D_, F_, 32, 64);
    make_map(fn, &mp.wd, d_in[6], F_, D_, 64, 64);
    make_map(fn, &mp.wmod, d_in[8], D_, 6 * D_, 64, 64);
    make_map(fn, &mp.wm8, d_in[8], D_ / 8, 8 * 6 * D_, 128, 16);
    make_map3(fn, &mp.x, d_in[0]);
    make_map3(fn, &mp.out, d_out);
    make_map48(fn, &mp.wg3, d_in[4], D_, 32);
    make_map48(fn, &mp.wu3, d_in[5], D_, 32);
    make_map48(fn, &mp.hb3, hb, S_, 64);
    cudaFuncSetAttribute(fused_block_kernel, cudaFuncAttributeMaxDynamicSharedMemorySize, SMEM_BYTES);
    cudaLaunchConfig_t cfg = {};
    cfg.gridDim = dim3(NCTA); cfg.blockDim = dim3(384); cfg.dynamicSmemBytes = SMEM_BYTES; cfg.stream = cudaStreamPerThread;
    cudaLaunchAttribute at[1];
    at[0].id = cudaLaunchAttributeClusterDimension; at[0].val.clusterDim.x = 2; at[0].val.clusterDim.y = 1; at[0].val.clusterDim.z = 1;
    cfg.attrs = at; cfg.numAttrs = 1;
    const Ptrs pt{(const __nv_bfloat16*)d_in[7], (Mail*)mail, (const uint32_t*)h1, (const uint32_t*)o, 0};
    cudaLaunchKernelEx(&cfg, fused_block_kernel, pt, mp);
}
```

```cpp
#include <cuda_runtime.h>
#include <cuda_bf16.h>
#include <cuda.h>
#include <stdint.h>
#include <stddef.h>

#define LAG 4
#define LAGS 4
#define LAGW 3
#define LAGQ 4
#define MIDW 2
#define PFWO 12
#define P1H 3000
#define AGW 6
#define CSW 0
#define LWAIT 2
#define BW0 0
#define BWEV EV_WIN
#define BW1 3
#define PDLY 500
#define HD1 5500
#define HD0 5500
#define HP 2200
#define LAGD 4
#define MIDD 5
#define XST ST_O
#define AG0 6
#define AG1 6
#define AG2 8
#define PFG 8
#define PFN 24
#define PFO 0
#define MVE 8
#define P2L 2000
#define P2F 3000
#define KDEBUG 0

namespace {

constexpr int S_ = 2048, D_ = 1024, F_ = 3584;
constexpr int NCTA = 132;
constexpr int NSLOT = 6;
constexpr uint32_t SLOT = 32768;
constexpr uint32_t OFF_STG = NSLOT * SLOT;
constexpr uint32_t OFF_BAR = OFF_STG + 32768;
constexpr uint32_t OFF_PAR = OFF_BAR + 512;
constexpr uint32_t OFF_TAB = OFF_PAR + 768;
constexpr uint32_t OFF_TL = OFF_PAR + 2048;
constexpr uint32_t SMEM_BYTES = OFF_TL + (KDEBUG ? 512 : 0);
constexpr uint32_t P3_SLOT1 = (32 + 16 + 32) % NSLOT, P3_SLOT0 = (P3_SLOT1 + 1) % NSLOT;

constexpr int ST_H1 = 1, ST_O = 2, ST_H2 = 3, ST_H = 4, FL_DONE = 0, FL_LN2 = 1, FL_AUX = 32, FL_PROG = 64;

struct Maps {
    CUtensorMap h1h, h1s, o, h2h, h2l, h2s, hb, wqkv, wo, wg, wu, wd, wmod, wm8, x, out, wg3, wu3, hb3;
};

struct Mail {
    uint32_t flags[16 * 32 + 64];
    uint2 mod[6 * D_ / 2];
    uint4 mod1[8 * 512];
    uint4 st1[128 * 512];
    uint32_t par2[D_];
    uint4 halo[128 * 512];
};
struct Ptrs { const __nv_bfloat16* c; Mail* mail; const uint32_t *h1, *o; uint32_t zero; };

__device__ __align__(128) Mail g_mail;
__device__ __align__(128) __nv_bfloat16 g_h1[S_ * D_];
__device__ __align__(128) __nv_bfloat16 g_o[S_ * D_];
__device__ __align__(128) __nv_bfloat16 g_hb[S_ * F_];
#define TL(i) do {} while (0)
#define TC(i) do {} while (0)
#define TS(g, which) do {} while (0)
#define CS(i) do {} while (0)

__device__ __forceinline__ uint32_t smem_u32(const void* p) { return (uint32_t)__cvta_generic_to_shared(p); }
__device__ __forceinline__ void mbar_init(uint32_t bar, uint32_t cnt) { asm volatile("mbarrier.init.shared::cta.b64 [%0], %1;" :: "r"(bar), "r"(cnt) : "memory"); }
__device__ __forceinline__ void mbar_expect_tx(uint32_t bar, uint32_t bytes) { asm volatile("mbarrier.arrive.expect_tx.shared::cta.b64 _, [%0], %1;" :: "r"(bar), "r"(bytes) : "memory"); }
__device__ __forceinline__ void mbar_arrive(uint32_t bar) { asm volatile("mbarrier.arrive.shared::cta.b64 _, [%0];" :: "r"(bar) : "memory"); }
__device__ __forceinline__ void mbar_arrive_cta(uint32_t bar, uint32_t cta) {
    asm volatile("{\n.reg .b32 r;\nmapa.shared::cluster.u32 r, %0, %1;\nmbarrier.arrive.shared::cluster.b64 _, [r];\n}" :: "r"(bar), "r"(cta) : "memory");
}
__device__ __forceinline__ void mbar_wait(uint32_t bar, uint32_t parity) {
    asm volatile("{\n.reg .pred p;\n.reg .u32 n;\nmov.u32 n, 0;\n"
        "W_LOOP:\nmbarrier.try_wait.parity.shared::cta.b64 p, [%0], %1;\n@p bra W_DONE;\n"
        "add.u32 n, n, 1;\nsetp.lt.u32 p, n, 0x400000;\n@p bra W_LOOP;\ntrap;\nW_DONE:\n}" :: "r"(bar), "r"(parity) : "memory");
}
__device__ __forceinline__ void mbar_wait2(uint32_t b0, uint32_t b1, uint32_t parity) {
    asm volatile("{\n.reg .pred p, q;\n.reg .u32 n;\nmov.u32 n, 0;\n"
        "W_LOOP:\nmbarrier.try_wait.parity.shared::cta.b64 p, [%0], %2;\nmbarrier.try_wait.parity.shared::cta.b64 q, [%1], %2;\nand.pred p, p, q;\n@p bra W_DONE;\n"
        "add.u32 n, n, 1;\nsetp.lt.u32 p, n, 0x400000;\n@p bra W_LOOP;\ntrap;\nW_DONE:\n}" :: "r"(b0), "r"(b1), "r"(parity) : "memory");
}
__device__ __forceinline__ bool mbar_test(uint32_t bar, uint32_t parity) {
    uint32_t r; asm volatile("{\n.reg .pred p;\nmbarrier.test_wait.parity.shared::cta.b64 p, [%1], %2;\nselp.u32 %0, 1, 0, p;\n}" : "=r"(r) : "r"(bar), "r"(parity) : "memory"); return r;
}
__device__ __forceinline__ bool mbar_test2(uint32_t b0, uint32_t b1, uint32_t parity) {
    uint32_t r;
    asm volatile("{\n.reg .pred p, q;\nmbarrier.test_wait.parity.shared::cta.b64 p, [%1], %3;\nmbarrier.test_wait.parity.shared::cta.b64 q, [%2], %3;\n"
        "and.pred p, p, q;\nselp.u32 %0, 1, 0, p;\n}" : "=r"(r) : "r"(b0), "r"(b1), "r"(parity) : "memory");
    return r;
}
__device__ __forceinline__ void tma_load3(uint32_t dst, const CUtensorMap* m, int c0, int c1, uint32_t bar) {
    asm volatile("cp.async.bulk.tensor.3d.shared::cluster.global.mbarrier::complete_tx::bytes [%0], [%1, {%3, %4, %5}], [%2];"
        :: "r"(dst), "l"(m), "r"(bar), "r"(c0), "r"(c1), "r"(0) : "memory");
}
__device__ __forceinline__ void tma_store3(const CUtensorMap* m, int c0, int c1, int c2, uint32_t src) {
    asm volatile("cp.async.bulk.tensor.3d.global.shared::cta.bulk_group [%0, {%2, %3, %4}], [%1];" :: "l"(m), "r"(src), "r"(c0), "r"(c1), "r"(c2) : "memory");
}
__device__ __forceinline__ void tma_load3_mc(uint32_t dst, const CUtensorMap* m, int c1, int c2, uint32_t bar) {
    asm volatile("cp.async.bulk.tensor.3d.shared::cluster.global.mbarrier::complete_tx::bytes.multicast::cluster.L2::cache_hint [%0], [%1, {%3, %4, %5}], [%2], %6, %7;"
        :: "r"(dst), "l"(m), "r"(bar), "r"(0), "r"(c1), "r"(c2), "h"((uint16_t)3), "l"(0x12F0000000000000ull) : "memory");
}
__device__ __forceinline__ void tma_load(uint32_t dst, const CUtensorMap* m, int c0, int c1, uint32_t bar) {
    asm volatile("cp.async.bulk.tensor.2d.shared::cluster.global.mbarrier::complete_tx::bytes [%0], [%1, {%3, %4}], [%2];"
        :: "r"(dst), "l"(m), "r"(bar), "r"(c0), "r"(c1) : "memory");
}
__device__ __forceinline__ void tma_load_mc(uint32_t dst, const CUtensorMap* m, int c0, int c1, uint32_t bar) {
    asm volatile("cp.async.bulk.tensor.2d.shared::cluster.global.mbarrier::complete_tx::bytes.multicast::cluster.L2::cache_hint [%0], [%1, {%3, %4}], [%2], %5, %6;"
        :: "r"(dst), "l"(m), "r"(bar), "r"(c0), "r"(c1), "h"((uint16_t)3), "l"(0x12F0000000000000ull) : "memory");
}
__device__ __forceinline__ void tma_prefetch(const CUtensorMap* m, int c0, int c1) {
    asm volatile("cp.async.bulk.prefetch.tensor.2d.L2.global [%0, {%1, %2}];" :: "l"(m), "r"(c0), "r"(c1) : "memory");
}
__device__ __forceinline__ void tma_store(const CUtensorMap* m, int c0, int c1, uint32_t src) {
    asm volatile("cp.async.bulk.tensor.2d.global.shared::cta.bulk_group [%0, {%2, %3}], [%1];" :: "l"(m), "r"(src), "r"(c0), "r"(c1) : "memory");
}
__device__ __forceinline__ void bulk_commit() { asm volatile("cp.async.bulk.commit_group;" ::: "memory"); }
__device__ __forceinline__ void bulk_wait_read() { asm volatile("cp.async.bulk.wait_group.read 0;" ::: "memory"); }
__device__ __forceinline__ void fence_async_smem() { asm volatile("fence.proxy.async.shared::cta;" ::: "memory"); }
__device__ __forceinline__ void prefetch_map(const CUtensorMap* m) { asm volatile("prefetch.tensormap [%0];" :: "l"(m) : "memory"); }
__device__ __forceinline__ void wg_fence() { asm volatile("wgmma.fence.sync.aligned;" ::: "memory"); }
__device__ __forceinline__ void wg_commit() { asm volatile("wgmma.commit_group.sync.aligned;" ::: "memory"); }
template <int N> __device__ __forceinline__ void wg_wait() { asm volatile("wgmma.wait_group.sync.aligned %0;" :: "n"(N) : "memory"); }
__device__ __forceinline__ void bar_sync(int id, int n) { asm volatile("bar.sync %0, %1;" :: "r"(id), "r"(n) : "memory"); }
__device__ __forceinline__ void bar_arrive(int id, int n) { asm volatile("bar.arrive %0, %1;" :: "r"(id), "r"(n) : "memory"); }
__device__ __forceinline__ void flag_add(uint32_t* f) { asm volatile("red.relaxed.gpu.global.add.u32 [%0], 1;" :: "l"(f) : "memory"); }
__device__ __forceinline__ void flag_set(uint32_t* f, uint32_t v) { asm volatile("red.relaxed.gpu.global.max.u32 [%0], %1;" :: "l"(f), "r"(v) : "memory"); }
__device__ __forceinline__ uint32_t flag_get(const uint32_t* f) { uint32_t v; asm volatile("ld.relaxed.gpu.global.u32 %0, [%1];" : "=r"(v) : "l"(f) : "memory"); return v; }
__device__ __forceinline__ void bulk_wait_fence() { asm volatile("cp.async.bulk.wait_group 0;\nfence.proxy.async.global;\nfence.acq_rel.gpu;" ::: "memory"); }
__device__ __forceinline__ uint32_t landed(bool el, const uint32_t* p, uint32_t pitch, uint32_t zero) {
    if (el) asm volatile("cp.async.bulk.wait_group 0;" ::: "memory");
    __syncwarp();
    const uint32_t a = flag_get(p), b = flag_get(p + 32 * pitch);
    return __reduce_or_sync(0xffffffffu, (a | b) & zero);
}
__device__ __forceinline__ uint32_t d16(uint32_t addr) { return (addr & 0x3FFFF) >> 4; }
__device__ __forceinline__ uint64_t mk_desc(uint32_t a16, uint32_t off, uint32_t lbo, uint32_t sbo, uint32_t swz) {
    const uint32_t lo = a16 + (off >> 4) + ((lbo >> 4) << 16), hi = (sbo >> 4) | (swz << 30);
    return ((uint64_t)hi << 32) | lo;
}
__device__ __forceinline__ uint32_t pack2(float lo, float hi) {
    uint32_t r; asm("cvt.rn.bf16x2.f32 %0, %1, %2;" : "=r"(r) : "f"(hi), "f"(lo)); return r;
}
__device__ __forceinline__ uint32_t hfma2_bf16(uint32_t a, uint32_t b, uint32_t c) {
    uint32_t r; asm("fma.rn.bf16x2 %0, %1, %2, %3;" : "=r"(r) : "r"(a), "r"(b), "r"(c)); return r;
}
__device__ __forceinline__ float bf_lo(uint32_t v) { return __uint_as_float(v << 16); }
__device__ __forceinline__ float bf_hi(uint32_t v) { return __uint_as_float(v & 0xFFFF0000u); }
__device__ __forceinline__ void unpack2(uint32_t v, float& lo, float& hi) {
    asm volatile("shl.b32 %0, %2, 16;\nand.b32 %1, %2, 0xffff0000;" : "=f"(lo), "=f"(hi) : "r"(v));
}
__device__ __forceinline__ float bf_round(float x) { return __bfloat162float(__float2bfloat16_rn(x)); }
__device__ __forceinline__ void stsm4(uint32_t addr, uint32_t r0, uint32_t r1, uint32_t r2, uint32_t r3) {
    asm volatile("stmatrix.sync.aligned.m8n8.x4.shared.b16 [%0], {%1, %2, %3, %4};" :: "r"(addr), "r"(r0), "r"(r1), "r"(r2), "r"(r3) : "memory");
}
__device__ __forceinline__ void stsm4t(uint32_t addr, uint32_t r0, uint32_t r1, uint32_t r2, uint32_t r3) {
    asm volatile("stmatrix.sync.aligned.m8n8.x4.trans.shared.b16 [%0], {%1, %2, %3, %4};" :: "r"(addr), "r"(r0), "r"(r1), "r"(r2), "r"(r3) : "memory");
}
__device__ __forceinline__ uint32_t movm(uint32_t a) { uint32_t d; asm volatile("movmatrix.sync.aligned.m8n8.trans.b16 %0, %1;" : "=r"(d) : "r"(a)); return d; }
__device__ __forceinline__ void ldsm4(uint32_t addr, uint32_t& r0, uint32_t& r1, uint32_t& r2, uint32_t& r3) {
    asm volatile("ldmatrix.sync.aligned.m8n8.x4.shared.b16 {%0, %1, %2, %3}, [%4];" : "=r"(r0), "=r"(r1), "=r"(r2), "=r"(r3) : "r"(addr) : "memory");
}
__device__ __forceinline__ void ldsm4t(uint32_t addr, uint32_t& r0, uint32_t& r1, uint32_t& r2, uint32_t& r3) {
    asm volatile("ldmatrix.sync.aligned.m8n8.x4.trans.shared.b16 {%0, %1, %2, %3}, [%4];" : "=r"(r0), "=r"(r1), "=r"(r2), "=r"(r3) : "r"(addr) : "memory");
}
__device__ __forceinline__ void mma16816(float (&c)[4], uint32_t a0, uint32_t a1, uint32_t a2, uint32_t a3, uint32_t b0, uint32_t b1) {
    asm("mma.sync.aligned.m16n8k16.row.col.f32.bf16.bf16.f32 {%0, %1, %2, %3}, {%4, %5, %6, %7}, {%8, %9}, {%0, %1, %2, %3};"
        : "+f"(c[0]), "+f"(c[1]), "+f"(c[2]), "+f"(c[3]) : "r"(a0), "r"(a1), "r"(a2), "r"(a3), "r"(b0), "r"(b1));
}
__device__ __forceinline__ float rcp(float x) { float r; asm("rcp.approx.ftz.f32 %0, %1;" : "=f"(r) : "f"(x)); return r; }
__device__ __forceinline__ float ex2(float x) { float r; asm("ex2.approx.ftz.f32 %0, %1;" : "=f"(r) : "f"(x)); return r; }
__device__ __forceinline__ float tanh_(float x) { float t; asm("tanh.approx.f32 %0, %1;" : "=f"(t) : "f"(x)); return t; }
__device__ __forceinline__ void block_end(uint32_t opaque, uint32_t id) { asm volatile("{\n.reg .pred p;\nsetp.eq.u32 p, %0, %1;\n@p trap;\n}" :: "r"(opaque), "r"(0xffffff00u + id)); }
__device__ __forceinline__ float silu_(float x) { return __fdividef(x, 1.f + __expf(-x)); }
__device__ __forceinline__ void st_pkt(void* p, uint32_t a, uint32_t b) {
    asm volatile("{\n.reg .b64 t;\nmov.b64 t, {%1, %2};\nst.relaxed.gpu.global.b64 [%0], t;\n}" :: "l"(p), "r"(a), "r"(b) : "memory");
}
__device__ __forceinline__ uint4 ld_pkt2(const void* p) {
    uint4 v; asm volatile("{\n.reg .b64 t, u;\nld.relaxed.gpu.global.v2.b64 {t, u}, [%4];\nmov.b64 {%0, %1}, t;\nmov.b64 {%2, %3}, u;\n}"
        : "=r"(v.x), "=r"(v.y), "=r"(v.z), "=r"(v.w) : "l"(p) : "memory"); return v;
}
__device__ __forceinline__ void st_pkt16(void* p, uint32_t a, uint32_t b, uint32_t c, uint32_t d) {
    asm volatile("{\n.reg .b64 t, u;\n.reg .b128 w;\nmov.b64 t, {%1, %2};\nmov.b64 u, {%3, %4};\nmov.b128 w, {t, u};\nst.relaxed.gpu.global.b128 [%0], w;\n}"
        :: "l"(p), "r"(a), "r"(b), "r"(c), "r"(d) : "memory");
}
__device__ __forceinline__ uint4 ld_pkt16(const void* p) {
    uint4 v; asm volatile("{\n.reg .b64 t, u;\n.reg .b128 w;\nld.relaxed.gpu.global.b128 w, [%4];\nmov.b128 {t, u}, w;\nmov.b64 {%0, %1}, t;\nmov.b64 {%2, %3}, u;\n}"
        : "=r"(v.x), "=r"(v.y), "=r"(v.z), "=r"(v.w) : "l"(p) : "memory"); return v;
}
#define SPIN_GUARD(n) do { if (++(n) > (1u << 22)) asm volatile("trap;"); } while (0)
__device__ __forceinline__ uint4 lds128(uint32_t a) { uint4 v; asm volatile("ld.shared.v4.u32 {%0, %1, %2, %3}, [%4];" : "=r"(v.x), "=r"(v.y), "=r"(v.z), "=r"(v.w) : "r"(a) : "memory"); return v; }
__device__ __forceinline__ void sts128(uint32_t a, uint32_t x, uint32_t y, uint32_t z, uint32_t w) { asm volatile("st.shared.v4.u32 [%0], {%1, %2, %3, %4};" :: "r"(a), "r"(x), "r"(y), "r"(z), "r"(w) : "memory"); }
__device__ __forceinline__ uint32_t lds32(uint32_t a) { uint32_t v; asm volatile("ld.shared.u32 %0, [%1];" : "=r"(v) : "r"(a) : "memory"); return v; }
__device__ __forceinline__ void sts32(uint32_t a, uint32_t v) { asm volatile("st.shared.u32 [%0], %1;" :: "r"(a), "r"(v) : "memory"); }
__device__ __forceinline__ bool elect_one() {
    uint32_t p; asm volatile("{\n.reg .pred q;\nelect.sync _|q, 0xffffffff;\nselp.u32 %0, 1, 0, q;\n}" : "=r"(p)); return p;
}
__device__ __forceinline__ void pause(uint32_t cycles) {
    uint32_t t0, t; asm volatile("mov.u32 %0, %%clock;" : "=r"(t0));
    do { __nanosleep(64); asm volatile("mov.u32 %0, %%clock;" : "=r"(t)); } while (t - t0 < cycles);
}
__device__ __forceinline__ void cluster_arrive() { asm volatile("barrier.cluster.arrive.relaxed.aligned;" ::: "memory"); }
__device__ __forceinline__ void cluster_wait() { asm volatile("barrier.cluster.wait.aligned;" ::: "memory"); }

__device__ __forceinline__ void wgmma_n128_z(float (&d)[64], uint64_t da, uint64_t db) {
    asm volatile("{\n.reg .pred p;\nsetp.ne.b32 p, 0, 0;\n"
        "wgmma.mma_async.sync.aligned.m64n128k16.f32.bf16.bf16 {"
        "%0, %1, %2, %3, %4, %5, %6, %7, %8, %9, %10, %11, %12, %13, %14, %15, "
        "%16, %17, %18, %19, %20, %21, %22, %23, %24, %25, %26, %27, %28, %29, %30, %31, "
        "%32, %33, %34, %35, %36, %37, %38, %39, %40, %41, %42, %43, %44, %45, %46, %47, "
        "%48, %49, %50, %51, %52, %53, %54, %55, %56, %57, %58, %59, %60, %61, %62, %63"
        "}, %64, %65, p, 1, 1, 0, 1;\n}\n"
        : "=f"(d[0]), "=f"(d[1]), "=f"(d[2]), "=f"(d[3]), "=f"(d[4]), "=f"(d[5]), "=f"(d[6]), "=f"(d[7]),
          "=f"(d[8]), "=f"(d[9]), "=f"(d[10]), "=f"(d[11]), "=f"(d[12]), "=f"(d[13]), "=f"(d[14]), "=f"(d[15]),
          "=f"(d[16]), "=f"(d[17]), "=f"(d[18]), "=f"(d[19]), "=f"(d[20]), "=f"(d[21]), "=f"(d[22]), "=f"(d[23]),
          "=f"(d[24]), "=f"(d[25]), "=f"(d[26]), "=f"(d[27]), "=f"(d[28]), "=f"(d[29]), "=f"(d[30]), "=f"(d[31]),
          "=f"(d[32]), "=f"(d[33]), "=f"(d[34]), "=f"(d[35]), "=f"(d[36]), "=f"(d[37]), "=f"(d[38]), "=f"(d[39]),
          "=f"(d[40]), "=f"(d[41]), "=f"(d[42]), "=f"(d[43]), "=f"(d[44]), "=f"(d[45]), "=f"(d[46]), "=f"(d[47]),
          "=f"(d[48]), "=f"(d[49]), "=f"(d[50]), "=f"(d[51]), "=f"(d[52]), "=f"(d[53]), "=f"(d[54]), "=f"(d[55]),
          "=f"(d[56]), "=f"(d[57]), "=f"(d[58]), "=f"(d[59]), "=f"(d[60]), "=f"(d[61]), "=f"(d[62]), "=f"(d[63])
        : "l"(da), "l"(db));
}
__device__ __forceinline__ void wgmma_n128(float (&d)[64], uint64_t da, uint64_t db) {
    asm volatile("{\n.reg .pred p;\nsetp.eq.b32 p, 0, 0;\n"
        "wgmma.mma_async.sync.aligned.m64n128k16.f32.bf16.bf16 {"
        "%0, %1, %2, %3, %4, %5, %6, %7, %8, %9, %10, %11, %12, %13, %14, %15, "
        "%16, %17, %18, %19, %20, %21, %22, %23, %24, %25, %26, %27, %28, %29, %30, %31, "
        "%32, %33, %34, %35, %36, %37, %38, %39, %40, %41, %42, %43, %44, %45, %46, %47, "
        "%48, %49, %50, %51, %52, %53, %54, %55, %56, %57, %58, %59, %60, %61, %62, %63"
        "}, %64, %65, p, 1, 1, 0, 1;\n}\n"
        : "+f"(d[0]), "+f"(d[1]), "+f"(d[2]), "+f"(d[3]), "+f"(d[4]), "+f"(d[5]), "+f"(d[6]), "+f"(d[7]),
          "+f"(d[8]), "+f"(d[9]), "+f"(d[10]), "+f"(d[11]), "+f"(d[12]), "+f"(d[13]), "+f"(d[14]), "+f"(d[15]),
          "+f"(d[16]), "+f"(d[17]), "+f"(d[18]), "+f"(d[19]), "+f"(d[20]), "+f"(d[21]), "+f"(d[22]), "+f"(d[23]),
          "+f"(d[24]), "+f"(d[25]), "+f"(d[26]), "+f"(d[27]), "+f"(d[28]), "+f"(d[29]), "+f"(d[30]), "+f"(d[31]),
          "+f"(d[32]), "+f"(d[33]), "+f"(d[34]), "+f"(d[35]), "+f"(d[36]), "+f"(d[37]), "+f"(d[38]), "+f"(d[39]),
          "+f"(d[40]), "+f"(d[41]), "+f"(d[42]), "+f"(d[43]), "+f"(d[44]), "+f"(d[45]), "+f"(d[46]), "+f"(d[47]),
          "+f"(d[48]), "+f"(d[49]), "+f"(d[50]), "+f"(d[51]), "+f"(d[52]), "+f"(d[53]), "+f"(d[54]), "+f"(d[55]),
          "+f"(d[56]), "+f"(d[57]), "+f"(d[58]), "+f"(d[59]), "+f"(d[60]), "+f"(d[61]), "+f"(d[62]), "+f"(d[63])
        : "l"(da), "l"(db));
}
__device__ __forceinline__ void wgmma_n176_z(float (&d)[88], uint64_t da, uint64_t db) {
    asm volatile("{\n.reg .pred p;\nsetp.ne.b32 p, 0, 0;\n"
        "wgmma.mma_async.sync.aligned.m64n176k16.f32.bf16.bf16 {"
        "%0, %1, %2, %3, %4, %5, %6, %7, %8, %9, %10, %11, %12, %13, %14, %15, "
        "%16, %17, %18, %19, %20, %21, %22, %23, %24, %25, %26, %27, %28, %29, %30, %31, "
        "%32, %33, %34, %35, %36, %37, %38, %39, %40, %41, %42, %43, %44, %45, %46, %47, "
        "%48, %49, %50, %51, %52, %53, %54, %55, %56, %57, %58, %59, %60, %61, %62, %63, "
        "%64, %65, %66, %67, %68, %69, %70, %71, %72, %73, %74, %75, %76, %77, %78, %79, "
        "%80, %81, %82, %83, %84, %85, %86, %87"
        "}, %88, %89, p, 1, 1, 0, 1;\n}\n"
        : "=f"(d[0]), "=f"(d[1]), "=f"(d[2]), "=f"(d[3]), "=f"(d[4]), "=f"(d[5]), "=f"(d[6]), "=f"(d[7]),
          "=f"(d[8]), "=f"(d[9]), "=f"(d[10]), "=f"(d[11]), "=f"(d[12]), "=f"(d[13]), "=f"(d[14]), "=f"(d[15]),
          "=f"(d[16]), "=f"(d[17]), "=f"(d[18]), "=f"(d[19]), "=f"(d[20]), "=f"(d[21]), "=f"(d[22]), "=f"(d[23]),
          "=f"(d[24]), "=f"(d[25]), "=f"(d[26]), "=f"(d[27]), "=f"(d[28]), "=f"(d[29]), "=f"(d[30]), "=f"(d[31]),
          "=f"(d[32]), "=f"(d[33]), "=f"(d[34]), "=f"(d[35]), "=f"(d[36]), "=f"(d[37]), "=f"(d[38]), "=f"(d[39]),
          "=f"(d[40]), "=f"(d[41]), "=f"(d[42]), "=f"(d[43]), "=f"(d[44]), "=f"(d[45]), "=f"(d[46]), "=f"(d[47]),
          "=f"(d[48]), "=f"(d[49]), "=f"(d[50]), "=f"(d[51]), "=f"(d[52]), "=f"(d[53]), "=f"(d[54]), "=f"(d[55]),
          "=f"(d[56]), "=f"(d[57]), "=f"(d[58]), "=f"(d[59]), "=f"(d[60]), "=f"(d[61]), "=f"(d[62]), "=f"(d[63]),
          "=f"(d[64]), "=f"(d[65]), "=f"(d[66]), "=f"(d[67]), "=f"(d[68]), "=f"(d[69]), "=f"(d[70]), "=f"(d[71]),
          "=f"(d[72]), "=f"(d[73]), "=f"(d[74]), "=f"(d[75]), "=f"(d[76]), "=f"(d[77]), "=f"(d[78]), "=f"(d[79]),
          "=f"(d[80]), "=f"(d[81]), "=f"(d[82]), "=f"(d[83]), "=f"(d[84]), "=f"(d[85]), "=f"(d[86]), "=f"(d[87])
        : "l"(da), "l"(db));
}
__device__ __forceinline__ void wgmma_n176(float (&d)[88], uint64_t da, uint64_t db) {
    asm volatile("{\n.reg .pred p;\nsetp.eq.b32 p, 0, 0;\n"
        "wgmma.mma_async.sync.aligned.m64n176k16.f32.bf16.bf16 {"
        "%0, %1, %2, %3, %4, %5, %6, %7, %8, %9, %10, %11, %12, %13, %14, %15, "
        "%16, %17, %18, %19, %20, %21, %22, %23, %24, %25, %26, %27, %28, %29, %30, %31, "
        "%32, %33, %34, %35, %36, %37, %38, %39, %40, %41, %42, %43, %44, %45, %46, %47, "
        "%48, %49, %50, %51, %52, %53, %54, %55, %56, %57, %58, %59, %60, %61, %62, %63, "
        "%64, %65, %66, %67, %68, %69, %70, %71, %72, %73, %74, %75, %76, %77, %78, %79, "
        "%80, %81, %82, %83, %84, %85, %86, %87"
        "}, %88, %89, p, 1, 1, 0, 1;\n}\n"
        : "+f"(d[0]), "+f"(d[1]), "+f"(d[2]), "+f"(d[3]), "+f"(d[4]), "+f"(d[5]), "+f"(d[6]), "+f"(d[7]),
          "+f"(d[8]), "+f"(d[9]), "+f"(d[10]), "+f"(d[11]), "+f"(d[12]), "+f"(d[13]), "+f"(d[14]), "+f"(d[15]),
          "+f"(d[16]), "+f"(d[17]), "+f"(d[18]), "+f"(d[19]), "+f"(d[20]), "+f"(d[21]), "+f"(d[22]), "+f"(d[23]),
          "+f"(d[24]), "+f"(d[25]), "+f"(d[26]), "+f"(d[27]), "+f"(d[28]), "+f"(d[29]), "+f"(d[30]), "+f"(d[31]),
          "+f"(d[32]), "+f"(d[33]), "+f"(d[34]), "+f"(d[35]), "+f"(d[36]), "+f"(d[37]), "+f"(d[38]), "+f"(d[39]),
          "+f"(d[40]), "+f"(d[41]), "+f"(d[42]), "+f"(d[43]), "+f"(d[44]), "+f"(d[45]), "+f"(d[46]), "+f"(d[47]),
          "+f"(d[48]), "+f"(d[49]), "+f"(d[50]), "+f"(d[51]), "+f"(d[52]), "+f"(d[53]), "+f"(d[54]), "+f"(d[55]),
          "+f"(d[56]), "+f"(d[57]), "+f"(d[58]), "+f"(d[59]), "+f"(d[60]), "+f"(d[61]), "+f"(d[62]), "+f"(d[63]),
          "+f"(d[64]), "+f"(d[65]), "+f"(d[66]), "+f"(d[67]), "+f"(d[68]), "+f"(d[69]), "+f"(d[70]), "+f"(d[71]),
          "+f"(d[72]), "+f"(d[73]), "+f"(d[74]), "+f"(d[75]), "+f"(d[76]), "+f"(d[77]), "+f"(d[78]), "+f"(d[79]),
          "+f"(d[80]), "+f"(d[81]), "+f"(d[82]), "+f"(d[83]), "+f"(d[84]), "+f"(d[85]), "+f"(d[86]), "+f"(d[87])
        : "l"(da), "l"(db));
}
__device__ __forceinline__ void wgmma_n256_z(float (&d)[128], uint64_t da, uint64_t db) {
    asm volatile("{\n.reg .pred p;\nsetp.ne.b32 p, 0, 0;\n"
        "wgmma.mma_async.sync.aligned.m64n256k16.f32.bf16.bf16 {"
        "%0, %1, %2, %3, %4, %5, %6, %7, %8, %9, %10, %11, %12, %13, %14, %15, "
        "%16, %17, %18, %19, %20, %21, %22, %23, %24, %25, %26, %27, %28, %29, %30, %31, "
        "%32, %33, %34, %35, %36, %37, %38, %39, %40, %41, %42, %43, %44, %45, %46, %47, "
        "%48, %49, %50, %51, %52, %53, %54, %55, %56, %57, %58, %59, %60, %61, %62, %63, "
        "%64, %65, %66, %67, %68, %69, %70, %71, %72, %73, %74, %75, %76, %77, %78, %79, "
        "%80, %81, %82, %83, %84, %85, %86, %87, %88, %89, %90, %91, %92, %93, %94, %95, "
        "%96, %97, %98, %99, %100, %101, %102, %103, %104, %105, %106, %107, %108, %109, %110, %111, "
        "%112, %113, %114, %115, %116, %117, %118, %119, %120, %121, %122, %123, %124, %125, %126, %127"
        "}, %128, %129, p, 1, 1, 0, 1;\n}\n"
        : "=f"(d[0]), "=f"(d[1]), "=f"(d[2]), "=f"(d[3]), "=f"(d[4]), "=f"(d[5]), "=f"(d[6]), "=f"(d[7]),
          "=f"(d[8]), "=f"(d[9]), "=f"(d[10]), "=f"(d[11]), "=f"(d[12]), "=f"(d[13]), "=f"(d[14]), "=f"(d[15]),
          "=f"(d[16]), "=f"(d[17]), "=f"(d[18]), "=f"(d[19]), "=f"(d[20]), "=f"(d[21]), "=f"(d[22]), "=f"(d[23]),
          "=f"(d[24]), "=f"(d[25]), "=f"(d[26]), "=f"(d[27]), "=f"(d[28]), "=f"(d[29]), "=f"(d[30]), "=f"(d[31]),
          "=f"(d[32]), "=f"(d[33]), "=f"(d[34]), "=f"(d[35]), "=f"(d[36]), "=f"(d[37]), "=f"(d[38]), "=f"(d[39]),
          "=f"(d[40]), "=f"(d[41]), "=f"(d[42]), "=f"(d[43]), "=f"(d[44]), "=f"(d[45]), "=f"(d[46]), "=f"(d[47]),
          "=f"(d[48]), "=f"(d[49]), "=f"(d[50]), "=f"(d[51]), "=f"(d[52]), "=f"(d[53]), "=f"(d[54]), "=f"(d[55]),
          "=f"(d[56]), "=f"(d[57]), "=f"(d[58]), "=f"(d[59]), "=f"(d[60]), "=f"(d[61]), "=f"(d[62]), "=f"(d[63]),
          "=f"(d[64]), "=f"(d[65]), "=f"(d[66]), "=f"(d[67]), "=f"(d[68]), "=f"(d[69]), "=f"(d[70]), "=f"(d[71]),
          "=f"(d[72]), "=f"(d[73]), "=f"(d[74]), "=f"(d[75]), "=f"(d[76]), "=f"(d[77]), "=f"(d[78]), "=f"(d[79]),
          "=f"(d[80]), "=f"(d[81]), "=f"(d[82]), "=f"(d[83]), "=f"(d[84]), "=f"(d[85]), "=f"(d[86]), "=f"(d[87]),
          "=f"(d[88]), "=f"(d[89]), "=f"(d[90]), "=f"(d[91]), "=f"(d[92]), "=f"(d[93]), "=f"(d[94]), "=f"(d[95]),
          "=f"(d[96]), "=f"(d[97]), "=f"(d[98]), "=f"(d[99]), "=f"(d[100]), "=f"(d[101]), "=f"(d[102]), "=f"(d[103]),
          "=f"(d[104]), "=f"(d[105]), "=f"(d[106]), "=f"(d[107]), "=f"(d[108]), "=f"(d[109]), "=f"(d[110]), "=f"(d[111]),
          "=f"(d[112]), "=f"(d[113]), "=f"(d[114]), "=f"(d[115]), "=f"(d[116]), "=f"(d[117]), "=f"(d[118]), "=f"(d[119]),
          "=f"(d[120]), "=f"(d[121]), "=f"(d[122]), "=f"(d[123]), "=f"(d[124]), "=f"(d[125]), "=f"(d[126]), "=f"(d[127])
        : "l"(da), "l"(db));
}
__device__ __forceinline__ void wgmma_n256(float (&d)[128], uint64_t da, uint64_t db) {
    asm volatile("{\n.reg .pred p;\nsetp.eq.b32 p, 0, 0;\n"
        "wgmma.mma_async.sync.aligned.m64n256k16.f32.bf16.bf16 {"
        "%0, %1, %2, %3, %4, %5, %6, %7, %8, %9, %10, %11, %12, %13, %14, %15, "
        "%16, %17, %18, %19, %20, %21, %22, %23, %24, %25, %26, %27, %28, %29, %30, %31, "
        "%32, %33, %34, %35, %36, %37, %38, %39, %40, %41, %42, %43, %44, %45, %46, %47, "
        "%48, %49, %50, %51, %52, %53, %54, %55, %56, %57, %58, %59, %60, %61, %62, %63, "
        "%64, %65, %66, %67, %68, %69, %70, %71, %72, %73, %74, %75, %76, %77, %78, %79, "
        "%80, %81, %82, %83, %84, %85, %86, %87, %88, %89, %90, %91, %92, %93, %94, %95, "
        "%96, %97, %98, %99, %100, %101, %102, %103, %104, %105, %106, %107, %108, %109, %110, %111, "
        "%112, %113, %114, %115, %116, %117, %118, %119, %120, %121, %122, %123, %124, %125, %126, %127"
        "}, %128, %129, p, 1, 1, 0, 1;\n}\n"
        : "+f"(d[0]), "+f"(d[1]), "+f"(d[2]), "+f"(d[3]), "+f"(d[4]), "+f"(d[5]), "+f"(d[6]), "+f"(d[7]),
          "+f"(d[8]), "+f"(d[9]), "+f"(d[10]), "+f"(d[11]), "+f"(d[12]), "+f"(d[13]), "+f"(d[14]), "+f"(d[15]),
          "+f"(d[16]), "+f"(d[17]), "+f"(d[18]), "+f"(d[19]), "+f"(d[20]), "+f"(d[21]), "+f"(d[22]), "+f"(d[23]),
          "+f"(d[24]), "+f"(d[25]), "+f"(d[26]), "+f"(d[27]), "+f"(d[28]), "+f"(d[29]), "+f"(d[30]), "+f"(d[31]),
          "+f"(d[32]), "+f"(d[33]), "+f"(d[34]), "+f"(d[35]), "+f"(d[36]), "+f"(d[37]), "+f"(d[38]), "+f"(d[39]),
          "+f"(d[40]), "+f"(d[41]), "+f"(d[42]), "+f"(d[43]), "+f"(d[44]), "+f"(d[45]), "+f"(d[46]), "+f"(d[47]),
          "+f"(d[48]), "+f"(d[49]), "+f"(d[50]), "+f"(d[51]), "+f"(d[52]), "+f"(d[53]), "+f"(d[54]), "+f"(d[55]),
          "+f"(d[56]), "+f"(d[57]), "+f"(d[58]), "+f"(d[59]), "+f"(d[60]), "+f"(d[61]), "+f"(d[62]), "+f"(d[63]),
          "+f"(d[64]), "+f"(d[65]), "+f"(d[66]), "+f"(d[67]), "+f"(d[68]), "+f"(d[69]), "+f"(d[70]), "+f"(d[71]),
          "+f"(d[72]), "+f"(d[73]), "+f"(d[74]), "+f"(d[75]), "+f"(d[76]), "+f"(d[77]), "+f"(d[78]), "+f"(d[79]),
          "+f"(d[80]), "+f"(d[81]), "+f"(d[82]), "+f"(d[83]), "+f"(d[84]), "+f"(d[85]), "+f"(d[86]), "+f"(d[87]),
          "+f"(d[88]), "+f"(d[89]), "+f"(d[90]), "+f"(d[91]), "+f"(d[92]), "+f"(d[93]), "+f"(d[94]), "+f"(d[95]),
          "+f"(d[96]), "+f"(d[97]), "+f"(d[98]), "+f"(d[99]), "+f"(d[100]), "+f"(d[101]), "+f"(d[102]), "+f"(d[103]),
          "+f"(d[104]), "+f"(d[105]), "+f"(d[106]), "+f"(d[107]), "+f"(d[108]), "+f"(d[109]), "+f"(d[110]), "+f"(d[111]),
          "+f"(d[112]), "+f"(d[113]), "+f"(d[114]), "+f"(d[115]), "+f"(d[116]), "+f"(d[117]), "+f"(d[118]), "+f"(d[119]),
          "+f"(d[120]), "+f"(d[121]), "+f"(d[122]), "+f"(d[123]), "+f"(d[124]), "+f"(d[125]), "+f"(d[126]), "+f"(d[127])
        : "l"(da), "l"(db));
}

struct Idx {
    uint32_t lane, warp, w4, q4, g8, prow, pan;
    __device__ __forceinline__ Idx() {
        uint32_t t; asm volatile("mov.u32 %0, %%tid.x;" : "=r"(t));
        lane = t & 31; warp = t >> 5; w4 = warp & 3; q4 = lane & 3; g8 = lane >> 2;
        prow = w4 * 16 + ((lane >> 3) & 1) * 8 + (lane & 7);
        pan = prow * 128 + (((lane >> 4) ^ (lane & 7)) << 4);
    }
};
#define IDX() const Idx ix; const uint32_t lane = ix.lane, warp = ix.warp, w4 = ix.w4, q4 = ix.q4, g8 = ix.g8, prow = ix.prow, pan_addr = ix.pan; \
    (void)lane; (void)warp; (void)w4; (void)q4; (void)g8; (void)prow; (void)pan_addr;

__device__ __forceinline__ int kof(int t, int sh, int j) {
    const int p = t >> (sh - 1), pn = p < 2 ? p : p >= 9, q = p - 2 - 7 * pn;
    return ((p < 2 ? j : q + (q >= j)) << 7) + (pn << 6) + ((t & (sh - 1)) << 5);
}
__device__ __forceinline__ uint32_t fidx(uint32_t m, uint32_t w, uint32_t pn) {
    return m * 32 + w * 16 + pn;
}
constexpr int HC0 = 8 * 48, HC3 = HC0 + 3072;
__device__ __forceinline__ int hcol(int p, int j) { return HC0 + p * 1024 + j * 128; }
struct Ring {
    uint32_t slot, par;
    __device__ __forceinline__ void next() { if (++slot == NSLOT) { slot = 0; par ^= 1; } }
    __device__ __forceinline__ void skip(uint32_t n) { slot += n; if (slot >= NSLOT) { slot -= NSLOT; par ^= 1; } }
};
__device__ __forceinline__ uint32_t BAR_FULL(uint32_t sb, uint32_t s) { return sb + OFF_BAR + 8 * s; }
constexpr uint32_t AF_REL = 48;
__device__ __forceinline__ uint32_t BAR_EMPTY(uint32_t sb, uint32_t s) { return sb + OFF_BAR + 96 + 8 * s; }
__device__ __forceinline__ uint32_t BAR_SFULL(uint32_t sb, uint32_t i) { return sb + OFF_BAR + 152 + 8 * i; }
__device__ __forceinline__ uint32_t BAR_SREADY(uint32_t sb, uint32_t i) { return sb + OFF_BAR + 184 + 8 * i; }
__device__ __forceinline__ uint32_t BAR_ONE(uint32_t sb, uint32_t i) { return sb + OFF_BAR + 216 + 8 * i; }
enum { EV_WIN, EV_WIN1, EV_WIN2, EV_WIN3, EV_P0, EV_GA, EV_GB, EV_LN2, EV_LAG0, EV_LAG1, EV_LAG2, EV_LAG3, EV_LAG4, EV_LAG5, EV_KV, EV_PAR, EV_AGO, EV_AGO1, EV_AGO2, EV_FGO, EV_FGO1, EV_FGO2, EV_H0, EV_H1, EV_H2, EV_H3, EV_COUNT };
constexpr int NB_TAIL = 4;

struct Rel {
    uint32_t base; bool sig;
    __device__ __forceinline__ Rel(uint32_t sb, uint32_t tw) {
        uint32_t a; asm("mapa.shared::cluster.u32 %0, %1, %2;" : "=r"(a) : "r"(BAR_EMPTY(sb, 0)), "r"((tw >> 5) & 1));
        base = __shfl_sync(0xffffffffu, a, 0); sig = (tw & ~32u) == 0;
    }
    __device__ __forceinline__ void operator()(uint32_t slot) const {
        if (sig) asm volatile("mbarrier.arrive.shared::cluster.b64 _, [%0];" :: "r"(base + 8 * slot) : "memory");
    }
};
struct LnRow { float rs0, nm0, rs1, nm1; };
struct Pipe {
    Rel rel; uint32_t p1, p2;
    __device__ __forceinline__ Pipe(uint32_t sb, uint32_t tw, uint32_t first) : rel(sb, tw), p1(first), p2(NSLOT) {}
    template <bool TWO> __device__ __forceinline__ void acquire(uint32_t sb, uint32_t af, const Ring& r) {
        const uint32_t b0 = BAR_FULL(sb, r.slot), b1 = b0 + af;
        const bool ready = TWO ? mbar_test2(b0, b1, r.par) : mbar_test(b0, r.par);
        wg_wait<1>();
        rel(p2);
        if (!ready) { if (TWO) mbar_wait2(b0, b1, r.par); else mbar_wait(b0, r.par); }
    }
    __device__ __forceinline__ void issued(uint32_t slot) { p2 = p1; p1 = slot; }
    __device__ __forceinline__ void drain1() { wg_wait<1>(); rel(p2); p2 = NSLOT; }
    __device__ __forceinline__ void drain0() { wg_wait<0>(); rel(p1); p1 = NSLOT; }
    template <bool TWO, class Step> __device__ __forceinline__ void hold(int LG, uint32_t sb, uint32_t af, Ring& r, uint32_t lag_bar, Step step) {
        Ring q = r;
#pragma unroll 1
        for (int i = 0; i < LG; ++i) { if (TWO) mbar_wait2(BAR_FULL(sb, q.slot), BAR_FULL(sb, q.slot) + af, q.par); else mbar_wait(BAR_FULL(sb, q.slot), q.par); q.next(); }
        mbar_wait(lag_bar, 0);
#pragma unroll 1
        do {
            step(r.slot);
            wg_wait<2>(); rel(p2); p2 = p1; p1 = r.slot;
            if (++r.slot == NSLOT) r.slot = 0;
        } while (r.slot != q.slot);
        r.par = q.par;
    }
};
template <bool TWO, bool FIRST, int NA, int NB>
__device__ __forceinline__ void step32(float (&aa)[NA], float (&ab)[NB], uint32_t sb, uint32_t wg, uint32_t slot, int own) {
    const uint32_t st = d16(sb) + slot * (SLOT >> 4);
    const uint32_t alo = own >= 0 ? d16(sb) + OFF_STG / 16 + wg * 1024 + (own >> 1) * 512 + (own & 1) * 4 : st + wg * 256;
    const uint32_t ahi = own >= 0 ? (1024 >> 4) | (1u << 30) : (512 >> 4) | (2u << 30);
    wg_fence();
#pragma unroll
    for (int k = 0; k < 2; ++k) {
        const uint64_t da = ((uint64_t)ahi << 32) | (alo + k * 2 + 0x10000);
        if constexpr (NA == 88) {
            const uint64_t d0 = mk_desc(st, 8192 + k * 2048, 8192, 1024, 1), d1 = mk_desc(st, 12288 + k * 2048, 8192, 1024, 1);
            if (FIRST && k == 0) { wgmma_n176_z(aa, da, d0); wgmma_n176_z(ab, da, d1); }
            else { wgmma_n176(aa, da, d0); wgmma_n176(ab, da, d1); }
        } else {
            const uint64_t d0 = mk_desc(st, 8192 + k * 2048, 4096, 1024, 1), d1 = mk_desc(st, 24576 + k * 2048, 4096, 1024, 1);
            if (FIRST && k == 0) { wgmma_n256_z(aa, da, d0); if constexpr (TWO) wgmma_n128_z(ab, da, d1); }
            else { wgmma_n256(aa, da, d0); if constexpr (TWO) wgmma_n128(ab, da, d1); }
        }
    }
    wg_commit();
}
template <bool TWO, int LG, int NA, int NB, class Tail>
__device__ __forceinline__ void mainloop32(float (&aa)[NA], float (&ab)[NB], uint32_t sb, uint32_t wg, uint32_t tw, Ring& r, uint32_t lag_ev, int g0, Tail tail) {
    if (!TWO) mbar_wait(BAR_FULL(sb, r.slot), r.par);
    step32<TWO, true>(aa, ab, sb, wg, r.slot, TWO ? 0 : -1);
    TS(g0, 0);
    Pipe pp(sb, tw, r.slot);
    r.next();
    const int end = wg ? 32 : 32 - LG;
#pragma unroll 1
    for (int it = 1; it < end; ++it) {
        pp.acquire<TWO>(sb, wg ? 0 : AF_REL, r);
        step32<TWO, false>(aa, ab, sb, wg, r.slot, TWO && it < 4 ? it : -1);
        pp.issued(r.slot);
        TS(g0 + it, 0);
        r.next();
    }
    if (wg == 0) { pp.drain1(); pp.drain0(); pp.hold<TWO>(LG, sb, AF_REL, r, BAR_ONE(sb, lag_ev), [&](uint32_t slot) { step32<TWO, false>(aa, ab, sb, 0, slot, -1); }); }
    pp.drain1();
    if (wg == 1 && tw == 0) mbar_arrive(BAR_ONE(sb, lag_ev));
    tail();
    pp.drain0();
    TS(g0 + 31, 1);
}
template <bool FIRST>
__device__ __forceinline__ void step64(float (&acc)[64], uint32_t sb, uint32_t wg, uint32_t slot, int own) {
    const uint32_t sbb = d16(sb) + slot * (SLOT >> 4), sa = own >= 0 ? d16(sb) + OFF_STG / 16 + wg * 1024 + own * 512 : sbb + wg * 512;
    wg_fence();
#pragma unroll
    for (int k = 0; k < 4; ++k) {
        const uint64_t da = mk_desc(sa, k * 32, 16, 1024, 1), db = mk_desc(sbb, 16384 + k * 2048, 8192, 1024, 1);
        if (FIRST && k == 0) wgmma_n128_z(acc, da, db); else wgmma_n128(acc, da, db);
    }
    wg_commit();
}
template <class Mid, class Tail>
__device__ __forceinline__ void mainloop64(float (&acc)[64], bool wo, uint32_t sb, uint32_t wg, uint32_t tw, Ring& r, Mid mid, Tail tail) {
    const int g0 = wo ? 32 : 144, nst = wo ? 16 : 56, lg = wo ? LAGW : LAGD; (void)g0;
    const uint32_t lag_bar = BAR_ONE(sb, wo ? EV_LAG4 : EV_LAG5), af = wo && !wg ? AF_REL : 0;
    mbar_wait(BAR_FULL(sb, r.slot), r.par);
    if (!wo) CS(28);
    step64<true>(acc, sb, wg, r.slot, wo ? 0 : -1);
    if (!wo) CS(29);
    TS(g0, 0);
    Pipe pp(sb, tw, r.slot);
    r.next();
    int it = 1;
    auto run = [&](int end, int own) {
#pragma unroll 1
        do {
            pp.acquire<true>(sb, af, r);
            step64<false>(acc, sb, wg, r.slot, own);
            pp.issued(r.slot);
            TS(g0 + it, 0);
            if (wo && it == 2) CS(9);
            r.next();
            if (own > 0) {
                own = -1;
                pp.drain1(); pp.drain0();
                TS(g0 + 1, 1);
            }
        } while (++it < end);
    };
    const int end = wg ? nst : nst - lg;
    run(wo ? MIDW : wg ? MIDD : end, wo ? 1 : -1);
    mid();
    if (it < end) run(end, -1);
    if (wg == 0) { pp.drain1(); pp.drain0(); pp.hold<true>(lg, sb, af, r, lag_bar, [&](uint32_t slot) { step64<false>(acc, sb, 0, slot, -1); }); }
    pp.drain1();
    if (wg == 1 && tw == 0) mbar_arrive(lag_bar);
    tail();
    pp.drain0();
    TS(g0 + nst - 1, 1);
}

struct RowAcc {
    float sm[4] = {0.f, 0.f, 0.f, 0.f}, sq[4] = {0.f, 0.f, 0.f, 0.f};
    __device__ __forceinline__ void add(int e, float x) { sm[e & 3] += x; sq[e & 3] = fmaf(x, x, sq[e & 3]); }
    __device__ __forceinline__ void publish(uint4* dst, uint32_t q4, uint32_t ep) const {
        const float s0 = sm[0] + sm[1], s1 = sm[2] + sm[3], q0 = sq[0] + sq[1], q1 = sq[2] + sq[3];
        const bool od = q4 & 1;
        float sv = (od ? s1 : s0) + __shfl_xor_sync(0xffffffffu, od ? s0 : s1, 1), qv = (od ? q1 : q0) + __shfl_xor_sync(0xffffffffu, od ? q0 : q1, 1);
        sv += __shfl_xor_sync(0xffffffffu, sv, 2); qv += __shfl_xor_sync(0xffffffffu, qv, 2);
        st_pkt16(dst + (q4 & 1) * 8, 0, __float_as_uint(sv), __float_as_uint(qv), ep);
    }
};
__device__ __forceinline__ LnRow merge_stats(const uint4* src, uint32_t q4, uint32_t ep, uint32_t sb) {
    uint4 t[4];
    uint32_t n = 0;
    while (true) {
#pragma unroll
        for (int i = 0; i < 4; ++i) t[i] = ld_pkt16(src + (q4 * 2 + (i >> 1)) * 512 + (i & 1) * 8);
        const bool ok_ = __all_sync(0xffffffffu, t[0].w == ep && t[1].w == ep && t[2].w == ep && t[3].w == ep);
        if (n < 4) CS(14 + n);
        if (ok_) break;
        SPIN_GUARD(n);
    }
    float v[4];
#pragma unroll
    for (int h = 0; h < 2; ++h) { v[h] = __uint_as_float(t[h].y) + __uint_as_float(t[2 + h].y); v[2 + h] = __uint_as_float(t[h].z) + __uint_as_float(t[2 + h].z); }
#pragma unroll
    for (int o = 1; o < 4; o <<= 1)
#pragma unroll
        for (int i = 0; i < 4; ++i) v[i] += __shfl_xor_sync(0xffffffffu, v[i], o);
    const float m0 = v[0] * (1.f / D_), m1 = v[1] * (1.f / D_);
    const float r0 = rsqrtf(fmaxf(fmaf(-m0, m0, v[2] * (1.f / D_)), 0.f) + 1e-5f), r1 = rsqrtf(fmaxf(fmaf(-m1, m1, v[3] * (1.f / D_)), 0.f) + 1e-5f);
    return LnRow{r0, -m0 * r0, r1, -m1 * r1};
}
struct Stg {
    uint32_t b, par;
    __device__ __forceinline__ uint32_t acquire2(uint32_t sb, uint32_t wg) {
        mbar_wait2(BAR_SREADY(sb, wg * 2), BAR_SREADY(sb, wg * 2 + 1), par);
        par ^= 1;
        return sb + OFF_STG + wg * 16384;
    }
    __device__ __forceinline__ void publish(uint32_t sb, uint32_t wg, uint32_t lane) {
        fence_async_smem();
        __syncwarp();
        if (lane == 0) mbar_arrive(BAR_SFULL(sb, wg * 2 + b));
        b ^= 1;
    }
};

struct LnPar {
    uint4 p[8];
    __device__ __forceinline__ void load(uint32_t sb, uint32_t q4) {
#pragma unroll
        for (int i = 0; i < 8; ++i) p[i] = lds128(sb + OFF_PAR + i * 64 + q4 * 16);
    }
};
__device__ __forceinline__ void ln_norm(uint32_t (&xn)[32], const float (&x)[64], const LnRow& n) {
#pragma unroll
    for (int e = 0; e < 32; ++e) {
        const float rs = (e & 1) ? n.rs1 : n.rs0, nm = (e & 1) ? n.nm1 : n.nm0;
        xn[e] = pack2(fmaf(x[2 * e], rs, nm), fmaf(x[2 * e + 1], rs, nm));
    }
}
__device__ __forceinline__ void ln_emit(const uint32_t (&xr)[32], const LnPar& lp, uint32_t sb, uint32_t wg, const Idx& ix) {
#pragma unroll
    for (int i = 0; i < 8; ++i)
        stsm4(sb + OFF_STG + wg * 16384 + (i >> 2) * 8192 + (ix.pan ^ ((i & 3) << 5)), hfma2_bf16(xr[4 * i], lp.p[i].z, lp.p[i].x), hfma2_bf16(xr[4 * i + 1], lp.p[i].z, lp.p[i].x),
              hfma2_bf16(xr[4 * i + 2], lp.p[i].w, lp.p[i].y), hfma2_bf16(xr[4 * i + 3], lp.p[i].w, lp.p[i].y));
    fence_async_smem();
    __syncwarp();
    if (ix.lane < 2) mbar_arrive(BAR_SFULL(sb, wg * 2 + ix.lane));
    bar_sync(1 + wg, 128);
}
__device__ __forceinline__ void load_slab(uint32_t (&xr)[32], uint32_t buf) {
    IDX();
#pragma unroll
    for (int i = 0; i < 8; ++i) ldsm4(buf + (i >> 2) * 8192 + (pan_addr ^ ((i & 3) << 5)), xr[4 * i], xr[4 * i + 1], xr[4 * i + 2], xr[4 * i + 3]);
}
__device__ __forceinline__ void unpack_slab(float (&x)[64], const uint32_t (&xr)[32]) {
#pragma unroll
    for (int i = 0; i < 32; ++i) unpack2(xr[i], x[2 * i], x[2 * i + 1]);
}
__device__ __forceinline__ void store_slab(const float (&x)[64], uint32_t buf, uint32_t pitch, uint32_t pan, int i0, int i1) {
#pragma unroll
    for (int i = i0; i < i1; ++i)
        stsm4(buf + (i >> 2) * pitch + (pan ^ ((i & 3) << 5)), pack2(x[8 * i], x[8 * i + 1]), pack2(x[8 * i + 2], x[8 * i + 3]), pack2(x[8 * i + 4], x[8 * i + 5]), pack2(x[8 * i + 6], x[8 * i + 7]));
}
__device__ __forceinline__ void fetch_halo(uint4* src, bool first, uint32_t sb, uint32_t W, uint32_t lane) {
    mbar_wait(BAR_ONE(sb, EV_KV), 0);
    mbar_wait2(BAR_SREADY(sb, 0), BAR_SREADY(sb, 1), 1);
    uint4 hv[8];
    uint32_t n = 0;
    while (true) {
        bool ok = true;
#pragma unroll
        for (int i = 0; i < 8; ++i) { hv[i] = first ? make_uint4(0, 0, 0, 0) : ld_pkt16(src + i * 32); ok = ok && hv[i].x != 0; }
        if (first || __all_sync(0xffffffffu, ok)) break;
        SPIN_GUARD(n);
    }
#pragma unroll
    for (int i = 0; i < 8; ++i) stsm4(sb + OFF_STG + W * 2048 + (i >> 2) * 8192 + (i & 3) * 512 + lane * 16, hv[i].x, hv[i].y, hv[i].z, hv[i].w);
    bar_arrive(NB_TAIL + W, 64);
    if (!first) {
#pragma unroll
        for (int i = 0; i < 8; ++i) src[i * 32] = make_uint4(0, 0, 0, 0);
    }
}

template <int NG, class G, class U, class Buf>
__device__ __forceinline__ void glu(uint32_t sb, uint32_t wg, G g, U u, Buf buf) {
    IDX();
#pragma unroll
    for (int k = 0; k < NG; ++k) {
        float h[8];
#pragma unroll
        for (int e = 0; e < 8; ++e) h[e] = fmaf(tanh_(g(8 * k + e)), u(8 * k + e), u(8 * k + e));
        stsm4(buf(k >> 2) + (pan_addr ^ ((k & 3) << 5)), pack2(h[0], h[1]), pack2(h[2], h[3]), pack2(h[4], h[5]), pack2(h[6], h[7]));
    }
    fence_async_smem();
    __syncwarp();
    if (lane < 2) mbar_arrive(BAR_SFULL(sb, wg * 2 + lane));
}

template <int NP>
__device__ __forceinline__ void passes128(uint32_t sb, uint32_t wg, uint32_t tw, Ring& r, Stg& stg) {
#pragma unroll 1
    for (int p = 0; p < NP; ++p) {
        float b256[128], none[1];
        mainloop32<false, LAGS>(b256, none, sb, wg, tw, r, EV_LAG2 + p, 80 + 32 * (p & 1), [&] { stg.acquire2(sb, wg); });
        if (threadIdx.x == 0) { TL(29 + 2 * p); TC(114 + 2 * p); }
        if (threadIdx.x == 128) TL(53 + 2 * (p & 1));
        CS(24 + 2 * (p & 1));
        glu<8>(sb, wg, [&](int i) { return b256[i + (i & 32)]; }, [&](int i) { return b256[i + (i & 32) + 32]; }, [&](int pn) { return sb + OFF_STG + wg * 16384 + pn * 8192; });
        if (threadIdx.x == 0) { TL(30 + 2 * p); TC(115 + 2 * p); }
        if (threadIdx.x == 128) TL(54 + 2 * (p & 1));
        CS(25 + 2 * (p & 1));
    }
}

__global__ void __launch_bounds__(384, 1)
fused_block_kernel(const __grid_constant__ Ptrs pt, const __grid_constant__ Maps mp) {
    uint32_t* const g_flags = pt.mail->flags;
    uint2* const g_mod = pt.mail->mod;
    uint4* const g_st1 = pt.mail->st1;
    uint32_t* const g_par2 = pt.mail->par2;
    uint4* const g_halo = pt.mail->halo;
    const __nv_bfloat16* __restrict__ cvec = pt.c;
    if (threadIdx.x == 224) { prefetch_map(&mp.wm8); prefetch_map(&mp.x); }
    extern __shared__ __align__(1024) uint8_t smem[];
    const uint32_t sb = smem_u32(smem);
    const uint32_t tid = threadIdx.x, tw = tid & 127, lane = tid & 31;
    const uint32_t warp = __shfl_sync(0xffffffffu, tid >> 5, 0), wg = warp >> 2;
    uint32_t rank; asm("mov.u32 %0, %%cluster_ctarank;" : "=r"(rank));
    rank = __shfl_sync(0xffffffffu, rank, 0);
    uint32_t ep;
    uint32_t smid; asm volatile("mov.u32 %0, %%smid;" : "=r"(smid));
    const int c = __shfl_sync(0xffffffffu, smid >> 1, 0);
    const int c7 = ((c - 32) * 37) >> 8;
    int grp = c < 32 ? c & 7 : c < 60 ? c - 31 - 7 * c7 : c < 62 ? -1 : 0;
    const int j = c < 32 ? c >> 3 : c < 60 ? 4 + c7 : c < 62 ? (c - 60) * 2 + rank : c - 58;
    const bool aux = grp < 0;
    const int m = grp * 2 + rank;
    uint4* const g_st2 = g_halo + (m > 0 ? (m - 1) * 8 * 512 : 128);

    bool cluster_arrive_early = false;
    if (wg < 2) {
      if (!KDEBUG) cluster_arrive();
      ep = flag_get(g_flags + FL_DONE);
      uint16_t cw[8];
      {
          const __nv_bfloat16* cp = cvec + ((tw >> 5) * 32 + (tw & 3) * 2) * 8 + (lane >> 2);
#pragma unroll
          for (int i = 0; i < 8; ++i) asm volatile("ld.global.nc.u16 %0, [%1];" : "=h"(cw[i]) : "l"(cp + (i >> 1) * 64 + (i & 1) * 8));
      }
      asm volatile("setmaxnreg.inc.sync.aligned.u32 224;");
      if (tid == 0) TL(58);
      if (KDEBUG) cluster_arrive();
      Ring r{0, 0};
      Stg stg{0, 0};
      if (aux) {
        if (wg == 0) {
            const uint4 cv = *(const uint4*)(cvec + tw * 8);
            sts128(sb + OFF_STG + (tw >> 3) * 1024 + (tw & 7) * 16, pack2(silu_(bf_lo(cv.x)), silu_(bf_hi(cv.x))), pack2(silu_(bf_lo(cv.y)), silu_(bf_hi(cv.y))),
                   pack2(silu_(bf_lo(cv.z)), silu_(bf_hi(cv.z))), pack2(silu_(bf_lo(cv.w)), silu_(bf_hi(cv.w))));
            fence_async_smem();
        }
        cluster_wait();
        ep = __shfl_sync(0xffffffffu, ep, 0) / NCTA + 1;
        if (wg == 0) {
            bar_sync(1, 128);
#pragma unroll 1
            for (int p = 0; p < 4; ++p) {
                float acc[128];
#pragma unroll
                for (int i = 0; i < 128; ++i) acc[i] = 0.f;
                uint32_t prev = 0;
#pragma unroll 1
                for (int kc = 0; kc < 16; ++kc) {
                    mbar_wait(BAR_FULL(sb, r.slot), r.par);
                    wg_fence();
#pragma unroll
                    for (int k = 0; k < 4; ++k)
                        wgmma_n256(acc, mk_desc(d16(sb) + kc * 64, OFF_STG + k * 32, 16, 0, 1), mk_desc(d16(sb) + r.slot * (SLOT >> 4), k * 2048, 8192, 1024, 1));
                    wg_commit();
                    wg_wait<1>();
                    if (kc > 0 && tw < 4) mbar_arrive(BAR_EMPTY(sb, prev));
                    prev = r.slot;
                    r.next();
                }
                wg_wait<0>();
                if (tw < 4) mbar_arrive(BAR_EMPTY(sb, prev));
                if (tw < 4) {
#pragma unroll
                    for (int jn = 0; jn < 32; ++jn) sts32(sb + OFF_TAB + (jn * 4 + tw) * 4, pack2(acc[jn * 4], acc[jn * 4 + 1]));
                }
                bar_sync(1, 128);
                const int vec = 2 + p, blk = p * 4 + j;
                const uint32_t val = lds32(sb + OFF_TAB + tw * 4);
                if (vec == 2 || vec == 5) st_pkt(g_mod + (8 + blk) * 128 + tw, val, ep);
                else {
                    const float one = vec == 4 ? 1.f : 0.f;
                    g_par2[((blk & 3) * 16 + (tw >> 3)) * 16 + (tw & 3) * 4 + (vec - 3) * 2 + ((tw >> 2) & 1)] =
                        pack2(0.5f * bf_round(one + bf_lo(val)), 0.5f * bf_round(one + bf_hi(val)));
                }
                bar_sync(1, 128);
                if (tw == 0) {
                    if (vec == 3 || vec == 4) asm volatile("red.release.gpu.global.add.u32 [%0], 1;" :: "l"(&g_flags[FL_LN2]) : "memory");
                    TL(1 + p);
                }
            }
            if (lane < 2) mbar_arrive_cta(BAR_ONE(sb, EV_P0), lane);
        }
        r = Ring{64 % NSLOT, (64 / NSLOT) & 1};
        mbar_wait(BAR_ONE(sb, EV_P0), 0);
        passes128<4>(sb, wg, tw, r, stg);
      } else {
        float xs[64];
        uint32_t xp[32];
        {
            IDX();
            if (q4 < 2) st_pkt16(g_st1 + (m * 8 + j) * 512 + wg * 64 + w4 * 16 + g8 + q4 * 8, 0, 0, 0, 0);
            if (warp == 0) st_pkt16(pt.mail->mod1 + g8 * 512 + (m * 8 + j) * 4 + q4, 0, 0, 0, 0);
            sts128(sb + tid * 16, pack2(silu_(bf_lo(cw[0])), silu_(bf_lo(cw[1]))), pack2(silu_(bf_lo(cw[2])), silu_(bf_lo(cw[3]))),
                   pack2(silu_(bf_lo(cw[4])), silu_(bf_lo(cw[5]))), pack2(silu_(bf_lo(cw[6])), silu_(bf_lo(cw[7]))));
            cluster_wait();
            ep = __shfl_sync(0xffffffffu, ep, 0) / NCTA + 1;
            load_slab(xp, stg.acquire2(sb, wg));
            unpack_slab(xs, xp);
            if (tid == 0) TL(24);
            if (tid == 128) TL(27);
        }
#pragma unroll 1
        for (int blk = 0; ; ++blk) {
        {
            IDX();
            uint4* const st = (blk ? g_st2 : g_st1 + m * 8 * 512) + wg * 64 + w4 * 16 + g8;
            RowAcc ra;
#pragma unroll
            for (int e = 0; e < 64; ++e) ra.add(e, xs[e]);
            ra.publish(st + j * 512, q4, ep);
            uint32_t t_pub = 0; if (PDLY) asm volatile("mov.u32 %0, %%clock;" : "=r"(t_pub));
            if (tid == 0) TL(blk ? 9 : 26);
            if (tid == 128 && blk) TL(34);
            if (blk) CS(11);
            LnPar lp;
            if (blk == 0) {
            uint4* const mod_out = pt.mail->mod1 + g8 * 512 + (m * 8 + j) * 4 + q4;
            if (wg == 0) {
                uint4 af[8];
#pragma unroll
                for (int i = 0; i < 8; ++i) af[i] = lds128(sb + w4 * 512 + i * 64 + q4 * 16);
                float c[4][4] = {};
#pragma unroll
                for (int i = 0; i < 8; ++i) {
                    if (!(i & 1)) mbar_wait(BAR_ONE(sb, EV_WIN + (i >> 1)), 0);
                    if (i == 6 && tid == 0) TL(25);
#pragma unroll
                    for (int h = 0; h < 2; ++h) {
                        uint32_t b0, b1, b2, b3;
                        ldsm4t(sb + 5 * SLOT + i * 4096 + w4 * 1024 + h * 512 + (lane & 15) * 32 + (lane >> 4) * 16, b0, b1, b2, b3);
                        mma16816(c[2 * h], h ? af[i].z : af[i].x, 0u, h ? af[i].w : af[i].y, 0u, b0, b1);
                        mma16816(c[2 * h + 1], h ? af[i].z : af[i].x, 0u, h ? af[i].w : af[i].y, 0u, b2, b3);
                    }
                }
                if (lane < 4) sts128(sb + OFF_TAB + w4 * 64 + lane * 16, __float_as_uint(c[0][0] + c[2][0]), __float_as_uint(c[0][1] + c[2][1]),
                                     __float_as_uint(c[1][0] + c[3][0]), __float_as_uint(c[1][1] + c[3][1]));
                if (lane < 2) mbar_arrive_cta(BAR_ONE(sb, EV_P0), lane);
                bar_sync(1, 128);
                if (w4 == 0) {
                    float a[4] = {0.f, 0.f, 0.f, 0.f};
#pragma unroll
                    for (int i = 0; i < 4; ++i) {
                        const uint4 t = lds128(sb + OFF_TAB + i * 64 + q4 * 16);
                        a[0] += __uint_as_float(t.x); a[1] += __uint_as_float(t.y); a[2] += __uint_as_float(t.z); a[3] += __uint_as_float(t.w);
                    }
                    const float add = m >= 8 ? 1.f : 0.f;
                    st_pkt16(mod_out, pack2(bf_round(a[0]) + add, bf_round(a[1]) + add), pack2(bf_round(a[2]) + add, bf_round(a[3]) + add), ep, 0);
                    if (tid == 0) TL(3);
                }
            } else if (LWAIT >= 0) mbar_wait(BAR_ONE(sb, EV_WIN + LWAIT), 0);
            } else {
                mbar_wait2(BAR_ONE(sb, EV_LN2), BAR_FULL(sb, 0), 0);
            }
            lp.load(sb, q4);
#pragma unroll
            for (int e = 0; e < 32; ++e) xp[e] = pack2(xs[2 * e], xs[2 * e + 1]);
            if (PDLY && blk) { uint32_t t1; do { asm volatile("mov.u32 %0, %%clock;" : "=r"(t1)); } while (t1 - t_pub < PDLY); }
            if (blk) CS(13);
            const LnRow n = merge_stats(st, q4, ep, sb);
            if (tid == 0) TL(blk ? 49 : 48);
            if (tid == 128) TL(blk ? 45 : 28);
            if (blk) CS(18);
            uint32_t xn[32];
            ln_norm(xn, xs, n);
            if (blk == 0) { mbar_wait2(BAR_FULL(sb, 0), BAR_ONE(sb, EV_PAR), 0); lp.load(sb, q4); }
            ln_emit(xn, lp, sb, wg, ix);
            if (tid == 0) { TL(blk ? 36 : 8); TC(blk ? 109 : 103); }
            if (tid == 128) TL(blk ? 43 : 22);
            if (blk) CS(21);
        }
        if (blk == 0) {
        {
            float kv[128], qa[64];
            step32<true, true>(kv, qa, sb, wg, r.slot, 0);
            TS(0, 0);
            Pipe pp(sb, tw, r.slot);
            r.next();
#pragma unroll 1
            for (int it = 1; it < 32 - LAGQ; ++it) {
                pp.acquire<true>(sb, wg ? 0 : AF_REL, r);
                step32<true, false>(kv, qa, sb, wg, r.slot, it < 4 ? it : -1);
                pp.issued(r.slot);
                TS(it, 0);
                r.next();
            }
            auto half = [&](uint32_t slot, bool q) {
                const uint32_t st = d16(sb) + slot * (SLOT >> 4);
#pragma unroll
                for (int k = 0; k < 2; ++k) {
                    const uint64_t da = mk_desc(st + wg * 256, k * 32, 16, 512, 2);
                    if (q) wgmma_n128(qa, da, mk_desc(st, 24576 + k * 2048, 4096, 1024, 1)); else wgmma_n256(kv, da, mk_desc(st, 8192 + k * 2048, 4096, 1024, 1));
                }
            };
            auto part = [&](bool q) {
                wg_fence();
#pragma unroll
                for (int it = 32 - LAGQ; it < 32; ++it) half(it % NSLOT, q);
                wg_commit();
            };
            stg.acquire2(sb, wg); mbar_wait2(BAR_SREADY(sb, 2), BAR_SREADY(sb, 3), 1);
            if (wg == 0) { pp.drain1(); pp.drain0(); }
#pragma unroll 1
            for (int it = 32 - LAGQ; it < 32; ++it) {
                pp.acquire<true>(sb, wg ? 0 : AF_REL, r);
                if (wg) { wg_fence(); half(r.slot, false); wg_commit(); }
                pp.issued(NSLOT);
                TS(it, 0);
                r.next();
            }
            if (wg == 0) { mbar_wait(BAR_ONE(sb, EV_LAG0), 0); part(false); part(true); wg_wait<1>(); }
            else { wg_wait<1>(); if (tw == 0) mbar_arrive(BAR_ONE(sb, EV_LAG0)); wg_wait<0>(); }
            CS(8);
            IDX();
            uint32_t k1[16], k2[16], v1[16], v2[16], qf[32];
#pragma unroll
            for (int i = 0; i < 128; ++i) asm volatile("" : "+f"(kv[i]) :: "memory");
#pragma unroll
            for (int t = 0; t < 16; ++t) k2[t] = pack2(kv[4 * t + 2], kv[4 * t + 3]);
#pragma unroll
            for (int t = 0; t < 16; ++t) k1[t] = pack2(kv[4 * t], kv[4 * t + 1]);
#pragma unroll
            for (int t = 0; t < 16; ++t) v2[t] = pack2(kv[64 + 4 * t + 2], kv[64 + 4 * t + 3]);
            const uint32_t nxt = warp + ((warp & 1) ? 3 : 1);
            if (nxt < 8) {
                const uint32_t dst = sb + OFF_STG + (nxt >> 2) * 16384 + (nxt & 3) * 2048 + lane * 16;
#pragma unroll
                for (int h = 0; h < 4; ++h) stsm4(dst + h * 512, k2[4 * h], k2[4 * h + 1], k2[4 * h + 2], k2[4 * h + 3]);
#pragma unroll
                for (int h = 0; h < 4; ++h) stsm4(dst + 8192 + h * 512, v2[4 * h], v2[4 * h + 1], v2[4 * h + 2], v2[4 * h + 3]);
                bar_arrive(NB_TAIL + nxt, 64);
            } else if (m < 15) {
                uint4* dst = g_halo + (m * 8 + j) * 512 + (w4 >> 1) * 256 + lane;
#pragma unroll
                for (int h = 0; h < 4; ++h) { if (!k2[4 * h]) k2[4 * h] = 0x8000u; if (!v2[4 * h]) v2[4 * h] = 0x8000u; }
#pragma unroll
                for (int h = 0; h < 4; ++h) st_pkt16(dst + h * 32, k2[4 * h], k2[4 * h + 1], k2[4 * h + 2], k2[4 * h + 3]);
#pragma unroll
                for (int h = 0; h < 4; ++h) st_pkt16(dst + 128 + h * 32, v2[4 * h], v2[4 * h + 1], v2[4 * h + 2], v2[4 * h + 3]);
            }
#pragma unroll
            for (int t = 0; t < 16; ++t) { v1[t] = pack2(kv[64 + 4 * t], kv[64 + 4 * t + 1]); if (t < MVE) { v1[t] = movm(v1[t]); v2[t] = movm(v2[t]); } }
            if (tid == 0) TL(33);
            CS(2);
            if (wg) part(true);
            bar_sync(NB_TAIL + warp, 64);
            CS(4);
            if (tid == 0) TL(5);
            uint32_t k0[16], v0[16];
            const uint32_t mine = sb + OFF_STG + wg * 16384 + w4 * 2048;
#pragma unroll
            for (int h = 0; h < 4; ++h) ldsm4(mine + lane * 16 + h * 512, k0[4 * h], k0[4 * h + 1], k0[4 * h + 2], k0[4 * h + 3]);
#pragma unroll
            for (int h = 0; h < 4; ++h) ldsm4t(mine + lane * 16 + 8192 + h * 512, v0[4 * h], v0[4 * h + 1], v0[4 * h + 2], v0[4 * h + 3]);
            wg_wait<0>();
#pragma unroll
            for (int it = 32 - LAGQ; it < 32; ++it) pp.rel(it % NSLOT);
            TS(31, 1);
            if (tid == 0) { TL(4); TC(104); }
            if (tid == 128) TL(50);
            CS(1);
#pragma unroll
            for (int i = 0; i < 64; ++i) asm volatile("" : "+f"(qa[i]) :: "memory");
            const bool lo0 = q4 * 2 > g8, lo1 = q4 * 2 + 1 > g8;
            const bool nopast = m == 0 && (warp & 5) == 0;
            const uint32_t lomask = (lo0 ? 0xFFFFu : 0u) | (lo1 ? 0xFFFF0000u : 0u);
            const uint32_t orow = mine + (lane & 7) * 128 + (((lane >> 3) ^ (lane & 7)) << 4);
            const float sl2 = 0.17677669529663687f * 1.4426950408889634f;
#pragma unroll
            for (int pn = 0; pn < 2; ++pn) {
                float e0[4], e1[4], mx[4], sum[4];
#pragma unroll
                for (int hh = 0; hh < 2; ++hh) {
                    const int h = pn * 2 + hh;
#pragma unroll
                    for (int i = 8 * h; i < 8 * h + 8; ++i) qf[i] = pack2(qa[2 * i], qa[2 * i + 1]);
                    float s[3][4];
#pragma unroll
                    for (int t = 0; t < 3; ++t) {
                        const uint32_t* k = (t == 0 ? k0 : t == 1 ? k1 : k2) + 4 * h;
                        s[t][0] = s[t][1] = s[t][2] = s[t][3] = 0.f;
                        mma16816(s[t], qf[h * 8], qf[h * 8 + 1], qf[h * 8 + 2], qf[h * 8 + 3], k[0], k[1]);
                        mma16816(s[t], qf[h * 8 + 4], qf[h * 8 + 5], qf[h * 8 + 6], qf[h * 8 + 7], k[2], k[3]);
                    }
#pragma unroll
                    for (int hf = 0; hf < 2; ++hf) {
                        const int u = hh * 2 + hf;
                        e0[u] = lo0 ? ((hf == 0 && nopast) ? -INFINITY : s[hf][hf * 2]) : s[hf + 1][hf * 2];
                        e1[u] = lo1 ? ((hf == 0 && nopast) ? -INFINITY : s[hf][hf * 2 + 1]) : s[hf + 1][hf * 2 + 1];
                        mx[u] = fmaxf(e0[u], e1[u]);
                    }
                }
#pragma unroll
                for (int o = 1; o < 4; o <<= 1)
#pragma unroll
                    for (int u = 0; u < 4; ++u) mx[u] = fmaxf(mx[u], __shfl_xor_sync(0xffffffffu, mx[u], o));
#pragma unroll
                for (int u = 0; u < 4; ++u) {
                    const float c = -mx[u] * sl2;
                    e0[u] = ex2(fmaf(e0[u], sl2, c)); e1[u] = ex2(fmaf(e1[u], sl2, c));
                    sum[u] = e0[u] + e1[u];
                }
#pragma unroll
                for (int o = 1; o < 4; o <<= 1)
#pragma unroll
                    for (int u = 0; u < 4; ++u) sum[u] += __shfl_xor_sync(0xffffffffu, sum[u], o);
#pragma unroll
                for (int u = 0; u < 4; ++u) {
                    const int h = pn * 2 + (u >> 1);
                    const float inv = rcp(sum[u]);
                    const uint32_t p = pack2(e0[u] * inv, e1[u] * inv);
                    const uint32_t* va = ((u & 1) ? v1 : v0) + 4 * h;
                    const uint32_t* vb = ((u & 1) ? v2 : v1) + 4 * h;
                    float o[2][4] = {};
#pragma unroll
                    for (int d = 0; d < 2; ++d) mma16816(o[d], va[2 * d], va[2 * d + 1], vb[2 * d], vb[2 * d + 1], p & lomask, p & ~lomask);
                    stsm4t((orow ^ ((u >> 1) << 6)) + pn * 8192 + (u & 1) * 1024, pack2(o[0][0], o[0][1]), pack2(o[0][2], o[0][3]), pack2(o[1][0], o[1][1]), pack2(o[1][2], o[1][3]));
                }
                fence_async_smem();
                __syncwarp();
                if (lane == 0) mbar_arrive(BAR_SFULL(sb, wg * 2 + pn));
                if (pn == 0) {
                    CS(5); block_end(sb, 0);
#pragma unroll
                    for (int t = MVE; t < 16; ++t) { v1[t] = movm(v1[t]); v2[t] = movm(v2[t]); }
                }
            }
            CS(6);
            if (tid == 32) TL(41);
            mbar_wait(BAR_FULL(sb, 32 % NSLOT + wg), (32 / NSLOT) & 1);
            load_slab(xp, sb + (32 % NSLOT + wg) * SLOT);
            bar_sync(1 + wg, 128);
            if (tid == 0) { TL(6); TC(106); }
            if (tid == 128) TL(44);
            CS(7);
        }
        } else {
        {
            float ag[88], au[88];
            mainloop32<true, LAG>(ag, au, sb, wg, tw, r, EV_LAG1, 48, [&] {
                stg.acquire2(sb, wg);
                Ring q = r; if (!wg) q.next();
                mbar_wait(BAR_EMPTY(sb, q.slot), q.par ^ 1);
            });
            if (tid == 0) { TL(10); TC(110); }
            if (tid == 128) TL(51);
            CS(22);
            glu<11>(sb, wg, [&](int i) { return ag[i]; }, [&](int i) { return au[i]; },
                    [&](int pn) { return pn < 2 ? sb + OFF_STG + wg * 16384 + pn * 8192 : sb + (wg ? P3_SLOT1 : P3_SLOT0) * SLOT + 24576; });
            if (tid == 0) { TL(11); TC(111); }
            if (tid == 128) TL(52);
            CS(23);
        }
        passes128<2>(sb, wg, tw, r, stg);
        if (tid == 0) { TL(12); TC(112); }
        }
        {
            float acc[64], gf[32];
            mainloop64(acc, blk == 0, sb, wg, tw, r, [&] {
                mbar_wait(BAR_ONE(sb, EV_GA + blk), 0);
                unpack_slab(xs, xp);
                uint32_t gt[16];
#pragma unroll
                for (int cg = 0; cg < 16; ++cg) gt[cg] = lds32(sb + OFF_TAB + blk * 256 + cg * 16 + (tw & 3) * 4);
#pragma unroll
                for (int i = 0; i < 16; ++i) unpack2(gt[i], gf[2 * i], gf[2 * i + 1]);
            }, [&] { stg.acquire2(sb, wg); });
            if (tid == 0) { TL(blk ? 13 : 7); TC(blk ? 113 : 107); }
            if (tid == 128) TL(blk ? 57 : 42);
            CS(blk ? 30 : 10);
#pragma unroll
            for (int e = 0; e < 64; ++e) xs[e] = fmaf(gf[(e >> 2) * 2 + (e & 1)], acc[e], xs[e]);
        }
        if (blk) break;
        }
        {
            IDX();
#pragma unroll
            for (int p = 0; p < 2; ++p) {
                store_slab(xs, sb + OFF_STG + wg * 16384, 8192, pan_addr, 4 * p, 4 * p + 4);
                stg.publish(sb, wg, lane);
            }
            cluster_arrive();
            if (tid == 0) TL(14);
            CS(31);
        }
      }
    } else {
        if (warp == 8 && !aux && elect_one()) {
#pragma unroll
            for (int i = 0; i < 4; ++i) mbar_init(BAR_SREADY(sb, i), 1);
#pragma unroll
            for (int i = 0; i < 4; ++i) mbar_init(BAR_ONE(sb, EV_WIN + i), 1);
#pragma unroll
            for (int i = 0; i < 4; ++i) {
                mbar_expect_tx(BAR_SREADY(sb, i), 8192);
                tma_load3(sb + OFF_STG + i * 8192, &mp.x, j * 128 + (i & 1) * 64, m * 64 + (i >> 1) * 32, BAR_SREADY(sb, i));
            }
#pragma unroll 1
            for (int i = 0; i < 4; ++i) {
                mbar_expect_tx(BAR_ONE(sb, EV_WIN + i), 8192);
                tma_load(sb + 5 * SLOT + i * 8192, &mp.wm8, 2 * i * 6144 + (m * 8 + j) * 16, 0, BAR_ONE(sb, EV_WIN + i));
                tma_load(sb + 5 * SLOT + i * 8192 + 4096, &mp.wm8, (2 * i + 1) * 6144 + (m * 8 + j) * 16, 0, BAR_ONE(sb, EV_WIN + i));
            }
        }
        __syncwarp();
        asm volatile("setmaxnreg.dec.sync.aligned.u32 56;");
        if (elect_one()) {
            if (warp == 8) {
                prefetch_map(&mp.wqkv); prefetch_map(&mp.wmod);
            } else if (warp < 11) {
                mbar_init(BAR_EMPTY(sb, NSLOT), 1);
#pragma unroll
                for (int i = 0; i < 2; ++i) { mbar_init(BAR_SFULL(sb, (warp - 9) * 2 + i), 4); if (aux) mbar_init(BAR_SREADY(sb, (warp - 9) * 2 + i), 1); }
#pragma unroll
                for (int i = 0; i < 3; ++i) {
                    mbar_init(BAR_EMPTY(sb, (warp - 9) * 3 + i), 4);
                    mbar_init(BAR_FULL(sb, (warp - 9) * 3 + i), 1); mbar_init(BAR_FULL(sb, (warp - 9) * 3 + i) + AF_REL, 1);
                }
            } else {
#pragma unroll
                for (int i = EV_P0; i < EV_COUNT; ++i) mbar_init(BAR_ONE(sb, i), i == EV_P0 ? 8 : 1);
            }
            asm volatile("fence.mbarrier_init.release.cluster;" ::: "memory");
        }
        __syncwarp();
        cluster_arrive();
        ep = 0;
        if (warp != 8 || aux) ep = flag_get(g_flags + FL_DONE);
        cluster_wait();
        ep = __shfl_sync(0xffffffffu, ep, 0) / NCTA + 1;
        if (warp == 8) {
            const bool el = elect_one();
            Ring r{0, 1};
            if (aux) {
                {
                    uint32_t n = 0;
                    while (!__all_sync(0xffffffffu, ld_pkt16(pt.mail->mod1 + 256).z == ep)) { SPIN_GUARD(n); __nanosleep(200); }
                }
#pragma unroll 1
                for (int it = 0; it < 64; ++it) {
                    const int col = 2048 + (it >> 4) * 1024 + j * 256;
                    mbar_wait(BAR_EMPTY(sb, r.slot), r.par);
                    const uint32_t st = sb + r.slot * SLOT, fb = BAR_FULL(sb, r.slot);
                    if (el) {
                        mbar_expect_tx(fb, 32768);
#pragma unroll
                        for (int b = 0; b < 4; ++b) tma_load(st + b * 8192, &mp.wmod, col + b * 64, (it & 15) * 64, fb);
                    }
                    r.next();
                }
                mbar_wait(BAR_ONE(sb, EV_P0), 0);
                const CUtensorMap* wm = rank ? &mp.wu : &mp.wg;
#pragma unroll 1
                for (int g = 0; g < 128; ++g) {
                    const int mx = (j >> 1) * 8 + (g >> 5) * 2 + rank, k0 = ((g & 14) << 6) + ((g & 16) << 2) + ((g & 1) << 5);
                    if (!(g & 15)) {
                        uint32_t n = 0;
                        while (!__all_sync(0xffffffffu, (int32_t)(flag_get(g_flags + FL_PROG + fidx(mx, lane >> 4, (lane & 14) | ((g >> 4) & 1))) - (ep * 8 + ST_H2)) >= 0)) { SPIN_GUARD(n); __nanosleep(300); }
                    }
                    mbar_wait(BAR_EMPTY(sb, r.slot), r.par);
                    const uint32_t st = sb + r.slot * SLOT, fb = BAR_FULL(sb, r.slot);
                    if (el) {
                        mbar_expect_tx(fb, 24576);
                        tma_load_mc(st + 8192 + rank * 4096, wm, HC3, k0, fb);
                        tma_load_mc(st + 16384 + rank * 4096, wm, HC3 + 64, k0, fb);
                        tma_load(st, &mp.h2l, k0, mx * 128, fb);
                    }
                    r.next();
                }
            } else {
#pragma unroll 1
                for (int it = 0; it < 32; ++it) {
                    const int cb = j * 128 + rank * 64, k0 = kof(it, 2, j);
                    if (it == BW0) mbar_wait(BAR_ONE(sb, BWEV), 0);
                    if (it == BW1) mbar_wait(BAR_ONE(sb, EV_PAR), 0);
                    if (it == 5) mbar_wait(BAR_ONE(sb, EV_P0), 0);
                    if (it == AG0) mbar_wait(BAR_ONE(sb, (AGW & 1) ? EV_AGO : EV_FGO), 0);
                    mbar_wait(BAR_EMPTY(sb, r.slot), r.par);
                    const uint32_t st = sb + r.slot * SLOT, fb = BAR_FULL(sb, r.slot);
                    if (el) {
                        mbar_expect_tx(fb, it < 4 ? 24576 : 28672);
                        tma_load_mc(st + 8192 + rank * 4096, &mp.wqkv, 1024 + cb, k0, fb);
                        tma_load_mc(st + 16384 + rank * 4096, &mp.wqkv, 2048 + cb, k0, fb);
                        tma_load_mc(st + 24576 + rank * 4096, &mp.wqkv, cb, k0, fb);
                        if (it < 4) mbar_arrive(fb + AF_REL);
                        if (it == PFWO + (m >> 1)) { tma_prefetch(&mp.wo, j * 128, m * 64); tma_prefetch(&mp.wo, j * 128 + 64, m * 64); }
                        if (it >= PFG && it < PFG + PFN && (it & 7) == grp) {
                            const int kp = kof(it - PFG + PFO, 2, j);
                            tma_prefetch(rank ? &mp.wu : &mp.wg, hcol(0, j), kp); tma_prefetch(rank ? &mp.wu : &mp.wg, hcol(0, j) + 64, kp);
                            asm volatile("cp.async.bulk.prefetch.tensor.3d.L2.global [%0, {%1, %2, %3}];" :: "l"(rank ? &mp.wu3 : &mp.wg3), "r"(0), "r"(j), "r"(kp) : "memory");
                        }
                    }
                    r.next();
                }
                if (el) mbar_arrive(BAR_ONE(sb, EV_KV));
#pragma unroll 1
                for (int it = 0; it < 16; ++it) {
                    const int k0 = kof(it, 1, j);
                    if (it == AG1) mbar_wait(BAR_ONE(sb, (AGW & 2) ? EV_AGO1 : EV_FGO1), 0);
                    mbar_wait(BAR_EMPTY(sb, r.slot), r.par);
                    const uint32_t st = sb + r.slot * SLOT, fb = BAR_FULL(sb, r.slot);
                    if (el) {
                        mbar_expect_tx(fb, it < 2 ? 32768 : 24576);
                        tma_load_mc(st + 16384 + rank * 8192, &mp.wo, j * 128 + rank * 64, k0, fb);
                        if (it < 2) {
                            tma_load3(st, &mp.x, j * 128, m * 64 + it * 32, fb); tma_load3(st + 8192, &mp.x, j * 128 + 64, m * 64 + it * 32, fb);
                            mbar_arrive(fb + AF_REL);
                        }
                        if (it == 6) { prefetch_map(rank ? &mp.wu : &mp.wg); prefetch_map(rank ? &mp.wu3 : &mp.wg3); }
                    }
                    r.next();
                }
                const CUtensorMap* wm = rank ? &mp.wu : &mp.wg;
#pragma unroll 1
                for (int g = 0; g < 96; ++g) {
                    if (g == AG2) mbar_wait(BAR_ONE(sb, (AGW & 4) ? EV_AGO2 : EV_FGO2), 0);
                    const int p = g >> 5, cb = hcol(p, j), k0 = p == 0 ? kof(g, 2, j) : (g & 31) * 32;
                    mbar_wait(BAR_EMPTY(sb, r.slot), r.par);
                    const uint32_t st = sb + r.slot * SLOT, fb = BAR_FULL(sb, r.slot);
                    if (el) {
                        mbar_expect_tx(fb, (g < 4 || p > 0) ? 24576 : 28672);
                        tma_load_mc(st + 8192 + rank * 4096, wm, cb, k0, fb);
                        tma_load_mc(st + 16384 + rank * 4096, wm, cb + 64, k0, fb);
                        if (p == 0) tma_load3_mc(st + 24576 + rank * 4096, rank ? &mp.wu3 : &mp.wg3, j, k0, fb);
                        else tma_load(st, &mp.h2l, k0, m * 128, fb);
                        if (g < 4) mbar_arrive(fb + AF_REL);
                        if (g == 60) prefetch_map(&mp.wd);
                    }
                    r.next();
                }
#pragma unroll 1
                for (int g = 0; g < 56; ++g) {
                    if (g == 0 || (g & 15) == 6 && g > 6) mbar_wait(BAR_ONE(sb, EV_H0 + (g >> 4)), 0);
                    const int k0 = g * 64;
                    mbar_wait(BAR_EMPTY(sb, r.slot), r.par);
                    const uint32_t st = sb + r.slot * SLOT, fb = BAR_FULL(sb, r.slot);
                    if (el) {
                        mbar_expect_tx(fb, 32768);
                        tma_load_mc(st + 16384 + rank * 8192, &mp.wd, j * 128 + rank * 64, k0, fb);
                        tma_load(st, &mp.hb, k0, m * 128, fb); tma_load(st + 8192, &mp.hb, k0, m * 128 + 64, fb);
                    }
                    r.next();
                }
            }
        } else if (aux) {
            if (warp < 11) {
                const uint32_t w = warp - 9;
                const bool el = elect_one();
#pragma unroll 1
                for (int p = 0; p < 4; ++p) {
                    const int mx = (j >> 1) * 8 + p * 2 + rank;
                    if (el) { mbar_arrive(BAR_SREADY(sb, w * 2)); mbar_arrive(BAR_SREADY(sb, w * 2 + 1)); }
                    mbar_wait2(BAR_SFULL(sb, w * 2), BAR_SFULL(sb, w * 2 + 1), p & 1);
                    if (p < 3) pause(HD0);
                    if (el) tma_store(&mp.hb, HC3, mx * 128 + w * 64, sb + OFF_STG + w * 16384);
                    if (p < 3) pause(HP);
                    if (el) {
                        tma_store(&mp.hb, HC3 + 64, mx * 128 + w * 64, sb + OFF_STG + w * 16384 + 8192);
                        bulk_commit(); bulk_wait_fence(); flag_set(g_flags + FL_AUX + mx * 2 + w, ep * 8 + ST_H + 3);
                    }
                }
            }
        } else if (warp == 11) {
            const bool el = elect_one();
            const int row0 = m * 128;
            const uint32_t* const fl = g_flags + FL_PROG + fidx(m, lane >> 4, kof(lane & 15, 1, j) >> 6);
            if (el) { prefetch_map(&mp.h1h); prefetch_map(&mp.h2h); prefetch_map(&mp.h2l); }
            auto gate = [&](int vec, int ev) {
                uint4 v; uint32_t n = 0;
                while (true) {
                    v = ld_pkt2(g_mod + vec * 512 + j * 64 + lane * 2);
                    if (__all_sync(0xffffffffu, v.y == ep && v.w == ep)) break;
                    SPIN_GUARD(n); __nanosleep(300);
                }
                asm volatile("st.shared.v2.u32 [%0], {%1, %2};" :: "r"(sb + OFF_TAB + (ev - EV_GA) * 256 + lane * 8), "r"(v.x), "r"(v.z) : "memory");
                __syncwarp();
                if (lane == 0) mbar_arrive(BAR_ONE(sb, ev));
            };
            {
                const uint4* pk = pt.mail->mod1 + grp * 512 + j * 32 + lane;
                uint4 a, b; uint32_t n = 0;
                mbar_wait(BAR_ONE(sb, EV_WIN3), 0);
                while (true) {
                    a = ld_pkt16(pk); b = ld_pkt16(pk + 256);
                    if (__all_sync(0xffffffffu, a.z == ep && b.z == ep)) break;
                    SPIN_GUARD(n);
                }
                sts128(sb + OFF_PAR + lane * 16, a.x, a.y, b.x, b.y);
                __syncwarp();
                if (lane == 0) { mbar_arrive(BAR_ONE(sb, EV_PAR)); TL(46); }
            }
            mbar_wait(BAR_ONE(sb, EV_P0), 0);
            Ring r{0, 1};
#pragma unroll 1
            for (int ph = 0; ph < 3; ++ph) {
                const int sh = ph == 1 ? 1 : 2, nst = 8 << sh;
                const uint32_t half = 16384 >> sh, target = ep * 8 + ST_H1 + ph;
                const CUtensorMap* tm = ph == 0 ? &mp.h1h : ph == 1 ? &mp.o : &mp.h2h;
                if (ph == 1) gate(2, EV_GA);
                if (ph == 2) {
                    uint32_t n = 0;
                    while ((int32_t)(flag_get(g_flags + FL_LN2) - ep * 8) < 0) { SPIN_GUARD(n); __nanosleep(200); }
                    const uint4 v = __ldcg((const uint4*)(g_par2 + j * 128) + lane);
                    sts128(sb + OFF_PAR + lane * 16, v.x, v.y, v.z, v.w);
                    __syncwarp();
                    if (lane == 0) mbar_arrive(BAR_ONE(sb, EV_LN2));
                }
                const uint32_t lw = ~lane & 1, lt = lane >> 1, ls = (r.slot + lt) % NSLOT, lk = kof(lt, sh, j), lb = BAR_FULL(sb, ls) + (lw ? 0 : AF_REL);
                const uint32_t* const lf = g_flags + FL_PROG + fidx(m, lw, lk >> 6);
                int fr = 1 << sh;
                uint32_t todo = 0x3ffffu >> (2 * fr) << (2 * fr), have = ~todo, n = 0, v = 0;
                r.skip(fr);
#pragma unroll 1
                for (; fr < NSLOT; ++fr) { mbar_wait(BAR_EMPTY(sb, r.slot), r.par); r.next(); }
                if (ph == XST - 1) CS(33);
                do {
                    if (!((have >> lane) & 1)) v = flag_get(lf);
                    while (fr < 9 && mbar_test(BAR_EMPTY(sb, r.slot), r.par)) { ++fr; r.next(); }
                    SPIN_GUARD(n);
                    have |= __ballot_sync(0xffffffffu, (int32_t)(v - target) >= 0);
                    const uint32_t go = have & todo & ((1u << (2 * fr)) - 1);
                    if ((go >> lane) & 1) {
                        if (!lw) mbar_expect_tx(lb, half);
                        tma_load(sb + ls * SLOT + lw * half, tm, lk, row0 + lw * 64, lb);
                    }
                    __syncwarp();
                    if (lane < 2 && (todo & (0x555u << lane)) && !(todo & ~go & (0x555u << lane))) mbar_arrive(BAR_ONE(sb, (lane ? EV_FGO : EV_AGO) + ph));
                    if (ph == XST - 1) { if (go & (1u << (2 << sh))) CS(34); if (go & (2u << (2 << sh))) CS(35); if (todo & 0x555u) CS(36); if (todo & 0xaaau) CS(37); }
                    todo &= ~go;
                } while (~have);
                if (ph == XST - 1) CS(38);
                int k = kof(fr, sh, j);
#pragma unroll 1
                for (; fr < nst; ++fr) {
                    if (fr == 9 || fr == 18) {
                        const uint32_t skip = fr == 9 << (sh - 1) ? 0 : ~0x01fc01fcu;
                        while (~(__ballot_sync(0xffffffffu, (int32_t)(flag_get(fl) - target) >= 0) | skip)) SPIN_GUARD(n);
                    }
                    const uint32_t st = sb + r.slot * SLOT, fb = BAR_FULL(sb, r.slot);
                    mbar_wait(BAR_EMPTY(sb, r.slot), r.par);
                    if (el) {
                        tma_load(st + half, tm, k, row0 + 64, fb);
                        mbar_expect_tx(fb + AF_REL, half);
                        tma_load(st, tm, k, row0, fb + AF_REL);
                    }
                    if (ph == XST - 1 && fr == 9) CS(39);
                    r.next();
                    k = kof(fr + 1, sh, j);
                }
            }
#pragma unroll 1
            for (int p = 0; p < 4; ++p) {
                const uint32_t* f = p < 3 ? fl : g_flags + FL_AUX + m * 2 + (lane & 1);
                uint32_t n = 0;
                while (!__all_sync(0xffffffffu, (int32_t)(flag_get(f) - (ep * 8 + ST_H + p)) >= 0)) { SPIN_GUARD(n); __nanosleep(300); }
                if (el) mbar_arrive(BAR_ONE(sb, EV_H0 + p));
                if (p == 0) gate(5, EV_GB);
            }
        } else {
            const uint32_t w = warp - 9;
            const int row0 = m * 128 + w * 64;
            const uint32_t stg = sb + OFF_STG + w * 16384;
            uint32_t* const fl = g_flags + FL_PROG + fidx(m, w, 2 * j);
            uint32_t b = 0, par = 0;
            const bool el = elect_one();
            auto store = [&](const CUtensorMap* tm, int col, bool nat = false) {
                mbar_wait(BAR_SFULL(sb, w * 2 + b), (par >> b) & 1);
                par ^= 1u << b;
                if (el) {
                    if (nat) tma_store3(tm, col, row0 >> 1, 0, stg + b * 8192); else tma_store(tm, col, row0, stg + b * 8192);
                    bulk_commit();
                }
                b ^= 1;
            };
            auto send2 = [&](const CUtensorMap* tm, const uint32_t* buf, int step) {
                const uint32_t* const q = buf + (size_t)((row0 + lane) * (D_ / 2) + j * 64 + 31);
                store(tm, j * 128);
                if (step == XST) CS(33);
                uint32_t z = landed(el, q, D_ / 2, pt.zero);
                if (el) flag_set(fl, ep * 8 + step + z);
                if (step == XST) CS(34);
                if (step != ST_O) { mbar_wait(BAR_ONE(sb, EV_FGO + step - ST_H1), 0); pause(step == ST_H1 ? (w ? P1H : P1H + 1000) : w ? P2L : P2F); }
                store(tm, j * 128 + 64);
                if (step == XST) CS(35);
                z = landed(el, q + 32, D_ / 2, pt.zero);
                if (el) flag_set(fl + 1, ep * 8 + step + z);
                if (step == XST) CS(36);
            };
            auto free2 = [&]() { if (el) { mbar_arrive(BAR_SREADY(sb, w * 2)); mbar_arrive(BAR_SREADY(sb, w * 2 + 1)); } };
            if (el) { prefetch_map(&mp.h1s); prefetch_map(&mp.o); prefetch_map(&mp.h2s); prefetch_map(&mp.hb); prefetch_map(&mp.out); prefetch_map(&mp.wo); }
            if (el) { flag_set(fl, ep * 8); flag_set(fl + 1, ep * 8); }
            send2(&mp.h1s, pt.h1, ST_H1);
            if (w == 0) TL(47);
            free2();
            fetch_halo(g_halo + ((m - 1) * 8 + j) * 512 + w * 256 + lane, m == 0, sb, 2 * w, lane);
            send2(&mp.o, pt.o, ST_O);
            if (w == 0) TL(40); else TL(38);
            free2();
            send2(&mp.h2s, pt.o, ST_H2);
            if (el) { prefetch_map(&mp.hb); prefetch_map(&mp.hb3); }
            if (w == 0) TL(37);
            free2();
#pragma unroll 1
            for (int p = 0; p < 3; ++p) {
                const int col = hcol(p, j);
                mbar_wait(BAR_SFULL(sb, w * 2), par & 1);
                pause(w ? HD1 : HD0); store(&mp.hb, col);
                pause(HP); store(&mp.hb, col + 64);
                if (p == 0) {
                    pause(HP);
                    if (el) { tma_store3(&mp.hb3, 0, j, row0, sb + (w ? P3_SLOT1 : P3_SLOT0) * SLOT + 24576); bulk_commit(); }
                }
                if (el) bulk_wait_read();
                free2();
                if (el) { bulk_wait_fence(); flag_set(fl, ep * 8 + ST_H + p); flag_set(fl + 1, ep * 8 + ST_H + p); }
            }
            cluster_arrive_early = true;
            cluster_arrive();
            store(&mp.out, j * 128, true); store(&mp.out, j * 128 + 64, true);
            if (el) bulk_wait_read();
        }
        __syncwarp();
    }
    if (aux || (wg == 2 && !cluster_arrive_early)) cluster_arrive();
    cluster_wait();
    CS(32);
    if (KDEBUG == 5) __syncthreads();
    if (tid == 0) {
        TL(15);
        flag_add(pt.mail->flags + FL_DONE);
    }
}

typedef CUresult (*EncodeFn)(CUtensorMap*, CUtensorMapDataType, cuuint32_t, void*, const cuuint64_t*, const cuuint64_t*, const cuuint32_t*,
                             const cuuint32_t*, CUtensorMapInterleave, CUtensorMapSwizzle, CUtensorMapL2promotion, CUtensorMapFloatOOBfill);

void make_map(EncodeFn fn, CUtensorMap* m, const void* ptr, uint64_t rows, uint64_t cols, uint32_t brows, uint32_t bcols) {
    cuuint64_t dims[2] = {cols, rows}, strides[1] = {cols * 2};
    cuuint32_t box[2] = {bcols, brows}, es[2] = {1, 1};
    fn(m, CU_TENSOR_MAP_DATA_TYPE_BFLOAT16, 2, (void*)ptr, dims, strides, box, es, CU_TENSOR_MAP_INTERLEAVE_NONE,
       bcols == 64 ? CU_TENSOR_MAP_SWIZZLE_128B : bcols == 32 ? CU_TENSOR_MAP_SWIZZLE_64B : CU_TENSOR_MAP_SWIZZLE_NONE, CU_TENSOR_MAP_L2_PROMOTION_L2_256B, CU_TENSOR_MAP_FLOAT_OOB_FILL_NONE);
}

void make_map3(EncodeFn fn, CUtensorMap* m, const void* ptr) {
    cuuint64_t dims[3] = {D_, S_ / 2, 2}, strides[2] = {4 * D_, 2 * D_};
    cuuint32_t box[3] = {64, 32, 2}, es[3] = {1, 1, 1};
    fn(m, CU_TENSOR_MAP_DATA_TYPE_BFLOAT16, 3, (void*)ptr, dims, strides, box, es, CU_TENSOR_MAP_INTERLEAVE_NONE,
       CU_TENSOR_MAP_SWIZZLE_128B, CU_TENSOR_MAP_L2_PROMOTION_L2_256B, CU_TENSOR_MAP_FLOAT_OOB_FILL_NONE);
}

void make_map48(EncodeFn fn, CUtensorMap* m, const void* ptr, uint64_t rows, uint32_t brows) {
    cuuint64_t dims[3] = {48, 8, rows}, strides[2] = {96, 2 * F_};
    cuuint32_t box[3] = {64, 1, brows}, es[3] = {1, 1, 1};
    fn(m, CU_TENSOR_MAP_DATA_TYPE_BFLOAT16, 3, (void*)ptr, dims, strides, box, es, CU_TENSOR_MAP_INTERLEAVE_NONE,
       CU_TENSOR_MAP_SWIZZLE_128B, CU_TENSOR_MAP_L2_PROMOTION_L2_256B, CU_TENSOR_MAP_FLOAT_OOB_FILL_NONE);
}

}

extern "C" void kernel_launch(void* const* d_in, const int* in_sizes, int n_in, void* d_out, int out_size) {
    (void)in_sizes; (void)n_in; (void)out_size;
    void* fnp = nullptr;
    cudaDriverEntryPointQueryResult qr;
    cudaGetDriverEntryPoint("cuTensorMapEncodeTiled", &fnp, cudaEnableDefault, &qr);
    EncodeFn fn = (EncodeFn)fnp;
    void *h1, *o, *h2, *hb, *mail;
    cudaGetSymbolAddress(&h1, g_h1);
    cudaGetSymbolAddress(&mail, g_mail);
    cudaGetSymbolAddress(&o, g_o);
    cudaGetSymbolAddress(&hb, g_hb);
    h2 = o;
    Maps mp;
    make_map(fn, &mp.h1h, h1, S_, D_, 64, 32);
    make_map(fn, &mp.h2h, h2, S_, D_, 64, 32);
    make_map(fn, &mp.h1s, h1, S_, D_, 64, 64);
    make_map(fn, &mp.o, o, S_, D_, 64, 64);
    make_map(fn, &mp.h2l, h2, S_, D_, 128, 32);
    make_map(fn, &mp.h2s, h2, S_, D_, 64, 64);
    make_map(fn, &mp.hb, hb, S_, F_, 64, 64);
    make_map(fn, &mp.wqkv, d_in[1], D_, 3 * D_, 32, 64);
    make_map(fn, &mp.wo, d_in[2], D_, D_, 64, 64);
    make_map(fn, &mp.wg, d_in[4], D_, F_, 32, 64);
    make_map(fn, &mp.wu, d_in[5], D_, F_, 32, 64);
    make_map(fn, &mp.wd, d_in[6], F_, D_, 64, 64);
    make_map(fn, &mp.wmod, d_in[8], D_, 6 * D_, 64, 64);
    make_map(fn, &mp.wm8, d_in[8], D_ / 8, 8 * 6 * D_, 128, 16);
    make_map3(fn, &mp.x, d_in[0]);
    make_map3(fn, &mp.out, d_out);
    make_map48(fn, &mp.wg3, d_in[4], D_, 32);
    make_map48(fn, &mp.wu3, d_in[5], D_, 32);
    make_map48(fn, &mp.hb3, hb, S_, 64);
    cudaFuncSetAttribute(fused_block_kernel, cudaFuncAttributeMaxDynamicSharedMemorySize, SMEM_BYTES);
    cudaLaunchConfig_t cfg = {};
    cfg.gridDim = dim3(NCTA); cfg.blockDim = dim3(384); cfg.dynamicSmemBytes = SMEM_BYTES; cfg.stream = cudaStreamPerThread;
    cudaLaunchAttribute at[1];
    at[0].id = cudaLaunchAttributeClusterDimension; at[0].val.clusterDim.x = 2; at[0].val.clusterDim.y = 1; at[0].val.clusterDim.z = 1;
    cfg.attrs = at; cfg.numAttrs = 1;
    const Ptrs pt{(const __nv_bfloat16*)d_in[7], (Mail*)mail, (const uint32_t*)h1, (const uint32_t*)o, 0};
    cudaLaunchKernelEx(&cfg, fused_block_kernel, pt, mp);
}
```

```cpp
#include <cuda_runtime.h>
#include <cuda_bf16.h>
#include <cuda.h>
#include <stdint.h>
#include <stddef.h>

#define LAG 4
#define LAGS 4
#define LAGW 3
#define LAGQ 4
#define PFWO 12
#define P1H 3000
#define AGW 6
#define CSW 0
#define LWAIT 2
#define BW0 0
#define BWEV EV_WIN
#define BW1 3
#define PDLY 500
#define HD1 5500
#define HD0 5500
#define HP 2200
#define LAGD 4
#define MIDD 5
#define XST ST_O
#define AG0 6
#define AG1 6
#define AG2 8
#define PFG 8
#define PFN 24
#define PFO 0
#define P2L 2000
#define P2F 3000
#define KDEBUG 0

namespace {

constexpr int S_ = 2048, D_ = 1024, F_ = 3584;
constexpr int NCTA = 132;
constexpr int NSLOT = 6;
constexpr uint32_t SLOT = 32768;
constexpr uint32_t OFF_STG = NSLOT * SLOT;
constexpr uint32_t OFF_BAR = OFF_STG + 32768;
constexpr uint32_t OFF_PAR = OFF_BAR + 512;
constexpr uint32_t OFF_TAB = OFF_PAR + 768;
constexpr uint32_t OFF_TL = OFF_PAR + 2048;
constexpr uint32_t SMEM_BYTES = OFF_TL + (KDEBUG ? 512 : 0);
constexpr uint32_t P3_SLOT1 = (32 + 16 + 32) % NSLOT, P3_SLOT0 = (P3_SLOT1 + 1) % NSLOT;

constexpr int ST_H1 = 1, ST_O = 2, ST_H2 = 3, ST_H = 4, FL_DONE = 0, FL_LN2 = 1, FL_AUX = 32, FL_PROG = 64;

struct Maps {
    CUtensorMap h1h, h1s, o, h2h, h2l, h2s, hb, wqkv, wo, wg, wu, wd, wmod, wm8, x, out, wg3, wu3, hb3;
};

struct Mail {
    uint32_t flags[16 * 32 + 64];
    uint2 mod[6 * D_ / 2];
    uint4 mod1[8 * 512];
    uint4 st1[128 * 512];
    uint32_t par2[D_];
    uint4 halo[128 * 512];
};
struct Ptrs { const __nv_bfloat16* c; Mail* mail; const uint32_t *h1, *o; uint32_t zero; };

__device__ __align__(128) Mail g_mail;
__device__ __align__(128) __nv_bfloat16 g_h1[S_ * D_];
__device__ __align__(128) __nv_bfloat16 g_o[S_ * D_];
__device__ __align__(128) __nv_bfloat16 g_hb[S_ * F_];
#define TL(i) do {} while (0)
#define TC(i) do {} while (0)
#define TS(g, which) do {} while (0)
#define CS(i) do {} while (0)

__device__ __forceinline__ uint32_t smem_u32(const void* p) { return (uint32_t)__cvta_generic_to_shared(p); }
__device__ __forceinline__ void mbar_init(uint32_t bar, uint32_t cnt) { asm volatile("mbarrier.init.shared::cta.b64 [%0], %1;" :: "r"(bar), "r"(cnt) : "memory"); }
__device__ __forceinline__ void mbar_expect_tx(uint32_t bar, uint32_t bytes) { asm volatile("mbarrier.arrive.expect_tx.shared::cta.b64 _, [%0], %1;" :: "r"(bar), "r"(bytes) : "memory"); }
__device__ __forceinline__ void mbar_arrive(uint32_t bar) { asm volatile("mbarrier.arrive.shared::cta.b64 _, [%0];" :: "r"(bar) : "memory"); }
__device__ __forceinline__ void mbar_arrive_cta(uint32_t bar, uint32_t cta) {
    asm volatile("{\n.reg .b32 r;\nmapa.shared::cluster.u32 r, %0, %1;\nmbarrier.arrive.shared::cluster.b64 _, [r];\n}" :: "r"(bar), "r"(cta) : "memory");
}
__device__ __forceinline__ void mbar_wait(uint32_t bar, uint32_t parity) {
    asm volatile("{\n.reg .pred p;\n.reg .u32 n;\nmov.u32 n, 0;\n"
        "W_LOOP:\nmbarrier.try_wait.parity.shared::cta.b64 p, [%0], %1;\n@p bra W_DONE;\n"
        "add.u32 n, n, 1;\nsetp.lt.u32 p, n, 0x400000;\n@p bra W_LOOP;\ntrap;\nW_DONE:\n}" :: "r"(bar), "r"(parity) : "memory");
}
__device__ __forceinline__ void mbar_wait2(uint32_t b0, uint32_t b1, uint32_t parity) {
    asm volatile("{\n.reg .pred p, q;\n.reg .u32 n;\nmov.u32 n, 0;\n"
        "W_LOOP:\nmbarrier.try_wait.parity.shared::cta.b64 p, [%0], %2;\nmbarrier.try_wait.parity.shared::cta.b64 q, [%1], %2;\nand.pred p, p, q;\n@p bra W_DONE;\n"
        "add.u32 n, n, 1;\nsetp.lt.u32 p, n, 0x400000;\n@p bra W_LOOP;\ntrap;\nW_DONE:\n}" :: "r"(b0), "r"(b1), "r"(parity) : "memory");
}
__device__ __forceinline__ bool mbar_test(uint32_t bar, uint32_t parity) {
    uint32_t r; asm volatile("{\n.reg .pred p;\nmbarrier.test_wait.parity.shared::cta.b64 p, [%1], %2;\nselp.u32 %0, 1, 0, p;\n}" : "=r"(r) : "r"(bar), "r"(parity) : "memory"); return r;
}
__device__ __forceinline__ bool mbar_test2(uint32_t b0, uint32_t b1, uint32_t parity) {
    uint32_t r;
    asm volatile("{\n.reg .pred p, q;\nmbarrier.test_wait.parity.shared::cta.b64 p, [%1], %3;\nmbarrier.test_wait.parity.shared::cta.b64 q, [%2], %3;\n"
        "and.pred p, p, q;\nselp.u32 %0, 1, 0, p;\n}" : "=r"(r) : "r"(b0), "r"(b1), "r"(parity) : "memory");
    return r;
}
__device__ __forceinline__ void tma_load3(uint32_t dst, const CUtensorMap* m, int c0, int c1, uint32_t bar) {
    asm volatile("cp.async.bulk.tensor.3d.shared::cluster.global.mbarrier::complete_tx::bytes [%0], [%1, {%3, %4, %5}], [%2];"
        :: "r"(dst), "l"(m), "r"(bar), "r"(c0), "r"(c1), "r"(0) : "memory");
}
__device__ __forceinline__ void tma_store3(const CUtensorMap* m, int c0, int c1, int c2, uint32_t src) {
    asm volatile("cp.async.bulk.tensor.3d.global.shared::cta.bulk_group [%0, {%2, %3, %4}], [%1];" :: "l"(m), "r"(src), "r"(c0), "r"(c1), "r"(c2) : "memory");
}
__device__ __forceinline__ void tma_load3_mc(uint32_t dst, const CUtensorMap* m, int c1, int c2, uint32_t bar) {
    asm volatile("cp.async.bulk.tensor.3d.shared::cluster.global.mbarrier::complete_tx::bytes.multicast::cluster.L2::cache_hint [%0], [%1, {%3, %4, %5}], [%2], %6, %7;"
        :: "r"(dst), "l"(m), "r"(bar), "r"(0), "r"(c1), "r"(c2), "h"((uint16_t)3), "l"(0x12F0000000000000ull) : "memory");
}
__device__ __forceinline__ void tma_load(uint32_t dst, const CUtensorMap* m, int c0, int c1, uint32_t bar) {
    asm volatile("cp.async.bulk.tensor.2d.shared::cluster.global.mbarrier::complete_tx::bytes [%0], [%1, {%3, %4}], [%2];"
        :: "r"(dst), "l"(m), "r"(bar), "r"(c0), "r"(c1) : "memory");
}
__device__ __forceinline__ void tma_load_mc(uint32_t dst, const CUtensorMap* m, int c0, int c1, uint32_t bar) {
    asm volatile("cp.async.bulk.tensor.2d.shared::cluster.global.mbarrier::complete_tx::bytes.multicast::cluster.L2::cache_hint [%0], [%1, {%3, %4}], [%2], %5, %6;"
        :: "r"(dst), "l"(m), "r"(bar), "r"(c0), "r"(c1), "h"((uint16_t)3), "l"(0x12F0000000000000ull) : "memory");
}
__device__ __forceinline__ void tma_prefetch(const CUtensorMap* m, int c0, int c1) {
    asm volatile("cp.async.bulk.prefetch.tensor.2d.L2.global [%0, {%1, %2}];" :: "l"(m), "r"(c0), "r"(c1) : "memory");
}
__device__ __forceinline__ void tma_store(const CUtensorMap* m, int c0, int c1, uint32_t src) {
    asm volatile("cp.async.bulk.tensor.2d.global.shared::cta.bulk_group [%0, {%2, %3}], [%1];" :: "l"(m), "r"(src), "r"(c0), "r"(c1) : "memory");
}
__device__ __forceinline__ void bulk_commit() { asm volatile("cp.async.bulk.commit_group;" ::: "memory"); }
__device__ __forceinline__ void bulk_wait_read() { asm volatile("cp.async.bulk.wait_group.read 0;" ::: "memory"); }
__device__ __forceinline__ void fence_async_smem() { asm volatile("fence.proxy.async.shared::cta;" ::: "memory"); }
__device__ __forceinline__ void prefetch_map(const CUtensorMap* m) { asm volatile("prefetch.tensormap [%0];" :: "l"(m) : "memory"); }
__device__ __forceinline__ void wg_fence() { asm volatile("wgmma.fence.sync.aligned;" ::: "memory"); }
__device__ __forceinline__ void wg_commit() { asm volatile("wgmma.commit_group.sync.aligned;" ::: "memory"); }
template <int N> __device__ __forceinline__ void wg_wait() { asm volatile("wgmma.wait_group.sync.aligned %0;" :: "n"(N) : "memory"); }
__device__ __forceinline__ void bar_sync(int id, int n) { asm volatile("bar.sync %0, %1;" :: "r"(id), "r"(n) : "memory"); }
__device__ __forceinline__ void bar_arrive(int id, int n) { asm volatile("bar.arrive %0, %1;" :: "r"(id), "r"(n) : "memory"); }
__device__ __forceinline__ void flag_add(uint32_t* f) { asm volatile("red.relaxed.gpu.global.add.u32 [%0], 1;" :: "l"(f) : "memory"); }
__device__ __forceinline__ void flag_set(uint32_t* f, uint32_t v) { asm volatile("red.relaxed.gpu.global.max.u32 [%0], %1;" :: "l"(f), "r"(v) : "memory"); }
__device__ __forceinline__ uint32_t flag_get(const uint32_t* f) { uint32_t v; asm volatile("ld.relaxed.gpu.global.u32 %0, [%1];" : "=r"(v) : "l"(f) : "memory"); return v; }
__device__ __forceinline__ void bulk_wait_fence() { asm volatile("cp.async.bulk.wait_group 0;\nfence.proxy.async.global;\nfence.acq_rel.gpu;" ::: "memory"); }
__device__ __forceinline__ uint32_t landed(bool el, const uint32_t* p, uint32_t pitch, uint32_t zero) {
    if (el) asm volatile("cp.async.bulk.wait_group 0;" ::: "memory");
    __syncwarp();
    const uint32_t a = flag_get(p), b = flag_get(p + 32 * pitch);
    return __reduce_or_sync(0xffffffffu, (a | b) & zero);
}
__device__ __forceinline__ uint32_t d16(uint32_t addr) { return (addr & 0x3FFFF) >> 4; }
__device__ __forceinline__ uint64_t mk_desc(uint32_t a16, uint32_t off, uint32_t lbo, uint32_t sbo, uint32_t swz) {
    const uint32_t lo = a16 + (off >> 4) + ((lbo >> 4) << 16), hi = (sbo >> 4) | (swz << 30);
    return ((uint64_t)hi << 32) | lo;
}
__device__ __forceinline__ uint32_t pack2(float lo, float hi) {
    uint32_t r; asm("cvt.rn.bf16x2.f32 %0, %1, %2;" : "=r"(r) : "f"(hi), "f"(lo)); return r;
}
__device__ __forceinline__ uint32_t hfma2_bf16(uint32_t a, uint32_t b, uint32_t c) {
    uint32_t r; asm("fma.rn.bf16x2 %0, %1, %2, %3;" : "=r"(r) : "r"(a), "r"(b), "r"(c)); return r;
}
__device__ __forceinline__ float bf_lo(uint32_t v) { return __uint_as_float(v << 16); }
__device__ __forceinline__ float bf_hi(uint32_t v) { return __uint_as_float(v & 0xFFFF0000u); }
__device__ __forceinline__ void unpack2(uint32_t v, float& lo, float& hi) {
    asm volatile("shl.b32 %0, %2, 16;\nand.b32 %1, %2, 0xffff0000;" : "=f"(lo), "=f"(hi) : "r"(v));
}
__device__ __forceinline__ float bf_round(float x) { return __bfloat162float(__float2bfloat16_rn(x)); }
__device__ __forceinline__ void stsm4(uint32_t addr, uint32_t r0, uint32_t r1, uint32_t r2, uint32_t r3) {
    asm volatile("stmatrix.sync.aligned.m8n8.x4.shared.b16 [%0], {%1, %2, %3, %4};" :: "r"(addr), "r"(r0), "r"(r1), "r"(r2), "r"(r3) : "memory");
}
__device__ __forceinline__ void stsm4t(uint32_t addr, uint32_t r0, uint32_t r1, uint32_t r2, uint32_t r3) {
    asm volatile("stmatrix.sync.aligned.m8n8.x4.trans.shared.b16 [%0], {%1, %2, %3, %4};" :: "r"(addr), "r"(r0), "r"(r1), "r"(r2), "r"(r3) : "memory");
}
__device__ __forceinline__ uint32_t movm(uint32_t a) { uint32_t d; asm volatile("movmatrix.sync.aligned.m8n8.trans.b16 %0, %1;" : "=r"(d) : "r"(a)); return d; }
__device__ __forceinline__ void ldsm4(uint32_t addr, uint32_t& r0, uint32_t& r1, uint32_t& r2, uint32_t& r3) {
    asm volatile("ldmatrix.sync.aligned.m8n8.x4.shared.b16 {%0, %1, %2, %3}, [%4];" : "=r"(r0), "=r"(r1), "=r"(r2), "=r"(r3) : "r"(addr) : "memory");
}
__device__ __forceinline__ void ldsm4t(uint32_t addr, uint32_t& r0, uint32_t& r1, uint32_t& r2, uint32_t& r3) {
    asm volatile("ldmatrix.sync.aligned.m8n8.x4.trans.shared.b16 {%0, %1, %2, %3}, [%4];" : "=r"(r0), "=r"(r1), "=r"(r2), "=r"(r3) : "r"(addr) : "memory");
}
__device__ __forceinline__ void mma16816(float (&c)[4], uint32_t a0, uint32_t a1, uint32_t a2, uint32_t a3, uint32_t b0, uint32_t b1) {
    asm("mma.sync.aligned.m16n8k16.row.col.f32.bf16.bf16.f32 {%0, %1, %2, %3}, {%4, %5, %6, %7}, {%8, %9}, {%0, %1, %2, %3};"
        : "+f"(c[0]), "+f"(c[1]), "+f"(c[2]), "+f"(c[3]) : "r"(a0), "r"(a1), "r"(a2), "r"(a3), "r"(b0), "r"(b1));
}
__device__ __forceinline__ float rcp(float x) { float r; asm("rcp.approx.ftz.f32 %0, %1;" : "=f"(r) : "f"(x)); return r; }
__device__ __forceinline__ float ex2(float x) { float r; asm("ex2.approx.ftz.f32 %0, %1;" : "=f"(r) : "f"(x)); return r; }
__device__ __forceinline__ float tanh_(float x) { float t; asm("tanh.approx.f32 %0, %1;" : "=f"(t) : "f"(x)); return t; }
__device__ __forceinline__ void block_end(uint32_t opaque, uint32_t id) { asm volatile("{\n.reg .pred p;\nsetp.eq.u32 p, %0, %1;\n@p trap;\n}" :: "r"(opaque), "r"(0xffffff00u + id)); }
__device__ __forceinline__ float silu_(float x) { return __fdividef(x, 1.f + __expf(-x)); }
__device__ __forceinline__ void st_pkt(void* p, uint32_t a, uint32_t b) {
    asm volatile("{\n.reg .b64 t;\nmov.b64 t, {%1, %2};\nst.relaxed.gpu.global.b64 [%0], t;\n}" :: "l"(p), "r"(a), "r"(b) : "memory");
}
__device__ __forceinline__ uint4 ld_pkt2(const void* p) {
    uint4 v; asm volatile("{\n.reg .b64 t, u;\nld.relaxed.gpu.global.v2.b64 {t, u}, [%4];\nmov.b64 {%0, %1}, t;\nmov.b64 {%2, %3}, u;\n}"
        : "=r"(v.x), "=r"(v.y), "=r"(v.z), "=r"(v.w) : "l"(p) : "memory"); return v;
}
__device__ __forceinline__ void st_pkt16(void* p, uint32_t a, uint32_t b, uint32_t c, uint32_t d) {
    asm volatile("{\n.reg .b64 t, u;\n.reg .b128 w;\nmov.b64 t, {%1, %2};\nmov.b64 u, {%3, %4};\nmov.b128 w, {t, u};\nst.relaxed.gpu.global.b128 [%0], w;\n}"
        :: "l"(p), "r"(a), "r"(b), "r"(c), "r"(d) : "memory");
}
__device__ __forceinline__ uint4 ld_pkt16(const void* p) {
    uint4 v; asm volatile("{\n.reg .b64 t, u;\n.reg .b128 w;\nld.relaxed.gpu.global.b128 w, [%4];\nmov.b128 {t, u}, w;\nmov.b64 {%0, %1}, t;\nmov.b64 {%2, %3}, u;\n}"
        : "=r"(v.x), "=r"(v.y), "=r"(v.z), "=r"(v.w) : "l"(p) : "memory"); return v;
}
#define SPIN_GUARD(n) do { if (++(n) > (1u << 22)) asm volatile("trap;"); } while (0)
__device__ __forceinline__ uint4 lds128(uint32_t a) { uint4 v; asm volatile("ld.shared.v4.u32 {%0, %1, %2, %3}, [%4];" : "=r"(v.x), "=r"(v.y), "=r"(v.z), "=r"(v.w) : "r"(a) : "memory"); return v; }
__device__ __forceinline__ void sts128(uint32_t a, uint32_t x, uint32_t y, uint32_t z, uint32_t w) { asm volatile("st.shared.v4.u32 [%0], {%1, %2, %3, %4};" :: "r"(a), "r"(x), "r"(y), "r"(z), "r"(w) : "memory"); }
__device__ __forceinline__ uint32_t lds32(uint32_t a) { uint32_t v; asm volatile("ld.shared.u32 %0, [%1];" : "=r"(v) : "r"(a) : "memory"); return v; }
__device__ __forceinline__ void sts32(uint32_t a, uint32_t v) { asm volatile("st.shared.u32 [%0], %1;" :: "r"(a), "r"(v) : "memory"); }
__device__ __forceinline__ bool elect_one() {
    uint32_t p; asm volatile("{\n.reg .pred q;\nelect.sync _|q, 0xffffffff;\nselp.u32 %0, 1, 0, q;\n}" : "=r"(p)); return p;
}
__device__ __forceinline__ void pause(uint32_t cycles) {
    uint32_t t0, t; asm volatile("mov.u32 %0, %%clock;" : "=r"(t0));
    do { __nanosleep(64); asm volatile("mov.u32 %0, %%clock;" : "=r"(t)); } while (t - t0 < cycles);
}
__device__ __forceinline__ void cluster_arrive() { asm volatile("barrier.cluster.arrive.relaxed.aligned;" ::: "memory"); }
__device__ __forceinline__ void cluster_wait() { asm volatile("barrier.cluster.wait.aligned;" ::: "memory"); }

__device__ __forceinline__ void wgmma_n128_z(float (&d)[64], uint64_t da, uint64_t db) {
    asm volatile("{\n.reg .pred p;\nsetp.ne.b32 p, 0, 0;\n"
        "wgmma.mma_async.sync.aligned.m64n128k16.f32.bf16.bf16 {"
        "%0, %1, %2, %3, %4, %5, %6, %7, %8, %9, %10, %11, %12, %13, %14, %15, "
        "%16, %17, %18, %19, %20, %21, %22, %23, %24, %25, %26, %27, %28, %29, %30, %31, "
        "%32, %33, %34, %35, %36, %37, %38, %39, %40, %41, %42, %43, %44, %45, %46, %47, "
        "%48, %49, %50, %51, %52, %53, %54, %55, %56, %57, %58, %59, %60, %61, %62, %63"
        "}, %64, %65, p, 1, 1, 0, 1;\n}\n"
        : "=f"(d[0]), "=f"(d[1]), "=f"(d[2]), "=f"(d[3]), "=f"(d[4]), "=f"(d[5]), "=f"(d[6]), "=f"(d[7]),
          "=f"(d[8]), "=f"(d[9]), "=f"(d[10]), "=f"(d[11]), "=f"(d[12]), "=f"(d[13]), "=f"(d[14]), "=f"(d[15]),
          "=f"(d[16]), "=f"(d[17]), "=f"(d[18]), "=f"(d[19]), "=f"(d[20]), "=f"(d[21]), "=f"(d[22]), "=f"(d[23]),
          "=f"(d[24]), "=f"(d[25]), "=f"(d[26]), "=f"(d[27]), "=f"(d[28]), "=f"(d[29]), "=f"(d[30]), "=f"(d[31]),
          "=f"(d[32]), "=f"(d[33]), "=f"(d[34]), "=f"(d[35]), "=f"(d[36]), "=f"(d[37]), "=f"(d[38]), "=f"(d[39]),
          "=f"(d[40]), "=f"(d[41]), "=f"(d[42]), "=f"(d[43]), "=f"(d[44]), "=f"(d[45]), "=f"(d[46]), "=f"(d[47]),
          "=f"(d[48]), "=f"(d[49]), "=f"(d[50]), "=f"(d[51]), "=f"(d[52]), "=f"(d[53]), "=f"(d[54]), "=f"(d[55]),
          "=f"(d[56]), "=f"(d[57]), "=f"(d[58]), "=f"(d[59]), "=f"(d[60]), "=f"(d[61]), "=f"(d[62]), "=f"(d[63])
        : "l"(da), "l"(db));
}
__device__ __forceinline__ void wgmma_n128(float (&d)[64], uint64_t da, uint64_t db) {
    asm volatile("{\n.reg .pred p;\nsetp.eq.b32 p, 0, 0;\n"
        "wgmma.mma_async.sync.aligned.m64n128k16.f32.bf16.bf16 {"
        "%0, %1, %2, %3, %4, %5, %6, %7, %8, %9, %10, %11, %12, %13, %14, %15, "
        "%16, %17, %18, %19, %20, %21, %22, %23, %24, %25, %26, %27, %28, %29, %30, %31, "
        "%32, %33, %34, %35, %36, %37, %38, %39, %40, %41, %42, %43, %44, %45, %46, %47, "
        "%48, %49, %50, %51, %52, %53, %54, %55, %56, %57, %58, %59, %60, %61, %62, %63"
        "}, %64, %65, p, 1, 1, 0, 1;\n}\n"
        : "+f"(d[0]), "+f"(d[1]), "+f"(d[2]), "+f"(d[3]), "+f"(d[4]), "+f"(d[5]), "+f"(d[6]), "+f"(d[7]),
          "+f"(d[8]), "+f"(d[9]), "+f"(d[10]), "+f"(d[11]), "+f"(d[12]), "+f"(d[13]), "+f"(d[14]), "+f"(d[15]),
          "+f"(d[16]), "+f"(d[17]), "+f"(d[18]), "+f"(d[19]), "+f"(d[20]), "+f"(d[21]), "+f"(d[22]), "+f"(d[23]),
          "+f"(d[24]), "+f"(d[25]), "+f"(d[26]), "+f"(d[27]), "+f"(d[28]), "+f"(d[29]), "+f"(d[30]), "+f"(d[31]),
          "+f"(d[32]), "+f"(d[33]), "+f"(d[34]), "+f"(d[35]), "+f"(d[36]), "+f"(d[37]), "+f"(d[38]), "+f"(d[39]),
          "+f"(d[40]), "+f"(d[41]), "+f"(d[42]), "+f"(d[43]), "+f"(d[44]), "+f"(d[45]), "+f"(d[46]), "+f"(d[47]),
          "+f"(d[48]), "+f"(d[49]), "+f"(d[50]), "+f"(d[51]), "+f"(d[52]), "+f"(d[53]), "+f"(d[54]), "+f"(d[55]),
          "+f"(d[56]), "+f"(d[57]), "+f"(d[58]), "+f"(d[59]), "+f"(d[60]), "+f"(d[61]), "+f"(d[62]), "+f"(d[63])
        : "l"(da), "l"(db));
}
__device__ __forceinline__ void wgmma_n176_z(float (&d)[88], uint64_t da, uint64_t db) {
    asm volatile("{\n.reg .pred p;\nsetp.ne.b32 p, 0, 0;\n"
        "wgmma.mma_async.sync.aligned.m64n176k16.f32.bf16.bf16 {"
        "%0, %1, %2, %3, %4, %5, %6, %7, %8, %9, %10, %11, %12, %13, %14, %15, "
        "%16, %17, %18, %19, %20, %21, %22, %23, %24, %25, %26, %27, %28, %29, %30, %31, "
        "%32, %33, %34, %35, %36, %37, %38, %39, %40, %41, %42, %43, %44, %45, %46, %47, "
        "%48, %49, %50, %51, %52, %53, %54, %55, %56, %57, %58, %59, %60, %61, %62, %63, "
        "%64, %65, %66, %67, %68, %69, %70, %71, %72, %73, %74, %75, %76, %77, %78, %79, "
        "%80, %81, %82, %83, %84, %85, %86, %87"
        "}, %88, %89, p, 1, 1, 0, 1;\n}\n"
        : "=f"(d[0]), "=f"(d[1]), "=f"(d[2]), "=f"(d[3]), "=f"(d[4]), "=f"(d[5]), "=f"(d[6]), "=f"(d[7]),
          "=f"(d[8]), "=f"(d[9]), "=f"(d[10]), "=f"(d[11]), "=f"(d[12]), "=f"(d[13]), "=f"(d[14]), "=f"(d[15]),
          "=f"(d[16]), "=f"(d[17]), "=f"(d[18]), "=f"(d[19]), "=f"(d[20]), "=f"(d[21]), "=f"(d[22]), "=f"(d[23]),
          "=f"(d[24]), "=f"(d[25]), "=f"(d[26]), "=f"(d[27]), "=f"(d[28]), "=f"(d[29]), "=f"(d[30]), "=f"(d[31]),
          "=f"(d[32]), "=f"(d[33]), "=f"(d[34]), "=f"(d[35]), "=f"(d[36]), "=f"(d[37]), "=f"(d[38]), "=f"(d[39]),
          "=f"(d[40]), "=f"(d[41]), "=f"(d[42]), "=f"(d[43]), "=f"(d[44]), "=f"(d[45]), "=f"(d[46]), "=f"(d[47]),
          "=f"(d[48]), "=f"(d[49]), "=f"(d[50]), "=f"(d[51]), "=f"(d[52]), "=f"(d[53]), "=f"(d[54]), "=f"(d[55]),
          "=f"(d[56]), "=f"(d[57]), "=f"(d[58]), "=f"(d[59]), "=f"(d[60]), "=f"(d[61]), "=f"(d[62]), "=f"(d[63]),
          "=f"(d[64]), "=f"(d[65]), "=f"(d[66]), "=f"(d[67]), "=f"(d[68]), "=f"(d[69]), "=f"(d[70]), "=f"(d[71]),
          "=f"(d[72]), "=f"(d[73]), "=f"(d[74]), "=f"(d[75]), "=f"(d[76]), "=f"(d[77]), "=f"(d[78]), "=f"(d[79]),
          "=f"(d[80]), "=f"(d[81]), "=f"(d[82]), "=f"(d[83]), "=f"(d[84]), "=f"(d[85]), "=f"(d[86]), "=f"(d[87])
        : "l"(da), "l"(db));
}
__device__ __forceinline__ void wgmma_n176(float (&d)[88], uint64_t da, uint64_t db) {
    asm volatile("{\n.reg .pred p;\nsetp.eq.b32 p, 0, 0;\n"
        "wgmma.mma_async.sync.aligned.m64n176k16.f32.bf16.bf16 {"
        "%0, %1, %2, %3, %4, %5, %6, %7, %8, %9, %10, %11, %12, %13, %14, %15, "
        "%16, %17, %18, %19, %20, %21, %22, %23, %24, %25, %26, %27, %28, %29, %30, %31, "
        "%32, %33, %34, %35, %36, %37, %38, %39, %40, %41, %42, %43, %44, %45, %46, %47, "
        "%48, %49, %50, %51, %52, %53, %54, %55, %56, %57, %58, %59, %60, %61, %62, %63, "
        "%64, %65, %66, %67, %68, %69, %70, %71, %72, %73, %74, %75, %76, %77, %78, %79, "
        "%80, %81, %82, %83, %84, %85, %86, %87"
        "}, %88, %89, p, 1, 1, 0, 1;\n}\n"
        : "+f"(d[0]), "+f"(d[1]), "+f"(d[2]), "+f"(d[3]), "+f"(d[4]), "+f"(d[5]), "+f"(d[6]), "+f"(d[7]),
          "+f"(d[8]), "+f"(d[9]), "+f"(d[10]), "+f"(d[11]), "+f"(d[12]), "+f"(d[13]), "+f"(d[14]), "+f"(d[15]),
          "+f"(d[16]), "+f"(d[17]), "+f"(d[18]), "+f"(d[19]), "+f"(d[20]), "+f"(d[21]), "+f"(d[22]), "+f"(d[23]),
          "+f"(d[24]), "+f"(d[25]), "+f"(d[26]), "+f"(d[27]), "+f"(d[28]), "+f"(d[29]), "+f"(d[30]), "+f"(d[31]),
          "+f"(d[32]), "+f"(d[33]), "+f"(d[34]), "+f"(d[35]), "+f"(d[36]), "+f"(d[37]), "+f"(d[38]), "+f"(d[39]),
          "+f"(d[40]), "+f"(d[41]), "+f"(d[42]), "+f"(d[43]), "+f"(d[44]), "+f"(d[45]), "+f"(d[46]), "+f"(d[47]),
          "+f"(d[48]), "+f"(d[49]), "+f"(d[50]), "+f"(d[51]), "+f"(d[52]), "+f"(d[53]), "+f"(d[54]), "+f"(d[55]),
          "+f"(d[56]), "+f"(d[57]), "+f"(d[58]), "+f"(d[59]), "+f"(d[60]), "+f"(d[61]), "+f"(d[62]), "+f"(d[63]),
          "+f"(d[64]), "+f"(d[65]), "+f"(d[66]), "+f"(d[67]), "+f"(d[68]), "+f"(d[69]), "+f"(d[70]), "+f"(d[71]),
          "+f"(d[72]), "+f"(d[73]), "+f"(d[74]), "+f"(d[75]), "+f"(d[76]), "+f"(d[77]), "+f"(d[78]), "+f"(d[79]),
          "+f"(d[80]), "+f"(d[81]), "+f"(d[82]), "+f"(d[83]), "+f"(d[84]), "+f"(d[85]), "+f"(d[86]), "+f"(d[87])
        : "l"(da), "l"(db));
}
__device__ __forceinline__ void wgmma_n256_z(float (&d)[128], uint64_t da, uint64_t db) {
    asm volatile("{\n.reg .pred p;\nsetp.ne.b32 p, 0, 0;\n"
        "wgmma.mma_async.sync.aligned.m64n256k16.f32.bf16.bf16 {"
        "%0, %1, %2, %3, %4, %5, %6, %7, %8, %9, %10, %11, %12, %13, %14, %15, "
        "%16, %17, %18, %19, %20, %21, %22, %23, %24, %25, %26, %27, %28, %29, %30, %31, "
        "%32, %33, %34, %35, %36, %37, %38, %39, %40, %41, %42, %43, %44, %45, %46, %47, "
        "%48, %49, %50, %51, %52, %53, %54, %55, %56, %57, %58, %59, %60, %61, %62, %63, "
        "%64, %65, %66, %67, %68, %69, %70, %71, %72, %73, %74, %75, %76, %77, %78, %79, "
        "%80, %81, %82, %83, %84, %85, %86, %87, %88, %89, %90, %91, %92, %93, %94, %95, "
        "%96, %97, %98, %99, %100, %101, %102, %103, %104, %105, %106, %107, %108, %109, %110, %111, "
        "%112, %113, %114, %115, %116, %117, %118, %119, %120, %121, %122, %123, %124, %125, %126, %127"
        "}, %128, %129, p, 1, 1, 0, 1;\n}\n"
        : "=f"(d[0]), "=f"(d[1]), "=f"(d[2]), "=f"(d[3]), "=f"(d[4]), "=f"(d[5]), "=f"(d[6]), "=f"(d[7]),
          "=f"(d[8]), "=f"(d[9]), "=f"(d[10]), "=f"(d[11]), "=f"(d[12]), "=f"(d[13]), "=f"(d[14]), "=f"(d[15]),
          "=f"(d[16]), "=f"(d[17]), "=f"(d[18]), "=f"(d[19]), "=f"(d[20]), "=f"(d[21]), "=f"(d[22]), "=f"(d[23]),
          "=f"(d[24]), "=f"(d[25]), "=f"(d[26]), "=f"(d[27]), "=f"(d[28]), "=f"(d[29]), "=f"(d[30]), "=f"(d[31]),
          "=f"(d[32]), "=f"(d[33]), "=f"(d[34]), "=f"(d[35]), "=f"(d[36]), "=f"(d[37]), "=f"(d[38]), "=f"(d[39]),
          "=f"(d[40]), "=f"(d[41]), "=f"(d[42]), "=f"(d[43]), "=f"(d[44]), "=f"(d[45]), "=f"(d[46]), "=f"(d[47]),
          "=f"(d[48]), "=f"(d[49]), "=f"(d[50]), "=f"(d[51]), "=f"(d[52]), "=f"(d[53]), "=f"(d[54]), "=f"(d[55]),
          "=f"(d[56]), "=f"(d[57]), "=f"(d[58]), "=f"(d[59]), "=f"(d[60]), "=f"(d[61]), "=f"(d[62]), "=f"(d[63]),
          "=f"(d[64]), "=f"(d[65]), "=f"(d[66]), "=f"(d[67]), "=f"(d[68]), "=f"(d[69]), "=f"(d[70]), "=f"(d[71]),
          "=f"(d[72]), "=f"(d[73]), "=f"(d[74]), "=f"(d[75]), "=f"(d[76]), "=f"(d[77]), "=f"(d[78]), "=f"(d[79]),
          "=f"(d[80]), "=f"(d[81]), "=f"(d[82]), "=f"(d[83]), "=f"(d[84]), "=f"(d[85]), "=f"(d[86]), "=f"(d[87]),
          "=f"(d[88]), "=f"(d[89]), "=f"(d[90]), "=f"(d[91]), "=f"(d[92]), "=f"(d[93]), "=f"(d[94]), "=f"(d[95]),
          "=f"(d[96]), "=f"(d[97]), "=f"(d[98]), "=f"(d[99]), "=f"(d[100]), "=f"(d[101]), "=f"(d[102]), "=f"(d[103]),
          "=f"(d[104]), "=f"(d[105]), "=f"(d[106]), "=f"(d[107]), "=f"(d[108]), "=f"(d[109]), "=f"(d[110]), "=f"(d[111]),
          "=f"(d[112]), "=f"(d[113]), "=f"(d[114]), "=f"(d[115]), "=f"(d[116]), "=f"(d[117]), "=f"(d[118]), "=f"(d[119]),
          "=f"(d[120]), "=f"(d[121]), "=f"(d[122]), "=f"(d[123]), "=f"(d[124]), "=f"(d[125]), "=f"(d[126]), "=f"(d[127])
        : "l"(da), "l"(db));
}
__device__ __forceinline__ void wgmma_n256(float (&d)[128], uint64_t da, uint64_t db) {
    asm volatile("{\n.reg .pred p;\nsetp.eq.b32 p, 0, 0;\n"
        "wgmma.mma_async.sync.aligned.m64n256k16.f32.bf16.bf16 {"
        "%0, %1, %2, %3, %4, %5, %6, %7, %8, %9, %10, %11, %12, %13, %14, %15, "
        "%16, %17, %18, %19, %20, %21, %22, %23, %24, %25, %26, %27, %28, %29, %30, %31, "
        "%32, %33, %34, %35, %36, %37, %38, %39, %40, %41, %42, %43, %44, %45, %46, %47, "
        "%48, %49, %50, %51, %52, %53, %54, %55, %56, %57, %58, %59, %60, %61, %62, %63, "
        "%64, %65, %66, %67, %68, %69, %70, %71, %72, %73, %74, %75, %76, %77, %78, %79, "
        "%80, %81, %82, %83, %84, %85, %86, %87, %88, %89, %90, %91, %92, %93, %94, %95, "
        "%96, %97, %98, %99, %100, %101, %102, %103, %104, %105, %106, %107, %108, %109, %110, %111, "
        "%112, %113, %114, %115, %116, %117, %118, %119, %120, %121, %122, %123, %124, %125, %126, %127"
        "}, %128, %129, p, 1, 1, 0, 1;\n}\n"
        : "+f"(d[0]), "+f"(d[1]), "+f"(d[2]), "+f"(d[3]), "+f"(d[4]), "+f"(d[5]), "+f"(d[6]), "+f"(d[7]),
          "+f"(d[8]), "+f"(d[9]), "+f"(d[10]), "+f"(d[11]), "+f"(d[12]), "+f"(d[13]), "+f"(d[14]), "+f"(d[15]),
          "+f"(d[16]), "+f"(d[17]), "+f"(d[18]), "+f"(d[19]), "+f"(d[20]), "+f"(d[21]), "+f"(d[22]), "+f"(d[23]),
          "+f"(d[24]), "+f"(d[25]), "+f"(d[26]), "+f"(d[27]), "+f"(d[28]), "+f"(d[29]), "+f"(d[30]), "+f"(d[31]),
          "+f"(d[32]), "+f"(d[33]), "+f"(d[34]), "+f"(d[35]), "+f"(d[36]), "+f"(d[37]), "+f"(d[38]), "+f"(d[39]),
          "+f"(d[40]), "+f"(d[41]), "+f"(d[42]), "+f"(d[43]), "+f"(d[44]), "+f"(d[45]), "+f"(d[46]), "+f"(d[47]),
          "+f"(d[48]), "+f"(d[49]), "+f"(d[50]), "+f"(d[51]), "+f"(d[52]), "+f"(d[53]), "+f"(d[54]), "+f"(d[55]),
          "+f"(d[56]), "+f"(d[57]), "+f"(d[58]), "+f"(d[59]), "+f"(d[60]), "+f"(d[61]), "+f"(d[62]), "+f"(d[63]),
          "+f"(d[64]), "+f"(d[65]), "+f"(d[66]), "+f"(d[67]), "+f"(d[68]), "+f"(d[69]), "+f"(d[70]), "+f"(d[71]),
          "+f"(d[72]), "+f"(d[73]), "+f"(d[74]), "+f"(d[75]), "+f"(d[76]), "+f"(d[77]), "+f"(d[78]), "+f"(d[79]),
          "+f"(d[80]), "+f"(d[81]), "+f"(d[82]), "+f"(d[83]), "+f"(d[84]), "+f"(d[85]), "+f"(d[86]), "+f"(d[87]),
          "+f"(d[88]), "+f"(d[89]), "+f"(d[90]), "+f"(d[91]), "+f"(d[92]), "+f"(d[93]), "+f"(d[94]), "+f"(d[95]),
          "+f"(d[96]), "+f"(d[97]), "+f"(d[98]), "+f"(d[99]), "+f"(d[100]), "+f"(d[101]), "+f"(d[102]), "+f"(d[103]),
          "+f"(d[104]), "+f"(d[105]), "+f"(d[106]), "+f"(d[107]), "+f"(d[108]), "+f"(d[109]), "+f"(d[110]), "+f"(d[111]),
          "+f"(d[112]), "+f"(d[113]), "+f"(d[114]), "+f"(d[115]), "+f"(d[116]), "+f"(d[117]), "+f"(d[118]), "+f"(d[119]),
          "+f"(d[120]), "+f"(d[121]), "+f"(d[122]), "+f"(d[123]), "+f"(d[124]), "+f"(d[125]), "+f"(d[126]), "+f"(d[127])
        : "l"(da), "l"(db));
}

struct Idx {
    uint32_t lane, warp, w4, q4, g8, prow, pan;
    __device__ __forceinline__ Idx() {
        uint32_t t; asm volatile("mov.u32 %0, %%tid.x;" : "=r"(t));
        lane = t & 31; warp = t >> 5; w4 = warp & 3; q4 = lane & 3; g8 = lane >> 2;
        prow = w4 * 16 + ((lane >> 3) & 1) * 8 + (lane & 7);
        pan = prow * 128 + (((lane >> 4) ^ (lane & 7)) << 4);
    }
};
#define IDX() const Idx ix; const uint32_t lane = ix.lane, warp = ix.warp, w4 = ix.w4, q4 = ix.q4, g8 = ix.g8, prow = ix.prow, pan_addr = ix.pan; \
    (void)lane; (void)warp; (void)w4; (void)q4; (void)g8; (void)prow; (void)pan_addr;

__device__ __forceinline__ int kof(int t, int sh, int j) {
    const int p = t >> (sh - 1), pn = p < 2 ? p : p >= 9, q = p - 2 - 7 * pn;
    return ((p < 2 ? j : q + (q >= j)) << 7) + (pn << 6) + ((t & (sh - 1)) << 5);
}
__device__ __forceinline__ uint32_t fidx(uint32_t m, uint32_t w, uint32_t pn) {
    return m * 32 + w * 16 + pn;
}
constexpr int HC0 = 8 * 48, HC3 = HC0 + 3072;
__device__ __forceinline__ int hcol(int p, int j) { return HC0 + p * 1024 + j * 128; }
struct Ring {
    uint32_t slot, par;
    __device__ __forceinline__ void next() { if (++slot == NSLOT) { slot = 0; par ^= 1; } }
    __device__ __forceinline__ void skip(uint32_t n) { slot += n; if (slot >= NSLOT) { slot -= NSLOT; par ^= 1; } }
};
__device__ __forceinline__ uint32_t BAR_FULL(uint32_t sb, uint32_t s) { return sb + OFF_BAR + 8 * s; }
constexpr uint32_t AF_REL = 48;
__device__ __forceinline__ uint32_t BAR_EMPTY(uint32_t sb, uint32_t s) { return sb + OFF_BAR + 96 + 8 * s; }
__device__ __forceinline__ uint32_t BAR_SFULL(uint32_t sb, uint32_t i) { return sb + OFF_BAR + 152 + 8 * i; }
__device__ __forceinline__ uint32_t BAR_SREADY(uint32_t sb, uint32_t i) { return sb + OFF_BAR + 184 + 8 * i; }
__device__ __forceinline__ uint32_t BAR_ONE(uint32_t sb, uint32_t i) { return sb + OFF_BAR + 216 + 8 * i; }
enum { EV_WIN, EV_WIN1, EV_WIN2, EV_WIN3, EV_P0, EV_GA, EV_GB, EV_LN2, EV_LAG1, EV_LAG2, EV_LAG3, EV_LAG4, EV_LAG5, EV_KV, EV_PAR, EV_AGO, EV_AGO1, EV_AGO2, EV_FGO, EV_FGO1, EV_FGO2, EV_H0, EV_H1, EV_H2, EV_H3, EV_TAIL, EV_COUNT = EV_TAIL + 8 };
constexpr int NB_TAIL = 4;

struct Rel {
    uint32_t base; bool sig;
    __device__ __forceinline__ Rel(uint32_t sb, uint32_t tw) {
        uint32_t a; asm("mapa.shared::cluster.u32 %0, %1, %2;" : "=r"(a) : "r"(BAR_EMPTY(sb, 0)), "r"((tw >> 5) & 1));
        base = __shfl_sync(0xffffffffu, a, 0); sig = (tw & ~32u) == 0;
    }
    __device__ __forceinline__ void operator()(uint32_t slot) const {
        if (sig) asm volatile("mbarrier.arrive.shared::cluster.b64 _, [%0];" :: "r"(base + 8 * slot) : "memory");
    }
};
struct LnRow { float rs0, nm0, rs1, nm1; };
struct Pipe {
    Rel rel; uint32_t p1, p2;
    __device__ __forceinline__ Pipe(uint32_t sb, uint32_t tw, uint32_t first) : rel(sb, tw), p1(first), p2(NSLOT) {}
    template <bool TWO> __device__ __forceinline__ void acquire(uint32_t sb, uint32_t af, const Ring& r) {
        const uint32_t b0 = BAR_FULL(sb, r.slot), b1 = b0 + af;
        const bool ready = TWO ? mbar_test2(b0, b1, r.par) : mbar_test(b0, r.par);
        wg_wait<1>();
        rel(p2);
        if (!ready) { if (TWO) mbar_wait2(b0, b1, r.par); else mbar_wait(b0, r.par); }
    }
    __device__ __forceinline__ void issued(uint32_t slot) { p2 = p1; p1 = slot; }
    __device__ __forceinline__ void drain1() { wg_wait<1>(); rel(p2); p2 = NSLOT; }
    __device__ __forceinline__ void drain0() { wg_wait<0>(); rel(p1); p1 = NSLOT; }
    template <bool TWO, class Step> __device__ __forceinline__ void hold(int LG, uint32_t sb, uint32_t af, Ring& r, uint32_t lag_bar, Step step) {
        Ring q = r;
#pragma unroll 1
        for (int i = 0; i < LG; ++i) { if (TWO) mbar_wait2(BAR_FULL(sb, q.slot), BAR_FULL(sb, q.slot) + af, q.par); else mbar_wait(BAR_FULL(sb, q.slot), q.par); q.next(); }
        mbar_wait(lag_bar, 0);
#pragma unroll 1
        do {
            step(r.slot);
            wg_wait<2>(); rel(p2); p2 = p1; p1 = r.slot;
            if (++r.slot == NSLOT) r.slot = 0;
        } while (r.slot != q.slot);
        r.par = q.par;
    }
};
template <bool TWO, bool FIRST, int NA, int NB>
__device__ __forceinline__ void step32(float (&aa)[NA], float (&ab)[NB], uint32_t sb, uint32_t wg, uint32_t slot, int own) {
    const uint32_t st = d16(sb) + slot * (SLOT >> 4);
    const uint32_t alo = own >= 0 ? d16(sb) + OFF_STG / 16 + wg * 1024 + (own >> 1) * 512 + (own & 1) * 4 : st + wg * 256;
    const uint32_t ahi = own >= 0 ? (1024 >> 4) | (1u << 30) : (512 >> 4) | (2u << 30);
    wg_fence();
#pragma unroll
    for (int k = 0; k < 2; ++k) {
        const uint64_t da = ((uint64_t)ahi << 32) | (alo + k * 2 + 0x10000);
        if constexpr (NA == 88) {
            const uint64_t d0 = mk_desc(st, 8192 + k * 2048, 8192, 1024, 1), d1 = mk_desc(st, 12288 + k * 2048, 8192, 1024, 1);
            if (FIRST && k == 0) { wgmma_n176_z(aa, da, d0); wgmma_n176_z(ab, da, d1); }
            else { wgmma_n176(aa, da, d0); wgmma_n176(ab, da, d1); }
        } else {
            const uint64_t d0 = mk_desc(st, 8192 + k * 2048, 4096, 1024, 1), d1 = mk_desc(st, 24576 + k * 2048, 4096, 1024, 1);
            if (FIRST && k == 0) { wgmma_n256_z(aa, da, d0); if constexpr (TWO) wgmma_n128_z(ab, da, d1); }
            else { wgmma_n256(aa, da, d0); if constexpr (TWO) wgmma_n128(ab, da, d1); }
        }
    }
    wg_commit();
}
template <bool TWO, int LG, int NA, int NB, class Tail>
__device__ __forceinline__ void mainloop32(float (&aa)[NA], float (&ab)[NB], uint32_t sb, uint32_t wg, uint32_t tw, Ring& r, uint32_t lag_ev, int g0, Tail tail) {
    if (!TWO) mbar_wait(BAR_FULL(sb, r.slot), r.par);
    step32<TWO, true>(aa, ab, sb, wg, r.slot, TWO ? 0 : -1);
    TS(g0, 0);
    Pipe pp(sb, tw, r.slot);
    r.next();
    const int end = wg ? 32 : 32 - LG;
#pragma unroll 1
    for (int it = 1; it < end; ++it) {
        pp.acquire<TWO>(sb, wg ? 0 : AF_REL, r);
        step32<TWO, false>(aa, ab, sb, wg, r.slot, TWO && it < 4 ? it : -1);
        pp.issued(r.slot);
        TS(g0 + it, 0);
        r.next();
    }
    if (wg == 0) { pp.drain1(); pp.drain0(); pp.hold<TWO>(LG, sb, AF_REL, r, BAR_ONE(sb, lag_ev), [&](uint32_t slot) { step32<TWO, false>(aa, ab, sb, 0, slot, -1); }); }
    pp.drain1();
    if (wg == 1 && tw == 0) mbar_arrive(BAR_ONE(sb, lag_ev));
    tail();
    pp.drain0();
    TS(g0 + 31, 1);
}
template <bool FIRST>
__device__ __forceinline__ void step64(float (&acc)[64], uint32_t sb, uint32_t wg, uint32_t slot, int own) {
    const uint32_t sbb = d16(sb) + slot * (SLOT >> 4), sa = own >= 0 ? d16(sb) + OFF_STG / 16 + wg * 1024 + own * 512 : sbb + wg * 512;
    wg_fence();
#pragma unroll
    for (int k = 0; k < 4; ++k) {
        const uint64_t da = mk_desc(sa, k * 32, 16, 1024, 1), db = mk_desc(sbb, 16384 + k * 2048, 8192, 1024, 1);
        if (FIRST && k == 0) wgmma_n128_z(acc, da, db); else wgmma_n128(acc, da, db);
    }
    wg_commit();
}
template <class Mid, class Tail>
__device__ __forceinline__ void mainloop64(float (&acc)[64], bool wo, uint32_t sb, uint32_t wg, uint32_t tw, Ring& r, Mid mid, Tail tail) {
    const int g0 = wo ? 32 : 144, nst = wo ? 16 : 56, lg = wo ? LAGW : LAGD; (void)g0;
    const uint32_t lag_bar = BAR_ONE(sb, wo ? EV_LAG4 : EV_LAG5), af = wo && !wg ? AF_REL : 0;
    mbar_wait(BAR_FULL(sb, r.slot), r.par);
    if (!wo) CS(28);
    step64<true>(acc, sb, wg, r.slot, wo ? 0 : -1);
    if (!wo) CS(29);
    TS(g0, 0);
    Pipe pp(sb, tw, r.slot);
    r.next();
    int it = 1;
    auto run = [&](int end, int own) {
#pragma unroll 1
        do {
            pp.acquire<true>(sb, af, r);
            step64<false>(acc, sb, wg, r.slot, own);
            pp.issued(r.slot);
            TS(g0 + it, 0);
            if (wo && it == 2) CS(9);
            r.next();
        } while (++it < end);
    };
    const int end = wg ? nst : nst - lg;
    run(wo ? 2 : wg ? MIDD : end, wo ? 1 : -1);
    mid();
    if (wo) { pp.drain1(); pp.drain0(); TS(g0 + 1, 1); }
    if (it < end) run(end, -1);
    if (wg == 0) { pp.drain1(); pp.drain0(); pp.hold<true>(lg, sb, af, r, lag_bar, [&](uint32_t slot) { step64<false>(acc, sb, 0, slot, -1); }); }
    pp.drain1();
    if (wg == 1 && tw == 0) mbar_arrive(lag_bar);
    tail();
    pp.drain0();
    TS(g0 + nst - 1, 1);
}

struct RowAcc {
    float sm[4] = {0.f, 0.f, 0.f, 0.f}, sq[4] = {0.f, 0.f, 0.f, 0.f};
    __device__ __forceinline__ void add(int e, float x) { sm[e & 3] += x; sq[e & 3] = fmaf(x, x, sq[e & 3]); }
    __device__ __forceinline__ void publish(uint4* dst, uint32_t q4, uint32_t ep) const {
        const float s0 = sm[0] + sm[1], s1 = sm[2] + sm[3], q0 = sq[0] + sq[1], q1 = sq[2] + sq[3];
        const bool od = q4 & 1;
        float sv = (od ? s1 : s0) + __shfl_xor_sync(0xffffffffu, od ? s0 : s1, 1), qv = (od ? q1 : q0) + __shfl_xor_sync(0xffffffffu, od ? q0 : q1, 1);
        sv += __shfl_xor_sync(0xffffffffu, sv, 2); qv += __shfl_xor_sync(0xffffffffu, qv, 2);
        st_pkt16(dst + (q4 & 1) * 8, 0, __float_as_uint(sv), __float_as_uint(qv), ep);
    }
};
__device__ __forceinline__ LnRow merge_stats(const uint4* src, uint32_t q4, uint32_t ep, uint32_t sb) {
    uint4 t[4];
    uint32_t n = 0;
    while (true) {
#pragma unroll
        for (int i = 0; i < 4; ++i) t[i] = ld_pkt16(src + (q4 * 2 + (i >> 1)) * 512 + (i & 1) * 8);
        const bool ok_ = __all_sync(0xffffffffu, t[0].w == ep && t[1].w == ep && t[2].w == ep && t[3].w == ep);
        if (n < 4) CS(14 + n);
        if (ok_) break;
        SPIN_GUARD(n);
    }
    float v[4];
#pragma unroll
    for (int h = 0; h < 2; ++h) { v[h] = __uint_as_float(t[h].y) + __uint_as_float(t[2 + h].y); v[2 + h] = __uint_as_float(t[h].z) + __uint_as_float(t[2 + h].z); }
#pragma unroll
    for (int o = 1; o < 4; o <<= 1)
#pragma unroll
        for (int i = 0; i < 4; ++i) v[i] += __shfl_xor_sync(0xffffffffu, v[i], o);
    const float m0 = v[0] * (1.f / D_), m1 = v[1] * (1.f / D_);
    const float r0 = rsqrtf(fmaxf(fmaf(-m0, m0, v[2] * (1.f / D_)), 0.f) + 1e-5f), r1 = rsqrtf(fmaxf(fmaf(-m1, m1, v[3] * (1.f / D_)), 0.f) + 1e-5f);
    return LnRow{r0, -m0 * r0, r1, -m1 * r1};
}
struct Stg {
    uint32_t b, par;
    __device__ __forceinline__ uint32_t acquire2(uint32_t sb, uint32_t wg) {
        mbar_wait2(BAR_SREADY(sb, wg * 2), BAR_SREADY(sb, wg * 2 + 1), par);
        par ^= 1;
        return sb + OFF_STG + wg * 16384;
    }
    __device__ __forceinline__ void publish(uint32_t sb, uint32_t wg, uint32_t lane) {
        fence_async_smem();
        __syncwarp();
        if (lane == 0) mbar_arrive(BAR_SFULL(sb, wg * 2 + b));
        b ^= 1;
    }
};

struct LnPar {
    uint4 p[8];
    __device__ __forceinline__ void load(uint32_t sb, uint32_t q4) {
#pragma unroll
        for (int i = 0; i < 8; ++i) p[i] = lds128(sb + OFF_PAR + i * 64 + q4 * 16);
    }
};
__device__ __forceinline__ void ln_norm(uint32_t (&xn)[32], const float (&x)[64], const LnRow& n) {
#pragma unroll
    for (int e = 0; e < 32; ++e) {
        const float rs = (e & 1) ? n.rs1 : n.rs0, nm = (e & 1) ? n.nm1 : n.nm0;
        xn[e] = pack2(fmaf(x[2 * e], rs, nm), fmaf(x[2 * e + 1], rs, nm));
    }
}
__device__ __forceinline__ void ln_emit(const uint32_t (&xr)[32], const LnPar& lp, uint32_t sb, uint32_t wg, const Idx& ix) {
#pragma unroll
    for (int i = 0; i < 8; ++i)
        stsm4(sb + OFF_STG + wg * 16384 + (i >> 2) * 8192 + (ix.pan ^ ((i & 3) << 5)), hfma2_bf16(xr[4 * i], lp.p[i].z, lp.p[i].x), hfma2_bf16(xr[4 * i + 1], lp.p[i].z, lp.p[i].x),
              hfma2_bf16(xr[4 * i + 2], lp.p[i].w, lp.p[i].y), hfma2_bf16(xr[4 * i + 3], lp.p[i].w, lp.p[i].y));
    fence_async_smem();
    __syncwarp();
    if (ix.lane < 2) mbar_arrive(BAR_SFULL(sb, wg * 2 + ix.lane));
    bar_sync(1 + wg, 128);
}
__device__ __forceinline__ void load_slab(uint32_t (&xr)[32], uint32_t buf) {
    IDX();
#pragma unroll
    for (int i = 0; i < 8; ++i) ldsm4(buf + (i >> 2) * 8192 + (pan_addr ^ ((i & 3) << 5)), xr[4 * i], xr[4 * i + 1], xr[4 * i + 2], xr[4 * i + 3]);
}
__device__ __forceinline__ void unpack_slab(float (&x)[64], const uint32_t (&xr)[32]) {
#pragma unroll
    for (int i = 0; i < 32; ++i) unpack2(xr[i], x[2 * i], x[2 * i + 1]);
}
__device__ __forceinline__ void store_slab(const float (&x)[64], uint32_t buf, uint32_t pitch, uint32_t pan, int i0, int i1) {
#pragma unroll
    for (int i = i0; i < i1; ++i)
        stsm4(buf + (i >> 2) * pitch + (pan ^ ((i & 3) << 5)), pack2(x[8 * i], x[8 * i + 1]), pack2(x[8 * i + 2], x[8 * i + 3]), pack2(x[8 * i + 4], x[8 * i + 5]), pack2(x[8 * i + 6], x[8 * i + 7]));
}
template <int NP, class Done>
__device__ __forceinline__ void fetch_halo(uint4* src, bool first, uint32_t dst, Done done) {
    uint4 hv[4 * NP];
    uint32_t n = 0;
    while (true) {
        bool ok = true;
#pragma unroll
        for (int i = 0; i < 4 * NP; ++i) { hv[i] = first ? make_uint4(0, 0, 0, 0) : ld_pkt16(src + (i >> 2) * 256 + (i & 3) * 32); ok = ok && hv[i].x != 0; }
        if (first || __all_sync(0xffffffffu, ok)) break;
        SPIN_GUARD(n);
    }
#pragma unroll
    for (int i = 0; i < 4 * NP; ++i) stsm4(dst + (i >> 2) * 4096 + (i & 3) * 512, hv[i].x, hv[i].y, hv[i].z, hv[i].w);
    done();
    if (!first) {
#pragma unroll
        for (int i = 0; i < 4 * NP; ++i) src[(i >> 2) * 256 + (i & 3) * 32] = make_uint4(0, 0, 0, 0);
    }
}

template <int NG, class G, class U, class Buf>
__device__ __forceinline__ void glu(uint32_t sb, uint32_t wg, G g, U u, Buf buf) {
    IDX();
#pragma unroll
    for (int k = 0; k < NG; ++k) {
        float h[8];
#pragma unroll
        for (int e = 0; e < 8; ++e) h[e] = fmaf(tanh_(g(8 * k + e)), u(8 * k + e), u(8 * k + e));
        stsm4(buf(k >> 2) + (pan_addr ^ ((k & 3) << 5)), pack2(h[0], h[1]), pack2(h[2], h[3]), pack2(h[4], h[5]), pack2(h[6], h[7]));
    }
    fence_async_smem();
    __syncwarp();
    if (lane < 2) mbar_arrive(BAR_SFULL(sb, wg * 2 + lane));
}

template <int NP>
__device__ __forceinline__ void passes128(uint32_t sb, uint32_t wg, uint32_t tw, Ring& r, Stg& stg) {
#pragma unroll 1
    for (int p = 0; p < NP; ++p) {
        float b256[128], none[1];
        mainloop32<false, LAGS>(b256, none, sb, wg, tw, r, EV_LAG2 + p, 80 + 32 * (p & 1), [&] { stg.acquire2(sb, wg); });
        if (threadIdx.x == 0) { TL(29 + 2 * p); TC(114 + 2 * p); }
        if (threadIdx.x == 128) TL(53 + 2 * (p & 1));
        CS(24 + 2 * (p & 1));
        glu<8>(sb, wg, [&](int i) { return b256[i + (i & 32)]; }, [&](int i) { return b256[i + (i & 32) + 32]; }, [&](int pn) { return sb + OFF_STG + wg * 16384 + pn * 8192; });
        if (threadIdx.x == 0) { TL(30 + 2 * p); TC(115 + 2 * p); }
        if (threadIdx.x == 128) TL(54 + 2 * (p & 1));
        CS(25 + 2 * (p & 1));
    }
}

__global__ void __launch_bounds__(384, 1)
fused_block_kernel(const __grid_constant__ Ptrs pt, const __grid_constant__ Maps mp) {
    uint32_t* const g_flags = pt.mail->flags;
    uint2* const g_mod = pt.mail->mod;
    uint4* const g_st1 = pt.mail->st1;
    uint32_t* const g_par2 = pt.mail->par2;
    uint4* const g_halo = pt.mail->halo;
    const __nv_bfloat16* __restrict__ cvec = pt.c;
    if (threadIdx.x == 224) { prefetch_map(&mp.wm8); prefetch_map(&mp.x); }
    extern __shared__ __align__(1024) uint8_t smem[];
    const uint32_t sb = smem_u32(smem);
    const uint32_t tid = threadIdx.x, tw = tid & 127, lane = tid & 31;
    const uint32_t warp = __shfl_sync(0xffffffffu, tid >> 5, 0), wg = warp >> 2;
    uint32_t rank; asm("mov.u32 %0, %%cluster_ctarank;" : "=r"(rank));
    rank = __shfl_sync(0xffffffffu, rank, 0);
    uint32_t ep;
    uint32_t smid; asm volatile("mov.u32 %0, %%smid;" : "=r"(smid));
    const int c = __shfl_sync(0xffffffffu, smid >> 1, 0);
    const int c7 = ((c - 32) * 37) >> 8;
    int grp = c < 32 ? c & 7 : c < 60 ? c - 31 - 7 * c7 : c < 62 ? -1 : 0;
    const int j = c < 32 ? c >> 3 : c < 60 ? 4 + c7 : c < 62 ? (c - 60) * 2 + rank : c - 58;
    const bool aux = grp < 0;
    const int m = grp * 2 + rank;
    uint4* const g_st2 = g_halo + (m > 0 ? (m - 1) * 8 * 512 : 128);

    bool cluster_arrive_early = false;
    if (wg < 2) {
      if (!KDEBUG) cluster_arrive();
      ep = flag_get(g_flags + FL_DONE);
      uint16_t cw[8];
      {
          const __nv_bfloat16* cp = cvec + ((tw >> 5) * 32 + (tw & 3) * 2) * 8 + (lane >> 2);
#pragma unroll
          for (int i = 0; i < 8; ++i) asm volatile("ld.global.nc.u16 %0, [%1];" : "=h"(cw[i]) : "l"(cp + (i >> 1) * 64 + (i & 1) * 8));
      }
      asm volatile("setmaxnreg.inc.sync.aligned.u32 224;");
      if (tid == 0) TL(58);
      if (KDEBUG) cluster_arrive();
      Ring r{0, 0};
      Stg stg{0, 0};
      if (aux) {
        if (wg == 0) {
            const uint4 cv = *(const uint4*)(cvec + tw * 8);
            sts128(sb + OFF_STG + (tw >> 3) * 1024 + (tw & 7) * 16, pack2(silu_(bf_lo(cv.x)), silu_(bf_hi(cv.x))), pack2(silu_(bf_lo(cv.y)), silu_(bf_hi(cv.y))),
                   pack2(silu_(bf_lo(cv.z)), silu_(bf_hi(cv.z))), pack2(silu_(bf_lo(cv.w)), silu_(bf_hi(cv.w))));
            fence_async_smem();
        }
        cluster_wait();
        ep = __shfl_sync(0xffffffffu, ep, 0) / NCTA + 1;
        if (wg == 0) {
            bar_sync(1, 128);
#pragma unroll 1
            for (int p = 0; p < 4; ++p) {
                float acc[128];
#pragma unroll
                for (int i = 0; i < 128; ++i) acc[i] = 0.f;
                uint32_t prev = 0;
#pragma unroll 1
                for (int kc = 0; kc < 16; ++kc) {
                    mbar_wait(BAR_FULL(sb, r.slot), r.par);
                    wg_fence();
#pragma unroll
                    for (int k = 0; k < 4; ++k)
                        wgmma_n256(acc, mk_desc(d16(sb) + kc * 64, OFF_STG + k * 32, 16, 0, 1), mk_desc(d16(sb) + r.slot * (SLOT >> 4), k * 2048, 8192, 1024, 1));
                    wg_commit();
                    wg_wait<1>();
                    if (kc > 0 && tw < 4) mbar_arrive(BAR_EMPTY(sb, prev));
                    prev = r.slot;
                    r.next();
                }
                wg_wait<0>();
                if (tw < 4) mbar_arrive(BAR_EMPTY(sb, prev));
                if (tw < 4) {
#pragma unroll
                    for (int jn = 0; jn < 32; ++jn) sts32(sb + OFF_TAB + (jn * 4 + tw) * 4, pack2(acc[jn * 4], acc[jn * 4 + 1]));
                }
                bar_sync(1, 128);
                const int vec = 2 + p, blk = p * 4 + j;
                const uint32_t val = lds32(sb + OFF_TAB + tw * 4);
                if (vec == 2 || vec == 5) st_pkt(g_mod + (8 + blk) * 128 + tw, val, ep);
                else {
                    const float one = vec == 4 ? 1.f : 0.f;
                    g_par2[((blk & 3) * 16 + (tw >> 3)) * 16 + (tw & 3) * 4 + (vec - 3) * 2 + ((tw >> 2) & 1)] =
                        pack2(0.5f * bf_round(one + bf_lo(val)), 0.5f * bf_round(one + bf_hi(val)));
                }
                bar_sync(1, 128);
                if (tw == 0) {
                    if (vec == 3 || vec == 4) asm volatile("red.release.gpu.global.add.u32 [%0], 1;" :: "l"(&g_flags[FL_LN2]) : "memory");
                    TL(1 + p);
                }
            }
            if (lane < 2) mbar_arrive_cta(BAR_ONE(sb, EV_P0), lane);
        }
        r = Ring{64 % NSLOT, (64 / NSLOT) & 1};
        mbar_wait(BAR_ONE(sb, EV_P0), 0);
        passes128<4>(sb, wg, tw, r, stg);
      } else {
        float xs[64];
        uint32_t xp[32];
        {
            IDX();
            if (q4 < 2) st_pkt16(g_st1 + (m * 8 + j) * 512 + wg * 64 + w4 * 16 + g8 + q4 * 8, 0, 0, 0, 0);
            if (warp == 0) st_pkt16(pt.mail->mod1 + g8 * 512 + (m * 8 + j) * 4 + q4, 0, 0, 0, 0);
            sts128(sb + tid * 16, pack2(silu_(bf_lo(cw[0])), silu_(bf_lo(cw[1]))), pack2(silu_(bf_lo(cw[2])), silu_(bf_lo(cw[3]))),
                   pack2(silu_(bf_lo(cw[4])), silu_(bf_lo(cw[5]))), pack2(silu_(bf_lo(cw[6])), silu_(bf_lo(cw[7]))));
            cluster_wait();
            ep = __shfl_sync(0xffffffffu, ep, 0) / NCTA + 1;
            load_slab(xp, stg.acquire2(sb, wg));
            unpack_slab(xs, xp);
            if (tid == 0) TL(24);
            if (tid == 128) TL(27);
        }
#pragma unroll 1
        for (int blk = 0; ; ++blk) {
        {
            IDX();
            uint4* const st = (blk ? g_st2 : g_st1 + m * 8 * 512) + wg * 64 + w4 * 16 + g8;
            RowAcc ra;
#pragma unroll
            for (int e = 0; e < 64; ++e) ra.add(e, xs[e]);
            ra.publish(st + j * 512, q4, ep);
            uint32_t t_pub = 0; if (PDLY) asm volatile("mov.u32 %0, %%clock;" : "=r"(t_pub));
            if (tid == 0) TL(blk ? 9 : 26);
            if (tid == 128 && blk) TL(34);
            if (blk) CS(11);
            LnPar lp;
            if (blk == 0) {
            uint4* const mod_out = pt.mail->mod1 + g8 * 512 + (m * 8 + j) * 4 + q4;
            if (wg == 0) {
                uint4 af[8];
#pragma unroll
                for (int i = 0; i < 8; ++i) af[i] = lds128(sb + w4 * 512 + i * 64 + q4 * 16);
                float c[4][4] = {};
#pragma unroll
                for (int i = 0; i < 8; ++i) {
                    if (!(i & 1)) mbar_wait(BAR_ONE(sb, EV_WIN + (i >> 1)), 0);
                    if (i == 6 && tid == 0) TL(25);
#pragma unroll
                    for (int h = 0; h < 2; ++h) {
                        uint32_t b0, b1, b2, b3;
                        ldsm4t(sb + 5 * SLOT + i * 4096 + w4 * 1024 + h * 512 + (lane & 15) * 32 + (lane >> 4) * 16, b0, b1, b2, b3);
                        mma16816(c[2 * h], h ? af[i].z : af[i].x, 0u, h ? af[i].w : af[i].y, 0u, b0, b1);
                        mma16816(c[2 * h + 1], h ? af[i].z : af[i].x, 0u, h ? af[i].w : af[i].y, 0u, b2, b3);
                    }
                }
                if (lane < 4) sts128(sb + OFF_TAB + w4 * 64 + lane * 16, __float_as_uint(c[0][0] + c[2][0]), __float_as_uint(c[0][1] + c[2][1]),
                                     __float_as_uint(c[1][0] + c[3][0]), __float_as_uint(c[1][1] + c[3][1]));
                if (lane < 2) mbar_arrive_cta(BAR_ONE(sb, EV_P0), lane);
                bar_sync(1, 128);
                if (w4 == 0) {
                    float a[4] = {0.f, 0.f, 0.f, 0.f};
#pragma unroll
                    for (int i = 0; i < 4; ++i) {
                        const uint4 t = lds128(sb + OFF_TAB + i * 64 + q4 * 16);
                        a[0] += __uint_as_float(t.x); a[1] += __uint_as_float(t.y); a[2] += __uint_as_float(t.z); a[3] += __uint_as_float(t.w);
                    }
                    const float add = m >= 8 ? 1.f : 0.f;
                    st_pkt16(mod_out, pack2(bf_round(a[0]) + add, bf_round(a[1]) + add), pack2(bf_round(a[2]) + add, bf_round(a[3]) + add), ep, 0);
                    if (tid == 0) TL(3);
                }
            } else if (LWAIT >= 0) mbar_wait(BAR_ONE(sb, EV_WIN + LWAIT), 0);
            } else {
                mbar_wait2(BAR_ONE(sb, EV_LN2), BAR_FULL(sb, 0), 0);
            }
            lp.load(sb, q4);
#pragma unroll
            for (int e = 0; e < 32; ++e) xp[e] = pack2(xs[2 * e], xs[2 * e + 1]);
            if (PDLY && blk) { uint32_t t1; do { asm volatile("mov.u32 %0, %%clock;" : "=r"(t1)); } while (t1 - t_pub < PDLY); }
            if (blk) CS(13);
            const LnRow n = merge_stats(st, q4, ep, sb);
            if (tid == 0) TL(blk ? 49 : 48);
            if (tid == 128) TL(blk ? 45 : 28);
            if (blk) CS(18);
            uint32_t xn[32];
            ln_norm(xn, xs, n);
            if (blk == 0) { mbar_wait2(BAR_FULL(sb, 0), BAR_ONE(sb, EV_PAR), 0); lp.load(sb, q4); }
            ln_emit(xn, lp, sb, wg, ix);
            if (tid == 0) { TL(blk ? 36 : 8); TC(blk ? 109 : 103); }
            if (tid == 128) TL(blk ? 43 : 22);
            if (blk) CS(21);
        }
        if (blk == 0) {
        {
            float big[128], sml[64];
            step32<true, true>(big, sml, sb, wg, r.slot, 0);
            TS(0, 0);
            Pipe pp(sb, tw, r.slot);
            r.next();
#pragma unroll 1
            for (int it = 1; it < 32 - LAGQ; ++it) {
                pp.acquire<true>(sb, wg ? 0 : AF_REL, r);
                step32<true, false>(big, sml, sb, wg, r.slot, it < 4 ? it : -1);
                pp.issued(r.slot);
                TS(it, 0);
                r.next();
            }
            auto half = [&](uint32_t slot, bool rest) {
                const uint32_t st = d16(sb) + slot * (SLOT >> 4);
#pragma unroll
                for (int k = 0; k < 2; ++k) {
                    const uint64_t da = mk_desc(st + wg * 256, k * 32, 16, 512, 2);
                    if (rest) wgmma_n256(big, da, mk_desc(st, 8192 + k * 2048, 4096, 1024, 1)); else wgmma_n128(sml, da, mk_desc(st, 24576 + k * 2048, 4096, 1024, 1));
                }
            };
            auto rest = [&](bool each) {
                wg_fence();
#pragma unroll
                for (int it = 32 - LAGQ; it < 32; ++it) { if (each && it > 32 - LAGQ) wg_fence(); half(it % NSLOT, true); if (each || it == 31) wg_commit(); }
            };
            stg.acquire2(sb, wg); mbar_wait2(BAR_SREADY(sb, 2), BAR_SREADY(sb, 3), 1);
#pragma unroll 1
            for (int it = 32 - LAGQ; it < 32; ++it) {
                pp.acquire<true>(sb, wg ? 0 : AF_REL, r);
                wg_fence(); half(r.slot, false); wg_commit();
                pp.issued(NSLOT);
                TS(it, 0);
                r.next();
            }
            if (wg) { rest(false); wg_wait<1>(); } else wg_wait<0>();
            CS(8);
            IDX();
            uint32_t k0[8], k1[8], k2[8], v0[8], v1[8], v2[8];
            const uint32_t nxt = warp + ((warp & 1) ? 3 : 1), mine = sb + OFF_STG + wg * 16384 + w4 * 2048;
            auto tails = [&](const float* kv, uint32_t (&kt)[8], uint32_t (&vt)[8]) {
#pragma unroll
                for (int t = 0; t < 8; ++t) { kt[t] = pack2(kv[4 * t + 2], kv[4 * t + 3]); vt[t] = pack2(kv[32 + 4 * t + 2], kv[32 + 4 * t + 3]); }
            };
            auto post = [&](int pn, uint32_t (&kt)[8], uint32_t (&vt)[8]) {
                uint4* dst = g_halo + (m * 8 + j) * 512 + (w4 >> 1) * 256 + pn * 128 + lane;
#pragma unroll
                for (int h = 0; h < 2; ++h) { if (!kt[4 * h]) kt[4 * h] = 0x8000u; if (!vt[4 * h]) vt[4 * h] = 0x8000u; }
#pragma unroll
                for (int h = 0; h < 2; ++h) { st_pkt16(dst + h * 32, kt[4 * h], kt[4 * h + 1], kt[4 * h + 2], kt[4 * h + 3]); st_pkt16(dst + 64 + h * 32, vt[4 * h], vt[4 * h + 1], vt[4 * h + 2], vt[4 * h + 3]); }
            };
            auto prepare = [&](int pn, const float* kv) {
                tails(kv, k2, v2);
                if (nxt < 8) {
                    const uint32_t dst = sb + OFF_STG + (nxt >> 2) * 16384 + (nxt & 3) * 2048 + pn * 8192 + lane * 16;
#pragma unroll
                    for (int h = 0; h < 2; ++h) { stsm4(dst + h * 512, k2[4 * h], k2[4 * h + 1], k2[4 * h + 2], k2[4 * h + 3]); stsm4(dst + 1024 + h * 512, v2[4 * h], v2[4 * h + 1], v2[4 * h + 2], v2[4 * h + 3]); }
                    if (pn == 0) bar_arrive(NB_TAIL + nxt, 64);
                    else { __syncwarp(); if (lane == 0) mbar_arrive(BAR_ONE(sb, EV_TAIL + nxt)); }
                } else if (pn == 0 && m < 15) post(0, k2, v2);
#pragma unroll
                for (int t = 0; t < 8; ++t) { k1[t] = pack2(kv[4 * t], kv[4 * t + 1]); v1[t] = movm(pack2(kv[32 + 4 * t], kv[32 + 4 * t + 1])); v2[t] = movm(v2[t]); }
                if (pn == 0) { CS(2); if (wg == 0) { rest(true); wg_wait<3>(); pp.rel(28 % NSLOT); wg_wait<2>(); pp.rel(29 % NSLOT); wg_wait<1>(); pp.rel(30 % NSLOT); } bar_sync(NB_TAIL + warp, 64); CS(4); }
                else mbar_wait(BAR_ONE(sb, EV_TAIL + __shfl_sync(0xffffffffu, warp, 0)), 0);
#pragma unroll
                for (int h = 0; h < 2; ++h) {
                    ldsm4(mine + pn * 8192 + lane * 16 + h * 512, k0[4 * h], k0[4 * h + 1], k0[4 * h + 2], k0[4 * h + 3]);
                    ldsm4t(mine + pn * 8192 + lane * 16 + 1024 + h * 512, v0[4 * h], v0[4 * h + 1], v0[4 * h + 2], v0[4 * h + 3]);
                }
            };
#pragma unroll
            for (int i = 0; i < 64; ++i) asm volatile("" : "+f"(sml[i]) :: "memory");
            prepare(0, sml);
            static_assert(LAGQ == 4, "");
            wg_wait<0>();
            if (wg) { pp.rel(28 % NSLOT); pp.rel(29 % NSLOT); pp.rel(30 % NSLOT); }
            pp.rel(31 % NSLOT);
            TS(31, 1);
            if (tid == 0) { TL(4); TC(104); }
            if (tid == 128) TL(50);
            CS(1);
#pragma unroll
            for (int i = 0; i < 128; ++i) asm volatile("" : "+f"(big[i]) :: "memory");
            if (nxt >= 8 && m < 15) { uint32_t kt[8], vt[8]; tails(big, kt, vt); post(1, kt, vt); }
            const bool lo0 = q4 * 2 > g8, lo1 = q4 * 2 + 1 > g8;
            const bool nopast = m == 0 && (warp & 5) == 0;
            const uint32_t lomask = (lo0 ? 0xFFFFu : 0u) | (lo1 ? 0xFFFF0000u : 0u);
            const uint32_t orow = mine + (lane & 7) * 128 + (((lane >> 3) ^ (lane & 7)) << 4);
            const float sl2 = 0.17677669529663687f * 1.4426950408889634f;
#pragma unroll
            for (int pn = 0; pn < 2; ++pn) {
                float e0[4], e1[4], mx[4], sum[4];
#pragma unroll
                for (int hh = 0; hh < 2; ++hh) {
                    uint32_t qf[8];
#pragma unroll
                    for (int i = 0; i < 8; ++i) qf[i] = pack2(big[64 + 32 * pn + 16 * hh + 2 * i], big[64 + 32 * pn + 16 * hh + 2 * i + 1]);
                    float s[3][4];
#pragma unroll
                    for (int t = 0; t < 3; ++t) {
                        const uint32_t* k = (t == 0 ? k0 : t == 1 ? k1 : k2) + 4 * hh;
                        s[t][0] = s[t][1] = s[t][2] = s[t][3] = 0.f;
                        mma16816(s[t], qf[0], qf[1], qf[2], qf[3], k[0], k[1]);
                        mma16816(s[t], qf[4], qf[5], qf[6], qf[7], k[2], k[3]);
                    }
#pragma unroll
                    for (int hf = 0; hf < 2; ++hf) {
                        const int u = hh * 2 + hf;
                        e0[u] = lo0 ? ((hf == 0 && nopast) ? -INFINITY : s[hf][hf * 2]) : s[hf + 1][hf * 2];
                        e1[u] = lo1 ? ((hf == 0 && nopast) ? -INFINITY : s[hf][hf * 2 + 1]) : s[hf + 1][hf * 2 + 1];
                        mx[u] = fmaxf(e0[u], e1[u]);
                    }
                }
#pragma unroll
                for (int o = 1; o < 4; o <<= 1)
#pragma unroll
                    for (int u = 0; u < 4; ++u) mx[u] = fmaxf(mx[u], __shfl_xor_sync(0xffffffffu, mx[u], o));
#pragma unroll
                for (int u = 0; u < 4; ++u) {
                    const float c = -mx[u] * sl2;
                    e0[u] = ex2(fmaf(e0[u], sl2, c)); e1[u] = ex2(fmaf(e1[u], sl2, c));
                    sum[u] = e0[u] + e1[u];
                }
#pragma unroll
                for (int o = 1; o < 4; o <<= 1)
#pragma unroll
                    for (int u = 0; u < 4; ++u) sum[u] += __shfl_xor_sync(0xffffffffu, sum[u], o);
#pragma unroll
                for (int u = 0; u < 4; ++u) {
                    const int h = u >> 1;
                    const float inv = rcp(sum[u]);
                    const uint32_t p = pack2(e0[u] * inv, e1[u] * inv);
                    const uint32_t* va = ((u & 1) ? v1 : v0) + 4 * h;
                    const uint32_t* vb = ((u & 1) ? v2 : v1) + 4 * h;
                    float o[2][4] = {};
#pragma unroll
                    for (int d = 0; d < 2; ++d) mma16816(o[d], va[2 * d], va[2 * d + 1], vb[2 * d], vb[2 * d + 1], p & lomask, p & ~lomask);
                    stsm4t((orow ^ ((u >> 1) << 6)) + pn * 8192 + (u & 1) * 1024, pack2(o[0][0], o[0][1]), pack2(o[0][2], o[0][3]), pack2(o[1][0], o[1][1]), pack2(o[1][2], o[1][3]));
                }
                fence_async_smem();
                __syncwarp();
                if (lane == 0) mbar_arrive(BAR_SFULL(sb, wg * 2 + pn));
                if (pn == 0) { CS(5); block_end(sb, 0); prepare(1, big); CS(3); }
            }
            CS(6);
            if (tid == 32) TL(41);
            mbar_wait(BAR_FULL(sb, 32 % NSLOT + wg), (32 / NSLOT) & 1);
            load_slab(xp, sb + (32 % NSLOT + wg) * SLOT);
            bar_sync(1 + wg, 128);
            if (tid == 0) { TL(6); TC(106); }
            if (tid == 128) TL(44);
            CS(7);
        }
        } else {
        {
            float ag[88], au[88];
            mainloop32<true, LAG>(ag, au, sb, wg, tw, r, EV_LAG1, 48, [&] {
                stg.acquire2(sb, wg);
                Ring q = r; if (!wg) q.next();
                mbar_wait(BAR_EMPTY(sb, q.slot), q.par ^ 1);
            });
            if (tid == 0) { TL(10); TC(110); }
            if (tid == 128) TL(51);
            CS(22);
            glu<11>(sb, wg, [&](int i) { return ag[i]; }, [&](int i) { return au[i]; },
                    [&](int pn) { return pn < 2 ? sb + OFF_STG + wg * 16384 + pn * 8192 : sb + (wg ? P3_SLOT1 : P3_SLOT0) * SLOT + 24576; });
            if (tid == 0) { TL(11); TC(111); }
            if (tid == 128) TL(52);
            CS(23);
        }
        passes128<2>(sb, wg, tw, r, stg);
        if (tid == 0) { TL(12); TC(112); }
        }
        {
            float acc[64], gf[32];
            mainloop64(acc, blk == 0, sb, wg, tw, r, [&] {
                mbar_wait(BAR_ONE(sb, EV_GA + blk), 0);
                unpack_slab(xs, xp);
                uint32_t gt[16];
#pragma unroll
                for (int cg = 0; cg < 16; ++cg) gt[cg] = lds32(sb + OFF_TAB + blk * 256 + cg * 16 + (tw & 3) * 4);
#pragma unroll
                for (int i = 0; i < 16; ++i) unpack2(gt[i], gf[2 * i], gf[2 * i + 1]);
            }, [&] { stg.acquire2(sb, wg); });
            if (tid == 0) { TL(blk ? 13 : 7); TC(blk ? 113 : 107); }
            if (tid == 128) TL(blk ? 57 : 42);
            CS(blk ? 30 : 10);
#pragma unroll
            for (int e = 0; e < 64; ++e) xs[e] = fmaf(gf[(e >> 2) * 2 + (e & 1)], acc[e], xs[e]);
        }
        if (blk) break;
        }
        {
            IDX();
#pragma unroll
            for (int p = 0; p < 2; ++p) {
                store_slab(xs, sb + OFF_STG + wg * 16384, 8192, pan_addr, 4 * p, 4 * p + 4);
                stg.publish(sb, wg, lane);
            }
            cluster_arrive();
            if (tid == 0) TL(14);
            CS(31);
        }
      }
    } else {
        if (warp == 8 && !aux && elect_one()) {
#pragma unroll
            for (int i = 0; i < 4; ++i) mbar_init(BAR_SREADY(sb, i), 1);
#pragma unroll
            for (int i = 0; i < 4; ++i) mbar_init(BAR_ONE(sb, EV_WIN + i), 1);
#pragma unroll
            for (int i = 0; i < 4; ++i) {
                mbar_expect_tx(BAR_SREADY(sb, i), 8192);
                tma_load3(sb + OFF_STG + i * 8192, &mp.x, j * 128 + (i & 1) * 64, m * 64 + (i >> 1) * 32, BAR_SREADY(sb, i));
            }
#pragma unroll 1
            for (int i = 0; i < 4; ++i) {
                mbar_expect_tx(BAR_ONE(sb, EV_WIN + i), 8192);
                tma_load(sb + 5 * SLOT + i * 8192, &mp.wm8, 2 * i * 6144 + (m * 8 + j) * 16, 0, BAR_ONE(sb, EV_WIN + i));
                tma_load(sb + 5 * SLOT + i * 8192 + 4096, &mp.wm8, (2 * i + 1) * 6144 + (m * 8 + j) * 16, 0, BAR_ONE(sb, EV_WIN + i));
            }
        }
        __syncwarp();
        asm volatile("setmaxnreg.dec.sync.aligned.u32 56;");
        if (elect_one()) {
            if (warp == 8) {
                prefetch_map(&mp.wqkv); prefetch_map(&mp.wmod);
            } else if (warp < 11) {
                mbar_init(BAR_EMPTY(sb, NSLOT), 1);
#pragma unroll
                for (int i = 0; i < 2; ++i) { mbar_init(BAR_SFULL(sb, (warp - 9) * 2 + i), 4); if (aux) mbar_init(BAR_SREADY(sb, (warp - 9) * 2 + i), 1); }
#pragma unroll
                for (int i = 0; i < 3; ++i) {
                    mbar_init(BAR_EMPTY(sb, (warp - 9) * 3 + i), 4);
                    mbar_init(BAR_FULL(sb, (warp - 9) * 3 + i), 1); mbar_init(BAR_FULL(sb, (warp - 9) * 3 + i) + AF_REL, 1);
                }
            } else {
#pragma unroll
                for (int i = EV_P0; i < EV_COUNT; ++i) mbar_init(BAR_ONE(sb, i), i == EV_P0 ? 8 : 1);
            }
            asm volatile("fence.mbarrier_init.release.cluster;" ::: "memory");
        }
        __syncwarp();
        cluster_arrive();
        ep = 0;
        if (warp != 8 || aux) ep = flag_get(g_flags + FL_DONE);
        cluster_wait();
        ep = __shfl_sync(0xffffffffu, ep, 0) / NCTA + 1;
        if (warp == 8) {
            const bool el = elect_one();
            Ring r{0, 1};
            if (aux) {
                {
                    uint32_t n = 0;
                    while (!__all_sync(0xffffffffu, ld_pkt16(pt.mail->mod1 + 256).z == ep)) { SPIN_GUARD(n); __nanosleep(200); }
                }
#pragma unroll 1
                for (int it = 0; it < 64; ++it) {
                    const int col = 2048 + (it >> 4) * 1024 + j * 256;
                    mbar_wait(BAR_EMPTY(sb, r.slot), r.par);
                    const uint32_t st = sb + r.slot * SLOT, fb = BAR_FULL(sb, r.slot);
                    if (el) {
                        mbar_expect_tx(fb, 32768);
#pragma unroll
                        for (int b = 0; b < 4; ++b) tma_load(st + b * 8192, &mp.wmod, col + b * 64, (it & 15) * 64, fb);
                    }
                    r.next();
                }
                mbar_wait(BAR_ONE(sb, EV_P0), 0);
                const CUtensorMap* wm = rank ? &mp.wu : &mp.wg;
#pragma unroll 1
                for (int g = 0; g < 128; ++g) {
                    const int mx = (j >> 1) * 8 + (g >> 5) * 2 + rank, k0 = ((g & 14) << 6) + ((g & 16) << 2) + ((g & 1) << 5);
                    if (!(g & 15)) {
                        uint32_t n = 0;
                        while (!__all_sync(0xffffffffu, (int32_t)(flag_get(g_flags + FL_PROG + fidx(mx, lane >> 4, (lane & 14) | ((g >> 4) & 1))) - (ep * 8 + ST_H2)) >= 0)) { SPIN_GUARD(n); __nanosleep(300); }
                    }
                    mbar_wait(BAR_EMPTY(sb, r.slot), r.par);
                    const uint32_t st = sb + r.slot * SLOT, fb = BAR_FULL(sb, r.slot);
                    if (el) {
                        mbar_expect_tx(fb, 24576);
                        tma_load_mc(st + 8192 + rank * 4096, wm, HC3, k0, fb);
                        tma_load_mc(st + 16384 + rank * 4096, wm, HC3 + 64, k0, fb);
                        tma_load(st, &mp.h2l, k0, mx * 128, fb);
                    }
                    r.next();
                }
            } else {
#pragma unroll 1
                for (int it = 0; it < 32; ++it) {
                    const int cb = j * 128 + rank * 64, k0 = kof(it, 2, j);
                    if (it == BW0) mbar_wait(BAR_ONE(sb, BWEV), 0);
                    if (it == BW1) mbar_wait(BAR_ONE(sb, EV_PAR), 0);
                    if (it == 5) mbar_wait(BAR_ONE(sb, EV_P0), 0);
                    if (it == AG0) mbar_wait(BAR_ONE(sb, (AGW & 1) ? EV_AGO : EV_FGO), 0);
                    mbar_wait(BAR_EMPTY(sb, r.slot), r.par);
                    const uint32_t st = sb + r.slot * SLOT, fb = BAR_FULL(sb, r.slot);
                    if (el) {
                        mbar_expect_tx(fb, it < 4 ? 24576 : 28672);
                        tma_load_mc(st + 24576 - rank * 16384, &mp.wqkv, 1024 + cb, k0, fb);
                        tma_load_mc(st + 28672 - rank * 16384, &mp.wqkv, 2048 + cb, k0, fb);
                        tma_load_mc(st + 16384 + rank * 4096, &mp.wqkv, cb, k0, fb);
                        if (it < 4) mbar_arrive(fb + AF_REL);
                        if (it == PFWO + (m >> 1)) { tma_prefetch(&mp.wo, j * 128, m * 64); tma_prefetch(&mp.wo, j * 128 + 64, m * 64); }
                        if (it >= PFG && it < PFG + PFN && (it & 7) == grp) {
                            const int kp = kof(it - PFG + PFO, 2, j);
                            tma_prefetch(rank ? &mp.wu : &mp.wg, hcol(0, j), kp); tma_prefetch(rank ? &mp.wu : &mp.wg, hcol(0, j) + 64, kp);
                            asm volatile("cp.async.bulk.prefetch.tensor.3d.L2.global [%0, {%1, %2, %3}];" :: "l"(rank ? &mp.wu3 : &mp.wg3), "r"(0), "r"(j), "r"(kp) : "memory");
                        }
                    }
                    r.next();
                }
                if (el) mbar_arrive(BAR_ONE(sb, EV_KV));
#pragma unroll 1
                for (int it = 0; it < 16; ++it) {
                    const int k0 = kof(it, 1, j);
                    if (it == AG1) mbar_wait(BAR_ONE(sb, (AGW & 2) ? EV_AGO1 : EV_FGO1), 0);
                    mbar_wait(BAR_EMPTY(sb, r.slot), r.par);
                    const uint32_t st = sb + r.slot * SLOT, fb = BAR_FULL(sb, r.slot);
                    if (el) {
                        mbar_expect_tx(fb, it < 2 ? 32768 : 24576);
                        tma_load_mc(st + 16384 + rank * 8192, &mp.wo, j * 128 + rank * 64, k0, fb);
                        if (it < 2) {
                            tma_load3(st, &mp.x, j * 128, m * 64 + it * 32, fb); tma_load3(st + 8192, &mp.x, j * 128 + 64, m * 64 + it * 32, fb);
                            mbar_arrive(fb + AF_REL);
                        }
                        if (it == 6) { prefetch_map(rank ? &mp.wu : &mp.wg); prefetch_map(rank ? &mp.wu3 : &mp.wg3); }
                    }
                    r.next();
                }
                const CUtensorMap* wm = rank ? &mp.wu : &mp.wg;
#pragma unroll 1
                for (int g = 0; g < 96; ++g) {
                    if (g == AG2) mbar_wait(BAR_ONE(sb, (AGW & 4) ? EV_AGO2 : EV_FGO2), 0);
                    const int p = g >> 5, cb = hcol(p, j), k0 = p == 0 ? kof(g, 2, j) : (g & 31) * 32;
                    mbar_wait(BAR_EMPTY(sb, r.slot), r.par);
                    const uint32_t st = sb + r.slot * SLOT, fb = BAR_FULL(sb, r.slot);
                    if (el) {
                        mbar_expect_tx(fb, (g < 4 || p > 0) ? 24576 : 28672);
                        tma_load_mc(st + 8192 + rank * 4096, wm, cb, k0, fb);
                        tma_load_mc(st + 16384 + rank * 4096, wm, cb + 64, k0, fb);
                        if (p == 0) tma_load3_mc(st + 24576 + rank * 4096, rank ? &mp.wu3 : &mp.wg3, j, k0, fb);
                        else tma_load(st, &mp.h2l, k0, m * 128, fb);
                        if (g < 4) mbar_arrive(fb + AF_REL);
                        if (g == 60) prefetch_map(&mp.wd);
                    }
                    r.next();
                }
#pragma unroll 1
                for (int g = 0; g < 56; ++g) {
                    if (g == 0 || (g & 15) == 6 && g > 6) mbar_wait(BAR_ONE(sb, EV_H0 + (g >> 4)), 0);
                    const int k0 = g * 64;
                    mbar_wait(BAR_EMPTY(sb, r.slot), r.par);
                    const uint32_t st = sb + r.slot * SLOT, fb = BAR_FULL(sb, r.slot);
                    if (el) {
                        mbar_expect_tx(fb, 32768);
                        tma_load_mc(st + 16384 + rank * 8192, &mp.wd, j * 128 + rank * 64, k0, fb);
                        tma_load(st, &mp.hb, k0, m * 128, fb); tma_load(st + 8192, &mp.hb, k0, m * 128 + 64, fb);
                    }
                    r.next();
                }
            }
        } else if (aux) {
            if (warp < 11) {
                const uint32_t w = warp - 9;
                const bool el = elect_one();
#pragma unroll 1
                for (int p = 0; p < 4; ++p) {
                    const int mx = (j >> 1) * 8 + p * 2 + rank;
                    if (el) { mbar_arrive(BAR_SREADY(sb, w * 2)); mbar_arrive(BAR_SREADY(sb, w * 2 + 1)); }
                    mbar_wait2(BAR_SFULL(sb, w * 2), BAR_SFULL(sb, w * 2 + 1), p & 1);
                    if (p < 3) pause(HD0);
                    if (el) tma_store(&mp.hb, HC3, mx * 128 + w * 64, sb + OFF_STG + w * 16384);
                    if (p < 3) pause(HP);
                    if (el) {
                        tma_store(&mp.hb, HC3 + 64, mx * 128 + w * 64, sb + OFF_STG + w * 16384 + 8192);
                        bulk_commit(); bulk_wait_fence(); flag_set(g_flags + FL_AUX + mx * 2 + w, ep * 8 + ST_H + 3);
                    }
                }
            }
        } else if (warp == 11) {
            const bool el = elect_one();
            const int row0 = m * 128;
            const uint32_t* const fl = g_flags + FL_PROG + fidx(m, lane >> 4, kof(lane & 15, 1, j) >> 6);
            if (el) { prefetch_map(&mp.h1h); prefetch_map(&mp.h2h); prefetch_map(&mp.h2l); }
            auto gate = [&](int vec, int ev) {
                uint4 v; uint32_t n = 0;
                while (true) {
                    v = ld_pkt2(g_mod + vec * 512 + j * 64 + lane * 2);
                    if (__all_sync(0xffffffffu, v.y == ep && v.w == ep)) break;
                    SPIN_GUARD(n); __nanosleep(300);
                }
                asm volatile("st.shared.v2.u32 [%0], {%1, %2};" :: "r"(sb + OFF_TAB + (ev - EV_GA) * 256 + lane * 8), "r"(v.x), "r"(v.z) : "memory");
                __syncwarp();
                if (lane == 0) mbar_arrive(BAR_ONE(sb, ev));
            };
            {
                const uint4* pk = pt.mail->mod1 + grp * 512 + j * 32 + lane;
                uint4 a, b; uint32_t n = 0;
                mbar_wait(BAR_ONE(sb, EV_WIN3), 0);
                while (true) {
                    a = ld_pkt16(pk); b = ld_pkt16(pk + 256);
                    if (__all_sync(0xffffffffu, a.z == ep && b.z == ep)) break;
                    SPIN_GUARD(n);
                }
                sts128(sb + OFF_PAR + lane * 16, a.x, a.y, b.x, b.y);
                __syncwarp();
                if (lane == 0) { mbar_arrive(BAR_ONE(sb, EV_PAR)); TL(46); }
            }
            mbar_wait(BAR_ONE(sb, EV_P0), 0);
            Ring r{0, 1};
#pragma unroll 1
            for (int ph = 0; ph < 3; ++ph) {
                const int sh = ph == 1 ? 1 : 2, nst = 8 << sh;
                const uint32_t half = 16384 >> sh, target = ep * 8 + ST_H1 + ph;
                const CUtensorMap* tm = ph == 0 ? &mp.h1h : ph == 1 ? &mp.o : &mp.h2h;
                if (ph == 1) {
                    gate(2, EV_GA);
                    mbar_wait(BAR_SREADY(sb, 1), 1);
#pragma unroll 1
                    for (int i = 0; i < 2; ++i)
                        fetch_halo<1>(g_halo + ((m - 1) * 8 + j) * 512 + i * 256 + 128 + lane, m == 0, sb + OFF_STG + 8192 + i * 4096 + lane * 16,
                                      [&] { __syncwarp(); if (el) mbar_arrive(BAR_ONE(sb, EV_TAIL + 2 * i)); });
                    CS(32);
                }
                if (ph == 2) {
                    uint32_t n = 0;
                    while ((int32_t)(flag_get(g_flags + FL_LN2) - ep * 8) < 0) { SPIN_GUARD(n); __nanosleep(200); }
                    const uint4 v = __ldcg((const uint4*)(g_par2 + j * 128) + lane);
                    sts128(sb + OFF_PAR + lane * 16, v.x, v.y, v.z, v.w);
                    __syncwarp();
                    if (lane == 0) mbar_arrive(BAR_ONE(sb, EV_LN2));
                }
                const uint32_t lw = ~lane & 1, lt = lane >> 1, ls = (r.slot + lt) % NSLOT, lk = kof(lt, sh, j), lb = BAR_FULL(sb, ls) + (lw ? 0 : AF_REL);
                const uint32_t* const lf = g_flags + FL_PROG + fidx(m, lw, lk >> 6);
                int fr = 1 << sh;
                uint32_t todo = 0x3ffffu >> (2 * fr) << (2 * fr), have = ~todo, n = 0, v = 0;
                r.skip(fr);
#pragma unroll 1
                for (; fr < NSLOT; ++fr) { mbar_wait(BAR_EMPTY(sb, r.slot), r.par); r.next(); }
                if (ph == XST - 1) CS(33);
                do {
                    if (!((have >> lane) & 1)) v = flag_get(lf);
                    while (fr < 9 && mbar_test(BAR_EMPTY(sb, r.slot), r.par)) { ++fr; r.next(); }
                    SPIN_GUARD(n);
                    have |= __ballot_sync(0xffffffffu, (int32_t)(v - target) >= 0);
                    const uint32_t go = have & todo & ((1u << (2 * fr)) - 1);
                    if ((go >> lane) & 1) {
                        if (!lw) mbar_expect_tx(lb, half);
                        tma_load(sb + ls * SLOT + lw * half, tm, lk, row0 + lw * 64, lb);
                    }
                    __syncwarp();
                    if (lane < 2 && (todo & (0x555u << lane)) && !(todo & ~go & (0x555u << lane))) mbar_arrive(BAR_ONE(sb, (lane ? EV_FGO : EV_AGO) + ph));
                    if (ph == XST - 1) { if (go & (1u << (2 << sh))) CS(34); if (go & (2u << (2 << sh))) CS(35); if (todo & 0x555u) CS(36); if (todo & 0xaaau) CS(37); }
                    todo &= ~go;
                } while (~have);
                if (ph == XST - 1) CS(38);
                int k = kof(fr, sh, j);
#pragma unroll 1
                for (; fr < nst; ++fr) {
                    if (fr == 9 || fr == 18) {
                        const uint32_t skip = fr == 9 << (sh - 1) ? 0 : ~0x01fc01fcu;
                        while (~(__ballot_sync(0xffffffffu, (int32_t)(flag_get(fl) - target) >= 0) | skip)) SPIN_GUARD(n);
                    }
                    const uint32_t st = sb + r.slot * SLOT, fb = BAR_FULL(sb, r.slot);
                    mbar_wait(BAR_EMPTY(sb, r.slot), r.par);
                    if (el) {
                        tma_load(st + half, tm, k, row0 + 64, fb);
                        mbar_expect_tx(fb + AF_REL, half);
                        tma_load(st, tm, k, row0, fb + AF_REL);
                    }
                    if (ph == XST - 1 && fr == 9) CS(39);
                    r.next();
                    k = kof(fr + 1, sh, j);
                }
            }
#pragma unroll 1
            for (int p = 0; p < 4; ++p) {
                const uint32_t* f = p < 3 ? fl : g_flags + FL_AUX + m * 2 + (lane & 1);
                uint32_t n = 0;
                while (!__all_sync(0xffffffffu, (int32_t)(flag_get(f) - (ep * 8 + ST_H + p)) >= 0)) { SPIN_GUARD(n); __nanosleep(300); }
                if (el) mbar_arrive(BAR_ONE(sb, EV_H0 + p));
                if (p == 0) gate(5, EV_GB);
            }
        } else {
            const uint32_t w = warp - 9;
            const int row0 = m * 128 + w * 64;
            const uint32_t stg = sb + OFF_STG + w * 16384;
            uint32_t* const fl = g_flags + FL_PROG + fidx(m, w, 2 * j);
            uint32_t b = 0, par = 0;
            const bool el = elect_one();
            auto store = [&](const CUtensorMap* tm, int col, bool nat = false) {
                mbar_wait(BAR_SFULL(sb, w * 2 + b), (par >> b) & 1);
                par ^= 1u << b;
                if (el) {
                    if (nat) tma_store3(tm, col, row0 >> 1, 0, stg + b * 8192); else tma_store(tm, col, row0, stg + b * 8192);
                    bulk_commit();
                }
                b ^= 1;
            };
            auto send2 = [&](const CUtensorMap* tm, const uint32_t* buf, int step) {
                const uint32_t* const q = buf + (size_t)((row0 + lane) * (D_ / 2) + j * 64 + 31);
                store(tm, j * 128);
                if (step == XST) CS(33);
                uint32_t z = landed(el, q, D_ / 2, pt.zero);
                if (el) flag_set(fl, ep * 8 + step + z);
                if (step == XST) CS(34);
                if (step != ST_O) { mbar_wait(BAR_ONE(sb, EV_FGO + step - ST_H1), 0); pause(step == ST_H1 ? (w ? P1H : P1H + 1000) : w ? P2L : P2F); }
                store(tm, j * 128 + 64);
                if (step == XST) CS(35);
                z = landed(el, q + 32, D_ / 2, pt.zero);
                if (el) flag_set(fl + 1, ep * 8 + step + z);
                if (step == XST) CS(36);
            };
            auto free2 = [&]() { if (el) { mbar_arrive(BAR_SREADY(sb, w * 2)); mbar_arrive(BAR_SREADY(sb, w * 2 + 1)); } };
            if (el) { prefetch_map(&mp.h1s); prefetch_map(&mp.o); prefetch_map(&mp.h2s); prefetch_map(&mp.hb); prefetch_map(&mp.out); prefetch_map(&mp.wo); }
            if (el) { flag_set(fl, ep * 8); flag_set(fl + 1, ep * 8); }
            send2(&mp.h1s, pt.h1, ST_H1);
            if (w == 0) TL(47);
            free2();
            mbar_wait(BAR_ONE(sb, EV_KV), 0);
            mbar_wait(BAR_SREADY(sb, 0), 1);
            fetch_halo<1>(g_halo + ((m - 1) * 8 + j) * 512 + w * 256 + lane, m == 0, sb + OFF_STG + w * 4096 + lane * 16, [&] { bar_arrive(NB_TAIL + 2 * w, 64); CS(38); });
            send2(&mp.o, pt.o, ST_O);
            if (w == 0) TL(40); else TL(38);
            free2();
            send2(&mp.h2s, pt.o, ST_H2);
            if (el) { prefetch_map(&mp.hb); prefetch_map(&mp.hb3); }
            if (w == 0) TL(37);
            free2();
#pragma unroll 1
            for (int p = 0; p < 3; ++p) {
                const int col = hcol(p, j);
                mbar_wait(BAR_SFULL(sb, w * 2), par & 1);
                pause(w ? HD1 : HD0); store(&mp.hb, col);
                pause(HP); store(&mp.hb, col + 64);
                if (p == 0) {
                    pause(HP);
                    if (el) { tma_store3(&mp.hb3, 0, j, row0, sb + (w ? P3_SLOT1 : P3_SLOT0) * SLOT + 24576); bulk_commit(); }
                }
                if (el) bulk_wait_read();
                free2();
                if (el) { bulk_wait_fence(); flag_set(fl, ep * 8 + ST_H + p); flag_set(fl + 1, ep * 8 + ST_H + p); }
            }
            cluster_arrive_early = true;
            cluster_arrive();
            store(&mp.out, j * 128, true); store(&mp.out, j * 128 + 64, true);
            if (el) bulk_wait_read();
        }
        __syncwarp();
    }
    if (aux || (wg == 2 && !cluster_arrive_early)) cluster_arrive();
    cluster_wait();
    if (KDEBUG == 5) __syncthreads();
    if (tid == 0) {
        TL(15);
        flag_add(pt.mail->flags + FL_DONE);
    }
}

typedef CUresult (*EncodeFn)(CUtensorMap*, CUtensorMapDataType, cuuint32_t, void*, const cuuint64_t*, const cuuint64_t*, const cuuint32_t*,
                             const cuuint32_t*, CUtensorMapInterleave, CUtensorMapSwizzle, CUtensorMapL2promotion, CUtensorMapFloatOOBfill);

void make_map(EncodeFn fn, CUtensorMap* m, const void* ptr, uint64_t rows, uint64_t cols, uint32_t brows, uint32_t bcols) {
    cuuint64_t dims[2] = {cols, rows}, strides[1] = {cols * 2};
    cuuint32_t box[2] = {bcols, brows}, es[2] = {1, 1};
    fn(m, CU_TENSOR_MAP_DATA_TYPE_BFLOAT16, 2, (void*)ptr, dims, strides, box, es, CU_TENSOR_MAP_INTERLEAVE_NONE,
       bcols == 64 ? CU_TENSOR_MAP_SWIZZLE_128B : bcols == 32 ? CU_TENSOR_MAP_SWIZZLE_64B : CU_TENSOR_MAP_SWIZZLE_NONE, CU_TENSOR_MAP_L2_PROMOTION_L2_256B, CU_TENSOR_MAP_FLOAT_OOB_FILL_NONE);
}

void make_map3(EncodeFn fn, CUtensorMap* m, const void* ptr) {
    cuuint64_t dims[3] = {D_, S_ / 2, 2}, strides[2] = {4 * D_, 2 * D_};
    cuuint32_t box[3] = {64, 32, 2}, es[3] = {1, 1, 1};
    fn(m, CU_TENSOR_MAP_DATA_TYPE_BFLOAT16, 3, (void*)ptr, dims, strides, box, es, CU_TENSOR_MAP_INTERLEAVE_NONE,
       CU_TENSOR_MAP_SWIZZLE_128B, CU_TENSOR_MAP_L2_PROMOTION_L2_256B, CU_TENSOR_MAP_FLOAT_OOB_FILL_NONE);
}

void make_map48(EncodeFn fn, CUtensorMap* m, const void* ptr, uint64_t rows, uint32_t brows) {
    cuuint64_t dims[3] = {48, 8, rows}, strides[2] = {96, 2 * F_};
    cuuint32_t box[3] = {64, 1, brows}, es[3] = {1, 1, 1};
    fn(m, CU_TENSOR_MAP_DATA_TYPE_BFLOAT16, 3, (void*)ptr, dims, strides, box, es, CU_TENSOR_MAP_INTERLEAVE_NONE,
       CU_TENSOR_MAP_SWIZZLE_128B, CU_TENSOR_MAP_L2_PROMOTION_L2_256B, CU_TENSOR_MAP_FLOAT_OOB_FILL_NONE);
}

}

extern "C" void kernel_launch(void* const* d_in, const int* in_sizes, int n_in, void* d_out, int out_size) {
    (void)in_sizes; (void)n_in; (void)out_size;
    void* fnp = nullptr;
    cudaDriverEntryPointQueryResult qr;
    cudaGetDriverEntryPoint("cuTensorMapEncodeTiled", &fnp, cudaEnableDefault, &qr);
    EncodeFn fn = (EncodeFn)fnp;
    void *h1, *o, *h2, *hb, *mail;
    cudaGetSymbolAddress(&h1, g_h1);
    cudaGetSymbolAddress(&mail, g_mail);
    cudaGetSymbolAddress(&o, g_o);
    cudaGetSymbolAddress(&hb, g_hb);
    h2 = o;
    Maps mp;
    make_map(fn, &mp.h1h, h1, S_, D_, 64, 32);
    make_map(fn, &mp.h2h, h2, S_, D_, 64, 32);
    make_map(fn, &mp.h1s, h1, S_, D_, 64, 64);
    make_map(fn, &mp.o, o, S_, D_, 64, 64);
    make_map(fn, &mp.h2l, h2, S_, D_, 128, 32);
    make_map(fn, &mp.h2s, h2, S_, D_, 64, 64);
    make_map(fn, &mp.hb, hb, S_, F_, 64, 64);
    make_map(fn, &mp.wqkv, d_in[1], D_, 3 * D_, 32, 64);
    make_map(fn, &mp.wo, d_in[2], D_, D_, 64, 64);
    make_map(fn, &mp.wg, d_in[4], D_, F_, 32, 64);
    make_map(fn, &mp.wu, d_in[5], D_, F_, 32, 64);
    make_map(fn, &mp.wd, d_in[6], F_, D_, 64, 64);
    make_map(fn, &mp.wmod, d_in[8], D_, 6 * D_, 64, 64);
    make_map(fn, &mp.wm8, d_in[8], D_ / 8, 8 * 6 * D_, 128, 16);
    make_map3(fn, &mp.x, d_in[0]);
    make_map3(fn, &mp.out, d_out);
    make_map48(fn, &mp.wg3, d_in[4], D_, 32);
    make_map48(fn, &mp.wu3, d_in[5], D_, 32);
    make_map48(fn, &mp.hb3, hb, S_, 64);
    cudaFuncSetAttribute(fused_block_kernel, cudaFuncAttributeMaxDynamicSharedMemorySize, SMEM_BYTES);
    cudaLaunchConfig_t cfg = {};
    cfg.gridDim = dim3(NCTA); cfg.blockDim = dim3(384); cfg.dynamicSmemBytes = SMEM_BYTES; cfg.stream = cudaStreamPerThread;
    cudaLaunchAttribute at[1];
    at[0].id = cudaLaunchAttributeClusterDimension; at[0].val.clusterDim.x = 2; at[0].val.clusterDim.y = 1; at[0].val.clusterDim.z = 1;
    cfg.attrs = at; cfg.numAttrs = 1;
    const Ptrs pt{(const __nv_bfloat16*)d_in[7], (Mail*)mail, (const uint32_t*)h1, (const uint32_t*)o, 0};
    cudaLaunchKernelEx(&cfg, fused_block_kernel, pt, mp);
}
```

```cpp
#include <cuda_runtime.h>
#include <cuda_bf16.h>
#include <cuda.h>
#include <stdint.h>
#include <stddef.h>

#define LAG 4
#define LAGS 4
#define LAGW 3
#define LAGQ 4
#define PFWO 12
#define P1H 3000
#define AGW 6
#define CSW 0
#define LWAIT 2
#define BW0 0
#define BWEV EV_WIN
#define BW1 3
#define PDLY 500
#define HD1 3600
#define HD0 1200
#define HP 2200
#define LAGD 4
#define MIDD 30
#define XST ST_O
#define AG0 6
#define AG1 6
#define AG2 8
#define PFG 8
#define PFN 24
#define PFO 0
#define P2L 2000
#define P2F 3000
#define PUT1 5
#define PUT0 10
#define PUTD1 5
#define PUTD0 10
#define KDEBUG 0

namespace {

constexpr int S_ = 2048, D_ = 1024, F_ = 3584;
constexpr int NCTA = 132;
constexpr int NSLOT = 6;
constexpr uint32_t SLOT = 32768;
constexpr uint32_t OFF_STG = NSLOT * SLOT;
constexpr uint32_t OFF_BAR = OFF_STG + 32768;
constexpr uint32_t OFF_PAR = OFF_BAR + 512;
constexpr uint32_t OFF_TAB = OFF_PAR + 768;
constexpr uint32_t OFF_TL = OFF_PAR + 2048;
constexpr uint32_t SMEM_BYTES = OFF_TL + (KDEBUG ? 512 : 0);
constexpr uint32_t P3_SLOT1 = (32 + 16 + 32) % NSLOT, P3_SLOT0 = (P3_SLOT1 + 1) % NSLOT;

constexpr int ST_H1 = 1, ST_O = 2, ST_H2 = 3, ST_H = 4, FL_DONE = 0, FL_LN2 = 1, FL_AUX = 32, FL_PROG = 64;

struct Maps {
    CUtensorMap h1h, h1s, o, h2h, h2l, h2s, hb, wqkv, wo, wg, wu, wd, wmod, wm8, x, out, wg3, wu3, hb3;
};

struct Mail {
    uint32_t flags[16 * 32 + 64];
    uint2 mod[6 * D_ / 2];
    uint4 mod1[8 * 512];
    uint4 st1[128 * 512];
    uint32_t par2[D_];
    uint4 halo[128 * 512];
};
struct Ptrs { const __nv_bfloat16* c; Mail* mail; const uint32_t *h1, *o; uint32_t zero; };

__device__ __align__(128) Mail g_mail;
__device__ __align__(128) __nv_bfloat16 g_h1[S_ * D_];
__device__ __align__(128) __nv_bfloat16 g_o[S_ * D_];
__device__ __align__(128) __nv_bfloat16 g_hb[S_ * F_];
#define TL(i) do {} while (0)
#define TC(i) do {} while (0)
#define TS(g, which) do {} while (0)
#define CS(i) do {} while (0)

__device__ __forceinline__ uint32_t smem_u32(const void* p) { return (uint32_t)__cvta_generic_to_shared(p); }
__device__ __forceinline__ void mbar_init(uint32_t bar, uint32_t cnt) { asm volatile("mbarrier.init.shared::cta.b64 [%0], %1;" :: "r"(bar), "r"(cnt) : "memory"); }
__device__ __forceinline__ void mbar_expect_tx(uint32_t bar, uint32_t bytes) { asm volatile("mbarrier.arrive.expect_tx.shared::cta.b64 _, [%0], %1;" :: "r"(bar), "r"(bytes) : "memory"); }
__device__ __forceinline__ void mbar_arrive(uint32_t bar) { asm volatile("mbarrier.arrive.shared::cta.b64 _, [%0];" :: "r"(bar) : "memory"); }
__device__ __forceinline__ void mbar_arrive_cta(uint32_t bar, uint32_t cta) {
    asm volatile("{\n.reg .b32 r;\nmapa.shared::cluster.u32 r, %0, %1;\nmbarrier.arrive.shared::cluster.b64 _, [r];\n}" :: "r"(bar), "r"(cta) : "memory");
}
__device__ __forceinline__ void mbar_wait(uint32_t bar, uint32_t parity) {
    asm volatile("{\n.reg .pred p;\n.reg .u32 n;\nmov.u32 n, 0;\n"
        "W_LOOP:\nmbarrier.try_wait.parity.shared::cta.b64 p, [%0], %1;\n@p bra W_DONE;\n"
        "add.u32 n, n, 1;\nsetp.lt.u32 p, n, 0x400000;\n@p bra W_LOOP;\ntrap;\nW_DONE:\n}" :: "r"(bar), "r"(parity) : "memory");
}
__device__ __forceinline__ void mbar_wait2(uint32_t b0, uint32_t b1, uint32_t parity) {
    asm volatile("{\n.reg .pred p, q;\n.reg .u32 n;\nmov.u32 n, 0;\n"
        "W_LOOP:\nmbarrier.try_wait.parity.shared::cta.b64 p, [%0], %2;\nmbarrier.try_wait.parity.shared::cta.b64 q, [%1], %2;\nand.pred p, p, q;\n@p bra W_DONE;\n"
        "add.u32 n, n, 1;\nsetp.lt.u32 p, n, 0x400000;\n@p bra W_LOOP;\ntrap;\nW_DONE:\n}" :: "r"(b0), "r"(b1), "r"(parity) : "memory");
}
__device__ __forceinline__ bool mbar_test(uint32_t bar, uint32_t parity) {
    uint32_t r; asm volatile("{\n.reg .pred p;\nmbarrier.test_wait.parity.shared::cta.b64 p, [%1], %2;\nselp.u32 %0, 1, 0, p;\n}" : "=r"(r) : "r"(bar), "r"(parity) : "memory"); return r;
}
__device__ __forceinline__ bool mbar_test2(uint32_t b0, uint32_t b1, uint32_t parity) {
    uint32_t r;
    asm volatile("{\n.reg .pred p, q;\nmbarrier.test_wait.parity.shared::cta.b64 p, [%1], %3;\nmbarrier.test_wait.parity.shared::cta.b64 q, [%2], %3;\n"
        "and.pred p, p, q;\nselp.u32 %0, 1, 0, p;\n}" : "=r"(r) : "r"(b0), "r"(b1), "r"(parity) : "memory");
    return r;
}
__device__ __forceinline__ void tma_load3(uint32_t dst, const CUtensorMap* m, int c0, int c1, uint32_t bar) {
    asm volatile("cp.async.bulk.tensor.3d.shared::cluster.global.mbarrier::complete_tx::bytes [%0], [%1, {%3, %4, %5}], [%2];"
        :: "r"(dst), "l"(m), "r"(bar), "r"(c0), "r"(c1), "r"(0) : "memory");
}
__device__ __forceinline__ void tma_store3(const CUtensorMap* m, int c0, int c1, int c2, uint32_t src) {
    asm volatile("cp.async.bulk.tensor.3d.global.shared::cta.bulk_group [%0, {%2, %3, %4}], [%1];" :: "l"(m), "r"(src), "r"(c0), "r"(c1), "r"(c2) : "memory");
}
__device__ __forceinline__ void tma_load3_mc(uint32_t dst, const CUtensorMap* m, int c1, int c2, uint32_t bar) {
    asm volatile("cp.async.bulk.tensor.3d.shared::cluster.global.mbarrier::complete_tx::bytes.multicast::cluster.L2::cache_hint [%0], [%1, {%3, %4, %5}], [%2], %6, %7;"
        :: "r"(dst), "l"(m), "r"(bar), "r"(0), "r"(c1), "r"(c2), "h"((uint16_t)3), "l"(0x12F0000000000000ull) : "memory");
}
__device__ __forceinline__ void tma_load(uint32_t dst, const CUtensorMap* m, int c0, int c1, uint32_t bar) {
    asm volatile("cp.async.bulk.tensor.2d.shared::cluster.global.mbarrier::complete_tx::bytes [%0], [%1, {%3, %4}], [%2];"
        :: "r"(dst), "l"(m), "r"(bar), "r"(c0), "r"(c1) : "memory");
}
__device__ __forceinline__ void tma_load_mc(uint32_t dst, const CUtensorMap* m, int c0, int c1, uint32_t bar) {
    asm volatile("cp.async.bulk.tensor.2d.shared::cluster.global.mbarrier::complete_tx::bytes.multicast::cluster.L2::cache_hint [%0], [%1, {%3, %4}], [%2], %5, %6;"
        :: "r"(dst), "l"(m), "r"(bar), "r"(c0), "r"(c1), "h"((uint16_t)3), "l"(0x12F0000000000000ull) : "memory");
}
__device__ __forceinline__ void tma_prefetch(const CUtensorMap* m, int c0, int c1) {
    asm volatile("cp.async.bulk.prefetch.tensor.2d.L2.global [%0, {%1, %2}];" :: "l"(m), "r"(c0), "r"(c1) : "memory");
}
__device__ __forceinline__ void tma_store(const CUtensorMap* m, int c0, int c1, uint32_t src) {
    asm volatile("cp.async.bulk.tensor.2d.global.shared::cta.bulk_group [%0, {%2, %3}], [%1];" :: "l"(m), "r"(src), "r"(c0), "r"(c1) : "memory");
}
__device__ __forceinline__ void bulk_commit() { asm volatile("cp.async.bulk.commit_group;" ::: "memory"); }
__device__ __forceinline__ void bulk_wait_read() { asm volatile("cp.async.bulk.wait_group.read 0;" ::: "memory"); }
__device__ __forceinline__ void fence_async_smem() { asm volatile("fence.proxy.async.shared::cta;" ::: "memory"); }
__device__ __forceinline__ void prefetch_map(const CUtensorMap* m) { asm volatile("prefetch.tensormap [%0];" :: "l"(m) : "memory"); }
__device__ __forceinline__ void wg_fence() { asm volatile("wgmma.fence.sync.aligned;" ::: "memory"); }
__device__ __forceinline__ void wg_commit() { asm volatile("wgmma.commit_group.sync.aligned;" ::: "memory"); }
template <int N> __device__ __forceinline__ void wg_wait() { asm volatile("wgmma.wait_group.sync.aligned %0;" :: "n"(N) : "memory"); }
__device__ __forceinline__ void bar_sync(int id, int n) { asm volatile("bar.sync %0, %1;" :: "r"(id), "r"(n) : "memory"); }
__device__ __forceinline__ void bar_arrive(int id, int n) { asm volatile("bar.arrive %0, %1;" :: "r"(id), "r"(n) : "memory"); }
__device__ __forceinline__ void flag_add(uint32_t* f) { asm volatile("red.relaxed.gpu.global.add.u32 [%0], 1;" :: "l"(f) : "memory"); }
__device__ __forceinline__ void flag_set(uint32_t* f, uint32_t v) { asm volatile("red.relaxed.gpu.global.max.u32 [%0], %1;" :: "l"(f), "r"(v) : "memory"); }
__device__ __forceinline__ uint32_t flag_get(const uint32_t* f) { uint32_t v; asm volatile("ld.relaxed.gpu.global.u32 %0, [%1];" : "=r"(v) : "l"(f) : "memory"); return v; }
__device__ __forceinline__ void bulk_wait_fence() { asm volatile("cp.async.bulk.wait_group 0;\nfence.proxy.async.global;\nfence.acq_rel.gpu;" ::: "memory"); }
__device__ __forceinline__ uint32_t landed(bool el, const uint32_t* p, uint32_t pitch, uint32_t zero) {
    if (el) asm volatile("cp.async.bulk.wait_group 0;" ::: "memory");
    __syncwarp();
    const uint32_t a = flag_get(p), b = flag_get(p + 32 * pitch);
    return __reduce_or_sync(0xffffffffu, (a | b) & zero);
}
__device__ __forceinline__ uint32_t d16(uint32_t addr) { return (addr & 0x3FFFF) >> 4; }
__device__ __forceinline__ uint64_t mk_desc(uint32_t a16, uint32_t off, uint32_t lbo, uint32_t sbo, uint32_t swz) {
    const uint32_t lo = a16 + (off >> 4) + ((lbo >> 4) << 16), hi = (sbo >> 4) | (swz << 30);
    return ((uint64_t)hi << 32) | lo;
}
__device__ __forceinline__ uint32_t pack2(float lo, float hi) {
    uint32_t r; asm("cvt.rn.bf16x2.f32 %0, %1, %2;" : "=r"(r) : "f"(hi), "f"(lo)); return r;
}
__device__ __forceinline__ uint32_t hfma2_bf16(uint32_t a, uint32_t b, uint32_t c) {
    uint32_t r; asm("fma.rn.bf16x2 %0, %1, %2, %3;" : "=r"(r) : "r"(a), "r"(b), "r"(c)); return r;
}
__device__ __forceinline__ float bf_lo(uint32_t v) { return __uint_as_float(v << 16); }
__device__ __forceinline__ float bf_hi(uint32_t v) { return __uint_as_float(v & 0xFFFF0000u); }
__device__ __forceinline__ void unpack2(uint32_t v, float& lo, float& hi) {
    asm volatile("shl.b32 %0, %2, 16;\nand.b32 %1, %2, 0xffff0000;" : "=f"(lo), "=f"(hi) : "r"(v));
}
__device__ __forceinline__ float bf_round(float x) { return __bfloat162float(__float2bfloat16_rn(x)); }
__device__ __forceinline__ void stsm4(uint32_t addr, uint32_t r0, uint32_t r1, uint32_t r2, uint32_t r3) {
    asm volatile("stmatrix.sync.aligned.m8n8.x4.shared.b16 [%0], {%1, %2, %3, %4};" :: "r"(addr), "r"(r0), "r"(r1), "r"(r2), "r"(r3) : "memory");
}
__device__ __forceinline__ void stsm4t(uint32_t addr, uint32_t r0, uint32_t r1, uint32_t r2, uint32_t r3) {
    asm volatile("stmatrix.sync.aligned.m8n8.x4.trans.shared.b16 [%0], {%1, %2, %3, %4};" :: "r"(addr), "r"(r0), "r"(r1), "r"(r2), "r"(r3) : "memory");
}
__device__ __forceinline__ uint32_t movm(uint32_t a) { uint32_t d; asm volatile("movmatrix.sync.aligned.m8n8.trans.b16 %0, %1;" : "=r"(d) : "r"(a)); return d; }
__device__ __forceinline__ void ldsm4(uint32_t addr, uint32_t& r0, uint32_t& r1, uint32_t& r2, uint32_t& r3) {
    asm volatile("ldmatrix.sync.aligned.m8n8.x4.shared.b16 {%0, %1, %2, %3}, [%4];" : "=r"(r0), "=r"(r1), "=r"(r2), "=r"(r3) : "r"(addr) : "memory");
}
__device__ __forceinline__ void ldsm4t(uint32_t addr, uint32_t& r0, uint32_t& r1, uint32_t& r2, uint32_t& r3) {
    asm volatile("ldmatrix.sync.aligned.m8n8.x4.trans.shared.b16 {%0, %1, %2, %3}, [%4];" : "=r"(r0), "=r"(r1), "=r"(r2), "=r"(r3) : "r"(addr) : "memory");
}
__device__ __forceinline__ void mma16816(float (&c)[4], uint32_t a0, uint32_t a1, uint32_t a2, uint32_t a3, uint32_t b0, uint32_t b1) {
    asm("mma.sync.aligned.m16n8k16.row.col.f32.bf16.bf16.f32 {%0, %1, %2, %3}, {%4, %5, %6, %7}, {%8, %9}, {%0, %1, %2, %3};"
        : "+f"(c[0]), "+f"(c[1]), "+f"(c[2]), "+f"(c[3]) : "r"(a0), "r"(a1), "r"(a2), "r"(a3), "r"(b0), "r"(b1));
}
__device__ __forceinline__ float rcp(float x) { float r; asm("rcp.approx.ftz.f32 %0, %1;" : "=f"(r) : "f"(x)); return r; }
__device__ __forceinline__ float ex2(float x) { float r; asm("ex2.approx.ftz.f32 %0, %1;" : "=f"(r) : "f"(x)); return r; }
__device__ __forceinline__ float tanh_(float x) { float t; asm("tanh.approx.f32 %0, %1;" : "=f"(t) : "f"(x)); return t; }
__device__ __forceinline__ void block_end(uint32_t opaque, uint32_t id) { asm volatile("{\n.reg .pred p;\nsetp.eq.u32 p, %0, %1;\n@p trap;\n}" :: "r"(opaque), "r"(0xffffff00u + id)); }
__device__ __forceinline__ float silu_(float x) { return __fdividef(x, 1.f + __expf(-x)); }
__device__ __forceinline__ void st_pkt(void* p, uint32_t a, uint32_t b) {
    asm volatile("{\n.reg .b64 t;\nmov.b64 t, {%1, %2};\nst.relaxed.gpu.global.b64 [%0], t;\n}" :: "l"(p), "r"(a), "r"(b) : "memory");
}
__device__ __forceinline__ uint4 ld_pkt2(const void* p) {
    uint4 v; asm volatile("{\n.reg .b64 t, u;\nld.relaxed.gpu.global.v2.b64 {t, u}, [%4];\nmov.b64 {%0, %1}, t;\nmov.b64 {%2, %3}, u;\n}"
        : "=r"(v.x), "=r"(v.y), "=r"(v.z), "=r"(v.w) : "l"(p) : "memory"); return v;
}
__device__ __forceinline__ void st_pkt16(void* p, uint32_t a, uint32_t b, uint32_t c, uint32_t d) {
    asm volatile("{\n.reg .b64 t, u;\n.reg .b128 w;\nmov.b64 t, {%1, %2};\nmov.b64 u, {%3, %4};\nmov.b128 w, {t, u};\nst.relaxed.gpu.global.b128 [%0], w;\n}"
        :: "l"(p), "r"(a), "r"(b), "r"(c), "r"(d) : "memory");
}
__device__ __forceinline__ uint4 ld_pkt16(const void* p) {
    uint4 v; asm volatile("{\n.reg .b64 t, u;\n.reg .b128 w;\nld.relaxed.gpu.global.b128 w, [%4];\nmov.b128 {t, u}, w;\nmov.b64 {%0, %1}, t;\nmov.b64 {%2, %3}, u;\n}"
        : "=r"(v.x), "=r"(v.y), "=r"(v.z), "=r"(v.w) : "l"(p) : "memory"); return v;
}
#define SPIN_GUARD(n) do { if (++(n) > (1u << 22)) asm volatile("trap;"); } while (0)
__device__ __forceinline__ uint4 lds128(uint32_t a) { uint4 v; asm volatile("ld.shared.v4.u32 {%0, %1, %2, %3}, [%4];" : "=r"(v.x), "=r"(v.y), "=r"(v.z), "=r"(v.w) : "r"(a) : "memory"); return v; }
__device__ __forceinline__ void sts128(uint32_t a, uint32_t x, uint32_t y, uint32_t z, uint32_t w) { asm volatile("st.shared.v4.u32 [%0], {%1, %2, %3, %4};" :: "r"(a), "r"(x), "r"(y), "r"(z), "r"(w) : "memory"); }
__device__ __forceinline__ uint32_t lds32(uint32_t a) { uint32_t v; asm volatile("ld.shared.u32 %0, [%1];" : "=r"(v) : "r"(a) : "memory"); return v; }
__device__ __forceinline__ void sts32(uint32_t a, uint32_t v) { asm volatile("st.shared.u32 [%0], %1;" :: "r"(a), "r"(v) : "memory"); }
__device__ __forceinline__ bool elect_one() {
    uint32_t p; asm volatile("{\n.reg .pred q;\nelect.sync _|q, 0xffffffff;\nselp.u32 %0, 1, 0, q;\n}" : "=r"(p)); return p;
}
__device__ __forceinline__ void pause(uint32_t cycles) {
    uint32_t t0, t; asm volatile("mov.u32 %0, %%clock;" : "=r"(t0));
    do { __nanosleep(64); asm volatile("mov.u32 %0, %%clock;" : "=r"(t)); } while (t - t0 < cycles);
}
__device__ __forceinline__ void cluster_arrive() { asm volatile("barrier.cluster.arrive.relaxed.aligned;" ::: "memory"); }
__device__ __forceinline__ void cluster_wait() { asm volatile("barrier.cluster.wait.aligned;" ::: "memory"); }

__device__ __forceinline__ void wgmma_n128_z(float (&d)[64], uint64_t da, uint64_t db) {
    asm volatile("{\n.reg .pred p;\nsetp.ne.b32 p, 0, 0;\n"
        "wgmma.mma_async.sync.aligned.m64n128k16.f32.bf16.bf16 {"
        "%0, %1, %2, %3, %4, %5, %6, %7, %8, %9, %10, %11, %12, %13, %14, %15, "
        "%16, %17, %18, %19, %20, %21, %22, %23, %24, %25, %26, %27, %28, %29, %30, %31, "
        "%32, %33, %34, %35, %36, %37, %38, %39, %40, %41, %42, %43, %44, %45, %46, %47, "
        "%48, %49, %50, %51, %52, %53, %54, %55, %56, %57, %58, %59, %60, %61, %62, %63"
        "}, %64, %65, p, 1, 1, 0, 1;\n}\n"
        : "=f"(d[0]), "=f"(d[1]), "=f"(d[2]), "=f"(d[3]), "=f"(d[4]), "=f"(d[5]), "=f"(d[6]), "=f"(d[7]),
          "=f"(d[8]), "=f"(d[9]), "=f"(d[10]), "=f"(d[11]), "=f"(d[12]), "=f"(d[13]), "=f"(d[14]), "=f"(d[15]),
          "=f"(d[16]), "=f"(d[17]), "=f"(d[18]), "=f"(d[19]), "=f"(d[20]), "=f"(d[21]), "=f"(d[22]), "=f"(d[23]),
          "=f"(d[24]), "=f"(d[25]), "=f"(d[26]), "=f"(d[27]), "=f"(d[28]), "=f"(d[29]), "=f"(d[30]), "=f"(d[31]),
          "=f"(d[32]), "=f"(d[33]), "=f"(d[34]), "=f"(d[35]), "=f"(d[36]), "=f"(d[37]), "=f"(d[38]), "=f"(d[39]),
          "=f"(d[40]), "=f"(d[41]), "=f"(d[42]), "=f"(d[43]), "=f"(d[44]), "=f"(d[45]), "=f"(d[46]), "=f"(d[47]),
          "=f"(d[48]), "=f"(d[49]), "=f"(d[50]), "=f"(d[51]), "=f"(d[52]), "=f"(d[53]), "=f"(d[54]), "=f"(d[55]),
          "=f"(d[56]), "=f"(d[57]), "=f"(d[58]), "=f"(d[59]), "=f"(d[60]), "=f"(d[61]), "=f"(d[62]), "=f"(d[63])
        : "l"(da), "l"(db));
}
__device__ __forceinline__ void wgmma_n128(float (&d)[64], uint64_t da, uint64_t db) {
    asm volatile("{\n.reg .pred p;\nsetp.eq.b32 p, 0, 0;\n"
        "wgmma.mma_async.sync.aligned.m64n128k16.f32.bf16.bf16 {"
        "%0, %1, %2, %3, %4, %5, %6, %7, %8, %9, %10, %11, %12, %13, %14, %15, "
        "%16, %17, %18, %19, %20, %21, %22, %23, %24, %25, %26, %27, %28, %29, %30, %31, "
        "%32, %33, %34, %35, %36, %37, %38, %39, %40, %41, %42, %43, %44, %45, %46, %47, "
        "%48, %49, %50, %51, %52, %53, %54, %55, %56, %57, %58, %59, %60, %61, %62, %63"
        "}, %64, %65, p, 1, 1, 0, 1;\n}\n"
        : "+f"(d[0]), "+f"(d[1]), "+f"(d[2]), "+f"(d[3]), "+f"(d[4]), "+f"(d[5]), "+f"(d[6]), "+f"(d[7]),
          "+f"(d[8]), "+f"(d[9]), "+f"(d[10]), "+f"(d[11]), "+f"(d[12]), "+f"(d[13]), "+f"(d[14]), "+f"(d[15]),
          "+f"(d[16]), "+f"(d[17]), "+f"(d[18]), "+f"(d[19]), "+f"(d[20]), "+f"(d[21]), "+f"(d[22]), "+f"(d[23]),
          "+f"(d[24]), "+f"(d[25]), "+f"(d[26]), "+f"(d[27]), "+f"(d[28]), "+f"(d[29]), "+f"(d[30]), "+f"(d[31]),
          "+f"(d[32]), "+f"(d[33]), "+f"(d[34]), "+f"(d[35]), "+f"(d[36]), "+f"(d[37]), "+f"(d[38]), "+f"(d[39]),
          "+f"(d[40]), "+f"(d[41]), "+f"(d[42]), "+f"(d[43]), "+f"(d[44]), "+f"(d[45]), "+f"(d[46]), "+f"(d[47]),
          "+f"(d[48]), "+f"(d[49]), "+f"(d[50]), "+f"(d[51]), "+f"(d[52]), "+f"(d[53]), "+f"(d[54]), "+f"(d[55]),
          "+f"(d[56]), "+f"(d[57]), "+f"(d[58]), "+f"(d[59]), "+f"(d[60]), "+f"(d[61]), "+f"(d[62]), "+f"(d[63])
        : "l"(da), "l"(db));
}
__device__ __forceinline__ void wgmma_n176_z(float (&d)[88], uint64_t da, uint64_t db) {
    asm volatile("{\n.reg .pred p;\nsetp.ne.b32 p, 0, 0;\n"
        "wgmma.mma_async.sync.aligned.m64n176k16.f32.bf16.bf16 {"
        "%0, %1, %2, %3, %4, %5, %6, %7, %8, %9, %10, %11, %12, %13, %14, %15, "
        "%16, %17, %18, %19, %20, %21, %22, %23, %24, %25, %26, %27, %28, %29, %30, %31, "
        "%32, %33, %34, %35, %36, %37, %38, %39, %40, %41, %42, %43, %44, %45, %46, %47, "
        "%48, %49, %50, %51, %52, %53, %54, %55, %56, %57, %58, %59, %60, %61, %62, %63, "
        "%64, %65, %66, %67, %68, %69, %70, %71, %72, %73, %74, %75, %76, %77, %78, %79, "
        "%80, %81, %82, %83, %84, %85, %86, %87"
        "}, %88, %89, p, 1, 1, 0, 1;\n}\n"
        : "=f"(d[0]), "=f"(d[1]), "=f"(d[2]), "=f"(d[3]), "=f"(d[4]), "=f"(d[5]), "=f"(d[6]), "=f"(d[7]),
          "=f"(d[8]), "=f"(d[9]), "=f"(d[10]), "=f"(d[11]), "=f"(d[12]), "=f"(d[13]), "=f"(d[14]), "=f"(d[15]),
          "=f"(d[16]), "=f"(d[17]), "=f"(d[18]), "=f"(d[19]), "=f"(d[20]), "=f"(d[21]), "=f"(d[22]), "=f"(d[23]),
          "=f"(d[24]), "=f"(d[25]), "=f"(d[26]), "=f"(d[27]), "=f"(d[28]), "=f"(d[29]), "=f"(d[30]), "=f"(d[31]),
          "=f"(d[32]), "=f"(d[33]), "=f"(d[34]), "=f"(d[35]), "=f"(d[36]), "=f"(d[37]), "=f"(d[38]), "=f"(d[39]),
          "=f"(d[40]), "=f"(d[41]), "=f"(d[42]), "=f"(d[43]), "=f"(d[44]), "=f"(d[45]), "=f"(d[46]), "=f"(d[47]),
          "=f"(d[48]), "=f"(d[49]), "=f"(d[50]), "=f"(d[51]), "=f"(d[52]), "=f"(d[53]), "=f"(d[54]), "=f"(d[55]),
          "=f"(d[56]), "=f"(d[57]), "=f"(d[58]), "=f"(d[59]), "=f"(d[60]), "=f"(d[61]), "=f"(d[62]), "=f"(d[63]),
          "=f"(d[64]), "=f"(d[65]), "=f"(d[66]), "=f"(d[67]), "=f"(d[68]), "=f"(d[69]), "=f"(d[70]), "=f"(d[71]),
          "=f"(d[72]), "=f"(d[73]), "=f"(d[74]), "=f"(d[75]), "=f"(d[76]), "=f"(d[77]), "=f"(d[78]), "=f"(d[79]),
          "=f"(d[80]), "=f"(d[81]), "=f"(d[82]), "=f"(d[83]), "=f"(d[84]), "=f"(d[85]), "=f"(d[86]), "=f"(d[87])
        : "l"(da), "l"(db));
}
__device__ __forceinline__ void wgmma_n176(float (&d)[88], uint64_t da, uint64_t db) {
    asm volatile("{\n.reg .pred p;\nsetp.eq.b32 p, 0, 0;\n"
        "wgmma.mma_async.sync.aligned.m64n176k16.f32.bf16.bf16 {"
        "%0, %1, %2, %3, %4, %5, %6, %7, %8, %9, %10, %11, %12, %13, %14, %15, "
        "%16, %17, %18, %19, %20, %21, %22, %23, %24, %25, %26, %27, %28, %29, %30, %31, "
        "%32, %33, %34, %35, %36, %37, %38, %39, %40, %41, %42, %43, %44, %45, %46, %47, "
        "%48, %49, %50, %51, %52, %53, %54, %55, %56, %57, %58, %59, %60, %61, %62, %63, "
        "%64, %65, %66, %67, %68, %69, %70, %71, %72, %73, %74, %75, %76, %77, %78, %79, "
        "%80, %81, %82, %83, %84, %85, %86, %87"
        "}, %88, %89, p, 1, 1, 0, 1;\n}\n"
        : "+f"(d[0]), "+f"(d[1]), "+f"(d[2]), "+f"(d[3]), "+f"(d[4]), "+f"(d[5]), "+f"(d[6]), "+f"(d[7]),
          "+f"(d[8]), "+f"(d[9]), "+f"(d[10]), "+f"(d[11]), "+f"(d[12]), "+f"(d[13]), "+f"(d[14]), "+f"(d[15]),
          "+f"(d[16]), "+f"(d[17]), "+f"(d[18]), "+f"(d[19]), "+f"(d[20]), "+f"(d[21]), "+f"(d[22]), "+f"(d[23]),
          "+f"(d[24]), "+f"(d[25]), "+f"(d[26]), "+f"(d[27]), "+f"(d[28]), "+f"(d[29]), "+f"(d[30]), "+f"(d[31]),
          "+f"(d[32]), "+f"(d[33]), "+f"(d[34]), "+f"(d[35]), "+f"(d[36]), "+f"(d[37]), "+f"(d[38]), "+f"(d[39]),
          "+f"(d[40]), "+f"(d[41]), "+f"(d[42]), "+f"(d[43]), "+f"(d[44]), "+f"(d[45]), "+f"(d[46]), "+f"(d[47]),
          "+f"(d[48]), "+f"(d[49]), "+f"(d[50]), "+f"(d[51]), "+f"(d[52]), "+f"(d[53]), "+f"(d[54]), "+f"(d[55]),
          "+f"(d[56]), "+f"(d[57]), "+f"(d[58]), "+f"(d[59]), "+f"(d[60]), "+f"(d[61]), "+f"(d[62]), "+f"(d[63]),
          "+f"(d[64]), "+f"(d[65]), "+f"(d[66]), "+f"(d[67]), "+f"(d[68]), "+f"(d[69]), "+f"(d[70]), "+f"(d[71]),
          "+f"(d[72]), "+f"(d[73]), "+f"(d[74]), "+f"(d[75]), "+f"(d[76]), "+f"(d[77]), "+f"(d[78]), "+f"(d[79]),
          "+f"(d[80]), "+f"(d[81]), "+f"(d[82]), "+f"(d[83]), "+f"(d[84]), "+f"(d[85]), "+f"(d[86]), "+f"(d[87])
        : "l"(da), "l"(db));
}
__device__ __forceinline__ void wgmma_n256_z(float (&d)[128], uint64_t da, uint64_t db) {
    asm volatile("{\n.reg .pred p;\nsetp.ne.b32 p, 0, 0;\n"
        "wgmma.mma_async.sync.aligned.m64n256k16.f32.bf16.bf16 {"
        "%0, %1, %2, %3, %4, %5, %6, %7, %8, %9, %10, %11, %12, %13, %14, %15, "
        "%16, %17, %18, %19, %20, %21, %22, %23, %24, %25, %26, %27, %28, %29, %30, %31, "
        "%32, %33, %34, %35, %36, %37, %38, %39, %40, %41, %42, %43, %44, %45, %46, %47, "
        "%48, %49, %50, %51, %52, %53, %54, %55, %56, %57, %58, %59, %60, %61, %62, %63, "
        "%64, %65, %66, %67, %68, %69, %70, %71, %72, %73, %74, %75, %76, %77, %78, %79, "
        "%80, %81, %82, %83, %84, %85, %86, %87, %88, %89, %90, %91, %92, %93, %94, %95, "
        "%96, %97, %98, %99, %100, %101, %102, %103, %104, %105, %106, %107, %108, %109, %110, %111, "
        "%112, %113, %114, %115, %116, %117, %118, %119, %120, %121, %122, %123, %124, %125, %126, %127"
        "}, %128, %129, p, 1, 1, 0, 1;\n}\n"
        : "=f"(d[0]), "=f"(d[1]), "=f"(d[2]), "=f"(d[3]), "=f"(d[4]), "=f"(d[5]), "=f"(d[6]), "=f"(d[7]),
          "=f"(d[8]), "=f"(d[9]), "=f"(d[10]), "=f"(d[11]), "=f"(d[12]), "=f"(d[13]), "=f"(d[14]), "=f"(d[15]),
          "=f"(d[16]), "=f"(d[17]), "=f"(d[18]), "=f"(d[19]), "=f"(d[20]), "=f"(d[21]), "=f"(d[22]), "=f"(d[23]),
          "=f"(d[24]), "=f"(d[25]), "=f"(d[26]), "=f"(d[27]), "=f"(d[28]), "=f"(d[29]), "=f"(d[30]), "=f"(d[31]),
          "=f"(d[32]), "=f"(d[33]), "=f"(d[34]), "=f"(d[35]), "=f"(d[36]), "=f"(d[37]), "=f"(d[38]), "=f"(d[39]),
          "=f"(d[40]), "=f"(d[41]), "=f"(d[42]), "=f"(d[43]), "=f"(d[44]), "=f"(d[45]), "=f"(d[46]), "=f"(d[47]),
          "=f"(d[48]), "=f"(d[49]), "=f"(d[50]), "=f"(d[51]), "=f"(d[52]), "=f"(d[53]), "=f"(d[54]), "=f"(d[55]),
          "=f"(d[56]), "=f"(d[57]), "=f"(d[58]), "=f"(d[59]), "=f"(d[60]), "=f"(d[61]), "=f"(d[62]), "=f"(d[63]),
          "=f"(d[64]), "=f"(d[65]), "=f"(d[66]), "=f"(d[67]), "=f"(d[68]), "=f"(d[69]), "=f"(d[70]), "=f"(d[71]),
          "=f"(d[72]), "=f"(d[73]), "=f"(d[74]), "=f"(d[75]), "=f"(d[76]), "=f"(d[77]), "=f"(d[78]), "=f"(d[79]),
          "=f"(d[80]), "=f"(d[81]), "=f"(d[82]), "=f"(d[83]), "=f"(d[84]), "=f"(d[85]), "=f"(d[86]), "=f"(d[87]),
          "=f"(d[88]), "=f"(d[89]), "=f"(d[90]), "=f"(d[91]), "=f"(d[92]), "=f"(d[93]), "=f"(d[94]), "=f"(d[95]),
          "=f"(d[96]), "=f"(d[97]), "=f"(d[98]), "=f"(d[99]), "=f"(d[100]), "=f"(d[101]), "=f"(d[102]), "=f"(d[103]),
          "=f"(d[104]), "=f"(d[105]), "=f"(d[106]), "=f"(d[107]), "=f"(d[108]), "=f"(d[109]), "=f"(d[110]), "=f"(d[111]),
          "=f"(d[112]), "=f"(d[113]), "=f"(d[114]), "=f"(d[115]), "=f"(d[116]), "=f"(d[117]), "=f"(d[118]), "=f"(d[119]),
          "=f"(d[120]), "=f"(d[121]), "=f"(d[122]), "=f"(d[123]), "=f"(d[124]), "=f"(d[125]), "=f"(d[126]), "=f"(d[127])
        : "l"(da), "l"(db));
}
__device__ __forceinline__ void wgmma_n256(float (&d)[128], uint64_t da, uint64_t db) {
    asm volatile("{\n.reg .pred p;\nsetp.eq.b32 p, 0, 0;\n"
        "wgmma.mma_async.sync.aligned.m64n256k16.f32.bf16.bf16 {"
        "%0, %1, %2, %3, %4, %5, %6, %7, %8, %9, %10, %11, %12, %13, %14, %15, "
        "%16, %17, %18, %19, %20, %21, %22, %23, %24, %25, %26, %27, %28, %29, %30, %31, "
        "%32, %33, %34, %35, %36, %37, %38, %39, %40, %41, %42, %43, %44, %45, %46, %47, "
        "%48, %49, %50, %51, %52, %53, %54, %55, %56, %57, %58, %59, %60, %61, %62, %63, "
        "%64, %65, %66, %67, %68, %69, %70, %71, %72, %73, %74, %75, %76, %77, %78, %79, "
        "%80, %81, %82, %83, %84, %85, %86, %87, %88, %89, %90, %91, %92, %93, %94, %95, "
        "%96, %97, %98, %99, %100, %101, %102, %103, %104, %105, %106, %107, %108, %109, %110, %111, "
        "%112, %113, %114, %115, %116, %117, %118, %119, %120, %121, %122, %123, %124, %125, %126, %127"
        "}, %128, %129, p, 1, 1, 0, 1;\n}\n"
        : "+f"(d[0]), "+f"(d[1]), "+f"(d[2]), "+f"(d[3]), "+f"(d[4]), "+f"(d[5]), "+f"(d[6]), "+f"(d[7]),
          "+f"(d[8]), "+f"(d[9]), "+f"(d[10]), "+f"(d[11]), "+f"(d[12]), "+f"(d[13]), "+f"(d[14]), "+f"(d[15]),
          "+f"(d[16]), "+f"(d[17]), "+f"(d[18]), "+f"(d[19]), "+f"(d[20]), "+f"(d[21]), "+f"(d[22]), "+f"(d[23]),
          "+f"(d[24]), "+f"(d[25]), "+f"(d[26]), "+f"(d[27]), "+f"(d[28]), "+f"(d[29]), "+f"(d[30]), "+f"(d[31]),
          "+f"(d[32]), "+f"(d[33]), "+f"(d[34]), "+f"(d[35]), "+f"(d[36]), "+f"(d[37]), "+f"(d[38]), "+f"(d[39]),
          "+f"(d[40]), "+f"(d[41]), "+f"(d[42]), "+f"(d[43]), "+f"(d[44]), "+f"(d[45]), "+f"(d[46]), "+f"(d[47]),
          "+f"(d[48]), "+f"(d[49]), "+f"(d[50]), "+f"(d[51]), "+f"(d[52]), "+f"(d[53]), "+f"(d[54]), "+f"(d[55]),
          "+f"(d[56]), "+f"(d[57]), "+f"(d[58]), "+f"(d[59]), "+f"(d[60]), "+f"(d[61]), "+f"(d[62]), "+f"(d[63]),
          "+f"(d[64]), "+f"(d[65]), "+f"(d[66]), "+f"(d[67]), "+f"(d[68]), "+f"(d[69]), "+f"(d[70]), "+f"(d[71]),
          "+f"(d[72]), "+f"(d[73]), "+f"(d[74]), "+f"(d[75]), "+f"(d[76]), "+f"(d[77]), "+f"(d[78]), "+f"(d[79]),
          "+f"(d[80]), "+f"(d[81]), "+f"(d[82]), "+f"(d[83]), "+f"(d[84]), "+f"(d[85]), "+f"(d[86]), "+f"(d[87]),
          "+f"(d[88]), "+f"(d[89]), "+f"(d[90]), "+f"(d[91]), "+f"(d[92]), "+f"(d[93]), "+f"(d[94]), "+f"(d[95]),
          "+f"(d[96]), "+f"(d[97]), "+f"(d[98]), "+f"(d[99]), "+f"(d[100]), "+f"(d[101]), "+f"(d[102]), "+f"(d[103]),
          "+f"(d[104]), "+f"(d[105]), "+f"(d[106]), "+f"(d[107]), "+f"(d[108]), "+f"(d[109]), "+f"(d[110]), "+f"(d[111]),
          "+f"(d[112]), "+f"(d[113]), "+f"(d[114]), "+f"(d[115]), "+f"(d[116]), "+f"(d[117]), "+f"(d[118]), "+f"(d[119]),
          "+f"(d[120]), "+f"(d[121]), "+f"(d[122]), "+f"(d[123]), "+f"(d[124]), "+f"(d[125]), "+f"(d[126]), "+f"(d[127])
        : "l"(da), "l"(db));
}

struct Idx {
    uint32_t lane, warp, w4, q4, g8, prow, pan;
    __device__ __forceinline__ Idx() {
        uint32_t t; asm volatile("mov.u32 %0, %%tid.x;" : "=r"(t));
        lane = t & 31; warp = t >> 5; w4 = warp & 3; q4 = lane & 3; g8 = lane >> 2;
        prow = w4 * 16 + ((lane >> 3) & 1) * 8 + (lane & 7);
        pan = prow * 128 + (((lane >> 4) ^ (lane & 7)) << 4);
    }
};
#define IDX() const Idx ix; const uint32_t lane = ix.lane, warp = ix.warp, w4 = ix.w4, q4 = ix.q4, g8 = ix.g8, prow = ix.prow, pan_addr = ix.pan; \
    (void)lane; (void)warp; (void)w4; (void)q4; (void)g8; (void)prow; (void)pan_addr;

__device__ __forceinline__ int kof(int t, int sh, int j) {
    const int p = t >> (sh - 1), pn = p < 2 ? p : p >= 9, q = p - 2 - 7 * pn;
    return ((p < 2 ? j : q + (q >= j)) << 7) + (pn << 6) + ((t & (sh - 1)) << 5);
}
__device__ __forceinline__ uint32_t fidx(uint32_t m, uint32_t w, uint32_t pn) {
    return m * 32 + w * 16 + pn;
}
constexpr int HC0 = 8 * 48, HC3 = HC0 + 3072;
__device__ __forceinline__ int hcol(int p, int j) { return HC0 + p * 1024 + j * 128; }
struct Ring {
    uint32_t slot, par;
    __device__ __forceinline__ void next() { if (++slot == NSLOT) { slot = 0; par ^= 1; } }
    __device__ __forceinline__ void skip(uint32_t n) { slot += n; if (slot >= NSLOT) { slot -= NSLOT; par ^= 1; } }
};
__device__ __forceinline__ uint32_t BAR_FULL(uint32_t sb, uint32_t s) { return sb + OFF_BAR + 8 * s; }
constexpr uint32_t AF_REL = 48;
__device__ __forceinline__ uint32_t BAR_EMPTY(uint32_t sb, uint32_t s) { return sb + OFF_BAR + 96 + 8 * s; }
__device__ __forceinline__ uint32_t BAR_SFULL(uint32_t sb, uint32_t i) { return sb + OFF_BAR + 152 + 8 * i; }
__device__ __forceinline__ uint32_t BAR_SREADY(uint32_t sb, uint32_t i) { return sb + OFF_BAR + 184 + 8 * i; }
__device__ __forceinline__ uint32_t BAR_ONE(uint32_t sb, uint32_t i) { return sb + OFF_BAR + 216 + 8 * i; }
enum { EV_WIN, EV_WIN1, EV_WIN2, EV_WIN3, EV_P0, EV_GA, EV_GB, EV_LN2, EV_LAG1, EV_LAG2, EV_LAG3, EV_LAG4, EV_LAG5, EV_KV, EV_PAR, EV_AGO, EV_AGO1, EV_AGO2, EV_FGO, EV_FGO1, EV_FGO2, EV_H0, EV_H1, EV_H2, EV_H3, EV_TAIL, EV_COUNT = EV_TAIL + 8 };
constexpr int NB_TAIL = 4;

struct Rel {
    uint32_t base; bool sig;
    __device__ __forceinline__ Rel(uint32_t sb, uint32_t tw) {
        uint32_t a; asm("mapa.shared::cluster.u32 %0, %1, %2;" : "=r"(a) : "r"(BAR_EMPTY(sb, 0)), "r"((tw >> 5) & 1));
        base = __shfl_sync(0xffffffffu, a, 0); sig = (tw & ~32u) == 0;
    }
    __device__ __forceinline__ void operator()(uint32_t slot) const {
        if (sig) asm volatile("mbarrier.arrive.shared::cluster.b64 _, [%0];" :: "r"(base + 8 * slot) : "memory");
    }
};
struct LnRow { float rs0, nm0, rs1, nm1; };
struct Pipe {
    Rel rel; uint32_t p1, p2;
    __device__ __forceinline__ Pipe(uint32_t sb, uint32_t tw, uint32_t first) : rel(sb, tw), p1(first), p2(NSLOT) {}
    template <bool TWO> __device__ __forceinline__ void acquire(uint32_t sb, uint32_t af, const Ring& r) {
        const uint32_t b0 = BAR_FULL(sb, r.slot), b1 = b0 + af;
        const bool ready = TWO ? mbar_test2(b0, b1, r.par) : mbar_test(b0, r.par);
        wg_wait<1>();
        rel(p2);
        if (!ready) { if (TWO) mbar_wait2(b0, b1, r.par); else mbar_wait(b0, r.par); }
    }
    __device__ __forceinline__ void issued(uint32_t slot) { p2 = p1; p1 = slot; }
    __device__ __forceinline__ void drain1() { wg_wait<1>(); rel(p2); p2 = NSLOT; }
    __device__ __forceinline__ void drain0() { wg_wait<0>(); rel(p1); p1 = NSLOT; }
    template <bool TWO, class Step> __device__ __forceinline__ void hold(int LG, uint32_t sb, uint32_t af, Ring& r, uint32_t lag_bar, Step step) {
        Ring q = r;
#pragma unroll 1
        for (int i = 0; i < LG; ++i) { if (TWO) mbar_wait2(BAR_FULL(sb, q.slot), BAR_FULL(sb, q.slot) + af, q.par); else mbar_wait(BAR_FULL(sb, q.slot), q.par); q.next(); }
        mbar_wait(lag_bar, 0);
#pragma unroll 1
        do {
            step(r.slot);
            wg_wait<2>(); rel(p2); p2 = p1; p1 = r.slot;
            if (++r.slot == NSLOT) r.slot = 0;
        } while (r.slot != q.slot);
        r.par = q.par;
    }
};
template <bool TWO, bool FIRST, int NA, int NB>
__device__ __forceinline__ void step32(float (&aa)[NA], float (&ab)[NB], uint32_t sb, uint32_t wg, uint32_t slot, int own) {
    const uint32_t st = d16(sb) + slot * (SLOT >> 4);
    const uint32_t alo = own >= 0 ? d16(sb) + OFF_STG / 16 + wg * 1024 + (own >> 1) * 512 + (own & 1) * 4 : st + wg * 256;
    const uint32_t ahi = own >= 0 ? (1024 >> 4) | (1u << 30) : (512 >> 4) | (2u << 30);
    wg_fence();
#pragma unroll
    for (int k = 0; k < 2; ++k) {
        const uint64_t da = ((uint64_t)ahi << 32) | (alo + k * 2 + 0x10000);
        if constexpr (NA == 88) {
            const uint64_t d0 = mk_desc(st, 8192 + k * 2048, 8192, 1024, 1), d1 = mk_desc(st, 12288 + k * 2048, 8192, 1024, 1);
            if (FIRST && k == 0) { wgmma_n176_z(aa, da, d0); wgmma_n176_z(ab, da, d1); }
            else { wgmma_n176(aa, da, d0); wgmma_n176(ab, da, d1); }
        } else {
            const uint64_t d0 = mk_desc(st, 8192 + k * 2048, 4096, 1024, 1), d1 = mk_desc(st, 24576 + k * 2048, 4096, 1024, 1);
            if (FIRST && k == 0) { wgmma_n256_z(aa, da, d0); if constexpr (TWO) wgmma_n128_z(ab, da, d1); }
            else { wgmma_n256(aa, da, d0); if constexpr (TWO) wgmma_n128(ab, da, d1); }
        }
    }
    wg_commit();
}
template <bool TWO, int LG, int NA, int NB, class Mid, class Tail>
__device__ __forceinline__ void mainloop32(float (&aa)[NA], float (&ab)[NB], uint32_t sb, uint32_t wg, uint32_t tw, Ring& r, uint32_t lag_ev, int g0, Mid mid, Tail tail) {
    if (!TWO) mbar_wait(BAR_FULL(sb, r.slot), r.par);
    step32<TWO, true>(aa, ab, sb, wg, r.slot, TWO ? 0 : -1);
    TS(g0, 0);
    Pipe pp(sb, tw, r.slot);
    r.next();
    const int end = wg ? 32 : 32 - LG;
#pragma unroll 1
    for (int it = 1; it < end; ++it) {
        pp.acquire<TWO>(sb, wg ? 0 : AF_REL, r);
        step32<TWO, false>(aa, ab, sb, wg, r.slot, TWO && it < 4 ? it : -1);
        pp.issued(r.slot);
        TS(g0 + it, 0);
        r.next();
        mid(it);
    }
    if (wg == 0) { pp.drain1(); pp.drain0(); pp.hold<TWO>(LG, sb, AF_REL, r, BAR_ONE(sb, lag_ev), [&](uint32_t slot) { step32<TWO, false>(aa, ab, sb, 0, slot, -1); }); }
    pp.drain1();
    if (wg == 1 && tw == 0) mbar_arrive(BAR_ONE(sb, lag_ev));
    tail();
    pp.drain0();
    TS(g0 + 31, 1);
}
template <bool FIRST>
__device__ __forceinline__ void step64(float (&acc)[64], uint32_t sb, uint32_t wg, uint32_t slot, int own) {
    const uint32_t sbb = d16(sb) + slot * (SLOT >> 4), sa = own >= 0 ? d16(sb) + OFF_STG / 16 + wg * 1024 + own * 512 : sbb + wg * 512;
    wg_fence();
#pragma unroll
    for (int k = 0; k < 4; ++k) {
        const uint64_t da = mk_desc(sa, k * 32, 16, 1024, 1), db = mk_desc(sbb, 16384 + k * 2048, 8192, 1024, 1);
        if (FIRST && k == 0) wgmma_n128_z(acc, da, db); else wgmma_n128(acc, da, db);
    }
    wg_commit();
}
template <class Put, class Mid, class Tail>
__device__ __forceinline__ void mainloop64(float (&acc)[64], bool wo, uint32_t sb, uint32_t wg, uint32_t tw, Ring& r, Put put, Mid mid, Tail tail) {
    const int g0 = wo ? 32 : 144, nst = wo ? 16 : 56, lg = wo ? LAGW : LAGD; (void)g0;
    const uint32_t lag_bar = BAR_ONE(sb, wo ? EV_LAG4 : EV_LAG5), af = wo && !wg ? AF_REL : 0;
    mbar_wait(BAR_FULL(sb, r.slot), r.par);
    if (!wo) CS(28);
    step64<true>(acc, sb, wg, r.slot, wo ? 0 : -1);
    if (!wo) CS(29);
    TS(g0, 0);
    Pipe pp(sb, tw, r.slot);
    r.next();
    int it = 1;
    auto run = [&](int end, int own, bool with_put) {
#pragma unroll 1
        do {
            pp.acquire<true>(sb, af, r);
            step64<false>(acc, sb, wg, r.slot, own);
            pp.issued(r.slot);
            TS(g0 + it, 0);
            if (wo && it == 2) CS(9);
            r.next();
            if (with_put && it == (wg ? PUTD1 : PUTD0)) put();
        } while (++it < end);
    };
    const int end = wg ? nst : nst - lg;
    run(wo ? 2 : wg ? MIDD : end, wo ? 1 : -1, true);
    mid();
    if (wo) { pp.drain1(); pp.drain0(); TS(g0 + 1, 1); }
    if (it < end) run(end, -1, false);
    if (wg == 0) { pp.drain1(); pp.drain0(); pp.hold<true>(lg, sb, af, r, lag_bar, [&](uint32_t slot) { step64<false>(acc, sb, 0, slot, -1); }); }
    pp.drain1();
    if (wg == 1 && tw == 0) mbar_arrive(lag_bar);
    tail();
    pp.drain0();
    TS(g0 + nst - 1, 1);
}

struct RowAcc {
    float sm[4] = {0.f, 0.f, 0.f, 0.f}, sq[4] = {0.f, 0.f, 0.f, 0.f};
    __device__ __forceinline__ void add(int e, float x) { sm[e & 3] += x; sq[e & 3] = fmaf(x, x, sq[e & 3]); }
    __device__ __forceinline__ void publish(uint4* dst, uint32_t q4, uint32_t ep) const {
        const float s0 = sm[0] + sm[1], s1 = sm[2] + sm[3], q0 = sq[0] + sq[1], q1 = sq[2] + sq[3];
        const bool od = q4 & 1;
        float sv = (od ? s1 : s0) + __shfl_xor_sync(0xffffffffu, od ? s0 : s1, 1), qv = (od ? q1 : q0) + __shfl_xor_sync(0xffffffffu, od ? q0 : q1, 1);
        sv += __shfl_xor_sync(0xffffffffu, sv, 2); qv += __shfl_xor_sync(0xffffffffu, qv, 2);
        st_pkt16(dst + (q4 & 1) * 8, 0, __float_as_uint(sv), __float_as_uint(qv), ep);
    }
};
__device__ __forceinline__ LnRow merge_stats(const uint4* src, uint32_t q4, uint32_t ep, uint32_t sb) {
    uint4 t[4];
    uint32_t n = 0;
    while (true) {
#pragma unroll
        for (int i = 0; i < 4; ++i) t[i] = ld_pkt16(src + (q4 * 2 + (i >> 1)) * 512 + (i & 1) * 8);
        const bool ok_ = __all_sync(0xffffffffu, t[0].w == ep && t[1].w == ep && t[2].w == ep && t[3].w == ep);
        if (n < 4) CS(14 + n);
        if (ok_) break;
        SPIN_GUARD(n);
    }
    float v[4];
#pragma unroll
    for (int h = 0; h < 2; ++h) { v[h] = __uint_as_float(t[h].y) + __uint_as_float(t[2 + h].y); v[2 + h] = __uint_as_float(t[h].z) + __uint_as_float(t[2 + h].z); }
#pragma unroll
    for (int o = 1; o < 4; o <<= 1)
#pragma unroll
        for (int i = 0; i < 4; ++i) v[i] += __shfl_xor_sync(0xffffffffu, v[i], o);
    const float m0 = v[0] * (1.f / D_), m1 = v[1] * (1.f / D_);
    const float r0 = rsqrtf(fmaxf(fmaf(-m0, m0, v[2] * (1.f / D_)), 0.f) + 1e-5f), r1 = rsqrtf(fmaxf(fmaf(-m1, m1, v[3] * (1.f / D_)), 0.f) + 1e-5f);
    return LnRow{r0, -m0 * r0, r1, -m1 * r1};
}
struct Stg {
    uint32_t b, par;
    __device__ __forceinline__ uint32_t acquire2(uint32_t sb, uint32_t wg) {
        mbar_wait2(BAR_SREADY(sb, wg * 2), BAR_SREADY(sb, wg * 2 + 1), par);
        par ^= 1;
        return sb + OFF_STG + wg * 16384;
    }
    __device__ __forceinline__ void publish(uint32_t sb, uint32_t wg, uint32_t lane) {
        fence_async_smem();
        __syncwarp();
        if (lane == 0) mbar_arrive(BAR_SFULL(sb, wg * 2 + b));
        b ^= 1;
    }
};

struct LnPar {
    uint4 p[8];
    __device__ __forceinline__ void load(uint32_t sb, uint32_t q4) {
#pragma unroll
        for (int i = 0; i < 8; ++i) p[i] = lds128(sb + OFF_PAR + i * 64 + q4 * 16);
    }
};
__device__ __forceinline__ void ln_norm(uint32_t (&xn)[32], const float (&x)[64], const LnRow& n) {
#pragma unroll
    for (int e = 0; e < 32; ++e) {
        const float rs = (e & 1) ? n.rs1 : n.rs0, nm = (e & 1) ? n.nm1 : n.nm0;
        xn[e] = pack2(fmaf(x[2 * e], rs, nm), fmaf(x[2 * e + 1], rs, nm));
    }
}
__device__ __forceinline__ void ln_emit(const uint32_t (&xr)[32], const LnPar& lp, uint32_t sb, uint32_t wg, const Idx& ix) {
#pragma unroll
    for (int i = 0; i < 8; ++i)
        stsm4(sb + OFF_STG + wg * 16384 + (i >> 2) * 8192 + (ix.pan ^ ((i & 3) << 5)), hfma2_bf16(xr[4 * i], lp.p[i].z, lp.p[i].x), hfma2_bf16(xr[4 * i + 1], lp.p[i].z, lp.p[i].x),
              hfma2_bf16(xr[4 * i + 2], lp.p[i].w, lp.p[i].y), hfma2_bf16(xr[4 * i + 3], lp.p[i].w, lp.p[i].y));
    fence_async_smem();
    __syncwarp();
    if (ix.lane < 2) mbar_arrive(BAR_SFULL(sb, wg * 2 + ix.lane));
    bar_sync(1 + wg, 128);
}
__device__ __forceinline__ void load_slab(uint32_t (&xr)[32], uint32_t buf) {
    IDX();
#pragma unroll
    for (int i = 0; i < 8; ++i) ldsm4(buf + (i >> 2) * 8192 + (pan_addr ^ ((i & 3) << 5)), xr[4 * i], xr[4 * i + 1], xr[4 * i + 2], xr[4 * i + 3]);
}
__device__ __forceinline__ void unpack_slab(float (&x)[64], const uint32_t (&xr)[32]) {
#pragma unroll
    for (int i = 0; i < 32; ++i) unpack2(xr[i], x[2 * i], x[2 * i + 1]);
}
__device__ __forceinline__ void store_slab(const float (&x)[64], uint32_t buf, uint32_t pitch, uint32_t pan, int i0, int i1) {
#pragma unroll
    for (int i = i0; i < i1; ++i)
        stsm4(buf + (i >> 2) * pitch + (pan ^ ((i & 3) << 5)), pack2(x[8 * i], x[8 * i + 1]), pack2(x[8 * i + 2], x[8 * i + 3]), pack2(x[8 * i + 4], x[8 * i + 5]), pack2(x[8 * i + 6], x[8 * i + 7]));
}
template <int NP, class Done>
__device__ __forceinline__ void fetch_halo(uint4* src, bool first, uint32_t dst, Done done) {
    uint4 hv[4 * NP];
    uint32_t n = 0;
    while (true) {
        bool ok = true;
#pragma unroll
        for (int i = 0; i < 4 * NP; ++i) { hv[i] = first ? make_uint4(0, 0, 0, 0) : ld_pkt16(src + (i >> 2) * 256 + (i & 3) * 32); ok = ok && hv[i].x != 0; }
        if (first || __all_sync(0xffffffffu, ok)) break;
        SPIN_GUARD(n);
    }
#pragma unroll
    for (int i = 0; i < 4 * NP; ++i) stsm4(dst + (i >> 2) * 4096 + (i & 3) * 512, hv[i].x, hv[i].y, hv[i].z, hv[i].w);
    done();
    if (!first) {
#pragma unroll
        for (int i = 0; i < 4 * NP; ++i) src[(i >> 2) * 256 + (i & 3) * 32] = make_uint4(0, 0, 0, 0);
    }
}

template <int N, class G, class U>
__device__ __forceinline__ void glu(uint32_t (&h)[N], G g, U u) {
#pragma unroll
    for (int i = 0; i < N; ++i) h[i] = pack2(fmaf(tanh_(g(2 * i)), u(2 * i), u(2 * i)), fmaf(tanh_(g(2 * i + 1)), u(2 * i + 1), u(2 * i + 1)));
}
__device__ __forceinline__ void put_h(const uint32_t (&h)[32], uint32_t sb, uint32_t wg, Stg& stg) {
    IDX();
    const uint32_t buf = stg.acquire2(sb, wg);
#pragma unroll
    for (int k = 0; k < 8; ++k) stsm4(buf + (k >> 2) * 8192 + (pan_addr ^ ((k & 3) << 5)), h[4 * k], h[4 * k + 1], h[4 * k + 2], h[4 * k + 3]);
    fence_async_smem();
    __syncwarp();
    if (lane < 2) mbar_arrive(BAR_SFULL(sb, wg * 2 + lane));
}

template <int NP, bool PREV>
__device__ __forceinline__ void passes128(uint32_t (&hp)[32], uint32_t sb, uint32_t wg, uint32_t tw, Ring& r, Stg& stg) {
#pragma unroll 1
    for (int p = 0; p < NP; ++p) {
        float b256[128], none[1];
        const int put_at = !PREV && p == 0 ? -1 : wg ? PUT1 : PUT0;
        mainloop32<false, LAGS>(b256, none, sb, wg, tw, r, EV_LAG2 + p, 80 + 32 * (p & 1), [&](int it) { if (it == put_at) put_h(hp, sb, wg, stg); }, [] {});
        if (threadIdx.x == 0) { TL(29 + 2 * p); TC(114 + 2 * p); }
        if (threadIdx.x == 128) TL(53 + 2 * (p & 1));
        CS(24 + 2 * (p & 1));
        glu(hp, [&](int i) { return b256[i + (i & 32)]; }, [&](int i) { return b256[i + (i & 32) + 32]; });
        if (threadIdx.x == 0) { TL(30 + 2 * p); TC(115 + 2 * p); }
        if (threadIdx.x == 128) TL(54 + 2 * (p & 1));
        CS(25 + 2 * (p & 1));
    }
}

__global__ void __launch_bounds__(384, 1)
fused_block_kernel(const __grid_constant__ Ptrs pt, const __grid_constant__ Maps mp) {
    uint32_t* const g_flags = pt.mail->flags;
    uint2* const g_mod = pt.mail->mod;
    uint4* const g_st1 = pt.mail->st1;
    uint32_t* const g_par2 = pt.mail->par2;
    uint4* const g_halo = pt.mail->halo;
    const __nv_bfloat16* __restrict__ cvec = pt.c;
    if (threadIdx.x == 224) { prefetch_map(&mp.wm8); prefetch_map(&mp.x); }
    extern __shared__ __align__(1024) uint8_t smem[];
    const uint32_t sb = smem_u32(smem);
    const uint32_t tid = threadIdx.x, tw = tid & 127, lane = tid & 31;
    const uint32_t warp = __shfl_sync(0xffffffffu, tid >> 5, 0), wg = warp >> 2;
    uint32_t rank; asm("mov.u32 %0, %%cluster_ctarank;" : "=r"(rank));
    rank = __shfl_sync(0xffffffffu, rank, 0);
    uint32_t ep;
    uint32_t smid; asm volatile("mov.u32 %0, %%smid;" : "=r"(smid));
    const int c = __shfl_sync(0xffffffffu, smid >> 1, 0);
    const int c7 = ((c - 32) * 37) >> 8;
    int grp = c < 32 ? c & 7 : c < 60 ? c - 31 - 7 * c7 : c < 62 ? -1 : 0;
    const int j = c < 32 ? c >> 3 : c < 60 ? 4 + c7 : c < 62 ? (c - 60) * 2 + rank : c - 58;
    const bool aux = grp < 0;
    const int m = grp * 2 + rank;
    uint4* const g_st2 = g_halo + (m > 0 ? (m - 1) * 8 * 512 : 128);

    bool cluster_arrive_early = false;
    if (wg < 2) {
      if (!KDEBUG) cluster_arrive();
      ep = flag_get(g_flags + FL_DONE);
      uint16_t cw[8];
      {
          const __nv_bfloat16* cp = cvec + ((tw >> 5) * 32 + (tw & 3) * 2) * 8 + (lane >> 2);
#pragma unroll
          for (int i = 0; i < 8; ++i) asm volatile("ld.global.nc.u16 %0, [%1];" : "=h"(cw[i]) : "l"(cp + (i >> 1) * 64 + (i & 1) * 8));
      }
      asm volatile("setmaxnreg.inc.sync.aligned.u32 224;");
      if (tid == 0) TL(58);
      if (KDEBUG) cluster_arrive();
      Ring r{0, 0};
      Stg stg{0, 0};
      if (aux) {
        if (wg == 0) {
            const uint4 cv = *(const uint4*)(cvec + tw * 8);
            sts128(sb + OFF_STG + (tw >> 3) * 1024 + (tw & 7) * 16, pack2(silu_(bf_lo(cv.x)), silu_(bf_hi(cv.x))), pack2(silu_(bf_lo(cv.y)), silu_(bf_hi(cv.y))),
                   pack2(silu_(bf_lo(cv.z)), silu_(bf_hi(cv.z))), pack2(silu_(bf_lo(cv.w)), silu_(bf_hi(cv.w))));
            fence_async_smem();
        }
        cluster_wait();
        ep = __shfl_sync(0xffffffffu, ep, 0) / NCTA + 1;
        if (wg == 0) {
            bar_sync(1, 128);
#pragma unroll 1
            for (int p = 0; p < 4; ++p) {
                float acc[128];
#pragma unroll
                for (int i = 0; i < 128; ++i) acc[i] = 0.f;
                uint32_t prev = 0;
#pragma unroll 1
                for (int kc = 0; kc < 16; ++kc) {
                    mbar_wait(BAR_FULL(sb, r.slot), r.par);
                    wg_fence();
#pragma unroll
                    for (int k = 0; k < 4; ++k)
                        wgmma_n256(acc, mk_desc(d16(sb) + kc * 64, OFF_STG + k * 32, 16, 0, 1), mk_desc(d16(sb) + r.slot * (SLOT >> 4), k * 2048, 8192, 1024, 1));
                    wg_commit();
                    wg_wait<1>();
                    if (kc > 0 && tw < 4) mbar_arrive(BAR_EMPTY(sb, prev));
                    prev = r.slot;
                    r.next();
                }
                wg_wait<0>();
                if (tw < 4) mbar_arrive(BAR_EMPTY(sb, prev));
                if (tw < 4) {
#pragma unroll
                    for (int jn = 0; jn < 32; ++jn) sts32(sb + OFF_TAB + (jn * 4 + tw) * 4, pack2(acc[jn * 4], acc[jn * 4 + 1]));
                }
                bar_sync(1, 128);
                const int vec = 2 + p, blk = p * 4 + j;
                const uint32_t val = lds32(sb + OFF_TAB + tw * 4);
                if (vec == 2 || vec == 5) st_pkt(g_mod + (8 + blk) * 128 + tw, val, ep);
                else {
                    const float one = vec == 4 ? 1.f : 0.f;
                    g_par2[((blk & 3) * 16 + (tw >> 3)) * 16 + (tw & 3) * 4 + (vec - 3) * 2 + ((tw >> 2) & 1)] =
                        pack2(0.5f * bf_round(one + bf_lo(val)), 0.5f * bf_round(one + bf_hi(val)));
                }
                bar_sync(1, 128);
                if (tw == 0) {
                    if (vec == 3 || vec == 4) asm volatile("red.release.gpu.global.add.u32 [%0], 1;" :: "l"(&g_flags[FL_LN2]) : "memory");
                    TL(1 + p);
                }
            }
            if (lane < 2) mbar_arrive_cta(BAR_ONE(sb, EV_P0), lane);
        }
        r = Ring{64 % NSLOT, (64 / NSLOT) & 1};
        mbar_wait(BAR_ONE(sb, EV_P0), 0);
        uint32_t hp[32] = {};
        passes128<4, false>(hp, sb, wg, tw, r, stg);
        put_h(hp, sb, wg, stg);
      } else {
        float xs[64];
        uint32_t xp[32];
        {
            IDX();
            if (q4 < 2) st_pkt16(g_st1 + (m * 8 + j) * 512 + wg * 64 + w4 * 16 + g8 + q4 * 8, 0, 0, 0, 0);
            if (warp == 0) st_pkt16(pt.mail->mod1 + g8 * 512 + (m * 8 + j) * 4 + q4, 0, 0, 0, 0);
            sts128(sb + tid * 16, pack2(silu_(bf_lo(cw[0])), silu_(bf_lo(cw[1]))), pack2(silu_(bf_lo(cw[2])), silu_(bf_lo(cw[3]))),
                   pack2(silu_(bf_lo(cw[4])), silu_(bf_lo(cw[5]))), pack2(silu_(bf_lo(cw[6])), silu_(bf_lo(cw[7]))));
            cluster_wait();
            ep = __shfl_sync(0xffffffffu, ep, 0) / NCTA + 1;
            load_slab(xp, stg.acquire2(sb, wg));
            unpack_slab(xs, xp);
            if (tid == 0) TL(24);
            if (tid == 128) TL(27);
        }
#pragma unroll 1
        for (int blk = 0; ; ++blk) {
        {
            IDX();
            uint4* const st = (blk ? g_st2 : g_st1 + m * 8 * 512) + wg * 64 + w4 * 16 + g8;
            RowAcc ra;
#pragma unroll
            for (int e = 0; e < 64; ++e) ra.add(e, xs[e]);
            ra.publish(st + j * 512, q4, ep);
            uint32_t t_pub = 0; if (PDLY) asm volatile("mov.u32 %0, %%clock;" : "=r"(t_pub));
            if (tid == 0) TL(blk ? 9 : 26);
            if (tid == 128 && blk) TL(34);
            if (blk) CS(11);
            LnPar lp;
            if (blk == 0) {
            uint4* const mod_out = pt.mail->mod1 + g8 * 512 + (m * 8 + j) * 4 + q4;
            if (wg == 0) {
                uint4 af[8];
#pragma unroll
                for (int i = 0; i < 8; ++i) af[i] = lds128(sb + w4 * 512 + i * 64 + q4 * 16);
                float c[4][4] = {};
#pragma unroll
                for (int i = 0; i < 8; ++i) {
                    if (!(i & 1)) mbar_wait(BAR_ONE(sb, EV_WIN + (i >> 1)), 0);
                    if (i == 6 && tid == 0) TL(25);
#pragma unroll
                    for (int h = 0; h < 2; ++h) {
                        uint32_t b0, b1, b2, b3;
                        ldsm4t(sb + 5 * SLOT + i * 4096 + w4 * 1024 + h * 512 + (lane & 15) * 32 + (lane >> 4) * 16, b0, b1, b2, b3);
                        mma16816(c[2 * h], h ? af[i].z : af[i].x, 0u, h ? af[i].w : af[i].y, 0u, b0, b1);
                        mma16816(c[2 * h + 1], h ? af[i].z : af[i].x, 0u, h ? af[i].w : af[i].y, 0u, b2, b3);
                    }
                }
                if (lane < 4) sts128(sb + OFF_TAB + w4 * 64 + lane * 16, __float_as_uint(c[0][0] + c[2][0]), __float_as_uint(c[0][1] + c[2][1]),
                                     __float_as_uint(c[1][0] + c[3][0]), __float_as_uint(c[1][1] + c[3][1]));
                if (lane < 2) mbar_arrive_cta(BAR_ONE(sb, EV_P0), lane);
                bar_sync(1, 128);
                if (w4 == 0) {
                    float a[4] = {0.f, 0.f, 0.f, 0.f};
#pragma unroll
                    for (int i = 0; i < 4; ++i) {
                        const uint4 t = lds128(sb + OFF_TAB + i * 64 + q4 * 16);
                        a[0] += __uint_as_float(t.x); a[1] += __uint_as_float(t.y); a[2] += __uint_as_float(t.z); a[3] += __uint_as_float(t.w);
                    }
                    const float add = m >= 8 ? 1.f : 0.f;
                    st_pkt16(mod_out, pack2(bf_round(a[0]) + add, bf_round(a[1]) + add), pack2(bf_round(a[2]) + add, bf_round(a[3]) + add), ep, 0);
                    if (tid == 0) TL(3);
                }
            } else if (LWAIT >= 0) mbar_wait(BAR_ONE(sb, EV_WIN + LWAIT), 0);
            } else {
                mbar_wait2(BAR_ONE(sb, EV_LN2), BAR_FULL(sb, 0), 0);
            }
            lp.load(sb, q4);
#pragma unroll
            for (int e = 0; e < 32; ++e) xp[e] = pack2(xs[2 * e], xs[2 * e + 1]);
            if (PDLY && blk) { uint32_t t1; do { asm volatile("mov.u32 %0, %%clock;" : "=r"(t1)); } while (t1 - t_pub < PDLY); }
            if (blk) CS(13);
            const LnRow n = merge_stats(st, q4, ep, sb);
            if (tid == 0) TL(blk ? 49 : 48);
            if (tid == 128) TL(blk ? 45 : 28);
            if (blk) CS(18);
            uint32_t xn[32];
            ln_norm(xn, xs, n);
            if (blk == 0) { mbar_wait2(BAR_FULL(sb, 0), BAR_ONE(sb, EV_PAR), 0); lp.load(sb, q4); }
            ln_emit(xn, lp, sb, wg, ix);
            if (tid == 0) { TL(blk ? 36 : 8); TC(blk ? 109 : 103); }
            if (tid == 128) TL(blk ? 43 : 22);
            if (blk) CS(21);
        }
        uint32_t hp[32];
        if (blk == 0) {
        {
            float big[128], sml[64];
            step32<true, true>(big, sml, sb, wg, r.slot, 0);
            TS(0, 0);
            Pipe pp(sb, tw, r.slot);
            r.next();
#pragma unroll 1
            for (int it = 1; it < 32 - LAGQ; ++it) {
                pp.acquire<true>(sb, wg ? 0 : AF_REL, r);
                step32<true, false>(big, sml, sb, wg, r.slot, it < 4 ? it : -1);
                pp.issued(r.slot);
                TS(it, 0);
                r.next();
            }
            auto half = [&](uint32_t slot, bool rest) {
                const uint32_t st = d16(sb) + slot * (SLOT >> 4);
#pragma unroll
                for (int k = 0; k < 2; ++k) {
                    const uint64_t da = mk_desc(st + wg * 256, k * 32, 16, 512, 2);
                    if (rest) wgmma_n256(big, da, mk_desc(st, 8192 + k * 2048, 4096, 1024, 1)); else wgmma_n128(sml, da, mk_desc(st, 24576 + k * 2048, 4096, 1024, 1));
                }
            };
            auto rest = [&](bool each) {
                wg_fence();
#pragma unroll
                for (int it = 32 - LAGQ; it < 32; ++it) { if (each && it > 32 - LAGQ) wg_fence(); half(it % NSLOT, true); if (each || it == 31) wg_commit(); }
            };
            stg.acquire2(sb, wg); mbar_wait2(BAR_SREADY(sb, 2), BAR_SREADY(sb, 3), 1);
#pragma unroll 1
            for (int it = 32 - LAGQ; it < 32; ++it) {
                pp.acquire<true>(sb, wg ? 0 : AF_REL, r);
                wg_fence(); half(r.slot, false); wg_commit();
                pp.issued(NSLOT);
                TS(it, 0);
                r.next();
            }
            if (wg) { rest(false); wg_wait<1>(); } else wg_wait<0>();
            CS(8);
            IDX();
            uint32_t k0[8], k1[8], k2[8], v0[8], v1[8], v2[8];
            const uint32_t nxt = warp + ((warp & 1) ? 3 : 1), mine = sb + OFF_STG + wg * 16384 + w4 * 2048;
            auto tails = [&](const float* kv, uint32_t (&kt)[8], uint32_t (&vt)[8]) {
#pragma unroll
                for (int t = 0; t < 8; ++t) { kt[t] = pack2(kv[4 * t + 2], kv[4 * t + 3]); vt[t] = pack2(kv[32 + 4 * t + 2], kv[32 + 4 * t + 3]); }
            };
            auto post = [&](int pn, uint32_t (&kt)[8], uint32_t (&vt)[8]) {
                uint4* dst = g_halo + (m * 8 + j) * 512 + (w4 >> 1) * 256 + pn * 128 + lane;
#pragma unroll
                for (int h = 0; h < 2; ++h) { if (!kt[4 * h]) kt[4 * h] = 0x8000u; if (!vt[4 * h]) vt[4 * h] = 0x8000u; }
#pragma unroll
                for (int h = 0; h < 2; ++h) { st_pkt16(dst + h * 32, kt[4 * h], kt[4 * h + 1], kt[4 * h + 2], kt[4 * h + 3]); st_pkt16(dst + 64 + h * 32, vt[4 * h], vt[4 * h + 1], vt[4 * h + 2], vt[4 * h + 3]); }
            };
            auto prepare = [&](int pn, const float* kv) {
                tails(kv, k2, v2);
                if (nxt < 8) {
                    const uint32_t dst = sb + OFF_STG + (nxt >> 2) * 16384 + (nxt & 3) * 2048 + pn * 8192 + lane * 16;
#pragma unroll
                    for (int h = 0; h < 2; ++h) { stsm4(dst + h * 512, k2[4 * h], k2[4 * h + 1], k2[4 * h + 2], k2[4 * h + 3]); stsm4(dst + 1024 + h * 512, v2[4 * h], v2[4 * h + 1], v2[4 * h + 2], v2[4 * h + 3]); }
                    if (pn == 0) bar_arrive(NB_TAIL + nxt, 64);
                    else { __syncwarp(); if (lane == 0) mbar_arrive(BAR_ONE(sb, EV_TAIL + nxt)); }
                } else if (pn == 0 && m < 15) post(0, k2, v2);
#pragma unroll
                for (int t = 0; t < 8; ++t) { k1[t] = pack2(kv[4 * t], kv[4 * t + 1]); v1[t] = movm(pack2(kv[32 + 4 * t], kv[32 + 4 * t + 1])); v2[t] = movm(v2[t]); }
                if (pn == 0) { CS(2); if (wg == 0) { rest(true); wg_wait<3>(); pp.rel(28 % NSLOT); wg_wait<2>(); pp.rel(29 % NSLOT); wg_wait<1>(); pp.rel(30 % NSLOT); } bar_sync(NB_TAIL + warp, 64); CS(4); }
                else mbar_wait(BAR_ONE(sb, EV_TAIL + __shfl_sync(0xffffffffu, warp, 0)), 0);
#pragma unroll
                for (int h = 0; h < 2; ++h) {
                    ldsm4(mine + pn * 8192 + lane * 16 + h * 512, k0[4 * h], k0[4 * h + 1], k0[4 * h + 2], k0[4 * h + 3]);
                    ldsm4t(mine + pn * 8192 + lane * 16 + 1024 + h * 512, v0[4 * h], v0[4 * h + 1], v0[4 * h + 2], v0[4 * h + 3]);
                }
            };
#pragma unroll
            for (int i = 0; i < 64; ++i) asm volatile("" : "+f"(sml[i]) :: "memory");
            prepare(0, sml);
            static_assert(LAGQ == 4, "");
            wg_wait<0>();
            if (wg) { pp.rel(28 % NSLOT); pp.rel(29 % NSLOT); pp.rel(30 % NSLOT); }
            pp.rel(31 % NSLOT);
            TS(31, 1);
            if (tid == 0) { TL(4); TC(104); }
            if (tid == 128) TL(50);
            CS(1);
#pragma unroll
            for (int i = 0; i < 128; ++i) asm volatile("" : "+f"(big[i]) :: "memory");
            if (nxt >= 8 && m < 15) { uint32_t kt[8], vt[8]; tails(big, kt, vt); post(1, kt, vt); }
            const bool lo0 = q4 * 2 > g8, lo1 = q4 * 2 + 1 > g8;
            const bool nopast = m == 0 && (warp & 5) == 0;
            const uint32_t lomask = (lo0 ? 0xFFFFu : 0u) | (lo1 ? 0xFFFF0000u : 0u);
            const uint32_t orow = mine + (lane & 7) * 128 + (((lane >> 3) ^ (lane & 7)) << 4);
            const float sl2 = 0.17677669529663687f * 1.4426950408889634f;
#pragma unroll
            for (int pn = 0; pn < 2; ++pn) {
                float e0[4], e1[4], mx[4], sum[4];
#pragma unroll
                for (int hh = 0; hh < 2; ++hh) {
                    uint32_t qf[8];
#pragma unroll
                    for (int i = 0; i < 8; ++i) qf[i] = pack2(big[64 + 32 * pn + 16 * hh + 2 * i], big[64 + 32 * pn + 16 * hh + 2 * i + 1]);
                    float s[3][4];
#pragma unroll
                    for (int t = 0; t < 3; ++t) {
                        const uint32_t* k = (t == 0 ? k0 : t == 1 ? k1 : k2) + 4 * hh;
                        s[t][0] = s[t][1] = s[t][2] = s[t][3] = 0.f;
                        mma16816(s[t], qf[0], qf[1], qf[2], qf[3], k[0], k[1]);
                        mma16816(s[t], qf[4], qf[5], qf[6], qf[7], k[2], k[3]);
                    }
#pragma unroll
                    for (int hf = 0; hf < 2; ++hf) {
                        const int u = hh * 2 + hf;
                        e0[u] = lo0 ? ((hf == 0 && nopast) ? -INFINITY : s[hf][hf * 2]) : s[hf + 1][hf * 2];
                        e1[u] = lo1 ? ((hf == 0 && nopast) ? -INFINITY : s[hf][hf * 2 + 1]) : s[hf + 1][hf * 2 + 1];
                        mx[u] = fmaxf(e0[u], e1[u]);
                    }
                }
#pragma unroll
                for (int o = 1; o < 4; o <<= 1)
#pragma unroll
                    for (int u = 0; u < 4; ++u) mx[u] = fmaxf(mx[u], __shfl_xor_sync(0xffffffffu, mx[u], o));
#pragma unroll
                for (int u = 0; u < 4; ++u) {
                    const float c = -mx[u] * sl2;
                    e0[u] = ex2(fmaf(e0[u], sl2, c)); e1[u] = ex2(fmaf(e1[u], sl2, c));
                    sum[u] = e0[u] + e1[u];
                }
#pragma unroll
                for (int o = 1; o < 4; o <<= 1)
#pragma unroll
                    for (int u = 0; u < 4; ++u) sum[u] += __shfl_xor_sync(0xffffffffu, sum[u], o);
#pragma unroll
                for (int u = 0; u < 4; ++u) {
                    const int h = u >> 1;
                    const float inv = rcp(sum[u]);
                    const uint32_t p = pack2(e0[u] * inv, e1[u] * inv);
                    const uint32_t* va = ((u & 1) ? v1 : v0) + 4 * h;
                    const uint32_t* vb = ((u & 1) ? v2 : v1) + 4 * h;
                    float o[2][4] = {};
#pragma unroll
                    for (int d = 0; d < 2; ++d) mma16816(o[d], va[2 * d], va[2 * d + 1], vb[2 * d], vb[2 * d + 1], p & lomask, p & ~lomask);
                    stsm4t((orow ^ ((u >> 1) << 6)) + pn * 8192 + (u & 1) * 1024, pack2(o[0][0], o[0][1]), pack2(o[0][2], o[0][3]), pack2(o[1][0], o[1][1]), pack2(o[1][2], o[1][3]));
                }
                fence_async_smem();
                __syncwarp();
                if (lane == 0) mbar_arrive(BAR_SFULL(sb, wg * 2 + pn));
                if (pn == 0) { CS(5); block_end(sb, 0); prepare(1, big); CS(3); }
            }
            CS(6);
            if (tid == 32) TL(41);
            mbar_wait(BAR_FULL(sb, 32 % NSLOT + wg), (32 / NSLOT) & 1);
            load_slab(xp, sb + (32 % NSLOT + wg) * SLOT);
#pragma unroll
            for (int e = 0; e < 32; ++e) hp[e] = __float_as_uint(big[e]);
            bar_sync(1 + wg, 128);
            if (tid == 0) { TL(6); TC(106); }
            if (tid == 128) TL(44);
            CS(7);
        }
        } else {
        {
            float ag[88], au[88];
            mainloop32<true, LAG>(ag, au, sb, wg, tw, r, EV_LAG1, 48, [](int) {}, [&] {
                Ring q = r; if (!wg) q.next();
                mbar_wait(BAR_EMPTY(sb, q.slot), q.par ^ 1);
            });
            if (tid == 0) { TL(10); TC(110); }
            if (tid == 128) TL(51);
            CS(22);
            {
                IDX();
                uint32_t h3[12];
                glu(h3, [&](int i) { return ag[64 + i]; }, [&](int i) { return au[64 + i]; });
#pragma unroll
                for (int k = 0; k < 3; ++k) stsm4(sb + (wg ? P3_SLOT1 : P3_SLOT0) * SLOT + 24576 + (pan_addr ^ (k << 5)), h3[4 * k], h3[4 * k + 1], h3[4 * k + 2], h3[4 * k + 3]);
            }
            glu(hp, [&](int i) { return ag[i]; }, [&](int i) { return au[i]; });
            if (tid == 0) { TL(11); TC(111); }
            if (tid == 128) TL(52);
            CS(23);
        }
        passes128<2, true>(hp, sb, wg, tw, r, stg);
        if (tid == 0) { TL(12); TC(112); }
        }
        {
            float acc[64], gf[32];
            mainloop64(acc, blk == 0, sb, wg, tw, r, [&] { put_h(hp, sb, wg, stg); }, [&] {
                mbar_wait(BAR_ONE(sb, EV_GA + blk), 0);
                unpack_slab(xs, xp);
                uint32_t gt[16];
#pragma unroll
                for (int cg = 0; cg < 16; ++cg) gt[cg] = lds32(sb + OFF_TAB + blk * 256 + cg * 16 + (tw & 3) * 4);
#pragma unroll
                for (int i = 0; i < 16; ++i) unpack2(gt[i], gf[2 * i], gf[2 * i + 1]);
            }, [&] { stg.acquire2(sb, wg); });
            if (tid == 0) { TL(blk ? 13 : 7); TC(blk ? 113 : 107); }
            if (tid == 128) TL(blk ? 57 : 42);
            CS(blk ? 30 : 10);
#pragma unroll
            for (int e = 0; e < 64; ++e) xs[e] = fmaf(gf[(e >> 2) * 2 + (e & 1)], acc[e], xs[e]);
        }
        if (blk) break;
        }
        {
            IDX();
#pragma unroll
            for (int p = 0; p < 2; ++p) {
                store_slab(xs, sb + OFF_STG + wg * 16384, 8192, pan_addr, 4 * p, 4 * p + 4);
                stg.publish(sb, wg, lane);
            }
            cluster_arrive();
            if (tid == 0) TL(14);
            CS(31);
        }
      }
    } else {
        if (warp == 8 && !aux && elect_one()) {
#pragma unroll
            for (int i = 0; i < 4; ++i) mbar_init(BAR_SREADY(sb, i), 1);
#pragma unroll
            for (int i = 0; i < 4; ++i) mbar_init(BAR_ONE(sb, EV_WIN + i), 1);
#pragma unroll
            for (int i = 0; i < 4; ++i) {
                mbar_expect_tx(BAR_SREADY(sb, i), 8192);
                tma_load3(sb + OFF_STG + i * 8192, &mp.x, j * 128 + (i & 1) * 64, m * 64 + (i >> 1) * 32, BAR_SREADY(sb, i));
            }
#pragma unroll 1
            for (int i = 0; i < 4; ++i) {
                mbar_expect_tx(BAR_ONE(sb, EV_WIN + i), 8192);
                tma_load(sb + 5 * SLOT + i * 8192, &mp.wm8, 2 * i * 6144 + (m * 8 + j) * 16, 0, BAR_ONE(sb, EV_WIN + i));
                tma_load(sb + 5 * SLOT + i * 8192 + 4096, &mp.wm8, (2 * i + 1) * 6144 + (m * 8 + j) * 16, 0, BAR_ONE(sb, EV_WIN + i));
            }
        }
        __syncwarp();
        asm volatile("setmaxnreg.dec.sync.aligned.u32 56;");
        if (elect_one()) {
            if (warp == 8) {
                prefetch_map(&mp.wqkv); prefetch_map(&mp.wmod);
            } else if (warp < 11) {
                mbar_init(BAR_EMPTY(sb, NSLOT), 1);
#pragma unroll
                for (int i = 0; i < 2; ++i) { mbar_init(BAR_SFULL(sb, (warp - 9) * 2 + i), 4); if (aux) mbar_init(BAR_SREADY(sb, (warp - 9) * 2 + i), 1); }
#pragma unroll
                for (int i = 0; i < 3; ++i) {
                    mbar_init(BAR_EMPTY(sb, (warp - 9) * 3 + i), 4);
                    mbar_init(BAR_FULL(sb, (warp - 9) * 3 + i), 1); mbar_init(BAR_FULL(sb, (warp - 9) * 3 + i) + AF_REL, 1);
                }
            } else {
#pragma unroll
                for (int i = EV_P0; i < EV_COUNT; ++i) mbar_init(BAR_ONE(sb, i), i == EV_P0 ? 8 : 1);
            }
            asm volatile("fence.mbarrier_init.release.cluster;" ::: "memory");
        }
        __syncwarp();
        cluster_arrive();
        ep = 0;
        if (warp != 8 || aux) ep = flag_get(g_flags + FL_DONE);
        cluster_wait();
        ep = __shfl_sync(0xffffffffu, ep, 0) / NCTA + 1;
        if (warp == 8) {
            const bool el = elect_one();
            Ring r{0, 1};
            if (aux) {
                {
                    uint32_t n = 0;
                    while (!__all_sync(0xffffffffu, ld_pkt16(pt.mail->mod1 + 256).z == ep)) { SPIN_GUARD(n); __nanosleep(200); }
                }
#pragma unroll 1
                for (int it = 0; it < 64; ++it) {
                    const int col = 2048 + (it >> 4) * 1024 + j * 256;
                    mbar_wait(BAR_EMPTY(sb, r.slot), r.par);
                    const uint32_t st = sb + r.slot * SLOT, fb = BAR_FULL(sb, r.slot);
                    if (el) {
                        mbar_expect_tx(fb, 32768);
#pragma unroll
                        for (int b = 0; b < 4; ++b) tma_load(st + b * 8192, &mp.wmod, col + b * 64, (it & 15) * 64, fb);
                    }
                    r.next();
                }
                mbar_wait(BAR_ONE(sb, EV_P0), 0);
                const CUtensorMap* wm = rank ? &mp.wu : &mp.wg;
#pragma unroll 1
                for (int g = 0; g < 128; ++g) {
                    const int mx = (j >> 1) * 8 + (g >> 5) * 2 + rank, k0 = ((g & 14) << 6) + ((g & 16) << 2) + ((g & 1) << 5);
                    if (!(g & 15)) {
                        uint32_t n = 0;
                        while (!__all_sync(0xffffffffu, (int32_t)(flag_get(g_flags + FL_PROG + fidx(mx, lane >> 4, (lane & 14) | ((g >> 4) & 1))) - (ep * 8 + ST_H2)) >= 0)) { SPIN_GUARD(n); __nanosleep(300); }
                    }
                    mbar_wait(BAR_EMPTY(sb, r.slot), r.par);
                    const uint32_t st = sb + r.slot * SLOT, fb = BAR_FULL(sb, r.slot);
                    if (el) {
                        mbar_expect_tx(fb, 24576);
                        tma_load_mc(st + 8192 + rank * 4096, wm, HC3, k0, fb);
                        tma_load_mc(st + 16384 + rank * 4096, wm, HC3 + 64, k0, fb);
                        tma_load(st, &mp.h2l, k0, mx * 128, fb);
                    }
                    r.next();
                }
            } else {
#pragma unroll 1
                for (int it = 0; it < 32; ++it) {
                    const int cb = j * 128 + rank * 64, k0 = kof(it, 2, j);
                    if (it == BW0) mbar_wait(BAR_ONE(sb, BWEV), 0);
                    if (it == BW1) mbar_wait(BAR_ONE(sb, EV_PAR), 0);
                    if (it == 5) mbar_wait(BAR_ONE(sb, EV_P0), 0);
                    if (it == AG0) mbar_wait(BAR_ONE(sb, (AGW & 1) ? EV_AGO : EV_FGO), 0);
                    mbar_wait(BAR_EMPTY(sb, r.slot), r.par);
                    const uint32_t st = sb + r.slot * SLOT, fb = BAR_FULL(sb, r.slot);
                    if (el) {
                        mbar_expect_tx(fb, it < 4 ? 24576 : 28672);
                        tma_load_mc(st + 24576 - rank * 16384, &mp.wqkv, 1024 + cb, k0, fb);
                        tma_load_mc(st + 28672 - rank * 16384, &mp.wqkv, 2048 + cb, k0, fb);
                        tma_load_mc(st + 16384 + rank * 4096, &mp.wqkv, cb, k0, fb);
                        if (it < 4) mbar_arrive(fb + AF_REL);
                        if (it == PFWO + (m >> 1)) { tma_prefetch(&mp.wo, j * 128, m * 64); tma_prefetch(&mp.wo, j * 128 + 64, m * 64); }
                        if (it >= PFG && it < PFG + PFN && (it & 7) == grp) {
                            const int kp = kof(it - PFG + PFO, 2, j);
                            tma_prefetch(rank ? &mp.wu : &mp.wg, hcol(0, j), kp); tma_prefetch(rank ? &mp.wu : &mp.wg, hcol(0, j) + 64, kp);
                            asm volatile("cp.async.bulk.prefetch.tensor.3d.L2.global [%0, {%1, %2, %3}];" :: "l"(rank ? &mp.wu3 : &mp.wg3), "r"(0), "r"(j), "r"(kp) : "memory");
                        }
                    }
                    r.next();
                }
                if (el) mbar_arrive(BAR_ONE(sb, EV_KV));
#pragma unroll 1
                for (int it = 0; it < 16; ++it) {
                    const int k0 = kof(it, 1, j);
                    if (it == AG1) mbar_wait(BAR_ONE(sb, (AGW & 2) ? EV_AGO1 : EV_FGO1), 0);
                    mbar_wait(BAR_EMPTY(sb, r.slot), r.par);
                    const uint32_t st = sb + r.slot * SLOT, fb = BAR_FULL(sb, r.slot);
                    if (el) {
                        mbar_expect_tx(fb, it < 2 ? 32768 : 24576);
                        tma_load_mc(st + 16384 + rank * 8192, &mp.wo, j * 128 + rank * 64, k0, fb);
                        if (it < 2) {
                            tma_load3(st, &mp.x, j * 128, m * 64 + it * 32, fb); tma_load3(st + 8192, &mp.x, j * 128 + 64, m * 64 + it * 32, fb);
                            mbar_arrive(fb + AF_REL);
                        }
                        if (it == 6) { prefetch_map(rank ? &mp.wu : &mp.wg); prefetch_map(rank ? &mp.wu3 : &mp.wg3); }
                    }
                    r.next();
                }
                const CUtensorMap* wm = rank ? &mp.wu : &mp.wg;
#pragma unroll 1
                for (int g = 0; g < 96; ++g) {
                    if (g == AG2) mbar_wait(BAR_ONE(sb, (AGW & 4) ? EV_AGO2 : EV_FGO2), 0);
                    const int p = g >> 5, cb = hcol(p, j), k0 = p == 0 ? kof(g, 2, j) : (g & 31) * 32;
                    mbar_wait(BAR_EMPTY(sb, r.slot), r.par);
                    const uint32_t st = sb + r.slot * SLOT, fb = BAR_FULL(sb, r.slot);
                    if (el) {
                        mbar_expect_tx(fb, (g < 4 || p > 0) ? 24576 : 28672);
                        tma_load_mc(st + 8192 + rank * 4096, wm, cb, k0, fb);
                        tma_load_mc(st + 16384 + rank * 4096, wm, cb + 64, k0, fb);
                        if (p == 0) tma_load3_mc(st + 24576 + rank * 4096, rank ? &mp.wu3 : &mp.wg3, j, k0, fb);
                        else tma_load(st, &mp.h2l, k0, m * 128, fb);
                        if (g < 4) mbar_arrive(fb + AF_REL);
                        if (g == 60) prefetch_map(&mp.wd);
                    }
                    r.next();
                }
#pragma unroll 1
                for (int g = 0; g < 56; ++g) {
                    if (g == 0 || (g & 15) == 6 && g > 6) mbar_wait(BAR_ONE(sb, EV_H0 + (g >> 4)), 0);
                    const int k0 = g * 64;
                    mbar_wait(BAR_EMPTY(sb, r.slot), r.par);
                    const uint32_t st = sb + r.slot * SLOT, fb = BAR_FULL(sb, r.slot);
                    if (el) {
                        mbar_expect_tx(fb, 32768);
                        tma_load_mc(st + 16384 + rank * 8192, &mp.wd, j * 128 + rank * 64, k0, fb);
                        tma_load(st, &mp.hb, k0, m * 128, fb); tma_load(st + 8192, &mp.hb, k0, m * 128 + 64, fb);
                    }
                    r.next();
                }
            }
        } else if (aux) {
            if (warp < 11) {
                const uint32_t w = warp - 9;
                const bool el = elect_one();
#pragma unroll 1
                for (int p = 0; p < 4; ++p) {
                    const int mx = (j >> 1) * 8 + p * 2 + rank;
                    if (el) { mbar_arrive(BAR_SREADY(sb, w * 2)); mbar_arrive(BAR_SREADY(sb, w * 2 + 1)); }
                    mbar_wait2(BAR_SFULL(sb, w * 2), BAR_SFULL(sb, w * 2 + 1), p & 1);
                    if (p < 3) pause(w ? HD1 : HD0);
                    if (el) tma_store(&mp.hb, HC3, mx * 128 + w * 64, sb + OFF_STG + w * 16384);
                    if (p < 3) pause(HP);
                    if (el) {
                        tma_store(&mp.hb, HC3 + 64, mx * 128 + w * 64, sb + OFF_STG + w * 16384 + 8192);
                        bulk_commit(); bulk_wait_fence(); flag_set(g_flags + FL_AUX + mx * 2 + w, ep * 8 + ST_H + 3);
                    }
                }
            }
        } else if (warp == 11) {
            const bool el = elect_one();
            const int row0 = m * 128;
            const uint32_t* const fl = g_flags + FL_PROG + fidx(m, lane >> 4, kof(lane & 15, 1, j) >> 6);
            if (el) { prefetch_map(&mp.h1h); prefetch_map(&mp.h2h); prefetch_map(&mp.h2l); }
            auto gate = [&](int vec, int ev) {
                uint4 v; uint32_t n = 0;
                while (true) {
                    v = ld_pkt2(g_mod + vec * 512 + j * 64 + lane * 2);
                    if (__all_sync(0xffffffffu, v.y == ep && v.w == ep)) break;
                    SPIN_GUARD(n); __nanosleep(300);
                }
                asm volatile("st.shared.v2.u32 [%0], {%1, %2};" :: "r"(sb + OFF_TAB + (ev - EV_GA) * 256 + lane * 8), "r"(v.x), "r"(v.z) : "memory");
                __syncwarp();
                if (lane == 0) mbar_arrive(BAR_ONE(sb, ev));
            };
            {
                const uint4* pk = pt.mail->mod1 + grp * 512 + j * 32 + lane;
                uint4 a, b; uint32_t n = 0;
                mbar_wait(BAR_ONE(sb, EV_WIN3), 0);
                while (true) {
                    a = ld_pkt16(pk); b = ld_pkt16(pk + 256);
                    if (__all_sync(0xffffffffu, a.z == ep && b.z == ep)) break;
                    SPIN_GUARD(n);
                }
                sts128(sb + OFF_PAR + lane * 16, a.x, a.y, b.x, b.y);
                __syncwarp();
                if (lane == 0) { mbar_arrive(BAR_ONE(sb, EV_PAR)); TL(46); }
            }
            mbar_wait(BAR_ONE(sb, EV_P0), 0);
            Ring r{0, 1};
#pragma unroll 1
            for (int ph = 0; ph < 3; ++ph) {
                const int sh = ph == 1 ? 1 : 2, nst = 8 << sh;
                const uint32_t half = 16384 >> sh, target = ep * 8 + ST_H1 + ph;
                const CUtensorMap* tm = ph == 0 ? &mp.h1h : ph == 1 ? &mp.o : &mp.h2h;
                if (ph == 1) {
                    gate(2, EV_GA);
                    mbar_wait(BAR_SREADY(sb, 1), 1);
#pragma unroll 1
                    for (int i = 0; i < 2; ++i)
                        fetch_halo<1>(g_halo + ((m - 1) * 8 + j) * 512 + i * 256 + 128 + lane, m == 0, sb + OFF_STG + 8192 + i * 4096 + lane * 16,
                                      [&] { __syncwarp(); if (el) mbar_arrive(BAR_ONE(sb, EV_TAIL + 2 * i)); });
                    CS(32);
                }
                if (ph == 2) {
                    uint32_t n = 0;
                    while ((int32_t)(flag_get(g_flags + FL_LN2) - ep * 8) < 0) { SPIN_GUARD(n); __nanosleep(200); }
                    const uint4 v = __ldcg((const uint4*)(g_par2 + j * 128) + lane);
                    sts128(sb + OFF_PAR + lane * 16, v.x, v.y, v.z, v.w);
                    __syncwarp();
                    if (lane == 0) mbar_arrive(BAR_ONE(sb, EV_LN2));
                }
                const uint32_t lw = ~lane & 1, lt = lane >> 1, ls = (r.slot + lt) % NSLOT, lk = kof(lt, sh, j), lb = BAR_FULL(sb, ls) + (lw ? 0 : AF_REL);
                const uint32_t* const lf = g_flags + FL_PROG + fidx(m, lw, lk >> 6);
                int fr = 1 << sh;
                uint32_t todo = 0x3ffffu >> (2 * fr) << (2 * fr), have = ~todo, n = 0, v = 0;
                r.skip(fr);
#pragma unroll 1
                for (; fr < NSLOT; ++fr) { mbar_wait(BAR_EMPTY(sb, r.slot), r.par); r.next(); }
                if (ph == XST - 1) CS(33);
                do {
                    if (!((have >> lane) & 1)) v = flag_get(lf);
                    while (fr < 9 && mbar_test(BAR_EMPTY(sb, r.slot), r.par)) { ++fr; r.next(); }
                    SPIN_GUARD(n);
                    have |= __ballot_sync(0xffffffffu, (int32_t)(v - target) >= 0);
                    const uint32_t go = have & todo & ((1u << (2 * fr)) - 1);
                    if ((go >> lane) & 1) {
                        if (!lw) mbar_expect_tx(lb, half);
                        tma_load(sb + ls * SLOT + lw * half, tm, lk, row0 + lw * 64, lb);
                    }
                    __syncwarp();
                    if (lane < 2 && (todo & (0x555u << lane)) && !(todo & ~go & (0x555u << lane))) mbar_arrive(BAR_ONE(sb, (lane ? EV_FGO : EV_AGO) + ph));
                    if (ph == XST - 1) { if (go & (1u << (2 << sh))) CS(34); if (go & (2u << (2 << sh))) CS(35); if (todo & 0x555u) CS(36); if (todo & 0xaaau) CS(37); }
                    todo &= ~go;
                } while (~have);
                if (ph == XST - 1) CS(38);
                int k = kof(fr, sh, j);
#pragma unroll 1
                for (; fr < nst; ++fr) {
                    if (fr == 9 || fr == 18) {
                        const uint32_t skip = fr == 9 << (sh - 1) ? 0 : ~0x01fc01fcu;
                        while (~(__ballot_sync(0xffffffffu, (int32_t)(flag_get(fl) - target) >= 0) | skip)) SPIN_GUARD(n);
                    }
                    const uint32_t st = sb + r.slot * SLOT, fb = BAR_FULL(sb, r.slot);
                    mbar_wait(BAR_EMPTY(sb, r.slot), r.par);
                    if (el) {
                        tma_load(st + half, tm, k, row0 + 64, fb);
                        mbar_expect_tx(fb + AF_REL, half);
                        tma_load(st, tm, k, row0, fb + AF_REL);
                    }
                    if (ph == XST - 1 && fr == 9) CS(39);
                    r.next();
                    k = kof(fr + 1, sh, j);
                }
            }
#pragma unroll 1
            for (int p = 0; p < 4; ++p) {
                const uint32_t* f = p < 3 ? fl : g_flags + FL_AUX + m * 2 + (lane & 1);
                uint32_t n = 0;
                while (!__all_sync(0xffffffffu, (int32_t)(flag_get(f) - (ep * 8 + ST_H + p)) >= 0)) { SPIN_GUARD(n); __nanosleep(300); }
                if (el) mbar_arrive(BAR_ONE(sb, EV_H0 + p));
                if (p == 0) gate(5, EV_GB);
            }
        } else {
            const uint32_t w = warp - 9;
            const int row0 = m * 128 + w * 64;
            const uint32_t stg = sb + OFF_STG + w * 16384;
            uint32_t* const fl = g_flags + FL_PROG + fidx(m, w, 2 * j);
            uint32_t b = 0, par = 0;
            const bool el = elect_one();
            auto store = [&](const CUtensorMap* tm, int col, bool nat = false) {
                mbar_wait(BAR_SFULL(sb, w * 2 + b), (par >> b) & 1);
                par ^= 1u << b;
                if (el) {
                    if (nat) tma_store3(tm, col, row0 >> 1, 0, stg + b * 8192); else tma_store(tm, col, row0, stg + b * 8192);
                    bulk_commit();
                }
                b ^= 1;
            };
            auto send2 = [&](const CUtensorMap* tm, const uint32_t* buf, int step) {
                const uint32_t* const q = buf + (size_t)((row0 + lane) * (D_ / 2) + j * 64 + 31);
                store(tm, j * 128);
                if (step == XST) CS(33);
                uint32_t z = landed(el, q, D_ / 2, pt.zero);
                if (el) flag_set(fl, ep * 8 + step + z);
                if (step == XST) CS(34);
                if (step != ST_O) { mbar_wait(BAR_ONE(sb, EV_FGO + step - ST_H1), 0); pause(step == ST_H1 ? (w ? P1H : P1H + 1000) : w ? P2L : P2F); }
                store(tm, j * 128 + 64);
                if (step == XST) CS(35);
                z = landed(el, q + 32, D_ / 2, pt.zero);
                if (el) flag_set(fl + 1, ep * 8 + step + z);
                if (step == XST) CS(36);
            };
            auto free2 = [&]() { if (el) { mbar_arrive(BAR_SREADY(sb, w * 2)); mbar_arrive(BAR_SREADY(sb, w * 2 + 1)); } };
            if (el) { prefetch_map(&mp.h1s); prefetch_map(&mp.o); prefetch_map(&mp.h2s); prefetch_map(&mp.hb); prefetch_map(&mp.out); prefetch_map(&mp.wo); }
            if (el) { flag_set(fl, ep * 8); flag_set(fl + 1, ep * 8); }
            send2(&mp.h1s, pt.h1, ST_H1);
            if (w == 0) TL(47);
            free2();
            mbar_wait(BAR_ONE(sb, EV_KV), 0);
            mbar_wait(BAR_SREADY(sb, 0), 1);
            fetch_halo<1>(g_halo + ((m - 1) * 8 + j) * 512 + w * 256 + lane, m == 0, sb + OFF_STG + w * 4096 + lane * 16, [&] { bar_arrive(NB_TAIL + 2 * w, 64); CS(38); });
            send2(&mp.o, pt.o, ST_O);
            if (w == 0) TL(40); else TL(38);
            free2();
            send2(&mp.h2s, pt.o, ST_H2);
            if (el) { prefetch_map(&mp.hb); prefetch_map(&mp.hb3); }
            if (w == 0) TL(37);
            free2();
#pragma unroll 1
            for (int p = 0; p < 3; ++p) {
                const int col = hcol(p, j);
                mbar_wait(BAR_SFULL(sb, w * 2), par & 1);
                pause(w ? HD1 : HD0); store(&mp.hb, col);
                pause(HP); store(&mp.hb, col + 64);
                if (p == 0) {
                    pause(HP);
                    if (el) { tma_store3(&mp.hb3, 0, j, row0, sb + (w ? P3_SLOT1 : P3_SLOT0) * SLOT + 24576); bulk_commit(); }
                }
                if (el) bulk_wait_read();
                free2();
                if (el) { bulk_wait_fence(); flag_set(fl, ep * 8 + ST_H + p); flag_set(fl + 1, ep * 8 + ST_H + p); }
            }
            cluster_arrive_early = true;
            cluster_arrive();
            store(&mp.out, j * 128, true); store(&mp.out, j * 128 + 64, true);
            if (el) bulk_wait_read();
        }
        __syncwarp();
    }
    if (aux || (wg == 2 && !cluster_arrive_early)) cluster_arrive();
    cluster_wait();
    if (KDEBUG == 5) __syncthreads();
    if (tid == 0) {
        TL(15);
        flag_add(pt.mail->flags + FL_DONE);
    }
}

typedef CUresult (*EncodeFn)(CUtensorMap*, CUtensorMapDataType, cuuint32_t, void*, const cuuint64_t*, const cuuint64_t*, const cuuint32_t*,
                             const cuuint32_t*, CUtensorMapInterleave, CUtensorMapSwizzle, CUtensorMapL2promotion, CUtensorMapFloatOOBfill);

void make_map(EncodeFn fn, CUtensorMap* m, const void* ptr, uint64_t rows, uint64_t cols, uint32_t brows, uint32_t bcols) {
    cuuint64_t dims[2] = {cols, rows}, strides[1] = {cols * 2};
    cuuint32_t box[2] = {bcols, brows}, es[2] = {1, 1};
    fn(m, CU_TENSOR_MAP_DATA_TYPE_BFLOAT16, 2, (void*)ptr, dims, strides, box, es, CU_TENSOR_MAP_INTERLEAVE_NONE,
       bcols == 64 ? CU_TENSOR_MAP_SWIZZLE_128B : bcols == 32 ? CU_TENSOR_MAP_SWIZZLE_64B : CU_TENSOR_MAP_SWIZZLE_NONE, CU_TENSOR_MAP_L2_PROMOTION_L2_256B, CU_TENSOR_MAP_FLOAT_OOB_FILL_NONE);
}

void make_map3(EncodeFn fn, CUtensorMap* m, const void* ptr) {
    cuuint64_t dims[3] = {D_, S_ / 2, 2}, strides[2] = {4 * D_, 2 * D_};
    cuuint32_t box[3] = {64, 32, 2}, es[3] = {1, 1, 1};
    fn(m, CU_TENSOR_MAP_DATA_TYPE_BFLOAT16, 3, (void*)ptr, dims, strides, box, es, CU_TENSOR_MAP_INTERLEAVE_NONE,
       CU_TENSOR_MAP_SWIZZLE_128B, CU_TENSOR_MAP_L2_PROMOTION_L2_256B, CU_TENSOR_MAP_FLOAT_OOB_FILL_NONE);
}

void make_map48(EncodeFn fn, CUtensorMap* m, const void* ptr, uint64_t rows, uint32_t brows) {
    cuuint64_t dims[3] = {48, 8, rows}, strides[2] = {96, 2 * F_};
    cuuint32_t box[3] = {64, 1, brows}, es[3] = {1, 1, 1};
    fn(m, CU_TENSOR_MAP_DATA_TYPE_BFLOAT16, 3, (void*)ptr, dims, strides, box, es, CU_TENSOR_MAP_INTERLEAVE_NONE,
       CU_TENSOR_MAP_SWIZZLE_128B, CU_TENSOR_MAP_L2_PROMOTION_L2_256B, CU_TENSOR_MAP_FLOAT_OOB_FILL_NONE);
}

}

extern "C" void kernel_launch(void* const* d_in, const int* in_sizes, int n_in, void* d_out, int out_size) {
    (void)in_sizes; (void)n_in; (void)out_size;
    void* fnp = nullptr;
    cudaDriverEntryPointQueryResult qr;
    cudaGetDriverEntryPoint("cuTensorMapEncodeTiled", &fnp, cudaEnableDefault, &qr);
    EncodeFn fn = (EncodeFn)fnp;
    void *h1, *o, *h2, *hb, *mail;
    cudaGetSymbolAddress(&h1, g_h1);
    cudaGetSymbolAddress(&mail, g_mail);
    cudaGetSymbolAddress(&o, g_o);
    cudaGetSymbolAddress(&hb, g_hb);
    h2 = o;
    Maps mp;
    make_map(fn, &mp.h1h, h1, S_, D_, 64, 32);
    make_map(fn, &mp.h2h, h2, S_, D_, 64, 32);
    make_map(fn, &mp.h1s, h1, S_, D_, 64, 64);
    make_map(fn, &mp.o, o, S_, D_, 64, 64);
    make_map(fn, &mp.h2l, h2, S_, D_, 128, 32);
    make_map(fn, &mp.h2s, h2, S_, D_, 64, 64);
    make_map(fn, &mp.hb, hb, S_, F_, 64, 64);
    make_map(fn, &mp.wqkv, d_in[1], D_, 3 * D_, 32, 64);
    make_map(fn, &mp.wo, d_in[2], D_, D_, 64, 64);
    make_map(fn, &mp.wg, d_in[4], D_, F_, 32, 64);
    make_map(fn, &mp.wu, d_in[5], D_, F_, 32, 64);
    make_map(fn, &mp.wd, d_in[6], F_, D_, 64, 64);
    make_map(fn, &mp.wmod, d_in[8], D_, 6 * D_, 64, 64);
    make_map(fn, &mp.wm8, d_in[8], D_ / 8, 8 * 6 * D_, 128, 16);
    make_map3(fn, &mp.x, d_in[0]);
    make_map3(fn, &mp.out, d_out);
    make_map48(fn, &mp.wg3, d_in[4], D_, 32);
    make_map48(fn, &mp.wu3, d_in[5], D_, 32);
    make_map48(fn, &mp.hb3, hb, S_, 64);
    cudaFuncSetAttribute(fused_block_kernel, cudaFuncAttributeMaxDynamicSharedMemorySize, SMEM_BYTES);
    cudaLaunchConfig_t cfg = {};
    cfg.gridDim = dim3(NCTA); cfg.blockDim = dim3(384); cfg.dynamicSmemBytes = SMEM_BYTES; cfg.stream = cudaStreamPerThread;
    cudaLaunchAttribute at[1];
    at[0].id = cudaLaunchAttributeClusterDimension; at[0].val.clusterDim.x = 2; at[0].val.clusterDim.y = 1; at[0].val.clusterDim.z = 1;
    cfg.attrs = at; cfg.numAttrs = 1;
    const Ptrs pt{(const __nv_bfloat16*)d_in[7], (Mail*)mail, (const uint32_t*)h1, (const uint32_t*)o, 0};
    cudaLaunchKernelEx(&cfg, fused_block_kernel, pt, mp);
}
```

```cpp
#include <cuda_runtime.h>
#include <cuda_bf16.h>
#include <cuda.h>
#include <stdint.h>
#include <stddef.h>

#define LAG 4
#define LAGS 4
#define LAGW 2
#define LAGQ 4
#define PFWO 12
#define P1H 3000
#define AGW 2
#define CSW 0
#define LWAIT 2
#define BW0 0
#define BWEV EV_WIN
#define BW1 3
#define PDLY 500
#define HD1 3600
#define HD0 1500
#define HP 2600
#define LAGD 4
#define MIDD 30
#define XST ST_O
#define AG0 6
#define AG1 6
#define AG2 8
#define PFG 8
#define PFN 24
#define PFO 0
#define P2L 2000
#define P2F 3000
#define PUT1 5
#define PUT0 10
#define PUTD1 5
#define PUTD0 10
#define FRCAP 8
#define KDEBUG 0

namespace {

constexpr int S_ = 2048, D_ = 1024, F_ = 3584;
constexpr int NCTA = 132;
constexpr int NSLOT = 6;
constexpr uint32_t SLOT = 32768;
constexpr uint32_t OFF_STG = NSLOT * SLOT;
constexpr uint32_t OFF_BAR = OFF_STG + 32768;
constexpr uint32_t OFF_PAR = OFF_BAR + 512;
constexpr uint32_t OFF_TAB = OFF_PAR + 768;
constexpr uint32_t OFF_TL = OFF_PAR + 2048;
constexpr uint32_t SMEM_BYTES = OFF_TL + (KDEBUG ? 512 : 0);
constexpr uint32_t P3_SLOT1 = (32 + 16 + 32) % NSLOT, P3_SLOT0 = (P3_SLOT1 + 1) % NSLOT;

constexpr int ST_H1 = 1, ST_O = 2, ST_H2 = 3, ST_H = 4, FL_DONE = 0, FL_LN2 = 1, FL_AUX = 32, FL_PROG = 64;

struct Maps {
    CUtensorMap h1h, h1s, o, h2h, h2l, h2s, hb, wqkv, wo, wg, wu, wd, wmod, wm8, x, out, wg3, wu3, hb3;
};

struct Mail {
    uint32_t flags[16 * 32 + 64];
    uint2 mod[6 * D_ / 2];
    uint4 mod1[8 * 512];
    uint4 st1[128 * 512];
    uint32_t par2[D_];
    uint4 halo[128 * 512];
};
struct Ptrs { const __nv_bfloat16* c; Mail* mail; const uint32_t *h1, *o; uint32_t zero; };

__device__ __align__(128) Mail g_mail;
__device__ __align__(128) __nv_bfloat16 g_h1[S_ * D_];
__device__ __align__(128) __nv_bfloat16 g_o[S_ * D_];
__device__ __align__(128) __nv_bfloat16 g_hb[S_ * F_];
#define TL(i) do {} while (0)
#define TC(i) do {} while (0)
#define TS(g, which) do {} while (0)
#define CS(i) do {} while (0)

__device__ __forceinline__ uint32_t smem_u32(const void* p) { return (uint32_t)__cvta_generic_to_shared(p); }
__device__ __forceinline__ void mbar_init(uint32_t bar, uint32_t cnt) { asm volatile("mbarrier.init.shared::cta.b64 [%0], %1;" :: "r"(bar), "r"(cnt) : "memory"); }
__device__ __forceinline__ void mbar_expect_tx(uint32_t bar, uint32_t bytes) { asm volatile("mbarrier.arrive.expect_tx.shared::cta.b64 _, [%0], %1;" :: "r"(bar), "r"(bytes) : "memory"); }
__device__ __forceinline__ void mbar_arrive(uint32_t bar) { asm volatile("mbarrier.arrive.shared::cta.b64 _, [%0];" :: "r"(bar) : "memory"); }
__device__ __forceinline__ void mbar_arrive_cta(uint32_t bar, uint32_t cta) {
    asm volatile("{\n.reg .b32 r;\nmapa.shared::cluster.u32 r, %0, %1;\nmbarrier.arrive.shared::cluster.b64 _, [r];\n}" :: "r"(bar), "r"(cta) : "memory");
}
__device__ __forceinline__ void mbar_wait(uint32_t bar, uint32_t parity) {
    asm volatile("{\n.reg .pred p;\n.reg .u32 n;\nmov.u32 n, 0;\n"
        "W_LOOP:\nmbarrier.try_wait.parity.shared::cta.b64 p, [%0], %1;\n@p bra W_DONE;\n"
        "add.u32 n, n, 1;\nsetp.lt.u32 p, n, 0x400000;\n@p bra W_LOOP;\ntrap;\nW_DONE:\n}" :: "r"(bar), "r"(parity) : "memory");
}
__device__ __forceinline__ void mbar_wait2(uint32_t b0, uint32_t b1, uint32_t parity) {
    asm volatile("{\n.reg .pred p, q;\n.reg .u32 n;\nmov.u32 n, 0;\n"
        "W_LOOP:\nmbarrier.try_wait.parity.shared::cta.b64 p, [%0], %2;\nmbarrier.try_wait.parity.shared::cta.b64 q, [%1], %2;\nand.pred p, p, q;\n@p bra W_DONE;\n"
        "add.u32 n, n, 1;\nsetp.lt.u32 p, n, 0x400000;\n@p bra W_LOOP;\ntrap;\nW_DONE:\n}" :: "r"(b0), "r"(b1), "r"(parity) : "memory");
}
__device__ __forceinline__ bool mbar_test(uint32_t bar, uint32_t parity) {
    uint32_t r; asm volatile("{\n.reg .pred p;\nmbarrier.test_wait.parity.shared::cta.b64 p, [%1], %2;\nselp.u32 %0, 1, 0, p;\n}" : "=r"(r) : "r"(bar), "r"(parity) : "memory"); return r;
}
__device__ __forceinline__ bool mbar_test2(uint32_t b0, uint32_t b1, uint32_t parity) {
    uint32_t r;
    asm volatile("{\n.reg .pred p, q;\nmbarrier.test_wait.parity.shared::cta.b64 p, [%1], %3;\nmbarrier.test_wait.parity.shared::cta.b64 q, [%2], %3;\n"
        "and.pred p, p, q;\nselp.u32 %0, 1, 0, p;\n}" : "=r"(r) : "r"(b0), "r"(b1), "r"(parity) : "memory");
    return r;
}
__device__ __forceinline__ void tma_load3(uint32_t dst, const CUtensorMap* m, int c0, int c1, uint32_t bar) {
    asm volatile("cp.async.bulk.tensor.3d.shared::cluster.global.mbarrier::complete_tx::bytes [%0], [%1, {%3, %4, %5}], [%2];"
        :: "r"(dst), "l"(m), "r"(bar), "r"(c0), "r"(c1), "r"(0) : "memory");
}
__device__ __forceinline__ void tma_store3(const CUtensorMap* m, int c0, int c1, int c2, uint32_t src) {
    asm volatile("cp.async.bulk.tensor.3d.global.shared::cta.bulk_group [%0, {%2, %3, %4}], [%1];" :: "l"(m), "r"(src), "r"(c0), "r"(c1), "r"(c2) : "memory");
}
__device__ __forceinline__ void tma_load3_mc(uint32_t dst, const CUtensorMap* m, int c1, int c2, uint32_t bar) {
    asm volatile("cp.async.bulk.tensor.3d.shared::cluster.global.mbarrier::complete_tx::bytes.multicast::cluster.L2::cache_hint [%0], [%1, {%3, %4, %5}], [%2], %6, %7;"
        :: "r"(dst), "l"(m), "r"(bar), "r"(0), "r"(c1), "r"(c2), "h"((uint16_t)3), "l"(0x12F0000000000000ull) : "memory");
}
__device__ __forceinline__ void tma_load(uint32_t dst, const CUtensorMap* m, int c0, int c1, uint32_t bar) {
    asm volatile("cp.async.bulk.tensor.2d.shared::cluster.global.mbarrier::complete_tx::bytes [%0], [%1, {%3, %4}], [%2];"
        :: "r"(dst), "l"(m), "r"(bar), "r"(c0), "r"(c1) : "memory");
}
__device__ __forceinline__ void tma_load_mc(uint32_t dst, const CUtensorMap* m, int c0, int c1, uint32_t bar) {
    asm volatile("cp.async.bulk.tensor.2d.shared::cluster.global.mbarrier::complete_tx::bytes.multicast::cluster.L2::cache_hint [%0], [%1, {%3, %4}], [%2], %5, %6;"
        :: "r"(dst), "l"(m), "r"(bar), "r"(c0), "r"(c1), "h"((uint16_t)3), "l"(0x12F0000000000000ull) : "memory");
}
__device__ __forceinline__ void tma_prefetch(const CUtensorMap* m, int c0, int c1) {
    asm volatile("cp.async.bulk.prefetch.tensor.2d.L2.global [%0, {%1, %2}];" :: "l"(m), "r"(c0), "r"(c1) : "memory");
}
__device__ __forceinline__ void tma_store(const CUtensorMap* m, int c0, int c1, uint32_t src) {
    asm volatile("cp.async.bulk.tensor.2d.global.shared::cta.bulk_group [%0, {%2, %3}], [%1];" :: "l"(m), "r"(src), "r"(c0), "r"(c1) : "memory");
}
__device__ __forceinline__ void bulk_commit() { asm volatile("cp.async.bulk.commit_group;" ::: "memory"); }
__device__ __forceinline__ void bulk_wait_read() { asm volatile("cp.async.bulk.wait_group.read 0;" ::: "memory"); }
__device__ __forceinline__ void fence_async_smem() { asm volatile("fence.proxy.async.shared::cta;" ::: "memory"); }
__device__ __forceinline__ void prefetch_map(const CUtensorMap* m) { asm volatile("prefetch.tensormap [%0];" :: "l"(m) : "memory"); }
__device__ __forceinline__ void wg_fence() { asm volatile("wgmma.fence.sync.aligned;" ::: "memory"); }
__device__ __forceinline__ void wg_commit() { asm volatile("wgmma.commit_group.sync.aligned;" ::: "memory"); }
template <int N> __device__ __forceinline__ void wg_wait() { asm volatile("wgmma.wait_group.sync.aligned %0;" :: "n"(N) : "memory"); }
__device__ __forceinline__ void bar_sync(int id, int n) { asm volatile("bar.sync %0, %1;" :: "r"(id), "r"(n) : "memory"); }
__device__ __forceinline__ void bar_arrive(int id, int n) { asm volatile("bar.arrive %0, %1;" :: "r"(id), "r"(n) : "memory"); }
__device__ __forceinline__ void flag_add(uint32_t* f) { asm volatile("red.relaxed.gpu.global.add.u32 [%0], 1;" :: "l"(f) : "memory"); }
__device__ __forceinline__ void flag_set(uint32_t* f, uint32_t v) { asm volatile("red.relaxed.gpu.global.max.u32 [%0], %1;" :: "l"(f), "r"(v) : "memory"); }
__device__ __forceinline__ uint32_t flag_get(const uint32_t* f) { uint32_t v; asm volatile("ld.relaxed.gpu.global.u32 %0, [%1];" : "=r"(v) : "l"(f) : "memory"); return v; }
__device__ __forceinline__ void bulk_wait_fence() { asm volatile("cp.async.bulk.wait_group 0;\nfence.proxy.async.global;\nfence.acq_rel.gpu;" ::: "memory"); }
__device__ __forceinline__ uint32_t landed(bool el, const uint32_t* p, uint32_t pitch, uint32_t zero) {
    if (el) asm volatile("cp.async.bulk.wait_group 0;" ::: "memory");
    __syncwarp();
    const uint32_t a = flag_get(p), b = flag_get(p + 32 * pitch);
    return __reduce_or_sync(0xffffffffu, (a | b) & zero);
}
__device__ __forceinline__ uint32_t d16(uint32_t addr) { return (addr & 0x3FFFF) >> 4; }
__device__ __forceinline__ uint64_t mk_desc(uint32_t a16, uint32_t off, uint32_t lbo, uint32_t sbo, uint32_t swz) {
    const uint32_t lo = a16 + (off >> 4) + ((lbo >> 4) << 16), hi = (sbo >> 4) | (swz << 30);
    return ((uint64_t)hi << 32) | lo;
}
__device__ __forceinline__ uint32_t pack2(float lo, float hi) {
    uint32_t r; asm("cvt.rn.bf16x2.f32 %0, %1, %2;" : "=r"(r) : "f"(hi), "f"(lo)); return r;
}
__device__ __forceinline__ uint32_t hfma2_bf16(uint32_t a, uint32_t b, uint32_t c) {
    uint32_t r; asm("fma.rn.bf16x2 %0, %1, %2, %3;" : "=r"(r) : "r"(a), "r"(b), "r"(c)); return r;
}
__device__ __forceinline__ float bf_lo(uint32_t v) { return __uint_as_float(v << 16); }
__device__ __forceinline__ float bf_hi(uint32_t v) { return __uint_as_float(v & 0xFFFF0000u); }
__device__ __forceinline__ void unpack2(uint32_t v, float& lo, float& hi) {
    asm volatile("shl.b32 %0, %2, 16;\nand.b32 %1, %2, 0xffff0000;" : "=f"(lo), "=f"(hi) : "r"(v));
}
__device__ __forceinline__ float bf_round(float x) { return __bfloat162float(__float2bfloat16_rn(x)); }
__device__ __forceinline__ void stsm4(uint32_t addr, uint32_t r0, uint32_t r1, uint32_t r2, uint32_t r3) {
    asm volatile("stmatrix.sync.aligned.m8n8.x4.shared.b16 [%0], {%1, %2, %3, %4};" :: "r"(addr), "r"(r0), "r"(r1), "r"(r2), "r"(r3) : "memory");
}
__device__ __forceinline__ void stsm4t(uint32_t addr, uint32_t r0, uint32_t r1, uint32_t r2, uint32_t r3) {
    asm volatile("stmatrix.sync.aligned.m8n8.x4.trans.shared.b16 [%0], {%1, %2, %3, %4};" :: "r"(addr), "r"(r0), "r"(r1), "r"(r2), "r"(r3) : "memory");
}
__device__ __forceinline__ uint32_t movm(uint32_t a) { uint32_t d; asm volatile("movmatrix.sync.aligned.m8n8.trans.b16 %0, %1;" : "=r"(d) : "r"(a)); return d; }
__device__ __forceinline__ void ldsm4(uint32_t addr, uint32_t& r0, uint32_t& r1, uint32_t& r2, uint32_t& r3) {
    asm volatile("ldmatrix.sync.aligned.m8n8.x4.shared.b16 {%0, %1, %2, %3}, [%4];" : "=r"(r0), "=r"(r1), "=r"(r2), "=r"(r3) : "r"(addr) : "memory");
}
__device__ __forceinline__ void ldsm4t(uint32_t addr, uint32_t& r0, uint32_t& r1, uint32_t& r2, uint32_t& r3) {
    asm volatile("ldmatrix.sync.aligned.m8n8.x4.trans.shared.b16 {%0, %1, %2, %3}, [%4];" : "=r"(r0), "=r"(r1), "=r"(r2), "=r"(r3) : "r"(addr) : "memory");
}
__device__ __forceinline__ void mma16816(float (&c)[4], uint32_t a0, uint32_t a1, uint32_t a2, uint32_t a3, uint32_t b0, uint32_t b1) {
    asm("mma.sync.aligned.m16n8k16.row.col.f32.bf16.bf16.f32 {%0, %1, %2, %3}, {%4, %5, %6, %7}, {%8, %9}, {%0, %1, %2, %3};"
        : "+f"(c[0]), "+f"(c[1]), "+f"(c[2]), "+f"(c[3]) : "r"(a0), "r"(a1), "r"(a2), "r"(a3), "r"(b0), "r"(b1));
}
__device__ __forceinline__ float rsq(float x) { float r; asm("rsqrt.approx.ftz.f32 %0, %1;" : "=f"(r) : "f"(x)); return r; }
__device__ __forceinline__ float rcp(float x) { float r; asm("rcp.approx.ftz.f32 %0, %1;" : "=f"(r) : "f"(x)); return r; }
__device__ __forceinline__ float ex2(float x) { float r; asm("ex2.approx.ftz.f32 %0, %1;" : "=f"(r) : "f"(x)); return r; }
__device__ __forceinline__ float tanh_(float x) { float t; asm("tanh.approx.f32 %0, %1;" : "=f"(t) : "f"(x)); return t; }
__device__ __forceinline__ void block_end(uint32_t opaque, uint32_t id) { asm volatile("{\n.reg .pred p;\nsetp.eq.u32 p, %0, %1;\n@p trap;\n}" :: "r"(opaque), "r"(0xffffff00u + id)); }
__device__ __forceinline__ float silu_(float x) { return __fdividef(x, 1.f + __expf(-x)); }
__device__ __forceinline__ void st_pkt(void* p, uint32_t a, uint32_t b) {
    asm volatile("{\n.reg .b64 t;\nmov.b64 t, {%1, %2};\nst.relaxed.gpu.global.b64 [%0], t;\n}" :: "l"(p), "r"(a), "r"(b) : "memory");
}
__device__ __forceinline__ uint4 ld_pkt2(const void* p) {
    uint4 v; asm volatile("{\n.reg .b64 t, u;\nld.relaxed.gpu.global.v2.b64 {t, u}, [%4];\nmov.b64 {%0, %1}, t;\nmov.b64 {%2, %3}, u;\n}"
        : "=r"(v.x), "=r"(v.y), "=r"(v.z), "=r"(v.w) : "l"(p) : "memory"); return v;
}
__device__ __forceinline__ void st_pkt16(void* p, uint32_t a, uint32_t b, uint32_t c, uint32_t d) {
    asm volatile("{\n.reg .b64 t, u;\n.reg .b128 w;\nmov.b64 t, {%1, %2};\nmov.b64 u, {%3, %4};\nmov.b128 w, {t, u};\nst.relaxed.gpu.global.b128 [%0], w;\n}"
        :: "l"(p), "r"(a), "r"(b), "r"(c), "r"(d) : "memory");
}
__device__ __forceinline__ uint4 ld_pkt16(const void* p) {
    uint4 v; asm volatile("{\n.reg .b64 t, u;\n.reg .b128 w;\nld.relaxed.gpu.global.b128 w, [%4];\nmov.b128 {t, u}, w;\nmov.b64 {%0, %1}, t;\nmov.b64 {%2, %3}, u;\n}"
        : "=r"(v.x), "=r"(v.y), "=r"(v.z), "=r"(v.w) : "l"(p) : "memory"); return v;
}
#define SPIN_GUARD(n) do { if (++(n) > (1u << 22)) asm volatile("trap;"); } while (0)
__device__ __forceinline__ uint4 lds128(uint32_t a) { uint4 v; asm volatile("ld.shared.v4.u32 {%0, %1, %2, %3}, [%4];" : "=r"(v.x), "=r"(v.y), "=r"(v.z), "=r"(v.w) : "r"(a) : "memory"); return v; }
__device__ __forceinline__ void sts128(uint32_t a, uint32_t x, uint32_t y, uint32_t z, uint32_t w) { asm volatile("st.shared.v4.u32 [%0], {%1, %2, %3, %4};" :: "r"(a), "r"(x), "r"(y), "r"(z), "r"(w) : "memory"); }
__device__ __forceinline__ uint32_t lds32(uint32_t a) { uint32_t v; asm volatile("ld.shared.u32 %0, [%1];" : "=r"(v) : "r"(a) : "memory"); return v; }
__device__ __forceinline__ void sts32(uint32_t a, uint32_t v) { asm volatile("st.shared.u32 [%0], %1;" :: "r"(a), "r"(v) : "memory"); }
__device__ __forceinline__ bool elect_one() {
    uint32_t p; asm volatile("{\n.reg .pred q;\nelect.sync _|q, 0xffffffff;\nselp.u32 %0, 1, 0, q;\n}" : "=r"(p)); return p;
}
__device__ __forceinline__ void pause(uint32_t cycles) {
    uint32_t t0, t; asm volatile("mov.u32 %0, %%clock;" : "=r"(t0));
    do { __nanosleep(64); asm volatile("mov.u32 %0, %%clock;" : "=r"(t)); } while (t - t0 < cycles);
}
__device__ __forceinline__ void cluster_arrive() { asm volatile("barrier.cluster.arrive.relaxed.aligned;" ::: "memory"); }
__device__ __forceinline__ void cluster_wait() { asm volatile("barrier.cluster.wait.aligned;" ::: "memory"); }

__device__ __forceinline__ void wgmma_n128_z(float (&d)[64], uint64_t da, uint64_t db) {
    asm volatile("{\n.reg .pred p;\nsetp.ne.b32 p, 0, 0;\n"
        "wgmma.mma_async.sync.aligned.m64n128k16.f32.bf16.bf16 {"
        "%0, %1, %2, %3, %4, %5, %6, %7, %8, %9, %10, %11, %12, %13, %14, %15, "
        "%16, %17, %18, %19, %20, %21, %22, %23, %24, %25, %26, %27, %28, %29, %30, %31, "
        "%32, %33, %34, %35, %36, %37, %38, %39, %40, %41, %42, %43, %44, %45, %46, %47, "
        "%48, %49, %50, %51, %52, %53, %54, %55, %56, %57, %58, %59, %60, %61, %62, %63"
        "}, %64, %65, p, 1, 1, 0, 1;\n}\n"
        : "=f"(d[0]), "=f"(d[1]), "=f"(d[2]), "=f"(d[3]), "=f"(d[4]), "=f"(d[5]), "=f"(d[6]), "=f"(d[7]),
          "=f"(d[8]), "=f"(d[9]), "=f"(d[10]), "=f"(d[11]), "=f"(d[12]), "=f"(d[13]), "=f"(d[14]), "=f"(d[15]),
          "=f"(d[16]), "=f"(d[17]), "=f"(d[18]), "=f"(d[19]), "=f"(d[20]), "=f"(d[21]), "=f"(d[22]), "=f"(d[23]),
          "=f"(d[24]), "=f"(d[25]), "=f"(d[26]), "=f"(d[27]), "=f"(d[28]), "=f"(d[29]), "=f"(d[30]), "=f"(d[31]),
          "=f"(d[32]), "=f"(d[33]), "=f"(d[34]), "=f"(d[35]), "=f"(d[36]), "=f"(d[37]), "=f"(d[38]), "=f"(d[39]),
          "=f"(d[40]), "=f"(d[41]), "=f"(d[42]), "=f"(d[43]), "=f"(d[44]), "=f"(d[45]), "=f"(d[46]), "=f"(d[47]),
          "=f"(d[48]), "=f"(d[49]), "=f"(d[50]), "=f"(d[51]), "=f"(d[52]), "=f"(d[53]), "=f"(d[54]), "=f"(d[55]),
          "=f"(d[56]), "=f"(d[57]), "=f"(d[58]), "=f"(d[59]), "=f"(d[60]), "=f"(d[61]), "=f"(d[62]), "=f"(d[63])
        : "l"(da), "l"(db));
}
__device__ __forceinline__ void wgmma_n128(float (&d)[64], uint64_t da, uint64_t db) {
    asm volatile("{\n.reg .pred p;\nsetp.eq.b32 p, 0, 0;\n"
        "wgmma.mma_async.sync.aligned.m64n128k16.f32.bf16.bf16 {"
        "%0, %1, %2, %3, %4, %5, %6, %7, %8, %9, %10, %11, %12, %13, %14, %15, "
        "%16, %17, %18, %19, %20, %21, %22, %23, %24, %25, %26, %27, %28, %29, %30, %31, "
        "%32, %33, %34, %35, %36, %37, %38, %39, %40, %41, %42, %43, %44, %45, %46, %47, "
        "%48, %49, %50, %51, %52, %53, %54, %55, %56, %57, %58, %59, %60, %61, %62, %63"
        "}, %64, %65, p, 1, 1, 0, 1;\n}\n"
        : "+f"(d[0]), "+f"(d[1]), "+f"(d[2]), "+f"(d[3]), "+f"(d[4]), "+f"(d[5]), "+f"(d[6]), "+f"(d[7]),
          "+f"(d[8]), "+f"(d[9]), "+f"(d[10]), "+f"(d[11]), "+f"(d[12]), "+f"(d[13]), "+f"(d[14]), "+f"(d[15]),
          "+f"(d[16]), "+f"(d[17]), "+f"(d[18]), "+f"(d[19]), "+f"(d[20]), "+f"(d[21]), "+f"(d[22]), "+f"(d[23]),
          "+f"(d[24]), "+f"(d[25]), "+f"(d[26]), "+f"(d[27]), "+f"(d[28]), "+f"(d[29]), "+f"(d[30]), "+f"(d[31]),
          "+f"(d[32]), "+f"(d[33]), "+f"(d[34]), "+f"(d[35]), "+f"(d[36]), "+f"(d[37]), "+f"(d[38]), "+f"(d[39]),
          "+f"(d[40]), "+f"(d[41]), "+f"(d[42]), "+f"(d[43]), "+f"(d[44]), "+f"(d[45]), "+f"(d[46]), "+f"(d[47]),
          "+f"(d[48]), "+f"(d[49]), "+f"(d[50]), "+f"(d[51]), "+f"(d[52]), "+f"(d[53]), "+f"(d[54]), "+f"(d[55]),
          "+f"(d[56]), "+f"(d[57]), "+f"(d[58]), "+f"(d[59]), "+f"(d[60]), "+f"(d[61]), "+f"(d[62]), "+f"(d[63])
        : "l"(da), "l"(db));
}
__device__ __forceinline__ void wgmma_n176_z(float (&d)[88], uint64_t da, uint64_t db) {
    asm volatile("{\n.reg .pred p;\nsetp.ne.b32 p, 0, 0;\n"
        "wgmma.mma_async.sync.aligned.m64n176k16.f32.bf16.bf16 {"
        "%0, %1, %2, %3, %4, %5, %6, %7, %8, %9, %10, %11, %12, %13, %14, %15, "
        "%16, %17, %18, %19, %20, %21, %22, %23, %24, %25, %26, %27, %28, %29, %30, %31, "
        "%32, %33, %34, %35, %36, %37, %38, %39, %40, %41, %42, %43, %44, %45, %46, %47, "
        "%48, %49, %50, %51, %52, %53, %54, %55, %56, %57, %58, %59, %60, %61, %62, %63, "
        "%64, %65, %66, %67, %68, %69, %70, %71, %72, %73, %74, %75, %76, %77, %78, %79, "
        "%80, %81, %82, %83, %84, %85, %86, %87"
        "}, %88, %89, p, 1, 1, 0, 1;\n}\n"
        : "=f"(d[0]), "=f"(d[1]), "=f"(d[2]), "=f"(d[3]), "=f"(d[4]), "=f"(d[5]), "=f"(d[6]), "=f"(d[7]),
          "=f"(d[8]), "=f"(d[9]), "=f"(d[10]), "=f"(d[11]), "=f"(d[12]), "=f"(d[13]), "=f"(d[14]), "=f"(d[15]),
          "=f"(d[16]), "=f"(d[17]), "=f"(d[18]), "=f"(d[19]), "=f"(d[20]), "=f"(d[21]), "=f"(d[22]), "=f"(d[23]),
          "=f"(d[24]), "=f"(d[25]), "=f"(d[26]), "=f"(d[27]), "=f"(d[28]), "=f"(d[29]), "=f"(d[30]), "=f"(d[31]),
          "=f"(d[32]), "=f"(d[33]), "=f"(d[34]), "=f"(d[35]), "=f"(d[36]), "=f"(d[37]), "=f"(d[38]), "=f"(d[39]),
          "=f"(d[40]), "=f"(d[41]), "=f"(d[42]), "=f"(d[43]), "=f"(d[44]), "=f"(d[45]), "=f"(d[46]), "=f"(d[47]),
          "=f"(d[48]), "=f"(d[49]), "=f"(d[50]), "=f"(d[51]), "=f"(d[52]), "=f"(d[53]), "=f"(d[54]), "=f"(d[55]),
          "=f"(d[56]), "=f"(d[57]), "=f"(d[58]), "=f"(d[59]), "=f"(d[60]), "=f"(d[61]), "=f"(d[62]), "=f"(d[63]),
          "=f"(d[64]), "=f"(d[65]), "=f"(d[66]), "=f"(d[67]), "=f"(d[68]), "=f"(d[69]), "=f"(d[70]), "=f"(d[71]),
          "=f"(d[72]), "=f"(d[73]), "=f"(d[74]), "=f"(d[75]), "=f"(d[76]), "=f"(d[77]), "=f"(d[78]), "=f"(d[79]),
          "=f"(d[80]), "=f"(d[81]), "=f"(d[82]), "=f"(d[83]), "=f"(d[84]), "=f"(d[85]), "=f"(d[86]), "=f"(d[87])
        : "l"(da), "l"(db));
}
__device__ __forceinline__ void wgmma_n176(float (&d)[88], uint64_t da, uint64_t db) {
    asm volatile("{\n.reg .pred p;\nsetp.eq.b32 p, 0, 0;\n"
        "wgmma.mma_async.sync.aligned.m64n176k16.f32.bf16.bf16 {"
        "%0, %1, %2, %3, %4, %5, %6, %7, %8, %9, %10, %11, %12, %13, %14, %15, "
        "%16, %17, %18, %19, %20, %21, %22, %23, %24, %25, %26, %27, %28, %29, %30, %31, "
        "%32, %33, %34, %35, %36, %37, %38, %39, %40, %41, %42, %43, %44, %45, %46, %47, "
        "%48, %49, %50, %51, %52, %53, %54, %55, %56, %57, %58, %59, %60, %61, %62, %63, "
        "%64, %65, %66, %67, %68, %69, %70, %71, %72, %73, %74, %75, %76, %77, %78, %79, "
        "%80, %81, %82, %83, %84, %85, %86, %87"
        "}, %88, %89, p, 1, 1, 0, 1;\n}\n"
        : "+f"(d[0]), "+f"(d[1]), "+f"(d[2]), "+f"(d[3]), "+f"(d[4]), "+f"(d[5]), "+f"(d[6]), "+f"(d[7]),
          "+f"(d[8]), "+f"(d[9]), "+f"(d[10]), "+f"(d[11]), "+f"(d[12]), "+f"(d[13]), "+f"(d[14]), "+f"(d[15]),
          "+f"(d[16]), "+f"(d[17]), "+f"(d[18]), "+f"(d[19]), "+f"(d[20]), "+f"(d[21]), "+f"(d[22]), "+f"(d[23]),
          "+f"(d[24]), "+f"(d[25]), "+f"(d[26]), "+f"(d[27]), "+f"(d[28]), "+f"(d[29]), "+f"(d[30]), "+f"(d[31]),
          "+f"(d[32]), "+f"(d[33]), "+f"(d[34]), "+f"(d[35]), "+f"(d[36]), "+f"(d[37]), "+f"(d[38]), "+f"(d[39]),
          "+f"(d[40]), "+f"(d[41]), "+f"(d[42]), "+f"(d[43]), "+f"(d[44]), "+f"(d[45]), "+f"(d[46]), "+f"(d[47]),
          "+f"(d[48]), "+f"(d[49]), "+f"(d[50]), "+f"(d[51]), "+f"(d[52]), "+f"(d[53]), "+f"(d[54]), "+f"(d[55]),
          "+f"(d[56]), "+f"(d[57]), "+f"(d[58]), "+f"(d[59]), "+f"(d[60]), "+f"(d[61]), "+f"(d[62]), "+f"(d[63]),
          "+f"(d[64]), "+f"(d[65]), "+f"(d[66]), "+f"(d[67]), "+f"(d[68]), "+f"(d[69]), "+f"(d[70]), "+f"(d[71]),
          "+f"(d[72]), "+f"(d[73]), "+f"(d[74]), "+f"(d[75]), "+f"(d[76]), "+f"(d[77]), "+f"(d[78]), "+f"(d[79]),
          "+f"(d[80]), "+f"(d[81]), "+f"(d[82]), "+f"(d[83]), "+f"(d[84]), "+f"(d[85]), "+f"(d[86]), "+f"(d[87])
        : "l"(da), "l"(db));
}
__device__ __forceinline__ void wgmma_n256_z(float (&d)[128], uint64_t da, uint64_t db) {
    asm volatile("{\n.reg .pred p;\nsetp.ne.b32 p, 0, 0;\n"
        "wgmma.mma_async.sync.aligned.m64n256k16.f32.bf16.bf16 {"
        "%0, %1, %2, %3, %4, %5, %6, %7, %8, %9, %10, %11, %12, %13, %14, %15, "
        "%16, %17, %18, %19, %20, %21, %22, %23, %24, %25, %26, %27, %28, %29, %30, %31, "
        "%32, %33, %34, %35, %36, %37, %38, %39, %40, %41, %42, %43, %44, %45, %46, %47, "
        "%48, %49, %50, %51, %52, %53, %54, %55, %56, %57, %58, %59, %60, %61, %62, %63, "
        "%64, %65, %66, %67, %68, %69, %70, %71, %72, %73, %74, %75, %76, %77, %78, %79, "
        "%80, %81, %82, %83, %84, %85, %86, %87, %88, %89, %90, %91, %92, %93, %94, %95, "
        "%96, %97, %98, %99, %100, %101, %102, %103, %104, %105, %106, %107, %108, %109, %110, %111, "
        "%112, %113, %114, %115, %116, %117, %118, %119, %120, %121, %122, %123, %124, %125, %126, %127"
        "}, %128, %129, p, 1, 1, 0, 1;\n}\n"
        : "=f"(d[0]), "=f"(d[1]), "=f"(d[2]), "=f"(d[3]), "=f"(d[4]), "=f"(d[5]), "=f"(d[6]), "=f"(d[7]),
          "=f"(d[8]), "=f"(d[9]), "=f"(d[10]), "=f"(d[11]), "=f"(d[12]), "=f"(d[13]), "=f"(d[14]), "=f"(d[15]),
          "=f"(d[16]), "=f"(d[17]), "=f"(d[18]), "=f"(d[19]), "=f"(d[20]), "=f"(d[21]), "=f"(d[22]), "=f"(d[23]),
          "=f"(d[24]), "=f"(d[25]), "=f"(d[26]), "=f"(d[27]), "=f"(d[28]), "=f"(d[29]), "=f"(d[30]), "=f"(d[31]),
          "=f"(d[32]), "=f"(d[33]), "=f"(d[34]), "=f"(d[35]), "=f"(d[36]), "=f"(d[37]), "=f"(d[38]), "=f"(d[39]),
          "=f"(d[40]), "=f"(d[41]), "=f"(d[42]), "=f"(d[43]), "=f"(d[44]), "=f"(d[45]), "=f"(d[46]), "=f"(d[47]),
          "=f"(d[48]), "=f"(d[49]), "=f"(d[50]), "=f"(d[51]), "=f"(d[52]), "=f"(d[53]), "=f"(d[54]), "=f"(d[55]),
          "=f"(d[56]), "=f"(d[57]), "=f"(d[58]), "=f"(d[59]), "=f"(d[60]), "=f"(d[61]), "=f"(d[62]), "=f"(d[63]),
          "=f"(d[64]), "=f"(d[65]), "=f"(d[66]), "=f"(d[67]), "=f"(d[68]), "=f"(d[69]), "=f"(d[70]), "=f"(d[71]),
          "=f"(d[72]), "=f"(d[73]), "=f"(d[74]), "=f"(d[75]), "=f"(d[76]), "=f"(d[77]), "=f"(d[78]), "=f"(d[79]),
          "=f"(d[80]), "=f"(d[81]), "=f"(d[82]), "=f"(d[83]), "=f"(d[84]), "=f"(d[85]), "=f"(d[86]), "=f"(d[87]),
          "=f"(d[88]), "=f"(d[89]), "=f"(d[90]), "=f"(d[91]), "=f"(d[92]), "=f"(d[93]), "=f"(d[94]), "=f"(d[95]),
          "=f"(d[96]), "=f"(d[97]), "=f"(d[98]), "=f"(d[99]), "=f"(d[100]), "=f"(d[101]), "=f"(d[102]), "=f"(d[103]),
          "=f"(d[104]), "=f"(d[105]), "=f"(d[106]), "=f"(d[107]), "=f"(d[108]), "=f"(d[109]), "=f"(d[110]), "=f"(d[111]),
          "=f"(d[112]), "=f"(d[113]), "=f"(d[114]), "=f"(d[115]), "=f"(d[116]), "=f"(d[117]), "=f"(d[118]), "=f"(d[119]),
          "=f"(d[120]), "=f"(d[121]), "=f"(d[122]), "=f"(d[123]), "=f"(d[124]), "=f"(d[125]), "=f"(d[126]), "=f"(d[127])
        : "l"(da), "l"(db));
}
__device__ __forceinline__ void wgmma_n256(float (&d)[128], uint64_t da, uint64_t db) {
    asm volatile("{\n.reg .pred p;\nsetp.eq.b32 p, 0, 0;\n"
        "wgmma.mma_async.sync.aligned.m64n256k16.f32.bf16.bf16 {"
        "%0, %1, %2, %3, %4, %5, %6, %7, %8, %9, %10, %11, %12, %13, %14, %15, "
        "%16, %17, %18, %19, %20, %21, %22, %23, %24, %25, %26, %27, %28, %29, %30, %31, "
        "%32, %33, %34, %35, %36, %37, %38, %39, %40, %41, %42, %43, %44, %45, %46, %47, "
        "%48, %49, %50, %51, %52, %53, %54, %55, %56, %57, %58, %59, %60, %61, %62, %63, "
        "%64, %65, %66, %67, %68, %69, %70, %71, %72, %73, %74, %75, %76, %77, %78, %79, "
        "%80, %81, %82, %83, %84, %85, %86, %87, %88, %89, %90, %91, %92, %93, %94, %95, "
        "%96, %97, %98, %99, %100, %101, %102, %103, %104, %105, %106, %107, %108, %109, %110, %111, "
        "%112, %113, %114, %115, %116, %117, %118, %119, %120, %121, %122, %123, %124, %125, %126, %127"
        "}, %128, %129, p, 1, 1, 0, 1;\n}\n"
        : "+f"(d[0]), "+f"(d[1]), "+f"(d[2]), "+f"(d[3]), "+f"(d[4]), "+f"(d[5]), "+f"(d[6]), "+f"(d[7]),
          "+f"(d[8]), "+f"(d[9]), "+f"(d[10]), "+f"(d[11]), "+f"(d[12]), "+f"(d[13]), "+f"(d[14]), "+f"(d[15]),
          "+f"(d[16]), "+f"(d[17]), "+f"(d[18]), "+f"(d[19]), "+f"(d[20]), "+f"(d[21]), "+f"(d[22]), "+f"(d[23]),
          "+f"(d[24]), "+f"(d[25]), "+f"(d[26]), "+f"(d[27]), "+f"(d[28]), "+f"(d[29]), "+f"(d[30]), "+f"(d[31]),
          "+f"(d[32]), "+f"(d[33]), "+f"(d[34]), "+f"(d[35]), "+f"(d[36]), "+f"(d[37]), "+f"(d[38]), "+f"(d[39]),
          "+f"(d[40]), "+f"(d[41]), "+f"(d[42]), "+f"(d[43]), "+f"(d[44]), "+f"(d[45]), "+f"(d[46]), "+f"(d[47]),
          "+f"(d[48]), "+f"(d[49]), "+f"(d[50]), "+f"(d[51]), "+f"(d[52]), "+f"(d[53]), "+f"(d[54]), "+f"(d[55]),
          "+f"(d[56]), "+f"(d[57]), "+f"(d[58]), "+f"(d[59]), "+f"(d[60]), "+f"(d[61]), "+f"(d[62]), "+f"(d[63]),
          "+f"(d[64]), "+f"(d[65]), "+f"(d[66]), "+f"(d[67]), "+f"(d[68]), "+f"(d[69]), "+f"(d[70]), "+f"(d[71]),
          "+f"(d[72]), "+f"(d[73]), "+f"(d[74]), "+f"(d[75]), "+f"(d[76]), "+f"(d[77]), "+f"(d[78]), "+f"(d[79]),
          "+f"(d[80]), "+f"(d[81]), "+f"(d[82]), "+f"(d[83]), "+f"(d[84]), "+f"(d[85]), "+f"(d[86]), "+f"(d[87]),
          "+f"(d[88]), "+f"(d[89]), "+f"(d[90]), "+f"(d[91]), "+f"(d[92]), "+f"(d[93]), "+f"(d[94]), "+f"(d[95]),
          "+f"(d[96]), "+f"(d[97]), "+f"(d[98]), "+f"(d[99]), "+f"(d[100]), "+f"(d[101]), "+f"(d[102]), "+f"(d[103]),
          "+f"(d[104]), "+f"(d[105]), "+f"(d[106]), "+f"(d[107]), "+f"(d[108]), "+f"(d[109]), "+f"(d[110]), "+f"(d[111]),
          "+f"(d[112]), "+f"(d[113]), "+f"(d[114]), "+f"(d[115]), "+f"(d[116]), "+f"(d[117]), "+f"(d[118]), "+f"(d[119]),
          "+f"(d[120]), "+f"(d[121]), "+f"(d[122]), "+f"(d[123]), "+f"(d[124]), "+f"(d[125]), "+f"(d[126]), "+f"(d[127])
        : "l"(da), "l"(db));
}

struct Idx {
    uint32_t lane, warp, w4, q4, g8, prow, pan;
    __device__ __forceinline__ Idx() {
        uint32_t t; asm volatile("mov.u32 %0, %%tid.x;" : "=r"(t));
        lane = t & 31; warp = t >> 5; w4 = warp & 3; q4 = lane & 3; g8 = lane >> 2;
        prow = w4 * 16 + ((lane >> 3) & 1) * 8 + (lane & 7);
        pan = prow * 128 + (((lane >> 4) ^ (lane & 7)) << 4);
    }
};
#define IDX() const Idx ix; const uint32_t lane = ix.lane, warp = ix.warp, w4 = ix.w4, q4 = ix.q4, g8 = ix.g8, prow = ix.prow, pan_addr = ix.pan; \
    (void)lane; (void)warp; (void)w4; (void)q4; (void)g8; (void)prow; (void)pan_addr;

__device__ __forceinline__ int kof(int t, int sh, int j) {
    const int p = t >> (sh - 1), pn = p < 2 ? p : p >= 9, q = p - 2 - 7 * pn;
    return ((p < 2 ? j : q + (q >= j)) << 7) + (pn << 6) + ((t & (sh - 1)) << 5);
}
__device__ __forceinline__ uint32_t fidx(uint32_t m, uint32_t w, uint32_t pn) {
    return m * 32 + w * 16 + pn;
}
constexpr int HC0 = 8 * 48, HC3 = HC0 + 3072;
__device__ __forceinline__ int hcol(int p, int j) { return HC0 + p * 1024 + j * 128; }
struct Ring {
    uint32_t slot, par;
    __device__ __forceinline__ void next() { if (++slot == NSLOT) { slot = 0; par ^= 1; } }
    __device__ __forceinline__ void skip(uint32_t n) { slot += n; if (slot >= NSLOT) { slot -= NSLOT; par ^= 1; } }
};
__device__ __forceinline__ uint32_t BAR_FULL(uint32_t sb, uint32_t s) { return sb + OFF_BAR + 8 * s; }
constexpr uint32_t AF_REL = 48;
__device__ __forceinline__ uint32_t BAR_EMPTY(uint32_t sb, uint32_t s) { return sb + OFF_BAR + 96 + 8 * s; }
__device__ __forceinline__ uint32_t BAR_SFULL(uint32_t sb, uint32_t i) { return sb + OFF_BAR + 152 + 8 * i; }
__device__ __forceinline__ uint32_t BAR_SREADY(uint32_t sb, uint32_t i) { return sb + OFF_BAR + 184 + 8 * i; }
__device__ __forceinline__ uint32_t BAR_ONE(uint32_t sb, uint32_t i) { return sb + OFF_BAR + 216 + 8 * i; }
enum { EV_WIN, EV_WIN1, EV_WIN2, EV_WIN3, EV_P0, EV_GA, EV_GB, EV_LN2, EV_LAG1, EV_LAG2, EV_LAG3, EV_LAG4, EV_LAG5, EV_KV, EV_PAR, EV_AGO, EV_AGO1, EV_AGO2, EV_FGO, EV_FGO1, EV_FGO2, EV_H0, EV_H1, EV_H2, EV_H3, EV_TAIL, EV_COUNT = EV_TAIL + 8 };
constexpr int NB_TAIL = 4;

struct Rel {
    uint32_t base; bool sig;
    __device__ __forceinline__ Rel(uint32_t sb, uint32_t tw) {
        uint32_t a; asm("mapa.shared::cluster.u32 %0, %1, %2;" : "=r"(a) : "r"(BAR_EMPTY(sb, 0)), "r"((tw >> 5) & 1));
        base = __shfl_sync(0xffffffffu, a, 0); sig = (tw & ~32u) == 0;
    }
    __device__ __forceinline__ void operator()(uint32_t slot) const {
        if (sig) asm volatile("mbarrier.arrive.shared::cluster.b64 _, [%0];" :: "r"(base + 8 * slot) : "memory");
    }
};
struct LnRow { float rs0, nm0, rs1, nm1; };
struct Pipe {
    Rel rel; uint32_t p1, p2;
    __device__ __forceinline__ Pipe(uint32_t sb, uint32_t tw, uint32_t first) : rel(sb, tw), p1(first), p2(NSLOT) {}
    template <bool TWO> __device__ __forceinline__ void acquire(uint32_t sb, uint32_t af, const Ring& r) {
        const uint32_t b0 = BAR_FULL(sb, r.slot), b1 = b0 + af;
        const bool ready = TWO ? mbar_test2(b0, b1, r.par) : mbar_test(b0, r.par);
        wg_wait<1>();
        rel(p2);
        if (!ready) { if (TWO) mbar_wait2(b0, b1, r.par); else mbar_wait(b0, r.par); }
    }
    __device__ __forceinline__ void issued(uint32_t slot) { p2 = p1; p1 = slot; }
    __device__ __forceinline__ void drain1() { wg_wait<1>(); rel(p2); p2 = NSLOT; }
    __device__ __forceinline__ void drain0() { wg_wait<0>(); rel(p1); p1 = NSLOT; }
    template <bool TWO, class Step> __device__ __forceinline__ void hold(int LG, uint32_t sb, uint32_t af, Ring& r, uint32_t lag_bar, Step step) {
        Ring q = r;
#pragma unroll 1
        for (int i = 0; i < LG; ++i) { if (TWO) mbar_wait2(BAR_FULL(sb, q.slot), BAR_FULL(sb, q.slot) + af, q.par); else mbar_wait(BAR_FULL(sb, q.slot), q.par); q.next(); }
        mbar_wait(lag_bar, 0);
#pragma unroll 1
        do {
            step(r.slot);
            wg_wait<2>(); rel(p2); p2 = p1; p1 = r.slot;
            if (++r.slot == NSLOT) r.slot = 0;
        } while (r.slot != q.slot);
        r.par = q.par;
    }
};
template <bool TWO, bool FIRST, int NA, int NB>
__device__ __forceinline__ void step32(float (&aa)[NA], float (&ab)[NB], uint32_t sb, uint32_t wg, uint32_t slot, int own) {
    const uint32_t st = d16(sb) + slot * (SLOT >> 4);
    const uint32_t alo = own >= 0 ? d16(sb) + OFF_STG / 16 + wg * 1024 + (own >> 1) * 512 + (own & 1) * 4 : st + wg * 256;
    const uint32_t ahi = own >= 0 ? (1024 >> 4) | (1u << 30) : (512 >> 4) | (2u << 30);
    wg_fence();
#pragma unroll
    for (int k = 0; k < 2; ++k) {
        const uint64_t da = ((uint64_t)ahi << 32) | (alo + k * 2 + 0x10000);
        if constexpr (NA == 88) {
            const uint64_t d0 = mk_desc(st, 8192 + k * 2048, 8192, 1024, 1), d1 = mk_desc(st, 12288 + k * 2048, 8192, 1024, 1);
            if (FIRST && k == 0) { wgmma_n176_z(aa, da, d0); wgmma_n176_z(ab, da, d1); }
            else { wgmma_n176(aa, da, d0); wgmma_n176(ab, da, d1); }
        } else {
            const uint64_t d0 = mk_desc(st, 8192 + k * 2048, 4096, 1024, 1), d1 = mk_desc(st, 24576 + k * 2048, 4096, 1024, 1);
            if (FIRST && k == 0) { wgmma_n256_z(aa, da, d0); if constexpr (TWO) wgmma_n128_z(ab, da, d1); }
            else { wgmma_n256(aa, da, d0); if constexpr (TWO) wgmma_n128(ab, da, d1); }
        }
    }
    wg_commit();
}
template <bool TWO, int LG, int NA, int NB, class Mid, class Tail>
__device__ __forceinline__ void mainloop32(float (&aa)[NA], float (&ab)[NB], uint32_t sb, uint32_t wg, uint32_t tw, Ring& r, uint32_t lag_ev, int g0, Mid mid, Tail tail) {
    step32<TWO, true>(aa, ab, sb, wg, r.slot, TWO ? 0 : -1);
    TS(g0, 0);
    Pipe pp(sb, tw, r.slot);
    r.next();
    const int end = wg ? 32 : 32 - LG;
#pragma unroll 1
    for (int it = 1; it < end; ++it) {
        pp.acquire<TWO>(sb, wg ? 0 : AF_REL, r);
        step32<TWO, false>(aa, ab, sb, wg, r.slot, TWO && it < 4 ? it : -1);
        pp.issued(r.slot);
        TS(g0 + it, 0);
        r.next();
        mid(it);
    }
    if (wg == 0) { pp.drain1(); pp.drain0(); pp.hold<TWO>(LG, sb, AF_REL, r, BAR_ONE(sb, lag_ev), [&](uint32_t slot) { step32<TWO, false>(aa, ab, sb, 0, slot, -1); }); }
    if (wg == 1 && tw == 0) mbar_arrive(BAR_ONE(sb, lag_ev));
    pp.drain1();
    tail();
    pp.drain0();
    TS(g0 + 31, 1);
}
template <bool FIRST>
__device__ __forceinline__ void step64(float (&acc)[64], uint32_t sb, uint32_t wg, uint32_t slot, int own) {
    const uint32_t sbb = d16(sb) + slot * (SLOT >> 4), sa = own >= 0 ? d16(sb) + OFF_STG / 16 + wg * 1024 + own * 512 : sbb + wg * 512;
    wg_fence();
#pragma unroll
    for (int k = 0; k < 4; ++k) {
        const uint64_t da = mk_desc(sa, k * 32, 16, 1024, 1), db = mk_desc(sbb, 16384 + k * 2048, 8192, 1024, 1);
        if (FIRST && k == 0) wgmma_n128_z(acc, da, db); else wgmma_n128(acc, da, db);
    }
    wg_commit();
}
template <class Put, class Mid, class Tail>
__device__ __forceinline__ void mainloop64(float (&acc)[64], bool wo, uint32_t sb, uint32_t wg, uint32_t tw, Ring& r, Put put, Mid mid, Tail tail) {
    const int g0 = wo ? 32 : 144, nst = wo ? 16 : 56, lg = wo ? LAGW : LAGD; (void)g0;
    const uint32_t lag_bar = BAR_ONE(sb, wo ? EV_LAG4 : EV_LAG5), af = wo && !wg ? AF_REL : 0;
    if (!wo) CS(28);
    step64<true>(acc, sb, wg, r.slot, wo ? 0 : -1);
    if (!wo) CS(29);
    TS(g0, 0);
    Pipe pp(sb, tw, r.slot);
    r.next();
    int it = 1;
    auto run = [&](int end, int own, bool with_put) {
#pragma unroll 1
        do {
            pp.acquire<true>(sb, af, r);
            step64<false>(acc, sb, wg, r.slot, own);
            pp.issued(r.slot);
            TS(g0 + it, 0);
            if (wo && it == 2) CS(9);
            r.next();
            if (with_put && it == (wg ? PUTD1 : PUTD0)) put();
        } while (++it < end);
    };
    const int end = wg ? nst : nst - lg;
    run(wo ? 2 : wg ? MIDD : end, wo ? 1 : -1, true);
    mid();
    if (wo) { pp.drain1(); pp.drain0(); TS(g0 + 1, 1); }
    if (it < end) run(end, -1, false);
    if (wg == 0) { pp.drain1(); pp.drain0(); pp.hold<true>(lg, sb, af, r, lag_bar, [&](uint32_t slot) { step64<false>(acc, sb, 0, slot, -1); }); }
    if (wg == 1 && tw == 0) mbar_arrive(lag_bar);
    pp.drain1();
    tail();
    pp.drain0();
    TS(g0 + nst - 1, 1);
}

struct RowAcc {
    float sm[4] = {0.f, 0.f, 0.f, 0.f}, sq[4] = {0.f, 0.f, 0.f, 0.f};
    __device__ __forceinline__ void add(int e, float x) { sm[e & 3] += x; sq[e & 3] = fmaf(x, x, sq[e & 3]); }
    __device__ __forceinline__ void publish(uint4* dst, uint32_t q4, uint32_t ep) const {
        const float s0 = sm[0] + sm[1], s1 = sm[2] + sm[3], q0 = sq[0] + sq[1], q1 = sq[2] + sq[3];
        const bool od = q4 & 1;
        float sv = (od ? s1 : s0) + __shfl_xor_sync(0xffffffffu, od ? s0 : s1, 1), qv = (od ? q1 : q0) + __shfl_xor_sync(0xffffffffu, od ? q0 : q1, 1);
        sv += __shfl_xor_sync(0xffffffffu, sv, 2); qv += __shfl_xor_sync(0xffffffffu, qv, 2);
        st_pkt16(dst + (q4 & 1) * 8, 0, __float_as_uint(sv), __float_as_uint(qv), ep);
    }
};
__device__ __forceinline__ LnRow merge_stats(const uint4* src, uint32_t q4, uint32_t ep, uint32_t sb) {
    uint4 t[4];
    uint32_t n = 0;
    while (true) {
#pragma unroll
        for (int i = 0; i < 4; ++i) t[i] = ld_pkt16(src + (q4 * 2 + (i >> 1)) * 512 + (i & 1) * 8);
        const bool ok_ = __all_sync(0xffffffffu, t[0].w == ep && t[1].w == ep && t[2].w == ep && t[3].w == ep);
        if (n < 4) CS(14 + n);
        if (ok_) break;
        SPIN_GUARD(n);
    }
    float v[4];
#pragma unroll
    for (int h = 0; h < 2; ++h) { v[h] = __uint_as_float(t[h].y) + __uint_as_float(t[2 + h].y); v[2 + h] = __uint_as_float(t[h].z) + __uint_as_float(t[2 + h].z); }
#pragma unroll
    for (int o = 1; o < 4; o <<= 1)
#pragma unroll
        for (int i = 0; i < 4; ++i) v[i] += __shfl_xor_sync(0xffffffffu, v[i], o);
    const float m0 = v[0] * (1.f / D_), m1 = v[1] * (1.f / D_);
    const float r0 = rsq(fmaxf(fmaf(-m0, m0, v[2] * (1.f / D_)), 0.f) + 1e-5f), r1 = rsq(fmaxf(fmaf(-m1, m1, v[3] * (1.f / D_)), 0.f) + 1e-5f);
    return LnRow{r0, -m0 * r0, r1, -m1 * r1};
}
struct Stg {
    uint32_t b, par;
    __device__ __forceinline__ uint32_t acquire2(uint32_t sb, uint32_t wg) {
        mbar_wait2(BAR_SREADY(sb, wg * 2), BAR_SREADY(sb, wg * 2 + 1), par);
        par ^= 1;
        return sb + OFF_STG + wg * 16384;
    }
    __device__ __forceinline__ void publish(uint32_t sb, uint32_t wg, uint32_t lane) {
        fence_async_smem();
        __syncwarp();
        if (lane == 0) mbar_arrive(BAR_SFULL(sb, wg * 2 + b));
        b ^= 1;
    }
};

struct LnPar {
    uint4 p[8];
    __device__ __forceinline__ void load(uint32_t sb, uint32_t q4) {
#pragma unroll
        for (int i = 0; i < 8; ++i) p[i] = lds128(sb + OFF_PAR + i * 64 + q4 * 16);
    }
};
__device__ __forceinline__ void ln_norm(uint32_t (&xn)[32], const float (&x)[64], const LnRow& n) {
#pragma unroll
    for (int e = 0; e < 32; ++e) {
        const float rs = (e & 1) ? n.rs1 : n.rs0, nm = (e & 1) ? n.nm1 : n.nm0;
        xn[e] = pack2(fmaf(x[2 * e], rs, nm), fmaf(x[2 * e + 1], rs, nm));
    }
}
__device__ __forceinline__ void ln_emit(const uint32_t (&xr)[32], const LnPar& lp, uint32_t sb, uint32_t wg, const Idx& ix) {
#pragma unroll
    for (int i = 0; i < 8; ++i)
        stsm4(sb + OFF_STG + wg * 16384 + (i >> 2) * 8192 + (ix.pan ^ ((i & 3) << 5)), hfma2_bf16(xr[4 * i], lp.p[i].z, lp.p[i].x), hfma2_bf16(xr[4 * i + 1], lp.p[i].z, lp.p[i].x),
              hfma2_bf16(xr[4 * i + 2], lp.p[i].w, lp.p[i].y), hfma2_bf16(xr[4 * i + 3], lp.p[i].w, lp.p[i].y));
    fence_async_smem();
    __syncwarp();
    if (ix.lane < 2) mbar_arrive(BAR_SFULL(sb, wg * 2 + ix.lane));
    bar_sync(1 + wg, 128);
}
__device__ __forceinline__ void load_slab(uint32_t (&xr)[32], uint32_t buf) {
    IDX();
#pragma unroll
    for (int i = 0; i < 8; ++i) ldsm4(buf + (i >> 2) * 8192 + (pan_addr ^ ((i & 3) << 5)), xr[4 * i], xr[4 * i + 1], xr[4 * i + 2], xr[4 * i + 3]);
}
__device__ __forceinline__ void unpack_slab(float (&x)[64], const uint32_t (&xr)[32]) {
#pragma unroll
    for (int i = 0; i < 32; ++i) unpack2(xr[i], x[2 * i], x[2 * i + 1]);
}
__device__ __forceinline__ void store_slab(const float (&x)[64], uint32_t buf, uint32_t pitch, uint32_t pan, int i0, int i1) {
#pragma unroll
    for (int i = i0; i < i1; ++i)
        stsm4(buf + (i >> 2) * pitch + (pan ^ ((i & 3) << 5)), pack2(x[8 * i], x[8 * i + 1]), pack2(x[8 * i + 2], x[8 * i + 3]), pack2(x[8 * i + 4], x[8 * i + 5]), pack2(x[8 * i + 6], x[8 * i + 7]));
}
template <int NP, class Done>
__device__ __forceinline__ void fetch_halo(uint4* src, bool first, uint32_t dst, Done done) {
    uint4 hv[4 * NP];
    uint32_t n = 0;
    while (true) {
        bool ok = true;
#pragma unroll
        for (int i = 0; i < 4 * NP; ++i) { hv[i] = first ? make_uint4(0, 0, 0, 0) : ld_pkt16(src + (i >> 2) * 256 + (i & 3) * 32); ok = ok && hv[i].x != 0; }
        if (first || __all_sync(0xffffffffu, ok)) break;
        SPIN_GUARD(n);
    }
#pragma unroll
    for (int i = 0; i < 4 * NP; ++i) stsm4(dst + (i >> 2) * 4096 + (i & 3) * 512, hv[i].x, hv[i].y, hv[i].z, hv[i].w);
    done();
    if (!first) {
#pragma unroll
        for (int i = 0; i < 4 * NP; ++i) src[(i >> 2) * 256 + (i & 3) * 32] = make_uint4(0, 0, 0, 0);
    }
}

template <int N, class G, class U>
__device__ __forceinline__ void glu(uint32_t (&h)[N], G g, U u) {
#pragma unroll
    for (int i = 0; i < N; ++i) h[i] = pack2(fmaf(tanh_(g(2 * i)), u(2 * i), u(2 * i)), fmaf(tanh_(g(2 * i + 1)), u(2 * i + 1), u(2 * i + 1)));
}
__device__ __forceinline__ void put_h(const uint32_t (&h)[32], uint32_t sb, uint32_t wg, Stg& stg) {
    IDX();
    const uint32_t buf = stg.acquire2(sb, wg);
#pragma unroll
    for (int k = 0; k < 8; ++k) stsm4(buf + (k >> 2) * 8192 + (pan_addr ^ ((k & 3) << 5)), h[4 * k], h[4 * k + 1], h[4 * k + 2], h[4 * k + 3]);
    fence_async_smem();
    __syncwarp();
    if (lane < 2) mbar_arrive(BAR_SFULL(sb, wg * 2 + lane));
}

template <int NP, bool PREV>
__device__ __forceinline__ void passes128(uint32_t (&hp)[32], uint32_t sb, uint32_t wg, uint32_t tw, Ring& r, Stg& stg) {
#pragma unroll 1
    for (int p = 0; p < NP; ++p) {
        float b256[128], none[1];
        const int put_at = !PREV && p == 0 ? -1 : wg ? PUT1 : PUT0;
        mainloop32<false, LAGS>(b256, none, sb, wg, tw, r, EV_LAG2 + p, 80 + 32 * (p & 1), [&](int it) { if (it == put_at) put_h(hp, sb, wg, stg); },
                                [&] { if (PREV || p < NP - 1) mbar_wait(BAR_FULL(sb, r.slot), r.par); });
        if (threadIdx.x == 0) { TL(29 + 2 * p); TC(114 + 2 * p); }
        if (threadIdx.x == 128) TL(53 + 2 * (p & 1));
        CS(24 + 2 * (p & 1));
        glu(hp, [&](int i) { return b256[i + (i & 32)]; }, [&](int i) { return b256[i + (i & 32) + 32]; });
        if (threadIdx.x == 0) { TL(30 + 2 * p); TC(115 + 2 * p); }
        if (threadIdx.x == 128) TL(54 + 2 * (p & 1));
        CS(25 + 2 * (p & 1));
    }
}

__global__ void __launch_bounds__(384, 1)
fused_block_kernel(const __grid_constant__ Ptrs pt, const __grid_constant__ Maps mp) {
    uint32_t* const g_flags = pt.mail->flags;
    uint2* const g_mod = pt.mail->mod;
    uint4* const g_st1 = pt.mail->st1;
    uint32_t* const g_par2 = pt.mail->par2;
    uint4* const g_halo = pt.mail->halo;
    const __nv_bfloat16* __restrict__ cvec = pt.c;
    if (threadIdx.x == 224) { prefetch_map(&mp.wm8); prefetch_map(&mp.x); }
    extern __shared__ __align__(1024) uint8_t smem[];
    const uint32_t sb = smem_u32(smem);
    const uint32_t tid = threadIdx.x, tw = tid & 127, lane = tid & 31;
    const uint32_t warp = __shfl_sync(0xffffffffu, tid >> 5, 0), wg = warp >> 2;
    uint32_t rank; asm("mov.u32 %0, %%cluster_ctarank;" : "=r"(rank));
    rank = __shfl_sync(0xffffffffu, rank, 0);
    uint32_t ep;
    uint32_t smid; asm volatile("mov.u32 %0, %%smid;" : "=r"(smid));
    const int c = __shfl_sync(0xffffffffu, smid >> 1, 0);
    const int c7 = ((c - 32) * 37) >> 8;
    int grp = c < 32 ? c & 7 : c < 60 ? c - 31 - 7 * c7 : c < 62 ? -1 : 0;
    const int j = c < 32 ? c >> 3 : c < 60 ? 4 + c7 : c < 62 ? (c - 60) * 2 + rank : c - 58;
    const bool aux = grp < 0;
    const int m = grp * 2 + rank;
    uint4* const g_st2 = g_halo + (m > 0 ? (m - 1) * 8 * 512 : 128);

    bool cluster_arrive_early = false;
    if (wg < 2) {
      if (!KDEBUG) cluster_arrive();
      ep = flag_get(g_flags + FL_DONE);
      uint16_t cw[8];
      {
          const __nv_bfloat16* cp = cvec + ((tw >> 5) * 32 + (tw & 3) * 2) * 8 + (lane >> 2);
#pragma unroll
          for (int i = 0; i < 8; ++i) asm volatile("ld.global.nc.u16 %0, [%1];" : "=h"(cw[i]) : "l"(cp + (i >> 1) * 64 + (i & 1) * 8));
      }
      asm volatile("setmaxnreg.inc.sync.aligned.u32 224;");
      if (tid == 0) TL(58);
      if (KDEBUG) cluster_arrive();
      Ring r{0, 0};
      Stg stg{0, 0};
      if (aux) {
        if (wg == 0) {
            const uint4 cv = *(const uint4*)(cvec + tw * 8);
            sts128(sb + OFF_STG + (tw >> 3) * 1024 + (tw & 7) * 16, pack2(silu_(bf_lo(cv.x)), silu_(bf_hi(cv.x))), pack2(silu_(bf_lo(cv.y)), silu_(bf_hi(cv.y))),
                   pack2(silu_(bf_lo(cv.z)), silu_(bf_hi(cv.z))), pack2(silu_(bf_lo(cv.w)), silu_(bf_hi(cv.w))));
            fence_async_smem();
        }
        cluster_wait();
        ep = __shfl_sync(0xffffffffu, ep, 0) / NCTA + 1;
        if (wg == 0) {
            bar_sync(1, 128);
#pragma unroll 1
            for (int p = 0; p < 4; ++p) {
                float acc[128];
#pragma unroll
                for (int i = 0; i < 128; ++i) acc[i] = 0.f;
                uint32_t prev = 0;
#pragma unroll 1
                for (int kc = 0; kc < 16; ++kc) {
                    mbar_wait(BAR_FULL(sb, r.slot), r.par);
                    wg_fence();
#pragma unroll
                    for (int k = 0; k < 4; ++k)
                        wgmma_n256(acc, mk_desc(d16(sb) + kc * 64, OFF_STG + k * 32, 16, 0, 1), mk_desc(d16(sb) + r.slot * (SLOT >> 4), k * 2048, 8192, 1024, 1));
                    wg_commit();
                    wg_wait<1>();
                    if (kc > 0 && tw < 4) mbar_arrive(BAR_EMPTY(sb, prev));
                    prev = r.slot;
                    r.next();
                }
                wg_wait<0>();
                if (tw < 4) mbar_arrive(BAR_EMPTY(sb, prev));
                if (tw < 4) {
#pragma unroll
                    for (int jn = 0; jn < 32; ++jn) sts32(sb + OFF_TAB + (jn * 4 + tw) * 4, pack2(acc[jn * 4], acc[jn * 4 + 1]));
                }
                bar_sync(1, 128);
                const int vec = 2 + p, blk = p * 4 + j;
                const uint32_t val = lds32(sb + OFF_TAB + tw * 4);
                if (vec == 2 || vec == 5) st_pkt(g_mod + (8 + blk) * 128 + tw, val, ep);
                else {
                    const float one = vec == 4 ? 1.f : 0.f;
                    g_par2[((blk & 3) * 16 + (tw >> 3)) * 16 + (tw & 3) * 4 + (vec - 3) * 2 + ((tw >> 2) & 1)] =
                        pack2(0.5f * bf_round(one + bf_lo(val)), 0.5f * bf_round(one + bf_hi(val)));
                }
                bar_sync(1, 128);
                if (tw == 0) {
                    if (vec == 3 || vec == 4) asm volatile("red.release.gpu.global.add.u32 [%0], 1;" :: "l"(&g_flags[FL_LN2]) : "memory");
                    TL(1 + p);
                }
            }
            if (lane < 2) mbar_arrive_cta(BAR_ONE(sb, EV_P0), lane);
        }
        r = Ring{64 % NSLOT, (64 / NSLOT) & 1};
        mbar_wait(BAR_ONE(sb, EV_P0), 0);
        mbar_wait(BAR_FULL(sb, r.slot), r.par);
        uint32_t hp[32] = {};
        passes128<4, false>(hp, sb, wg, tw, r, stg);
        put_h(hp, sb, wg, stg);
      } else {
        float xs[64];
        uint32_t xp[32];
        {
            IDX();
            if (q4 < 2) st_pkt16(g_st1 + (m * 8 + j) * 512 + wg * 64 + w4 * 16 + g8 + q4 * 8, 0, 0, 0, 0);
            if (warp == 0) st_pkt16(pt.mail->mod1 + g8 * 512 + (m * 8 + j) * 4 + q4, 0, 0, 0, 0);
            sts128(sb + tid * 16, pack2(silu_(bf_lo(cw[0])), silu_(bf_lo(cw[1]))), pack2(silu_(bf_lo(cw[2])), silu_(bf_lo(cw[3]))),
                   pack2(silu_(bf_lo(cw[4])), silu_(bf_lo(cw[5]))), pack2(silu_(bf_lo(cw[6])), silu_(bf_lo(cw[7]))));
            cluster_wait();
            ep = __shfl_sync(0xffffffffu, ep, 0) / NCTA + 1;
            load_slab(xp, stg.acquire2(sb, wg));
            unpack_slab(xs, xp);
            if (tid == 0) TL(24);
            if (tid == 128) TL(27);
        }
#pragma unroll 1
        for (int blk = 0; ; ++blk) {
        {
            IDX();
            uint4* const st = (blk ? g_st2 : g_st1 + m * 8 * 512) + wg * 64 + w4 * 16 + g8;
            RowAcc ra;
#pragma unroll
            for (int e = 0; e < 64; ++e) ra.add(e, xs[e]);
            ra.publish(st + j * 512, q4, ep);
            uint32_t t_pub = 0; if (PDLY) asm volatile("mov.u32 %0, %%clock;" : "=r"(t_pub));
            if (tid == 0) TL(blk ? 9 : 26);
            if (tid == 128 && blk) TL(34);
            if (blk) CS(11);
            LnPar lp;
            if (blk == 0) {
            uint4* const mod_out = pt.mail->mod1 + g8 * 512 + (m * 8 + j) * 4 + q4;
            if (wg == 0) {
                uint4 af[8];
#pragma unroll
                for (int i = 0; i < 8; ++i) af[i] = lds128(sb + w4 * 512 + i * 64 + q4 * 16);
                float c[4][4] = {};
#pragma unroll
                for (int i = 0; i < 8; ++i) {
                    if (!(i & 1)) mbar_wait(BAR_ONE(sb, EV_WIN + (i >> 1)), 0);
                    if (i == 6 && tid == 0) TL(25);
#pragma unroll
                    for (int h = 0; h < 2; ++h) {
                        uint32_t b0, b1, b2, b3;
                        ldsm4t(sb + 5 * SLOT + i * 4096 + w4 * 1024 + h * 512 + (lane & 15) * 32 + (lane >> 4) * 16, b0, b1, b2, b3);
                        mma16816(c[2 * h], h ? af[i].z : af[i].x, 0u, h ? af[i].w : af[i].y, 0u, b0, b1);
                        mma16816(c[2 * h + 1], h ? af[i].z : af[i].x, 0u, h ? af[i].w : af[i].y, 0u, b2, b3);
                    }
                }
                if (lane < 4) sts128(sb + OFF_TAB + w4 * 64 + lane * 16, __float_as_uint(c[0][0] + c[2][0]), __float_as_uint(c[0][1] + c[2][1]),
                                     __float_as_uint(c[1][0] + c[3][0]), __float_as_uint(c[1][1] + c[3][1]));
                if (lane < 2) mbar_arrive_cta(BAR_ONE(sb, EV_P0), lane);
                bar_sync(1, 128);
                if (w4 == 0) {
                    float a[4] = {0.f, 0.f, 0.f, 0.f};
#pragma unroll
                    for (int i = 0; i < 4; ++i) {
                        const uint4 t = lds128(sb + OFF_TAB + i * 64 + q4 * 16);
                        a[0] += __uint_as_float(t.x); a[1] += __uint_as_float(t.y); a[2] += __uint_as_float(t.z); a[3] += __uint_as_float(t.w);
                    }
                    const float add = m >= 8 ? 1.f : 0.f;
                    st_pkt16(mod_out, pack2(bf_round(a[0]) + add, bf_round(a[1]) + add), pack2(bf_round(a[2]) + add, bf_round(a[3]) + add), ep, 0);
                    if (tid == 0) TL(3);
                }
            } else if (LWAIT >= 0) mbar_wait(BAR_ONE(sb, EV_WIN + LWAIT), 0);
            } else {
                mbar_wait2(BAR_ONE(sb, EV_LN2), BAR_FULL(sb, 0), 0);
            }
            lp.load(sb, q4);
#pragma unroll
            for (int e = 0; e < 32; ++e) xp[e] = pack2(xs[2 * e], xs[2 * e + 1]);
            if (PDLY && blk) { uint32_t t1; do { asm volatile("mov.u32 %0, %%clock;" : "=r"(t1)); } while (t1 - t_pub < PDLY); }
            if (blk) CS(13);
            const LnRow n = merge_stats(st, q4, ep, sb);
            if (tid == 0) TL(blk ? 49 : 48);
            if (tid == 128) TL(blk ? 45 : 28);
            if (blk) CS(18);
            uint32_t xn[32];
            ln_norm(xn, xs, n);
            if (blk == 0) { mbar_wait2(BAR_FULL(sb, 0), BAR_ONE(sb, EV_PAR), 0); lp.load(sb, q4); }
            ln_emit(xn, lp, sb, wg, ix);
            if (tid == 0) { TL(blk ? 36 : 8); TC(blk ? 109 : 103); }
            if (tid == 128) TL(blk ? 43 : 22);
            if (blk) CS(21);
        }
        uint32_t hp[32];
        if (blk == 0) {
        {
            float big[128], sml[64];
            step32<true, true>(big, sml, sb, wg, r.slot, 0);
            TS(0, 0);
            Pipe pp(sb, tw, r.slot);
            r.next();
#pragma unroll 1
            for (int it = 1; it < 32 - LAGQ; ++it) {
                pp.acquire<true>(sb, wg ? 0 : AF_REL, r);
                step32<true, false>(big, sml, sb, wg, r.slot, it < 4 ? it : -1);
                pp.issued(r.slot);
                TS(it, 0);
                r.next();
            }
            auto half = [&](uint32_t slot, bool rest) {
                const uint32_t st = d16(sb) + slot * (SLOT >> 4);
#pragma unroll
                for (int k = 0; k < 2; ++k) {
                    const uint64_t da = mk_desc(st + wg * 256, k * 32, 16, 512, 2);
                    if (rest) wgmma_n256(big, da, mk_desc(st, 8192 + k * 2048, 4096, 1024, 1)); else wgmma_n128(sml, da, mk_desc(st, 24576 + k * 2048, 4096, 1024, 1));
                }
            };
            auto rest = [&](bool each) {
                wg_fence();
#pragma unroll
                for (int it = 32 - LAGQ; it < 32; ++it) { if (each && it > 32 - LAGQ) wg_fence(); half(it % NSLOT, true); if (each || it == 31) wg_commit(); }
            };
            stg.acquire2(sb, wg); mbar_wait2(BAR_SREADY(sb, 2), BAR_SREADY(sb, 3), 1);
#pragma unroll 1
            for (int it = 32 - LAGQ; it < 32; ++it) {
                pp.acquire<true>(sb, wg ? 0 : AF_REL, r);
                wg_fence(); half(r.slot, false); wg_commit();
                pp.issued(NSLOT);
                TS(it, 0);
                r.next();
            }
            if (wg) { rest(false); wg_wait<1>(); } else wg_wait<0>();
            CS(8);
            IDX();
            uint32_t k0[8], k1[8], k2[8], v0[8], v1[8], v2[8];
            const uint32_t nxt = warp + ((warp & 1) ? 3 : 1), mine = sb + OFF_STG + wg * 16384 + w4 * 2048;
            auto tails = [&](const float* kv, uint32_t (&kt)[8], uint32_t (&vt)[8]) {
#pragma unroll
                for (int t = 0; t < 8; ++t) { kt[t] = pack2(kv[4 * t + 2], kv[4 * t + 3]); vt[t] = pack2(kv[32 + 4 * t + 2], kv[32 + 4 * t + 3]); }
            };
            auto post = [&](int pn, uint32_t (&kt)[8], uint32_t (&vt)[8]) {
                uint4* dst = g_halo + (m * 8 + j) * 512 + (w4 >> 1) * 256 + pn * 128 + lane;
#pragma unroll
                for (int h = 0; h < 2; ++h) { if (!kt[4 * h]) kt[4 * h] = 0x8000u; if (!vt[4 * h]) vt[4 * h] = 0x8000u; }
#pragma unroll
                for (int h = 0; h < 2; ++h) { st_pkt16(dst + h * 32, kt[4 * h], kt[4 * h + 1], kt[4 * h + 2], kt[4 * h + 3]); st_pkt16(dst + 64 + h * 32, vt[4 * h], vt[4 * h + 1], vt[4 * h + 2], vt[4 * h + 3]); }
            };
            auto prepare = [&](int pn, const float* kv) {
                tails(kv, k2, v2);
                if (nxt < 8) {
                    const uint32_t dst = sb + OFF_STG + (nxt >> 2) * 16384 + (nxt & 3) * 2048 + pn * 8192 + lane * 16;
#pragma unroll
                    for (int h = 0; h < 2; ++h) { stsm4(dst + h * 512, k2[4 * h], k2[4 * h + 1], k2[4 * h + 2], k2[4 * h + 3]); stsm4(dst + 1024 + h * 512, v2[4 * h], v2[4 * h + 1], v2[4 * h + 2], v2[4 * h + 3]); }
                    if (pn == 0) bar_arrive(NB_TAIL + nxt, 64);
                    else { __syncwarp(); if (lane == 0) mbar_arrive(BAR_ONE(sb, EV_TAIL + nxt)); }
                } else if (pn == 0 && m < 15) post(0, k2, v2);
#pragma unroll
                for (int t = 0; t < 8; ++t) { k1[t] = pack2(kv[4 * t], kv[4 * t + 1]); v1[t] = movm(pack2(kv[32 + 4 * t], kv[32 + 4 * t + 1])); v2[t] = movm(v2[t]); }
                if (pn == 0) { CS(2); if (wg == 0) { rest(true); wg_wait<3>(); pp.rel(28 % NSLOT); wg_wait<2>(); pp.rel(29 % NSLOT); wg_wait<1>(); pp.rel(30 % NSLOT); } bar_sync(NB_TAIL + warp, 64); CS(4); }
                else mbar_wait(BAR_ONE(sb, EV_TAIL + __shfl_sync(0xffffffffu, warp, 0)), 0);
#pragma unroll
                for (int h = 0; h < 2; ++h) {
                    ldsm4(mine + pn * 8192 + lane * 16 + h * 512, k0[4 * h], k0[4 * h + 1], k0[4 * h + 2], k0[4 * h + 3]);
                    ldsm4t(mine + pn * 8192 + lane * 16 + 1024 + h * 512, v0[4 * h], v0[4 * h + 1], v0[4 * h + 2], v0[4 * h + 3]);
                }
            };
#pragma unroll
            for (int i = 0; i < 64; ++i) asm volatile("" : "+f"(sml[i]) :: "memory");
            prepare(0, sml);
            static_assert(LAGQ == 4, "");
            wg_wait<0>();
            if (wg) { pp.rel(28 % NSLOT); pp.rel(29 % NSLOT); pp.rel(30 % NSLOT); }
            pp.rel(31 % NSLOT);
            TS(31, 1);
            if (tid == 0) { TL(4); TC(104); }
            if (tid == 128) TL(50);
            CS(1);
#pragma unroll
            for (int i = 0; i < 128; ++i) asm volatile("" : "+f"(big[i]) :: "memory");
            if (nxt >= 8 && m < 15) { uint32_t kt[8], vt[8]; tails(big, kt, vt); post(1, kt, vt); }
            const bool lo0 = q4 * 2 > g8, lo1 = q4 * 2 + 1 > g8;
            const bool nopast = m == 0 && (warp & 5) == 0;
            const uint32_t lomask = (lo0 ? 0xFFFFu : 0u) | (lo1 ? 0xFFFF0000u : 0u);
            const uint32_t orow = mine + (lane & 7) * 128 + (((lane >> 3) ^ (lane & 7)) << 4);
            const float sl2 = 0.17677669529663687f * 1.4426950408889634f;
#pragma unroll
            for (int pn = 0; pn < 2; ++pn) {
                float e0[4], e1[4], mx[4], sum[4];
#pragma unroll
                for (int hh = 0; hh < 2; ++hh) {
                    uint32_t qf[8];
#pragma unroll
                    for (int i = 0; i < 8; ++i) qf[i] = pack2(big[64 + 32 * pn + 16 * hh + 2 * i], big[64 + 32 * pn + 16 * hh + 2 * i + 1]);
                    float s[3][4];
#pragma unroll
                    for (int t = 0; t < 3; ++t) {
                        const uint32_t* k = (t == 0 ? k0 : t == 1 ? k1 : k2) + 4 * hh;
                        s[t][0] = s[t][1] = s[t][2] = s[t][3] = 0.f;
                        mma16816(s[t], qf[0], qf[1], qf[2], qf[3], k[0], k[1]);
                        mma16816(s[t], qf[4], qf[5], qf[6], qf[7], k[2], k[3]);
                    }
#pragma unroll
                    for (int hf = 0; hf < 2; ++hf) {
                        const int u = hh * 2 + hf;
                        e0[u] = lo0 ? ((hf == 0 && nopast) ? -INFINITY : s[hf][hf * 2]) : s[hf + 1][hf * 2];
                        e1[u] = lo1 ? ((hf == 0 && nopast) ? -INFINITY : s[hf][hf * 2 + 1]) : s[hf + 1][hf * 2 + 1];
                        mx[u] = fmaxf(e0[u], e1[u]);
                    }
                }
#pragma unroll
                for (int o = 1; o < 4; o <<= 1)
#pragma unroll
                    for (int u = 0; u < 4; ++u) mx[u] = fmaxf(mx[u], __shfl_xor_sync(0xffffffffu, mx[u], o));
#pragma unroll
                for (int u = 0; u < 4; ++u) {
                    const float c = -mx[u] * sl2;
                    e0[u] = ex2(fmaf(e0[u], sl2, c)); e1[u] = ex2(fmaf(e1[u], sl2, c));
                    sum[u] = e0[u] + e1[u];
                }
#pragma unroll
                for (int o = 1; o < 4; o <<= 1)
#pragma unroll
                    for (int u = 0; u < 4; ++u) sum[u] += __shfl_xor_sync(0xffffffffu, sum[u], o);
#pragma unroll
                for (int u = 0; u < 4; ++u) {
                    const int h = u >> 1;
                    const float inv = rcp(sum[u]);
                    const uint32_t p = pack2(e0[u] * inv, e1[u] * inv);
                    const uint32_t* va = ((u & 1) ? v1 : v0) + 4 * h;
                    const uint32_t* vb = ((u & 1) ? v2 : v1) + 4 * h;
                    float o[2][4] = {};
#pragma unroll
                    for (int d = 0; d < 2; ++d) mma16816(o[d], va[2 * d], va[2 * d + 1], vb[2 * d], vb[2 * d + 1], p & lomask, p & ~lomask);
                    stsm4t((orow ^ ((u >> 1) << 6)) + pn * 8192 + (u & 1) * 1024, pack2(o[0][0], o[0][1]), pack2(o[0][2], o[0][3]), pack2(o[1][0], o[1][1]), pack2(o[1][2], o[1][3]));
                }
                fence_async_smem();
                __syncwarp();
                if (lane == 0) mbar_arrive(BAR_SFULL(sb, wg * 2 + pn));
                if (pn == 0) { CS(5); block_end(sb, 0); prepare(1, big); CS(3); }
            }
            CS(6);
            if (tid == 32) TL(41);
            mbar_wait2(BAR_FULL(sb, 32 % NSLOT), BAR_FULL(sb, 33 % NSLOT), (32 / NSLOT) & 1);
            load_slab(xp, sb + (32 % NSLOT + wg) * SLOT);
#pragma unroll
            for (int e = 0; e < 32; ++e) hp[e] = __float_as_uint(big[e]);
            bar_sync(1 + wg, 128);
            if (tid == 0) { TL(6); TC(106); }
            if (tid == 128) TL(44);
            CS(7);
        }
        } else {
        {
            float ag[88], au[88];
            mainloop32<true, LAG>(ag, au, sb, wg, tw, r, EV_LAG1, 48, [](int) {}, [&] {
                Ring q = r; if (!wg) q.next();
                mbar_wait(BAR_EMPTY(sb, q.slot), q.par ^ 1);
                mbar_wait(BAR_FULL(sb, r.slot), r.par);
            });
            if (tid == 0) { TL(10); TC(110); }
            if (tid == 128) TL(51);
            CS(22);
            {
                IDX();
                uint32_t h3[12];
                glu(h3, [&](int i) { return ag[64 + i]; }, [&](int i) { return au[64 + i]; });
#pragma unroll
                for (int k = 0; k < 3; ++k) stsm4(sb + (wg ? P3_SLOT1 : P3_SLOT0) * SLOT + 24576 + (pan_addr ^ (k << 5)), h3[4 * k], h3[4 * k + 1], h3[4 * k + 2], h3[4 * k + 3]);
            }
            glu(hp, [&](int i) { return ag[i]; }, [&](int i) { return au[i]; });
            if (tid == 0) { TL(11); TC(111); }
            if (tid == 128) TL(52);
            CS(23);
        }
        passes128<2, true>(hp, sb, wg, tw, r, stg);
        if (tid == 0) { TL(12); TC(112); }
        }
        {
            float acc[64], gf[32];
            mainloop64(acc, blk == 0, sb, wg, tw, r, [&] { put_h(hp, sb, wg, stg); }, [&] {
                mbar_wait(BAR_ONE(sb, EV_GA + blk), 0);
                unpack_slab(xs, xp);
                uint32_t gt[16];
#pragma unroll
                for (int cg = 0; cg < 16; ++cg) gt[cg] = lds32(sb + OFF_TAB + blk * 256 + cg * 16 + (tw & 3) * 4);
#pragma unroll
                for (int i = 0; i < 16; ++i) unpack2(gt[i], gf[2 * i], gf[2 * i + 1]);
            }, [&] { stg.acquire2(sb, wg); });
            if (tid == 0) { TL(blk ? 13 : 7); TC(blk ? 113 : 107); }
            if (tid == 128) TL(blk ? 57 : 42);
            CS(blk ? 30 : 10);
#pragma unroll
            for (int e = 0; e < 64; ++e) xs[e] = fmaf(gf[(e >> 2) * 2 + (e & 1)], acc[e], xs[e]);
        }
        if (blk) break;
        }
        {
            IDX();
#pragma unroll
            for (int p = 0; p < 2; ++p) {
                store_slab(xs, sb + OFF_STG + wg * 16384, 8192, pan_addr, 4 * p, 4 * p + 4);
                stg.publish(sb, wg, lane);
            }
            cluster_arrive();
            if (tid == 0) TL(14);
            CS(31);
        }
      }
    } else {
        if (warp == 8 && !aux && elect_one()) {
#pragma unroll
            for (int i = 0; i < 4; ++i) mbar_init(BAR_SREADY(sb, i), 1);
#pragma unroll
            for (int i = 0; i < 4; ++i) mbar_init(BAR_ONE(sb, EV_WIN + i), 1);
#pragma unroll
            for (int i = 0; i < 4; ++i) {
                mbar_expect_tx(BAR_SREADY(sb, i), 8192);
                tma_load3(sb + OFF_STG + i * 8192, &mp.x, j * 128 + (i & 1) * 64, m * 64 + (i >> 1) * 32, BAR_SREADY(sb, i));
            }
#pragma unroll 1
            for (int i = 0; i < 4; ++i) {
                mbar_expect_tx(BAR_ONE(sb, EV_WIN + i), 8192);
                tma_load(sb + 5 * SLOT + i * 8192, &mp.wm8, 2 * i * 6144 + (m * 8 + j) * 16, 0, BAR_ONE(sb, EV_WIN + i));
                tma_load(sb + 5 * SLOT + i * 8192 + 4096, &mp.wm8, (2 * i + 1) * 6144 + (m * 8 + j) * 16, 0, BAR_ONE(sb, EV_WIN + i));
            }
        }
        __syncwarp();
        asm volatile("setmaxnreg.dec.sync.aligned.u32 56;");
        if (elect_one()) {
            if (warp == 8) {
                prefetch_map(&mp.wqkv); prefetch_map(&mp.wmod);
            } else if (warp < 11) {
                mbar_init(BAR_EMPTY(sb, NSLOT), 1);
#pragma unroll
                for (int i = 0; i < 2; ++i) { mbar_init(BAR_SFULL(sb, (warp - 9) * 2 + i), 4); if (aux) mbar_init(BAR_SREADY(sb, (warp - 9) * 2 + i), 1); }
#pragma unroll
                for (int i = 0; i < 3; ++i) {
                    mbar_init(BAR_EMPTY(sb, (warp - 9) * 3 + i), 4);
                    mbar_init(BAR_FULL(sb, (warp - 9) * 3 + i), 1); mbar_init(BAR_FULL(sb, (warp - 9) * 3 + i) + AF_REL, 1);
                }
            } else {
#pragma unroll
                for (int i = EV_P0; i < EV_COUNT; ++i) mbar_init(BAR_ONE(sb, i), i == EV_P0 ? 8 : 1);
            }
            asm volatile("fence.mbarrier_init.release.cluster;" ::: "memory");
        }
        __syncwarp();
        cluster_arrive();
        ep = 0;
        if (warp != 8 || aux) ep = flag_get(g_flags + FL_DONE);
        cluster_wait();
        ep = __shfl_sync(0xffffffffu, ep, 0) / NCTA + 1;
        if (warp == 8) {
            const bool el = elect_one();
            Ring r{0, 1};
            if (aux) {
                {
                    uint32_t n = 0;
                    while (!__all_sync(0xffffffffu, ld_pkt16(pt.mail->mod1 + 256).z == ep)) { SPIN_GUARD(n); __nanosleep(200); }
                }
#pragma unroll 1
                for (int it = 0; it < 64; ++it) {
                    const int col = 2048 + (it >> 4) * 1024 + j * 256;
                    mbar_wait(BAR_EMPTY(sb, r.slot), r.par);
                    const uint32_t st = sb + r.slot * SLOT, fb = BAR_FULL(sb, r.slot);
                    if (el) {
                        mbar_expect_tx(fb, 32768);
#pragma unroll
                        for (int b = 0; b < 4; ++b) tma_load(st + b * 8192, &mp.wmod, col + b * 64, (it & 15) * 64, fb);
                    }
                    r.next();
                }
                mbar_wait(BAR_ONE(sb, EV_P0), 0);
                const CUtensorMap* wm = rank ? &mp.wu : &mp.wg;
#pragma unroll 1
                for (int g = 0; g < 128; ++g) {
                    const int mx = (j >> 1) * 8 + (g >> 5) * 2 + rank, k0 = ((g & 14) << 6) + ((g & 16) << 2) + ((g & 1) << 5);
                    if (!(g & 15)) {
                        uint32_t n = 0;
                        while (!__all_sync(0xffffffffu, (int32_t)(flag_get(g_flags + FL_PROG + fidx(mx, lane >> 4, (lane & 14) | ((g >> 4) & 1))) - (ep * 8 + ST_H2)) >= 0)) { SPIN_GUARD(n); __nanosleep(300); }
                    }
                    mbar_wait(BAR_EMPTY(sb, r.slot), r.par);
                    const uint32_t st = sb + r.slot * SLOT, fb = BAR_FULL(sb, r.slot);
                    if (el) {
                        mbar_expect_tx(fb, 24576);
                        tma_load_mc(st + 8192 + rank * 4096, wm, HC3, k0, fb);
                        tma_load_mc(st + 16384 + rank * 4096, wm, HC3 + 64, k0, fb);
                        tma_load(st, &mp.h2l, k0, mx * 128, fb);
                    }
                    r.next();
                }
            } else {
#pragma unroll 1
                for (int it = 0; it < 32; ++it) {
                    const int cb = j * 128 + rank * 64, k0 = kof(it, 2, j);
                    if (it == BW0) mbar_wait(BAR_ONE(sb, BWEV), 0);
                    if (it == BW1) mbar_wait(BAR_ONE(sb, EV_PAR), 0);
                    if (it == 5) mbar_wait(BAR_ONE(sb, EV_P0), 0);
                    if (it == AG0) mbar_wait(BAR_ONE(sb, (AGW & 1) ? EV_AGO : EV_FGO), 0);
                    mbar_wait(BAR_EMPTY(sb, r.slot), r.par);
                    const uint32_t st = sb + r.slot * SLOT, fb = BAR_FULL(sb, r.slot);
                    if (el) {
                        mbar_expect_tx(fb, it < 4 ? 24576 : 28672);
                        tma_load_mc(st + 24576 - rank * 16384, &mp.wqkv, 1024 + cb, k0, fb);
                        tma_load_mc(st + 28672 - rank * 16384, &mp.wqkv, 2048 + cb, k0, fb);
                        tma_load_mc(st + 16384 + rank * 4096, &mp.wqkv, cb, k0, fb);
                        if (it < 4) mbar_arrive(fb + AF_REL);
                        if (it == PFWO + (m >> 1)) { tma_prefetch(&mp.wo, j * 128, m * 64); tma_prefetch(&mp.wo, j * 128 + 64, m * 64); }
                        if (it >= PFG && it < PFG + PFN && (it & 7) == grp) {
                            const int kp = kof(it - PFG + PFO, 2, j);
                            tma_prefetch(rank ? &mp.wu : &mp.wg, hcol(0, j), kp); tma_prefetch(rank ? &mp.wu : &mp.wg, hcol(0, j) + 64, kp);
                            asm volatile("cp.async.bulk.prefetch.tensor.3d.L2.global [%0, {%1, %2, %3}];" :: "l"(rank ? &mp.wu3 : &mp.wg3), "r"(0), "r"(j), "r"(kp) : "memory");
                        }
                    }
                    r.next();
                }
                if (el) mbar_arrive(BAR_ONE(sb, EV_KV));
#pragma unroll 1
                for (int it = 0; it < 16; ++it) {
                    const int k0 = kof(it, 1, j);
                    if (it == AG1) mbar_wait(BAR_ONE(sb, (AGW & 2) ? EV_AGO1 : EV_FGO1), 0);
                    mbar_wait(BAR_EMPTY(sb, r.slot), r.par);
                    const uint32_t st = sb + r.slot * SLOT, fb = BAR_FULL(sb, r.slot);
                    if (el) {
                        mbar_expect_tx(fb, it < 2 ? 32768 : 24576);
                        tma_load_mc(st + 16384 + rank * 8192, &mp.wo, j * 128 + rank * 64, k0, fb);
                        if (it < 2) {
                            tma_load3(st, &mp.x, j * 128, m * 64 + it * 32, fb); tma_load3(st + 8192, &mp.x, j * 128 + 64, m * 64 + it * 32, fb);
                            mbar_arrive(fb + AF_REL);
                        }
                        if (it == 6) { prefetch_map(rank ? &mp.wu : &mp.wg); prefetch_map(rank ? &mp.wu3 : &mp.wg3); }
                    }
                    r.next();
                }
                const CUtensorMap* wm = rank ? &mp.wu : &mp.wg;
#pragma unroll 1
                for (int g = 0; g < 96; ++g) {
                    if (g == AG2) mbar_wait(BAR_ONE(sb, (AGW & 4) ? EV_AGO2 : EV_FGO2), 0);
                    const int p = g >> 5, cb = hcol(p, j), k0 = p == 0 ? kof(g, 2, j) : (g & 31) * 32;
                    mbar_wait(BAR_EMPTY(sb, r.slot), r.par);
                    const uint32_t st = sb + r.slot * SLOT, fb = BAR_FULL(sb, r.slot);
                    if (el) {
                        mbar_expect_tx(fb, (g < 4 || p > 0) ? 24576 : 28672);
                        tma_load_mc(st + 8192 + rank * 4096, wm, cb, k0, fb);
                        tma_load_mc(st + 16384 + rank * 4096, wm, cb + 64, k0, fb);
                        if (p == 0) tma_load3_mc(st + 24576 + rank * 4096, rank ? &mp.wu3 : &mp.wg3, j, k0, fb);
                        else tma_load(st, &mp.h2l, k0, m * 128, fb);
                        if (g < 4) mbar_arrive(fb + AF_REL);
                        if (g == 60) prefetch_map(&mp.wd);
                    }
                    r.next();
                }
#pragma unroll 1
                for (int g = 0; g < 56; ++g) {
                    if (g == 0 || (g & 15) == 6 && g > 6) mbar_wait(BAR_ONE(sb, EV_H0 + (g >> 4)), 0);
                    const int k0 = g * 64;
                    mbar_wait(BAR_EMPTY(sb, r.slot), r.par);
                    const uint32_t st = sb + r.slot * SLOT, fb = BAR_FULL(sb, r.slot);
                    if (el) {
                        mbar_expect_tx(fb, 32768);
                        tma_load_mc(st + 16384 + rank * 8192, &mp.wd, j * 128 + rank * 64, k0, fb);
                        tma_load(st, &mp.hb, k0, m * 128, fb); tma_load(st + 8192, &mp.hb, k0, m * 128 + 64, fb);
                    }
                    r.next();
                }
            }
        } else if (aux) {
            if (warp < 11) {
                const uint32_t w = warp - 9;
                const bool el = elect_one();
#pragma unroll 1
                for (int p = 0; p < 4; ++p) {
                    const int mx = (j >> 1) * 8 + p * 2 + rank;
                    if (el) { mbar_arrive(BAR_SREADY(sb, w * 2)); mbar_arrive(BAR_SREADY(sb, w * 2 + 1)); }
                    mbar_wait2(BAR_SFULL(sb, w * 2), BAR_SFULL(sb, w * 2 + 1), p & 1);
                    if (p < 3) pause(w ? HD1 : HD0);
                    if (el) tma_store(&mp.hb, HC3, mx * 128 + w * 64, sb + OFF_STG + w * 16384);
                    if (p < 3) pause(HP);
                    if (el) {
                        tma_store(&mp.hb, HC3 + 64, mx * 128 + w * 64, sb + OFF_STG + w * 16384 + 8192);
                        bulk_commit(); bulk_wait_fence(); flag_set(g_flags + FL_AUX + mx * 2 + w, ep * 8 + ST_H + 3);
                    }
                }
            }
        } else if (warp == 11) {
            const bool el = elect_one();
            const int row0 = m * 128;
            const uint32_t* const fl = g_flags + FL_PROG + fidx(m, lane >> 4, kof(lane & 15, 1, j) >> 6);
            if (el) { prefetch_map(&mp.h1h); prefetch_map(&mp.h2h); prefetch_map(&mp.h2l); }
            auto gate = [&](int vec, int ev) {
                uint4 v; uint32_t n = 0;
                while (true) {
                    v = ld_pkt2(g_mod + vec * 512 + j * 64 + lane * 2);
                    if (__all_sync(0xffffffffu, v.y == ep && v.w == ep)) break;
                    SPIN_GUARD(n); __nanosleep(300);
                }
                asm volatile("st.shared.v2.u32 [%0], {%1, %2};" :: "r"(sb + OFF_TAB + (ev - EV_GA) * 256 + lane * 8), "r"(v.x), "r"(v.z) : "memory");
                __syncwarp();
                if (lane == 0) mbar_arrive(BAR_ONE(sb, ev));
            };
            {
                const uint4* pk = pt.mail->mod1 + grp * 512 + j * 32 + lane;
                uint4 a, b; uint32_t n = 0;
                mbar_wait(BAR_ONE(sb, EV_WIN3), 0);
                while (true) {
                    a = ld_pkt16(pk); b = ld_pkt16(pk + 256);
                    if (__all_sync(0xffffffffu, a.z == ep && b.z == ep)) break;
                    SPIN_GUARD(n);
                }
                sts128(sb + OFF_PAR + lane * 16, a.x, a.y, b.x, b.y);
                __syncwarp();
                if (lane == 0) { mbar_arrive(BAR_ONE(sb, EV_PAR)); TL(46); }
            }
            mbar_wait(BAR_ONE(sb, EV_P0), 0);
            Ring r{0, 1};
#pragma unroll 1
            for (int ph = 0; ph < 3; ++ph) {
                const int sh = ph == 1 ? 1 : 2, nst = 8 << sh;
                const uint32_t half = 16384 >> sh, target = ep * 8 + ST_H1 + ph;
                const CUtensorMap* tm = ph == 0 ? &mp.h1h : ph == 1 ? &mp.o : &mp.h2h;
                if (ph == 1) {
                    gate(2, EV_GA);
                    mbar_wait(BAR_SREADY(sb, 1), 1);
#pragma unroll 1
                    for (int i = 0; i < 2; ++i)
                        fetch_halo<1>(g_halo + ((m - 1) * 8 + j) * 512 + i * 256 + 128 + lane, m == 0, sb + OFF_STG + 8192 + i * 4096 + lane * 16,
                                      [&] { __syncwarp(); if (el) mbar_arrive(BAR_ONE(sb, EV_TAIL + 2 * i)); });
                    CS(32);
                }
                if (ph == 2) {
                    uint32_t n = 0;
                    while ((int32_t)(flag_get(g_flags + FL_LN2) - ep * 8) < 0) { SPIN_GUARD(n); __nanosleep(200); }
                    const uint4 v = __ldcg((const uint4*)(g_par2 + j * 128) + lane);
                    sts128(sb + OFF_PAR + lane * 16, v.x, v.y, v.z, v.w);
                    __syncwarp();
                    if (lane == 0) mbar_arrive(BAR_ONE(sb, EV_LN2));
                }
                const uint32_t lw = ~lane & 1, lt = lane >> 1, ls = (r.slot + lt) % NSLOT, lk = kof(lt, sh, j), lb = BAR_FULL(sb, ls) + (lw ? 0 : AF_REL);
                const uint32_t* const lf = g_flags + FL_PROG + fidx(m, lw, lk >> 6);
                int fr = 1 << sh;
                uint32_t todo = 0x3ffffu >> (2 * fr) << (2 * fr), have = ~todo, n = 0, v = 0;
                r.skip(fr);
#pragma unroll 1
                for (; fr < NSLOT; ++fr) { mbar_wait(BAR_EMPTY(sb, r.slot), r.par); r.next(); }
                if (ph == XST - 1) CS(33);
                do {
                    if (!((have >> lane) & 1)) v = flag_get(lf);
                    while (ph == 2 && fr < FRCAP && mbar_test(BAR_EMPTY(sb, r.slot), r.par)) { ++fr; r.next(); }
                    SPIN_GUARD(n);
                    have |= __ballot_sync(0xffffffffu, (int32_t)(v - target) >= 0);
                    const uint32_t go = have & todo & ((1u << (2 * fr)) - 1);
                    if ((go >> lane) & 1) {
                        if (!lw) mbar_expect_tx(lb, half);
                        tma_load(sb + ls * SLOT + lw * half, tm, lk, row0 + lw * 64, lb);
                    }
                    __syncwarp();
                    if (lane < 2 && (todo & (0x555u << lane)) && !(todo & ~go & (0x555u << lane))) mbar_arrive(BAR_ONE(sb, (lane ? EV_FGO : EV_AGO) + ph));
                    if (ph == XST - 1) { if (go & (1u << (2 << sh))) CS(34); if (go & (2u << (2 << sh))) CS(35); if (todo & 0x555u) CS(36); if (todo & 0xaaau) CS(37); }
                    todo &= ~go;
                } while (~have);
                if (ph == XST - 1) CS(38);
                int k = kof(fr, sh, j);
#pragma unroll 1
                for (; fr < nst; ++fr) {
                    if (fr == 9 || fr == 18) {
                        const uint32_t skip = fr == 9 << (sh - 1) ? 0 : ~0x01fc01fcu;
                        while (~(__ballot_sync(0xffffffffu, (int32_t)(flag_get(fl) - target) >= 0) | skip)) SPIN_GUARD(n);
                    }
                    const uint32_t st = sb + r.slot * SLOT, fb = BAR_FULL(sb, r.slot);
                    mbar_wait(BAR_EMPTY(sb, r.slot), r.par);
                    if (el) {
                        tma_load(st + half, tm, k, row0 + 64, fb);
                        mbar_expect_tx(fb + AF_REL, half);
                        tma_load(st, tm, k, row0, fb + AF_REL);
                    }
                    if (ph == XST - 1 && fr == 9) CS(39);
                    r.next();
                    k = kof(fr + 1, sh, j);
                }
            }
#pragma unroll 1
            for (int p = 0; p < 4; ++p) {
                const uint32_t* f = p < 3 ? fl : g_flags + FL_AUX + m * 2 + (lane & 1);
                uint32_t n = 0;
                while (!__all_sync(0xffffffffu, (int32_t)(flag_get(f) - (ep * 8 + ST_H + p)) >= 0)) { SPIN_GUARD(n); __nanosleep(300); }
                if (el) mbar_arrive(BAR_ONE(sb, EV_H0 + p));
                if (p == 0) gate(5, EV_GB);
            }
        } else {
            const uint32_t w = warp - 9;
            const int row0 = m * 128 + w * 64;
            const uint32_t stg = sb + OFF_STG + w * 16384;
            uint32_t* const fl = g_flags + FL_PROG + fidx(m, w, 2 * j);
            uint32_t b = 0, par = 0;
            const bool el = elect_one();
            auto store = [&](const CUtensorMap* tm, int col, bool nat = false) {
                mbar_wait(BAR_SFULL(sb, w * 2 + b), (par >> b) & 1);
                par ^= 1u << b;
                if (el) {
                    if (nat) tma_store3(tm, col, row0 >> 1, 0, stg + b * 8192); else tma_store(tm, col, row0, stg + b * 8192);
                    bulk_commit();
                }
                b ^= 1;
            };
            auto send2 = [&](const CUtensorMap* tm, const uint32_t* buf, int step) {
                const uint32_t* const q = buf + (size_t)((row0 + lane) * (D_ / 2) + j * 64 + 31);
                store(tm, j * 128);
                if (step == XST) CS(33);
                uint32_t z = landed(el, q, D_ / 2, pt.zero);
                if (el) flag_set(fl, ep * 8 + step + z);
                if (step == XST) CS(34);
                if (step != ST_O) { mbar_wait(BAR_ONE(sb, EV_FGO + step - ST_H1), 0); pause(step == ST_H1 ? (w ? P1H : P1H + 1000) : w ? P2L : P2F); }
                store(tm, j * 128 + 64);
                if (step == XST) CS(35);
                z = landed(el, q + 32, D_ / 2, pt.zero);
                if (el) flag_set(fl + 1, ep * 8 + step + z);
                if (step == XST) CS(36);
            };
            auto free2 = [&]() { if (el) { mbar_arrive(BAR_SREADY(sb, w * 2)); mbar_arrive(BAR_SREADY(sb, w * 2 + 1)); } };
            if (el) { prefetch_map(&mp.h1s); prefetch_map(&mp.o); prefetch_map(&mp.h2s); prefetch_map(&mp.hb); prefetch_map(&mp.out); prefetch_map(&mp.wo); }
            if (el) { flag_set(fl, ep * 8); flag_set(fl + 1, ep * 8); }
            send2(&mp.h1s, pt.h1, ST_H1);
            if (w == 0) TL(47);
            free2();
            mbar_wait(BAR_ONE(sb, EV_KV), 0);
            mbar_wait(BAR_SREADY(sb, 0), 1);
            fetch_halo<1>(g_halo + ((m - 1) * 8 + j) * 512 + w * 256 + lane, m == 0, sb + OFF_STG + w * 4096 + lane * 16, [&] { bar_arrive(NB_TAIL + 2 * w, 64); CS(38); });
            send2(&mp.o, pt.o, ST_O);
            if (w == 0) TL(40); else TL(38);
            free2();
            send2(&mp.h2s, pt.o, ST_H2);
            if (el) { prefetch_map(&mp.hb); prefetch_map(&mp.hb3); }
            if (w == 0) TL(37);
            free2();
#pragma unroll 1
            for (int p = 0; p < 3; ++p) {
                const int col = hcol(p, j);
                mbar_wait(BAR_SFULL(sb, w * 2), par & 1);
                pause(w ? HD1 : HD0); store(&mp.hb, col);
                pause(HP); store(&mp.hb, col + 64);
                if (p == 0) {
                    pause(HP);
                    if (el) { tma_store3(&mp.hb3, 0, j, row0, sb + (w ? P3_SLOT1 : P3_SLOT0) * SLOT + 24576); bulk_commit(); }
                }
                if (el) bulk_wait_read();
                free2();
                if (el) { bulk_wait_fence(); flag_set(fl, ep * 8 + ST_H + p); flag_set(fl + 1, ep * 8 + ST_H + p); }
            }
            cluster_arrive_early = true;
            cluster_arrive();
            store(&mp.out, j * 128, true); store(&mp.out, j * 128 + 64, true);
            if (el) bulk_wait_read();
        }
        __syncwarp();
    }
    if (aux || (wg == 2 && !cluster_arrive_early)) cluster_arrive();
    cluster_wait();
    if (KDEBUG == 5) __syncthreads();
    if (tid == 0) {
        TL(15);
        flag_add(pt.mail->flags + FL_DONE);
    }
}

typedef CUresult (*EncodeFn)(CUtensorMap*, CUtensorMapDataType, cuuint32_t, void*, const cuuint64_t*, const cuuint64_t*, const cuuint32_t*,
                             const cuuint32_t*, CUtensorMapInterleave, CUtensorMapSwizzle, CUtensorMapL2promotion, CUtensorMapFloatOOBfill);

void make_map(EncodeFn fn, CUtensorMap* m, const void* ptr, uint64_t rows, uint64_t cols, uint32_t brows, uint32_t bcols) {
    cuuint64_t dims[2] = {cols, rows}, strides[1] = {cols * 2};
    cuuint32_t box[2] = {bcols, brows}, es[2] = {1, 1};
    fn(m, CU_TENSOR_MAP_DATA_TYPE_BFLOAT16, 2, (void*)ptr, dims, strides, box, es, CU_TENSOR_MAP_INTERLEAVE_NONE,
       bcols == 64 ? CU_TENSOR_MAP_SWIZZLE_128B : bcols == 32 ? CU_TENSOR_MAP_SWIZZLE_64B : CU_TENSOR_MAP_SWIZZLE_NONE, CU_TENSOR_MAP_L2_PROMOTION_L2_256B, CU_TENSOR_MAP_FLOAT_OOB_FILL_NONE);
}

void make_map3(EncodeFn fn, CUtensorMap* m, const void* ptr) {
    cuuint64_t dims[3] = {D_, S_ / 2, 2}, strides[2] = {4 * D_, 2 * D_};
    cuuint32_t box[3] = {64, 32, 2}, es[3] = {1, 1, 1};
    fn(m, CU_TENSOR_MAP_DATA_TYPE_BFLOAT16, 3, (void*)ptr, dims, strides, box, es, CU_TENSOR_MAP_INTERLEAVE_NONE,
       CU_TENSOR_MAP_SWIZZLE_128B, CU_TENSOR_MAP_L2_PROMOTION_L2_256B, CU_TENSOR_MAP_FLOAT_OOB_FILL_NONE);
}

void make_map48(EncodeFn fn, CUtensorMap* m, const void* ptr, uint64_t rows, uint32_t brows) {
    cuuint64_t dims[3] = {48, 8, rows}, strides[2] = {96, 2 * F_};
    cuuint32_t box[3] = {64, 1, brows}, es[3] = {1, 1, 1};
    fn(m, CU_TENSOR_MAP_DATA_TYPE_BFLOAT16, 3, (void*)ptr, dims, strides, box, es, CU_TENSOR_MAP_INTERLEAVE_NONE,
       CU_TENSOR_MAP_SWIZZLE_128B, CU_TENSOR_MAP_L2_PROMOTION_L2_256B, CU_TENSOR_MAP_FLOAT_OOB_FILL_NONE);
}

}

extern "C" void kernel_launch(void* const* d_in, const int* in_sizes, int n_in, void* d_out, int out_size) {
    (void)in_sizes; (void)n_in; (void)out_size;
    void* fnp = nullptr;
    cudaDriverEntryPointQueryResult qr;
    cudaGetDriverEntryPoint("cuTensorMapEncodeTiled", &fnp, cudaEnableDefault, &qr);
    EncodeFn fn = (EncodeFn)fnp;
    void *h1, *o, *h2, *hb, *mail;
    cudaGetSymbolAddress(&h1, g_h1);
    cudaGetSymbolAddress(&mail, g_mail);
    cudaGetSymbolAddress(&o, g_o);
    cudaGetSymbolAddress(&hb, g_hb);
    h2 = o;
    Maps mp;
    make_map(fn, &mp.h1h, h1, S_, D_, 64, 32);
    make_map(fn, &mp.h2h, h2, S_, D_, 64, 32);
    make_map(fn, &mp.h1s, h1, S_, D_, 64, 64);
    make_map(fn, &mp.o, o, S_, D_, 64, 64);
    make_map(fn, &mp.h2l, h2, S_, D_, 128, 32);
    make_map(fn, &mp.h2s, h2, S_, D_, 64, 64);
    make_map(fn, &mp.hb, hb, S_, F_, 64, 64);
    make_map(fn, &mp.wqkv, d_in[1], D_, 3 * D_, 32, 64);
    make_map(fn, &mp.wo, d_in[2], D_, D_, 64, 64);
    make_map(fn, &mp.wg, d_in[4], D_, F_, 32, 64);
    make_map(fn, &mp.wu, d_in[5], D_, F_, 32, 64);
    make_map(fn, &mp.wd, d_in[6], F_, D_, 64, 64);
    make_map(fn, &mp.wmod, d_in[8], D_, 6 * D_, 64, 64);
    make_map(fn, &mp.wm8, d_in[8], D_ / 8, 8 * 6 * D_, 128, 16);
    make_map3(fn, &mp.x, d_in[0]);
    make_map3(fn, &mp.out, d_out);
    make_map48(fn, &mp.wg3, d_in[4], D_, 32);
    make_map48(fn, &mp.wu3, d_in[5], D_, 32);
    make_map48(fn, &mp.hb3, hb, S_, 64);
    cudaFuncSetAttribute(fused_block_kernel, cudaFuncAttributeMaxDynamicSharedMemorySize, SMEM_BYTES);
    cudaLaunchConfig_t cfg = {};
    cfg.gridDim = dim3(NCTA); cfg.blockDim = dim3(384); cfg.dynamicSmemBytes = SMEM_BYTES; cfg.stream = cudaStreamPerThread;
    cudaLaunchAttribute at[1];
    at[0].id = cudaLaunchAttributeClusterDimension; at[0].val.clusterDim.x = 2; at[0].val.clusterDim.y = 1; at[0].val.clusterDim.z = 1;
    cfg.attrs = at; cfg.numAttrs = 1;
    const Ptrs pt{(const __nv_bfloat16*)d_in[7], (Mail*)mail, (const uint32_t*)h1, (const uint32_t*)o, 0};
    cudaLaunchKernelEx(&cfg, fused_block_kernel, pt, mp);
}
```

```cpp
#include <cuda_runtime.h>
#include <cuda_bf16.h>
#include <cuda.h>
#include <stdint.h>
#include <stddef.h>

#define LAG 4
#define LAGS 4
#define LAGW 2
#define LAGD 4
#define LAGQ 4
#define PUT1 5
#define PUT0 10
#define PUTD1 5
#define PUTD0 10
#define MIDD 30
#define HD1 3600
#define HD0 1500
#define HP 2600
#define P1H 3000
#define P2L 2000
#define P2F 3000
#define PDLY 500
#define FD0 150
#define AG0 6
#define AG1 6
#define AG2 8
#define AGW 2
#define FRCAP 8
#define BW0 0
#define BWEV EV_WIN
#define BW1 3
#define LWAIT 2
#define PFWO 12
#define PFG 8
#define PFN 24
#define PFO 0
#define KDEBUG 0
#define CSW 0
#define XST ST_O

namespace {

constexpr int S_ = 2048, D_ = 1024, F_ = 3584;
constexpr int NCTA = 132;
constexpr int NSLOT = 6;
constexpr uint32_t SLOT = 32768;
constexpr uint32_t OFF_STG = NSLOT * SLOT;
constexpr uint32_t OFF_BAR = OFF_STG + 32768;
constexpr uint32_t OFF_PAR = OFF_BAR + 512;
constexpr uint32_t OFF_TAB = OFF_PAR + 768;
constexpr uint32_t OFF_TL = OFF_PAR + 2048;
constexpr uint32_t SMEM_BYTES = OFF_TL + (KDEBUG ? 512 : 0);
constexpr uint32_t P3_SLOT1 = (32 + 16 + 32) % NSLOT, P3_SLOT0 = (P3_SLOT1 + 1) % NSLOT;

constexpr int ST_H1 = 1, ST_O = 2, ST_H2 = 3, ST_H = 4, FL_DONE = 0, FL_LN2 = 1, FL_AUX = 32, FL_PROG = 64;

struct Maps {
    CUtensorMap h1h, h1s, o, h2h, h2l, h2s, hb, wqkv, wo, wg, wu, wd, wmod, wm8, x, out, wg3, wu3, hb3;
};

struct Mail {
    uint32_t flags[16 * 32 + 64];
    uint2 mod[6 * D_ / 2];
    uint4 mod1[8 * 512];
    uint4 st1[128 * 512];
    uint32_t par2[D_];
    uint4 halo[128 * 512];
};
struct Ptrs { const __nv_bfloat16* c; Mail* mail; const uint32_t *h1, *o; uint32_t zero; };

__device__ __align__(128) Mail g_mail;
__device__ __align__(128) __nv_bfloat16 g_h1[S_ * D_];
__device__ __align__(128) __nv_bfloat16 g_o[S_ * D_];
__device__ __align__(128) __nv_bfloat16 g_hb[S_ * F_];
#define TL(i) do {} while (0)
#define TC(i) do {} while (0)
#define TS(g, which) do {} while (0)
#define CS(i) do {} while (0)

__device__ __forceinline__ uint32_t smem_u32(const void* p) { return (uint32_t)__cvta_generic_to_shared(p); }
__device__ __forceinline__ void mbar_init(uint32_t bar, uint32_t cnt) { asm volatile("mbarrier.init.shared::cta.b64 [%0], %1;" :: "r"(bar), "r"(cnt) : "memory"); }
__device__ __forceinline__ void mbar_expect_tx(uint32_t bar, uint32_t bytes) { asm volatile("mbarrier.arrive.expect_tx.shared::cta.b64 _, [%0], %1;" :: "r"(bar), "r"(bytes) : "memory"); }
__device__ __forceinline__ void mbar_arrive(uint32_t bar) { asm volatile("mbarrier.arrive.shared::cta.b64 _, [%0];" :: "r"(bar) : "memory"); }
__device__ __forceinline__ void mbar_arrive_cta(uint32_t bar, uint32_t cta) {
    asm volatile("{\n.reg .b32 r;\nmapa.shared::cluster.u32 r, %0, %1;\nmbarrier.arrive.shared::cluster.b64 _, [r];\n}" :: "r"(bar), "r"(cta) : "memory");
}
__device__ __forceinline__ void mbar_wait(uint32_t bar, uint32_t parity) {
    asm volatile("{\n.reg .pred p;\n.reg .u32 n;\nmov.u32 n, 0;\n"
        "W_LOOP:\nmbarrier.try_wait.parity.shared::cta.b64 p, [%0], %1;\n@p bra W_DONE;\n"
        "add.u32 n, n, 1;\nsetp.lt.u32 p, n, 0x400000;\n@p bra W_LOOP;\ntrap;\nW_DONE:\n}" :: "r"(bar), "r"(parity) : "memory");
}
__device__ __forceinline__ void mbar_wait2(uint32_t b0, uint32_t b1, uint32_t parity) {
    asm volatile("{\n.reg .pred p, q;\n.reg .u32 n;\nmov.u32 n, 0;\n"
        "W_LOOP:\nmbarrier.try_wait.parity.shared::cta.b64 p, [%0], %2;\nmbarrier.try_wait.parity.shared::cta.b64 q, [%1], %2;\nand.pred p, p, q;\n@p bra W_DONE;\n"
        "add.u32 n, n, 1;\nsetp.lt.u32 p, n, 0x400000;\n@p bra W_LOOP;\ntrap;\nW_DONE:\n}" :: "r"(b0), "r"(b1), "r"(parity) : "memory");
}
__device__ __forceinline__ bool mbar_test(uint32_t bar, uint32_t parity) {
    uint32_t r; asm volatile("{\n.reg .pred p;\nmbarrier.test_wait.parity.shared::cta.b64 p, [%1], %2;\nselp.u32 %0, 1, 0, p;\n}" : "=r"(r) : "r"(bar), "r"(parity) : "memory"); return r;
}
__device__ __forceinline__ bool mbar_test2(uint32_t b0, uint32_t b1, uint32_t parity) {
    uint32_t r;
    asm volatile("{\n.reg .pred p, q;\nmbarrier.test_wait.parity.shared::cta.b64 p, [%1], %3;\nmbarrier.test_wait.parity.shared::cta.b64 q, [%2], %3;\n"
        "and.pred p, p, q;\nselp.u32 %0, 1, 0, p;\n}" : "=r"(r) : "r"(b0), "r"(b1), "r"(parity) : "memory");
    return r;
}
__device__ __forceinline__ void tma_load3(uint32_t dst, const CUtensorMap* m, int c0, int c1, uint32_t bar) {
    asm volatile("cp.async.bulk.tensor.3d.shared::cluster.global.mbarrier::complete_tx::bytes [%0], [%1, {%3, %4, %5}], [%2];"
        :: "r"(dst), "l"(m), "r"(bar), "r"(c0), "r"(c1), "r"(0) : "memory");
}
__device__ __forceinline__ void tma_store3(const CUtensorMap* m, int c0, int c1, int c2, uint32_t src) {
    asm volatile("cp.async.bulk.tensor.3d.global.shared::cta.bulk_group [%0, {%2, %3, %4}], [%1];" :: "l"(m), "r"(src), "r"(c0), "r"(c1), "r"(c2) : "memory");
}
__device__ __forceinline__ void tma_load3_mc(uint32_t dst, const CUtensorMap* m, int c1, int c2, uint32_t bar) {
    asm volatile("cp.async.bulk.tensor.3d.shared::cluster.global.mbarrier::complete_tx::bytes.multicast::cluster.L2::cache_hint [%0], [%1, {%3, %4, %5}], [%2], %6, %7;"
        :: "r"(dst), "l"(m), "r"(bar), "r"(0), "r"(c1), "r"(c2), "h"((uint16_t)3), "l"(0x12F0000000000000ull) : "memory");
}
__device__ __forceinline__ void tma_load(uint32_t dst, const CUtensorMap* m, int c0, int c1, uint32_t bar) {
    asm volatile("cp.async.bulk.tensor.2d.shared::cluster.global.mbarrier::complete_tx::bytes [%0], [%1, {%3, %4}], [%2];"
        :: "r"(dst), "l"(m), "r"(bar), "r"(c0), "r"(c1) : "memory");
}
__device__ __forceinline__ void tma_load_mc(uint32_t dst, const CUtensorMap* m, int c0, int c1, uint32_t bar) {
    asm volatile("cp.async.bulk.tensor.2d.shared::cluster.global.mbarrier::complete_tx::bytes.multicast::cluster.L2::cache_hint [%0], [%1, {%3, %4}], [%2], %5, %6;"
        :: "r"(dst), "l"(m), "r"(bar), "r"(c0), "r"(c1), "h"((uint16_t)3), "l"(0x12F0000000000000ull) : "memory");
}
__device__ __forceinline__ void tma_prefetch(const CUtensorMap* m, int c0, int c1) {
    asm volatile("cp.async.bulk.prefetch.tensor.2d.L2.global [%0, {%1, %2}];" :: "l"(m), "r"(c0), "r"(c1) : "memory");
}
__device__ __forceinline__ void tma_store(const CUtensorMap* m, int c0, int c1, uint32_t src) {
    asm volatile("cp.async.bulk.tensor.2d.global.shared::cta.bulk_group [%0, {%2, %3}], [%1];" :: "l"(m), "r"(src), "r"(c0), "r"(c1) : "memory");
}
__device__ __forceinline__ void bulk_commit() { asm volatile("cp.async.bulk.commit_group;" ::: "memory"); }
__device__ __forceinline__ void bulk_wait_read() { asm volatile("cp.async.bulk.wait_group.read 0;" ::: "memory"); }
__device__ __forceinline__ void fence_async_smem() { asm volatile("fence.proxy.async.shared::cta;" ::: "memory"); }
__device__ __forceinline__ void prefetch_map(const CUtensorMap* m) { asm volatile("prefetch.tensormap [%0];" :: "l"(m) : "memory"); }
__device__ __forceinline__ void wg_fence() { asm volatile("wgmma.fence.sync.aligned;" ::: "memory"); }
__device__ __forceinline__ void wg_commit() { asm volatile("wgmma.commit_group.sync.aligned;" ::: "memory"); }
template <int N> __device__ __forceinline__ void wg_wait() { asm volatile("wgmma.wait_group.sync.aligned %0;" :: "n"(N) : "memory"); }
__device__ __forceinline__ void bar_sync(int id, int n) { asm volatile("bar.sync %0, %1;" :: "r"(id), "r"(n) : "memory"); }
__device__ __forceinline__ void bar_arrive(int id, int n) { asm volatile("bar.arrive %0, %1;" :: "r"(id), "r"(n) : "memory"); }
__device__ __forceinline__ void flag_add(uint32_t* f) { asm volatile("red.relaxed.gpu.global.add.u32 [%0], 1;" :: "l"(f) : "memory"); }
__device__ __forceinline__ void flag_set(uint32_t* f, uint32_t v) { asm volatile("red.relaxed.gpu.global.max.u32 [%0], %1;" :: "l"(f), "r"(v) : "memory"); }
__device__ __forceinline__ uint32_t flag_get(const uint32_t* f) { uint32_t v; asm volatile("ld.relaxed.gpu.global.u32 %0, [%1];" : "=r"(v) : "l"(f) : "memory"); return v; }
__device__ __forceinline__ void bulk_wait_fence() { asm volatile("cp.async.bulk.wait_group 0;\nfence.proxy.async.global;\nfence.acq_rel.gpu;" ::: "memory"); }
__device__ __forceinline__ uint32_t landed(bool el, const uint32_t* p, uint32_t pitch, uint32_t zero) {
    if (el) asm volatile("cp.async.bulk.wait_group 0;" ::: "memory");
    __syncwarp();
    const uint32_t a = flag_get(p), b = flag_get(p + 32 * pitch);
    return __reduce_or_sync(0xffffffffu, (a | b) & zero);
}
__device__ __forceinline__ uint32_t d16(uint32_t addr) { return (addr & 0x3FFFF) >> 4; }
__device__ __forceinline__ uint64_t mk_desc(uint32_t a16, uint32_t off, uint32_t lbo, uint32_t sbo, uint32_t swz) {
    const uint32_t lo = a16 + (off >> 4) + ((lbo >> 4) << 16), hi = (sbo >> 4) | (swz << 30);
    return ((uint64_t)hi << 32) | lo;
}
__device__ __forceinline__ uint32_t pack2(float lo, float hi) {
    uint32_t r; asm("cvt.rn.bf16x2.f32 %0, %1, %2;" : "=r"(r) : "f"(hi), "f"(lo)); return r;
}
__device__ __forceinline__ uint32_t hfma2_bf16(uint32_t a, uint32_t b, uint32_t c) {
    uint32_t r; asm("fma.rn.bf16x2 %0, %1, %2, %3;" : "=r"(r) : "r"(a), "r"(b), "r"(c)); return r;
}
__device__ __forceinline__ float bf_lo(uint32_t v) { return __uint_as_float(v << 16); }
__device__ __forceinline__ float bf_hi(uint32_t v) { return __uint_as_float(v & 0xFFFF0000u); }
__device__ __forceinline__ void unpack2(uint32_t v, float& lo, float& hi) {
    asm volatile("shl.b32 %0, %2, 16;\nand.b32 %1, %2, 0xffff0000;" : "=f"(lo), "=f"(hi) : "r"(v));
}
__device__ __forceinline__ float bf_round(float x) { return __bfloat162float(__float2bfloat16_rn(x)); }
__device__ __forceinline__ void stsm4(uint32_t addr, uint32_t r0, uint32_t r1, uint32_t r2, uint32_t r3) {
    asm volatile("stmatrix.sync.aligned.m8n8.x4.shared.b16 [%0], {%1, %2, %3, %4};" :: "r"(addr), "r"(r0), "r"(r1), "r"(r2), "r"(r3) : "memory");
}
__device__ __forceinline__ void stsm4t(uint32_t addr, uint32_t r0, uint32_t r1, uint32_t r2, uint32_t r3) {
    asm volatile("stmatrix.sync.aligned.m8n8.x4.trans.shared.b16 [%0], {%1, %2, %3, %4};" :: "r"(addr), "r"(r0), "r"(r1), "r"(r2), "r"(r3) : "memory");
}
__device__ __forceinline__ uint32_t movm(uint32_t a) { uint32_t d; asm volatile("movmatrix.sync.aligned.m8n8.trans.b16 %0, %1;" : "=r"(d) : "r"(a)); return d; }
__device__ __forceinline__ void ldsm4(uint32_t addr, uint32_t& r0, uint32_t& r1, uint32_t& r2, uint32_t& r3) {
    asm volatile("ldmatrix.sync.aligned.m8n8.x4.shared.b16 {%0, %1, %2, %3}, [%4];" : "=r"(r0), "=r"(r1), "=r"(r2), "=r"(r3) : "r"(addr) : "memory");
}
__device__ __forceinline__ void ldsm4t(uint32_t addr, uint32_t& r0, uint32_t& r1, uint32_t& r2, uint32_t& r3) {
    asm volatile("ldmatrix.sync.aligned.m8n8.x4.trans.shared.b16 {%0, %1, %2, %3}, [%4];" : "=r"(r0), "=r"(r1), "=r"(r2), "=r"(r3) : "r"(addr) : "memory");
}
__device__ __forceinline__ void mma16816(float (&c)[4], uint32_t a0, uint32_t a1, uint32_t a2, uint32_t a3, uint32_t b0, uint32_t b1) {
    asm("mma.sync.aligned.m16n8k16.row.col.f32.bf16.bf16.f32 {%0, %1, %2, %3}, {%4, %5, %6, %7}, {%8, %9}, {%0, %1, %2, %3};"
        : "+f"(c[0]), "+f"(c[1]), "+f"(c[2]), "+f"(c[3]) : "r"(a0), "r"(a1), "r"(a2), "r"(a3), "r"(b0), "r"(b1));
}
__device__ __forceinline__ float rsq(float x) { float r; asm("rsqrt.approx.ftz.f32 %0, %1;" : "=f"(r) : "f"(x)); return r; }
__device__ __forceinline__ float rcp(float x) { float r; asm("rcp.approx.ftz.f32 %0, %1;" : "=f"(r) : "f"(x)); return r; }
__device__ __forceinline__ float ex2(float x) { float r; asm("ex2.approx.ftz.f32 %0, %1;" : "=f"(r) : "f"(x)); return r; }
__device__ __forceinline__ float tanh_(float x) { float t; asm("tanh.approx.f32 %0, %1;" : "=f"(t) : "f"(x)); return t; }
__device__ __forceinline__ void block_end(uint32_t opaque, uint32_t id) { asm volatile("{\n.reg .pred p;\nsetp.eq.u32 p, %0, %1;\n@p trap;\n}" :: "r"(opaque), "r"(0xffffff00u + id)); }
__device__ __forceinline__ float silu_(float x) { return __fdividef(x, 1.f + __expf(-x)); }
__device__ __forceinline__ void st_pkt(void* p, uint32_t a, uint32_t b) {
    asm volatile("{\n.reg .b64 t;\nmov.b64 t, {%1, %2};\nst.relaxed.gpu.global.b64 [%0], t;\n}" :: "l"(p), "r"(a), "r"(b) : "memory");
}
__device__ __forceinline__ uint4 ld_pkt2(const void* p) {
    uint4 v; asm volatile("{\n.reg .b64 t, u;\nld.relaxed.gpu.global.v2.b64 {t, u}, [%4];\nmov.b64 {%0, %1}, t;\nmov.b64 {%2, %3}, u;\n}"
        : "=r"(v.x), "=r"(v.y), "=r"(v.z), "=r"(v.w) : "l"(p) : "memory"); return v;
}
__device__ __forceinline__ void st_pkt16(void* p, uint32_t a, uint32_t b, uint32_t c, uint32_t d) {
    asm volatile("{\n.reg .b64 t, u;\n.reg .b128 w;\nmov.b64 t, {%1, %2};\nmov.b64 u, {%3, %4};\nmov.b128 w, {t, u};\nst.relaxed.gpu.global.b128 [%0], w;\n}"
        :: "l"(p), "r"(a), "r"(b), "r"(c), "r"(d) : "memory");
}
__device__ __forceinline__ uint4 ld_pkt16(const void* p) {
    uint4 v; asm volatile("{\n.reg .b64 t, u;\n.reg .b128 w;\nld.relaxed.gpu.global.b128 w, [%4];\nmov.b128 {t, u}, w;\nmov.b64 {%0, %1}, t;\nmov.b64 {%2, %3}, u;\n}"
        : "=r"(v.x), "=r"(v.y), "=r"(v.z), "=r"(v.w) : "l"(p) : "memory"); return v;
}
#define SPIN_GUARD(n) do { if (++(n) > (1u << 22)) asm volatile("trap;"); } while (0)
__device__ __forceinline__ uint4 lds128(uint32_t a) { uint4 v; asm volatile("ld.shared.v4.u32 {%0, %1, %2, %3}, [%4];" : "=r"(v.x), "=r"(v.y), "=r"(v.z), "=r"(v.w) : "r"(a) : "memory"); return v; }
__device__ __forceinline__ void sts128(uint32_t a, uint32_t x, uint32_t y, uint32_t z, uint32_t w) { asm volatile("st.shared.v4.u32 [%0], {%1, %2, %3, %4};" :: "r"(a), "r"(x), "r"(y), "r"(z), "r"(w) : "memory"); }
__device__ __forceinline__ uint32_t lds32(uint32_t a) { uint32_t v; asm volatile("ld.shared.u32 %0, [%1];" : "=r"(v) : "r"(a) : "memory"); return v; }
__device__ __forceinline__ void sts32(uint32_t a, uint32_t v) { asm volatile("st.shared.u32 [%0], %1;" :: "r"(a), "r"(v) : "memory"); }
__device__ __forceinline__ bool elect_one() {
    uint32_t p; asm volatile("{\n.reg .pred q;\nelect.sync _|q, 0xffffffff;\nselp.u32 %0, 1, 0, q;\n}" : "=r"(p)); return p;
}
__device__ __forceinline__ void pause(uint32_t cycles) {
    uint32_t t0, t; asm volatile("mov.u32 %0, %%clock;" : "=r"(t0));
    do { __nanosleep(64); asm volatile("mov.u32 %0, %%clock;" : "=r"(t)); } while (t - t0 < cycles);
}
__device__ __forceinline__ void cluster_arrive() { asm volatile("barrier.cluster.arrive.relaxed.aligned;" ::: "memory"); }
__device__ __forceinline__ void cluster_wait() { asm volatile("barrier.cluster.wait.aligned;" ::: "memory"); }

__device__ __forceinline__ void wgmma_n128_z(float (&d)[64], uint64_t da, uint64_t db) {
    asm volatile("{\n.reg .pred p;\nsetp.ne.b32 p, 0, 0;\n"
        "wgmma.mma_async.sync.aligned.m64n128k16.f32.bf16.bf16 {"
        "%0, %1, %2, %3, %4, %5, %6, %7, %8, %9, %10, %11, %12, %13, %14, %15, "
        "%16, %17, %18, %19, %20, %21, %22, %23, %24, %25, %26, %27, %28, %29, %30, %31, "
        "%32, %33, %34, %35, %36, %37, %38, %39, %40, %41, %42, %43, %44, %45, %46, %47, "
        "%48, %49, %50, %51, %52, %53, %54, %55, %56, %57, %58, %59, %60, %61, %62, %63"
        "}, %64, %65, p, 1, 1, 0, 1;\n}\n"
        : "=f"(d[0]), "=f"(d[1]), "=f"(d[2]), "=f"(d[3]), "=f"(d[4]), "=f"(d[5]), "=f"(d[6]), "=f"(d[7]),
          "=f"(d[8]), "=f"(d[9]), "=f"(d[10]), "=f"(d[11]), "=f"(d[12]), "=f"(d[13]), "=f"(d[14]), "=f"(d[15]),
          "=f"(d[16]), "=f"(d[17]), "=f"(d[18]), "=f"(d[19]), "=f"(d[20]), "=f"(d[21]), "=f"(d[22]), "=f"(d[23]),
          "=f"(d[24]), "=f"(d[25]), "=f"(d[26]), "=f"(d[27]), "=f"(d[28]), "=f"(d[29]), "=f"(d[30]), "=f"(d[31]),
          "=f"(d[32]), "=f"(d[33]), "=f"(d[34]), "=f"(d[35]), "=f"(d[36]), "=f"(d[37]), "=f"(d[38]), "=f"(d[39]),
          "=f"(d[40]), "=f"(d[41]), "=f"(d[42]), "=f"(d[43]), "=f"(d[44]), "=f"(d[45]), "=f"(d[46]), "=f"(d[47]),
          "=f"(d[48]), "=f"(d[49]), "=f"(d[50]), "=f"(d[51]), "=f"(d[52]), "=f"(d[53]), "=f"(d[54]), "=f"(d[55]),
          "=f"(d[56]), "=f"(d[57]), "=f"(d[58]), "=f"(d[59]), "=f"(d[60]), "=f"(d[61]), "=f"(d[62]), "=f"(d[63])
        : "l"(da), "l"(db));
}
__device__ __forceinline__ void wgmma_n128(float (&d)[64], uint64_t da, uint64_t db) {
    asm volatile("{\n.reg .pred p;\nsetp.eq.b32 p, 0, 0;\n"
        "wgmma.mma_async.sync.aligned.m64n128k16.f32.bf16.bf16 {"
        "%0, %1, %2, %3, %4, %5, %6, %7, %8, %9, %10, %11, %12, %13, %14, %15, "
        "%16, %17, %18, %19, %20, %21, %22, %23, %24, %25, %26, %27, %28, %29, %30, %31, "
        "%32, %33, %34, %35, %36, %37, %38, %39, %40, %41, %42, %43, %44, %45, %46, %47, "
        "%48, %49, %50, %51, %52, %53, %54, %55, %56, %57, %58, %59, %60, %61, %62, %63"
        "}, %64, %65, p, 1, 1, 0, 1;\n}\n"
        : "+f"(d[0]), "+f"(d[1]), "+f"(d[2]), "+f"(d[3]), "+f"(d[4]), "+f"(d[5]), "+f"(d[6]), "+f"(d[7]),
          "+f"(d[8]), "+f"(d[9]), "+f"(d[10]), "+f"(d[11]), "+f"(d[12]), "+f"(d[13]), "+f"(d[14]), "+f"(d[15]),
          "+f"(d[16]), "+f"(d[17]), "+f"(d[18]), "+f"(d[19]), "+f"(d[20]), "+f"(d[21]), "+f"(d[22]), "+f"(d[23]),
          "+f"(d[24]), "+f"(d[25]), "+f"(d[26]), "+f"(d[27]), "+f"(d[28]), "+f"(d[29]), "+f"(d[30]), "+f"(d[31]),
          "+f"(d[32]), "+f"(d[33]), "+f"(d[34]), "+f"(d[35]), "+f"(d[36]), "+f"(d[37]), "+f"(d[38]), "+f"(d[39]),
          "+f"(d[40]), "+f"(d[41]), "+f"(d[42]), "+f"(d[43]), "+f"(d[44]), "+f"(d[45]), "+f"(d[46]), "+f"(d[47]),
          "+f"(d[48]), "+f"(d[49]), "+f"(d[50]), "+f"(d[51]), "+f"(d[52]), "+f"(d[53]), "+f"(d[54]), "+f"(d[55]),
          "+f"(d[56]), "+f"(d[57]), "+f"(d[58]), "+f"(d[59]), "+f"(d[60]), "+f"(d[61]), "+f"(d[62]), "+f"(d[63])
        : "l"(da), "l"(db));
}
__device__ __forceinline__ void wgmma_n176_z(float (&d)[88], uint64_t da, uint64_t db) {
    asm volatile("{\n.reg .pred p;\nsetp.ne.b32 p, 0, 0;\n"
        "wgmma.mma_async.sync.aligned.m64n176k16.f32.bf16.bf16 {"
        "%0, %1, %2, %3, %4, %5, %6, %7, %8, %9, %10, %11, %12, %13, %14, %15, "
        "%16, %17, %18, %19, %20, %21, %22, %23, %24, %25, %26, %27, %28, %29, %30, %31, "
        "%32, %33, %34, %35, %36, %37, %38, %39, %40, %41, %42, %43, %44, %45, %46, %47, "
        "%48, %49, %50, %51, %52, %53, %54, %55, %56, %57, %58, %59, %60, %61, %62, %63, "
        "%64, %65, %66, %67, %68, %69, %70, %71, %72, %73, %74, %75, %76, %77, %78, %79, "
        "%80, %81, %82, %83, %84, %85, %86, %87"
        "}, %88, %89, p, 1, 1, 0, 1;\n}\n"
        : "=f"(d[0]), "=f"(d[1]), "=f"(d[2]), "=f"(d[3]), "=f"(d[4]), "=f"(d[5]), "=f"(d[6]), "=f"(d[7]),
          "=f"(d[8]), "=f"(d[9]), "=f"(d[10]), "=f"(d[11]), "=f"(d[12]), "=f"(d[13]), "=f"(d[14]), "=f"(d[15]),
          "=f"(d[16]), "=f"(d[17]), "=f"(d[18]), "=f"(d[19]), "=f"(d[20]), "=f"(d[21]), "=f"(d[22]), "=f"(d[23]),
          "=f"(d[24]), "=f"(d[25]), "=f"(d[26]), "=f"(d[27]), "=f"(d[28]), "=f"(d[29]), "=f"(d[30]), "=f"(d[31]),
          "=f"(d[32]), "=f"(d[33]), "=f"(d[34]), "=f"(d[35]), "=f"(d[36]), "=f"(d[37]), "=f"(d[38]), "=f"(d[39]),
          "=f"(d[40]), "=f"(d[41]), "=f"(d[42]), "=f"(d[43]), "=f"(d[44]), "=f"(d[45]), "=f"(d[46]), "=f"(d[47]),
          "=f"(d[48]), "=f"(d[49]), "=f"(d[50]), "=f"(d[51]), "=f"(d[52]), "=f"(d[53]), "=f"(d[54]), "=f"(d[55]),
          "=f"(d[56]), "=f"(d[57]), "=f"(d[58]), "=f"(d[59]), "=f"(d[60]), "=f"(d[61]), "=f"(d[62]), "=f"(d[63]),
          "=f"(d[64]), "=f"(d[65]), "=f"(d[66]), "=f"(d[67]), "=f"(d[68]), "=f"(d[69]), "=f"(d[70]), "=f"(d[71]),
          "=f"(d[72]), "=f"(d[73]), "=f"(d[74]), "=f"(d[75]), "=f"(d[76]), "=f"(d[77]), "=f"(d[78]), "=f"(d[79]),
          "=f"(d[80]), "=f"(d[81]), "=f"(d[82]), "=f"(d[83]), "=f"(d[84]), "=f"(d[85]), "=f"(d[86]), "=f"(d[87])
        : "l"(da), "l"(db));
}
__device__ __forceinline__ void wgmma_n176(float (&d)[88], uint64_t da, uint64_t db) {
    asm volatile("{\n.reg .pred p;\nsetp.eq.b32 p, 0, 0;\n"
        "wgmma.mma_async.sync.aligned.m64n176k16.f32.bf16.bf16 {"
        "%0, %1, %2, %3, %4, %5, %6, %7, %8, %9, %10, %11, %12, %13, %14, %15, "
        "%16, %17, %18, %19, %20, %21, %22, %23, %24, %25, %26, %27, %28, %29, %30, %31, "
        "%32, %33, %34, %35, %36, %37, %38, %39, %40, %41, %42, %43, %44, %45, %46, %47, "
        "%48, %49, %50, %51, %52, %53, %54, %55, %56, %57, %58, %59, %60, %61, %62, %63, "
        "%64, %65, %66, %67, %68, %69, %70, %71, %72, %73, %74, %75, %76, %77, %78, %79, "
        "%80, %81, %82, %83, %84, %85, %86, %87"
        "}, %88, %89, p, 1, 1, 0, 1;\n}\n"
        : "+f"(d[0]), "+f"(d[1]), "+f"(d[2]), "+f"(d[3]), "+f"(d[4]), "+f"(d[5]), "+f"(d[6]), "+f"(d[7]),
          "+f"(d[8]), "+f"(d[9]), "+f"(d[10]), "+f"(d[11]), "+f"(d[12]), "+f"(d[13]), "+f"(d[14]), "+f"(d[15]),
          "+f"(d[16]), "+f"(d[17]), "+f"(d[18]), "+f"(d[19]), "+f"(d[20]), "+f"(d[21]), "+f"(d[22]), "+f"(d[23]),
          "+f"(d[24]), "+f"(d[25]), "+f"(d[26]), "+f"(d[27]), "+f"(d[28]), "+f"(d[29]), "+f"(d[30]), "+f"(d[31]),
          "+f"(d[32]), "+f"(d[33]), "+f"(d[34]), "+f"(d[35]), "+f"(d[36]), "+f"(d[37]), "+f"(d[38]), "+f"(d[39]),
          "+f"(d[40]), "+f"(d[41]), "+f"(d[42]), "+f"(d[43]), "+f"(d[44]), "+f"(d[45]), "+f"(d[46]), "+f"(d[47]),
          "+f"(d[48]), "+f"(d[49]), "+f"(d[50]), "+f"(d[51]), "+f"(d[52]), "+f"(d[53]), "+f"(d[54]), "+f"(d[55]),
          "+f"(d[56]), "+f"(d[57]), "+f"(d[58]), "+f"(d[59]), "+f"(d[60]), "+f"(d[61]), "+f"(d[62]), "+f"(d[63]),
          "+f"(d[64]), "+f"(d[65]), "+f"(d[66]), "+f"(d[67]), "+f"(d[68]), "+f"(d[69]), "+f"(d[70]), "+f"(d[71]),
          "+f"(d[72]), "+f"(d[73]), "+f"(d[74]), "+f"(d[75]), "+f"(d[76]), "+f"(d[77]), "+f"(d[78]), "+f"(d[79]),
          "+f"(d[80]), "+f"(d[81]), "+f"(d[82]), "+f"(d[83]), "+f"(d[84]), "+f"(d[85]), "+f"(d[86]), "+f"(d[87])
        : "l"(da), "l"(db));
}
__device__ __forceinline__ void wgmma_n256_z(float (&d)[128], uint64_t da, uint64_t db) {
    asm volatile("{\n.reg .pred p;\nsetp.ne.b32 p, 0, 0;\n"
        "wgmma.mma_async.sync.aligned.m64n256k16.f32.bf16.bf16 {"
        "%0, %1, %2, %3, %4, %5, %6, %7, %8, %9, %10, %11, %12, %13, %14, %15, "
        "%16, %17, %18, %19, %20, %21, %22, %23, %24, %25, %26, %27, %28, %29, %30, %31, "
        "%32, %33, %34, %35, %36, %37, %38, %39, %40, %41, %42, %43, %44, %45, %46, %47, "
        "%48, %49, %50, %51, %52, %53, %54, %55, %56, %57, %58, %59, %60, %61, %62, %63, "
        "%64, %65, %66, %67, %68, %69, %70, %71, %72, %73, %74, %75, %76, %77, %78, %79, "
        "%80, %81, %82, %83, %84, %85, %86, %87, %88, %89, %90, %91, %92, %93, %94, %95, "
        "%96, %97, %98, %99, %100, %101, %102, %103, %104, %105, %106, %107, %108, %109, %110, %111, "
        "%112, %113, %114, %115, %116, %117, %118, %119, %120, %121, %122, %123, %124, %125, %126, %127"
        "}, %128, %129, p, 1, 1, 0, 1;\n}\n"
        : "=f"(d[0]), "=f"(d[1]), "=f"(d[2]), "=f"(d[3]), "=f"(d[4]), "=f"(d[5]), "=f"(d[6]), "=f"(d[7]),
          "=f"(d[8]), "=f"(d[9]), "=f"(d[10]), "=f"(d[11]), "=f"(d[12]), "=f"(d[13]), "=f"(d[14]), "=f"(d[15]),
          "=f"(d[16]), "=f"(d[17]), "=f"(d[18]), "=f"(d[19]), "=f"(d[20]), "=f"(d[21]), "=f"(d[22]), "=f"(d[23]),
          "=f"(d[24]), "=f"(d[25]), "=f"(d[26]), "=f"(d[27]), "=f"(d[28]), "=f"(d[29]), "=f"(d[30]), "=f"(d[31]),
          "=f"(d[32]), "=f"(d[33]), "=f"(d[34]), "=f"(d[35]), "=f"(d[36]), "=f"(d[37]), "=f"(d[38]), "=f"(d[39]),
          "=f"(d[40]), "=f"(d[41]), "=f"(d[42]), "=f"(d[43]), "=f"(d[44]), "=f"(d[45]), "=f"(d[46]), "=f"(d[47]),
          "=f"(d[48]), "=f"(d[49]), "=f"(d[50]), "=f"(d[51]), "=f"(d[52]), "=f"(d[53]), "=f"(d[54]), "=f"(d[55]),
          "=f"(d[56]), "=f"(d[57]), "=f"(d[58]), "=f"(d[59]), "=f"(d[60]), "=f"(d[61]), "=f"(d[62]), "=f"(d[63]),
          "=f"(d[64]), "=f"(d[65]), "=f"(d[66]), "=f"(d[67]), "=f"(d[68]), "=f"(d[69]), "=f"(d[70]), "=f"(d[71]),
          "=f"(d[72]), "=f"(d[73]), "=f"(d[74]), "=f"(d[75]), "=f"(d[76]), "=f"(d[77]), "=f"(d[78]), "=f"(d[79]),
          "=f"(d[80]), "=f"(d[81]), "=f"(d[82]), "=f"(d[83]), "=f"(d[84]), "=f"(d[85]), "=f"(d[86]), "=f"(d[87]),
          "=f"(d[88]), "=f"(d[89]), "=f"(d[90]), "=f"(d[91]), "=f"(d[92]), "=f"(d[93]), "=f"(d[94]), "=f"(d[95]),
          "=f"(d[96]), "=f"(d[97]), "=f"(d[98]), "=f"(d[99]), "=f"(d[100]), "=f"(d[101]), "=f"(d[102]), "=f"(d[103]),
          "=f"(d[104]), "=f"(d[105]), "=f"(d[106]), "=f"(d[107]), "=f"(d[108]), "=f"(d[109]), "=f"(d[110]), "=f"(d[111]),
          "=f"(d[112]), "=f"(d[113]), "=f"(d[114]), "=f"(d[115]), "=f"(d[116]), "=f"(d[117]), "=f"(d[118]), "=f"(d[119]),
          "=f"(d[120]), "=f"(d[121]), "=f"(d[122]), "=f"(d[123]), "=f"(d[124]), "=f"(d[125]), "=f"(d[126]), "=f"(d[127])
        : "l"(da), "l"(db));
}
__device__ __forceinline__ void wgmma_n256(float (&d)[128], uint64_t da, uint64_t db) {
    asm volatile("{\n.reg .pred p;\nsetp.eq.b32 p, 0, 0;\n"
        "wgmma.mma_async.sync.aligned.m64n256k16.f32.bf16.bf16 {"
        "%0, %1, %2, %3, %4, %5, %6, %7, %8, %9, %10, %11, %12, %13, %14, %15, "
        "%16, %17, %18, %19, %20, %21, %22, %23, %24, %25, %26, %27, %28, %29, %30, %31, "
        "%32, %33, %34, %35, %36, %37, %38, %39, %40, %41, %42, %43, %44, %45, %46, %47, "
        "%48, %49, %50, %51, %52, %53, %54, %55, %56, %57, %58, %59, %60, %61, %62, %63, "
        "%64, %65, %66, %67, %68, %69, %70, %71, %72, %73, %74, %75, %76, %77, %78, %79, "
        "%80, %81, %82, %83, %84, %85, %86, %87, %88, %89, %90, %91, %92, %93, %94, %95, "
        "%96, %97, %98, %99, %100, %101, %102, %103, %104, %105, %106, %107, %108, %109, %110, %111, "
        "%112, %113, %114, %115, %116, %117, %118, %119, %120, %121, %122, %123, %124, %125, %126, %127"
        "}, %128, %129, p, 1, 1, 0, 1;\n}\n"
        : "+f"(d[0]), "+f"(d[1]), "+f"(d[2]), "+f"(d[3]), "+f"(d[4]), "+f"(d[5]), "+f"(d[6]), "+f"(d[7]),
          "+f"(d[8]), "+f"(d[9]), "+f"(d[10]), "+f"(d[11]), "+f"(d[12]), "+f"(d[13]), "+f"(d[14]), "+f"(d[15]),
          "+f"(d[16]), "+f"(d[17]), "+f"(d[18]), "+f"(d[19]), "+f"(d[20]), "+f"(d[21]), "+f"(d[22]), "+f"(d[23]),
          "+f"(d[24]), "+f"(d[25]), "+f"(d[26]), "+f"(d[27]), "+f"(d[28]), "+f"(d[29]), "+f"(d[30]), "+f"(d[31]),
          "+f"(d[32]), "+f"(d[33]), "+f"(d[34]), "+f"(d[35]), "+f"(d[36]), "+f"(d[37]), "+f"(d[38]), "+f"(d[39]),
          "+f"(d[40]), "+f"(d[41]), "+f"(d[42]), "+f"(d[43]), "+f"(d[44]), "+f"(d[45]), "+f"(d[46]), "+f"(d[47]),
          "+f"(d[48]), "+f"(d[49]), "+f"(d[50]), "+f"(d[51]), "+f"(d[52]), "+f"(d[53]), "+f"(d[54]), "+f"(d[55]),
          "+f"(d[56]), "+f"(d[57]), "+f"(d[58]), "+f"(d[59]), "+f"(d[60]), "+f"(d[61]), "+f"(d[62]), "+f"(d[63]),
          "+f"(d[64]), "+f"(d[65]), "+f"(d[66]), "+f"(d[67]), "+f"(d[68]), "+f"(d[69]), "+f"(d[70]), "+f"(d[71]),
          "+f"(d[72]), "+f"(d[73]), "+f"(d[74]), "+f"(d[75]), "+f"(d[76]), "+f"(d[77]), "+f"(d[78]), "+f"(d[79]),
          "+f"(d[80]), "+f"(d[81]), "+f"(d[82]), "+f"(d[83]), "+f"(d[84]), "+f"(d[85]), "+f"(d[86]), "+f"(d[87]),
          "+f"(d[88]), "+f"(d[89]), "+f"(d[90]), "+f"(d[91]), "+f"(d[92]), "+f"(d[93]), "+f"(d[94]), "+f"(d[95]),
          "+f"(d[96]), "+f"(d[97]), "+f"(d[98]), "+f"(d[99]), "+f"(d[100]), "+f"(d[101]), "+f"(d[102]), "+f"(d[103]),
          "+f"(d[104]), "+f"(d[105]), "+f"(d[106]), "+f"(d[107]), "+f"(d[108]), "+f"(d[109]), "+f"(d[110]), "+f"(d[111]),
          "+f"(d[112]), "+f"(d[113]), "+f"(d[114]), "+f"(d[115]), "+f"(d[116]), "+f"(d[117]), "+f"(d[118]), "+f"(d[119]),
          "+f"(d[120]), "+f"(d[121]), "+f"(d[122]), "+f"(d[123]), "+f"(d[124]), "+f"(d[125]), "+f"(d[126]), "+f"(d[127])
        : "l"(da), "l"(db));
}

struct Idx {
    uint32_t lane, warp, w4, q4, g8, prow, pan;
    __device__ __forceinline__ Idx() {
        uint32_t t; asm volatile("mov.u32 %0, %%tid.x;" : "=r"(t));
        lane = t & 31; warp = t >> 5; w4 = warp & 3; q4 = lane & 3; g8 = lane >> 2;
        prow = w4 * 16 + ((lane >> 3) & 1) * 8 + (lane & 7);
        pan = prow * 128 + (((lane >> 4) ^ (lane & 7)) << 4);
    }
};
#define IDX() const Idx ix; const uint32_t lane = ix.lane, warp = ix.warp, w4 = ix.w4, q4 = ix.q4, g8 = ix.g8, prow = ix.prow, pan_addr = ix.pan; \
    (void)lane; (void)warp; (void)w4; (void)q4; (void)g8; (void)prow; (void)pan_addr;

__device__ __forceinline__ int kof(int t, int sh, int j) {
    const int p = t >> (sh - 1), pn = p < 2 ? p : p >= 9, q = p - 2 - 7 * pn;
    return ((p < 2 ? j : q + (q >= j)) << 7) + (pn << 6) + ((t & (sh - 1)) << 5);
}
__device__ __forceinline__ uint32_t fidx(uint32_t m, uint32_t w, uint32_t pn) {
    return m * 32 + w * 16 + pn;
}
constexpr int HC0 = 8 * 48, HC3 = HC0 + 3072;
__device__ __forceinline__ int hcol(int p, int j) { return HC0 + p * 1024 + j * 128; }
struct Ring {
    uint32_t slot, par;
    __device__ __forceinline__ void next() { if (++slot == NSLOT) { slot = 0; par ^= 1; } }
    __device__ __forceinline__ void skip(uint32_t n) { slot += n; if (slot >= NSLOT) { slot -= NSLOT; par ^= 1; } }
};
__device__ __forceinline__ uint32_t BAR_FULL(uint32_t sb, uint32_t s) { return sb + OFF_BAR + 8 * s; }
constexpr uint32_t AF_REL = 48;
__device__ __forceinline__ uint32_t BAR_EMPTY(uint32_t sb, uint32_t s) { return sb + OFF_BAR + 96 + 8 * s; }
__device__ __forceinline__ uint32_t BAR_SFULL(uint32_t sb, uint32_t i) { return sb + OFF_BAR + 152 + 8 * i; }
__device__ __forceinline__ uint32_t BAR_SREADY(uint32_t sb, uint32_t i) { return sb + OFF_BAR + 184 + 8 * i; }
__device__ __forceinline__ uint32_t BAR_ONE(uint32_t sb, uint32_t i) { return sb + OFF_BAR + 216 + 8 * i; }
enum { EV_WIN, EV_WIN1, EV_WIN2, EV_WIN3, EV_P0, EV_GA, EV_GB, EV_LN2, EV_LAG1, EV_LAG2, EV_LAG3, EV_LAG4, EV_LAG5, EV_KV, EV_PAR, EV_AGO, EV_AGO1, EV_AGO2, EV_FGO, EV_FGO1, EV_FGO2, EV_H0, EV_H1, EV_H2, EV_H3, EV_TAIL, EV_COUNT = EV_TAIL + 8 };
constexpr int NB_TAIL = 4;

struct Rel {
    uint32_t base; bool sig;
    __device__ __forceinline__ Rel(uint32_t sb, uint32_t tw) {
        uint32_t a; asm("mapa.shared::cluster.u32 %0, %1, %2;" : "=r"(a) : "r"(BAR_EMPTY(sb, 0)), "r"((tw >> 5) & 1));
        base = __shfl_sync(0xffffffffu, a, 0); sig = (tw & ~32u) == 0;
    }
    __device__ __forceinline__ void operator()(uint32_t slot) const {
        if (sig) asm volatile("mbarrier.arrive.shared::cluster.b64 _, [%0];" :: "r"(base + 8 * slot) : "memory");
    }
};
struct LnRow { float rs0, nm0, rs1, nm1; };
struct Pipe {
    Rel rel; uint32_t p1, p2;
    __device__ __forceinline__ Pipe(uint32_t sb, uint32_t tw, uint32_t first) : rel(sb, tw), p1(first), p2(NSLOT) {}
    template <bool TWO> __device__ __forceinline__ void acquire(uint32_t sb, uint32_t af, const Ring& r) {
        const uint32_t b0 = BAR_FULL(sb, r.slot), b1 = b0 + af;
        const bool ready = TWO ? mbar_test2(b0, b1, r.par) : mbar_test(b0, r.par);
        wg_wait<1>();
        rel(p2);
        if (!ready) { if (TWO) mbar_wait2(b0, b1, r.par); else mbar_wait(b0, r.par); }
    }
    __device__ __forceinline__ void issued(uint32_t slot) { p2 = p1; p1 = slot; }
    __device__ __forceinline__ void drain1() { wg_wait<1>(); rel(p2); p2 = NSLOT; }
    __device__ __forceinline__ void drain0() { wg_wait<0>(); rel(p1); p1 = NSLOT; }
    template <bool TWO, class Step> __device__ __forceinline__ void hold(int LG, uint32_t sb, uint32_t af, Ring& r, uint32_t lag_bar, Step step) {
        Ring q = r;
#pragma unroll 1
        for (int i = 0; i < LG; ++i) { if (TWO) mbar_wait2(BAR_FULL(sb, q.slot), BAR_FULL(sb, q.slot) + af, q.par); else mbar_wait(BAR_FULL(sb, q.slot), q.par); q.next(); }
        mbar_wait(lag_bar, 0);
#pragma unroll 1
        do {
            step(r.slot);
            wg_wait<2>(); rel(p2); p2 = p1; p1 = r.slot;
            if (++r.slot == NSLOT) r.slot = 0;
        } while (r.slot != q.slot);
        r.par = q.par;
    }
};
template <bool TWO, bool FIRST, int NA, int NB>
__device__ __forceinline__ void step32(float (&aa)[NA], float (&ab)[NB], uint32_t sb, uint32_t wg, uint32_t slot, int own) {
    const uint32_t st = d16(sb) + slot * (SLOT >> 4);
    const uint32_t alo = own >= 0 ? d16(sb) + OFF_STG / 16 + wg * 1024 + (own >> 1) * 512 + (own & 1) * 4 : st + wg * 256;
    const uint32_t ahi = own >= 0 ? (1024 >> 4) | (1u << 30) : (512 >> 4) | (2u << 30);
    wg_fence();
#pragma unroll
    for (int k = 0; k < 2; ++k) {
        const uint64_t da = ((uint64_t)ahi << 32) | (alo + k * 2 + 0x10000);
        if constexpr (NA == 88) {
            const uint64_t d0 = mk_desc(st, 8192 + k * 2048, 8192, 1024, 1), d1 = mk_desc(st, 12288 + k * 2048, 8192, 1024, 1);
            if (FIRST && k == 0) { wgmma_n176_z(aa, da, d0); wgmma_n176_z(ab, da, d1); }
            else { wgmma_n176(aa, da, d0); wgmma_n176(ab, da, d1); }
        } else {
            const uint64_t d0 = mk_desc(st, 8192 + k * 2048, 4096, 1024, 1), d1 = mk_desc(st, 24576 + k * 2048, 4096, 1024, 1);
            if (FIRST && k == 0) { wgmma_n256_z(aa, da, d0); if constexpr (TWO) wgmma_n128_z(ab, da, d1); }
            else { wgmma_n256(aa, da, d0); if constexpr (TWO) wgmma_n128(ab, da, d1); }
        }
    }
    wg_commit();
}
template <bool TWO, int LG, int NA, int NB, class Mid, class Tail>
__device__ __forceinline__ void mainloop32(float (&aa)[NA], float (&ab)[NB], uint32_t sb, uint32_t wg, uint32_t tw, Ring& r, uint32_t lag_ev, int g0, Mid mid, Tail tail) {
    step32<TWO, true>(aa, ab, sb, wg, r.slot, TWO ? 0 : -1);
    TS(g0, 0);
    Pipe pp(sb, tw, r.slot);
    r.next();
    const int end = wg ? 32 : 32 - LG;
#pragma unroll 1
    for (int it = 1; it < end; ++it) {
        pp.acquire<TWO>(sb, wg ? 0 : AF_REL, r);
        step32<TWO, false>(aa, ab, sb, wg, r.slot, TWO && it < 4 ? it : -1);
        pp.issued(r.slot);
        TS(g0 + it, 0);
        r.next();
        mid(it);
    }
    if (wg == 0) { pp.drain1(); pp.drain0(); pp.hold<TWO>(LG, sb, AF_REL, r, BAR_ONE(sb, lag_ev), [&](uint32_t slot) { step32<TWO, false>(aa, ab, sb, 0, slot, -1); }); }
    if (wg == 1 && tw == 0) mbar_arrive(BAR_ONE(sb, lag_ev));
    pp.drain1();
    tail();
    pp.drain0();
    TS(g0 + 31, 1);
}
template <bool FIRST>
__device__ __forceinline__ void step64(float (&acc)[64], uint32_t sb, uint32_t wg, uint32_t slot, int own) {
    const uint32_t sbb = d16(sb) + slot * (SLOT >> 4), sa = own >= 0 ? d16(sb) + OFF_STG / 16 + wg * 1024 + own * 512 : sbb + wg * 512;
    wg_fence();
#pragma unroll
    for (int k = 0; k < 4; ++k) {
        const uint64_t da = mk_desc(sa, k * 32, 16, 1024, 1), db = mk_desc(sbb, 16384 + k * 2048, 8192, 1024, 1);
        if (FIRST && k == 0) wgmma_n128_z(acc, da, db); else wgmma_n128(acc, da, db);
    }
    wg_commit();
}
template <class Put, class Mid, class Tail>
__device__ __forceinline__ void mainloop64(float (&acc)[64], bool wo, uint32_t sb, uint32_t wg, uint32_t tw, Ring& r, Put put, Mid mid, Tail tail) {
    const int g0 = wo ? 32 : 144, nst = wo ? 16 : 56, lg = wo ? LAGW : LAGD; (void)g0;
    const uint32_t lag_bar = BAR_ONE(sb, wo ? EV_LAG4 : EV_LAG5), af = wo && !wg ? AF_REL : 0;
    if (!wo) CS(28);
    step64<true>(acc, sb, wg, r.slot, wo ? 0 : -1);
    if (!wo) CS(29);
    TS(g0, 0);
    Pipe pp(sb, tw, r.slot);
    r.next();
    int it = 1;
    auto run = [&](int end, int own, bool with_put) {
#pragma unroll 1
        do {
            pp.acquire<true>(sb, af, r);
            step64<false>(acc, sb, wg, r.slot, own);
            pp.issued(r.slot);
            TS(g0 + it, 0);
            if (wo && it == 2) CS(9);
            r.next();
            if (with_put && it == (wg ? PUTD1 : PUTD0)) put();
        } while (++it < end);
    };
    const int end = wg ? nst : nst - lg;
    run(wo ? 2 : wg ? MIDD : end, wo ? 1 : -1, true);
    mid();
    if (wo) { pp.drain1(); pp.drain0(); TS(g0 + 1, 1); }
    if (it < end) run(end, -1, false);
    if (wg == 0) { pp.drain1(); pp.drain0(); pp.hold<true>(lg, sb, af, r, lag_bar, [&](uint32_t slot) { step64<false>(acc, sb, 0, slot, -1); }); }
    if (wg == 1 && tw == 0) mbar_arrive(lag_bar);
    pp.drain1();
    tail();
    pp.drain0();
    TS(g0 + nst - 1, 1);
}

struct RowAcc {
    float sm[4] = {0.f, 0.f, 0.f, 0.f}, sq[4] = {0.f, 0.f, 0.f, 0.f};
    __device__ __forceinline__ void add(int e, float x) { sm[e & 3] += x; sq[e & 3] = fmaf(x, x, sq[e & 3]); }
    __device__ __forceinline__ void publish(uint4* dst, uint32_t q4, uint32_t ep) const {
        const float s0 = sm[0] + sm[1], s1 = sm[2] + sm[3], q0 = sq[0] + sq[1], q1 = sq[2] + sq[3];
        const bool od = q4 & 1;
        float sv = (od ? s1 : s0) + __shfl_xor_sync(0xffffffffu, od ? s0 : s1, 1), qv = (od ? q1 : q0) + __shfl_xor_sync(0xffffffffu, od ? q0 : q1, 1);
        sv += __shfl_xor_sync(0xffffffffu, sv, 2); qv += __shfl_xor_sync(0xffffffffu, qv, 2);
        st_pkt16(dst + (q4 & 1) * 8, 0, __float_as_uint(sv), __float_as_uint(qv), ep);
    }
};
__device__ __forceinline__ LnRow merge_stats(const uint4* src, uint32_t q4, uint32_t ep, uint32_t sb) {
    uint4 t[4];
    uint32_t n = 0;
    while (true) {
#pragma unroll
        for (int i = 0; i < 4; ++i) t[i] = ld_pkt16(src + (q4 * 2 + (i >> 1)) * 512 + (i & 1) * 8);
        const bool ok_ = __all_sync(0xffffffffu, t[0].w == ep && t[1].w == ep && t[2].w == ep && t[3].w == ep);
        if (n < 4) CS(14 + n);
        if (ok_) break;
        SPIN_GUARD(n);
    }
    float v[4];
#pragma unroll
    for (int h = 0; h < 2; ++h) { v[h] = __uint_as_float(t[h].y) + __uint_as_float(t[2 + h].y); v[2 + h] = __uint_as_float(t[h].z) + __uint_as_float(t[2 + h].z); }
#pragma unroll
    for (int o = 1; o < 4; o <<= 1)
#pragma unroll
        for (int i = 0; i < 4; ++i) v[i] += __shfl_xor_sync(0xffffffffu, v[i], o);
    const float m0 = v[0] * (1.f / D_), m1 = v[1] * (1.f / D_);
    const float r0 = rsq(fmaxf(fmaf(-m0, m0, v[2] * (1.f / D_)), 0.f) + 1e-5f), r1 = rsq(fmaxf(fmaf(-m1, m1, v[3] * (1.f / D_)), 0.f) + 1e-5f);
    return LnRow{r0, -m0 * r0, r1, -m1 * r1};
}
struct Stg {
    uint32_t b, par;
    __device__ __forceinline__ uint32_t acquire2(uint32_t sb, uint32_t wg) {
        mbar_wait2(BAR_SREADY(sb, wg * 2), BAR_SREADY(sb, wg * 2 + 1), par);
        par ^= 1;
        return sb + OFF_STG + wg * 16384;
    }
    __device__ __forceinline__ void publish(uint32_t sb, uint32_t wg, uint32_t lane) {
        fence_async_smem();
        __syncwarp();
        if (lane == 0) mbar_arrive(BAR_SFULL(sb, wg * 2 + b));
        b ^= 1;
    }
};

struct LnPar {
    uint4 p[8];
    __device__ __forceinline__ void load(uint32_t sb, uint32_t q4) {
#pragma unroll
        for (int i = 0; i < 8; ++i) p[i] = lds128(sb + OFF_PAR + i * 64 + q4 * 16);
    }
};
__device__ __forceinline__ void ln_norm(uint32_t (&xn)[32], const float (&x)[64], const LnRow& n) {
#pragma unroll
    for (int e = 0; e < 32; ++e) {
        const float rs = (e & 1) ? n.rs1 : n.rs0, nm = (e & 1) ? n.nm1 : n.nm0;
        xn[e] = pack2(fmaf(x[2 * e], rs, nm), fmaf(x[2 * e + 1], rs, nm));
    }
}
__device__ __forceinline__ void ln_emit(const uint32_t (&xr)[32], const LnPar& lp, uint32_t sb, uint32_t wg, const Idx& ix) {
#pragma unroll
    for (int i = 0; i < 8; ++i)
        stsm4(sb + OFF_STG + wg * 16384 + (i >> 2) * 8192 + (ix.pan ^ ((i & 3) << 5)), hfma2_bf16(xr[4 * i], lp.p[i].z, lp.p[i].x), hfma2_bf16(xr[4 * i + 1], lp.p[i].z, lp.p[i].x),
              hfma2_bf16(xr[4 * i + 2], lp.p[i].w, lp.p[i].y), hfma2_bf16(xr[4 * i + 3], lp.p[i].w, lp.p[i].y));
    fence_async_smem();
    __syncwarp();
    if (ix.lane < 2) mbar_arrive(BAR_SFULL(sb, wg * 2 + ix.lane));
    bar_sync(1 + wg, 128);
}
__device__ __forceinline__ void load_slab(uint32_t (&xr)[32], uint32_t buf) {
    IDX();
#pragma unroll
    for (int i = 0; i < 8; ++i) ldsm4(buf + (i >> 2) * 8192 + (pan_addr ^ ((i & 3) << 5)), xr[4 * i], xr[4 * i + 1], xr[4 * i + 2], xr[4 * i + 3]);
}
__device__ __forceinline__ void unpack_slab(float (&x)[64], const uint32_t (&xr)[32]) {
#pragma unroll
    for (int i = 0; i < 32; ++i) unpack2(xr[i], x[2 * i], x[2 * i + 1]);
}
__device__ __forceinline__ void store_slab(const float (&x)[64], uint32_t buf, uint32_t pitch, uint32_t pan, int i0, int i1) {
#pragma unroll
    for (int i = i0; i < i1; ++i)
        stsm4(buf + (i >> 2) * pitch + (pan ^ ((i & 3) << 5)), pack2(x[8 * i], x[8 * i + 1]), pack2(x[8 * i + 2], x[8 * i + 3]), pack2(x[8 * i + 4], x[8 * i + 5]), pack2(x[8 * i + 6], x[8 * i + 7]));
}
template <int NP, class Done>
__device__ __forceinline__ void fetch_halo(uint4* src, bool first, uint32_t dst, Done done) {
    uint4 hv[4 * NP];
    uint32_t n = 0;
    while (true) {
        bool ok = true;
#pragma unroll
        for (int i = 0; i < 4 * NP; ++i) { hv[i] = first ? make_uint4(0, 0, 0, 0) : ld_pkt16(src + (i >> 2) * 256 + (i & 3) * 32); ok = ok && hv[i].x != 0; }
        if (first || __all_sync(0xffffffffu, ok)) break;
        SPIN_GUARD(n);
    }
#pragma unroll
    for (int i = 0; i < 4 * NP; ++i) stsm4(dst + (i >> 2) * 4096 + (i & 3) * 512, hv[i].x, hv[i].y, hv[i].z, hv[i].w);
    done();
    if (!first) {
#pragma unroll
        for (int i = 0; i < 4 * NP; ++i) src[(i >> 2) * 256 + (i & 3) * 32] = make_uint4(0, 0, 0, 0);
    }
}

template <int N, class G, class U>
__device__ __forceinline__ void glu(uint32_t (&h)[N], G g, U u) {
#pragma unroll
    for (int i = 0; i < N; ++i) h[i] = pack2(fmaf(tanh_(g(2 * i)), u(2 * i), u(2 * i)), fmaf(tanh_(g(2 * i + 1)), u(2 * i + 1), u(2 * i + 1)));
}
__device__ __forceinline__ void put_h(const uint32_t (&h)[32], uint32_t sb, uint32_t wg, Stg& stg) {
    IDX();
    const uint32_t buf = stg.acquire2(sb, wg);
#pragma unroll
    for (int k = 0; k < 8; ++k) stsm4(buf + (k >> 2) * 8192 + (pan_addr ^ ((k & 3) << 5)), h[4 * k], h[4 * k + 1], h[4 * k + 2], h[4 * k + 3]);
    fence_async_smem();
    __syncwarp();
    if (lane < 2) mbar_arrive(BAR_SFULL(sb, wg * 2 + lane));
}

template <int NP, bool PREV>
__device__ __forceinline__ void passes128(uint32_t (&hp)[32], uint32_t sb, uint32_t wg, uint32_t tw, Ring& r, Stg& stg) {
#pragma unroll 1
    for (int p = 0; p < NP; ++p) {
        float b256[128], none[1];
        const int put_at = !PREV && p == 0 ? -1 : wg ? PUT1 : PUT0;
        mainloop32<false, LAGS>(b256, none, sb, wg, tw, r, EV_LAG2 + p, 80 + 32 * (p & 1), [&](int it) { if (it == put_at) put_h(hp, sb, wg, stg); },
                                [&] { if (PREV || p < NP - 1) mbar_wait(BAR_FULL(sb, r.slot), r.par); });
        if (threadIdx.x == 0) { TL(29 + 2 * p); TC(114 + 2 * p); }
        if (threadIdx.x == 128) TL(53 + 2 * (p & 1));
        CS(24 + 2 * (p & 1));
        glu(hp, [&](int i) { return b256[i + (i & 32)]; }, [&](int i) { return b256[i + (i & 32) + 32]; });
        if (threadIdx.x == 0) { TL(30 + 2 * p); TC(115 + 2 * p); }
        if (threadIdx.x == 128) TL(54 + 2 * (p & 1));
        CS(25 + 2 * (p & 1));
    }
}

__global__ void __launch_bounds__(384, 1)
fused_block_kernel(const __grid_constant__ Ptrs pt, const __grid_constant__ Maps mp) {
    uint32_t* const g_flags = pt.mail->flags;
    uint2* const g_mod = pt.mail->mod;
    uint4* const g_st1 = pt.mail->st1;
    uint32_t* const g_par2 = pt.mail->par2;
    uint4* const g_halo = pt.mail->halo;
    const __nv_bfloat16* __restrict__ cvec = pt.c;
    if (threadIdx.x == 224) { prefetch_map(&mp.wm8); prefetch_map(&mp.x); }
    extern __shared__ __align__(1024) uint8_t smem[];
    const uint32_t sb = smem_u32(smem);
    const uint32_t tid = threadIdx.x, tw = tid & 127, lane = tid & 31;
    const uint32_t warp = __shfl_sync(0xffffffffu, tid >> 5, 0), wg = warp >> 2;
    uint32_t rank; asm("mov.u32 %0, %%cluster_ctarank;" : "=r"(rank));
    rank = __shfl_sync(0xffffffffu, rank, 0);
    uint32_t ep;
    uint32_t smid; asm volatile("mov.u32 %0, %%smid;" : "=r"(smid));
    const int c = __shfl_sync(0xffffffffu, smid >> 1, 0);
    const int c7 = ((c - 32) * 37) >> 8;
    int grp = c < 32 ? c & 7 : c < 60 ? c - 31 - 7 * c7 : c < 62 ? -1 : 0;
    const int j = c < 32 ? c >> 3 : c < 60 ? 4 + c7 : c < 62 ? (c - 60) * 2 + rank : c - 58;
    const bool aux = grp < 0;
    const int m = grp * 2 + rank;
    uint4* const g_st2 = g_halo + (m > 0 ? (m - 1) * 8 * 512 : 128);

    bool cluster_arrive_early = false;
    if (wg < 2) {
      if (!KDEBUG) cluster_arrive();
      ep = flag_get(g_flags + FL_DONE);
      uint16_t cw[8];
      {
          const __nv_bfloat16* cp = cvec + ((tw >> 5) * 32 + (tw & 3) * 2) * 8 + (lane >> 2);
#pragma unroll
          for (int i = 0; i < 8; ++i) asm volatile("ld.global.nc.u16 %0, [%1];" : "=h"(cw[i]) : "l"(cp + (i >> 1) * 64 + (i & 1) * 8));
      }
      asm volatile("setmaxnreg.inc.sync.aligned.u32 224;");
      if (tid == 0) TL(58);
      if (KDEBUG) cluster_arrive();
      Ring r{0, 0};
      Stg stg{0, 0};
      if (aux) {
        if (wg == 0) {
            const uint4 cv = *(const uint4*)(cvec + tw * 8);
            sts128(sb + OFF_STG + (tw >> 3) * 1024 + (tw & 7) * 16, pack2(silu_(bf_lo(cv.x)), silu_(bf_hi(cv.x))), pack2(silu_(bf_lo(cv.y)), silu_(bf_hi(cv.y))),
                   pack2(silu_(bf_lo(cv.z)), silu_(bf_hi(cv.z))), pack2(silu_(bf_lo(cv.w)), silu_(bf_hi(cv.w))));
            fence_async_smem();
        }
        cluster_wait();
        ep = __shfl_sync(0xffffffffu, ep, 0) / NCTA + 1;
        if (wg == 0) {
            bar_sync(1, 128);
#pragma unroll 1
            for (int p = 0; p < 4; ++p) {
                float acc[128];
#pragma unroll
                for (int i = 0; i < 128; ++i) acc[i] = 0.f;
                uint32_t prev = 0;
#pragma unroll 1
                for (int kc = 0; kc < 16; ++kc) {
                    mbar_wait(BAR_FULL(sb, r.slot), r.par);
                    wg_fence();
#pragma unroll
                    for (int k = 0; k < 4; ++k)
                        wgmma_n256(acc, mk_desc(d16(sb) + kc * 64, OFF_STG + k * 32, 16, 0, 1), mk_desc(d16(sb) + r.slot * (SLOT >> 4), k * 2048, 8192, 1024, 1));
                    wg_commit();
                    wg_wait<1>();
                    if (kc > 0 && tw < 4) mbar_arrive(BAR_EMPTY(sb, prev));
                    prev = r.slot;
                    r.next();
                }
                wg_wait<0>();
                if (tw < 4) mbar_arrive(BAR_EMPTY(sb, prev));
                if (tw < 4) {
#pragma unroll
                    for (int jn = 0; jn < 32; ++jn) sts32(sb + OFF_TAB + (jn * 4 + tw) * 4, pack2(acc[jn * 4], acc[jn * 4 + 1]));
                }
                bar_sync(1, 128);
                const int vec = 2 + p, blk = p * 4 + j;
                const uint32_t val = lds32(sb + OFF_TAB + tw * 4);
                if (vec == 2 || vec == 5) st_pkt(g_mod + (8 + blk) * 128 + tw, val, ep);
                else {
                    const float one = vec == 4 ? 1.f : 0.f;
                    g_par2[((blk & 3) * 16 + (tw >> 3)) * 16 + (tw & 3) * 4 + (vec - 3) * 2 + ((tw >> 2) & 1)] =
                        pack2(0.5f * bf_round(one + bf_lo(val)), 0.5f * bf_round(one + bf_hi(val)));
                }
                bar_sync(1, 128);
                if (tw == 0) {
                    if (vec == 3 || vec == 4) asm volatile("red.release.gpu.global.add.u32 [%0], 1;" :: "l"(&g_flags[FL_LN2]) : "memory");
                    TL(1 + p);
                }
            }
            if (lane < 2) mbar_arrive_cta(BAR_ONE(sb, EV_P0), lane);
        }
        r = Ring{64 % NSLOT, (64 / NSLOT) & 1};
        mbar_wait(BAR_ONE(sb, EV_P0), 0);
        mbar_wait(BAR_FULL(sb, r.slot), r.par);
        uint32_t hp[32] = {};
        passes128<4, false>(hp, sb, wg, tw, r, stg);
        put_h(hp, sb, wg, stg);
      } else {
        float xs[64];
        uint32_t xp[32];
        {
            sts128(sb + tid * 16, pack2(silu_(bf_lo(cw[0])), silu_(bf_lo(cw[1]))), pack2(silu_(bf_lo(cw[2])), silu_(bf_lo(cw[3]))),
                   pack2(silu_(bf_lo(cw[4])), silu_(bf_lo(cw[5]))), pack2(silu_(bf_lo(cw[6])), silu_(bf_lo(cw[7]))));
            cluster_wait();
            ep = __shfl_sync(0xffffffffu, ep, 0) / NCTA + 1;
            load_slab(xp, stg.acquire2(sb, wg));
            unpack_slab(xs, xp);
            if (tid == 0) TL(24);
            if (tid == 128) TL(27);
        }
#pragma unroll 1
        for (int blk = 0; ; ++blk) {
        {
            IDX();
            uint4* const st = (blk ? g_st2 : g_st1 + m * 8 * 512) + wg * 64 + w4 * 16 + g8;
            RowAcc ra;
#pragma unroll
            for (int e = 0; e < 64; ++e) ra.add(e, xs[e]);
            ra.publish(st + j * 512, q4, ep);
            uint32_t t_pub = 0; if (PDLY) asm volatile("mov.u32 %0, %%clock;" : "=r"(t_pub));
            if (tid == 0) TL(blk ? 9 : 26);
            if (tid == 128 && blk) TL(34);
            if (blk) CS(11);
            LnPar lp;
            if (blk == 0) {
            uint4* const mod_out = pt.mail->mod1 + g8 * 512 + (m * 8 + j) * 4 + q4;
            if (wg == 0) {
                uint4 af[8];
#pragma unroll
                for (int i = 0; i < 8; ++i) af[i] = lds128(sb + w4 * 512 + i * 64 + q4 * 16);
                float c[4][4] = {};
#pragma unroll
                for (int i = 0; i < 8; ++i) {
                    if (!(i & 1)) mbar_wait(BAR_ONE(sb, EV_WIN + (i >> 1)), 0);
                    if (i == 6 && tid == 0) TL(25);
#pragma unroll
                    for (int h = 0; h < 2; ++h) {
                        uint32_t b0, b1, b2, b3;
                        ldsm4t(sb + 5 * SLOT + i * 4096 + w4 * 1024 + h * 512 + (lane & 15) * 32 + (lane >> 4) * 16, b0, b1, b2, b3);
                        mma16816(c[2 * h], h ? af[i].z : af[i].x, 0u, h ? af[i].w : af[i].y, 0u, b0, b1);
                        mma16816(c[2 * h + 1], h ? af[i].z : af[i].x, 0u, h ? af[i].w : af[i].y, 0u, b2, b3);
                    }
                }
                if (lane < 4) sts128(sb + OFF_TAB + w4 * 64 + lane * 16, __float_as_uint(c[0][0] + c[2][0]), __float_as_uint(c[0][1] + c[2][1]),
                                     __float_as_uint(c[1][0] + c[3][0]), __float_as_uint(c[1][1] + c[3][1]));
                if (lane < 2) mbar_arrive_cta(BAR_ONE(sb, EV_P0), lane);
                bar_sync(1, 128);
                if (w4 == 0) {
                    float a[4] = {0.f, 0.f, 0.f, 0.f};
#pragma unroll
                    for (int i = 0; i < 4; ++i) {
                        const uint4 t = lds128(sb + OFF_TAB + i * 64 + q4 * 16);
                        a[0] += __uint_as_float(t.x); a[1] += __uint_as_float(t.y); a[2] += __uint_as_float(t.z); a[3] += __uint_as_float(t.w);
                    }
                    const float add = m >= 8 ? 1.f : 0.f;
                    st_pkt16(mod_out, pack2(bf_round(a[0]) + add, bf_round(a[1]) + add), pack2(bf_round(a[2]) + add, bf_round(a[3]) + add), ep, 0);
                    if (tid == 0) TL(3);
                }
            } else if (LWAIT >= 0) mbar_wait(BAR_ONE(sb, EV_WIN + LWAIT), 0);
            } else {
                mbar_wait2(BAR_ONE(sb, EV_LN2), BAR_FULL(sb, 0), 0);
            }
            lp.load(sb, q4);
#pragma unroll
            for (int e = 0; e < 32; ++e) xp[e] = pack2(xs[2 * e], xs[2 * e + 1]);
            if (PDLY && blk) { uint32_t t1; do { asm volatile("mov.u32 %0, %%clock;" : "=r"(t1)); } while (t1 - t_pub < PDLY); }
            if (blk) CS(13);
            const LnRow n = merge_stats(st, q4, ep, sb);
            if (tid == 0) TL(blk ? 49 : 48);
            if (tid == 128) TL(blk ? 45 : 28);
            if (blk) CS(18);
            uint32_t xn[32];
            ln_norm(xn, xs, n);
            if (blk == 0) {
                mbar_wait2(BAR_FULL(sb, 0), BAR_ONE(sb, EV_PAR), 0);
                if (FD0 && wg == 0) { uint32_t t0, t1; asm volatile("mov.u32 %0, %%clock;" : "=r"(t0)); do { asm volatile("mov.u32 %0, %%clock;" : "=r"(t1)); } while (t1 - t0 < FD0); }
                lp.load(sb, q4);
            }
            ln_emit(xn, lp, sb, wg, ix);
            if (tid == 0) { TL(blk ? 36 : 8); TC(blk ? 109 : 103); }
            if (tid == 128) TL(blk ? 43 : 22);
            if (blk) CS(21);
        }
        uint32_t hp[32];
        if (blk == 0) {
        {
            float big[128], sml[64];
            step32<true, true>(big, sml, sb, wg, r.slot, 0);
            TS(0, 0);
            Pipe pp(sb, tw, r.slot);
            r.next();
#pragma unroll 1
            for (int it = 1; it < 32 - LAGQ; ++it) {
                pp.acquire<true>(sb, wg ? 0 : AF_REL, r);
                step32<true, false>(big, sml, sb, wg, r.slot, it < 4 ? it : -1);
                pp.issued(r.slot);
                TS(it, 0);
                r.next();
            }
            auto half = [&](uint32_t slot, bool rest) {
                const uint32_t st = d16(sb) + slot * (SLOT >> 4);
#pragma unroll
                for (int k = 0; k < 2; ++k) {
                    const uint64_t da = mk_desc(st + wg * 256, k * 32, 16, 512, 2);
                    if (rest) wgmma_n256(big, da, mk_desc(st, 8192 + k * 2048, 4096, 1024, 1)); else wgmma_n128(sml, da, mk_desc(st, 24576 + k * 2048, 4096, 1024, 1));
                }
            };
            auto rest = [&](bool each) {
                wg_fence();
#pragma unroll
                for (int it = 32 - LAGQ; it < 32; ++it) { if (each && it > 32 - LAGQ) wg_fence(); half(it % NSLOT, true); if (each || it == 31) wg_commit(); }
            };
            stg.acquire2(sb, wg); mbar_wait2(BAR_SREADY(sb, 2), BAR_SREADY(sb, 3), 1);
#pragma unroll 1
            for (int it = 32 - LAGQ; it < 32; ++it) {
                pp.acquire<true>(sb, wg ? 0 : AF_REL, r);
                wg_fence(); half(r.slot, false); wg_commit();
                pp.issued(NSLOT);
                TS(it, 0);
                r.next();
            }
            if (wg) { rest(false); wg_wait<1>(); } else wg_wait<0>();
            CS(8);
            IDX();
            uint32_t k0[8], k1[8], k2[8], v0[8], v1[8], v2[8];
            const uint32_t nxt = warp + ((warp & 1) ? 3 : 1), mine = sb + OFF_STG + wg * 16384 + w4 * 2048;
            auto tails = [&](const float* kv, uint32_t (&kt)[8], uint32_t (&vt)[8]) {
#pragma unroll
                for (int t = 0; t < 8; ++t) { kt[t] = pack2(kv[4 * t + 2], kv[4 * t + 3]); vt[t] = pack2(kv[32 + 4 * t + 2], kv[32 + 4 * t + 3]); }
            };
            auto post = [&](int pn, uint32_t (&kt)[8], uint32_t (&vt)[8]) {
                uint4* dst = g_halo + (m * 8 + j) * 512 + (w4 >> 1) * 256 + pn * 128 + lane;
#pragma unroll
                for (int h = 0; h < 2; ++h) { if (!kt[4 * h]) kt[4 * h] = 0x8000u; if (!vt[4 * h]) vt[4 * h] = 0x8000u; }
#pragma unroll
                for (int h = 0; h < 2; ++h) { st_pkt16(dst + h * 32, kt[4 * h], kt[4 * h + 1], kt[4 * h + 2], kt[4 * h + 3]); st_pkt16(dst + 64 + h * 32, vt[4 * h], vt[4 * h + 1], vt[4 * h + 2], vt[4 * h + 3]); }
            };
            auto prepare = [&](int pn, const float* kv) {
                tails(kv, k2, v2);
                if (nxt < 8) {
                    const uint32_t dst = sb + OFF_STG + (nxt >> 2) * 16384 + (nxt & 3) * 2048 + pn * 8192 + lane * 16;
#pragma unroll
                    for (int h = 0; h < 2; ++h) { stsm4(dst + h * 512, k2[4 * h], k2[4 * h + 1], k2[4 * h + 2], k2[4 * h + 3]); stsm4(dst + 1024 + h * 512, v2[4 * h], v2[4 * h + 1], v2[4 * h + 2], v2[4 * h + 3]); }
                    if (pn == 0) bar_arrive(NB_TAIL + nxt, 64);
                    else { __syncwarp(); if (lane == 0) mbar_arrive(BAR_ONE(sb, EV_TAIL + nxt)); }
                } else if (pn == 0 && m < 15) post(0, k2, v2);
#pragma unroll
                for (int t = 0; t < 8; ++t) { k1[t] = pack2(kv[4 * t], kv[4 * t + 1]); v1[t] = movm(pack2(kv[32 + 4 * t], kv[32 + 4 * t + 1])); v2[t] = movm(v2[t]); }
                if (pn == 0) { CS(2); if (wg == 0) { rest(true); wg_wait<3>(); pp.rel(28 % NSLOT); wg_wait<2>(); pp.rel(29 % NSLOT); wg_wait<1>(); pp.rel(30 % NSLOT); } bar_sync(NB_TAIL + warp, 64); CS(4); }
                else mbar_wait(BAR_ONE(sb, EV_TAIL + __shfl_sync(0xffffffffu, warp, 0)), 0);
#pragma unroll
                for (int h = 0; h < 2; ++h) {
                    ldsm4(mine + pn * 8192 + lane * 16 + h * 512, k0[4 * h], k0[4 * h + 1], k0[4 * h + 2], k0[4 * h + 3]);
                    ldsm4t(mine + pn * 8192 + lane * 16 + 1024 + h * 512, v0[4 * h], v0[4 * h + 1], v0[4 * h + 2], v0[4 * h + 3]);
                }
            };
#pragma unroll
            for (int i = 0; i < 64; ++i) asm volatile("" : "+f"(sml[i]) :: "memory");
            prepare(0, sml);
            static_assert(LAGQ == 4, "");
            wg_wait<0>();
            if (wg) { pp.rel(28 % NSLOT); pp.rel(29 % NSLOT); pp.rel(30 % NSLOT); }
            pp.rel(31 % NSLOT);
            TS(31, 1);
            if (tid == 0) { TL(4); TC(104); }
            if (tid == 128) TL(50);
            CS(1);
#pragma unroll
            for (int i = 0; i < 128; ++i) asm volatile("" : "+f"(big[i]) :: "memory");
            if (nxt >= 8 && m < 15) { uint32_t kt[8], vt[8]; tails(big, kt, vt); post(1, kt, vt); }
            const bool lo0 = q4 * 2 > g8, lo1 = q4 * 2 + 1 > g8;
            const bool nopast = m == 0 && (warp & 5) == 0;
            const uint32_t lomask = (lo0 ? 0xFFFFu : 0u) | (lo1 ? 0xFFFF0000u : 0u);
            const uint32_t orow = mine + (lane & 7) * 128 + (((lane >> 3) ^ (lane & 7)) << 4);
            const float sl2 = 0.17677669529663687f * 1.4426950408889634f;
#pragma unroll
            for (int pn = 0; pn < 2; ++pn) {
                float e0[4], e1[4], mx[4], sum[4];
#pragma unroll
                for (int hh = 0; hh < 2; ++hh) {
                    uint32_t qf[8];
#pragma unroll
                    for (int i = 0; i < 8; ++i) qf[i] = pack2(big[64 + 32 * pn + 16 * hh + 2 * i], big[64 + 32 * pn + 16 * hh + 2 * i + 1]);
                    float s[3][4];
#pragma unroll
                    for (int t = 0; t < 3; ++t) {
                        const uint32_t* k = (t == 0 ? k0 : t == 1 ? k1 : k2) + 4 * hh;
                        s[t][0] = s[t][1] = s[t][2] = s[t][3] = 0.f;
                        mma16816(s[t], qf[0], qf[1], qf[2], qf[3], k[0], k[1]);
                        mma16816(s[t], qf[4], qf[5], qf[6], qf[7], k[2], k[3]);
                    }
#pragma unroll
                    for (int hf = 0; hf < 2; ++hf) {
                        const int u = hh * 2 + hf;
                        e0[u] = lo0 ? ((hf == 0 && nopast) ? -INFINITY : s[hf][hf * 2]) : s[hf + 1][hf * 2];
                        e1[u] = lo1 ? ((hf == 0 && nopast) ? -INFINITY : s[hf][hf * 2 + 1]) : s[hf + 1][hf * 2 + 1];
                        mx[u] = fmaxf(e0[u], e1[u]);
                    }
                }
#pragma unroll
                for (int o = 1; o < 4; o <<= 1)
#pragma unroll
                    for (int u = 0; u < 4; ++u) mx[u] = fmaxf(mx[u], __shfl_xor_sync(0xffffffffu, mx[u], o));
#pragma unroll
                for (int u = 0; u < 4; ++u) {
                    const float c = -mx[u] * sl2;
                    e0[u] = ex2(fmaf(e0[u], sl2, c)); e1[u] = ex2(fmaf(e1[u], sl2, c));
                    sum[u] = e0[u] + e1[u];
                }
#pragma unroll
                for (int o = 1; o < 4; o <<= 1)
#pragma unroll
                    for (int u = 0; u < 4; ++u) sum[u] += __shfl_xor_sync(0xffffffffu, sum[u], o);
#pragma unroll
                for (int u = 0; u < 4; ++u) {
                    const int h = u >> 1;
                    const float inv = rcp(sum[u]);
                    const uint32_t p = pack2(e0[u] * inv, e1[u] * inv);
                    const uint32_t* va = ((u & 1) ? v1 : v0) + 4 * h;
                    const uint32_t* vb = ((u & 1) ? v2 : v1) + 4 * h;
                    float o[2][4] = {};
#pragma unroll
                    for (int d = 0; d < 2; ++d) mma16816(o[d], va[2 * d], va[2 * d + 1], vb[2 * d], vb[2 * d + 1], p & lomask, p & ~lomask);
                    stsm4t((orow ^ ((u >> 1) << 6)) + pn * 8192 + (u & 1) * 1024, pack2(o[0][0], o[0][1]), pack2(o[0][2], o[0][3]), pack2(o[1][0], o[1][1]), pack2(o[1][2], o[1][3]));
                }
                fence_async_smem();
                __syncwarp();
                if (lane == 0) mbar_arrive(BAR_SFULL(sb, wg * 2 + pn));
                if (pn == 0) { CS(5); block_end(sb, 0); prepare(1, big); CS(3); }
            }
            CS(6);
            if (tid == 32) TL(41);
            mbar_wait2(BAR_FULL(sb, 32 % NSLOT), BAR_FULL(sb, 33 % NSLOT), (32 / NSLOT) & 1);
            load_slab(xp, sb + (32 % NSLOT + wg) * SLOT);
#pragma unroll
            for (int e = 0; e < 32; ++e) hp[e] = __float_as_uint(big[e]);
            bar_sync(1 + wg, 128);
            if (tid == 0) { TL(6); TC(106); }
            if (tid == 128) TL(44);
            CS(7);
        }
        } else {
        {
            float ag[88], au[88];
            mainloop32<true, LAG>(ag, au, sb, wg, tw, r, EV_LAG1, 48, [](int) {}, [&] {
                Ring q = r; if (!wg) q.next();
                mbar_wait(BAR_EMPTY(sb, q.slot), q.par ^ 1);
                mbar_wait(BAR_FULL(sb, r.slot), r.par);
            });
            if (tid == 0) { TL(10); TC(110); }
            if (tid == 128) TL(51);
            CS(22);
            {
                IDX();
                uint32_t h3[12];
                glu(h3, [&](int i) { return ag[64 + i]; }, [&](int i) { return au[64 + i]; });
#pragma unroll
                for (int k = 0; k < 3; ++k) stsm4(sb + (wg ? P3_SLOT1 : P3_SLOT0) * SLOT + 24576 + (pan_addr ^ (k << 5)), h3[4 * k], h3[4 * k + 1], h3[4 * k + 2], h3[4 * k + 3]);
            }
            glu(hp, [&](int i) { return ag[i]; }, [&](int i) { return au[i]; });
            if (tid == 0) { TL(11); TC(111); }
            if (tid == 128) TL(52);
            CS(23);
        }
        passes128<2, true>(hp, sb, wg, tw, r, stg);
        if (tid == 0) { TL(12); TC(112); }
        }
        {
            float acc[64], gf[32];
            mainloop64(acc, blk == 0, sb, wg, tw, r, [&] { put_h(hp, sb, wg, stg); }, [&] {
                mbar_wait(BAR_ONE(sb, EV_GA + blk), 0);
                unpack_slab(xs, xp);
                uint32_t gt[16];
#pragma unroll
                for (int cg = 0; cg < 16; ++cg) gt[cg] = lds32(sb + OFF_TAB + blk * 256 + cg * 16 + (tw & 3) * 4);
#pragma unroll
                for (int i = 0; i < 16; ++i) unpack2(gt[i], gf[2 * i], gf[2 * i + 1]);
            }, [&] { stg.acquire2(sb, wg); });
            if (tid == 0) { TL(blk ? 13 : 7); TC(blk ? 113 : 107); }
            if (tid == 128) TL(blk ? 57 : 42);
            CS(blk ? 30 : 10);
#pragma unroll
            for (int e = 0; e < 64; ++e) xs[e] = fmaf(gf[(e >> 2) * 2 + (e & 1)], acc[e], xs[e]);
        }
        if (blk) break;
        }
        {
            IDX();
#pragma unroll
            for (int p = 0; p < 2; ++p) {
                store_slab(xs, sb + OFF_STG + wg * 16384, 8192, pan_addr, 4 * p, 4 * p + 4);
                stg.publish(sb, wg, lane);
            }
            cluster_arrive();
            if (tid == 0) TL(14);
            CS(31);
        }
      }
    } else {
        if (warp == 8 && !aux && elect_one()) {
#pragma unroll
            for (int i = 0; i < 4; ++i) mbar_init(BAR_SREADY(sb, i), 1);
#pragma unroll
            for (int i = 0; i < 4; ++i) mbar_init(BAR_ONE(sb, EV_WIN + i), 1);
#pragma unroll
            for (int i = 0; i < 4; ++i) {
                mbar_expect_tx(BAR_SREADY(sb, i), 8192);
                tma_load3(sb + OFF_STG + i * 8192, &mp.x, j * 128 + (i & 1) * 64, m * 64 + (i >> 1) * 32, BAR_SREADY(sb, i));
            }
#pragma unroll 1
            for (int i = 0; i < 4; ++i) {
                mbar_expect_tx(BAR_ONE(sb, EV_WIN + i), 8192);
                tma_load(sb + 5 * SLOT + i * 8192, &mp.wm8, 2 * i * 6144 + (m * 8 + j) * 16, 0, BAR_ONE(sb, EV_WIN + i));
                tma_load(sb + 5 * SLOT + i * 8192 + 4096, &mp.wm8, (2 * i + 1) * 6144 + (m * 8 + j) * 16, 0, BAR_ONE(sb, EV_WIN + i));
            }
        }
        __syncwarp();
        asm volatile("setmaxnreg.dec.sync.aligned.u32 56;");
        if (elect_one()) {
            if (warp == 8) {
                prefetch_map(&mp.wqkv); prefetch_map(&mp.wmod);
            } else if (warp < 11) {
                mbar_init(BAR_EMPTY(sb, NSLOT), 1);
#pragma unroll
                for (int i = 0; i < 2; ++i) { mbar_init(BAR_SFULL(sb, (warp - 9) * 2 + i), 4); if (aux) mbar_init(BAR_SREADY(sb, (warp - 9) * 2 + i), 1); }
#pragma unroll
                for (int i = 0; i < 3; ++i) {
                    mbar_init(BAR_EMPTY(sb, (warp - 9) * 3 + i), 4);
                    mbar_init(BAR_FULL(sb, (warp - 9) * 3 + i), 1); mbar_init(BAR_FULL(sb, (warp - 9) * 3 + i) + AF_REL, 1);
                }
            } else {
#pragma unroll
                for (int i = EV_P0; i < EV_COUNT; ++i) mbar_init(BAR_ONE(sb, i), i == EV_P0 ? 8 : 1);
            }
            asm volatile("fence.mbarrier_init.release.cluster;" ::: "memory");
        }
        __syncwarp();
        cluster_arrive();
        ep = 0;
        if (warp != 8 || aux) ep = flag_get(g_flags + FL_DONE);
        cluster_wait();
        ep = __shfl_sync(0xffffffffu, ep, 0) / NCTA + 1;
        if (warp == 8) {
            const bool el = elect_one();
            Ring r{0, 1};
            if (aux) {
                {
                    uint32_t n = 0;
                    while (!__all_sync(0xffffffffu, ld_pkt16(pt.mail->mod1 + 256).z == ep)) { SPIN_GUARD(n); __nanosleep(200); }
                }
#pragma unroll 1
                for (int it = 0; it < 64; ++it) {
                    const int col = 2048 + (it >> 4) * 1024 + j * 256;
                    mbar_wait(BAR_EMPTY(sb, r.slot), r.par);
                    const uint32_t st = sb + r.slot * SLOT, fb = BAR_FULL(sb, r.slot);
                    if (el) {
                        mbar_expect_tx(fb, 32768);
#pragma unroll
                        for (int b = 0; b < 4; ++b) tma_load(st + b * 8192, &mp.wmod, col + b * 64, (it & 15) * 64, fb);
                    }
                    r.next();
                }
                mbar_wait(BAR_ONE(sb, EV_P0), 0);
                const CUtensorMap* wm = rank ? &mp.wu : &mp.wg;
#pragma unroll 1
                for (int g = 0; g < 128; ++g) {
                    const int mx = (j >> 1) * 8 + (g >> 5) * 2 + rank, k0 = ((g & 14) << 6) + ((g & 16) << 2) + ((g & 1) << 5);
                    if (!(g & 15)) {
                        uint32_t n = 0;
                        while (!__all_sync(0xffffffffu, (int32_t)(flag_get(g_flags + FL_PROG + fidx(mx, lane >> 4, (lane & 14) | ((g >> 4) & 1))) - (ep * 8 + ST_H2)) >= 0)) { SPIN_GUARD(n); __nanosleep(300); }
                    }
                    mbar_wait(BAR_EMPTY(sb, r.slot), r.par);
                    const uint32_t st = sb + r.slot * SLOT, fb = BAR_FULL(sb, r.slot);
                    if (el) {
                        mbar_expect_tx(fb, 24576);
                        tma_load_mc(st + 8192 + rank * 4096, wm, HC3, k0, fb);
                        tma_load_mc(st + 16384 + rank * 4096, wm, HC3 + 64, k0, fb);
                        tma_load(st, &mp.h2l, k0, mx * 128, fb);
                    }
                    r.next();
                }
            } else {
#pragma unroll 1
                for (int it = 0; it < 32; ++it) {
                    const int cb = j * 128 + rank * 64, k0 = kof(it, 2, j);
                    if (it == BW0) mbar_wait(BAR_ONE(sb, BWEV), 0);
                    if (it == BW1) mbar_wait(BAR_ONE(sb, EV_PAR), 0);
                    if (it == 5) mbar_wait(BAR_ONE(sb, EV_P0), 0);
                    if (it == AG0) mbar_wait(BAR_ONE(sb, (AGW & 1) ? EV_AGO : EV_FGO), 0);
                    mbar_wait(BAR_EMPTY(sb, r.slot), r.par);
                    const uint32_t st = sb + r.slot * SLOT, fb = BAR_FULL(sb, r.slot);
                    if (el) {
                        mbar_expect_tx(fb, it < 4 ? 24576 : 28672);
                        tma_load_mc(st + 24576 - rank * 16384, &mp.wqkv, 1024 + cb, k0, fb);
                        tma_load_mc(st + 28672 - rank * 16384, &mp.wqkv, 2048 + cb, k0, fb);
                        tma_load_mc(st + 16384 + rank * 4096, &mp.wqkv, cb, k0, fb);
                        if (it < 4) mbar_arrive(fb + AF_REL);
                        if (it == PFWO + (m >> 1)) { tma_prefetch(&mp.wo, j * 128, m * 64); tma_prefetch(&mp.wo, j * 128 + 64, m * 64); }
                        if (it >= PFG && it < PFG + PFN && (it & 7) == grp) {
                            const int kp = kof(it - PFG + PFO, 2, j);
                            tma_prefetch(rank ? &mp.wu : &mp.wg, hcol(0, j), kp); tma_prefetch(rank ? &mp.wu : &mp.wg, hcol(0, j) + 64, kp);
                            asm volatile("cp.async.bulk.prefetch.tensor.3d.L2.global [%0, {%1, %2, %3}];" :: "l"(rank ? &mp.wu3 : &mp.wg3), "r"(0), "r"(j), "r"(kp) : "memory");
                        }
                    }
                    r.next();
                }
                if (el) mbar_arrive(BAR_ONE(sb, EV_KV));
#pragma unroll 1
                for (int it = 0; it < 16; ++it) {
                    const int k0 = kof(it, 1, j);
                    if (it == AG1) mbar_wait(BAR_ONE(sb, (AGW & 2) ? EV_AGO1 : EV_FGO1), 0);
                    mbar_wait(BAR_EMPTY(sb, r.slot), r.par);
                    const uint32_t st = sb + r.slot * SLOT, fb = BAR_FULL(sb, r.slot);
                    if (el) {
                        mbar_expect_tx(fb, it < 2 ? 32768 : 24576);
                        tma_load_mc(st + 16384 + rank * 8192, &mp.wo, j * 128 + rank * 64, k0, fb);
                        if (it < 2) {
                            tma_load3(st, &mp.x, j * 128, m * 64 + it * 32, fb); tma_load3(st + 8192, &mp.x, j * 128 + 64, m * 64 + it * 32, fb);
                            mbar_arrive(fb + AF_REL);
                        }
                        if (it == 6) { prefetch_map(rank ? &mp.wu : &mp.wg); prefetch_map(rank ? &mp.wu3 : &mp.wg3); }
                    }
                    r.next();
                }
                const CUtensorMap* wm = rank ? &mp.wu : &mp.wg;
#pragma unroll 1
                for (int g = 0; g < 96; ++g) {
                    if (g == AG2) mbar_wait(BAR_ONE(sb, (AGW & 4) ? EV_AGO2 : EV_FGO2), 0);
                    const int p = g >> 5, cb = hcol(p, j), k0 = p == 0 ? kof(g, 2, j) : (g & 31) * 32;
                    mbar_wait(BAR_EMPTY(sb, r.slot), r.par);
                    const uint32_t st = sb + r.slot * SLOT, fb = BAR_FULL(sb, r.slot);
                    if (el) {
                        mbar_expect_tx(fb, (g < 4 || p > 0) ? 24576 : 28672);
                        tma_load_mc(st + 8192 + rank * 4096, wm, cb, k0, fb);
                        tma_load_mc(st + 16384 + rank * 4096, wm, cb + 64, k0, fb);
                        if (p == 0) tma_load3_mc(st + 24576 + rank * 4096, rank ? &mp.wu3 : &mp.wg3, j, k0, fb);
                        else tma_load(st, &mp.h2l, k0, m * 128, fb);
                        if (g < 4) mbar_arrive(fb + AF_REL);
                        if (g == 60) prefetch_map(&mp.wd);
                    }
                    r.next();
                }
#pragma unroll 1
                for (int g = 0; g < 56; ++g) {
                    if (g == 0 || (g & 15) == 6 && g > 6) mbar_wait(BAR_ONE(sb, EV_H0 + (g >> 4)), 0);
                    const int k0 = g * 64;
                    mbar_wait(BAR_EMPTY(sb, r.slot), r.par);
                    const uint32_t st = sb + r.slot * SLOT, fb = BAR_FULL(sb, r.slot);
                    if (el) {
                        mbar_expect_tx(fb, 32768);
                        tma_load_mc(st + 16384 + rank * 8192, &mp.wd, j * 128 + rank * 64, k0, fb);
                        tma_load(st, &mp.hb, k0, m * 128, fb); tma_load(st + 8192, &mp.hb, k0, m * 128 + 64, fb);
                    }
                    r.next();
                }
            }
        } else if (aux) {
            if (warp < 11) {
                const uint32_t w = warp - 9;
                const bool el = elect_one();
#pragma unroll 1
                for (int p = 0; p < 4; ++p) {
                    const int mx = (j >> 1) * 8 + p * 2 + rank;
                    if (el) { mbar_arrive(BAR_SREADY(sb, w * 2)); mbar_arrive(BAR_SREADY(sb, w * 2 + 1)); }
                    mbar_wait2(BAR_SFULL(sb, w * 2), BAR_SFULL(sb, w * 2 + 1), p & 1);
                    if (p < 3) pause(w ? HD1 : HD0);
                    if (el) tma_store(&mp.hb, HC3, mx * 128 + w * 64, sb + OFF_STG + w * 16384);
                    if (p < 3) pause(HP);
                    if (el) {
                        tma_store(&mp.hb, HC3 + 64, mx * 128 + w * 64, sb + OFF_STG + w * 16384 + 8192);
                        bulk_commit(); bulk_wait_fence(); flag_set(g_flags + FL_AUX + mx * 2 + w, ep * 8 + ST_H + 3);
                    }
                }
            }
        } else if (warp == 11) {
            const bool el = elect_one();
            const int row0 = m * 128;
            const uint32_t* const fl = g_flags + FL_PROG + fidx(m, lane >> 4, kof(lane & 15, 1, j) >> 6);
            if (el) { prefetch_map(&mp.h1h); prefetch_map(&mp.h2h); prefetch_map(&mp.h2l); }
            auto gate = [&](int vec, int ev) {
                uint4 v; uint32_t n = 0;
                while (true) {
                    v = ld_pkt2(g_mod + vec * 512 + j * 64 + lane * 2);
                    if (__all_sync(0xffffffffu, v.y == ep && v.w == ep)) break;
                    SPIN_GUARD(n); __nanosleep(300);
                }
                asm volatile("st.shared.v2.u32 [%0], {%1, %2};" :: "r"(sb + OFF_TAB + (ev - EV_GA) * 256 + lane * 8), "r"(v.x), "r"(v.z) : "memory");
                __syncwarp();
                if (lane == 0) mbar_arrive(BAR_ONE(sb, ev));
            };
            {
                const uint4* pk = pt.mail->mod1 + grp * 512 + j * 32 + lane;
                uint4 a, b; uint32_t n = 0;
                mbar_wait(BAR_ONE(sb, EV_WIN3), 0);
                while (true) {
                    a = ld_pkt16(pk); b = ld_pkt16(pk + 256);
                    if (__all_sync(0xffffffffu, a.z == ep && b.z == ep)) break;
                    SPIN_GUARD(n);
                }
                sts128(sb + OFF_PAR + lane * 16, a.x, a.y, b.x, b.y);
                __syncwarp();
                if (lane == 0) { mbar_arrive(BAR_ONE(sb, EV_PAR)); TL(46); }
            }
            mbar_wait(BAR_ONE(sb, EV_P0), 0);
            Ring r{0, 1};
#pragma unroll 1
            for (int ph = 0; ph < 3; ++ph) {
                const int sh = ph == 1 ? 1 : 2, nst = 8 << sh;
                const uint32_t half = 16384 >> sh, target = ep * 8 + ST_H1 + ph;
                const CUtensorMap* tm = ph == 0 ? &mp.h1h : ph == 1 ? &mp.o : &mp.h2h;
                if (ph == 1) {
                    gate(2, EV_GA);
                    mbar_wait(BAR_SREADY(sb, 1), 1);
#pragma unroll 1
                    for (int i = 0; i < 2; ++i)
                        fetch_halo<1>(g_halo + ((m - 1) * 8 + j) * 512 + i * 256 + 128 + lane, m == 0, sb + OFF_STG + 8192 + i * 4096 + lane * 16,
                                      [&] { __syncwarp(); if (el) mbar_arrive(BAR_ONE(sb, EV_TAIL + 2 * i)); });
                    CS(32);
                }
                if (ph == 2) {
                    uint32_t n = 0;
                    while ((int32_t)(flag_get(g_flags + FL_LN2) - ep * 8) < 0) { SPIN_GUARD(n); __nanosleep(200); }
                    const uint4 v = __ldcg((const uint4*)(g_par2 + j * 128) + lane);
                    sts128(sb + OFF_PAR + lane * 16, v.x, v.y, v.z, v.w);
                    __syncwarp();
                    if (lane == 0) mbar_arrive(BAR_ONE(sb, EV_LN2));
                }
                const uint32_t lw = ~lane & 1, lt = lane >> 1, ls = (r.slot + lt) % NSLOT, lk = kof(lt, sh, j), lb = BAR_FULL(sb, ls) + (lw ? 0 : AF_REL);
                const uint32_t* const lf = g_flags + FL_PROG + fidx(m, lw, lk >> 6);
                int fr = 1 << sh;
                uint32_t todo = 0x3ffffu >> (2 * fr) << (2 * fr), have = ~todo, n = 0, v = 0;
                r.skip(fr);
#pragma unroll 1
                for (; fr < NSLOT; ++fr) { mbar_wait(BAR_EMPTY(sb, r.slot), r.par); r.next(); }
                if (ph == XST - 1) CS(33);
                do {
                    if (!((have >> lane) & 1)) v = flag_get(lf);
                    while (ph == 2 && fr < FRCAP && mbar_test(BAR_EMPTY(sb, r.slot), r.par)) { ++fr; r.next(); }
                    SPIN_GUARD(n);
                    have |= __ballot_sync(0xffffffffu, (int32_t)(v - target) >= 0);
                    const uint32_t go = have & todo & ((1u << (2 * fr)) - 1);
                    if ((go >> lane) & 1) {
                        if (!lw) mbar_expect_tx(lb, half);
                        tma_load(sb + ls * SLOT + lw * half, tm, lk, row0 + lw * 64, lb);
                    }
                    __syncwarp();
                    if (lane < 2 && (todo & (0x555u << lane)) && !(todo & ~go & (0x555u << lane))) mbar_arrive(BAR_ONE(sb, (lane ? EV_FGO : EV_AGO) + ph));
                    if (ph == XST - 1) { if (go & (1u << (2 << sh))) CS(34); if (go & (2u << (2 << sh))) CS(35); if (todo & 0x555u) CS(36); if (todo & 0xaaau) CS(37); }
                    todo &= ~go;
                } while (~have);
                if (ph == XST - 1) CS(38);
                int k = kof(fr, sh, j);
#pragma unroll 1
                for (; fr < nst; ++fr) {
                    if (fr == 9 || fr == 18) {
                        const uint32_t skip = fr == 9 << (sh - 1) ? 0 : ~0x01fc01fcu;
                        while (~(__ballot_sync(0xffffffffu, (int32_t)(flag_get(fl) - target) >= 0) | skip)) SPIN_GUARD(n);
                    }
                    const uint32_t st = sb + r.slot * SLOT, fb = BAR_FULL(sb, r.slot);
                    mbar_wait(BAR_EMPTY(sb, r.slot), r.par);
                    if (el) {
                        tma_load(st + half, tm, k, row0 + 64, fb);
                        mbar_expect_tx(fb + AF_REL, half);
                        tma_load(st, tm, k, row0, fb + AF_REL);
                    }
                    if (ph == XST - 1 && fr == 9) CS(39);
                    r.next();
                    k = kof(fr + 1, sh, j);
                }
            }
#pragma unroll 1
            for (int p = 0; p < 4; ++p) {
                const uint32_t* f = p < 3 ? fl : g_flags + FL_AUX + m * 2 + (lane & 1);
                uint32_t n = 0;
                while (!__all_sync(0xffffffffu, (int32_t)(flag_get(f) - (ep * 8 + ST_H + p)) >= 0)) { SPIN_GUARD(n); __nanosleep(300); }
                if (el) mbar_arrive(BAR_ONE(sb, EV_H0 + p));
                if (p == 0) gate(5, EV_GB);
            }
        } else {
            const uint32_t w = warp - 9;
            const int row0 = m * 128 + w * 64;
            const uint32_t stg = sb + OFF_STG + w * 16384;
            uint32_t* const fl = g_flags + FL_PROG + fidx(m, w, 2 * j);
            uint32_t b = 0, par = 0;
            const bool el = elect_one();
            auto store = [&](const CUtensorMap* tm, int col, bool nat = false) {
                mbar_wait(BAR_SFULL(sb, w * 2 + b), (par >> b) & 1);
                par ^= 1u << b;
                if (el) {
                    if (nat) tma_store3(tm, col, row0 >> 1, 0, stg + b * 8192); else tma_store(tm, col, row0, stg + b * 8192);
                    bulk_commit();
                }
                b ^= 1;
            };
            auto send2 = [&](const CUtensorMap* tm, const uint32_t* buf, int step) {
                const uint32_t* const q = buf + (size_t)((row0 + lane) * (D_ / 2) + j * 64 + 31);
                store(tm, j * 128);
                if (step == XST) CS(33);
                uint32_t z = landed(el, q, D_ / 2, pt.zero);
                if (el) flag_set(fl, ep * 8 + step + z);
                if (step == XST) CS(34);
                if (step != ST_O) { mbar_wait(BAR_ONE(sb, EV_FGO + step - ST_H1), 0); pause(step == ST_H1 ? (w ? P1H : P1H + 1000) : w ? P2L : P2F); }
                store(tm, j * 128 + 64);
                if (step == XST) CS(35);
                z = landed(el, q + 32, D_ / 2, pt.zero);
                if (el) flag_set(fl + 1, ep * 8 + step + z);
                if (step == XST) CS(36);
            };
            auto free2 = [&]() { if (el) { mbar_arrive(BAR_SREADY(sb, w * 2)); mbar_arrive(BAR_SREADY(sb, w * 2 + 1)); } };
            if (el) { prefetch_map(&mp.h1s); prefetch_map(&mp.o); prefetch_map(&mp.h2s); prefetch_map(&mp.hb); prefetch_map(&mp.out); prefetch_map(&mp.wo); }
            send2(&mp.h1s, pt.h1, ST_H1);
            if (w == 0) TL(47);
            free2();
            mbar_wait(BAR_ONE(sb, EV_KV), 0);
            mbar_wait(BAR_SREADY(sb, 0), 1);
            fetch_halo<1>(g_halo + ((m - 1) * 8 + j) * 512 + w * 256 + lane, m == 0, sb + OFF_STG + w * 4096 + lane * 16, [&] { bar_arrive(NB_TAIL + 2 * w, 64); CS(38); });
            send2(&mp.o, pt.o, ST_O);
            if (w == 0) TL(40); else TL(38);
            free2();
            send2(&mp.h2s, pt.o, ST_H2);
            if (el) { prefetch_map(&mp.hb); prefetch_map(&mp.hb3); }
            if (w == 0) TL(37);
            free2();
#pragma unroll 1
            for (int p = 0; p < 3; ++p) {
                const int col = hcol(p, j);
                mbar_wait(BAR_SFULL(sb, w * 2), par & 1);
                pause(w ? HD1 : HD0); store(&mp.hb, col);
                pause(HP); store(&mp.hb, col + 64);
                if (p == 0) {
                    pause(HP);
                    if (el) { tma_store3(&mp.hb3, 0, j, row0, sb + (w ? P3_SLOT1 : P3_SLOT0) * SLOT + 24576); bulk_commit(); }
                }
                if (el) bulk_wait_read();
                free2();
                if (el) { bulk_wait_fence(); flag_set(fl, ep * 8 + ST_H + p); flag_set(fl + 1, ep * 8 + ST_H + p); }
            }
            cluster_arrive_early = true;
            cluster_arrive();
            store(&mp.out, j * 128, true); store(&mp.out, j * 128 + 64, true);
            if (el) bulk_wait_read();
        }
        __syncwarp();
    }
    if (aux || (wg == 2 && !cluster_arrive_early)) cluster_arrive();
    cluster_wait();
    if (KDEBUG == 5) __syncthreads();
    if (tid == 0) {
        TL(15);
        flag_add(pt.mail->flags + FL_DONE);
    }
}

typedef CUresult (*EncodeFn)(CUtensorMap*, CUtensorMapDataType, cuuint32_t, void*, const cuuint64_t*, const cuuint64_t*, const cuuint32_t*,
                             const cuuint32_t*, CUtensorMapInterleave, CUtensorMapSwizzle, CUtensorMapL2promotion, CUtensorMapFloatOOBfill);

void make_map(EncodeFn fn, CUtensorMap* m, const void* ptr, uint64_t rows, uint64_t cols, uint32_t brows, uint32_t bcols) {
    cuuint64_t dims[2] = {cols, rows}, strides[1] = {cols * 2};
    cuuint32_t box[2] = {bcols, brows}, es[2] = {1, 1};
    fn(m, CU_TENSOR_MAP_DATA_TYPE_BFLOAT16, 2, (void*)ptr, dims, strides, box, es, CU_TENSOR_MAP_INTERLEAVE_NONE,
       bcols == 64 ? CU_TENSOR_MAP_SWIZZLE_128B : bcols == 32 ? CU_TENSOR_MAP_SWIZZLE_64B : CU_TENSOR_MAP_SWIZZLE_NONE, CU_TENSOR_MAP_L2_PROMOTION_L2_256B, CU_TENSOR_MAP_FLOAT_OOB_FILL_NONE);
}

void make_map3(EncodeFn fn, CUtensorMap* m, const void* ptr) {
    cuuint64_t dims[3] = {D_, S_ / 2, 2}, strides[2] = {4 * D_, 2 * D_};
    cuuint32_t box[3] = {64, 32, 2}, es[3] = {1, 1, 1};
    fn(m, CU_TENSOR_MAP_DATA_TYPE_BFLOAT16, 3, (void*)ptr, dims, strides, box, es, CU_TENSOR_MAP_INTERLEAVE_NONE,
       CU_TENSOR_MAP_SWIZZLE_128B, CU_TENSOR_MAP_L2_PROMOTION_L2_256B, CU_TENSOR_MAP_FLOAT_OOB_FILL_NONE);
}

void make_map48(EncodeFn fn, CUtensorMap* m, const void* ptr, uint64_t rows, uint32_t brows) {
    cuuint64_t dims[3] = {48, 8, rows}, strides[2] = {96, 2 * F_};
    cuuint32_t box[3] = {64, 1, brows}, es[3] = {1, 1, 1};
    fn(m, CU_TENSOR_MAP_DATA_TYPE_BFLOAT16, 3, (void*)ptr, dims, strides, box, es, CU_TENSOR_MAP_INTERLEAVE_NONE,
       CU_TENSOR_MAP_SWIZZLE_128B, CU_TENSOR_MAP_L2_PROMOTION_L2_256B, CU_TENSOR_MAP_FLOAT_OOB_FILL_NONE);
}

}

extern "C" void kernel_launch(void* const* d_in, const int* in_sizes, int n_in, void* d_out, int out_size) {
    (void)in_sizes; (void)n_in; (void)out_size;
    void* fnp = nullptr;
    cudaDriverEntryPointQueryResult qr;
    cudaGetDriverEntryPoint("cuTensorMapEncodeTiled", &fnp, cudaEnableDefault, &qr);
    EncodeFn fn = (EncodeFn)fnp;
    void *h1, *o, *h2, *hb, *mail;
    cudaGetSymbolAddress(&h1, g_h1);
    cudaGetSymbolAddress(&mail, g_mail);
    cudaGetSymbolAddress(&o, g_o);
    cudaGetSymbolAddress(&hb, g_hb);
    h2 = o;
    Maps mp;
    make_map(fn, &mp.h1h, h1, S_, D_, 64, 32);
    make_map(fn, &mp.h2h, h2, S_, D_, 64, 32);
    make_map(fn, &mp.h1s, h1, S_, D_, 64, 64);
    make_map(fn, &mp.o, o, S_, D_, 64, 64);
    make_map(fn, &mp.h2l, h2, S_, D_, 128, 32);
    make_map(fn, &mp.h2s, h2, S_, D_, 64, 64);
    make_map(fn, &mp.hb, hb, S_, F_, 64, 64);
    make_map(fn, &mp.wqkv, d_in[1], D_, 3 * D_, 32, 64);
    make_map(fn, &mp.wo, d_in[2], D_, D_, 64, 64);
    make_map(fn, &mp.wg, d_in[4], D_, F_, 32, 64);
    make_map(fn, &mp.wu, d_in[5], D_, F_, 32, 64);
    make_map(fn, &mp.wd, d_in[6], F_, D_, 64, 64);
    make_map(fn, &mp.wmod, d_in[8], D_, 6 * D_, 64, 64);
    make_map(fn, &mp.wm8, d_in[8], D_ / 8, 8 * 6 * D_, 128, 16);
    make_map3(fn, &mp.x, d_in[0]);
    make_map3(fn, &mp.out, d_out);
    make_map48(fn, &mp.wg3, d_in[4], D_, 32);
    make_map48(fn, &mp.wu3, d_in[5], D_, 32);
    make_map48(fn, &mp.hb3, hb, S_, 64);
    cudaFuncSetAttribute(fused_block_kernel, cudaFuncAttributeMaxDynamicSharedMemorySize, SMEM_BYTES);
    cudaLaunchConfig_t cfg = {};
    cfg.gridDim = dim3(NCTA); cfg.blockDim = dim3(384); cfg.dynamicSmemBytes = SMEM_BYTES; cfg.stream = cudaStreamPerThread;
    cudaLaunchAttribute at[1];
    at[0].id = cudaLaunchAttributeClusterDimension; at[0].val.clusterDim.x = 2; at[0].val.clusterDim.y = 1; at[0].val.clusterDim.z = 1;
    cfg.attrs = at; cfg.numAttrs = 1;
    const Ptrs pt{(const __nv_bfloat16*)d_in[7], (Mail*)mail, (const uint32_t*)h1, (const uint32_t*)o, 0};
    cudaLaunchKernelEx(&cfg, fused_block_kernel, pt, mp);
}
```

```cpp
#include <cuda_runtime.h>
#include <cuda_bf16.h>
#include <cuda.h>
#include <stdint.h>
#include <stddef.h>

#define LAG 4
#define LAGS 4
#define LAGW 2
#define LAGD 4
#define LAGQ 4
#define PUT1 5
#define PUT0 10
#define PUTD1 6
#define PUTD0 10
#define MIDD 40
#define HD1 3000
#define HD0 1500
#define NSPL 2
#define HE1 HD1
#define HE0 HD0
#define HP 2600
#define P1H 3000
#define P2L 2000
#define P2F 3000
#define PDLY 500
#define FD0 150
#define AG0 6
#define AG1 6
#define AG2 8
#define AGW 2
#define FRCAP 8
#define BW0 0
#define BWEV EV_WIN
#define BW1 3
#define LWAIT 3
#define PFWO 12
#define PFG 8
#define PFN 24
#define PFO 0
#define KDEBUG 0
#define CSW 0
#define XST ST_O

namespace {

constexpr int S_ = 2048, D_ = 1024, F_ = 3584;
constexpr int NCTA = 132;
constexpr int NSLOT = 6;
constexpr uint32_t SLOT = 32768;
constexpr uint32_t OFF_STG = NSLOT * SLOT;
constexpr uint32_t OFF_BAR = OFF_STG + 32768;
constexpr uint32_t OFF_PAR = OFF_BAR + 512;
constexpr uint32_t OFF_TAB = OFF_PAR + 768;
constexpr uint32_t OFF_TL = OFF_PAR + 2048;
constexpr uint32_t SMEM_BYTES = OFF_TL + (KDEBUG ? 512 : 0);
constexpr uint32_t P3_SLOT1 = (32 + 16 + 32) % NSLOT, P3_SLOT0 = (P3_SLOT1 + 1) % NSLOT;

constexpr int ST_H1 = 1, ST_O = 2, ST_H2 = 3, ST_H = 4, FL_DONE = 0, FL_LN2 = 1, FL_AUX = 32, FL_PROG = 64;

struct Maps {
    CUtensorMap h1h, h1s, o, h2h, h2l, hb, wqkv, wo, wg, wu, wd, wmod, wm8, x, out, wg3, wu3, hb3, hbs;
};

struct Mail {
    uint32_t flags[16 * 32 + 64];
    uint2 mod[6 * D_ / 2];
    uint4 mod1[8 * 512];
    uint4 st1[128 * 512];
    uint32_t par2[D_];
    uint4 halo[128 * 512];
};
struct Ptrs { const __nv_bfloat16* c; Mail* mail; const uint32_t *h1, *o; uint32_t zero; };

__device__ __align__(128) Mail g_mail;
__device__ __align__(128) __nv_bfloat16 g_h1[S_ * D_];
__device__ __align__(128) __nv_bfloat16 g_o[S_ * D_];
__device__ __align__(128) __nv_bfloat16 g_hb[S_ * F_];
#define TL(i) do {} while (0)
#define TC(i) do {} while (0)
#define TS(g, which) do {} while (0)
#define CS(i) do {} while (0)

__device__ __forceinline__ uint32_t smem_u32(const void* p) { return (uint32_t)__cvta_generic_to_shared(p); }
__device__ __forceinline__ void mbar_init(uint32_t bar, uint32_t cnt) { asm volatile("mbarrier.init.shared::cta.b64 [%0], %1;" :: "r"(bar), "r"(cnt) : "memory"); }
__device__ __forceinline__ void mbar_expect_tx(uint32_t bar, uint32_t bytes) { asm volatile("mbarrier.arrive.expect_tx.shared::cta.b64 _, [%0], %1;" :: "r"(bar), "r"(bytes) : "memory"); }
__device__ __forceinline__ void mbar_arrive(uint32_t bar) { asm volatile("mbarrier.arrive.shared::cta.b64 _, [%0];" :: "r"(bar) : "memory"); }
__device__ __forceinline__ void mbar_arrive_cta(uint32_t bar, uint32_t cta) {
    asm volatile("{\n.reg .b32 r;\nmapa.shared::cluster.u32 r, %0, %1;\nmbarrier.arrive.shared::cluster.b64 _, [r];\n}" :: "r"(bar), "r"(cta) : "memory");
}
__device__ __forceinline__ void mbar_wait(uint32_t bar, uint32_t parity) {
    asm volatile("{\n.reg .pred p;\n.reg .u32 n;\nmov.u32 n, 0;\n"
        "W_LOOP:\nmbarrier.try_wait.parity.shared::cta.b64 p, [%0], %1;\n@p bra W_DONE;\n"
        "add.u32 n, n, 1;\nsetp.lt.u32 p, n, 0x400000;\n@p bra W_LOOP;\ntrap;\nW_DONE:\n}" :: "r"(bar), "r"(parity) : "memory");
}
__device__ __forceinline__ void mbar_wait2(uint32_t b0, uint32_t b1, uint32_t parity) {
    asm volatile("{\n.reg .pred p, q;\n.reg .u32 n;\nmov.u32 n, 0;\n"
        "W_LOOP:\nmbarrier.try_wait.parity.shared::cta.b64 p, [%0], %2;\nmbarrier.try_wait.parity.shared::cta.b64 q, [%1], %2;\nand.pred p, p, q;\n@p bra W_DONE;\n"
        "add.u32 n, n, 1;\nsetp.lt.u32 p, n, 0x400000;\n@p bra W_LOOP;\ntrap;\nW_DONE:\n}" :: "r"(b0), "r"(b1), "r"(parity) : "memory");
}
__device__ __forceinline__ bool mbar_test(uint32_t bar, uint32_t parity) {
    uint32_t r; asm volatile("{\n.reg .pred p;\nmbarrier.test_wait.parity.shared::cta.b64 p, [%1], %2;\nselp.u32 %0, 1, 0, p;\n}" : "=r"(r) : "r"(bar), "r"(parity) : "memory"); return r;
}
__device__ __forceinline__ bool mbar_test2(uint32_t b0, uint32_t b1, uint32_t parity) {
    uint32_t r;
    asm volatile("{\n.reg .pred p, q;\nmbarrier.test_wait.parity.shared::cta.b64 p, [%1], %3;\nmbarrier.test_wait.parity.shared::cta.b64 q, [%2], %3;\n"
        "and.pred p, p, q;\nselp.u32 %0, 1, 0, p;\n}" : "=r"(r) : "r"(b0), "r"(b1), "r"(parity) : "memory");
    return r;
}
__device__ __forceinline__ void tma_load3(uint32_t dst, const CUtensorMap* m, int c0, int c1, uint32_t bar) {
    asm volatile("cp.async.bulk.tensor.3d.shared::cluster.global.mbarrier::complete_tx::bytes [%0], [%1, {%3, %4, %5}], [%2];"
        :: "r"(dst), "l"(m), "r"(bar), "r"(c0), "r"(c1), "r"(0) : "memory");
}
__device__ __forceinline__ void tma_store3(const CUtensorMap* m, int c0, int c1, int c2, uint32_t src) {
    asm volatile("cp.async.bulk.tensor.3d.global.shared::cta.bulk_group [%0, {%2, %3, %4}], [%1];" :: "l"(m), "r"(src), "r"(c0), "r"(c1), "r"(c2) : "memory");
}
__device__ __forceinline__ void tma_load3_mc(uint32_t dst, const CUtensorMap* m, int c1, int c2, uint32_t bar) {
    asm volatile("cp.async.bulk.tensor.3d.shared::cluster.global.mbarrier::complete_tx::bytes.multicast::cluster.L2::cache_hint [%0], [%1, {%3, %4, %5}], [%2], %6, %7;"
        :: "r"(dst), "l"(m), "r"(bar), "r"(0), "r"(c1), "r"(c2), "h"((uint16_t)3), "l"(0x12F0000000000000ull) : "memory");
}
__device__ __forceinline__ void tma_load(uint32_t dst, const CUtensorMap* m, int c0, int c1, uint32_t bar) {
    asm volatile("cp.async.bulk.tensor.2d.shared::cluster.global.mbarrier::complete_tx::bytes [%0], [%1, {%3, %4}], [%2];"
        :: "r"(dst), "l"(m), "r"(bar), "r"(c0), "r"(c1) : "memory");
}
__device__ __forceinline__ void tma_load_mc(uint32_t dst, const CUtensorMap* m, int c0, int c1, uint32_t bar) {
    asm volatile("cp.async.bulk.tensor.2d.shared::cluster.global.mbarrier::complete_tx::bytes.multicast::cluster.L2::cache_hint [%0], [%1, {%3, %4}], [%2], %5, %6;"
        :: "r"(dst), "l"(m), "r"(bar), "r"(c0), "r"(c1), "h"((uint16_t)3), "l"(0x12F0000000000000ull) : "memory");
}
__device__ __forceinline__ void tma_prefetch(const CUtensorMap* m, int c0, int c1) {
    asm volatile("cp.async.bulk.prefetch.tensor.2d.L2.global [%0, {%1, %2}];" :: "l"(m), "r"(c0), "r"(c1) : "memory");
}
__device__ __forceinline__ void tma_store(const CUtensorMap* m, int c0, int c1, uint32_t src) {
    asm volatile("cp.async.bulk.tensor.2d.global.shared::cta.bulk_group [%0, {%2, %3}], [%1];" :: "l"(m), "r"(src), "r"(c0), "r"(c1) : "memory");
}
__device__ __forceinline__ void bulk_commit() { asm volatile("cp.async.bulk.commit_group;" ::: "memory"); }
__device__ __forceinline__ void bulk_wait_read() { asm volatile("cp.async.bulk.wait_group.read 0;" ::: "memory"); }
__device__ __forceinline__ void fence_async_smem() { asm volatile("fence.proxy.async.shared::cta;" ::: "memory"); }
__device__ __forceinline__ void prefetch_map(const CUtensorMap* m) { asm volatile("prefetch.tensormap [%0];" :: "l"(m) : "memory"); }
__device__ __forceinline__ void wg_fence() { asm volatile("wgmma.fence.sync.aligned;" ::: "memory"); }
__device__ __forceinline__ void wg_commit() { asm volatile("wgmma.commit_group.sync.aligned;" ::: "memory"); }
template <int N> __device__ __forceinline__ void wg_wait() { asm volatile("wgmma.wait_group.sync.aligned %0;" :: "n"(N) : "memory"); }
__device__ __forceinline__ void bar_sync(int id, int n) { asm volatile("bar.sync %0, %1;" :: "r"(id), "r"(n) : "memory"); }
__device__ __forceinline__ void bar_arrive(int id, int n) { asm volatile("bar.arrive %0, %1;" :: "r"(id), "r"(n) : "memory"); }
__device__ __forceinline__ void flag_add(uint32_t* f) { asm volatile("red.relaxed.gpu.global.add.u32 [%0], 1;" :: "l"(f) : "memory"); }
__device__ __forceinline__ void flag_set(uint32_t* f, uint32_t v) { asm volatile("red.relaxed.gpu.global.max.u32 [%0], %1;" :: "l"(f), "r"(v) : "memory"); }
__device__ __forceinline__ uint32_t flag_get(const uint32_t* f) { uint32_t v; asm volatile("ld.relaxed.gpu.global.u32 %0, [%1];" : "=r"(v) : "l"(f) : "memory"); return v; }
__device__ __forceinline__ void bulk_wait_fence() { asm volatile("cp.async.bulk.wait_group 0;\nfence.proxy.async.global;\nfence.acq_rel.gpu;" ::: "memory"); }
__device__ __forceinline__ uint32_t landed(bool el, const uint32_t* p, uint32_t pitch, uint32_t zero) {
    if (el) asm volatile("cp.async.bulk.wait_group 0;" ::: "memory");
    __syncwarp();
    const uint32_t a = flag_get(p), b = flag_get(p + 32 * pitch);
    return __reduce_or_sync(0xffffffffu, (a | b) & zero);
}
__device__ __forceinline__ uint32_t d16(uint32_t addr) { return (addr & 0x3FFFF) >> 4; }
__device__ __forceinline__ uint64_t mk_desc(uint32_t a16, uint32_t off, uint32_t lbo, uint32_t sbo, uint32_t swz) {
    const uint32_t lo = a16 + (off >> 4) + ((lbo >> 4) << 16), hi = (sbo >> 4) | (swz << 30);
    return ((uint64_t)hi << 32) | lo;
}
__device__ __forceinline__ uint32_t pack2(float lo, float hi) {
    uint32_t r; asm("cvt.rn.bf16x2.f32 %0, %1, %2;" : "=r"(r) : "f"(hi), "f"(lo)); return r;
}
__device__ __forceinline__ uint32_t hfma2_bf16(uint32_t a, uint32_t b, uint32_t c) {
    uint32_t r; asm("fma.rn.bf16x2 %0, %1, %2, %3;" : "=r"(r) : "r"(a), "r"(b), "r"(c)); return r;
}
__device__ __forceinline__ float bf_lo(uint32_t v) { return __uint_as_float(v << 16); }
__device__ __forceinline__ float bf_hi(uint32_t v) { return __uint_as_float(v & 0xFFFF0000u); }
__device__ __forceinline__ void unpack2(uint32_t v, float& lo, float& hi) {
    asm volatile("shl.b32 %0, %2, 16;\nand.b32 %1, %2, 0xffff0000;" : "=f"(lo), "=f"(hi) : "r"(v));
}
__device__ __forceinline__ float bf_round(float x) { return __bfloat162float(__float2bfloat16_rn(x)); }
__device__ __forceinline__ void stsm4(uint32_t addr, uint32_t r0, uint32_t r1, uint32_t r2, uint32_t r3) {
    asm volatile("stmatrix.sync.aligned.m8n8.x4.shared.b16 [%0], {%1, %2, %3, %4};" :: "r"(addr), "r"(r0), "r"(r1), "r"(r2), "r"(r3) : "memory");
}
__device__ __forceinline__ void stsm4t(uint32_t addr, uint32_t r0, uint32_t r1, uint32_t r2, uint32_t r3) {
    asm volatile("stmatrix.sync.aligned.m8n8.x4.trans.shared.b16 [%0], {%1, %2, %3, %4};" :: "r"(addr), "r"(r0), "r"(r1), "r"(r2), "r"(r3) : "memory");
}
__device__ __forceinline__ uint32_t movm(uint32_t a) { uint32_t d; asm volatile("movmatrix.sync.aligned.m8n8.trans.b16 %0, %1;" : "=r"(d) : "r"(a)); return d; }
__device__ __forceinline__ void ldsm4(uint32_t addr, uint32_t& r0, uint32_t& r1, uint32_t& r2, uint32_t& r3) {
    asm volatile("ldmatrix.sync.aligned.m8n8.x4.shared.b16 {%0, %1, %2, %3}, [%4];" : "=r"(r0), "=r"(r1), "=r"(r2), "=r"(r3) : "r"(addr) : "memory");
}
__device__ __forceinline__ void ldsm4t(uint32_t addr, uint32_t& r0, uint32_t& r1, uint32_t& r2, uint32_t& r3) {
    asm volatile("ldmatrix.sync.aligned.m8n8.x4.trans.shared.b16 {%0, %1, %2, %3}, [%4];" : "=r"(r0), "=r"(r1), "=r"(r2), "=r"(r3) : "r"(addr) : "memory");
}
__device__ __forceinline__ void mma16816(float (&c)[4], uint32_t a0, uint32_t a1, uint32_t a2, uint32_t a3, uint32_t b0, uint32_t b1) {
    asm("mma.sync.aligned.m16n8k16.row.col.f32.bf16.bf16.f32 {%0, %1, %2, %3}, {%4, %5, %6, %7}, {%8, %9}, {%0, %1, %2, %3};"
        : "+f"(c[0]), "+f"(c[1]), "+f"(c[2]), "+f"(c[3]) : "r"(a0), "r"(a1), "r"(a2), "r"(a3), "r"(b0), "r"(b1));
}
__device__ __forceinline__ float rsq(float x) { float r; asm("rsqrt.approx.ftz.f32 %0, %1;" : "=f"(r) : "f"(x)); return r; }
__device__ __forceinline__ float rcp(float x) { float r; asm("rcp.approx.ftz.f32 %0, %1;" : "=f"(r) : "f"(x)); return r; }
__device__ __forceinline__ float ex2(float x) { float r; asm("ex2.approx.ftz.f32 %0, %1;" : "=f"(r) : "f"(x)); return r; }
__device__ __forceinline__ float tanh_(float x) { float t; asm("tanh.approx.f32 %0, %1;" : "=f"(t) : "f"(x)); return t; }
__device__ __forceinline__ void block_end(uint32_t opaque, uint32_t id) { asm volatile("{\n.reg .pred p;\nsetp.eq.u32 p, %0, %1;\n@p trap;\n}" :: "r"(opaque), "r"(0xffffff00u + id)); }
__device__ __forceinline__ float silu_(float x) { return __fdividef(x, 1.f + __expf(-x)); }
__device__ __forceinline__ void st_pkt(void* p, uint32_t a, uint32_t b) {
    asm volatile("{\n.reg .b64 t;\nmov.b64 t, {%1, %2};\nst.relaxed.gpu.global.b64 [%0], t;\n}" :: "l"(p), "r"(a), "r"(b) : "memory");
}
__device__ __forceinline__ uint4 ld_pkt2(const void* p) {
    uint4 v; asm volatile("{\n.reg .b64 t, u;\nld.relaxed.gpu.global.v2.b64 {t, u}, [%4];\nmov.b64 {%0, %1}, t;\nmov.b64 {%2, %3}, u;\n}"
        : "=r"(v.x), "=r"(v.y), "=r"(v.z), "=r"(v.w) : "l"(p) : "memory"); return v;
}
__device__ __forceinline__ void st_pkt16(void* p, uint32_t a, uint32_t b, uint32_t c, uint32_t d) {
    asm volatile("{\n.reg .b64 t, u;\n.reg .b128 w;\nmov.b64 t, {%1, %2};\nmov.b64 u, {%3, %4};\nmov.b128 w, {t, u};\nst.relaxed.gpu.global.b128 [%0], w;\n}"
        :: "l"(p), "r"(a), "r"(b), "r"(c), "r"(d) : "memory");
}
__device__ __forceinline__ uint4 ld_pkt16(const void* p) {
    uint4 v; asm volatile("{\n.reg .b64 t, u;\n.reg .b128 w;\nld.relaxed.gpu.global.b128 w, [%4];\nmov.b128 {t, u}, w;\nmov.b64 {%0, %1}, t;\nmov.b64 {%2, %3}, u;\n}"
        : "=r"(v.x), "=r"(v.y), "=r"(v.z), "=r"(v.w) : "l"(p) : "memory"); return v;
}
#define SPIN_GUARD(n) do { if (++(n) > (1u << 22)) asm volatile("trap;"); } while (0)
__device__ __forceinline__ uint4 lds128(uint32_t a) { uint4 v; asm volatile("ld.shared.v4.u32 {%0, %1, %2, %3}, [%4];" : "=r"(v.x), "=r"(v.y), "=r"(v.z), "=r"(v.w) : "r"(a) : "memory"); return v; }
__device__ __forceinline__ void sts128(uint32_t a, uint32_t x, uint32_t y, uint32_t z, uint32_t w) { asm volatile("st.shared.v4.u32 [%0], {%1, %2, %3, %4};" :: "r"(a), "r"(x), "r"(y), "r"(z), "r"(w) : "memory"); }
__device__ __forceinline__ uint32_t lds32(uint32_t a) { uint32_t v; asm volatile("ld.shared.u32 %0, [%1];" : "=r"(v) : "r"(a) : "memory"); return v; }
__device__ __forceinline__ void sts32(uint32_t a, uint32_t v) { asm volatile("st.shared.u32 [%0], %1;" :: "r"(a), "r"(v) : "memory"); }
__device__ __forceinline__ bool elect_one() {
    uint32_t p; asm volatile("{\n.reg .pred q;\nelect.sync _|q, 0xffffffff;\nselp.u32 %0, 1, 0, q;\n}" : "=r"(p)); return p;
}
__device__ __forceinline__ void pause(uint32_t cycles) {
    uint32_t t0, t; asm volatile("mov.u32 %0, %%clock;" : "=r"(t0));
    do { __nanosleep(64); asm volatile("mov.u32 %0, %%clock;" : "=r"(t)); } while (t - t0 < cycles);
}
__device__ __forceinline__ void cluster_arrive() { asm volatile("barrier.cluster.arrive.relaxed.aligned;" ::: "memory"); }
__device__ __forceinline__ void cluster_wait() { asm volatile("barrier.cluster.wait.aligned;" ::: "memory"); }

__device__ __forceinline__ void wgmma_n128_z(float (&d)[64], uint64_t da, uint64_t db) {
    asm volatile("{\n.reg .pred p;\nsetp.ne.b32 p, 0, 0;\n"
        "wgmma.mma_async.sync.aligned.m64n128k16.f32.bf16.bf16 {"
        "%0, %1, %2, %3, %4, %5, %6, %7, %8, %9, %10, %11, %12, %13, %14, %15, "
        "%16, %17, %18, %19, %20, %21, %22, %23, %24, %25, %26, %27, %28, %29, %30, %31, "
        "%32, %33, %34, %35, %36, %37, %38, %39, %40, %41, %42, %43, %44, %45, %46, %47, "
        "%48, %49, %50, %51, %52, %53, %54, %55, %56, %57, %58, %59, %60, %61, %62, %63"
        "}, %64, %65, p, 1, 1, 0, 1;\n}\n"
        : "=f"(d[0]), "=f"(d[1]), "=f"(d[2]), "=f"(d[3]), "=f"(d[4]), "=f"(d[5]), "=f"(d[6]), "=f"(d[7]),
          "=f"(d[8]), "=f"(d[9]), "=f"(d[10]), "=f"(d[11]), "=f"(d[12]), "=f"(d[13]), "=f"(d[14]), "=f"(d[15]),
          "=f"(d[16]), "=f"(d[17]), "=f"(d[18]), "=f"(d[19]), "=f"(d[20]), "=f"(d[21]), "=f"(d[22]), "=f"(d[23]),
          "=f"(d[24]), "=f"(d[25]), "=f"(d[26]), "=f"(d[27]), "=f"(d[28]), "=f"(d[29]), "=f"(d[30]), "=f"(d[31]),
          "=f"(d[32]), "=f"(d[33]), "=f"(d[34]), "=f"(d[35]), "=f"(d[36]), "=f"(d[37]), "=f"(d[38]), "=f"(d[39]),
          "=f"(d[40]), "=f"(d[41]), "=f"(d[42]), "=f"(d[43]), "=f"(d[44]), "=f"(d[45]), "=f"(d[46]), "=f"(d[47]),
          "=f"(d[48]), "=f"(d[49]), "=f"(d[50]), "=f"(d[51]), "=f"(d[52]), "=f"(d[53]), "=f"(d[54]), "=f"(d[55]),
          "=f"(d[56]), "=f"(d[57]), "=f"(d[58]), "=f"(d[59]), "=f"(d[60]), "=f"(d[61]), "=f"(d[62]), "=f"(d[63])
        : "l"(da), "l"(db));
}
__device__ __forceinline__ void wgmma_n128(float (&d)[64], uint64_t da, uint64_t db) {
    asm volatile("{\n.reg .pred p;\nsetp.eq.b32 p, 0, 0;\n"
        "wgmma.mma_async.sync.aligned.m64n128k16.f32.bf16.bf16 {"
        "%0, %1, %2, %3, %4, %5, %6, %7, %8, %9, %10, %11, %12, %13, %14, %15, "
        "%16, %17, %18, %19, %20, %21, %22, %23, %24, %25, %26, %27, %28, %29, %30, %31, "
        "%32, %33, %34, %35, %36, %37, %38, %39, %40, %41, %42, %43, %44, %45, %46, %47, "
        "%48, %49, %50, %51, %52, %53, %54, %55, %56, %57, %58, %59, %60, %61, %62, %63"
        "}, %64, %65, p, 1, 1, 0, 1;\n}\n"
        : "+f"(d[0]), "+f"(d[1]), "+f"(d[2]), "+f"(d[3]), "+f"(d[4]), "+f"(d[5]), "+f"(d[6]), "+f"(d[7]),
          "+f"(d[8]), "+f"(d[9]), "+f"(d[10]), "+f"(d[11]), "+f"(d[12]), "+f"(d[13]), "+f"(d[14]), "+f"(d[15]),
          "+f"(d[16]), "+f"(d[17]), "+f"(d[18]), "+f"(d[19]), "+f"(d[20]), "+f"(d[21]), "+f"(d[22]), "+f"(d[23]),
          "+f"(d[24]), "+f"(d[25]), "+f"(d[26]), "+f"(d[27]), "+f"(d[28]), "+f"(d[29]), "+f"(d[30]), "+f"(d[31]),
          "+f"(d[32]), "+f"(d[33]), "+f"(d[34]), "+f"(d[35]), "+f"(d[36]), "+f"(d[37]), "+f"(d[38]), "+f"(d[39]),
          "+f"(d[40]), "+f"(d[41]), "+f"(d[42]), "+f"(d[43]), "+f"(d[44]), "+f"(d[45]), "+f"(d[46]), "+f"(d[47]),
          "+f"(d[48]), "+f"(d[49]), "+f"(d[50]), "+f"(d[51]), "+f"(d[52]), "+f"(d[53]), "+f"(d[54]), "+f"(d[55]),
          "+f"(d[56]), "+f"(d[57]), "+f"(d[58]), "+f"(d[59]), "+f"(d[60]), "+f"(d[61]), "+f"(d[62]), "+f"(d[63])
        : "l"(da), "l"(db));
}
__device__ __forceinline__ void wgmma_n176_z(float (&d)[88], uint64_t da, uint64_t db) {
    asm volatile("{\n.reg .pred p;\nsetp.ne.b32 p, 0, 0;\n"
        "wgmma.mma_async.sync.aligned.m64n176k16.f32.bf16.bf16 {"
        "%0, %1, %2, %3, %4, %5, %6, %7, %8, %9, %10, %11, %12, %13, %14, %15, "
        "%16, %17, %18, %19, %20, %21, %22, %23, %24, %25, %26, %27, %28, %29, %30, %31, "
        "%32, %33, %34, %35, %36, %37, %38, %39, %40, %41, %42, %43, %44, %45, %46, %47, "
        "%48, %49, %50, %51, %52, %53, %54, %55, %56, %57, %58, %59, %60, %61, %62, %63, "
        "%64, %65, %66, %67, %68, %69, %70, %71, %72, %73, %74, %75, %76, %77, %78, %79, "
        "%80, %81, %82, %83, %84, %85, %86, %87"
        "}, %88, %89, p, 1, 1, 0, 1;\n}\n"
        : "=f"(d[0]), "=f"(d[1]), "=f"(d[2]), "=f"(d[3]), "=f"(d[4]), "=f"(d[5]), "=f"(d[6]), "=f"(d[7]),
          "=f"(d[8]), "=f"(d[9]), "=f"(d[10]), "=f"(d[11]), "=f"(d[12]), "=f"(d[13]), "=f"(d[14]), "=f"(d[15]),
          "=f"(d[16]), "=f"(d[17]), "=f"(d[18]), "=f"(d[19]), "=f"(d[20]), "=f"(d[21]), "=f"(d[22]), "=f"(d[23]),
          "=f"(d[24]), "=f"(d[25]), "=f"(d[26]), "=f"(d[27]), "=f"(d[28]), "=f"(d[29]), "=f"(d[30]), "=f"(d[31]),
          "=f"(d[32]), "=f"(d[33]), "=f"(d[34]), "=f"(d[35]), "=f"(d[36]), "=f"(d[37]), "=f"(d[38]), "=f"(d[39]),
          "=f"(d[40]), "=f"(d[41]), "=f"(d[42]), "=f"(d[43]), "=f"(d[44]), "=f"(d[45]), "=f"(d[46]), "=f"(d[47]),
          "=f"(d[48]), "=f"(d[49]), "=f"(d[50]), "=f"(d[51]), "=f"(d[52]), "=f"(d[53]), "=f"(d[54]), "=f"(d[55]),
          "=f"(d[56]), "=f"(d[57]), "=f"(d[58]), "=f"(d[59]), "=f"(d[60]), "=f"(d[61]), "=f"(d[62]), "=f"(d[63]),
          "=f"(d[64]), "=f"(d[65]), "=f"(d[66]), "=f"(d[67]), "=f"(d[68]), "=f"(d[69]), "=f"(d[70]), "=f"(d[71]),
          "=f"(d[72]), "=f"(d[73]), "=f"(d[74]), "=f"(d[75]), "=f"(d[76]), "=f"(d[77]), "=f"(d[78]), "=f"(d[79]),
          "=f"(d[80]), "=f"(d[81]), "=f"(d[82]), "=f"(d[83]), "=f"(d[84]), "=f"(d[85]), "=f"(d[86]), "=f"(d[87])
        : "l"(da), "l"(db));
}
__device__ __forceinline__ void wgmma_n176(float (&d)[88], uint64_t da, uint64_t db) {
    asm volatile("{\n.reg .pred p;\nsetp.eq.b32 p, 0, 0;\n"
        "wgmma.mma_async.sync.aligned.m64n176k16.f32.bf16.bf16 {"
        "%0, %1, %2, %3, %4, %5, %6, %7, %8, %9, %10, %11, %12, %13, %14, %15, "
        "%16, %17, %18, %19, %20, %21, %22, %23, %24, %25, %26, %27, %28, %29, %30, %31, "
        "%32, %33, %34, %35, %36, %37, %38, %39, %40, %41, %42, %43, %44, %45, %46, %47, "
        "%48, %49, %50, %51, %52, %53, %54, %55, %56, %57, %58, %59, %60, %61, %62, %63, "
        "%64, %65, %66, %67, %68, %69, %70, %71, %72, %73, %74, %75, %76, %77, %78, %79, "
        "%80, %81, %82, %83, %84, %85, %86, %87"
        "}, %88, %89, p, 1, 1, 0, 1;\n}\n"
        : "+f"(d[0]), "+f"(d[1]), "+f"(d[2]), "+f"(d[3]), "+f"(d[4]), "+f"(d[5]), "+f"(d[6]), "+f"(d[7]),
          "+f"(d[8]), "+f"(d[9]), "+f"(d[10]), "+f"(d[11]), "+f"(d[12]), "+f"(d[13]), "+f"(d[14]), "+f"(d[15]),
          "+f"(d[16]), "+f"(d[17]), "+f"(d[18]), "+f"(d[19]), "+f"(d[20]), "+f"(d[21]), "+f"(d[22]), "+f"(d[23]),
          "+f"(d[24]), "+f"(d[25]), "+f"(d[26]), "+f"(d[27]), "+f"(d[28]), "+f"(d[29]), "+f"(d[30]), "+f"(d[31]),
          "+f"(d[32]), "+f"(d[33]), "+f"(d[34]), "+f"(d[35]), "+f"(d[36]), "+f"(d[37]), "+f"(d[38]), "+f"(d[39]),
          "+f"(d[40]), "+f"(d[41]), "+f"(d[42]), "+f"(d[43]), "+f"(d[44]), "+f"(d[45]), "+f"(d[46]), "+f"(d[47]),
          "+f"(d[48]), "+f"(d[49]), "+f"(d[50]), "+f"(d[51]), "+f"(d[52]), "+f"(d[53]), "+f"(d[54]), "+f"(d[55]),
          "+f"(d[56]), "+f"(d[57]), "+f"(d[58]), "+f"(d[59]), "+f"(d[60]), "+f"(d[61]), "+f"(d[62]), "+f"(d[63]),
          "+f"(d[64]), "+f"(d[65]), "+f"(d[66]), "+f"(d[67]), "+f"(d[68]), "+f"(d[69]), "+f"(d[70]), "+f"(d[71]),
          "+f"(d[72]), "+f"(d[73]), "+f"(d[74]), "+f"(d[75]), "+f"(d[76]), "+f"(d[77]), "+f"(d[78]), "+f"(d[79]),
          "+f"(d[80]), "+f"(d[81]), "+f"(d[82]), "+f"(d[83]), "+f"(d[84]), "+f"(d[85]), "+f"(d[86]), "+f"(d[87])
        : "l"(da), "l"(db));
}
__device__ __forceinline__ void wgmma_n256_z(float (&d)[128], uint64_t da, uint64_t db) {
    asm volatile("{\n.reg .pred p;\nsetp.ne.b32 p, 0, 0;\n"
        "wgmma.mma_async.sync.aligned.m64n256k16.f32.bf16.bf16 {"
        "%0, %1, %2, %3, %4, %5, %6, %7, %8, %9, %10, %11, %12, %13, %14, %15, "
        "%16, %17, %18, %19, %20, %21, %22, %23, %24, %25, %26, %27, %28, %29, %30, %31, "
        "%32, %33, %34, %35, %36, %37, %38, %39, %40, %41, %42, %43, %44, %45, %46, %47, "
        "%48, %49, %50, %51, %52, %53, %54, %55, %56, %57, %58, %59, %60, %61, %62, %63, "
        "%64, %65, %66, %67, %68, %69, %70, %71, %72, %73, %74, %75, %76, %77, %78, %79, "
        "%80, %81, %82, %83, %84, %85, %86, %87, %88, %89, %90, %91, %92, %93, %94, %95, "
        "%96, %97, %98, %99, %100, %101, %102, %103, %104, %105, %106, %107, %108, %109, %110, %111, "
        "%112, %113, %114, %115, %116, %117, %118, %119, %120, %121, %122, %123, %124, %125, %126, %127"
        "}, %128, %129, p, 1, 1, 0, 1;\n}\n"
        : "=f"(d[0]), "=f"(d[1]), "=f"(d[2]), "=f"(d[3]), "=f"(d[4]), "=f"(d[5]), "=f"(d[6]), "=f"(d[7]),
          "=f"(d[8]), "=f"(d[9]), "=f"(d[10]), "=f"(d[11]), "=f"(d[12]), "=f"(d[13]), "=f"(d[14]), "=f"(d[15]),
          "=f"(d[16]), "=f"(d[17]), "=f"(d[18]), "=f"(d[19]), "=f"(d[20]), "=f"(d[21]), "=f"(d[22]), "=f"(d[23]),
          "=f"(d[24]), "=f"(d[25]), "=f"(d[26]), "=f"(d[27]), "=f"(d[28]), "=f"(d[29]), "=f"(d[30]), "=f"(d[31]),
          "=f"(d[32]), "=f"(d[33]), "=f"(d[34]), "=f"(d[35]), "=f"(d[36]), "=f"(d[37]), "=f"(d[38]), "=f"(d[39]),
          "=f"(d[40]), "=f"(d[41]), "=f"(d[42]), "=f"(d[43]), "=f"(d[44]), "=f"(d[45]), "=f"(d[46]), "=f"(d[47]),
          "=f"(d[48]), "=f"(d[49]), "=f"(d[50]), "=f"(d[51]), "=f"(d[52]), "=f"(d[53]), "=f"(d[54]), "=f"(d[55]),
          "=f"(d[56]), "=f"(d[57]), "=f"(d[58]), "=f"(d[59]), "=f"(d[60]), "=f"(d[61]), "=f"(d[62]), "=f"(d[63]),
          "=f"(d[64]), "=f"(d[65]), "=f"(d[66]), "=f"(d[67]), "=f"(d[68]), "=f"(d[69]), "=f"(d[70]), "=f"(d[71]),
          "=f"(d[72]), "=f"(d[73]), "=f"(d[74]), "=f"(d[75]), "=f"(d[76]), "=f"(d[77]), "=f"(d[78]), "=f"(d[79]),
          "=f"(d[80]), "=f"(d[81]), "=f"(d[82]), "=f"(d[83]), "=f"(d[84]), "=f"(d[85]), "=f"(d[86]), "=f"(d[87]),
          "=f"(d[88]), "=f"(d[89]), "=f"(d[90]), "=f"(d[91]), "=f"(d[92]), "=f"(d[93]), "=f"(d[94]), "=f"(d[95]),
          "=f"(d[96]), "=f"(d[97]), "=f"(d[98]), "=f"(d[99]), "=f"(d[100]), "=f"(d[101]), "=f"(d[102]), "=f"(d[103]),
          "=f"(d[104]), "=f"(d[105]), "=f"(d[106]), "=f"(d[107]), "=f"(d[108]), "=f"(d[109]), "=f"(d[110]), "=f"(d[111]),
          "=f"(d[112]), "=f"(d[113]), "=f"(d[114]), "=f"(d[115]), "=f"(d[116]), "=f"(d[117]), "=f"(d[118]), "=f"(d[119]),
          "=f"(d[120]), "=f"(d[121]), "=f"(d[122]), "=f"(d[123]), "=f"(d[124]), "=f"(d[125]), "=f"(d[126]), "=f"(d[127])
        : "l"(da), "l"(db));
}
__device__ __forceinline__ void wgmma_n256(float (&d)[128], uint64_t da, uint64_t db) {
    asm volatile("{\n.reg .pred p;\nsetp.eq.b32 p, 0, 0;\n"
        "wgmma.mma_async.sync.aligned.m64n256k16.f32.bf16.bf16 {"
        "%0, %1, %2, %3, %4, %5, %6, %7, %8, %9, %10, %11, %12, %13, %14, %15, "
        "%16, %17, %18, %19, %20, %21, %22, %23, %24, %25, %26, %27, %28, %29, %30, %31, "
        "%32, %33, %34, %35, %36, %37, %38, %39, %40, %41, %42, %43, %44, %45, %46, %47, "
        "%48, %49, %50, %51, %52, %53, %54, %55, %56, %57, %58, %59, %60, %61, %62, %63, "
        "%64, %65, %66, %67, %68, %69, %70, %71, %72, %73, %74, %75, %76, %77, %78, %79, "
        "%80, %81, %82, %83, %84, %85, %86, %87, %88, %89, %90, %91, %92, %93, %94, %95, "
        "%96, %97, %98, %99, %100, %101, %102, %103, %104, %105, %106, %107, %108, %109, %110, %111, "
        "%112, %113, %114, %115, %116, %117, %118, %119, %120, %121, %122, %123, %124, %125, %126, %127"
        "}, %128, %129, p, 1, 1, 0, 1;\n}\n"
        : "+f"(d[0]), "+f"(d[1]), "+f"(d[2]), "+f"(d[3]), "+f"(d[4]), "+f"(d[5]), "+f"(d[6]), "+f"(d[7]),
          "+f"(d[8]), "+f"(d[9]), "+f"(d[10]), "+f"(d[11]), "+f"(d[12]), "+f"(d[13]), "+f"(d[14]), "+f"(d[15]),
          "+f"(d[16]), "+f"(d[17]), "+f"(d[18]), "+f"(d[19]), "+f"(d[20]), "+f"(d[21]), "+f"(d[22]), "+f"(d[23]),
          "+f"(d[24]), "+f"(d[25]), "+f"(d[26]), "+f"(d[27]), "+f"(d[28]), "+f"(d[29]), "+f"(d[30]), "+f"(d[31]),
          "+f"(d[32]), "+f"(d[33]), "+f"(d[34]), "+f"(d[35]), "+f"(d[36]), "+f"(d[37]), "+f"(d[38]), "+f"(d[39]),
          "+f"(d[40]), "+f"(d[41]), "+f"(d[42]), "+f"(d[43]), "+f"(d[44]), "+f"(d[45]), "+f"(d[46]), "+f"(d[47]),
          "+f"(d[48]), "+f"(d[49]), "+f"(d[50]), "+f"(d[51]), "+f"(d[52]), "+f"(d[53]), "+f"(d[54]), "+f"(d[55]),
          "+f"(d[56]), "+f"(d[57]), "+f"(d[58]), "+f"(d[59]), "+f"(d[60]), "+f"(d[61]), "+f"(d[62]), "+f"(d[63]),
          "+f"(d[64]), "+f"(d[65]), "+f"(d[66]), "+f"(d[67]), "+f"(d[68]), "+f"(d[69]), "+f"(d[70]), "+f"(d[71]),
          "+f"(d[72]), "+f"(d[73]), "+f"(d[74]), "+f"(d[75]), "+f"(d[76]), "+f"(d[77]), "+f"(d[78]), "+f"(d[79]),
          "+f"(d[80]), "+f"(d[81]), "+f"(d[82]), "+f"(d[83]), "+f"(d[84]), "+f"(d[85]), "+f"(d[86]), "+f"(d[87]),
          "+f"(d[88]), "+f"(d[89]), "+f"(d[90]), "+f"(d[91]), "+f"(d[92]), "+f"(d[93]), "+f"(d[94]), "+f"(d[95]),
          "+f"(d[96]), "+f"(d[97]), "+f"(d[98]), "+f"(d[99]), "+f"(d[100]), "+f"(d[101]), "+f"(d[102]), "+f"(d[103]),
          "+f"(d[104]), "+f"(d[105]), "+f"(d[106]), "+f"(d[107]), "+f"(d[108]), "+f"(d[109]), "+f"(d[110]), "+f"(d[111]),
          "+f"(d[112]), "+f"(d[113]), "+f"(d[114]), "+f"(d[115]), "+f"(d[116]), "+f"(d[117]), "+f"(d[118]), "+f"(d[119]),
          "+f"(d[120]), "+f"(d[121]), "+f"(d[122]), "+f"(d[123]), "+f"(d[124]), "+f"(d[125]), "+f"(d[126]), "+f"(d[127])
        : "l"(da), "l"(db));
}

struct Idx {
    uint32_t lane, warp, w4, q4, g8, prow, pan;
    __device__ __forceinline__ Idx() {
        uint32_t t; asm volatile("mov.u32 %0, %%tid.x;" : "=r"(t));
        lane = t & 31; warp = t >> 5; w4 = warp & 3; q4 = lane & 3; g8 = lane >> 2;
        prow = w4 * 16 + ((lane >> 3) & 1) * 8 + (lane & 7);
        pan = prow * 128 + (((lane >> 4) ^ (lane & 7)) << 4);
    }
};
#define IDX() const Idx ix; const uint32_t lane = ix.lane, warp = ix.warp, w4 = ix.w4, q4 = ix.q4, g8 = ix.g8, prow = ix.prow, pan_addr = ix.pan; \
    (void)lane; (void)warp; (void)w4; (void)q4; (void)g8; (void)prow; (void)pan_addr;

__device__ __forceinline__ int kof(int t, int sh, int j) {
    const int p = t >> (sh - 1), pn = p < 2 ? p : p >= 9, q = p - 2 - 7 * pn;
    return ((p < 2 ? j : q + (q >= j)) << 7) + (pn << 6) + ((t & (sh - 1)) << 5);
}
__device__ __forceinline__ uint32_t fidx(uint32_t m, uint32_t w, uint32_t pn) {
    return m * 32 + w * 16 + pn;
}
constexpr int HC0 = 8 * 48, HC3 = HC0 + 3072;
__device__ __forceinline__ int hcol(int p, int j) { return HC0 + p * 1024 + j * 128; }
struct Ring {
    uint32_t slot, par;
    __device__ __forceinline__ void next() { if (++slot == NSLOT) { slot = 0; par ^= 1; } }
    __device__ __forceinline__ void skip(uint32_t n) { slot += n; if (slot >= NSLOT) { slot -= NSLOT; par ^= 1; } }
};
__device__ __forceinline__ uint32_t BAR_FULL(uint32_t sb, uint32_t s) { return sb + OFF_BAR + 8 * s; }
constexpr uint32_t AF_REL = 48;
__device__ __forceinline__ uint32_t BAR_EMPTY(uint32_t sb, uint32_t s) { return sb + OFF_BAR + 96 + 8 * s; }
__device__ __forceinline__ uint32_t BAR_SFULL(uint32_t sb, uint32_t i) { return sb + OFF_BAR + 152 + 8 * i; }
__device__ __forceinline__ uint32_t BAR_SREADY(uint32_t sb, uint32_t i) { return sb + OFF_BAR + 184 + 8 * i; }
__device__ __forceinline__ uint32_t BAR_ONE(uint32_t sb, uint32_t i) { return sb + OFF_BAR + 216 + 8 * i; }
enum { EV_WIN, EV_WIN1, EV_WIN2, EV_WIN3, EV_P0, EV_GA, EV_GB, EV_LN2, EV_LAG1, EV_LAG2, EV_LAG3, EV_LAG4, EV_LAG5, EV_KV, EV_PAR, EV_AGO, EV_AGO1, EV_AGO2, EV_FGO, EV_FGO1, EV_FGO2, EV_H0, EV_H1, EV_H2, EV_H3, EV_TAIL, EV_COUNT = EV_TAIL + 8 };
constexpr int NB_TAIL = 4;

struct Rel {
    uint32_t base; bool sig;
    __device__ __forceinline__ Rel(uint32_t sb, uint32_t tw) {
        uint32_t a; asm("mapa.shared::cluster.u32 %0, %1, %2;" : "=r"(a) : "r"(BAR_EMPTY(sb, 0)), "r"((tw >> 5) & 1));
        base = __shfl_sync(0xffffffffu, a, 0); sig = (tw & ~32u) == 0;
    }
    __device__ __forceinline__ void operator()(uint32_t slot) const {
        if (sig) asm volatile("mbarrier.arrive.shared::cluster.b64 _, [%0];" :: "r"(base + 8 * slot) : "memory");
    }
};
struct LnRow { float rs0, nm0, rs1, nm1; };
struct Pipe {
    Rel rel; uint32_t p1, p2;
    __device__ __forceinline__ Pipe(uint32_t sb, uint32_t tw, uint32_t first) : rel(sb, tw), p1(first), p2(NSLOT) {}
    template <bool TWO> __device__ __forceinline__ void acquire(uint32_t sb, uint32_t af, const Ring& r) {
        const uint32_t b0 = BAR_FULL(sb, r.slot), b1 = b0 + af;
        const bool ready = TWO ? mbar_test2(b0, b1, r.par) : mbar_test(b0, r.par);
        wg_wait<1>();
        rel(p2);
        if (!ready) { if (TWO) mbar_wait2(b0, b1, r.par); else mbar_wait(b0, r.par); }
    }
    __device__ __forceinline__ void issued(uint32_t slot) { p2 = p1; p1 = slot; }
    __device__ __forceinline__ void drain1() { wg_wait<1>(); rel(p2); p2 = NSLOT; }
    __device__ __forceinline__ void drain0() { wg_wait<0>(); rel(p1); p1 = NSLOT; }
    template <bool TWO, class Step> __device__ __forceinline__ void hold(int LG, uint32_t sb, uint32_t af, Ring& r, uint32_t lag_bar, Step step) {
        Ring q = r;
#pragma unroll 1
        for (int i = 0; i < LG; ++i) { if (TWO) mbar_wait2(BAR_FULL(sb, q.slot), BAR_FULL(sb, q.slot) + af, q.par); else mbar_wait(BAR_FULL(sb, q.slot), q.par); q.next(); }
        mbar_wait(lag_bar, 0);
#pragma unroll 1
        do {
            step(r.slot);
            wg_wait<2>(); rel(p2); p2 = p1; p1 = r.slot;
            if (++r.slot == NSLOT) r.slot = 0;
        } while (r.slot != q.slot);
        r.par = q.par;
    }
};
template <bool TWO, bool FIRST, int NA, int NB>
__device__ __forceinline__ void step32(float (&aa)[NA], float (&ab)[NB], uint32_t sb, uint32_t wg, uint32_t slot, int own) {
    const uint32_t st = d16(sb) + slot * (SLOT >> 4);
    const uint32_t alo = own >= 0 ? d16(sb) + OFF_STG / 16 + wg * 1024 + (own >> 1) * 512 + (own & 1) * 4 : st + wg * 256;
    const uint32_t ahi = own >= 0 ? (1024 >> 4) | (1u << 30) : (512 >> 4) | (2u << 30);
    wg_fence();
#pragma unroll
    for (int k = 0; k < 2; ++k) {
        const uint64_t da = ((uint64_t)ahi << 32) | (alo + k * 2 + 0x10000);
        if constexpr (NA == 88) {
            const uint64_t d0 = mk_desc(st, 8192 + k * 2048, 8192, 1024, 1), d1 = mk_desc(st, 12288 + k * 2048, 8192, 1024, 1);
            if (FIRST && k == 0) { wgmma_n176_z(aa, da, d0); wgmma_n176_z(ab, da, d1); }
            else { wgmma_n176(aa, da, d0); wgmma_n176(ab, da, d1); }
        } else {
            const uint64_t d0 = mk_desc(st, 8192 + k * 2048, 4096, 1024, 1), d1 = mk_desc(st, 24576 + k * 2048, 4096, 1024, 1);
            if (FIRST && k == 0) { wgmma_n256_z(aa, da, d0); if constexpr (TWO) wgmma_n128_z(ab, da, d1); }
            else { wgmma_n256(aa, da, d0); if constexpr (TWO) wgmma_n128(ab, da, d1); }
        }
    }
    wg_commit();
}
template <bool TWO, int LG, int NA, int NB, class Mid, class Tail>
__device__ __forceinline__ void mainloop32(float (&aa)[NA], float (&ab)[NB], uint32_t sb, uint32_t wg, uint32_t tw, Ring& r, uint32_t lag_ev, int g0, Mid mid, Tail tail) {
    step32<TWO, true>(aa, ab, sb, wg, r.slot, TWO ? 0 : -1);
    TS(g0, 0);
    Pipe pp(sb, tw, r.slot);
    r.next();
    const int end = wg ? 32 : 32 - LG;
#pragma unroll 1
    for (int it = 1; it < end; ++it) {
        pp.acquire<TWO>(sb, wg ? 0 : AF_REL, r);
        step32<TWO, false>(aa, ab, sb, wg, r.slot, TWO && it < 4 ? it : -1);
        pp.issued(r.slot);
        TS(g0 + it, 0);
        r.next();
        mid(it);
    }
    if (wg == 0) { pp.drain1(); pp.drain0(); pp.hold<TWO>(LG, sb, AF_REL, r, BAR_ONE(sb, lag_ev), [&](uint32_t slot) { step32<TWO, false>(aa, ab, sb, 0, slot, -1); }); }
    if (wg == 1 && tw == 0) mbar_arrive(BAR_ONE(sb, lag_ev));
    pp.drain1();
    tail();
    pp.drain0();
    TS(g0 + 31, 1);
}
template <bool FIRST>
__device__ __forceinline__ void step64(float (&acc)[64], uint32_t sb, uint32_t wg, uint32_t slot, int own) {
    const uint32_t sbb = d16(sb) + slot * (SLOT >> 4), sa = own >= 0 ? d16(sb) + OFF_STG / 16 + wg * 1024 + own * 512 : sbb + wg * 512;
    wg_fence();
#pragma unroll
    for (int k = 0; k < 4; ++k) {
        const uint64_t da = mk_desc(sa, k * 32, 16, 1024, 1), db = mk_desc(sbb, 16384 + k * 2048, 8192, 1024, 1);
        if (FIRST && k == 0) wgmma_n128_z(acc, da, db); else wgmma_n128(acc, da, db);
    }
    wg_commit();
}
template <class Put, class Mid, class Tail>
__device__ __forceinline__ void mainloop64(float (&acc)[64], bool wo, uint32_t sb, uint32_t wg, uint32_t tw, Ring& r, Put put, Mid mid, Tail tail) {
    const int g0 = wo ? 32 : 144, nst = wo ? 16 : 56, lg = wo ? LAGW : LAGD; (void)g0;
    const uint32_t lag_bar = BAR_ONE(sb, wo ? EV_LAG4 : EV_LAG5), af = wo && !wg ? AF_REL : 0;
    if (!wo) CS(28);
    step64<true>(acc, sb, wg, r.slot, wo ? 0 : -1);
    if (!wo) CS(29);
    TS(g0, 0);
    Pipe pp(sb, tw, r.slot);
    r.next();
    int it = 1;
    auto run = [&](int end, int own, bool with_put) {
#pragma unroll 1
        do {
            pp.acquire<true>(sb, af, r);
            step64<false>(acc, sb, wg, r.slot, own);
            pp.issued(r.slot);
            TS(g0 + it, 0);
            if (wo && it == 2) CS(9);
            r.next();
            if (with_put && it == (wg ? PUTD1 : PUTD0)) put();
        } while (++it < end);
    };
    const int end = wg ? nst : nst - lg;
    run(wo ? 2 : wg ? MIDD : end, wo ? 1 : -1, true);
    mid();
    if (wo) { pp.drain1(); pp.drain0(); TS(g0 + 1, 1); }
    if (it < end) run(end, -1, false);
    if (wg == 0) { pp.drain1(); pp.drain0(); pp.hold<true>(lg, sb, af, r, lag_bar, [&](uint32_t slot) { step64<false>(acc, sb, 0, slot, -1); }); }
    if (wg == 1 && tw == 0) mbar_arrive(lag_bar);
    pp.drain1();
    tail();
    pp.drain0();
    TS(g0 + nst - 1, 1);
}

struct RowAcc {
    float sm[4] = {0.f, 0.f, 0.f, 0.f}, sq[4] = {0.f, 0.f, 0.f, 0.f};
    __device__ __forceinline__ void add(int e, float x) { sm[e & 3] += x; sq[e & 3] = fmaf(x, x, sq[e & 3]); }
    __device__ __forceinline__ void publish(uint4* dst, uint32_t q4, uint32_t ep) const {
        const float s0 = sm[0] + sm[1], s1 = sm[2] + sm[3], q0 = sq[0] + sq[1], q1 = sq[2] + sq[3];
        const bool od = q4 & 1;
        float sv = (od ? s1 : s0) + __shfl_xor_sync(0xffffffffu, od ? s0 : s1, 1), qv = (od ? q1 : q0) + __shfl_xor_sync(0xffffffffu, od ? q0 : q1, 1);
        sv += __shfl_xor_sync(0xffffffffu, sv, 2); qv += __shfl_xor_sync(0xffffffffu, qv, 2);
        st_pkt16(dst + (q4 & 1) * 8, 0, __float_as_uint(sv), __float_as_uint(qv), ep);
    }
};
__device__ __forceinline__ LnRow merge_stats(const uint4* src, uint32_t q4, uint32_t ep, uint32_t sb) {
    uint4 t[4];
    uint32_t n = 0;
    while (true) {
#pragma unroll
        for (int i = 0; i < 4; ++i) t[i] = ld_pkt16(src + (q4 * 2 + (i >> 1)) * 512 + (i & 1) * 8);
        const bool ok_ = __all_sync(0xffffffffu, t[0].w == ep && t[1].w == ep && t[2].w == ep && t[3].w == ep);
        if (n < 4) CS(14 + n);
        if (ok_) break;
        SPIN_GUARD(n);
    }
    float v[4];
#pragma unroll
    for (int h = 0; h < 2; ++h) { v[h] = __uint_as_float(t[h].y) + __uint_as_float(t[2 + h].y); v[2 + h] = __uint_as_float(t[h].z) + __uint_as_float(t[2 + h].z); }
#pragma unroll
    for (int o = 1; o < 4; o <<= 1)
#pragma unroll
        for (int i = 0; i < 4; ++i) v[i] += __shfl_xor_sync(0xffffffffu, v[i], o);
    const float m0 = v[0] * (1.f / D_), m1 = v[1] * (1.f / D_);
    const float r0 = rsq(fmaxf(fmaf(-m0, m0, v[2] * (1.f / D_)), 0.f) + 1e-5f), r1 = rsq(fmaxf(fmaf(-m1, m1, v[3] * (1.f / D_)), 0.f) + 1e-5f);
    return LnRow{r0, -m0 * r0, r1, -m1 * r1};
}
struct Stg {
    uint32_t b, par;
    __device__ __forceinline__ uint32_t acquire2(uint32_t sb, uint32_t wg) {
        mbar_wait2(BAR_SREADY(sb, wg * 2), BAR_SREADY(sb, wg * 2 + 1), par);
        par ^= 1;
        return sb + OFF_STG + wg * 16384;
    }
    __device__ __forceinline__ void publish(uint32_t sb, uint32_t wg, uint32_t lane) {
        fence_async_smem();
        __syncwarp();
        if (lane == 0) mbar_arrive(BAR_SFULL(sb, wg * 2 + b));
        b ^= 1;
    }
};

struct LnPar {
    uint4 p[8];
    __device__ __forceinline__ void load(uint32_t sb, uint32_t q4) {
#pragma unroll
        for (int i = 0; i < 8; ++i) p[i] = lds128(sb + OFF_PAR + i * 64 + q4 * 16);
    }
};
__device__ __forceinline__ void ln_norm(uint32_t (&xn)[32], const float (&x)[64], const LnRow& n) {
#pragma unroll
    for (int e = 0; e < 32; ++e) {
        const float rs = (e & 1) ? n.rs1 : n.rs0, nm = (e & 1) ? n.nm1 : n.nm0;
        xn[e] = pack2(fmaf(x[2 * e], rs, nm), fmaf(x[2 * e + 1], rs, nm));
    }
}
__device__ __forceinline__ void ln_emit(const uint32_t (&xr)[32], const LnPar& lp, uint32_t sb, uint32_t wg, const Idx& ix) {
#pragma unroll
    for (int i = 0; i < 8; ++i)
        stsm4(sb + OFF_STG + wg * 16384 + (i >> 2) * 8192 + (ix.pan ^ ((i & 3) << 5)), hfma2_bf16(xr[4 * i], lp.p[i].z, lp.p[i].x), hfma2_bf16(xr[4 * i + 1], lp.p[i].z, lp.p[i].x),
              hfma2_bf16(xr[4 * i + 2], lp.p[i].w, lp.p[i].y), hfma2_bf16(xr[4 * i + 3], lp.p[i].w, lp.p[i].y));
    fence_async_smem();
    __syncwarp();
    if (ix.lane < 2) mbar_arrive(BAR_SFULL(sb, wg * 2 + ix.lane));
    bar_sync(1 + wg, 128);
}
__device__ __forceinline__ void load_slab(uint32_t (&xr)[32], uint32_t buf) {
    IDX();
#pragma unroll
    for (int i = 0; i < 8; ++i) ldsm4(buf + (i >> 2) * 8192 + (pan_addr ^ ((i & 3) << 5)), xr[4 * i], xr[4 * i + 1], xr[4 * i + 2], xr[4 * i + 3]);
}
__device__ __forceinline__ void unpack_slab(float (&x)[64], const uint32_t (&xr)[32]) {
#pragma unroll
    for (int i = 0; i < 32; ++i) unpack2(xr[i], x[2 * i], x[2 * i + 1]);
}
__device__ __forceinline__ void store_slab(const float (&x)[64], uint32_t buf, uint32_t pitch, uint32_t pan, int i0, int i1) {
#pragma unroll
    for (int i = i0; i < i1; ++i)
        stsm4(buf + (i >> 2) * pitch + (pan ^ ((i & 3) << 5)), pack2(x[8 * i], x[8 * i + 1]), pack2(x[8 * i + 2], x[8 * i + 3]), pack2(x[8 * i + 4], x[8 * i + 5]), pack2(x[8 * i + 6], x[8 * i + 7]));
}
template <int NP, class Done>
__device__ __forceinline__ void fetch_halo(uint4* src, bool first, uint32_t dst, Done done) {
    uint4 hv[4 * NP];
    uint32_t n = 0;
    while (true) {
        bool ok = true;
#pragma unroll
        for (int i = 0; i < 4 * NP; ++i) { hv[i] = first ? make_uint4(0, 0, 0, 0) : ld_pkt16(src + (i >> 2) * 256 + (i & 3) * 32); ok = ok && hv[i].x != 0; }
        if (first || __all_sync(0xffffffffu, ok)) break;
        SPIN_GUARD(n);
    }
#pragma unroll
    for (int i = 0; i < 4 * NP; ++i) stsm4(dst + (i >> 2) * 4096 + (i & 3) * 512, hv[i].x, hv[i].y, hv[i].z, hv[i].w);
    done();
    if (!first) {
#pragma unroll
        for (int i = 0; i < 4 * NP; ++i) src[(i >> 2) * 256 + (i & 3) * 32] = make_uint4(0, 0, 0, 0);
    }
}

template <int N, class G, class U>
__device__ __forceinline__ void glu(uint32_t (&h)[N], G g, U u) {
#pragma unroll
    for (int i = 0; i < N; ++i) h[i] = pack2(fmaf(tanh_(g(2 * i)), u(2 * i), u(2 * i)), fmaf(tanh_(g(2 * i + 1)), u(2 * i + 1), u(2 * i + 1)));
}
__device__ __forceinline__ void put_h(const uint32_t (&h)[32], uint32_t sb, uint32_t wg, Stg& stg) {
    IDX();
    const uint32_t buf = stg.acquire2(sb, wg);
#pragma unroll
    for (int k = 0; k < 8; ++k) stsm4(buf + (k >> 2) * 8192 + (pan_addr ^ ((k & 3) << 5)), h[4 * k], h[4 * k + 1], h[4 * k + 2], h[4 * k + 3]);
    fence_async_smem();
    __syncwarp();
    if (lane < 2) mbar_arrive(BAR_SFULL(sb, wg * 2 + lane));
}

template <int NP, bool PREV>
__device__ __forceinline__ void passes128(uint32_t (&hp)[32], uint32_t sb, uint32_t wg, uint32_t tw, Ring& r, Stg& stg) {
#pragma unroll 1
    for (int p = 0; p < NP; ++p) {
        float b256[128], none[1];
        const int put_at = !PREV && p == 0 ? -1 : wg ? PUT1 : PUT0;
        mainloop32<false, LAGS>(b256, none, sb, wg, tw, r, EV_LAG2 + p, 80 + 32 * (p & 1), [&](int it) { if (it == put_at) put_h(hp, sb, wg, stg); },
                                [&] { if (PREV || p < NP - 1) mbar_wait(BAR_FULL(sb, r.slot), r.par); });
        if (threadIdx.x == 0) { TL(29 + 2 * p); TC(114 + 2 * p); }
        if (threadIdx.x == 128) TL(53 + 2 * (p & 1));
        CS(24 + 2 * (p & 1));
        glu(hp, [&](int i) { return b256[i + (i & 32)]; }, [&](int i) { return b256[i + (i & 32) + 32]; });
        if (threadIdx.x == 0) { TL(30 + 2 * p); TC(115 + 2 * p); }
        if (threadIdx.x == 128) TL(54 + 2 * (p & 1));
        CS(25 + 2 * (p & 1));
    }
}

__global__ void __launch_bounds__(384, 1)
fused_block_kernel(const __grid_constant__ Ptrs pt, const __grid_constant__ Maps mp) {
    uint32_t* const g_flags = pt.mail->flags;
    uint2* const g_mod = pt.mail->mod;
    uint4* const g_st1 = pt.mail->st1;
    uint32_t* const g_par2 = pt.mail->par2;
    uint4* const g_halo = pt.mail->halo;
    const __nv_bfloat16* __restrict__ cvec = pt.c;
    if (threadIdx.x == 224) { prefetch_map(&mp.wm8); prefetch_map(&mp.x); }
    extern __shared__ __align__(1024) uint8_t smem[];
    const uint32_t sb = smem_u32(smem);
    const uint32_t tid = threadIdx.x, tw = tid & 127, lane = tid & 31;
    const uint32_t warp = __shfl_sync(0xffffffffu, tid >> 5, 0), wg = warp >> 2;
    uint32_t rank; asm("mov.u32 %0, %%cluster_ctarank;" : "=r"(rank));
    rank = __shfl_sync(0xffffffffu, rank, 0);
    uint32_t ep;
    uint32_t smid; asm volatile("mov.u32 %0, %%smid;" : "=r"(smid));
    const int c = __shfl_sync(0xffffffffu, smid >> 1, 0);
    const int c7 = ((c - 32) * 37) >> 8;
    int grp = c < 32 ? c & 7 : c < 60 ? c - 31 - 7 * c7 : c < 62 ? -1 : 0;
    const int j = c < 32 ? c >> 3 : c < 60 ? 4 + c7 : c < 62 ? (c - 60) * 2 + rank : c - 58;
    const bool aux = grp < 0;
    const int m = grp * 2 + rank;
    uint4* const g_st2 = g_halo + (m > 0 ? (m - 1) * 8 * 512 : 128);

    bool cluster_arrive_early = false;
    if (wg < 2) {
      if (!KDEBUG) cluster_arrive();
      ep = flag_get(g_flags + FL_DONE);
      uint16_t cw[8];
      {
          const __nv_bfloat16* cp = cvec + ((tw >> 5) * 32 + (tw & 3) * 2) * 8 + (lane >> 2);
#pragma unroll
          for (int i = 0; i < 8; ++i) asm volatile("ld.global.nc.u16 %0, [%1];" : "=h"(cw[i]) : "l"(cp + (i >> 1) * 64 + (i & 1) * 8));
      }
      asm volatile("setmaxnreg.inc.sync.aligned.u32 224;");
      if (tid == 0) TL(58);
      if (KDEBUG) cluster_arrive();
      Ring r{0, 0};
      Stg stg{0, 0};
      if (aux) {
        if (wg == 0) {
            const uint4 cv = *(const uint4*)(cvec + tw * 8);
            sts128(sb + OFF_STG + (tw >> 3) * 1024 + (tw & 7) * 16, pack2(silu_(bf_lo(cv.x)), silu_(bf_hi(cv.x))), pack2(silu_(bf_lo(cv.y)), silu_(bf_hi(cv.y))),
                   pack2(silu_(bf_lo(cv.z)), silu_(bf_hi(cv.z))), pack2(silu_(bf_lo(cv.w)), silu_(bf_hi(cv.w))));
            fence_async_smem();
        }
        cluster_wait();
        ep = __shfl_sync(0xffffffffu, ep, 0) / NCTA + 1;
        if (wg == 0) {
            bar_sync(1, 128);
#pragma unroll 1
            for (int p = 0; p < 4; ++p) {
                float acc[128];
#pragma unroll
                for (int i = 0; i < 128; ++i) acc[i] = 0.f;
                uint32_t prev = 0;
#pragma unroll 1
                for (int kc = 0; kc < 16; ++kc) {
                    mbar_wait(BAR_FULL(sb, r.slot), r.par);
                    wg_fence();
#pragma unroll
                    for (int k = 0; k < 4; ++k)
                        wgmma_n256(acc, mk_desc(d16(sb) + kc * 64, OFF_STG + k * 32, 16, 0, 1), mk_desc(d16(sb) + r.slot * (SLOT >> 4), k * 2048, 8192, 1024, 1));
                    wg_commit();
                    wg_wait<1>();
                    if (kc > 0 && tw < 4) mbar_arrive(BAR_EMPTY(sb, prev));
                    prev = r.slot;
                    r.next();
                }
                wg_wait<0>();
                if (tw < 4) mbar_arrive(BAR_EMPTY(sb, prev));
                if (tw < 4) {
#pragma unroll
                    for (int jn = 0; jn < 32; ++jn) sts32(sb + OFF_TAB + (jn * 4 + tw) * 4, pack2(acc[jn * 4], acc[jn * 4 + 1]));
                }
                bar_sync(1, 128);
                const int vec = 2 + p, blk = p * 4 + j;
                const uint32_t val = lds32(sb + OFF_TAB + tw * 4);
                if (vec == 2 || vec == 5) st_pkt(g_mod + (8 + blk) * 128 + tw, val, ep);
                else {
                    const float one = vec == 4 ? 1.f : 0.f;
                    g_par2[((blk & 3) * 16 + (tw >> 3)) * 16 + (tw & 3) * 4 + (vec - 3) * 2 + ((tw >> 2) & 1)] =
                        pack2(0.5f * bf_round(one + bf_lo(val)), 0.5f * bf_round(one + bf_hi(val)));
                }
                bar_sync(1, 128);
                if (tw == 0) {
                    if (vec == 3 || vec == 4) asm volatile("red.release.gpu.global.add.u32 [%0], 1;" :: "l"(&g_flags[FL_LN2]) : "memory");
                    TL(1 + p);
                }
            }
            if (lane < 2) mbar_arrive_cta(BAR_ONE(sb, EV_P0), lane);
        }
        r = Ring{64 % NSLOT, (64 / NSLOT) & 1};
        mbar_wait(BAR_ONE(sb, EV_P0), 0);
        mbar_wait(BAR_FULL(sb, r.slot), r.par);
        uint32_t hp[32] = {};
        passes128<4, false>(hp, sb, wg, tw, r, stg);
        put_h(hp, sb, wg, stg);
      } else {
        float xs[64];
        uint32_t xp[32];
        {
            sts128(sb + tid * 16, pack2(silu_(bf_lo(cw[0])), silu_(bf_lo(cw[1]))), pack2(silu_(bf_lo(cw[2])), silu_(bf_lo(cw[3]))),
                   pack2(silu_(bf_lo(cw[4])), silu_(bf_lo(cw[5]))), pack2(silu_(bf_lo(cw[6])), silu_(bf_lo(cw[7]))));
            cluster_wait();
            ep = __shfl_sync(0xffffffffu, ep, 0) / NCTA + 1;
            load_slab(xp, stg.acquire2(sb, wg));
            unpack_slab(xs, xp);
            if (tid == 0) TL(24);
            if (tid == 128) TL(27);
        }
#pragma unroll 1
        for (int blk = 0; ; ++blk) {
        {
            IDX();
            uint4* const st = (blk ? g_st2 : g_st1 + m * 8 * 512) + wg * 64 + w4 * 16 + g8;
            RowAcc ra;
#pragma unroll
            for (int e = 0; e < 64; ++e) ra.add(e, xs[e]);
            ra.publish(st + j * 512, q4, ep);
            uint32_t t_pub = 0; if (PDLY) asm volatile("mov.u32 %0, %%clock;" : "=r"(t_pub));
            if (tid == 0) TL(blk ? 9 : 26);
            if (tid == 128 && blk) TL(34);
            if (blk) CS(11);
            LnPar lp;
            if (blk == 0) {
            uint4* const mod_out = pt.mail->mod1 + g8 * 512 + (m * 8 + j) * 4 + q4;
            if (wg == 0) {
                uint4 af[8];
#pragma unroll
                for (int i = 0; i < 8; ++i) af[i] = lds128(sb + w4 * 512 + i * 64 + q4 * 16);
                float c[4][4] = {};
#pragma unroll
                for (int i = 0; i < 8; ++i) {
                    if (!(i & 1)) mbar_wait(BAR_ONE(sb, EV_WIN + (i >> 1)), 0);
                    if (i == 6 && tid == 0) TL(25);
#pragma unroll
                    for (int h = 0; h < 2; ++h) {
                        uint32_t b0, b1, b2, b3;
                        ldsm4t(sb + 5 * SLOT + i * 4096 + w4 * 1024 + h * 512 + (lane & 15) * 32 + (lane >> 4) * 16, b0, b1, b2, b3);
                        mma16816(c[2 * h], h ? af[i].z : af[i].x, 0u, h ? af[i].w : af[i].y, 0u, b0, b1);
                        mma16816(c[2 * h + 1], h ? af[i].z : af[i].x, 0u, h ? af[i].w : af[i].y, 0u, b2, b3);
                    }
                }
                if (lane < 4) sts128(sb + OFF_TAB + w4 * 64 + lane * 16, __float_as_uint(c[0][0] + c[2][0]), __float_as_uint(c[0][1] + c[2][1]),
                                     __float_as_uint(c[1][0] + c[3][0]), __float_as_uint(c[1][1] + c[3][1]));
                if (lane < 2) mbar_arrive_cta(BAR_ONE(sb, EV_P0), lane);
                bar_sync(1, 128);
                if (w4 == 0) {
                    float a[4] = {0.f, 0.f, 0.f, 0.f};
#pragma unroll
                    for (int i = 0; i < 4; ++i) {
                        const uint4 t = lds128(sb + OFF_TAB + i * 64 + q4 * 16);
                        a[0] += __uint_as_float(t.x); a[1] += __uint_as_float(t.y); a[2] += __uint_as_float(t.z); a[3] += __uint_as_float(t.w);
                    }
                    const float add = m >= 8 ? 1.f : 0.f;
                    st_pkt16(mod_out, pack2(bf_round(a[0]) + add, bf_round(a[1]) + add), pack2(bf_round(a[2]) + add, bf_round(a[3]) + add), ep, 0);
                    if (tid == 0) TL(3);
                }
            } else if (LWAIT >= 0) mbar_wait(BAR_ONE(sb, EV_WIN + LWAIT), 0);
            } else {
                mbar_wait2(BAR_ONE(sb, EV_LN2), BAR_FULL(sb, 0), 0);
            }
            lp.load(sb, q4);
#pragma unroll
            for (int e = 0; e < 32; ++e) xp[e] = pack2(xs[2 * e], xs[2 * e + 1]);
            if (PDLY && blk) { uint32_t t1; do { asm volatile("mov.u32 %0, %%clock;" : "=r"(t1)); } while (t1 - t_pub < PDLY); }
            if (blk) CS(13);
            const LnRow n = merge_stats(st, q4, ep, sb);
            if (tid == 0) TL(blk ? 49 : 48);
            if (tid == 128) TL(blk ? 45 : 28);
            if (blk) CS(18);
            uint32_t xn[32];
            ln_norm(xn, xs, n);
            if (blk == 0) {
                mbar_wait2(BAR_FULL(sb, 0), BAR_ONE(sb, EV_PAR), 0);
                if (FD0 && wg == 0) { uint32_t t0, t1; asm volatile("mov.u32 %0, %%clock;" : "=r"(t0)); do { asm volatile("mov.u32 %0, %%clock;" : "=r"(t1)); } while (t1 - t0 < FD0); }
                lp.load(sb, q4);
            }
            ln_emit(xn, lp, sb, wg, ix);
            if (tid == 0) { TL(blk ? 36 : 8); TC(blk ? 109 : 103); }
            if (tid == 128) TL(blk ? 43 : 22);
            if (blk) CS(21);
        }
        uint32_t hp[32];
        if (blk == 0) {
        {
            float big[128], sml[64];
            step32<true, true>(big, sml, sb, wg, r.slot, 0);
            TS(0, 0);
            Pipe pp(sb, tw, r.slot);
            r.next();
#pragma unroll 1
            for (int it = 1; it < 32 - LAGQ; ++it) {
                pp.acquire<true>(sb, wg ? 0 : AF_REL, r);
                step32<true, false>(big, sml, sb, wg, r.slot, it < 4 ? it : -1);
                pp.issued(r.slot);
                TS(it, 0);
                r.next();
            }
            auto half = [&](uint32_t slot, bool rest) {
                const uint32_t st = d16(sb) + slot * (SLOT >> 4);
#pragma unroll
                for (int k = 0; k < 2; ++k) {
                    const uint64_t da = mk_desc(st + wg * 256, k * 32, 16, 512, 2);
                    if (rest) wgmma_n256(big, da, mk_desc(st, 8192 + k * 2048, 4096, 1024, 1)); else wgmma_n128(sml, da, mk_desc(st, 24576 + k * 2048, 4096, 1024, 1));
                }
            };
            auto rest = [&](bool each) {
                wg_fence();
#pragma unroll
                for (int it = 32 - LAGQ; it < 32; ++it) { if (each && it > 32 - LAGQ) wg_fence(); half(it % NSLOT, true); if (each || it == 31) wg_commit(); }
            };
            stg.acquire2(sb, wg); mbar_wait2(BAR_SREADY(sb, 2), BAR_SREADY(sb, 3), 1);
#pragma unroll 1
            for (int it = 32 - LAGQ; it < 32; ++it) {
                pp.acquire<true>(sb, wg ? 0 : AF_REL, r);
                wg_fence(); half(r.slot, false); wg_commit();
                pp.issued(NSLOT);
                TS(it, 0);
                r.next();
            }
            if (wg) { rest(false); wg_wait<1>(); } else wg_wait<0>();
            CS(8);
            IDX();
            uint32_t k0[8], k1[8], k2[8], v0[8], v1[8], v2[8];
            const uint32_t nxt = warp + ((warp & 1) ? 3 : 1), mine = sb + OFF_STG + wg * 16384 + w4 * 2048;
            auto tails = [&](const float* kv, uint32_t (&kt)[8], uint32_t (&vt)[8]) {
#pragma unroll
                for (int t = 0; t < 8; ++t) { kt[t] = pack2(kv[4 * t + 2], kv[4 * t + 3]); vt[t] = pack2(kv[32 + 4 * t + 2], kv[32 + 4 * t + 3]); }
            };
            auto post = [&](int pn, uint32_t (&kt)[8], uint32_t (&vt)[8]) {
                uint4* dst = g_halo + (m * 8 + j) * 512 + (w4 >> 1) * 256 + pn * 128 + lane;
#pragma unroll
                for (int h = 0; h < 2; ++h) { if (!kt[4 * h]) kt[4 * h] = 0x8000u; if (!vt[4 * h]) vt[4 * h] = 0x8000u; }
#pragma unroll
                for (int h = 0; h < 2; ++h) { st_pkt16(dst + h * 32, kt[4 * h], kt[4 * h + 1], kt[4 * h + 2], kt[4 * h + 3]); st_pkt16(dst + 64 + h * 32, vt[4 * h], vt[4 * h + 1], vt[4 * h + 2], vt[4 * h + 3]); }
            };
            auto prepare = [&](int pn, const float* kv) {
                tails(kv, k2, v2);
                if (nxt < 8) {
                    const uint32_t dst = sb + OFF_STG + (nxt >> 2) * 16384 + (nxt & 3) * 2048 + pn * 8192 + lane * 16;
#pragma unroll
                    for (int h = 0; h < 2; ++h) { stsm4(dst + h * 512, k2[4 * h], k2[4 * h + 1], k2[4 * h + 2], k2[4 * h + 3]); stsm4(dst + 1024 + h * 512, v2[4 * h], v2[4 * h + 1], v2[4 * h + 2], v2[4 * h + 3]); }
                    if (pn == 0) bar_arrive(NB_TAIL + nxt, 64);
                    else { __syncwarp(); if (lane == 0) mbar_arrive(BAR_ONE(sb, EV_TAIL + nxt)); }
                } else if (pn == 0 && m < 15) post(0, k2, v2);
#pragma unroll
                for (int t = 0; t < 8; ++t) { k1[t] = pack2(kv[4 * t], kv[4 * t + 1]); v1[t] = movm(pack2(kv[32 + 4 * t], kv[32 + 4 * t + 1])); v2[t] = movm(v2[t]); }
                if (pn == 0) { CS(2); if (wg == 0) { rest(true); wg_wait<3>(); pp.rel(28 % NSLOT); wg_wait<2>(); pp.rel(29 % NSLOT); wg_wait<1>(); pp.rel(30 % NSLOT); } bar_sync(NB_TAIL + warp, 64); CS(4); }
                else mbar_wait(BAR_ONE(sb, EV_TAIL + __shfl_sync(0xffffffffu, warp, 0)), 0);
#pragma unroll
                for (int h = 0; h < 2; ++h) {
                    ldsm4(mine + pn * 8192 + lane * 16 + h * 512, k0[4 * h], k0[4 * h + 1], k0[4 * h + 2], k0[4 * h + 3]);
                    ldsm4t(mine + pn * 8192 + lane * 16 + 1024 + h * 512, v0[4 * h], v0[4 * h + 1], v0[4 * h + 2], v0[4 * h + 3]);
                }
            };
#pragma unroll
            for (int i = 0; i < 64; ++i) asm volatile("" : "+f"(sml[i]) :: "memory");
            prepare(0, sml);
            static_assert(LAGQ == 4, "");
            wg_wait<0>();
            if (wg) { pp.rel(28 % NSLOT); pp.rel(29 % NSLOT); pp.rel(30 % NSLOT); }
            pp.rel(31 % NSLOT);
            TS(31, 1);
            if (tid == 0) { TL(4); TC(104); }
            if (tid == 128) TL(50);
            CS(1);
#pragma unroll
            for (int i = 0; i < 128; ++i) asm volatile("" : "+f"(big[i]) :: "memory");
            if (nxt >= 8 && m < 15) { uint32_t kt[8], vt[8]; tails(big, kt, vt); post(1, kt, vt); }
            const bool lo0 = q4 * 2 > g8, lo1 = q4 * 2 + 1 > g8;
            const bool nopast = m == 0 && (warp & 5) == 0;
            const uint32_t lomask = (lo0 ? 0xFFFFu : 0u) | (lo1 ? 0xFFFF0000u : 0u);
            const uint32_t orow = mine + (lane & 7) * 128 + (((lane >> 3) ^ (lane & 7)) << 4);
            const float sl2 = 0.17677669529663687f * 1.4426950408889634f;
#pragma unroll
            for (int pn = 0; pn < 2; ++pn) {
                float e0[4], e1[4], mx[4], sum[4];
#pragma unroll
                for (int hh = 0; hh < 2; ++hh) {
                    uint32_t qf[8];
#pragma unroll
                    for (int i = 0; i < 8; ++i) qf[i] = pack2(big[64 + 32 * pn + 16 * hh + 2 * i], big[64 + 32 * pn + 16 * hh + 2 * i + 1]);
                    float s[3][4];
#pragma unroll
                    for (int t = 0; t < 3; ++t) {
                        const uint32_t* k = (t == 0 ? k0 : t == 1 ? k1 : k2) + 4 * hh;
                        s[t][0] = s[t][1] = s[t][2] = s[t][3] = 0.f;
                        mma16816(s[t], qf[0], qf[1], qf[2], qf[3], k[0], k[1]);
                        mma16816(s[t], qf[4], qf[5], qf[6], qf[7], k[2], k[3]);
                    }
#pragma unroll
                    for (int hf = 0; hf < 2; ++hf) {
                        const int u = hh * 2 + hf;
                        e0[u] = lo0 ? ((hf == 0 && nopast) ? -INFINITY : s[hf][hf * 2]) : s[hf + 1][hf * 2];
                        e1[u] = lo1 ? ((hf == 0 && nopast) ? -INFINITY : s[hf][hf * 2 + 1]) : s[hf + 1][hf * 2 + 1];
                        mx[u] = fmaxf(e0[u], e1[u]);
                    }
                }
#pragma unroll
                for (int o = 1; o < 4; o <<= 1)
#pragma unroll
                    for (int u = 0; u < 4; ++u) mx[u] = fmaxf(mx[u], __shfl_xor_sync(0xffffffffu, mx[u], o));
#pragma unroll
                for (int u = 0; u < 4; ++u) {
                    const float c = -mx[u] * sl2;
                    e0[u] = ex2(fmaf(e0[u], sl2, c)); e1[u] = ex2(fmaf(e1[u], sl2, c));
                    sum[u] = e0[u] + e1[u];
                }
#pragma unroll
                for (int o = 1; o < 4; o <<= 1)
#pragma unroll
                    for (int u = 0; u < 4; ++u) sum[u] += __shfl_xor_sync(0xffffffffu, sum[u], o);
#pragma unroll
                for (int u = 0; u < 4; ++u) {
                    const int h = u >> 1;
                    const float inv = rcp(sum[u]);
                    const uint32_t p = pack2(e0[u] * inv, e1[u] * inv);
                    const uint32_t* va = ((u & 1) ? v1 : v0) + 4 * h;
                    const uint32_t* vb = ((u & 1) ? v2 : v1) + 4 * h;
                    float o[2][4] = {};
#pragma unroll
                    for (int d = 0; d < 2; ++d) mma16816(o[d], va[2 * d], va[2 * d + 1], vb[2 * d], vb[2 * d + 1], p & lomask, p & ~lomask);
                    stsm4t((orow ^ ((u >> 1) << 6)) + pn * 8192 + (u & 1) * 1024, pack2(o[0][0], o[0][1]), pack2(o[0][2], o[0][3]), pack2(o[1][0], o[1][1]), pack2(o[1][2], o[1][3]));
                }
                fence_async_smem();
                __syncwarp();
                if (lane == 0) mbar_arrive(BAR_SFULL(sb, wg * 2 + pn));
                if (pn == 0) { CS(5); block_end(sb, 0); prepare(1, big); CS(3); }
            }
            CS(6);
            if (tid == 32) TL(41);
            mbar_wait2(BAR_FULL(sb, 32 % NSLOT), BAR_FULL(sb, 33 % NSLOT), (32 / NSLOT) & 1);
            load_slab(xp, sb + (32 % NSLOT + wg) * SLOT);
#pragma unroll
            for (int e = 0; e < 32; ++e) hp[e] = __float_as_uint(big[e]);
            bar_sync(1 + wg, 128);
            if (tid == 0) { TL(6); TC(106); }
            if (tid == 128) TL(44);
            CS(7);
        }
        } else {
        {
            float ag[88], au[88];
            mainloop32<true, LAG>(ag, au, sb, wg, tw, r, EV_LAG1, 48, [](int) {}, [&] {
                Ring q = r; if (!wg) q.next();
                mbar_wait(BAR_EMPTY(sb, q.slot), q.par ^ 1);
                mbar_wait(BAR_FULL(sb, r.slot), r.par);
            });
            if (tid == 0) { TL(10); TC(110); }
            if (tid == 128) TL(51);
            CS(22);
            {
                IDX();
                uint32_t h3[12];
                glu(h3, [&](int i) { return ag[64 + i]; }, [&](int i) { return au[64 + i]; });
#pragma unroll
                for (int k = 0; k < 3; ++k) stsm4(sb + (wg ? P3_SLOT1 : P3_SLOT0) * SLOT + 24576 + (pan_addr ^ (k << 5)), h3[4 * k], h3[4 * k + 1], h3[4 * k + 2], h3[4 * k + 3]);
            }
            glu(hp, [&](int i) { return ag[i]; }, [&](int i) { return au[i]; });
            if (tid == 0) { TL(11); TC(111); }
            if (tid == 128) TL(52);
            CS(23);
        }
        passes128<2, true>(hp, sb, wg, tw, r, stg);
        if (tid == 0) { TL(12); TC(112); }
        }
        {
            float acc[64], gf[32];
            mainloop64(acc, blk == 0, sb, wg, tw, r, [&] { put_h(hp, sb, wg, stg); }, [&] {
                mbar_wait(BAR_ONE(sb, EV_GA + blk), 0);
                unpack_slab(xs, xp);
                uint32_t gt[16];
#pragma unroll
                for (int cg = 0; cg < 16; ++cg) gt[cg] = lds32(sb + OFF_TAB + blk * 256 + cg * 16 + (tw & 3) * 4);
#pragma unroll
                for (int i = 0; i < 16; ++i) unpack2(gt[i], gf[2 * i], gf[2 * i + 1]);
            }, [&] { stg.acquire2(sb, wg); });
            if (tid == 0) { TL(blk ? 13 : 7); TC(blk ? 113 : 107); }
            if (tid == 128) TL(blk ? 57 : 42);
            CS(blk ? 30 : 10);
#pragma unroll
            for (int e = 0; e < 64; ++e) xs[e] = fmaf(gf[(e >> 2) * 2 + (e & 1)], acc[e], xs[e]);
        }
        if (blk) break;
        }
        {
            IDX();
#pragma unroll
            for (int p = 0; p < 2; ++p) {
                store_slab(xs, sb + OFF_STG + wg * 16384, 8192, pan_addr, 4 * p, 4 * p + 4);
                stg.publish(sb, wg, lane);
            }
            cluster_arrive();
            if (tid == 0) TL(14);
            CS(31);
        }
      }
    } else {
        if (warp == 8 && !aux && elect_one()) {
#pragma unroll
            for (int i = 0; i < 4; ++i) mbar_init(BAR_SREADY(sb, i), 1);
#pragma unroll
            for (int i = 0; i < 4; ++i) mbar_init(BAR_ONE(sb, EV_WIN + i), 1);
#pragma unroll
            for (int i = 0; i < 4; ++i) {
                mbar_expect_tx(BAR_SREADY(sb, i), 8192);
                tma_load3(sb + OFF_STG + i * 8192, &mp.x, j * 128 + (i & 1) * 64, m * 64 + (i >> 1) * 32, BAR_SREADY(sb, i));
            }
#pragma unroll 1
            for (int i = 0; i < 4; ++i) {
                mbar_expect_tx(BAR_ONE(sb, EV_WIN + i), 8192);
                tma_load(sb + 5 * SLOT + i * 8192, &mp.wm8, 2 * i * 6144 + (m * 8 + j) * 16, 0, BAR_ONE(sb, EV_WIN + i));
                tma_load(sb + 5 * SLOT + i * 8192 + 4096, &mp.wm8, (2 * i + 1) * 6144 + (m * 8 + j) * 16, 0, BAR_ONE(sb, EV_WIN + i));
            }
        }
        __syncwarp();
        asm volatile("setmaxnreg.dec.sync.aligned.u32 56;");
        if (elect_one()) {
            if (warp == 8) {
                prefetch_map(&mp.wqkv); prefetch_map(&mp.wmod);
            } else if (warp < 11) {
                mbar_init(BAR_EMPTY(sb, NSLOT), 1);
#pragma unroll
                for (int i = 0; i < 2; ++i) { mbar_init(BAR_SFULL(sb, (warp - 9) * 2 + i), 4); if (aux) mbar_init(BAR_SREADY(sb, (warp - 9) * 2 + i), 1); }
#pragma unroll
                for (int i = 0; i < 3; ++i) {
                    mbar_init(BAR_EMPTY(sb, (warp - 9) * 3 + i), 4);
                    mbar_init(BAR_FULL(sb, (warp - 9) * 3 + i), 1); mbar_init(BAR_FULL(sb, (warp - 9) * 3 + i) + AF_REL, 1);
                }
            } else {
#pragma unroll
                for (int i = EV_P0; i < EV_COUNT; ++i) mbar_init(BAR_ONE(sb, i), i == EV_P0 ? 8 : 1);
            }
            asm volatile("fence.mbarrier_init.release.cluster;" ::: "memory");
        }
        __syncwarp();
        cluster_arrive();
        ep = 0;
        if (warp != 8 || aux) ep = flag_get(g_flags + FL_DONE);
        cluster_wait();
        ep = __shfl_sync(0xffffffffu, ep, 0) / NCTA + 1;
        if (warp == 8) {
            const bool el = elect_one();
            Ring r{0, 1};
            if (aux) {
                {
                    uint32_t n = 0;
                    while (!__all_sync(0xffffffffu, ld_pkt16(pt.mail->mod1 + 256).z == ep)) { SPIN_GUARD(n); __nanosleep(200); }
                }
#pragma unroll 1
                for (int it = 0; it < 64; ++it) {
                    const int col = 2048 + (it >> 4) * 1024 + j * 256;
                    mbar_wait(BAR_EMPTY(sb, r.slot), r.par);
                    const uint32_t st = sb + r.slot * SLOT, fb = BAR_FULL(sb, r.slot);
                    if (el) {
                        mbar_expect_tx(fb, 32768);
#pragma unroll
                        for (int b = 0; b < 4; ++b) tma_load(st + b * 8192, &mp.wmod, col + b * 64, (it & 15) * 64, fb);
                    }
                    r.next();
                }
                mbar_wait(BAR_ONE(sb, EV_P0), 0);
                const CUtensorMap* wm = rank ? &mp.wu : &mp.wg;
#pragma unroll 1
                for (int g = 0; g < 128; ++g) {
                    const int mx = (j >> 1) * 8 + (g >> 5) * 2 + rank, k0 = ((g & 14) << 6) + ((g & 16) << 2) + ((g & 1) << 5);
                    if (!(g & 15)) {
                        uint32_t n = 0;
                        while (!__all_sync(0xffffffffu, (int32_t)(flag_get(g_flags + FL_PROG + fidx(mx, lane >> 4, (lane & 14) | ((g >> 4) & 1))) - (ep * 8 + ST_H2)) >= 0)) { SPIN_GUARD(n); __nanosleep(300); }
                    }
                    mbar_wait(BAR_EMPTY(sb, r.slot), r.par);
                    const uint32_t st = sb + r.slot * SLOT, fb = BAR_FULL(sb, r.slot);
                    if (el) {
                        mbar_expect_tx(fb, 24576);
                        tma_load_mc(st + 8192 + rank * 4096, wm, HC3, k0, fb);
                        tma_load_mc(st + 16384 + rank * 4096, wm, HC3 + 64, k0, fb);
                        tma_load(st, &mp.h2l, k0, mx * 128, fb);
                    }
                    r.next();
                }
            } else {
#pragma unroll 1
                for (int it = 0; it < 32; ++it) {
                    const int cb = j * 128 + rank * 64, k0 = kof(it, 2, j);
                    if (it == BW0) mbar_wait(BAR_ONE(sb, BWEV), 0);
                    if (it == BW1) mbar_wait(BAR_ONE(sb, EV_PAR), 0);
                    if (it == 5) mbar_wait(BAR_ONE(sb, EV_P0), 0);
                    if (it == AG0) mbar_wait(BAR_ONE(sb, (AGW & 1) ? EV_AGO : EV_FGO), 0);
                    mbar_wait(BAR_EMPTY(sb, r.slot), r.par);
                    const uint32_t st = sb + r.slot * SLOT, fb = BAR_FULL(sb, r.slot);
                    if (el) {
                        mbar_expect_tx(fb, it < 4 ? 24576 : 28672);
                        tma_load_mc(st + 24576 - rank * 16384, &mp.wqkv, 1024 + cb, k0, fb);
                        tma_load_mc(st + 28672 - rank * 16384, &mp.wqkv, 2048 + cb, k0, fb);
                        tma_load_mc(st + 16384 + rank * 4096, &mp.wqkv, cb, k0, fb);
                        if (it < 4) mbar_arrive(fb + AF_REL);
                        if (it == PFWO + (m >> 1)) { tma_prefetch(&mp.wo, j * 128, m * 64); tma_prefetch(&mp.wo, j * 128 + 64, m * 64); }
                        if (it >= PFG && it < PFG + PFN && (it & 7) == grp) {
                            const int kp = kof(it - PFG + PFO, 2, j);
                            tma_prefetch(rank ? &mp.wu : &mp.wg, hcol(0, j), kp); tma_prefetch(rank ? &mp.wu : &mp.wg, hcol(0, j) + 64, kp);
                            asm volatile("cp.async.bulk.prefetch.tensor.3d.L2.global [%0, {%1, %2, %3}];" :: "l"(rank ? &mp.wu3 : &mp.wg3), "r"(0), "r"(j), "r"(kp) : "memory");
                        }
                    }
                    r.next();
                }
                if (el) mbar_arrive(BAR_ONE(sb, EV_KV));
#pragma unroll 1
                for (int it = 0; it < 16; ++it) {
                    const int k0 = kof(it, 1, j);
                    if (it == AG1) mbar_wait(BAR_ONE(sb, (AGW & 2) ? EV_AGO1 : EV_FGO1), 0);
                    mbar_wait(BAR_EMPTY(sb, r.slot), r.par);
                    const uint32_t st = sb + r.slot * SLOT, fb = BAR_FULL(sb, r.slot);
                    if (el) {
                        mbar_expect_tx(fb, it < 2 ? 32768 : 24576);
                        tma_load_mc(st + 16384 + rank * 8192, &mp.wo, j * 128 + rank * 64, k0, fb);
                        if (it < 2) {
                            tma_load3(st, &mp.x, j * 128, m * 64 + it * 32, fb); tma_load3(st + 8192, &mp.x, j * 128 + 64, m * 64 + it * 32, fb);
                            mbar_arrive(fb + AF_REL);
                        }
                        if (it == 6) { prefetch_map(rank ? &mp.wu : &mp.wg); prefetch_map(rank ? &mp.wu3 : &mp.wg3); }
                    }
                    r.next();
                }
                const CUtensorMap* wm = rank ? &mp.wu : &mp.wg;
#pragma unroll 1
                for (int g = 0; g < 96; ++g) {
                    if (g == AG2) mbar_wait(BAR_ONE(sb, (AGW & 4) ? EV_AGO2 : EV_FGO2), 0);
                    const int p = g >> 5, cb = hcol(p, j), k0 = p == 0 ? kof(g, 2, j) : (g & 31) * 32;
                    mbar_wait(BAR_EMPTY(sb, r.slot), r.par);
                    const uint32_t st = sb + r.slot * SLOT, fb = BAR_FULL(sb, r.slot);
                    if (el) {
                        mbar_expect_tx(fb, (g < 4 || p > 0) ? 24576 : 28672);
                        tma_load_mc(st + 8192 + rank * 4096, wm, cb, k0, fb);
                        tma_load_mc(st + 16384 + rank * 4096, wm, cb + 64, k0, fb);
                        if (p == 0) tma_load3_mc(st + 24576 + rank * 4096, rank ? &mp.wu3 : &mp.wg3, j, k0, fb);
                        else tma_load(st, &mp.h2l, k0, m * 128, fb);
                        if (g < 4) mbar_arrive(fb + AF_REL);
                        if (g == 60) { prefetch_map(&mp.wd); prefetch_map(&mp.hb); }
                    }
                    r.next();
                }
#pragma unroll 1
                for (int g = 0; g < 56; ++g) {
                    if (g == 0 || (g & 15) == 6 && g > 6) mbar_wait(BAR_ONE(sb, EV_H0 + (g >> 4)), 0);
                    const int k0 = g * 64;
                    mbar_wait(BAR_EMPTY(sb, r.slot), r.par);
                    const uint32_t st = sb + r.slot * SLOT, fb = BAR_FULL(sb, r.slot);
                    if (el) {
                        mbar_expect_tx(fb, 32768);
                        tma_load_mc(st + 16384 + rank * 8192, &mp.wd, j * 128 + rank * 64, k0, fb);
                        tma_load(st, &mp.hb, k0, m * 128, fb); tma_load(st + 8192, &mp.hb, k0, m * 128 + 64, fb);
                    }
                    r.next();
                }
            }
        } else if (aux) {
            if (warp < 11) {
                const uint32_t w = warp - 9;
                const bool el = elect_one();
#pragma unroll 1
                for (int p = 0; p < 4; ++p) {
                    const int mx = (j >> 1) * 8 + p * 2 + rank;
                    if (el) { mbar_arrive(BAR_SREADY(sb, w * 2)); mbar_arrive(BAR_SREADY(sb, w * 2 + 1)); }
                    mbar_wait2(BAR_SFULL(sb, w * 2), BAR_SFULL(sb, w * 2 + 1), p & 1);
                    if (p < 3) pause(w ? HD1 : HD0);
                    if (el) tma_store(&mp.hb, HC3, mx * 128 + w * 64, sb + OFF_STG + w * 16384);
                    if (p < 3) pause(HP);
                    if (el) {
                        tma_store(&mp.hb, HC3 + 64, mx * 128 + w * 64, sb + OFF_STG + w * 16384 + 8192);
                        bulk_commit(); bulk_wait_fence(); flag_set(g_flags + FL_AUX + mx * 2 + w, ep * 8 + ST_H + 3);
                    }
                }
            }
        } else if (warp == 11) {
            const bool el = elect_one();
            const int row0 = m * 128;
            const uint32_t* const fl = g_flags + FL_PROG + fidx(m, lane >> 4, kof(lane & 15, 1, j) >> 6);
            if (el) { prefetch_map(&mp.h1h); prefetch_map(&mp.h2h); prefetch_map(&mp.h2l); }
            auto gate = [&](int vec, int ev) {
                uint4 v; uint32_t n = 0;
                while (true) {
                    v = ld_pkt2(g_mod + vec * 512 + j * 64 + lane * 2);
                    if (__all_sync(0xffffffffu, v.y == ep && v.w == ep)) break;
                    SPIN_GUARD(n); __nanosleep(300);
                }
                asm volatile("st.shared.v2.u32 [%0], {%1, %2};" :: "r"(sb + OFF_TAB + (ev - EV_GA) * 256 + lane * 8), "r"(v.x), "r"(v.z) : "memory");
                __syncwarp();
                if (lane == 0) mbar_arrive(BAR_ONE(sb, ev));
            };
            {
                const uint4* pk = pt.mail->mod1 + grp * 512 + j * 32 + lane;
                uint4 a, b; uint32_t n = 0;
                mbar_wait(BAR_ONE(sb, EV_WIN3), 0);
                while (true) {
                    a = ld_pkt16(pk); b = ld_pkt16(pk + 256);
                    if (__all_sync(0xffffffffu, a.z == ep && b.z == ep)) break;
                    SPIN_GUARD(n);
                }
                sts128(sb + OFF_PAR + lane * 16, a.x, a.y, b.x, b.y);
                __syncwarp();
                if (lane == 0) { mbar_arrive(BAR_ONE(sb, EV_PAR)); TL(46); }
            }
            mbar_wait(BAR_ONE(sb, EV_P0), 0);
            Ring r{0, 1};
#pragma unroll 1
            for (int ph = 0; ph < 3; ++ph) {
                const int sh = ph == 1 ? 1 : 2, nst = 8 << sh;
                const uint32_t half = 16384 >> sh, target = ep * 8 + ST_H1 + ph;
                const CUtensorMap* tm = ph == 0 ? &mp.h1h : ph == 1 ? &mp.o : &mp.h2h;
                if (ph == 1) {
                    gate(2, EV_GA);
                    mbar_wait(BAR_SREADY(sb, 1), 1);
#pragma unroll 1
                    for (int i = 0; i < 2; ++i)
                        fetch_halo<1>(g_halo + ((m - 1) * 8 + j) * 512 + i * 256 + 128 + lane, m == 0, sb + OFF_STG + 8192 + i * 4096 + lane * 16,
                                      [&] { __syncwarp(); if (el) mbar_arrive(BAR_ONE(sb, EV_TAIL + 2 * i)); });
                    CS(32);
                }
                if (ph == 2) {
                    uint32_t n = 0;
                    while ((int32_t)(flag_get(g_flags + FL_LN2) - ep * 8) < 0) { SPIN_GUARD(n); __nanosleep(200); }
                    const uint4 v = __ldcg((const uint4*)(g_par2 + j * 128) + lane);
                    sts128(sb + OFF_PAR + lane * 16, v.x, v.y, v.z, v.w);
                    __syncwarp();
                    if (lane == 0) mbar_arrive(BAR_ONE(sb, EV_LN2));
                }
                const uint32_t lw = ~lane & 1, lt = lane >> 1, ls = (r.slot + lt) % NSLOT, lk = kof(lt, sh, j), lb = BAR_FULL(sb, ls) + (lw ? 0 : AF_REL);
                const uint32_t* const lf = g_flags + FL_PROG + fidx(m, lw, lk >> 6);
                int fr = 1 << sh;
                uint32_t todo = 0x3ffffu >> (2 * fr) << (2 * fr), have = ~todo, n = 0, v = 0;
                r.skip(fr);
#pragma unroll 1
                for (; fr < NSLOT; ++fr) { mbar_wait(BAR_EMPTY(sb, r.slot), r.par); r.next(); }
                if (ph == XST - 1) CS(33);
                do {
                    if (!((have >> lane) & 1)) v = flag_get(lf);
                    while (ph == 2 && fr < FRCAP && mbar_test(BAR_EMPTY(sb, r.slot), r.par)) { ++fr; r.next(); }
                    SPIN_GUARD(n);
                    have |= __ballot_sync(0xffffffffu, (int32_t)(v - target) >= 0);
                    const uint32_t go = have & todo & ((1u << (2 * fr)) - 1);
                    if ((go >> lane) & 1) {
                        if (!lw) mbar_expect_tx(lb, half);
                        tma_load(sb + ls * SLOT + lw * half, tm, lk, row0 + lw * 64, lb);
                    }
                    __syncwarp();
                    if (lane < 2 && (todo & (0x555u << lane)) && !(todo & ~go & (0x555u << lane))) mbar_arrive(BAR_ONE(sb, (lane ? EV_FGO : EV_AGO) + ph));
                    if (ph == XST - 1) { if (go & (1u << (2 << sh))) CS(34); if (go & (2u << (2 << sh))) CS(35); if (todo & 0x555u) CS(36); if (todo & 0xaaau) CS(37); }
                    todo &= ~go;
                } while (~have);
                if (ph == XST - 1) CS(38);
                int k = kof(fr, sh, j);
#pragma unroll 1
                for (; fr < nst; ++fr) {
                    if (fr == 9 || fr == 18) {
                        const uint32_t skip = fr == 9 << (sh - 1) ? 0 : ~0x01fc01fcu;
                        while (~(__ballot_sync(0xffffffffu, (int32_t)(flag_get(fl) - target) >= 0) | skip)) SPIN_GUARD(n);
                    }
                    const uint32_t st = sb + r.slot * SLOT, fb = BAR_FULL(sb, r.slot);
                    mbar_wait(BAR_EMPTY(sb, r.slot), r.par);
                    if (el) {
                        tma_load(st + half, tm, k, row0 + 64, fb);
                        mbar_expect_tx(fb + AF_REL, half);
                        tma_load(st, tm, k, row0, fb + AF_REL);
                    }
                    if (ph == XST - 1 && fr == 9) CS(39);
                    r.next();
                    k = kof(fr + 1, sh, j);
                }
            }
#pragma unroll 1
            for (int p = 0; p < 4; ++p) {
                const uint32_t* f = p < 3 ? fl : g_flags + FL_AUX + m * 2 + (lane & 1);
                uint32_t n = 0;
                while (!__all_sync(0xffffffffu, (int32_t)(flag_get(f) - (ep * 8 + ST_H + p)) >= 0)) { SPIN_GUARD(n); __nanosleep(300); }
                if (el) mbar_arrive(BAR_ONE(sb, EV_H0 + p));
                if (p == 0) gate(5, EV_GB);
            }
        } else {
            const uint32_t w = warp - 9;
            const int row0 = m * 128 + w * 64;
            const uint32_t stg = sb + OFF_STG + w * 16384;
            uint32_t* const fl = g_flags + FL_PROG + fidx(m, w, 2 * j);
            uint32_t b = 0, par = 0;
            const bool el = elect_one();
            auto store = [&](const CUtensorMap* tm, int col, bool nat = false) {
                mbar_wait(BAR_SFULL(sb, w * 2 + b), (par >> b) & 1);
                par ^= 1u << b;
                if (el) {
                    if (nat) tma_store3(tm, col, row0 >> 1, 0, stg + b * 8192); else tma_store(tm, col, row0, stg + b * 8192);
                    bulk_commit();
                }
                b ^= 1;
            };
            auto send2 = [&](const CUtensorMap* tm, const uint32_t* buf, int step) {
                const uint32_t* const q = buf + (size_t)((row0 + lane) * (D_ / 2) + j * 64 + 31);
                store(tm, j * 128);
                if (step == XST) CS(33);
                uint32_t z = landed(el, q, D_ / 2, pt.zero);
                if (el) flag_set(fl, ep * 8 + step + z);
                if (step == XST) CS(34);
                if (step != ST_O) { mbar_wait(BAR_ONE(sb, EV_FGO + step - ST_H1), 0); pause(step == ST_H1 ? (w ? P1H : P1H + 1000) : w ? P2L : P2F); }
                store(tm, j * 128 + 64);
                if (step == XST) CS(35);
                z = landed(el, q + 32, D_ / 2, pt.zero);
                if (el) flag_set(fl + 1, ep * 8 + step + z);
                if (step == XST) CS(36);
            };
            auto free2 = [&]() { if (el) { mbar_arrive(BAR_SREADY(sb, w * 2)); mbar_arrive(BAR_SREADY(sb, w * 2 + 1)); } };
            if (el) { prefetch_map(&mp.h1s); prefetch_map(&mp.o); prefetch_map(&mp.out); prefetch_map(&mp.wo); }
            send2(&mp.h1s, pt.h1, ST_H1);
            if (w == 0) TL(47);
            free2();
            mbar_wait(BAR_ONE(sb, EV_KV), 0);
            mbar_wait(BAR_SREADY(sb, 0), 1);
            fetch_halo<1>(g_halo + ((m - 1) * 8 + j) * 512 + w * 256 + lane, m == 0, sb + OFF_STG + w * 4096 + lane * 16, [&] { bar_arrive(NB_TAIL + 2 * w, 64); CS(38); });
            send2(&mp.o, pt.o, ST_O);
            if (w == 0) TL(40); else TL(38);
            free2();
            send2(&mp.o, pt.o, ST_H2);
            if (el) { prefetch_map(&mp.hbs); prefetch_map(&mp.hb3); }
            if (w == 0) TL(37);
            free2();
#pragma unroll 1
            for (int p = 0; p < 3; ++p) {
                const int col = hcol(p, j);
                mbar_wait2(BAR_SFULL(sb, w * 2), BAR_SFULL(sb, w * 2 + 1), par & 1);
                par ^= 3;
#pragma unroll 1
                for (int i = 0; i < (p ? 2 : 3) * NSPL; ++i) {
                    pause(i ? HP / NSPL : p == 2 ? (w ? HE1 : HE0) : w ? HD1 : HD0);
                    const int pn = i / NSPL, ro = (i % NSPL) * (64 / NSPL);
                    if (el) {
                        if (pn < 2) tma_store(&mp.hbs, col + pn * 64, row0 + ro, stg + i * (8192 / NSPL));
                        else tma_store3(&mp.hb3, 0, j, row0 + ro, sb + (w ? P3_SLOT1 : P3_SLOT0) * SLOT + 24576 + ro * 128);
                        bulk_commit();
                    }
                }
                if (el) bulk_wait_read();
                free2();
                if (el) { bulk_wait_fence(); flag_set(fl, ep * 8 + ST_H + p); flag_set(fl + 1, ep * 8 + ST_H + p); }
            }
            cluster_arrive_early = true;
            cluster_arrive();
            store(&mp.out, j * 128, true); store(&mp.out, j * 128 + 64, true);
            if (el) bulk_wait_read();
        }
        __syncwarp();
    }
    if (aux || (wg == 2 && !cluster_arrive_early)) cluster_arrive();
    cluster_wait();
    if (KDEBUG == 5) __syncthreads();
    if (tid == 0) {
        TL(15);
        flag_add(pt.mail->flags + FL_DONE);
    }
}

typedef CUresult (*EncodeFn)(CUtensorMap*, CUtensorMapDataType, cuuint32_t, void*, const cuuint64_t*, const cuuint64_t*, const cuuint32_t*,
                             const cuuint32_t*, CUtensorMapInterleave, CUtensorMapSwizzle, CUtensorMapL2promotion, CUtensorMapFloatOOBfill);

void make_map(EncodeFn fn, CUtensorMap* m, const void* ptr, uint64_t rows, uint64_t cols, uint32_t brows, uint32_t bcols) {
    cuuint64_t dims[2] = {cols, rows}, strides[1] = {cols * 2};
    cuuint32_t box[2] = {bcols, brows}, es[2] = {1, 1};
    fn(m, CU_TENSOR_MAP_DATA_TYPE_BFLOAT16, 2, (void*)ptr, dims, strides, box, es, CU_TENSOR_MAP_INTERLEAVE_NONE,
       bcols == 64 ? CU_TENSOR_MAP_SWIZZLE_128B : bcols == 32 ? CU_TENSOR_MAP_SWIZZLE_64B : CU_TENSOR_MAP_SWIZZLE_NONE, CU_TENSOR_MAP_L2_PROMOTION_L2_256B, CU_TENSOR_MAP_FLOAT_OOB_FILL_NONE);
}

void make_map3(EncodeFn fn, CUtensorMap* m, const void* ptr) {
    cuuint64_t dims[3] = {D_, S_ / 2, 2}, strides[2] = {4 * D_, 2 * D_};
    cuuint32_t box[3] = {64, 32, 2}, es[3] = {1, 1, 1};
    fn(m, CU_TENSOR_MAP_DATA_TYPE_BFLOAT16, 3, (void*)ptr, dims, strides, box, es, CU_TENSOR_MAP_INTERLEAVE_NONE,
       CU_TENSOR_MAP_SWIZZLE_128B, CU_TENSOR_MAP_L2_PROMOTION_L2_256B, CU_TENSOR_MAP_FLOAT_OOB_FILL_NONE);
}

void make_map48(EncodeFn fn, CUtensorMap* m, const void* ptr, uint64_t rows, uint32_t brows) {
    cuuint64_t dims[3] = {48, 8, rows}, strides[2] = {96, 2 * F_};
    cuuint32_t box[3] = {64, 1, brows}, es[3] = {1, 1, 1};
    fn(m, CU_TENSOR_MAP_DATA_TYPE_BFLOAT16, 3, (void*)ptr, dims, strides, box, es, CU_TENSOR_MAP_INTERLEAVE_NONE,
       CU_TENSOR_MAP_SWIZZLE_128B, CU_TENSOR_MAP_L2_PROMOTION_L2_256B, CU_TENSOR_MAP_FLOAT_OOB_FILL_NONE);
}

}

extern "C" void kernel_launch(void* const* d_in, const int* in_sizes, int n_in, void* d_out, int out_size) {
    (void)in_sizes; (void)n_in; (void)out_size;
    void* fnp = nullptr;
    cudaDriverEntryPointQueryResult qr;
    cudaGetDriverEntryPoint("cuTensorMapEncodeTiled", &fnp, cudaEnableDefault, &qr);
    EncodeFn fn = (EncodeFn)fnp;
    void *h1, *o, *h2, *hb, *mail;
    cudaGetSymbolAddress(&h1, g_h1);
    cudaGetSymbolAddress(&mail, g_mail);
    cudaGetSymbolAddress(&o, g_o);
    cudaGetSymbolAddress(&hb, g_hb);
    h2 = o;
    Maps mp;
    make_map(fn, &mp.h1h, h1, S_, D_, 64, 32);
    make_map(fn, &mp.h2h, h2, S_, D_, 64, 32);
    make_map(fn, &mp.h1s, h1, S_, D_, 64, 64);
    make_map(fn, &mp.o, o, S_, D_, 64, 64);
    make_map(fn, &mp.h2l, h2, S_, D_, 128, 32);
    make_map(fn, &mp.hb, hb, S_, F_, 64, 64);
    make_map(fn, &mp.wqkv, d_in[1], D_, 3 * D_, 32, 64);
    make_map(fn, &mp.wo, d_in[2], D_, D_, 64, 64);
    make_map(fn, &mp.wg, d_in[4], D_, F_, 32, 64);
    make_map(fn, &mp.wu, d_in[5], D_, F_, 32, 64);
    make_map(fn, &mp.wd, d_in[6], F_, D_, 64, 64);
    make_map(fn, &mp.wmod, d_in[8], D_, 6 * D_, 64, 64);
    make_map(fn, &mp.wm8, d_in[8], D_ / 8, 8 * 6 * D_, 128, 16);
    make_map3(fn, &mp.x, d_in[0]);
    make_map3(fn, &mp.out, d_out);
    make_map48(fn, &mp.wg3, d_in[4], D_, 32);
    make_map48(fn, &mp.wu3, d_in[5], D_, 32);
    make_map48(fn, &mp.hb3, hb, S_, 64 / NSPL);
    make_map(fn, &mp.hbs, hb, S_, F_, 64 / NSPL, 64);
    cudaFuncSetAttribute(fused_block_kernel, cudaFuncAttributeMaxDynamicSharedMemorySize, SMEM_BYTES);
    cudaLaunchConfig_t cfg = {};
    cfg.gridDim = dim3(NCTA); cfg.blockDim = dim3(384); cfg.dynamicSmemBytes = SMEM_BYTES; cfg.stream = cudaStreamPerThread;
    cudaLaunchAttribute at[1];
    at[0].id = cudaLaunchAttributeClusterDimension; at[0].val.clusterDim.x = 2; at[0].val.clusterDim.y = 1; at[0].val.clusterDim.z = 1;
    cfg.attrs = at; cfg.numAttrs = 1;
    const Ptrs pt{(const __nv_bfloat16*)d_in[7], (Mail*)mail, (const uint32_t*)h1, (const uint32_t*)o, 0};
    cudaLaunchKernelEx(&cfg, fused_block_kernel, pt, mp);
}
```

```cpp
#include <cuda_runtime.h>
#include <cuda_bf16.h>
#include <cuda.h>
#include <stdint.h>
#include <stddef.h>

#define LAG 4
#define LAGS 4
#define LAGW 2
#define LAGD 4
#define LAGQ 4
#define PUT1 5
#define PUT0 10
#define PUTD1 6
#define PUTD0 10
#define MIDD 40
#define HD1 3000
#define HD0 1500
#define NSPL 2
#define HE1 2000
#define HE0 HD0
#define HP 2600
#define P1H 3000
#define P2L 2000
#define P2F 3000
#define PDLY 500
#define FD0 200
#define AG0 6
#define AG1 6
#define AG2 8
#define AGW 2
#define FRCAP 8
#define BW0 0
#define BWEV EV_WIN
#define BW1 3
#define LWAIT 3
#define PFWO 12
#define PFG 8
#define PFN 24
#define PFC 10
#define PFO 0
#define KDEBUG 0
#define CSW 0
#define XST ST_O

namespace {

constexpr int S_ = 2048, D_ = 1024, F_ = 3584;
constexpr int NCTA = 132;
constexpr int NSLOT = 6;
constexpr uint32_t SLOT = 32768;
constexpr uint32_t OFF_STG = NSLOT * SLOT;
constexpr uint32_t OFF_BAR = OFF_STG + 32768;
constexpr uint32_t OFF_PAR = OFF_BAR + 512;
constexpr uint32_t OFF_TAB = OFF_PAR + 768;
constexpr uint32_t OFF_TL = OFF_PAR + 2048;
constexpr uint32_t SMEM_BYTES = OFF_TL + (KDEBUG ? 512 : 0);
constexpr uint32_t P3_SLOT1 = (32 + 16 + 32) % NSLOT, P3_SLOT0 = (P3_SLOT1 + 1) % NSLOT;

constexpr int ST_H1 = 1, ST_O = 2, ST_H2 = 3, ST_H = 4, FL_DONE = 0, FL_LN2 = 1, FL_AUX = 32, FL_PROG = 64;

struct Maps {
    CUtensorMap h1h, h1s, o, h2h, h2l, hb, wqkv, wo, wg, wu, wd, wmod, wm8, x, out, wg3, wu3, hb3, hbs;
};

struct Mail {
    uint32_t flags[16 * 32 + 64];
    uint2 mod[6 * D_ / 2];
    uint4 mod1[8 * 512];
    uint4 st1[128 * 512];
    uint32_t par2[D_];
    uint4 halo[128 * 512];
};
struct Ptrs { const __nv_bfloat16* c; Mail* mail; const uint32_t *h1, *o; uint32_t zero; };

__device__ __align__(128) Mail g_mail;
__device__ __align__(128) __nv_bfloat16 g_h1[S_ * D_];
__device__ __align__(128) __nv_bfloat16 g_o[S_ * D_];
__device__ __align__(128) __nv_bfloat16 g_hb[S_ * F_];
#define TL(i) do {} while (0)
#define TC(i) do {} while (0)
#define TS(g, which) do {} while (0)
#define CS(i) do {} while (0)

__device__ __forceinline__ uint32_t smem_u32(const void* p) { return (uint32_t)__cvta_generic_to_shared(p); }
__device__ __forceinline__ void mbar_init(uint32_t bar, uint32_t cnt) { asm volatile("mbarrier.init.shared::cta.b64 [%0], %1;" :: "r"(bar), "r"(cnt) : "memory"); }
__device__ __forceinline__ void mbar_expect_tx(uint32_t bar, uint32_t bytes) { asm volatile("mbarrier.arrive.expect_tx.shared::cta.b64 _, [%0], %1;" :: "r"(bar), "r"(bytes) : "memory"); }
__device__ __forceinline__ void mbar_arrive(uint32_t bar) { asm volatile("mbarrier.arrive.shared::cta.b64 _, [%0];" :: "r"(bar) : "memory"); }
__device__ __forceinline__ void mbar_arrive_cta(uint32_t bar, uint32_t cta) {
    asm volatile("{\n.reg .b32 r;\nmapa.shared::cluster.u32 r, %0, %1;\nmbarrier.arrive.shared::cluster.b64 _, [r];\n}" :: "r"(bar), "r"(cta) : "memory");
}
__device__ __forceinline__ void mbar_wait(uint32_t bar, uint32_t parity) {
    asm volatile("{\n.reg .pred p;\n.reg .u32 n;\nmov.u32 n, 0;\n"
        "W_LOOP:\nmbarrier.try_wait.parity.shared::cta.b64 p, [%0], %1;\n@p bra W_DONE;\n"
        "add.u32 n, n, 1;\nsetp.lt.u32 p, n, 0x400000;\n@p bra W_LOOP;\ntrap;\nW_DONE:\n}" :: "r"(bar), "r"(parity) : "memory");
}
__device__ __forceinline__ void mbar_wait2(uint32_t b0, uint32_t b1, uint32_t parity) {
    asm volatile("{\n.reg .pred p, q;\n.reg .u32 n;\nmov.u32 n, 0;\n"
        "W_LOOP:\nmbarrier.try_wait.parity.shared::cta.b64 p, [%0], %2;\nmbarrier.try_wait.parity.shared::cta.b64 q, [%1], %2;\nand.pred p, p, q;\n@p bra W_DONE;\n"
        "add.u32 n, n, 1;\nsetp.lt.u32 p, n, 0x400000;\n@p bra W_LOOP;\ntrap;\nW_DONE:\n}" :: "r"(b0), "r"(b1), "r"(parity) : "memory");
}
__device__ __forceinline__ bool mbar_test(uint32_t bar, uint32_t parity) {
    uint32_t r; asm volatile("{\n.reg .pred p;\nmbarrier.test_wait.parity.shared::cta.b64 p, [%1], %2;\nselp.u32 %0, 1, 0, p;\n}" : "=r"(r) : "r"(bar), "r"(parity) : "memory"); return r;
}
__device__ __forceinline__ bool mbar_test2(uint32_t b0, uint32_t b1, uint32_t parity) {
    uint32_t r;
    asm volatile("{\n.reg .pred p, q;\nmbarrier.test_wait.parity.shared::cta.b64 p, [%1], %3;\nmbarrier.test_wait.parity.shared::cta.b64 q, [%2], %3;\n"
        "and.pred p, p, q;\nselp.u32 %0, 1, 0, p;\n}" : "=r"(r) : "r"(b0), "r"(b1), "r"(parity) : "memory");
    return r;
}
__device__ __forceinline__ void tma_load3(uint32_t dst, const CUtensorMap* m, int c0, int c1, uint32_t bar) {
    asm volatile("cp.async.bulk.tensor.3d.shared::cluster.global.mbarrier::complete_tx::bytes [%0], [%1, {%3, %4, %5}], [%2];"
        :: "r"(dst), "l"(m), "r"(bar), "r"(c0), "r"(c1), "r"(0) : "memory");
}
__device__ __forceinline__ void tma_store3(const CUtensorMap* m, int c0, int c1, int c2, uint32_t src) {
    asm volatile("cp.async.bulk.tensor.3d.global.shared::cta.bulk_group [%0, {%2, %3, %4}], [%1];" :: "l"(m), "r"(src), "r"(c0), "r"(c1), "r"(c2) : "memory");
}
__device__ __forceinline__ void tma_load3_mc(uint32_t dst, const CUtensorMap* m, int c1, int c2, uint32_t bar) {
    asm volatile("cp.async.bulk.tensor.3d.shared::cluster.global.mbarrier::complete_tx::bytes.multicast::cluster.L2::cache_hint [%0], [%1, {%3, %4, %5}], [%2], %6, %7;"
        :: "r"(dst), "l"(m), "r"(bar), "r"(0), "r"(c1), "r"(c2), "h"((uint16_t)3), "l"(0x12F0000000000000ull) : "memory");
}
__device__ __forceinline__ void tma_load(uint32_t dst, const CUtensorMap* m, int c0, int c1, uint32_t bar) {
    asm volatile("cp.async.bulk.tensor.2d.shared::cluster.global.mbarrier::complete_tx::bytes [%0], [%1, {%3, %4}], [%2];"
        :: "r"(dst), "l"(m), "r"(bar), "r"(c0), "r"(c1) : "memory");
}
__device__ __forceinline__ void tma_load_mc(uint32_t dst, const CUtensorMap* m, int c0, int c1, uint32_t bar) {
    asm volatile("cp.async.bulk.tensor.2d.shared::cluster.global.mbarrier::complete_tx::bytes.multicast::cluster.L2::cache_hint [%0], [%1, {%3, %4}], [%2], %5, %6;"
        :: "r"(dst), "l"(m), "r"(bar), "r"(c0), "r"(c1), "h"((uint16_t)3), "l"(0x12F0000000000000ull) : "memory");
}
__device__ __forceinline__ void tma_prefetch(const CUtensorMap* m, int c0, int c1) {
    asm volatile("cp.async.bulk.prefetch.tensor.2d.L2.global [%0, {%1, %2}];" :: "l"(m), "r"(c0), "r"(c1) : "memory");
}
__device__ __forceinline__ void tma_store(const CUtensorMap* m, int c0, int c1, uint32_t src) {
    asm volatile("cp.async.bulk.tensor.2d.global.shared::cta.bulk_group [%0, {%2, %3}], [%1];" :: "l"(m), "r"(src), "r"(c0), "r"(c1) : "memory");
}
__device__ __forceinline__ void bulk_commit() { asm volatile("cp.async.bulk.commit_group;" ::: "memory"); }
__device__ __forceinline__ void bulk_wait_read() { asm volatile("cp.async.bulk.wait_group.read 0;" ::: "memory"); }
__device__ __forceinline__ void fence_async_smem() { asm volatile("fence.proxy.async.shared::cta;" ::: "memory"); }
__device__ __forceinline__ void prefetch_map(const CUtensorMap* m) { asm volatile("prefetch.tensormap [%0];" :: "l"(m) : "memory"); }
__device__ __forceinline__ void wg_fence() { asm volatile("wgmma.fence.sync.aligned;" ::: "memory"); }
__device__ __forceinline__ void wg_commit() { asm volatile("wgmma.commit_group.sync.aligned;" ::: "memory"); }
template <int N> __device__ __forceinline__ void wg_wait() { asm volatile("wgmma.wait_group.sync.aligned %0;" :: "n"(N) : "memory"); }
__device__ __forceinline__ void bar_sync(int id, int n) { asm volatile("bar.sync %0, %1;" :: "r"(id), "r"(n) : "memory"); }
__device__ __forceinline__ void bar_arrive(int id, int n) { asm volatile("bar.arrive %0, %1;" :: "r"(id), "r"(n) : "memory"); }
__device__ __forceinline__ void flag_add(uint32_t* f) { asm volatile("red.relaxed.gpu.global.add.u32 [%0], 1;" :: "l"(f) : "memory"); }
__device__ __forceinline__ void flag_set(uint32_t* f, uint32_t v) { asm volatile("red.relaxed.gpu.global.max.u32 [%0], %1;" :: "l"(f), "r"(v) : "memory"); }
__device__ __forceinline__ uint32_t flag_get(const uint32_t* f) { uint32_t v; asm volatile("ld.relaxed.gpu.global.u32 %0, [%1];" : "=r"(v) : "l"(f) : "memory"); return v; }
__device__ __forceinline__ void bulk_wait_fence() { asm volatile("cp.async.bulk.wait_group 0;\nfence.proxy.async.global;\nfence.acq_rel.gpu;" ::: "memory"); }
__device__ __forceinline__ uint32_t landed(bool el, const uint32_t* p, uint32_t pitch, uint32_t zero) {
    if (el) asm volatile("cp.async.bulk.wait_group 0;" ::: "memory");
    __syncwarp();
    const uint32_t a = flag_get(p), b = flag_get(p + 32 * pitch);
    return __reduce_or_sync(0xffffffffu, (a | b) & zero);
}
__device__ __forceinline__ uint32_t d16(uint32_t addr) { return (addr & 0x3FFFF) >> 4; }
__device__ __forceinline__ uint64_t mk_desc(uint32_t a16, uint32_t off, uint32_t lbo, uint32_t sbo, uint32_t swz) {
    const uint32_t lo = a16 + (off >> 4) + ((lbo >> 4) << 16), hi = (sbo >> 4) | (swz << 30);
    return ((uint64_t)hi << 32) | lo;
}
__device__ __forceinline__ uint32_t pack2(float lo, float hi) {
    uint32_t r; asm("cvt.rn.bf16x2.f32 %0, %1, %2;" : "=r"(r) : "f"(hi), "f"(lo)); return r;
}
__device__ __forceinline__ uint32_t hfma2_bf16(uint32_t a, uint32_t b, uint32_t c) {
    uint32_t r; asm("fma.rn.bf16x2 %0, %1, %2, %3;" : "=r"(r) : "r"(a), "r"(b), "r"(c)); return r;
}
__device__ __forceinline__ float bf_lo(uint32_t v) { return __uint_as_float(v << 16); }
__device__ __forceinline__ float bf_hi(uint32_t v) { return __uint_as_float(v & 0xFFFF0000u); }
__device__ __forceinline__ void unpack2(uint32_t v, float& lo, float& hi) {
    asm volatile("shl.b32 %0, %2, 16;\nand.b32 %1, %2, 0xffff0000;" : "=f"(lo), "=f"(hi) : "r"(v));
}
__device__ __forceinline__ float bf_round(float x) { return __bfloat162float(__float2bfloat16_rn(x)); }
__device__ __forceinline__ void stsm4(uint32_t addr, uint32_t r0, uint32_t r1, uint32_t r2, uint32_t r3) {
    asm volatile("stmatrix.sync.aligned.m8n8.x4.shared.b16 [%0], {%1, %2, %3, %4};" :: "r"(addr), "r"(r0), "r"(r1), "r"(r2), "r"(r3) : "memory");
}
__device__ __forceinline__ void stsm4t(uint32_t addr, uint32_t r0, uint32_t r1, uint32_t r2, uint32_t r3) {
    asm volatile("stmatrix.sync.aligned.m8n8.x4.trans.shared.b16 [%0], {%1, %2, %3, %4};" :: "r"(addr), "r"(r0), "r"(r1), "r"(r2), "r"(r3) : "memory");
}
__device__ __forceinline__ uint32_t movm(uint32_t a) { uint32_t d; asm volatile("movmatrix.sync.aligned.m8n8.trans.b16 %0, %1;" : "=r"(d) : "r"(a)); return d; }
__device__ __forceinline__ void ldsm4(uint32_t addr, uint32_t& r0, uint32_t& r1, uint32_t& r2, uint32_t& r3) {
    asm volatile("ldmatrix.sync.aligned.m8n8.x4.shared.b16 {%0, %1, %2, %3}, [%4];" : "=r"(r0), "=r"(r1), "=r"(r2), "=r"(r3) : "r"(addr) : "memory");
}
__device__ __forceinline__ void ldsm4t(uint32_t addr, uint32_t& r0, uint32_t& r1, uint32_t& r2, uint32_t& r3) {
    asm volatile("ldmatrix.sync.aligned.m8n8.x4.trans.shared.b16 {%0, %1, %2, %3}, [%4];" : "=r"(r0), "=r"(r1), "=r"(r2), "=r"(r3) : "r"(addr) : "memory");
}
__device__ __forceinline__ void mma16816(float (&c)[4], uint32_t a0, uint32_t a1, uint32_t a2, uint32_t a3, uint32_t b0, uint32_t b1) {
    asm("mma.sync.aligned.m16n8k16.row.col.f32.bf16.bf16.f32 {%0, %1, %2, %3}, {%4, %5, %6, %7}, {%8, %9}, {%0, %1, %2, %3};"
        : "+f"(c[0]), "+f"(c[1]), "+f"(c[2]), "+f"(c[3]) : "r"(a0), "r"(a1), "r"(a2), "r"(a3), "r"(b0), "r"(b1));
}
__device__ __forceinline__ float rsq(float x) { float r; asm("rsqrt.approx.ftz.f32 %0, %1;" : "=f"(r) : "f"(x)); return r; }
__device__ __forceinline__ float rcp(float x) { float r; asm("rcp.approx.ftz.f32 %0, %1;" : "=f"(r) : "f"(x)); return r; }
__device__ __forceinline__ float ex2(float x) { float r; asm("ex2.approx.ftz.f32 %0, %1;" : "=f"(r) : "f"(x)); return r; }
__device__ __forceinline__ float tanh_(float x) { float t; asm("tanh.approx.f32 %0, %1;" : "=f"(t) : "f"(x)); return t; }
__device__ __forceinline__ void block_end(uint32_t opaque, uint32_t id) { asm volatile("{\n.reg .pred p;\nsetp.eq.u32 p, %0, %1;\n@p trap;\n}" :: "r"(opaque), "r"(0xffffff00u + id)); }
__device__ __forceinline__ float silu_(float x) { return __fdividef(x, 1.f + __expf(-x)); }
__device__ __forceinline__ void st_pkt(void* p, uint32_t a, uint32_t b) {
    asm volatile("{\n.reg .b64 t;\nmov.b64 t, {%1, %2};\nst.relaxed.gpu.global.b64 [%0], t;\n}" :: "l"(p), "r"(a), "r"(b) : "memory");
}
__device__ __forceinline__ uint4 ld_pkt2(const void* p) {
    uint4 v; asm volatile("{\n.reg .b64 t, u;\nld.relaxed.gpu.global.v2.b64 {t, u}, [%4];\nmov.b64 {%0, %1}, t;\nmov.b64 {%2, %3}, u;\n}"
        : "=r"(v.x), "=r"(v.y), "=r"(v.z), "=r"(v.w) : "l"(p) : "memory"); return v;
}
__device__ __forceinline__ void st_pkt16(void* p, uint32_t a, uint32_t b, uint32_t c, uint32_t d) {
    asm volatile("{\n.reg .b64 t, u;\n.reg .b128 w;\nmov.b64 t, {%1, %2};\nmov.b64 u, {%3, %4};\nmov.b128 w, {t, u};\nst.relaxed.gpu.global.b128 [%0], w;\n}"
        :: "l"(p), "r"(a), "r"(b), "r"(c), "r"(d) : "memory");
}
__device__ __forceinline__ uint4 ld_pkt16(const void* p) {
    uint4 v; asm volatile("{\n.reg .b64 t, u;\n.reg .b128 w;\nld.relaxed.gpu.global.b128 w, [%4];\nmov.b128 {t, u}, w;\nmov.b64 {%0, %1}, t;\nmov.b64 {%2, %3}, u;\n}"
        : "=r"(v.x), "=r"(v.y), "=r"(v.z), "=r"(v.w) : "l"(p) : "memory"); return v;
}
#define SPIN_GUARD(n) do { if (++(n) > (1u << 22)) asm volatile("trap;"); } while (0)
__device__ __forceinline__ uint4 lds128(uint32_t a) { uint4 v; asm volatile("ld.shared.v4.u32 {%0, %1, %2, %3}, [%4];" : "=r"(v.x), "=r"(v.y), "=r"(v.z), "=r"(v.w) : "r"(a) : "memory"); return v; }
__device__ __forceinline__ void sts128(uint32_t a, uint32_t x, uint32_t y, uint32_t z, uint32_t w) { asm volatile("st.shared.v4.u32 [%0], {%1, %2, %3, %4};" :: "r"(a), "r"(x), "r"(y), "r"(z), "r"(w) : "memory"); }
__device__ __forceinline__ uint32_t lds32(uint32_t a) { uint32_t v; asm volatile("ld.shared.u32 %0, [%1];" : "=r"(v) : "r"(a) : "memory"); return v; }
__device__ __forceinline__ void sts32(uint32_t a, uint32_t v) { asm volatile("st.shared.u32 [%0], %1;" :: "r"(a), "r"(v) : "memory"); }
__device__ __forceinline__ bool elect_one() {
    uint32_t p; asm volatile("{\n.reg .pred q;\nelect.sync _|q, 0xffffffff;\nselp.u32 %0, 1, 0, q;\n}" : "=r"(p)); return p;
}
__device__ __forceinline__ void pause(uint32_t cycles) {
    uint32_t t0, t; asm volatile("mov.u32 %0, %%clock;" : "=r"(t0));
    do { __nanosleep(64); asm volatile("mov.u32 %0, %%clock;" : "=r"(t)); } while (t - t0 < cycles);
}
__device__ __forceinline__ void cluster_arrive() { asm volatile("barrier.cluster.arrive.relaxed.aligned;" ::: "memory"); }
__device__ __forceinline__ void cluster_wait() { asm volatile("barrier.cluster.wait.aligned;" ::: "memory"); }

__device__ __forceinline__ void wgmma_n128_z(float (&d)[64], uint64_t da, uint64_t db) {
    asm volatile("{\n.reg .pred p;\nsetp.ne.b32 p, 0, 0;\n"
        "wgmma.mma_async.sync.aligned.m64n128k16.f32.bf16.bf16 {"
        "%0, %1, %2, %3, %4, %5, %6, %7, %8, %9, %10, %11, %12, %13, %14, %15, "
        "%16, %17, %18, %19, %20, %21, %22, %23, %24, %25, %26, %27, %28, %29, %30, %31, "
        "%32, %33, %34, %35, %36, %37, %38, %39, %40, %41, %42, %43, %44, %45, %46, %47, "
        "%48, %49, %50, %51, %52, %53, %54, %55, %56, %57, %58, %59, %60, %61, %62, %63"
        "}, %64, %65, p, 1, 1, 0, 1;\n}\n"
        : "=f"(d[0]), "=f"(d[1]), "=f"(d[2]), "=f"(d[3]), "=f"(d[4]), "=f"(d[5]), "=f"(d[6]), "=f"(d[7]),
          "=f"(d[8]), "=f"(d[9]), "=f"(d[10]), "=f"(d[11]), "=f"(d[12]), "=f"(d[13]), "=f"(d[14]), "=f"(d[15]),
          "=f"(d[16]), "=f"(d[17]), "=f"(d[18]), "=f"(d[19]), "=f"(d[20]), "=f"(d[21]), "=f"(d[22]), "=f"(d[23]),
          "=f"(d[24]), "=f"(d[25]), "=f"(d[26]), "=f"(d[27]), "=f"(d[28]), "=f"(d[29]), "=f"(d[30]), "=f"(d[31]),
          "=f"(d[32]), "=f"(d[33]), "=f"(d[34]), "=f"(d[35]), "=f"(d[36]), "=f"(d[37]), "=f"(d[38]), "=f"(d[39]),
          "=f"(d[40]), "=f"(d[41]), "=f"(d[42]), "=f"(d[43]), "=f"(d[44]), "=f"(d[45]), "=f"(d[46]), "=f"(d[47]),
          "=f"(d[48]), "=f"(d[49]), "=f"(d[50]), "=f"(d[51]), "=f"(d[52]), "=f"(d[53]), "=f"(d[54]), "=f"(d[55]),
          "=f"(d[56]), "=f"(d[57]), "=f"(d[58]), "=f"(d[59]), "=f"(d[60]), "=f"(d[61]), "=f"(d[62]), "=f"(d[63])
        : "l"(da), "l"(db));
}
__device__ __forceinline__ void wgmma_n128(float (&d)[64], uint64_t da, uint64_t db) {
    asm volatile("{\n.reg .pred p;\nsetp.eq.b32 p, 0, 0;\n"
        "wgmma.mma_async.sync.aligned.m64n128k16.f32.bf16.bf16 {"
        "%0, %1, %2, %3, %4, %5, %6, %7, %8, %9, %10, %11, %12, %13, %14, %15, "
        "%16, %17, %18, %19, %20, %21, %22, %23, %24, %25, %26, %27, %28, %29, %30, %31, "
        "%32, %33, %34, %35, %36, %37, %38, %39, %40, %41, %42, %43, %44, %45, %46, %47, "
        "%48, %49, %50, %51, %52, %53, %54, %55, %56, %57, %58, %59, %60, %61, %62, %63"
        "}, %64, %65, p, 1, 1, 0, 1;\n}\n"
        : "+f"(d[0]), "+f"(d[1]), "+f"(d[2]), "+f"(d[3]), "+f"(d[4]), "+f"(d[5]), "+f"(d[6]), "+f"(d[7]),
          "+f"(d[8]), "+f"(d[9]), "+f"(d[10]), "+f"(d[11]), "+f"(d[12]), "+f"(d[13]), "+f"(d[14]), "+f"(d[15]),
          "+f"(d[16]), "+f"(d[17]), "+f"(d[18]), "+f"(d[19]), "+f"(d[20]), "+f"(d[21]), "+f"(d[22]), "+f"(d[23]),
          "+f"(d[24]), "+f"(d[25]), "+f"(d[26]), "+f"(d[27]), "+f"(d[28]), "+f"(d[29]), "+f"(d[30]), "+f"(d[31]),
          "+f"(d[32]), "+f"(d[33]), "+f"(d[34]), "+f"(d[35]), "+f"(d[36]), "+f"(d[37]), "+f"(d[38]), "+f"(d[39]),
          "+f"(d[40]), "+f"(d[41]), "+f"(d[42]), "+f"(d[43]), "+f"(d[44]), "+f"(d[45]), "+f"(d[46]), "+f"(d[47]),
          "+f"(d[48]), "+f"(d[49]), "+f"(d[50]), "+f"(d[51]), "+f"(d[52]), "+f"(d[53]), "+f"(d[54]), "+f"(d[55]),
          "+f"(d[56]), "+f"(d[57]), "+f"(d[58]), "+f"(d[59]), "+f"(d[60]), "+f"(d[61]), "+f"(d[62]), "+f"(d[63])
        : "l"(da), "l"(db));
}
__device__ __forceinline__ void wgmma_n176_z(float (&d)[88], uint64_t da, uint64_t db) {
    asm volatile("{\n.reg .pred p;\nsetp.ne.b32 p, 0, 0;\n"
        "wgmma.mma_async.sync.aligned.m64n176k16.f32.bf16.bf16 {"
        "%0, %1, %2, %3, %4, %5, %6, %7, %8, %9, %10, %11, %12, %13, %14, %15, "
        "%16, %17, %18, %19, %20, %21, %22, %23, %24, %25, %26, %27, %28, %29, %30, %31, "
        "%32, %33, %34, %35, %36, %37, %38, %39, %40, %41, %42, %43, %44, %45, %46, %47, "
        "%48, %49, %50, %51, %52, %53, %54, %55, %56, %57, %58, %59, %60, %61, %62, %63, "
        "%64, %65, %66, %67, %68, %69, %70, %71, %72, %73, %74, %75, %76, %77, %78, %79, "
        "%80, %81, %82, %83, %84, %85, %86, %87"
        "}, %88, %89, p, 1, 1, 0, 1;\n}\n"
        : "=f"(d[0]), "=f"(d[1]), "=f"(d[2]), "=f"(d[3]), "=f"(d[4]), "=f"(d[5]), "=f"(d[6]), "=f"(d[7]),
          "=f"(d[8]), "=f"(d[9]), "=f"(d[10]), "=f"(d[11]), "=f"(d[12]), "=f"(d[13]), "=f"(d[14]), "=f"(d[15]),
          "=f"(d[16]), "=f"(d[17]), "=f"(d[18]), "=f"(d[19]), "=f"(d[20]), "=f"(d[21]), "=f"(d[22]), "=f"(d[23]),
          "=f"(d[24]), "=f"(d[25]), "=f"(d[26]), "=f"(d[27]), "=f"(d[28]), "=f"(d[29]), "=f"(d[30]), "=f"(d[31]),
          "=f"(d[32]), "=f"(d[33]), "=f"(d[34]), "=f"(d[35]), "=f"(d[36]), "=f"(d[37]), "=f"(d[38]), "=f"(d[39]),
          "=f"(d[40]), "=f"(d[41]), "=f"(d[42]), "=f"(d[43]), "=f"(d[44]), "=f"(d[45]), "=f"(d[46]), "=f"(d[47]),
          "=f"(d[48]), "=f"(d[49]), "=f"(d[50]), "=f"(d[51]), "=f"(d[52]), "=f"(d[53]), "=f"(d[54]), "=f"(d[55]),
          "=f"(d[56]), "=f"(d[57]), "=f"(d[58]), "=f"(d[59]), "=f"(d[60]), "=f"(d[61]), "=f"(d[62]), "=f"(d[63]),
          "=f"(d[64]), "=f"(d[65]), "=f"(d[66]), "=f"(d[67]), "=f"(d[68]), "=f"(d[69]), "=f"(d[70]), "=f"(d[71]),
          "=f"(d[72]), "=f"(d[73]), "=f"(d[74]), "=f"(d[75]), "=f"(d[76]), "=f"(d[77]), "=f"(d[78]), "=f"(d[79]),
          "=f"(d[80]), "=f"(d[81]), "=f"(d[82]), "=f"(d[83]), "=f"(d[84]), "=f"(d[85]), "=f"(d[86]), "=f"(d[87])
        : "l"(da), "l"(db));
}
__device__ __forceinline__ void wgmma_n176(float (&d)[88], uint64_t da, uint64_t db) {
    asm volatile("{\n.reg .pred p;\nsetp.eq.b32 p, 0, 0;\n"
        "wgmma.mma_async.sync.aligned.m64n176k16.f32.bf16.bf16 {"
        "%0, %1, %2, %3, %4, %5, %6, %7, %8, %9, %10, %11, %12, %13, %14, %15, "
        "%16, %17, %18, %19, %20, %21, %22, %23, %24, %25, %26, %27, %28, %29, %30, %31, "
        "%32, %33, %34, %35, %36, %37, %38, %39, %40, %41, %42, %43, %44, %45, %46, %47, "
        "%48, %49, %50, %51, %52, %53, %54, %55, %56, %57, %58, %59, %60, %61, %62, %63, "
        "%64, %65, %66, %67, %68, %69, %70, %71, %72, %73, %74, %75, %76, %77, %78, %79, "
        "%80, %81, %82, %83, %84, %85, %86, %87"
        "}, %88, %89, p, 1, 1, 0, 1;\n}\n"
        : "+f"(d[0]), "+f"(d[1]), "+f"(d[2]), "+f"(d[3]), "+f"(d[4]), "+f"(d[5]), "+f"(d[6]), "+f"(d[7]),
          "+f"(d[8]), "+f"(d[9]), "+f"(d[10]), "+f"(d[11]), "+f"(d[12]), "+f"(d[13]), "+f"(d[14]), "+f"(d[15]),
          "+f"(d[16]), "+f"(d[17]), "+f"(d[18]), "+f"(d[19]), "+f"(d[20]), "+f"(d[21]), "+f"(d[22]), "+f"(d[23]),
          "+f"(d[24]), "+f"(d[25]), "+f"(d[26]), "+f"(d[27]), "+f"(d[28]), "+f"(d[29]), "+f"(d[30]), "+f"(d[31]),
          "+f"(d[32]), "+f"(d[33]), "+f"(d[34]), "+f"(d[35]), "+f"(d[36]), "+f"(d[37]), "+f"(d[38]), "+f"(d[39]),
          "+f"(d[40]), "+f"(d[41]), "+f"(d[42]), "+f"(d[43]), "+f"(d[44]), "+f"(d[45]), "+f"(d[46]), "+f"(d[47]),
          "+f"(d[48]), "+f"(d[49]), "+f"(d[50]), "+f"(d[51]), "+f"(d[52]), "+f"(d[53]), "+f"(d[54]), "+f"(d[55]),
          "+f"(d[56]), "+f"(d[57]), "+f"(d[58]), "+f"(d[59]), "+f"(d[60]), "+f"(d[61]), "+f"(d[62]), "+f"(d[63]),
          "+f"(d[64]), "+f"(d[65]), "+f"(d[66]), "+f"(d[67]), "+f"(d[68]), "+f"(d[69]), "+f"(d[70]), "+f"(d[71]),
          "+f"(d[72]), "+f"(d[73]), "+f"(d[74]), "+f"(d[75]), "+f"(d[76]), "+f"(d[77]), "+f"(d[78]), "+f"(d[79]),
          "+f"(d[80]), "+f"(d[81]), "+f"(d[82]), "+f"(d[83]), "+f"(d[84]), "+f"(d[85]), "+f"(d[86]), "+f"(d[87])
        : "l"(da), "l"(db));
}
__device__ __forceinline__ void wgmma_n256_z(float (&d)[128], uint64_t da, uint64_t db) {
    asm volatile("{\n.reg .pred p;\nsetp.ne.b32 p, 0, 0;\n"
        "wgmma.mma_async.sync.aligned.m64n256k16.f32.bf16.bf16 {"
        "%0, %1, %2, %3, %4, %5, %6, %7, %8, %9, %10, %11, %12, %13, %14, %15, "
        "%16, %17, %18, %19, %20, %21, %22, %23, %24, %25, %26, %27, %28, %29, %30, %31, "
        "%32, %33, %34, %35, %36, %37, %38, %39, %40, %41, %42, %43, %44, %45, %46, %47, "
        "%48, %49, %50, %51, %52, %53, %54, %55, %56, %57, %58, %59, %60, %61, %62, %63, "
        "%64, %65, %66, %67, %68, %69, %70, %71, %72, %73, %74, %75, %76, %77, %78, %79, "
        "%80, %81, %82, %83, %84, %85, %86, %87, %88, %89, %90, %91, %92, %93, %94, %95, "
        "%96, %97, %98, %99, %100, %101, %102, %103, %104, %105, %106, %107, %108, %109, %110, %111, "
        "%112, %113, %114, %115, %116, %117, %118, %119, %120, %121, %122, %123, %124, %125, %126, %127"
        "}, %128, %129, p, 1, 1, 0, 1;\n}\n"
        : "=f"(d[0]), "=f"(d[1]), "=f"(d[2]), "=f"(d[3]), "=f"(d[4]), "=f"(d[5]), "=f"(d[6]), "=f"(d[7]),
          "=f"(d[8]), "=f"(d[9]), "=f"(d[10]), "=f"(d[11]), "=f"(d[12]), "=f"(d[13]), "=f"(d[14]), "=f"(d[15]),
          "=f"(d[16]), "=f"(d[17]), "=f"(d[18]), "=f"(d[19]), "=f"(d[20]), "=f"(d[21]), "=f"(d[22]), "=f"(d[23]),
          "=f"(d[24]), "=f"(d[25]), "=f"(d[26]), "=f"(d[27]), "=f"(d[28]), "=f"(d[29]), "=f"(d[30]), "=f"(d[31]),
          "=f"(d[32]), "=f"(d[33]), "=f"(d[34]), "=f"(d[35]), "=f"(d[36]), "=f"(d[37]), "=f"(d[38]), "=f"(d[39]),
          "=f"(d[40]), "=f"(d[41]), "=f"(d[42]), "=f"(d[43]), "=f"(d[44]), "=f"(d[45]), "=f"(d[46]), "=f"(d[47]),
          "=f"(d[48]), "=f"(d[49]), "=f"(d[50]), "=f"(d[51]), "=f"(d[52]), "=f"(d[53]), "=f"(d[54]), "=f"(d[55]),
          "=f"(d[56]), "=f"(d[57]), "=f"(d[58]), "=f"(d[59]), "=f"(d[60]), "=f"(d[61]), "=f"(d[62]), "=f"(d[63]),
          "=f"(d[64]), "=f"(d[65]), "=f"(d[66]), "=f"(d[67]), "=f"(d[68]), "=f"(d[69]), "=f"(d[70]), "=f"(d[71]),
          "=f"(d[72]), "=f"(d[73]), "=f"(d[74]), "=f"(d[75]), "=f"(d[76]), "=f"(d[77]), "=f"(d[78]), "=f"(d[79]),
          "=f"(d[80]), "=f"(d[81]), "=f"(d[82]), "=f"(d[83]), "=f"(d[84]), "=f"(d[85]), "=f"(d[86]), "=f"(d[87]),
          "=f"(d[88]), "=f"(d[89]), "=f"(d[90]), "=f"(d[91]), "=f"(d[92]), "=f"(d[93]), "=f"(d[94]), "=f"(d[95]),
          "=f"(d[96]), "=f"(d[97]), "=f"(d[98]), "=f"(d[99]), "=f"(d[100]), "=f"(d[101]), "=f"(d[102]), "=f"(d[103]),
          "=f"(d[104]), "=f"(d[105]), "=f"(d[106]), "=f"(d[107]), "=f"(d[108]), "=f"(d[109]), "=f"(d[110]), "=f"(d[111]),
          "=f"(d[112]), "=f"(d[113]), "=f"(d[114]), "=f"(d[115]), "=f"(d[116]), "=f"(d[117]), "=f"(d[118]), "=f"(d[119]),
          "=f"(d[120]), "=f"(d[121]), "=f"(d[122]), "=f"(d[123]), "=f"(d[124]), "=f"(d[125]), "=f"(d[126]), "=f"(d[127])
        : "l"(da), "l"(db));
}
__device__ __forceinline__ void wgmma_n256(float (&d)[128], uint64_t da, uint64_t db) {
    asm volatile("{\n.reg .pred p;\nsetp.eq.b32 p, 0, 0;\n"
        "wgmma.mma_async.sync.aligned.m64n256k16.f32.bf16.bf16 {"
        "%0, %1, %2, %3, %4, %5, %6, %7, %8, %9, %10, %11, %12, %13, %14, %15, "
        "%16, %17, %18, %19, %20, %21, %22, %23, %24, %25, %26, %27, %28, %29, %30, %31, "
        "%32, %33, %34, %35, %36, %37, %38, %39, %40, %41, %42, %43, %44, %45, %46, %47, "
        "%48, %49, %50, %51, %52, %53, %54, %55, %56, %57, %58, %59, %60, %61, %62, %63, "
        "%64, %65, %66, %67, %68, %69, %70, %71, %72, %73, %74, %75, %76, %77, %78, %79, "
        "%80, %81, %82, %83, %84, %85, %86, %87, %88, %89, %90, %91, %92, %93, %94, %95, "
        "%96, %97, %98, %99, %100, %101, %102, %103, %104, %105, %106, %107, %108, %109, %110, %111, "
        "%112, %113, %114, %115, %116, %117, %118, %119, %120, %121, %122, %123, %124, %125, %126, %127"
        "}, %128, %129, p, 1, 1, 0, 1;\n}\n"
        : "+f"(d[0]), "+f"(d[1]), "+f"(d[2]), "+f"(d[3]), "+f"(d[4]), "+f"(d[5]), "+f"(d[6]), "+f"(d[7]),
          "+f"(d[8]), "+f"(d[9]), "+f"(d[10]), "+f"(d[11]), "+f"(d[12]), "+f"(d[13]), "+f"(d[14]), "+f"(d[15]),
          "+f"(d[16]), "+f"(d[17]), "+f"(d[18]), "+f"(d[19]), "+f"(d[20]), "+f"(d[21]), "+f"(d[22]), "+f"(d[23]),
          "+f"(d[24]), "+f"(d[25]), "+f"(d[26]), "+f"(d[27]), "+f"(d[28]), "+f"(d[29]), "+f"(d[30]), "+f"(d[31]),
          "+f"(d[32]), "+f"(d[33]), "+f"(d[34]), "+f"(d[35]), "+f"(d[36]), "+f"(d[37]), "+f"(d[38]), "+f"(d[39]),
          "+f"(d[40]), "+f"(d[41]), "+f"(d[42]), "+f"(d[43]), "+f"(d[44]), "+f"(d[45]), "+f"(d[46]), "+f"(d[47]),
          "+f"(d[48]), "+f"(d[49]), "+f"(d[50]), "+f"(d[51]), "+f"(d[52]), "+f"(d[53]), "+f"(d[54]), "+f"(d[55]),
          "+f"(d[56]), "+f"(d[57]), "+f"(d[58]), "+f"(d[59]), "+f"(d[60]), "+f"(d[61]), "+f"(d[62]), "+f"(d[63]),
          "+f"(d[64]), "+f"(d[65]), "+f"(d[66]), "+f"(d[67]), "+f"(d[68]), "+f"(d[69]), "+f"(d[70]), "+f"(d[71]),
          "+f"(d[72]), "+f"(d[73]), "+f"(d[74]), "+f"(d[75]), "+f"(d[76]), "+f"(d[77]), "+f"(d[78]), "+f"(d[79]),
          "+f"(d[80]), "+f"(d[81]), "+f"(d[82]), "+f"(d[83]), "+f"(d[84]), "+f"(d[85]), "+f"(d[86]), "+f"(d[87]),
          "+f"(d[88]), "+f"(d[89]), "+f"(d[90]), "+f"(d[91]), "+f"(d[92]), "+f"(d[93]), "+f"(d[94]), "+f"(d[95]),
          "+f"(d[96]), "+f"(d[97]), "+f"(d[98]), "+f"(d[99]), "+f"(d[100]), "+f"(d[101]), "+f"(d[102]), "+f"(d[103]),
          "+f"(d[104]), "+f"(d[105]), "+f"(d[106]), "+f"(d[107]), "+f"(d[108]), "+f"(d[109]), "+f"(d[110]), "+f"(d[111]),
          "+f"(d[112]), "+f"(d[113]), "+f"(d[114]), "+f"(d[115]), "+f"(d[116]), "+f"(d[117]), "+f"(d[118]), "+f"(d[119]),
          "+f"(d[120]), "+f"(d[121]), "+f"(d[122]), "+f"(d[123]), "+f"(d[124]), "+f"(d[125]), "+f"(d[126]), "+f"(d[127])
        : "l"(da), "l"(db));
}

struct Idx {
    uint32_t lane, warp, w4, q4, g8, prow, pan;
    __device__ __forceinline__ Idx() {
        uint32_t t; asm volatile("mov.u32 %0, %%tid.x;" : "=r"(t));
        lane = t & 31; warp = t >> 5; w4 = warp & 3; q4 = lane & 3; g8 = lane >> 2;
        prow = w4 * 16 + ((lane >> 3) & 1) * 8 + (lane & 7);
        pan = prow * 128 + (((lane >> 4) ^ (lane & 7)) << 4);
    }
};
#define IDX() const Idx ix; const uint32_t lane = ix.lane, warp = ix.warp, w4 = ix.w4, q4 = ix.q4, g8 = ix.g8, prow = ix.prow, pan_addr = ix.pan; \
    (void)lane; (void)warp; (void)w4; (void)q4; (void)g8; (void)prow; (void)pan_addr;

__device__ __forceinline__ int kof(int t, int sh, int j) {
    const int p = t >> (sh - 1), pn = p < 2 ? p : p >= 9, q = p - 2 - 7 * pn;
    return ((p < 2 ? j : q + (q >= j)) << 7) + (pn << 6) + ((t & (sh - 1)) << 5);
}
__device__ __forceinline__ uint32_t fidx(uint32_t m, uint32_t w, uint32_t pn) {
    return m * 32 + w * 16 + pn;
}
constexpr int HC0 = 8 * 48, HC3 = HC0 + 3072;
__device__ __forceinline__ int hcol(int p, int j) { return HC0 + p * 1024 + j * 128; }
struct Ring {
    uint32_t slot, par;
    __device__ __forceinline__ void next() { if (++slot == NSLOT) { slot = 0; par ^= 1; } }
    __device__ __forceinline__ void skip(uint32_t n) { slot += n; if (slot >= NSLOT) { slot -= NSLOT; par ^= 1; } }
};
__device__ __forceinline__ uint32_t BAR_FULL(uint32_t sb, uint32_t s) { return sb + OFF_BAR + 8 * s; }
constexpr uint32_t AF_REL = 48;
__device__ __forceinline__ uint32_t BAR_EMPTY(uint32_t sb, uint32_t s) { return sb + OFF_BAR + 96 + 8 * s; }
__device__ __forceinline__ uint32_t BAR_SFULL(uint32_t sb, uint32_t i) { return sb + OFF_BAR + 152 + 8 * i; }
__device__ __forceinline__ uint32_t BAR_SREADY(uint32_t sb, uint32_t i) { return sb + OFF_BAR + 184 + 8 * i; }
__device__ __forceinline__ uint32_t BAR_ONE(uint32_t sb, uint32_t i) { return sb + OFF_BAR + 216 + 8 * i; }
enum { EV_WIN, EV_WIN1, EV_WIN2, EV_WIN3, EV_P0, EV_GA, EV_GB, EV_LN2, EV_LAG1, EV_LAG2, EV_LAG3, EV_LAG4, EV_LAG5, EV_KV, EV_PAR, EV_AGO, EV_AGO1, EV_AGO2, EV_FGO, EV_FGO1, EV_FGO2, EV_H0, EV_H1, EV_H2, EV_H3, EV_TAIL, EV_COUNT = EV_TAIL + 8 };
constexpr int NB_TAIL = 4;

struct Rel {
    uint32_t base; bool sig;
    __device__ __forceinline__ Rel(uint32_t sb, uint32_t tw) {
        uint32_t a; asm("mapa.shared::cluster.u32 %0, %1, %2;" : "=r"(a) : "r"(BAR_EMPTY(sb, 0)), "r"((tw >> 5) & 1));
        base = __shfl_sync(0xffffffffu, a, 0); sig = (tw & ~32u) == 0;
    }
    __device__ __forceinline__ void operator()(uint32_t slot) const {
        if (sig) asm volatile("mbarrier.arrive.shared::cluster.b64 _, [%0];" :: "r"(base + 8 * slot) : "memory");
    }
};
struct LnRow { float rs0, nm0, rs1, nm1; };
struct Pipe {
    Rel rel; uint32_t p1, p2;
    __device__ __forceinline__ Pipe(uint32_t sb, uint32_t tw, uint32_t first) : rel(sb, tw), p1(first), p2(NSLOT) {}
    template <bool TWO> __device__ __forceinline__ void acquire(uint32_t sb, uint32_t af, const Ring& r) {
        const uint32_t b0 = BAR_FULL(sb, r.slot), b1 = b0 + af;
        const bool ready = TWO ? mbar_test2(b0, b1, r.par) : mbar_test(b0, r.par);
        wg_wait<1>();
        rel(p2);
        if (!ready) { if (TWO) mbar_wait2(b0, b1, r.par); else mbar_wait(b0, r.par); }
    }
    __device__ __forceinline__ void issued(uint32_t slot) { p2 = p1; p1 = slot; }
    __device__ __forceinline__ void drain1() { wg_wait<1>(); rel(p2); p2 = NSLOT; }
    __device__ __forceinline__ void drain0() { wg_wait<0>(); rel(p1); p1 = NSLOT; }
    template <bool TWO, class Step> __device__ __forceinline__ void hold(int LG, uint32_t sb, uint32_t af, Ring& r, uint32_t lag_bar, Step step) {
        Ring q = r;
#pragma unroll 1
        for (int i = 0; i < LG; ++i) { if (TWO) mbar_wait2(BAR_FULL(sb, q.slot), BAR_FULL(sb, q.slot) + af, q.par); else mbar_wait(BAR_FULL(sb, q.slot), q.par); q.next(); }
        mbar_wait(lag_bar, 0);
#pragma unroll 1
        do {
            step(r.slot);
            wg_wait<2>(); rel(p2); p2 = p1; p1 = r.slot;
            if (++r.slot == NSLOT) r.slot = 0;
        } while (r.slot != q.slot);
        r.par = q.par;
    }
};
template <bool TWO, bool FIRST, int NA, int NB>
__device__ __forceinline__ void step32(float (&aa)[NA], float (&ab)[NB], uint32_t sb, uint32_t wg, uint32_t slot, int own) {
    const uint32_t st = d16(sb) + slot * (SLOT >> 4);
    const uint32_t alo = own >= 0 ? d16(sb) + OFF_STG / 16 + wg * 1024 + (own >> 1) * 512 + (own & 1) * 4 : st + wg * 256;
    const uint32_t ahi = own >= 0 ? (1024 >> 4) | (1u << 30) : (512 >> 4) | (2u << 30);
    wg_fence();
#pragma unroll
    for (int k = 0; k < 2; ++k) {
        const uint64_t da = ((uint64_t)ahi << 32) | (alo + k * 2 + 0x10000);
        if constexpr (NA == 88) {
            const uint64_t d0 = mk_desc(st, 8192 + k * 2048, 8192, 1024, 1), d1 = mk_desc(st, 12288 + k * 2048, 8192, 1024, 1);
            if (FIRST && k == 0) { wgmma_n176_z(aa, da, d0); wgmma_n176_z(ab, da, d1); }
            else { wgmma_n176(aa, da, d0); wgmma_n176(ab, da, d1); }
        } else {
            const uint64_t d0 = mk_desc(st, 8192 + k * 2048, 4096, 1024, 1), d1 = mk_desc(st, 24576 + k * 2048, 4096, 1024, 1);
            if (FIRST && k == 0) { wgmma_n256_z(aa, da, d0); if constexpr (TWO) wgmma_n128_z(ab, da, d1); }
            else { wgmma_n256(aa, da, d0); if constexpr (TWO) wgmma_n128(ab, da, d1); }
        }
    }
    wg_commit();
}
template <bool TWO, int LG, int NA, int NB, class Mid, class Tail>
__device__ __forceinline__ void mainloop32(float (&aa)[NA], float (&ab)[NB], uint32_t sb, uint32_t wg, uint32_t tw, Ring& r, uint32_t lag_ev, int g0, Mid mid, Tail tail) {
    step32<TWO, true>(aa, ab, sb, wg, r.slot, TWO ? 0 : -1);
    TS(g0, 0);
    Pipe pp(sb, tw, r.slot);
    r.next();
    const int end = wg ? 32 : 32 - LG;
#pragma unroll 1
    for (int it = 1; it < end; ++it) {
        pp.acquire<TWO>(sb, wg ? 0 : AF_REL, r);
        step32<TWO, false>(aa, ab, sb, wg, r.slot, TWO && it < 4 ? it : -1);
        pp.issued(r.slot);
        TS(g0 + it, 0);
        r.next();
        mid(it);
    }
    if (wg == 0) { pp.drain1(); pp.drain0(); pp.hold<TWO>(LG, sb, AF_REL, r, BAR_ONE(sb, lag_ev), [&](uint32_t slot) { step32<TWO, false>(aa, ab, sb, 0, slot, -1); }); }
    if (wg == 1 && tw == 0) mbar_arrive(BAR_ONE(sb, lag_ev));
    pp.drain1();
    tail();
    pp.drain0();
    TS(g0 + 31, 1);
}
template <bool FIRST>
__device__ __forceinline__ void step64(float (&acc)[64], uint32_t sb, uint32_t wg, uint32_t slot, int own) {
    const uint32_t sbb = d16(sb) + slot * (SLOT >> 4), sa = own >= 0 ? d16(sb) + OFF_STG / 16 + wg * 1024 + own * 512 : sbb + wg * 512;
    wg_fence();
#pragma unroll
    for (int k = 0; k < 4; ++k) {
        const uint64_t da = mk_desc(sa, k * 32, 16, 1024, 1), db = mk_desc(sbb, 16384 + k * 2048, 8192, 1024, 1);
        if (FIRST && k == 0) wgmma_n128_z(acc, da, db); else wgmma_n128(acc, da, db);
    }
    wg_commit();
}
template <class Put, class Mid, class Tail>
__device__ __forceinline__ void mainloop64(float (&acc)[64], bool wo, uint32_t sb, uint32_t wg, uint32_t tw, Ring& r, Put put, Mid mid, Tail tail) {
    const int g0 = wo ? 32 : 144, nst = wo ? 16 : 56, lg = wo ? LAGW : LAGD; (void)g0;
    const uint32_t lag_bar = BAR_ONE(sb, wo ? EV_LAG4 : EV_LAG5), af = wo && !wg ? AF_REL : 0;
    if (!wo) CS(28);
    step64<true>(acc, sb, wg, r.slot, wo ? 0 : -1);
    if (!wo) CS(29);
    TS(g0, 0);
    Pipe pp(sb, tw, r.slot);
    r.next();
    int it = 1;
    auto run = [&](int end, int own, bool with_put) {
#pragma unroll 1
        do {
            pp.acquire<true>(sb, af, r);
            step64<false>(acc, sb, wg, r.slot, own);
            pp.issued(r.slot);
            TS(g0 + it, 0);
            if (wo && it == 2) CS(9);
            r.next();
            if (with_put && it == (wg ? PUTD1 : PUTD0)) put();
        } while (++it < end);
    };
    const int end = wg ? nst : nst - lg;
    run(wo ? 2 : wg ? MIDD : end, wo ? 1 : -1, true);
    mid();
    if (wo) { pp.drain1(); pp.drain0(); TS(g0 + 1, 1); }
    if (it < end) run(end, -1, false);
    if (wg == 0) { pp.drain1(); pp.drain0(); pp.hold<true>(lg, sb, af, r, lag_bar, [&](uint32_t slot) { step64<false>(acc, sb, 0, slot, -1); }); }
    if (wg == 1 && tw == 0) mbar_arrive(lag_bar);
    pp.drain1();
    tail();
    pp.drain0();
    TS(g0 + nst - 1, 1);
}

struct RowAcc {
    float sm[4] = {0.f, 0.f, 0.f, 0.f}, sq[4] = {0.f, 0.f, 0.f, 0.f};
    __device__ __forceinline__ void add(int e, float x) { sm[e & 3] += x; sq[e & 3] = fmaf(x, x, sq[e & 3]); }
    __device__ __forceinline__ void publish(uint4* dst, uint32_t q4, uint32_t ep) const {
        const float s0 = sm[0] + sm[1], s1 = sm[2] + sm[3], q0 = sq[0] + sq[1], q1 = sq[2] + sq[3];
        const bool od = q4 & 1;
        float sv = (od ? s1 : s0) + __shfl_xor_sync(0xffffffffu, od ? s0 : s1, 1), qv = (od ? q1 : q0) + __shfl_xor_sync(0xffffffffu, od ? q0 : q1, 1);
        sv += __shfl_xor_sync(0xffffffffu, sv, 2); qv += __shfl_xor_sync(0xffffffffu, qv, 2);
        st_pkt16(dst + (q4 & 1) * 8, 0, __float_as_uint(sv), __float_as_uint(qv), ep);
    }
};
__device__ __forceinline__ LnRow merge_stats(const uint4* src, uint32_t q4, uint32_t ep, uint32_t sb) {
    uint4 t[4];
    uint32_t n = 0;
    while (true) {
#pragma unroll
        for (int i = 0; i < 4; ++i) t[i] = ld_pkt16(src + (q4 * 2 + (i >> 1)) * 512 + (i & 1) * 8);
        const bool ok_ = __all_sync(0xffffffffu, t[0].w == ep && t[1].w == ep && t[2].w == ep && t[3].w == ep);
        if (n < 4) CS(14 + n);
        if (ok_) break;
        SPIN_GUARD(n);
    }
    float v[4];
#pragma unroll
    for (int h = 0; h < 2; ++h) { v[h] = __uint_as_float(t[h].y) + __uint_as_float(t[2 + h].y); v[2 + h] = __uint_as_float(t[h].z) + __uint_as_float(t[2 + h].z); }
#pragma unroll
    for (int o = 1; o < 4; o <<= 1)
#pragma unroll
        for (int i = 0; i < 4; ++i) v[i] += __shfl_xor_sync(0xffffffffu, v[i], o);
    const float m0 = v[0] * (1.f / D_), m1 = v[1] * (1.f / D_);
    const float r0 = rsq(fmaxf(fmaf(-m0, m0, v[2] * (1.f / D_)), 0.f) + 1e-5f), r1 = rsq(fmaxf(fmaf(-m1, m1, v[3] * (1.f / D_)), 0.f) + 1e-5f);
    return LnRow{r0, -m0 * r0, r1, -m1 * r1};
}
struct Stg {
    uint32_t b, par;
    __device__ __forceinline__ uint32_t acquire2(uint32_t sb, uint32_t wg) {
        mbar_wait2(BAR_SREADY(sb, wg * 2), BAR_SREADY(sb, wg * 2 + 1), par);
        par ^= 1;
        return sb + OFF_STG + wg * 16384;
    }
    __device__ __forceinline__ void publish(uint32_t sb, uint32_t wg, uint32_t lane) {
        fence_async_smem();
        __syncwarp();
        if (lane == 0) mbar_arrive(BAR_SFULL(sb, wg * 2 + b));
        b ^= 1;
    }
};

struct LnPar {
    uint4 p[8];
    __device__ __forceinline__ void load(uint32_t sb, uint32_t q4) {
#pragma unroll
        for (int i = 0; i < 8; ++i) p[i] = lds128(sb + OFF_PAR + i * 64 + q4 * 16);
    }
};
__device__ __forceinline__ void ln_norm(uint32_t (&xn)[32], const float (&x)[64], const LnRow& n) {
#pragma unroll
    for (int e = 0; e < 32; ++e) {
        const float rs = (e & 1) ? n.rs1 : n.rs0, nm = (e & 1) ? n.nm1 : n.nm0;
        xn[e] = pack2(fmaf(x[2 * e], rs, nm), fmaf(x[2 * e + 1], rs, nm));
    }
}
__device__ __forceinline__ void ln_emit(const uint32_t (&xr)[32], const LnPar& lp, uint32_t sb, uint32_t wg, const Idx& ix) {
#pragma unroll
    for (int i = 0; i < 8; ++i)
        stsm4(sb + OFF_STG + wg * 16384 + (i >> 2) * 8192 + (ix.pan ^ ((i & 3) << 5)), hfma2_bf16(xr[4 * i], lp.p[i].z, lp.p[i].x), hfma2_bf16(xr[4 * i + 1], lp.p[i].z, lp.p[i].x),
              hfma2_bf16(xr[4 * i + 2], lp.p[i].w, lp.p[i].y), hfma2_bf16(xr[4 * i + 3], lp.p[i].w, lp.p[i].y));
    fence_async_smem();
    __syncwarp();
    if (ix.lane < 2) mbar_arrive(BAR_SFULL(sb, wg * 2 + ix.lane));
    bar_sync(1 + wg, 128);
}
__device__ __forceinline__ void load_slab(uint32_t (&xr)[32], uint32_t buf) {
    IDX();
#pragma unroll
    for (int i = 0; i < 8; ++i) ldsm4(buf + (i >> 2) * 8192 + (pan_addr ^ ((i & 3) << 5)), xr[4 * i], xr[4 * i + 1], xr[4 * i + 2], xr[4 * i + 3]);
}
__device__ __forceinline__ void unpack_slab(float (&x)[64], const uint32_t (&xr)[32]) {
#pragma unroll
    for (int i = 0; i < 32; ++i) unpack2(xr[i], x[2 * i], x[2 * i + 1]);
}
__device__ __forceinline__ void store_slab(const float (&x)[64], uint32_t buf, uint32_t pitch, uint32_t pan, int i0, int i1) {
#pragma unroll
    for (int i = i0; i < i1; ++i)
        stsm4(buf + (i >> 2) * pitch + (pan ^ ((i & 3) << 5)), pack2(x[8 * i], x[8 * i + 1]), pack2(x[8 * i + 2], x[8 * i + 3]), pack2(x[8 * i + 4], x[8 * i + 5]), pack2(x[8 * i + 6], x[8 * i + 7]));
}
template <int NP, class Done>
__device__ __forceinline__ void fetch_halo(uint4* src, bool first, uint32_t dst, Done done) {
    uint4 hv[4 * NP];
    uint32_t n = 0;
    while (true) {
        bool ok = true;
#pragma unroll
        for (int i = 0; i < 4 * NP; ++i) { hv[i] = first ? make_uint4(0, 0, 0, 0) : ld_pkt16(src + (i >> 2) * 256 + (i & 3) * 32); ok = ok && hv[i].x != 0; }
        if (first || __all_sync(0xffffffffu, ok)) break;
        SPIN_GUARD(n);
    }
#pragma unroll
    for (int i = 0; i < 4 * NP; ++i) stsm4(dst + (i >> 2) * 4096 + (i & 3) * 512, hv[i].x, hv[i].y, hv[i].z, hv[i].w);
    done();
    if (!first) {
#pragma unroll
        for (int i = 0; i < 4 * NP; ++i) src[(i >> 2) * 256 + (i & 3) * 32] = make_uint4(0, 0, 0, 0);
    }
}

template <int N, class G, class U>
__device__ __forceinline__ void glu(uint32_t (&h)[N], G g, U u) {
#pragma unroll
    for (int i = 0; i < N; ++i) h[i] = pack2(fmaf(tanh_(g(2 * i)), u(2 * i), u(2 * i)), fmaf(tanh_(g(2 * i + 1)), u(2 * i + 1), u(2 * i + 1)));
}
__device__ __forceinline__ void put_h(const uint32_t (&h)[32], uint32_t sb, uint32_t wg, Stg& stg) {
    IDX();
    const uint32_t buf = stg.acquire2(sb, wg);
#pragma unroll
    for (int k = 0; k < 8; ++k) stsm4(buf + (k >> 2) * 8192 + (pan_addr ^ ((k & 3) << 5)), h[4 * k], h[4 * k + 1], h[4 * k + 2], h[4 * k + 3]);
    fence_async_smem();
    __syncwarp();
    if (lane < 2) mbar_arrive(BAR_SFULL(sb, wg * 2 + lane));
}

template <int NP, bool PREV>
__device__ __forceinline__ void passes128(uint32_t (&hp)[32], uint32_t sb, uint32_t wg, uint32_t tw, Ring& r, Stg& stg) {
#pragma unroll 1
    for (int p = 0; p < NP; ++p) {
        float b256[128], none[1];
        const int put_at = !PREV && p == 0 ? -1 : wg ? PUT1 : PUT0;
        mainloop32<false, LAGS>(b256, none, sb, wg, tw, r, EV_LAG2 + p, 80 + 32 * (p & 1), [&](int it) { if (it == put_at) put_h(hp, sb, wg, stg); },
                                [&] { if (PREV || p < NP - 1) mbar_wait(BAR_FULL(sb, r.slot), r.par); });
        if (threadIdx.x == 0) { TL(29 + 2 * p); TC(114 + 2 * p); }
        if (threadIdx.x == 128) TL(53 + 2 * (p & 1));
        CS(24 + 2 * (p & 1));
        glu(hp, [&](int i) { return b256[i + (i & 32)]; }, [&](int i) { return b256[i + (i & 32) + 32]; });
        if (threadIdx.x == 0) { TL(30 + 2 * p); TC(115 + 2 * p); }
        if (threadIdx.x == 128) TL(54 + 2 * (p & 1));
        CS(25 + 2 * (p & 1));
    }
}

__global__ void __launch_bounds__(384, 1)
fused_block_kernel(const __grid_constant__ Ptrs pt, const __grid_constant__ Maps mp) {
    uint32_t* const g_flags = pt.mail->flags;
    uint2* const g_mod = pt.mail->mod;
    uint4* const g_st1 = pt.mail->st1;
    uint32_t* const g_par2 = pt.mail->par2;
    uint4* const g_halo = pt.mail->halo;
    const __nv_bfloat16* __restrict__ cvec = pt.c;
    if (threadIdx.x == 224) { prefetch_map(&mp.wm8); prefetch_map(&mp.x); }
    extern __shared__ __align__(1024) uint8_t smem[];
    const uint32_t sb = smem_u32(smem);
    const uint32_t tid = threadIdx.x, tw = tid & 127, lane = tid & 31;
    const uint32_t warp = __shfl_sync(0xffffffffu, tid >> 5, 0), wg = warp >> 2;
    uint32_t rank; asm("mov.u32 %0, %%cluster_ctarank;" : "=r"(rank));
    rank = __shfl_sync(0xffffffffu, rank, 0);
    uint32_t ep;
    uint32_t smid; asm volatile("mov.u32 %0, %%smid;" : "=r"(smid));
    const int c = __shfl_sync(0xffffffffu, smid >> 1, 0);
    const int c7 = ((c - 32) * 37) >> 8;
    int grp = c < 32 ? c & 7 : c < 60 ? c - 31 - 7 * c7 : c < 62 ? -1 : 0;
    const int j = c < 32 ? c >> 3 : c < 60 ? 4 + c7 : c < 62 ? (c - 60) * 2 + rank : c - 58;
    const bool aux = grp < 0;
    const int m = grp * 2 + rank;
    uint4* const g_st2 = g_halo + (m > 0 ? (m - 1) * 8 * 512 : 128);

    bool cluster_arrive_early = false;
    if (wg < 2) {
      if (!KDEBUG) cluster_arrive();
      ep = flag_get(g_flags + FL_DONE);
      uint16_t cw[8];
      {
          const __nv_bfloat16* cp = cvec + ((tw >> 5) * 32 + (tw & 3) * 2) * 8 + (lane >> 2);
#pragma unroll
          for (int i = 0; i < 8; ++i) asm volatile("ld.global.nc.u16 %0, [%1];" : "=h"(cw[i]) : "l"(cp + (i >> 1) * 64 + (i & 1) * 8));
      }
      asm volatile("setmaxnreg.inc.sync.aligned.u32 224;");
      if (tid == 0) TL(58);
      if (KDEBUG) cluster_arrive();
      Ring r{0, 0};
      Stg stg{0, 0};
      if (aux) {
        if (wg == 0) {
            const uint4 cv = *(const uint4*)(cvec + tw * 8);
            sts128(sb + OFF_STG + (tw >> 3) * 1024 + (tw & 7) * 16, pack2(silu_(bf_lo(cv.x)), silu_(bf_hi(cv.x))), pack2(silu_(bf_lo(cv.y)), silu_(bf_hi(cv.y))),
                   pack2(silu_(bf_lo(cv.z)), silu_(bf_hi(cv.z))), pack2(silu_(bf_lo(cv.w)), silu_(bf_hi(cv.w))));
            fence_async_smem();
        }
        cluster_wait();
        ep = __shfl_sync(0xffffffffu, ep, 0) / NCTA + 1;
        if (wg == 0) {
            bar_sync(1, 128);
#pragma unroll 1
            for (int p = 0; p < 4; ++p) {
                float acc[128];
#pragma unroll
                for (int i = 0; i < 128; ++i) acc[i] = 0.f;
                uint32_t prev = 0;
#pragma unroll 1
                for (int kc = 0; kc < 16; ++kc) {
                    mbar_wait(BAR_FULL(sb, r.slot), r.par);
                    wg_fence();
#pragma unroll
                    for (int k = 0; k < 4; ++k)
                        wgmma_n256(acc, mk_desc(d16(sb) + kc * 64, OFF_STG + k * 32, 16, 0, 1), mk_desc(d16(sb) + r.slot * (SLOT >> 4), k * 2048, 8192, 1024, 1));
                    wg_commit();
                    wg_wait<1>();
                    if (kc > 0 && tw < 4) mbar_arrive(BAR_EMPTY(sb, prev));
                    prev = r.slot;
                    r.next();
                }
                wg_wait<0>();
                if (tw < 4) mbar_arrive(BAR_EMPTY(sb, prev));
                if (tw < 4) {
#pragma unroll
                    for (int jn = 0; jn < 32; ++jn) sts32(sb + OFF_TAB + (jn * 4 + tw) * 4, pack2(acc[jn * 4], acc[jn * 4 + 1]));
                }
                bar_sync(1, 128);
                const int vec = 2 + p, blk = p * 4 + j;
                const uint32_t val = lds32(sb + OFF_TAB + tw * 4);
                if (vec == 2 || vec == 5) st_pkt(g_mod + (8 + blk) * 128 + tw, val, ep);
                else {
                    const float one = vec == 4 ? 1.f : 0.f;
                    g_par2[((blk & 3) * 16 + (tw >> 3)) * 16 + (tw & 3) * 4 + (vec - 3) * 2 + ((tw >> 2) & 1)] =
                        pack2(0.5f * bf_round(one + bf_lo(val)), 0.5f * bf_round(one + bf_hi(val)));
                }
                bar_sync(1, 128);
                if (tw == 0) {
                    if (vec == 3 || vec == 4) asm volatile("red.release.gpu.global.add.u32 [%0], 1;" :: "l"(&g_flags[FL_LN2]) : "memory");
                    TL(1 + p);
                }
            }
            if (lane < 2) mbar_arrive_cta(BAR_ONE(sb, EV_P0), lane);
        }
        r = Ring{64 % NSLOT, (64 / NSLOT) & 1};
        mbar_wait(BAR_ONE(sb, EV_P0), 0);
        mbar_wait(BAR_FULL(sb, r.slot), r.par);
        uint32_t hp[32] = {};
        passes128<4, false>(hp, sb, wg, tw, r, stg);
        put_h(hp, sb, wg, stg);
      } else {
        float xs[64];
        uint32_t xp[32];
        {
            sts128(sb + tid * 16, pack2(silu_(bf_lo(cw[0])), silu_(bf_lo(cw[1]))), pack2(silu_(bf_lo(cw[2])), silu_(bf_lo(cw[3]))),
                   pack2(silu_(bf_lo(cw[4])), silu_(bf_lo(cw[5]))), pack2(silu_(bf_lo(cw[6])), silu_(bf_lo(cw[7]))));
            cluster_wait();
            ep = __shfl_sync(0xffffffffu, ep, 0) / NCTA + 1;
            load_slab(xp, stg.acquire2(sb, wg));
            unpack_slab(xs, xp);
            if (tid == 0) TL(24);
            if (tid == 128) TL(27);
        }
#pragma unroll 1
        for (int blk = 0; ; ++blk) {
        {
            IDX();
            uint4* const st = (blk ? g_st2 : g_st1 + m * 8 * 512) + wg * 64 + w4 * 16 + g8;
            RowAcc ra;
#pragma unroll
            for (int e = 0; e < 64; ++e) ra.add(e, xs[e]);
            ra.publish(st + j * 512, q4, ep);
            uint32_t t_pub = 0; if (PDLY) asm volatile("mov.u32 %0, %%clock;" : "=r"(t_pub));
            if (tid == 0) TL(blk ? 9 : 26);
            if (tid == 128 && blk) TL(34);
            if (blk) CS(11);
            LnPar lp;
            if (blk == 0) {
            uint4* const mod_out = pt.mail->mod1 + g8 * 512 + (m * 8 + j) * 4 + q4;
            if (wg == 0) {
                uint4 af[8];
#pragma unroll
                for (int i = 0; i < 8; ++i) af[i] = lds128(sb + w4 * 512 + i * 64 + q4 * 16);
                float c[4][4] = {};
#pragma unroll
                for (int i = 0; i < 8; ++i) {
                    if (!(i & 1)) mbar_wait(BAR_ONE(sb, EV_WIN + (i >> 1)), 0);
                    if (i == 6 && tid == 0) TL(25);
#pragma unroll
                    for (int h = 0; h < 2; ++h) {
                        uint32_t b0, b1, b2, b3;
                        ldsm4t(sb + 5 * SLOT + i * 4096 + w4 * 1024 + h * 512 + (lane & 15) * 32 + (lane >> 4) * 16, b0, b1, b2, b3);
                        mma16816(c[2 * h], h ? af[i].z : af[i].x, 0u, h ? af[i].w : af[i].y, 0u, b0, b1);
                        mma16816(c[2 * h + 1], h ? af[i].z : af[i].x, 0u, h ? af[i].w : af[i].y, 0u, b2, b3);
                    }
                }
                if (lane < 4) sts128(sb + OFF_TAB + w4 * 64 + lane * 16, __float_as_uint(c[0][0] + c[2][0]), __float_as_uint(c[0][1] + c[2][1]),
                                     __float_as_uint(c[1][0] + c[3][0]), __float_as_uint(c[1][1] + c[3][1]));
                if (lane < 2) mbar_arrive_cta(BAR_ONE(sb, EV_P0), lane);
                bar_sync(1, 128);
                if (w4 == 0) {
                    float a[4] = {0.f, 0.f, 0.f, 0.f};
#pragma unroll
                    for (int i = 0; i < 4; ++i) {
                        const uint4 t = lds128(sb + OFF_TAB + i * 64 + q4 * 16);
                        a[0] += __uint_as_float(t.x); a[1] += __uint_as_float(t.y); a[2] += __uint_as_float(t.z); a[3] += __uint_as_float(t.w);
                    }
                    const float add = m >= 8 ? 1.f : 0.f;
                    st_pkt16(mod_out, pack2(bf_round(a[0]) + add, bf_round(a[1]) + add), pack2(bf_round(a[2]) + add, bf_round(a[3]) + add), ep, 0);
                    if (tid == 0) TL(3);
                }
            } else if (LWAIT >= 0) mbar_wait(BAR_ONE(sb, EV_WIN + LWAIT), 0);
            } else {
                mbar_wait2(BAR_ONE(sb, EV_LN2), BAR_FULL(sb, 0), 0);
            }
            lp.load(sb, q4);
#pragma unroll
            for (int e = 0; e < 32; ++e) xp[e] = pack2(xs[2 * e], xs[2 * e + 1]);
            if (PDLY && blk) { uint32_t t1; do { asm volatile("mov.u32 %0, %%clock;" : "=r"(t1)); } while (t1 - t_pub < PDLY); }
            if (blk) CS(13);
            const LnRow n = merge_stats(st, q4, ep, sb);
            if (tid == 0) TL(blk ? 49 : 48);
            if (tid == 128) TL(blk ? 45 : 28);
            if (blk) CS(18);
            uint32_t xn[32];
            ln_norm(xn, xs, n);
            if (blk == 0) {
                mbar_wait2(BAR_FULL(sb, 0), BAR_ONE(sb, EV_PAR), 0);
                if (FD0 && wg == 0) { uint32_t t0, t1; asm volatile("mov.u32 %0, %%clock;" : "=r"(t0)); do { asm volatile("mov.u32 %0, %%clock;" : "=r"(t1)); } while (t1 - t0 < FD0); }
                lp.load(sb, q4);
            }
            ln_emit(xn, lp, sb, wg, ix);
            if (tid == 0) { TL(blk ? 36 : 8); TC(blk ? 109 : 103); }
            if (tid == 128) TL(blk ? 43 : 22);
            if (blk) CS(21);
        }
        uint32_t hp[32];
        if (blk == 0) {
        {
            float big[128], sml[64];
            step32<true, true>(big, sml, sb, wg, r.slot, 0);
            TS(0, 0);
            Pipe pp(sb, tw, r.slot);
            r.next();
#pragma unroll 1
            for (int it = 1; it < 32 - LAGQ; ++it) {
                pp.acquire<true>(sb, wg ? 0 : AF_REL, r);
                step32<true, false>(big, sml, sb, wg, r.slot, it < 4 ? it : -1);
                pp.issued(r.slot);
                TS(it, 0);
                r.next();
            }
            auto half = [&](uint32_t slot, bool rest) {
                const uint32_t st = d16(sb) + slot * (SLOT >> 4);
#pragma unroll
                for (int k = 0; k < 2; ++k) {
                    const uint64_t da = mk_desc(st + wg * 256, k * 32, 16, 512, 2);
                    if (rest) wgmma_n256(big, da, mk_desc(st, 8192 + k * 2048, 4096, 1024, 1)); else wgmma_n128(sml, da, mk_desc(st, 24576 + k * 2048, 4096, 1024, 1));
                }
            };
            auto rest = [&](bool each) {
                wg_fence();
#pragma unroll
                for (int it = 32 - LAGQ; it < 32; ++it) { if (each && it > 32 - LAGQ) wg_fence(); half(it % NSLOT, true); if (each || it == 31) wg_commit(); }
            };
            stg.acquire2(sb, wg); mbar_wait2(BAR_SREADY(sb, 2), BAR_SREADY(sb, 3), 1);
#pragma unroll 1
            for (int it = 32 - LAGQ; it < 32; ++it) {
                pp.acquire<true>(sb, wg ? 0 : AF_REL, r);
                wg_fence(); half(r.slot, false); wg_commit();
                pp.issued(NSLOT);
                TS(it, 0);
                r.next();
            }
            if (wg) { rest(false); wg_wait<1>(); } else wg_wait<0>();
            CS(8);
            IDX();
            uint32_t k0[8], k1[8], k2[8], v0[8], v1[8], v2[8];
            const uint32_t nxt = warp + ((warp & 1) ? 3 : 1), mine = sb + OFF_STG + wg * 16384 + w4 * 2048;
            auto tails = [&](const float* kv, uint32_t (&kt)[8], uint32_t (&vt)[8]) {
#pragma unroll
                for (int t = 0; t < 8; ++t) { kt[t] = pack2(kv[4 * t + 2], kv[4 * t + 3]); vt[t] = pack2(kv[32 + 4 * t + 2], kv[32 + 4 * t + 3]); }
            };
            auto post = [&](int pn, uint32_t (&kt)[8], uint32_t (&vt)[8]) {
                uint4* dst = g_halo + (m * 8 + j) * 512 + (w4 >> 1) * 256 + pn * 128 + lane;
#pragma unroll
                for (int h = 0; h < 2; ++h) { if (!kt[4 * h]) kt[4 * h] = 0x8000u; if (!vt[4 * h]) vt[4 * h] = 0x8000u; }
#pragma unroll
                for (int h = 0; h < 2; ++h) { st_pkt16(dst + h * 32, kt[4 * h], kt[4 * h + 1], kt[4 * h + 2], kt[4 * h + 3]); st_pkt16(dst + 64 + h * 32, vt[4 * h], vt[4 * h + 1], vt[4 * h + 2], vt[4 * h + 3]); }
            };
            auto prepare = [&](int pn, const float* kv) {
                tails(kv, k2, v2);
                if (nxt < 8) {
                    const uint32_t dst = sb + OFF_STG + (nxt >> 2) * 16384 + (nxt & 3) * 2048 + pn * 8192 + lane * 16;
#pragma unroll
                    for (int h = 0; h < 2; ++h) { stsm4(dst + h * 512, k2[4 * h], k2[4 * h + 1], k2[4 * h + 2], k2[4 * h + 3]); stsm4(dst + 1024 + h * 512, v2[4 * h], v2[4 * h + 1], v2[4 * h + 2], v2[4 * h + 3]); }
                    if (pn == 0) bar_arrive(NB_TAIL + nxt, 64);
                    else { __syncwarp(); if (lane == 0) mbar_arrive(BAR_ONE(sb, EV_TAIL + nxt)); }
                } else if (pn == 0 && m < 15) post(0, k2, v2);
#pragma unroll
                for (int t = 0; t < 8; ++t) { k1[t] = pack2(kv[4 * t], kv[4 * t + 1]); v1[t] = movm(pack2(kv[32 + 4 * t], kv[32 + 4 * t + 1])); v2[t] = movm(v2[t]); }
                if (pn == 0) { CS(2); if (wg == 0) { rest(true); wg_wait<3>(); pp.rel(28 % NSLOT); wg_wait<2>(); pp.rel(29 % NSLOT); wg_wait<1>(); pp.rel(30 % NSLOT); } bar_sync(NB_TAIL + warp, 64); CS(4); }
                else mbar_wait(BAR_ONE(sb, EV_TAIL + __shfl_sync(0xffffffffu, warp, 0)), 0);
#pragma unroll
                for (int h = 0; h < 2; ++h) {
                    ldsm4(mine + pn * 8192 + lane * 16 + h * 512, k0[4 * h], k0[4 * h + 1], k0[4 * h + 2], k0[4 * h + 3]);
                    ldsm4t(mine + pn * 8192 + lane * 16 + 1024 + h * 512, v0[4 * h], v0[4 * h + 1], v0[4 * h + 2], v0[4 * h + 3]);
                }
            };
#pragma unroll
            for (int i = 0; i < 64; ++i) asm volatile("" : "+f"(sml[i]) :: "memory");
            prepare(0, sml);
            static_assert(LAGQ == 4, "");
            wg_wait<0>();
            if (wg) { pp.rel(28 % NSLOT); pp.rel(29 % NSLOT); pp.rel(30 % NSLOT); }
            pp.rel(31 % NSLOT);
            TS(31, 1);
            if (tid == 0) { TL(4); TC(104); }
            if (tid == 128) TL(50);
            CS(1);
#pragma unroll
            for (int i = 0; i < 128; ++i) asm volatile("" : "+f"(big[i]) :: "memory");
            if (nxt >= 8 && m < 15) { uint32_t kt[8], vt[8]; tails(big, kt, vt); post(1, kt, vt); }
            const bool lo0 = q4 * 2 > g8, lo1 = q4 * 2 + 1 > g8;
            const bool nopast = m == 0 && (warp & 5) == 0;
            const uint32_t lomask = (lo0 ? 0xFFFFu : 0u) | (lo1 ? 0xFFFF0000u : 0u);
            const uint32_t orow = mine + (lane & 7) * 128 + (((lane >> 3) ^ (lane & 7)) << 4);
            const float sl2 = 0.17677669529663687f * 1.4426950408889634f;
#pragma unroll
            for (int pn = 0; pn < 2; ++pn) {
                float e0[4], e1[4], mx[4], sum[4];
#pragma unroll
                for (int hh = 0; hh < 2; ++hh) {
                    uint32_t qf[8];
#pragma unroll
                    for (int i = 0; i < 8; ++i) qf[i] = pack2(big[64 + 32 * pn + 16 * hh + 2 * i], big[64 + 32 * pn + 16 * hh + 2 * i + 1]);
                    float s[3][4];
#pragma unroll
                    for (int t = 0; t < 3; ++t) {
                        const uint32_t* k = (t == 0 ? k0 : t == 1 ? k1 : k2) + 4 * hh;
                        s[t][0] = s[t][1] = s[t][2] = s[t][3] = 0.f;
                        mma16816(s[t], qf[0], qf[1], qf[2], qf[3], k[0], k[1]);
                        mma16816(s[t], qf[4], qf[5], qf[6], qf[7], k[2], k[3]);
                    }
#pragma unroll
                    for (int hf = 0; hf < 2; ++hf) {
                        const int u = hh * 2 + hf;
                        e0[u] = lo0 ? ((hf == 0 && nopast) ? -INFINITY : s[hf][hf * 2]) : s[hf + 1][hf * 2];
                        e1[u] = lo1 ? ((hf == 0 && nopast) ? -INFINITY : s[hf][hf * 2 + 1]) : s[hf + 1][hf * 2 + 1];
                        mx[u] = fmaxf(e0[u], e1[u]);
                    }
                }
#pragma unroll
                for (int o = 1; o < 4; o <<= 1)
#pragma unroll
                    for (int u = 0; u < 4; ++u) mx[u] = fmaxf(mx[u], __shfl_xor_sync(0xffffffffu, mx[u], o));
#pragma unroll
                for (int u = 0; u < 4; ++u) {
                    const float c = -mx[u] * sl2;
                    e0[u] = ex2(fmaf(e0[u], sl2, c)); e1[u] = ex2(fmaf(e1[u], sl2, c));
                    sum[u] = e0[u] + e1[u];
                }
#pragma unroll
                for (int o = 1; o < 4; o <<= 1)
#pragma unroll
                    for (int u = 0; u < 4; ++u) sum[u] += __shfl_xor_sync(0xffffffffu, sum[u], o);
#pragma unroll
                for (int u = 0; u < 4; ++u) {
                    const int h = u >> 1;
                    const float inv = rcp(sum[u]);
                    const uint32_t p = pack2(e0[u] * inv, e1[u] * inv);
                    const uint32_t* va = ((u & 1) ? v1 : v0) + 4 * h;
                    const uint32_t* vb = ((u & 1) ? v2 : v1) + 4 * h;
                    float o[2][4] = {};
#pragma unroll
                    for (int d = 0; d < 2; ++d) mma16816(o[d], va[2 * d], va[2 * d + 1], vb[2 * d], vb[2 * d + 1], p & lomask, p & ~lomask);
                    stsm4t((orow ^ ((u >> 1) << 6)) + pn * 8192 + (u & 1) * 1024, pack2(o[0][0], o[0][1]), pack2(o[0][2], o[0][3]), pack2(o[1][0], o[1][1]), pack2(o[1][2], o[1][3]));
                }
                fence_async_smem();
                __syncwarp();
                if (lane == 0) mbar_arrive(BAR_SFULL(sb, wg * 2 + pn));
                if (pn == 0) { CS(5); block_end(sb, 0); prepare(1, big); CS(3); }
            }
            CS(6);
            if (tid == 32) TL(41);
            mbar_wait2(BAR_FULL(sb, 32 % NSLOT), BAR_FULL(sb, 33 % NSLOT), (32 / NSLOT) & 1);
            load_slab(xp, sb + (32 % NSLOT + wg) * SLOT);
#pragma unroll
            for (int e = 0; e < 32; ++e) hp[e] = __float_as_uint(big[e]);
            bar_sync(1 + wg, 128);
            if (tid == 0) { TL(6); TC(106); }
            if (tid == 128) TL(44);
            CS(7);
        }
        } else {
        {
            float ag[88], au[88];
            mainloop32<true, LAG>(ag, au, sb, wg, tw, r, EV_LAG1, 48, [](int) {}, [&] {
                Ring q = r; if (!wg) q.next();
                mbar_wait(BAR_EMPTY(sb, q.slot), q.par ^ 1);
                mbar_wait(BAR_FULL(sb, r.slot), r.par);
            });
            if (tid == 0) { TL(10); TC(110); }
            if (tid == 128) TL(51);
            CS(22);
            {
                IDX();
                uint32_t h3[12];
                glu(h3, [&](int i) { return ag[64 + i]; }, [&](int i) { return au[64 + i]; });
#pragma unroll
                for (int k = 0; k < 3; ++k) stsm4(sb + (wg ? P3_SLOT1 : P3_SLOT0) * SLOT + 24576 + (pan_addr ^ (k << 5)), h3[4 * k], h3[4 * k + 1], h3[4 * k + 2], h3[4 * k + 3]);
            }
            glu(hp, [&](int i) { return ag[i]; }, [&](int i) { return au[i]; });
            if (tid == 0) { TL(11); TC(111); }
            if (tid == 128) TL(52);
            CS(23);
        }
        passes128<2, true>(hp, sb, wg, tw, r, stg);
        if (tid == 0) { TL(12); TC(112); }
        }
        {
            float acc[64], gf[32];
            mainloop64(acc, blk == 0, sb, wg, tw, r, [&] { put_h(hp, sb, wg, stg); }, [&] {
                mbar_wait(BAR_ONE(sb, EV_GA + blk), 0);
                unpack_slab(xs, xp);
                uint32_t gt[16];
#pragma unroll
                for (int cg = 0; cg < 16; ++cg) gt[cg] = lds32(sb + OFF_TAB + blk * 256 + cg * 16 + (tw & 3) * 4);
#pragma unroll
                for (int i = 0; i < 16; ++i) unpack2(gt[i], gf[2 * i], gf[2 * i + 1]);
            }, [&] { stg.acquire2(sb, wg); });
            if (tid == 0) { TL(blk ? 13 : 7); TC(blk ? 113 : 107); }
            if (tid == 128) TL(blk ? 57 : 42);
            CS(blk ? 30 : 10);
#pragma unroll
            for (int e = 0; e < 64; ++e) xs[e] = fmaf(gf[(e >> 2) * 2 + (e & 1)], acc[e], xs[e]);
        }
        if (blk) break;
        }
        {
            IDX();
#pragma unroll
            for (int p = 0; p < 2; ++p) {
                store_slab(xs, sb + OFF_STG + wg * 16384, 8192, pan_addr, 4 * p, 4 * p + 4);
                stg.publish(sb, wg, lane);
            }
            cluster_arrive();
            if (tid == 0) TL(14);
            CS(31);
        }
      }
    } else {
        if (warp == 8 && !aux && elect_one()) {
#pragma unroll
            for (int i = 0; i < 4; ++i) mbar_init(BAR_SREADY(sb, i), 1);
#pragma unroll
            for (int i = 0; i < 4; ++i) mbar_init(BAR_ONE(sb, EV_WIN + i), 1);
#pragma unroll
            for (int i = 0; i < 4; ++i) {
                mbar_expect_tx(BAR_SREADY(sb, i), 8192);
                tma_load3(sb + OFF_STG + i * 8192, &mp.x, j * 128 + (i & 1) * 64, m * 64 + (i >> 1) * 32, BAR_SREADY(sb, i));
            }
#pragma unroll 1
            for (int i = 0; i < 4; ++i) {
                mbar_expect_tx(BAR_ONE(sb, EV_WIN + i), 8192);
                tma_load(sb + 5 * SLOT + i * 8192, &mp.wm8, 2 * i * 6144 + (m * 8 + j) * 16, 0, BAR_ONE(sb, EV_WIN + i));
                tma_load(sb + 5 * SLOT + i * 8192 + 4096, &mp.wm8, (2 * i + 1) * 6144 + (m * 8 + j) * 16, 0, BAR_ONE(sb, EV_WIN + i));
            }
        }
        __syncwarp();
        asm volatile("setmaxnreg.dec.sync.aligned.u32 56;");
        if (elect_one()) {
            if (warp == 8) {
                prefetch_map(&mp.wqkv); prefetch_map(&mp.wmod);
            } else if (warp < 11) {
                mbar_init(BAR_EMPTY(sb, NSLOT), 1);
#pragma unroll
                for (int i = 0; i < 2; ++i) { mbar_init(BAR_SFULL(sb, (warp - 9) * 2 + i), 4); if (aux) mbar_init(BAR_SREADY(sb, (warp - 9) * 2 + i), 1); }
#pragma unroll
                for (int i = 0; i < 3; ++i) {
                    mbar_init(BAR_EMPTY(sb, (warp - 9) * 3 + i), 4);
                    mbar_init(BAR_FULL(sb, (warp - 9) * 3 + i), 1); mbar_init(BAR_FULL(sb, (warp - 9) * 3 + i) + AF_REL, 1);
                }
            } else {
#pragma unroll
                for (int i = EV_P0; i < EV_COUNT; ++i) mbar_init(BAR_ONE(sb, i), i == EV_P0 ? 8 : 1);
            }
            asm volatile("fence.mbarrier_init.release.cluster;" ::: "memory");
        }
        __syncwarp();
        cluster_arrive();
        ep = 0;
        if (warp != 8 || aux) ep = flag_get(g_flags + FL_DONE);
        cluster_wait();
        ep = __shfl_sync(0xffffffffu, ep, 0) / NCTA + 1;
        if (warp == 8) {
            const bool el = elect_one();
            Ring r{0, 1};
            if (aux) {
                {
                    uint32_t n = 0;
                    while (!__all_sync(0xffffffffu, ld_pkt16(pt.mail->mod1 + 256).z == ep)) { SPIN_GUARD(n); __nanosleep(200); }
                }
#pragma unroll 1
                for (int it = 0; it < 64; ++it) {
                    const int col = 2048 + (it >> 4) * 1024 + j * 256;
                    mbar_wait(BAR_EMPTY(sb, r.slot), r.par);
                    const uint32_t st = sb + r.slot * SLOT, fb = BAR_FULL(sb, r.slot);
                    if (el) {
                        mbar_expect_tx(fb, 32768);
#pragma unroll
                        for (int b = 0; b < 4; ++b) tma_load(st + b * 8192, &mp.wmod, col + b * 64, (it & 15) * 64, fb);
                    }
                    r.next();
                }
                mbar_wait(BAR_ONE(sb, EV_P0), 0);
                const CUtensorMap* wm = rank ? &mp.wu : &mp.wg;
#pragma unroll 1
                for (int g = 0; g < 128; ++g) {
                    const int mx = (j >> 1) * 8 + (g >> 5) * 2 + rank, k0 = ((g & 14) << 6) + ((g & 16) << 2) + ((g & 1) << 5);
                    if (!(g & 15)) {
                        uint32_t n = 0;
                        while (!__all_sync(0xffffffffu, (int32_t)(flag_get(g_flags + FL_PROG + fidx(mx, lane >> 4, (lane & 14) | ((g >> 4) & 1))) - (ep * 8 + ST_H2)) >= 0)) { SPIN_GUARD(n); __nanosleep(300); }
                    }
                    mbar_wait(BAR_EMPTY(sb, r.slot), r.par);
                    const uint32_t st = sb + r.slot * SLOT, fb = BAR_FULL(sb, r.slot);
                    if (el) {
                        mbar_expect_tx(fb, 24576);
                        tma_load_mc(st + 8192 + rank * 4096, wm, HC3, k0, fb);
                        tma_load_mc(st + 16384 + rank * 4096, wm, HC3 + 64, k0, fb);
                        tma_load(st, &mp.h2l, k0, mx * 128, fb);
                    }
                    r.next();
                }
            } else {
#pragma unroll 1
                for (int it = 0; it < 32; ++it) {
                    const int cb = j * 128 + rank * 64, k0 = kof(it, 2, j);
                    if (it == BW0) mbar_wait(BAR_ONE(sb, BWEV), 0);
                    if (it == BW1) mbar_wait(BAR_ONE(sb, EV_PAR), 0);
                    if (it == 5) mbar_wait(BAR_ONE(sb, EV_P0), 0);
                    if (it == AG0) mbar_wait(BAR_ONE(sb, (AGW & 1) ? EV_AGO : EV_FGO), 0);
                    mbar_wait(BAR_EMPTY(sb, r.slot), r.par);
                    const uint32_t st = sb + r.slot * SLOT, fb = BAR_FULL(sb, r.slot);
                    if (el) {
                        mbar_expect_tx(fb, it < 4 ? 24576 : 28672);
                        tma_load_mc(st + 24576 - rank * 16384, &mp.wqkv, 1024 + cb, k0, fb);
                        tma_load_mc(st + 28672 - rank * 16384, &mp.wqkv, 2048 + cb, k0, fb);
                        tma_load_mc(st + 16384 + rank * 4096, &mp.wqkv, cb, k0, fb);
                        if (it < 4) mbar_arrive(fb + AF_REL);
                        if (it == PFWO + (m >> 1)) { tma_prefetch(&mp.wo, j * 128, m * 64); tma_prefetch(&mp.wo, j * 128 + 64, m * 64); }
                        if (it >= PFG && it < PFG + PFN && (it & 7) == grp) {
                            const int kp = kof(it - PFG + PFO, 2, j);
                            tma_prefetch(rank ? &mp.wu : &mp.wg, hcol(0, j), kp); tma_prefetch(rank ? &mp.wu : &mp.wg, hcol(0, j) + 64, kp);
                            asm volatile("cp.async.bulk.prefetch.tensor.3d.L2.global [%0, {%1, %2, %3}];" :: "l"(rank ? &mp.wu3 : &mp.wg3), "r"(0), "r"(j), "r"(kp) : "memory");
                        }
                    }
                    r.next();
                }
                if (el) mbar_arrive(BAR_ONE(sb, EV_KV));
#pragma unroll 1
                for (int it = 0; it < 16; ++it) {
                    const int k0 = kof(it, 1, j);
                    if (it == AG1) mbar_wait(BAR_ONE(sb, (AGW & 2) ? EV_AGO1 : EV_FGO1), 0);
                    mbar_wait(BAR_EMPTY(sb, r.slot), r.par);
                    const uint32_t st = sb + r.slot * SLOT, fb = BAR_FULL(sb, r.slot);
                    if (el) {
                        mbar_expect_tx(fb, it < 2 ? 32768 : 24576);
                        tma_load_mc(st + 16384 + rank * 8192, &mp.wo, j * 128 + rank * 64, k0, fb);
                        if (it < 2) {
                            tma_load3(st, &mp.x, j * 128, m * 64 + it * 32, fb); tma_load3(st + 8192, &mp.x, j * 128 + 64, m * 64 + it * 32, fb);
                            mbar_arrive(fb + AF_REL);
                        }
                        if (it == 6) { prefetch_map(rank ? &mp.wu : &mp.wg); prefetch_map(rank ? &mp.wu3 : &mp.wg3); }
                    }
                    r.next();
                }
                const CUtensorMap* wm = rank ? &mp.wu : &mp.wg;
#pragma unroll 1
                for (int g = 0; g < 96; ++g) {
                    if (g == AG2) mbar_wait(BAR_ONE(sb, (AGW & 4) ? EV_AGO2 : EV_FGO2), 0);
                    const int p = g >> 5, cb = hcol(p, j), k0 = p == 0 ? kof(g, 2, j) : (g & 31) * 32;
                    mbar_wait(BAR_EMPTY(sb, r.slot), r.par);
                    const uint32_t st = sb + r.slot * SLOT, fb = BAR_FULL(sb, r.slot);
                    if (el) {
                        mbar_expect_tx(fb, (g < 4 || p > 0) ? 24576 : 28672);
                        tma_load_mc(st + 8192 + rank * 4096, wm, cb, k0, fb);
                        tma_load_mc(st + 16384 + rank * 4096, wm, cb + 64, k0, fb);
                        if (p == 0) tma_load3_mc(st + 24576 + rank * 4096, rank ? &mp.wu3 : &mp.wg3, j, k0, fb);
                        else tma_load(st, &mp.h2l, k0, m * 128, fb);
                        if (g < 4) mbar_arrive(fb + AF_REL);
                        if ((g & 7) == grp && g + PFC >= 96) tma_prefetch(&mp.wd, j * 128 + rank * 64, (g + PFC - 96) * 64);
                        if (g == 60) { prefetch_map(&mp.wd); prefetch_map(&mp.hb); }
                    }
                    r.next();
                }
#pragma unroll 1
                for (int g = 0; g < 56; ++g) {
                    if (g == 0 || (g & 15) == 6 && g > 6) mbar_wait(BAR_ONE(sb, EV_H0 + (g >> 4)), 0);
                    const int k0 = g * 64;
                    mbar_wait(BAR_EMPTY(sb, r.slot), r.par);
                    const uint32_t st = sb + r.slot * SLOT, fb = BAR_FULL(sb, r.slot);
                    if (el) {
                        mbar_expect_tx(fb, 32768);
                        tma_load_mc(st + 16384 + rank * 8192, &mp.wd, j * 128 + rank * 64, k0, fb);
                        tma_load(st, &mp.hb, k0, m * 128, fb); tma_load(st + 8192, &mp.hb, k0, m * 128 + 64, fb);
                        if ((g & 7) == grp && g + PFC < 56) tma_prefetch(&mp.wd, j * 128 + rank * 64, k0 + PFC * 64);
                    }
                    r.next();
                }
            }
        } else if (aux) {
            if (warp < 11) {
                const uint32_t w = warp - 9;
                const bool el = elect_one();
#pragma unroll 1
                for (int p = 0; p < 4; ++p) {
                    const int mx = (j >> 1) * 8 + p * 2 + rank;
                    if (el) { mbar_arrive(BAR_SREADY(sb, w * 2)); mbar_arrive(BAR_SREADY(sb, w * 2 + 1)); }
                    mbar_wait2(BAR_SFULL(sb, w * 2), BAR_SFULL(sb, w * 2 + 1), p & 1);
                    if (p < 3) pause(w ? HD1 : HD0);
                    if (el) tma_store(&mp.hb, HC3, mx * 128 + w * 64, sb + OFF_STG + w * 16384);
                    if (p < 3) pause(HP);
                    if (el) {
                        tma_store(&mp.hb, HC3 + 64, mx * 128 + w * 64, sb + OFF_STG + w * 16384 + 8192);
                        bulk_commit(); bulk_wait_fence(); flag_set(g_flags + FL_AUX + mx * 2 + w, ep * 8 + ST_H + 3);
                    }
                }
            }
        } else if (warp == 11) {
            const bool el = elect_one();
            const int row0 = m * 128;
            const uint32_t* const fl = g_flags + FL_PROG + fidx(m, lane >> 4, kof(lane & 15, 1, j) >> 6);
            if (el) { prefetch_map(&mp.h1h); prefetch_map(&mp.h2h); prefetch_map(&mp.h2l); }
            auto gate = [&](int vec, int ev) {
                uint4 v; uint32_t n = 0;
                while (true) {
                    v = ld_pkt2(g_mod + vec * 512 + j * 64 + lane * 2);
                    if (__all_sync(0xffffffffu, v.y == ep && v.w == ep)) break;
                    SPIN_GUARD(n); __nanosleep(300);
                }
                asm volatile("st.shared.v2.u32 [%0], {%1, %2};" :: "r"(sb + OFF_TAB + (ev - EV_GA) * 256 + lane * 8), "r"(v.x), "r"(v.z) : "memory");
                __syncwarp();
                if (lane == 0) mbar_arrive(BAR_ONE(sb, ev));
            };
            {
                const uint4* pk = pt.mail->mod1 + grp * 512 + j * 32 + lane;
                uint4 a, b; uint32_t n = 0;
                mbar_wait(BAR_ONE(sb, EV_WIN3), 0);
                while (true) {
                    a = ld_pkt16(pk); b = ld_pkt16(pk + 256);
                    if (__all_sync(0xffffffffu, a.z == ep && b.z == ep)) break;
                    SPIN_GUARD(n);
                }
                sts128(sb + OFF_PAR + lane * 16, a.x, a.y, b.x, b.y);
                __syncwarp();
                if (lane == 0) { mbar_arrive(BAR_ONE(sb, EV_PAR)); TL(46); }
            }
            mbar_wait(BAR_ONE(sb, EV_P0), 0);
            Ring r{0, 1};
#pragma unroll 1
            for (int ph = 0; ph < 3; ++ph) {
                const int sh = ph == 1 ? 1 : 2, nst = 8 << sh;
                const uint32_t half = 16384 >> sh, target = ep * 8 + ST_H1 + ph;
                const CUtensorMap* tm = ph == 0 ? &mp.h1h : ph == 1 ? &mp.o : &mp.h2h;
                if (ph == 1) {
                    gate(2, EV_GA);
                    mbar_wait(BAR_SREADY(sb, 1), 1);
#pragma unroll 1
                    for (int i = 0; i < 2; ++i)
                        fetch_halo<1>(g_halo + ((m - 1) * 8 + j) * 512 + i * 256 + 128 + lane, m == 0, sb + OFF_STG + 8192 + i * 4096 + lane * 16,
                                      [&] { __syncwarp(); if (el) mbar_arrive(BAR_ONE(sb, EV_TAIL + 2 * i)); });
                    CS(32);
                }
                if (ph == 2) {
                    uint32_t n = 0;
                    while ((int32_t)(flag_get(g_flags + FL_LN2) - ep * 8) < 0) { SPIN_GUARD(n); __nanosleep(200); }
                    const uint4 v = __ldcg((const uint4*)(g_par2 + j * 128) + lane);
                    sts128(sb + OFF_PAR + lane * 16, v.x, v.y, v.z, v.w);
                    __syncwarp();
                    if (lane == 0) mbar_arrive(BAR_ONE(sb, EV_LN2));
                }
                const uint32_t lw = ~lane & 1, lt = lane >> 1, ls = (r.slot + lt) % NSLOT, lk = kof(lt, sh, j), lb = BAR_FULL(sb, ls) + (lw ? 0 : AF_REL);
                const uint32_t* const lf = g_flags + FL_PROG + fidx(m, lw, lk >> 6);
                int fr = 1 << sh;
                uint32_t todo = 0x3ffffu >> (2 * fr) << (2 * fr), have = ~todo, n = 0, v = 0;
                r.skip(fr);
#pragma unroll 1
                for (; fr < NSLOT; ++fr) { mbar_wait(BAR_EMPTY(sb, r.slot), r.par); r.next(); }
                if (ph == XST - 1) CS(33);
                do {
                    if (!((have >> lane) & 1)) v = flag_get(lf);
                    while (ph == 2 && fr < FRCAP && mbar_test(BAR_EMPTY(sb, r.slot), r.par)) { ++fr; r.next(); }
                    SPIN_GUARD(n);
                    have |= __ballot_sync(0xffffffffu, (int32_t)(v - target) >= 0);
                    const uint32_t go = have & todo & ((1u << (2 * fr)) - 1);
                    if ((go >> lane) & 1) {
                        if (!lw) mbar_expect_tx(lb, half);
                        tma_load(sb + ls * SLOT + lw * half, tm, lk, row0 + lw * 64, lb);
                    }
                    __syncwarp();
                    if (lane < 2 && (todo & (0x555u << lane)) && !(todo & ~go & (0x555u << lane))) mbar_arrive(BAR_ONE(sb, (lane ? EV_FGO : EV_AGO) + ph));
                    if (ph == XST - 1) { if (go & (1u << (2 << sh))) CS(34); if (go & (2u << (2 << sh))) CS(35); if (todo & 0x555u) CS(36); if (todo & 0xaaau) CS(37); }
                    todo &= ~go;
                } while (~have);
                if (ph == XST - 1) CS(38);
                int k = kof(fr, sh, j);
#pragma unroll 1
                for (; fr < nst; ++fr) {
                    if (fr == 9 || fr == 18) {
                        const uint32_t skip = fr == 9 << (sh - 1) ? 0 : ~0x01fc01fcu;
                        while (~(__ballot_sync(0xffffffffu, (int32_t)(flag_get(fl) - target) >= 0) | skip)) SPIN_GUARD(n);
                    }
                    const uint32_t st = sb + r.slot * SLOT, fb = BAR_FULL(sb, r.slot);
                    mbar_wait(BAR_EMPTY(sb, r.slot), r.par);
                    if (el) {
                        tma_load(st + half, tm, k, row0 + 64, fb);
                        mbar_expect_tx(fb + AF_REL, half);
                        tma_load(st, tm, k, row0, fb + AF_REL);
                    }
                    if (ph == XST - 1 && fr == 9) CS(39);
                    r.next();
                    k = kof(fr + 1, sh, j);
                }
            }
#pragma unroll 1
            for (int p = 0; p < 4; ++p) {
                const uint32_t* f = p < 3 ? fl : g_flags + FL_AUX + m * 2 + (lane & 1);
                uint32_t n = 0;
                while (!__all_sync(0xffffffffu, (int32_t)(flag_get(f) - (ep * 8 + ST_H + p)) >= 0)) { SPIN_GUARD(n); __nanosleep(300); }
                if (el) mbar_arrive(BAR_ONE(sb, EV_H0 + p));
                if (p == 0) gate(5, EV_GB);
            }
        } else {
            const uint32_t w = warp - 9;
            const int row0 = m * 128 + w * 64;
            const uint32_t stg = sb + OFF_STG + w * 16384;
            uint32_t* const fl = g_flags + FL_PROG + fidx(m, w, 2 * j);
            uint32_t b = 0, par = 0;
            const bool el = elect_one();
            auto store = [&](const CUtensorMap* tm, int col, bool nat = false) {
                mbar_wait(BAR_SFULL(sb, w * 2 + b), (par >> b) & 1);
                par ^= 1u << b;
                if (el) {
                    if (nat) tma_store3(tm, col, row0 >> 1, 0, stg + b * 8192); else tma_store(tm, col, row0, stg + b * 8192);
                    bulk_commit();
                }
                b ^= 1;
            };
            auto send2 = [&](const CUtensorMap* tm, const uint32_t* buf, int step) {
                const uint32_t* const q = buf + (size_t)((row0 + lane) * (D_ / 2) + j * 64 + 31);
                store(tm, j * 128);
                if (step == XST) CS(33);
                uint32_t z = landed(el, q, D_ / 2, pt.zero);
                if (el) flag_set(fl, ep * 8 + step + z);
                if (step == XST) CS(34);
                if (step != ST_O) { mbar_wait(BAR_ONE(sb, EV_FGO + step - ST_H1), 0); pause(step == ST_H1 ? (w ? P1H : P1H + 1000) : w ? P2L : P2F); }
                store(tm, j * 128 + 64);
                if (step == XST) CS(35);
                z = landed(el, q + 32, D_ / 2, pt.zero);
                if (el) flag_set(fl + 1, ep * 8 + step + z);
                if (step == XST) CS(36);
            };
            auto free2 = [&]() { if (el) { mbar_arrive(BAR_SREADY(sb, w * 2)); mbar_arrive(BAR_SREADY(sb, w * 2 + 1)); } };
            if (el) { prefetch_map(&mp.h1s); prefetch_map(&mp.o); prefetch_map(&mp.out); prefetch_map(&mp.wo); }
            send2(&mp.h1s, pt.h1, ST_H1);
            if (w == 0) TL(47);
            free2();
            mbar_wait(BAR_ONE(sb, EV_KV), 0);
            mbar_wait(BAR_SREADY(sb, 0), 1);
            fetch_halo<1>(g_halo + ((m - 1) * 8 + j) * 512 + w * 256 + lane, m == 0, sb + OFF_STG + w * 4096 + lane * 16, [&] { bar_arrive(NB_TAIL + 2 * w, 64); CS(38); });
            send2(&mp.o, pt.o, ST_O);
            if (w == 0) TL(40); else TL(38);
            free2();
            send2(&mp.o, pt.o, ST_H2);
            if (el) { prefetch_map(&mp.hbs); prefetch_map(&mp.hb3); }
            if (w == 0) TL(37);
            free2();
#pragma unroll 1
            for (int p = 0; p < 3; ++p) {
                const int col = hcol(p, j);
                mbar_wait2(BAR_SFULL(sb, w * 2), BAR_SFULL(sb, w * 2 + 1), par & 1);
                par ^= 3;
#pragma unroll 1
                for (int i = 0; i < (p ? 2 : 3) * NSPL; ++i) {
                    pause(i ? HP / NSPL : p == 2 ? (w ? HE1 : HE0) : w ? HD1 : HD0);
                    const int pn = i / NSPL, ro = (i % NSPL) * (64 / NSPL);
                    if (el) {
                        if (pn < 2) tma_store(&mp.hbs, col + pn * 64, row0 + ro, stg + i * (8192 / NSPL));
                        else tma_store3(&mp.hb3, 0, j, row0 + ro, sb + (w ? P3_SLOT1 : P3_SLOT0) * SLOT + 24576 + ro * 128);
                        bulk_commit();
                    }
                }
                if (el) bulk_wait_read();
                free2();
                if (el) { bulk_wait_fence(); flag_set(fl, ep * 8 + ST_H + p); flag_set(fl + 1, ep * 8 + ST_H + p); }
            }
            cluster_arrive_early = true;
            cluster_arrive();
            store(&mp.out, j * 128, true); store(&mp.out, j * 128 + 64, true);
            if (el) bulk_wait_read();
        }
        __syncwarp();
    }
    if (aux || (wg == 2 && !cluster_arrive_early)) cluster_arrive();
    cluster_wait();
    if (KDEBUG == 5) __syncthreads();
    if (tid == 0) {
        TL(15);
        flag_add(pt.mail->flags + FL_DONE);
    }
}

typedef CUresult (*EncodeFn)(CUtensorMap*, CUtensorMapDataType, cuuint32_t, void*, const cuuint64_t*, const cuuint64_t*, const cuuint32_t*,
                             const cuuint32_t*, CUtensorMapInterleave, CUtensorMapSwizzle, CUtensorMapL2promotion, CUtensorMapFloatOOBfill);

void make_map(EncodeFn fn, CUtensorMap* m, const void* ptr, uint64_t rows, uint64_t cols, uint32_t brows, uint32_t bcols) {
    cuuint64_t dims[2] = {cols, rows}, strides[1] = {cols * 2};
    cuuint32_t box[2] = {bcols, brows}, es[2] = {1, 1};
    fn(m, CU_TENSOR_MAP_DATA_TYPE_BFLOAT16, 2, (void*)ptr, dims, strides, box, es, CU_TENSOR_MAP_INTERLEAVE_NONE,
       bcols == 64 ? CU_TENSOR_MAP_SWIZZLE_128B : bcols == 32 ? CU_TENSOR_MAP_SWIZZLE_64B : CU_TENSOR_MAP_SWIZZLE_NONE, CU_TENSOR_MAP_L2_PROMOTION_L2_256B, CU_TENSOR_MAP_FLOAT_OOB_FILL_NONE);
}

void make_map3(EncodeFn fn, CUtensorMap* m, const void* ptr) {
    cuuint64_t dims[3] = {D_, S_ / 2, 2}, strides[2] = {4 * D_, 2 * D_};
    cuuint32_t box[3] = {64, 32, 2}, es[3] = {1, 1, 1};
    fn(m, CU_TENSOR_MAP_DATA_TYPE_BFLOAT16, 3, (void*)ptr, dims, strides, box, es, CU_TENSOR_MAP_INTERLEAVE_NONE,
       CU_TENSOR_MAP_SWIZZLE_128B, CU_TENSOR_MAP_L2_PROMOTION_L2_256B, CU_TENSOR_MAP_FLOAT_OOB_FILL_NONE);
}

void make_map48(EncodeFn fn, CUtensorMap* m, const void* ptr, uint64_t rows, uint32_t brows) {
    cuuint64_t dims[3] = {48, 8, rows}, strides[2] = {96, 2 * F_};
    cuuint32_t box[3] = {64, 1, brows}, es[3] = {1, 1, 1};
    fn(m, CU_TENSOR_MAP_DATA_TYPE_BFLOAT16, 3, (void*)ptr, dims, strides, box, es, CU_TENSOR_MAP_INTERLEAVE_NONE,
       CU_TENSOR_MAP_SWIZZLE_128B, CU_TENSOR_MAP_L2_PROMOTION_L2_256B, CU_TENSOR_MAP_FLOAT_OOB_FILL_NONE);
}

}

extern "C" void kernel_launch(void* const* d_in, const int* in_sizes, int n_in, void* d_out, int out_size) {
    (void)in_sizes; (void)n_in; (void)out_size;
    void* fnp = nullptr;
    cudaDriverEntryPointQueryResult qr;
    cudaGetDriverEntryPoint("cuTensorMapEncodeTiled", &fnp, cudaEnableDefault, &qr);
    EncodeFn fn = (EncodeFn)fnp;
    void *h1, *o, *h2, *hb, *mail;
    cudaGetSymbolAddress(&h1, g_h1);
    cudaGetSymbolAddress(&mail, g_mail);
    cudaGetSymbolAddress(&o, g_o);
    cudaGetSymbolAddress(&hb, g_hb);
    h2 = o;
    Maps mp;
    make_map(fn, &mp.h1h, h1, S_, D_, 64, 32);
    make_map(fn, &mp.h2h, h2, S_, D_, 64, 32);
    make_map(fn, &mp.h1s, h1, S_, D_, 64, 64);
    make_map(fn, &mp.o, o, S_, D_, 64, 64);
    make_map(fn, &mp.h2l, h2, S_, D_, 128, 32);
    make_map(fn, &mp.hb, hb, S_, F_, 64, 64);
    make_map(fn, &mp.wqkv, d_in[1], D_, 3 * D_, 32, 64);
    make_map(fn, &mp.wo, d_in[2], D_, D_, 64, 64);
    make_map(fn, &mp.wg, d_in[4], D_, F_, 32, 64);
    make_map(fn, &mp.wu, d_in[5], D_, F_, 32, 64);
    make_map(fn, &mp.wd, d_in[6], F_, D_, 64, 64);
    make_map(fn, &mp.wmod, d_in[8], D_, 6 * D_, 64, 64);
    make_map(fn, &mp.wm8, d_in[8], D_ / 8, 8 * 6 * D_, 128, 16);
    make_map3(fn, &mp.x, d_in[0]);
    make_map3(fn, &mp.out, d_out);
    make_map48(fn, &mp.wg3, d_in[4], D_, 32);
    make_map48(fn, &mp.wu3, d_in[5], D_, 32);
    make_map48(fn, &mp.hb3, hb, S_, 64 / NSPL);
    make_map(fn, &mp.hbs, hb, S_, F_, 64 / NSPL, 64);
    cudaFuncSetAttribute(fused_block_kernel, cudaFuncAttributeMaxDynamicSharedMemorySize, SMEM_BYTES);
    cudaLaunchConfig_t cfg = {};
    cfg.gridDim = dim3(NCTA); cfg.blockDim = dim3(384); cfg.dynamicSmemBytes = SMEM_BYTES; cfg.stream = cudaStreamPerThread;
    cudaLaunchAttribute at[1];
    at[0].id = cudaLaunchAttributeClusterDimension; at[0].val.clusterDim.x = 2; at[0].val.clusterDim.y = 1; at[0].val.clusterDim.z = 1;
    cfg.attrs = at; cfg.numAttrs = 1;
    const Ptrs pt{(const __nv_bfloat16*)d_in[7], (Mail*)mail, (const uint32_t*)h1, (const uint32_t*)o, 0};
    cudaLaunchKernelEx(&cfg, fused_block_kernel, pt, mp);
}
```

```cpp
#include <cuda_runtime.h>
#include <cuda_bf16.h>
#include <cuda.h>
#include <stdint.h>
#include <stddef.h>

#define LAG 4
#define LAGS 4
#define LAGW 2
#define LAGD 4
#define LAGQ 4
#define PUT1 5
#define PUT0 10
#define PUTD1 6
#define PUTD0 10
#define MIDD 40
#define HD1 3000
#define HD0 1500
#define NSPL 2
#define HE1 2000
#define HE0 HD0
#define HP 2600
#define P1H 3000
#define P2L 2000
#define P2F 3000
#define AUXD 5000
#define PDLY 500
#define FD0 200
#define AG0 6
#define AG1 6
#define AG2 8
#define AGW 2
#define FRCAP 8
#define BW0 0
#define BWEV EV_WIN
#define BW1 3
#define LWAIT 3
#define PFWO 12
#define PFG 8
#define PFN 24
#define PFC 10
#define PFO 0
#define KDEBUG 0
#define CSW 0
#define XST ST_O

namespace {

constexpr int S_ = 2048, D_ = 1024, F_ = 3584;
constexpr int NCTA = 132;
constexpr int NSLOT = 6;
constexpr uint32_t SLOT = 32768;
constexpr uint32_t OFF_STG = NSLOT * SLOT;
constexpr uint32_t OFF_BAR = OFF_STG + 32768;
constexpr uint32_t OFF_PAR = OFF_BAR + 512;
constexpr uint32_t OFF_TAB = OFF_PAR + 768;
constexpr uint32_t OFF_TL = OFF_PAR + 2048;
constexpr uint32_t SMEM_BYTES = OFF_TL + (KDEBUG ? 512 : 0);
constexpr uint32_t P3_SLOT1 = (32 + 16 + 32) % NSLOT, P3_SLOT0 = (P3_SLOT1 + 1) % NSLOT;

constexpr int ST_H1 = 1, ST_O = 2, ST_H2 = 3, ST_H = 4, FL_DONE = 0, FL_LN2 = 1, FL_AUX = 32, FL_PROG = 64;

struct Maps {
    CUtensorMap h1h, h1s, o, h2h, h2l, hb, wqkv, wo, wg, wu, wd, wmod, wm8, x, out, wg3, wu3, hb3, hbs;
};

struct Mail {
    uint32_t flags[16 * 32 + 64];
    uint2 mod[6 * D_ / 2];
    uint4 mod1[8 * 512];
    uint4 st1[128 * 512];
    uint32_t par2[D_];
    uint4 halo[128 * 512];
};
struct Ptrs { const __nv_bfloat16* c; Mail* mail; const uint32_t *h1, *o; uint32_t zero; };

__device__ __align__(128) Mail g_mail;
__device__ __align__(128) __nv_bfloat16 g_h1[S_ * D_];
__device__ __align__(128) __nv_bfloat16 g_o[S_ * D_];
__device__ __align__(128) __nv_bfloat16 g_hb[S_ * F_];
#define TL(i) do {} while (0)
#define TC(i) do {} while (0)
#define TS(g, which) do {} while (0)
#define CS(i) do {} while (0)

__device__ __forceinline__ uint32_t smem_u32(const void* p) { return (uint32_t)__cvta_generic_to_shared(p); }
__device__ __forceinline__ void mbar_init(uint32_t bar, uint32_t cnt) { asm volatile("mbarrier.init.shared::cta.b64 [%0], %1;" :: "r"(bar), "r"(cnt) : "memory"); }
__device__ __forceinline__ void mbar_expect_tx(uint32_t bar, uint32_t bytes) { asm volatile("mbarrier.arrive.expect_tx.shared::cta.b64 _, [%0], %1;" :: "r"(bar), "r"(bytes) : "memory"); }
__device__ __forceinline__ void mbar_arrive(uint32_t bar) { asm volatile("mbarrier.arrive.shared::cta.b64 _, [%0];" :: "r"(bar) : "memory"); }
__device__ __forceinline__ void mbar_arrive_cta(uint32_t bar, uint32_t cta) {
    asm volatile("{\n.reg .b32 r;\nmapa.shared::cluster.u32 r, %0, %1;\nmbarrier.arrive.shared::cluster.b64 _, [r];\n}" :: "r"(bar), "r"(cta) : "memory");
}
__device__ __forceinline__ void mbar_wait(uint32_t bar, uint32_t parity) {
    asm volatile("{\n.reg .pred p;\n.reg .u32 n;\nmov.u32 n, 0;\n"
        "W_LOOP:\nmbarrier.try_wait.parity.shared::cta.b64 p, [%0], %1;\n@p bra W_DONE;\n"
        "add.u32 n, n, 1;\nsetp.lt.u32 p, n, 0x400000;\n@p bra W_LOOP;\ntrap;\nW_DONE:\n}" :: "r"(bar), "r"(parity) : "memory");
}
__device__ __forceinline__ void mbar_wait2(uint32_t b0, uint32_t b1, uint32_t parity) {
    asm volatile("{\n.reg .pred p, q;\n.reg .u32 n;\nmov.u32 n, 0;\n"
        "W_LOOP:\nmbarrier.try_wait.parity.shared::cta.b64 p, [%0], %2;\nmbarrier.try_wait.parity.shared::cta.b64 q, [%1], %2;\nand.pred p, p, q;\n@p bra W_DONE;\n"
        "add.u32 n, n, 1;\nsetp.lt.u32 p, n, 0x400000;\n@p bra W_LOOP;\ntrap;\nW_DONE:\n}" :: "r"(b0), "r"(b1), "r"(parity) : "memory");
}
__device__ __forceinline__ bool mbar_test(uint32_t bar, uint32_t parity) {
    uint32_t r; asm volatile("{\n.reg .pred p;\nmbarrier.test_wait.parity.shared::cta.b64 p, [%1], %2;\nselp.u32 %0, 1, 0, p;\n}" : "=r"(r) : "r"(bar), "r"(parity) : "memory"); return r;
}
__device__ __forceinline__ bool mbar_test2(uint32_t b0, uint32_t b1, uint32_t parity) {
    uint32_t r;
    asm volatile("{\n.reg .pred p, q;\nmbarrier.test_wait.parity.shared::cta.b64 p, [%1], %3;\nmbarrier.test_wait.parity.shared::cta.b64 q, [%2], %3;\n"
        "and.pred p, p, q;\nselp.u32 %0, 1, 0, p;\n}" : "=r"(r) : "r"(b0), "r"(b1), "r"(parity) : "memory");
    return r;
}
__device__ __forceinline__ void tma_load3(uint32_t dst, const CUtensorMap* m, int c0, int c1, uint32_t bar) {
    asm volatile("cp.async.bulk.tensor.3d.shared::cluster.global.mbarrier::complete_tx::bytes [%0], [%1, {%3, %4, %5}], [%2];"
        :: "r"(dst), "l"(m), "r"(bar), "r"(c0), "r"(c1), "r"(0) : "memory");
}
__device__ __forceinline__ void tma_store3(const CUtensorMap* m, int c0, int c1, int c2, uint32_t src) {
    asm volatile("cp.async.bulk.tensor.3d.global.shared::cta.bulk_group [%0, {%2, %3, %4}], [%1];" :: "l"(m), "r"(src), "r"(c0), "r"(c1), "r"(c2) : "memory");
}
__device__ __forceinline__ void tma_load3_mc(uint32_t dst, const CUtensorMap* m, int c1, int c2, uint32_t bar) {
    asm volatile("cp.async.bulk.tensor.3d.shared::cluster.global.mbarrier::complete_tx::bytes.multicast::cluster.L2::cache_hint [%0], [%1, {%3, %4, %5}], [%2], %6, %7;"
        :: "r"(dst), "l"(m), "r"(bar), "r"(0), "r"(c1), "r"(c2), "h"((uint16_t)3), "l"(0x12F0000000000000ull) : "memory");
}
__device__ __forceinline__ void tma_load(uint32_t dst, const CUtensorMap* m, int c0, int c1, uint32_t bar) {
    asm volatile("cp.async.bulk.tensor.2d.shared::cluster.global.mbarrier::complete_tx::bytes [%0], [%1, {%3, %4}], [%2];"
        :: "r"(dst), "l"(m), "r"(bar), "r"(c0), "r"(c1) : "memory");
}
__device__ __forceinline__ void tma_load_mc(uint32_t dst, const CUtensorMap* m, int c0, int c1, uint32_t bar) {
    asm volatile("cp.async.bulk.tensor.2d.shared::cluster.global.mbarrier::complete_tx::bytes.multicast::cluster.L2::cache_hint [%0], [%1, {%3, %4}], [%2], %5, %6;"
        :: "r"(dst), "l"(m), "r"(bar), "r"(c0), "r"(c1), "h"((uint16_t)3), "l"(0x12F0000000000000ull) : "memory");
}
__device__ __forceinline__ void tma_prefetch(const CUtensorMap* m, int c0, int c1) {
    asm volatile("cp.async.bulk.prefetch.tensor.2d.L2.global [%0, {%1, %2}];" :: "l"(m), "r"(c0), "r"(c1) : "memory");
}
__device__ __forceinline__ void tma_store(const CUtensorMap* m, int c0, int c1, uint32_t src) {
    asm volatile("cp.async.bulk.tensor.2d.global.shared::cta.bulk_group [%0, {%2, %3}], [%1];" :: "l"(m), "r"(src), "r"(c0), "r"(c1) : "memory");
}
__device__ __forceinline__ void bulk_commit() { asm volatile("cp.async.bulk.commit_group;" ::: "memory"); }
__device__ __forceinline__ void bulk_wait_read() { asm volatile("cp.async.bulk.wait_group.read 0;" ::: "memory"); }
__device__ __forceinline__ void fence_async_smem() { asm volatile("fence.proxy.async.shared::cta;" ::: "memory"); }
__device__ __forceinline__ void prefetch_map(const CUtensorMap* m) { asm volatile("prefetch.tensormap [%0];" :: "l"(m) : "memory"); }
__device__ __forceinline__ void wg_fence() { asm volatile("wgmma.fence.sync.aligned;" ::: "memory"); }
__device__ __forceinline__ void wg_commit() { asm volatile("wgmma.commit_group.sync.aligned;" ::: "memory"); }
template <int N> __device__ __forceinline__ void wg_wait() { asm volatile("wgmma.wait_group.sync.aligned %0;" :: "n"(N) : "memory"); }
__device__ __forceinline__ void bar_sync(int id, int n) { asm volatile("bar.sync %0, %1;" :: "r"(id), "r"(n) : "memory"); }
__device__ __forceinline__ void bar_arrive(int id, int n) { asm volatile("bar.arrive %0, %1;" :: "r"(id), "r"(n) : "memory"); }
__device__ __forceinline__ void flag_add(uint32_t* f) { asm volatile("red.relaxed.gpu.global.add.u32 [%0], 1;" :: "l"(f) : "memory"); }
__device__ __forceinline__ void flag_set(uint32_t* f, uint32_t v) { asm volatile("red.relaxed.gpu.global.max.u32 [%0], %1;" :: "l"(f), "r"(v) : "memory"); }
__device__ __forceinline__ uint32_t flag_get(const uint32_t* f) { uint32_t v; asm volatile("ld.relaxed.gpu.global.u32 %0, [%1];" : "=r"(v) : "l"(f) : "memory"); return v; }
__device__ __forceinline__ void bulk_wait_fence() { asm volatile("cp.async.bulk.wait_group 0;\nfence.proxy.async.global;\nfence.acq_rel.gpu;" ::: "memory"); }
__device__ __forceinline__ uint32_t landed(bool el, const uint32_t* p, uint32_t pitch, uint32_t zero) {
    if (el) asm volatile("cp.async.bulk.wait_group 0;" ::: "memory");
    __syncwarp();
    const uint32_t a = flag_get(p), b = flag_get(p + 32 * pitch);
    return __reduce_or_sync(0xffffffffu, (a | b) & zero);
}
__device__ __forceinline__ uint32_t d16(uint32_t addr) { return (addr & 0x3FFFF) >> 4; }
__device__ __forceinline__ uint64_t mk_desc(uint32_t a16, uint32_t off, uint32_t lbo, uint32_t sbo, uint32_t swz) {
    const uint32_t lo = a16 + (off >> 4) + ((lbo >> 4) << 16), hi = (sbo >> 4) | (swz << 30);
    return ((uint64_t)hi << 32) | lo;
}
__device__ __forceinline__ uint32_t pack2(float lo, float hi) {
    uint32_t r; asm("cvt.rn.bf16x2.f32 %0, %1, %2;" : "=r"(r) : "f"(hi), "f"(lo)); return r;
}
__device__ __forceinline__ uint32_t hfma2_bf16(uint32_t a, uint32_t b, uint32_t c) {
    uint32_t r; asm("fma.rn.bf16x2 %0, %1, %2, %3;" : "=r"(r) : "r"(a), "r"(b), "r"(c)); return r;
}
__device__ __forceinline__ float bf_lo(uint32_t v) { return __uint_as_float(v << 16); }
__device__ __forceinline__ float bf_hi(uint32_t v) { return __uint_as_float(v & 0xFFFF0000u); }
__device__ __forceinline__ void unpack2(uint32_t v, float& lo, float& hi) {
    asm volatile("shl.b32 %0, %2, 16;\nand.b32 %1, %2, 0xffff0000;" : "=f"(lo), "=f"(hi) : "r"(v));
}
__device__ __forceinline__ float bf_round(float x) { return __bfloat162float(__float2bfloat16_rn(x)); }
__device__ __forceinline__ void stsm4(uint32_t addr, uint32_t r0, uint32_t r1, uint32_t r2, uint32_t r3) {
    asm volatile("stmatrix.sync.aligned.m8n8.x4.shared.b16 [%0], {%1, %2, %3, %4};" :: "r"(addr), "r"(r0), "r"(r1), "r"(r2), "r"(r3) : "memory");
}
__device__ __forceinline__ void stsm4t(uint32_t addr, uint32_t r0, uint32_t r1, uint32_t r2, uint32_t r3) {
    asm volatile("stmatrix.sync.aligned.m8n8.x4.trans.shared.b16 [%0], {%1, %2, %3, %4};" :: "r"(addr), "r"(r0), "r"(r1), "r"(r2), "r"(r3) : "memory");
}
__device__ __forceinline__ uint32_t movm(uint32_t a) { uint32_t d; asm volatile("movmatrix.sync.aligned.m8n8.trans.b16 %0, %1;" : "=r"(d) : "r"(a)); return d; }
__device__ __forceinline__ void ldsm4(uint32_t addr, uint32_t& r0, uint32_t& r1, uint32_t& r2, uint32_t& r3) {
    asm volatile("ldmatrix.sync.aligned.m8n8.x4.shared.b16 {%0, %1, %2, %3}, [%4];" : "=r"(r0), "=r"(r1), "=r"(r2), "=r"(r3) : "r"(addr) : "memory");
}
__device__ __forceinline__ void ldsm4t(uint32_t addr, uint32_t& r0, uint32_t& r1, uint32_t& r2, uint32_t& r3) {
    asm volatile("ldmatrix.sync.aligned.m8n8.x4.trans.shared.b16 {%0, %1, %2, %3}, [%4];" : "=r"(r0), "=r"(r1), "=r"(r2), "=r"(r3) : "r"(addr) : "memory");
}
__device__ __forceinline__ void mma16816(float (&c)[4], uint32_t a0, uint32_t a1, uint32_t a2, uint32_t a3, uint32_t b0, uint32_t b1) {
    asm("mma.sync.aligned.m16n8k16.row.col.f32.bf16.bf16.f32 {%0, %1, %2, %3}, {%4, %5, %6, %7}, {%8, %9}, {%0, %1, %2, %3};"
        : "+f"(c[0]), "+f"(c[1]), "+f"(c[2]), "+f"(c[3]) : "r"(a0), "r"(a1), "r"(a2), "r"(a3), "r"(b0), "r"(b1));
}
__device__ __forceinline__ float rsq(float x) { float r; asm("rsqrt.approx.ftz.f32 %0, %1;" : "=f"(r) : "f"(x)); return r; }
__device__ __forceinline__ float rcp(float x) { float r; asm("rcp.approx.ftz.f32 %0, %1;" : "=f"(r) : "f"(x)); return r; }
__device__ __forceinline__ float ex2(float x) { float r; asm("ex2.approx.ftz.f32 %0, %1;" : "=f"(r) : "f"(x)); return r; }
__device__ __forceinline__ float tanh_(float x) { float t; asm("tanh.approx.f32 %0, %1;" : "=f"(t) : "f"(x)); return t; }
__device__ __forceinline__ void block_end(uint32_t opaque, uint32_t id) { asm volatile("{\n.reg .pred p;\nsetp.eq.u32 p, %0, %1;\n@p trap;\n}" :: "r"(opaque), "r"(0xffffff00u + id)); }
__device__ __forceinline__ float silu_(float x) { return __fdividef(x, 1.f + __expf(-x)); }
__device__ __forceinline__ void st_pkt(void* p, uint32_t a, uint32_t b) {
    asm volatile("{\n.reg .b64 t;\nmov.b64 t, {%1, %2};\nst.relaxed.gpu.global.b64 [%0], t;\n}" :: "l"(p), "r"(a), "r"(b) : "memory");
}
__device__ __forceinline__ uint4 ld_pkt2(const void* p) {
    uint4 v; asm volatile("{\n.reg .b64 t, u;\nld.relaxed.gpu.global.v2.b64 {t, u}, [%4];\nmov.b64 {%0, %1}, t;\nmov.b64 {%2, %3}, u;\n}"
        : "=r"(v.x), "=r"(v.y), "=r"(v.z), "=r"(v.w) : "l"(p) : "memory"); return v;
}
__device__ __forceinline__ void st_pkt16(void* p, uint32_t a, uint32_t b, uint32_t c, uint32_t d) {
    asm volatile("{\n.reg .b64 t, u;\n.reg .b128 w;\nmov.b64 t, {%1, %2};\nmov.b64 u, {%3, %4};\nmov.b128 w, {t, u};\nst.relaxed.gpu.global.b128 [%0], w;\n}"
        :: "l"(p), "r"(a), "r"(b), "r"(c), "r"(d) : "memory");
}
__device__ __forceinline__ uint4 ld_pkt16(const void* p) {
    uint4 v; asm volatile("{\n.reg .b64 t, u;\n.reg .b128 w;\nld.relaxed.gpu.global.b128 w, [%4];\nmov.b128 {t, u}, w;\nmov.b64 {%0, %1}, t;\nmov.b64 {%2, %3}, u;\n}"
        : "=r"(v.x), "=r"(v.y), "=r"(v.z), "=r"(v.w) : "l"(p) : "memory"); return v;
}
#define SPIN_GUARD(n) do { if (++(n) > (1u << 22)) asm volatile("trap;"); } while (0)
__device__ __forceinline__ uint4 lds128(uint32_t a) { uint4 v; asm volatile("ld.shared.v4.u32 {%0, %1, %2, %3}, [%4];" : "=r"(v.x), "=r"(v.y), "=r"(v.z), "=r"(v.w) : "r"(a) : "memory"); return v; }
__device__ __forceinline__ void sts128(uint32_t a, uint32_t x, uint32_t y, uint32_t z, uint32_t w) { asm volatile("st.shared.v4.u32 [%0], {%1, %2, %3, %4};" :: "r"(a), "r"(x), "r"(y), "r"(z), "r"(w) : "memory"); }
__device__ __forceinline__ uint32_t lds32(uint32_t a) { uint32_t v; asm volatile("ld.shared.u32 %0, [%1];" : "=r"(v) : "r"(a) : "memory"); return v; }
__device__ __forceinline__ void sts32(uint32_t a, uint32_t v) { asm volatile("st.shared.u32 [%0], %1;" :: "r"(a), "r"(v) : "memory"); }
__device__ __forceinline__ bool elect_one() {
    uint32_t p; asm volatile("{\n.reg .pred q;\nelect.sync _|q, 0xffffffff;\nselp.u32 %0, 1, 0, q;\n}" : "=r"(p)); return p;
}
__device__ __forceinline__ void pause(uint32_t cycles) {
    uint32_t t0, t; asm volatile("mov.u32 %0, %%clock;" : "=r"(t0));
    do { __nanosleep(64); asm volatile("mov.u32 %0, %%clock;" : "=r"(t)); } while (t - t0 < cycles);
}
__device__ __forceinline__ void cluster_arrive() { asm volatile("barrier.cluster.arrive.relaxed.aligned;" ::: "memory"); }
__device__ __forceinline__ void cluster_wait() { asm volatile("barrier.cluster.wait.aligned;" ::: "memory"); }

__device__ __forceinline__ void wgmma_n128_z(float (&d)[64], uint64_t da, uint64_t db) {
    asm volatile("{\n.reg .pred p;\nsetp.ne.b32 p, 0, 0;\n"
        "wgmma.mma_async.sync.aligned.m64n128k16.f32.bf16.bf16 {"
        "%0, %1, %2, %3, %4, %5, %6, %7, %8, %9, %10, %11, %12, %13, %14, %15, "
        "%16, %17, %18, %19, %20, %21, %22, %23, %24, %25, %26, %27, %28, %29, %30, %31, "
        "%32, %33, %34, %35, %36, %37, %38, %39, %40, %41, %42, %43, %44, %45, %46, %47, "
        "%48, %49, %50, %51, %52, %53, %54, %55, %56, %57, %58, %59, %60, %61, %62, %63"
        "}, %64, %65, p, 1, 1, 0, 1;\n}\n"
        : "=f"(d[0]), "=f"(d[1]), "=f"(d[2]), "=f"(d[3]), "=f"(d[4]), "=f"(d[5]), "=f"(d[6]), "=f"(d[7]),
          "=f"(d[8]), "=f"(d[9]), "=f"(d[10]), "=f"(d[11]), "=f"(d[12]), "=f"(d[13]), "=f"(d[14]), "=f"(d[15]),
          "=f"(d[16]), "=f"(d[17]), "=f"(d[18]), "=f"(d[19]), "=f"(d[20]), "=f"(d[21]), "=f"(d[22]), "=f"(d[23]),
          "=f"(d[24]), "=f"(d[25]), "=f"(d[26]), "=f"(d[27]), "=f"(d[28]), "=f"(d[29]), "=f"(d[30]), "=f"(d[31]),
          "=f"(d[32]), "=f"(d[33]), "=f"(d[34]), "=f"(d[35]), "=f"(d[36]), "=f"(d[37]), "=f"(d[38]), "=f"(d[39]),
          "=f"(d[40]), "=f"(d[41]), "=f"(d[42]), "=f"(d[43]), "=f"(d[44]), "=f"(d[45]), "=f"(d[46]), "=f"(d[47]),
          "=f"(d[48]), "=f"(d[49]), "=f"(d[50]), "=f"(d[51]), "=f"(d[52]), "=f"(d[53]), "=f"(d[54]), "=f"(d[55]),
          "=f"(d[56]), "=f"(d[57]), "=f"(d[58]), "=f"(d[59]), "=f"(d[60]), "=f"(d[61]), "=f"(d[62]), "=f"(d[63])
        : "l"(da), "l"(db));
}
__device__ __forceinline__ void wgmma_n128(float (&d)[64], uint64_t da, uint64_t db) {
    asm volatile("{\n.reg .pred p;\nsetp.eq.b32 p, 0, 0;\n"
        "wgmma.mma_async.sync.aligned.m64n128k16.f32.bf16.bf16 {"
        "%0, %1, %2, %3, %4, %5, %6, %7, %8, %9, %10, %11, %12, %13, %14, %15, "
        "%16, %17, %18, %19, %20, %21, %22, %23, %24, %25, %26, %27, %28, %29, %30, %31, "
        "%32, %33, %34, %35, %36, %37, %38, %39, %40, %41, %42, %43, %44, %45, %46, %47, "
        "%48, %49, %50, %51, %52, %53, %54, %55, %56, %57, %58, %59, %60, %61, %62, %63"
        "}, %64, %65, p, 1, 1, 0, 1;\n}\n"
        : "+f"(d[0]), "+f"(d[1]), "+f"(d[2]), "+f"(d[3]), "+f"(d[4]), "+f"(d[5]), "+f"(d[6]), "+f"(d[7]),
          "+f"(d[8]), "+f"(d[9]), "+f"(d[10]), "+f"(d[11]), "+f"(d[12]), "+f"(d[13]), "+f"(d[14]), "+f"(d[15]),
          "+f"(d[16]), "+f"(d[17]), "+f"(d[18]), "+f"(d[19]), "+f"(d[20]), "+f"(d[21]), "+f"(d[22]), "+f"(d[23]),
          "+f"(d[24]), "+f"(d[25]), "+f"(d[26]), "+f"(d[27]), "+f"(d[28]), "+f"(d[29]), "+f"(d[30]), "+f"(d[31]),
          "+f"(d[32]), "+f"(d[33]), "+f"(d[34]), "+f"(d[35]), "+f"(d[36]), "+f"(d[37]), "+f"(d[38]), "+f"(d[39]),
          "+f"(d[40]), "+f"(d[41]), "+f"(d[42]), "+f"(d[43]), "+f"(d[44]), "+f"(d[45]), "+f"(d[46]), "+f"(d[47]),
          "+f"(d[48]), "+f"(d[49]), "+f"(d[50]), "+f"(d[51]), "+f"(d[52]), "+f"(d[53]), "+f"(d[54]), "+f"(d[55]),
          "+f"(d[56]), "+f"(d[57]), "+f"(d[58]), "+f"(d[59]), "+f"(d[60]), "+f"(d[61]), "+f"(d[62]), "+f"(d[63])
        : "l"(da), "l"(db));
}
__device__ __forceinline__ void wgmma_n176_z(float (&d)[88], uint64_t da, uint64_t db) {
    asm volatile("{\n.reg .pred p;\nsetp.ne.b32 p, 0, 0;\n"
        "wgmma.mma_async.sync.aligned.m64n176k16.f32.bf16.bf16 {"
        "%0, %1, %2, %3, %4, %5, %6, %7, %8, %9, %10, %11, %12, %13, %14, %15, "
        "%16, %17, %18, %19, %20, %21, %22, %23, %24, %25, %26, %27, %28, %29, %30, %31, "
        "%32, %33, %34, %35, %36, %37, %38, %39, %40, %41, %42, %43, %44, %45, %46, %47, "
        "%48, %49, %50, %51, %52, %53, %54, %55, %56, %57, %58, %59, %60, %61, %62, %63, "
        "%64, %65, %66, %67, %68, %69, %70, %71, %72, %73, %74, %75, %76, %77, %78, %79, "
        "%80, %81, %82, %83, %84, %85, %86, %87"
        "}, %88, %89, p, 1, 1, 0, 1;\n}\n"
        : "=f"(d[0]), "=f"(d[1]), "=f"(d[2]), "=f"(d[3]), "=f"(d[4]), "=f"(d[5]), "=f"(d[6]), "=f"(d[7]),
          "=f"(d[8]), "=f"(d[9]), "=f"(d[10]), "=f"(d[11]), "=f"(d[12]), "=f"(d[13]), "=f"(d[14]), "=f"(d[15]),
          "=f"(d[16]), "=f"(d[17]), "=f"(d[18]), "=f"(d[19]), "=f"(d[20]), "=f"(d[21]), "=f"(d[22]), "=f"(d[23]),
          "=f"(d[24]), "=f"(d[25]), "=f"(d[26]), "=f"(d[27]), "=f"(d[28]), "=f"(d[29]), "=f"(d[30]), "=f"(d[31]),
          "=f"(d[32]), "=f"(d[33]), "=f"(d[34]), "=f"(d[35]), "=f"(d[36]), "=f"(d[37]), "=f"(d[38]), "=f"(d[39]),
          "=f"(d[40]), "=f"(d[41]), "=f"(d[42]), "=f"(d[43]), "=f"(d[44]), "=f"(d[45]), "=f"(d[46]), "=f"(d[47]),
          "=f"(d[48]), "=f"(d[49]), "=f"(d[50]), "=f"(d[51]), "=f"(d[52]), "=f"(d[53]), "=f"(d[54]), "=f"(d[55]),
          "=f"(d[56]), "=f"(d[57]), "=f"(d[58]), "=f"(d[59]), "=f"(d[60]), "=f"(d[61]), "=f"(d[62]), "=f"(d[63]),
          "=f"(d[64]), "=f"(d[65]), "=f"(d[66]), "=f"(d[67]), "=f"(d[68]), "=f"(d[69]), "=f"(d[70]), "=f"(d[71]),
          "=f"(d[72]), "=f"(d[73]), "=f"(d[74]), "=f"(d[75]), "=f"(d[76]), "=f"(d[77]), "=f"(d[78]), "=f"(d[79]),
          "=f"(d[80]), "=f"(d[81]), "=f"(d[82]), "=f"(d[83]), "=f"(d[84]), "=f"(d[85]), "=f"(d[86]), "=f"(d[87])
        : "l"(da), "l"(db));
}
__device__ __forceinline__ void wgmma_n176(float (&d)[88], uint64_t da, uint64_t db) {
    asm volatile("{\n.reg .pred p;\nsetp.eq.b32 p, 0, 0;\n"
        "wgmma.mma_async.sync.aligned.m64n176k16.f32.bf16.bf16 {"
        "%0, %1, %2, %3, %4, %5, %6, %7, %8, %9, %10, %11, %12, %13, %14, %15, "
        "%16, %17, %18, %19, %20, %21, %22, %23, %24, %25, %26, %27, %28, %29, %30, %31, "
        "%32, %33, %34, %35, %36, %37, %38, %39, %40, %41, %42, %43, %44, %45, %46, %47, "
        "%48, %49, %50, %51, %52, %53, %54, %55, %56, %57, %58, %59, %60, %61, %62, %63, "
        "%64, %65, %66, %67, %68, %69, %70, %71, %72, %73, %74, %75, %76, %77, %78, %79, "
        "%80, %81, %82, %83, %84, %85, %86, %87"
        "}, %88, %89, p, 1, 1, 0, 1;\n}\n"
        : "+f"(d[0]), "+f"(d[1]), "+f"(d[2]), "+f"(d[3]), "+f"(d[4]), "+f"(d[5]), "+f"(d[6]), "+f"(d[7]),
          "+f"(d[8]), "+f"(d[9]), "+f"(d[10]), "+f"(d[11]), "+f"(d[12]), "+f"(d[13]), "+f"(d[14]), "+f"(d[15]),
          "+f"(d[16]), "+f"(d[17]), "+f"(d[18]), "+f"(d[19]), "+f"(d[20]), "+f"(d[21]), "+f"(d[22]), "+f"(d[23]),
          "+f"(d[24]), "+f"(d[25]), "+f"(d[26]), "+f"(d[27]), "+f"(d[28]), "+f"(d[29]), "+f"(d[30]), "+f"(d[31]),
          "+f"(d[32]), "+f"(d[33]), "+f"(d[34]), "+f"(d[35]), "+f"(d[36]), "+f"(d[37]), "+f"(d[38]), "+f"(d[39]),
          "+f"(d[40]), "+f"(d[41]), "+f"(d[42]), "+f"(d[43]), "+f"(d[44]), "+f"(d[45]), "+f"(d[46]), "+f"(d[47]),
          "+f"(d[48]), "+f"(d[49]), "+f"(d[50]), "+f"(d[51]), "+f"(d[52]), "+f"(d[53]), "+f"(d[54]), "+f"(d[55]),
          "+f"(d[56]), "+f"(d[57]), "+f"(d[58]), "+f"(d[59]), "+f"(d[60]), "+f"(d[61]), "+f"(d[62]), "+f"(d[63]),
          "+f"(d[64]), "+f"(d[65]), "+f"(d[66]), "+f"(d[67]), "+f"(d[68]), "+f"(d[69]), "+f"(d[70]), "+f"(d[71]),
          "+f"(d[72]), "+f"(d[73]), "+f"(d[74]), "+f"(d[75]), "+f"(d[76]), "+f"(d[77]), "+f"(d[78]), "+f"(d[79]),
          "+f"(d[80]), "+f"(d[81]), "+f"(d[82]), "+f"(d[83]), "+f"(d[84]), "+f"(d[85]), "+f"(d[86]), "+f"(d[87])
        : "l"(da), "l"(db));
}
__device__ __forceinline__ void wgmma_n256_z(float (&d)[128], uint64_t da, uint64_t db) {
    asm volatile("{\n.reg .pred p;\nsetp.ne.b32 p, 0, 0;\n"
        "wgmma.mma_async.sync.aligned.m64n256k16.f32.bf16.bf16 {"
        "%0, %1, %2, %3, %4, %5, %6, %7, %8, %9, %10, %11, %12, %13, %14, %15, "
        "%16, %17, %18, %19, %20, %21, %22, %23, %24, %25, %26, %27, %28, %29, %30, %31, "
        "%32, %33, %34, %35, %36, %37, %38, %39, %40, %41, %42, %43, %44, %45, %46, %47, "
        "%48, %49, %50, %51, %52, %53, %54, %55, %56, %57, %58, %59, %60, %61, %62, %63, "
        "%64, %65, %66, %67, %68, %69, %70, %71, %72, %73, %74, %75, %76, %77, %78, %79, "
        "%80, %81, %82, %83, %84, %85, %86, %87, %88, %89, %90, %91, %92, %93, %94, %95, "
        "%96, %97, %98, %99, %100, %101, %102, %103, %104, %105, %106, %107, %108, %109, %110, %111, "
        "%112, %113, %114, %115, %116, %117, %118, %119, %120, %121, %122, %123, %124, %125, %126, %127"
        "}, %128, %129, p, 1, 1, 0, 1;\n}\n"
        : "=f"(d[0]), "=f"(d[1]), "=f"(d[2]), "=f"(d[3]), "=f"(d[4]), "=f"(d[5]), "=f"(d[6]), "=f"(d[7]),
          "=f"(d[8]), "=f"(d[9]), "=f"(d[10]), "=f"(d[11]), "=f"(d[12]), "=f"(d[13]), "=f"(d[14]), "=f"(d[15]),
          "=f"(d[16]), "=f"(d[17]), "=f"(d[18]), "=f"(d[19]), "=f"(d[20]), "=f"(d[21]), "=f"(d[22]), "=f"(d[23]),
          "=f"(d[24]), "=f"(d[25]), "=f"(d[26]), "=f"(d[27]), "=f"(d[28]), "=f"(d[29]), "=f"(d[30]), "=f"(d[31]),
          "=f"(d[32]), "=f"(d[33]), "=f"(d[34]), "=f"(d[35]), "=f"(d[36]), "=f"(d[37]), "=f"(d[38]), "=f"(d[39]),
          "=f"(d[40]), "=f"(d[41]), "=f"(d[42]), "=f"(d[43]), "=f"(d[44]), "=f"(d[45]), "=f"(d[46]), "=f"(d[47]),
          "=f"(d[48]), "=f"(d[49]), "=f"(d[50]), "=f"(d[51]), "=f"(d[52]), "=f"(d[53]), "=f"(d[54]), "=f"(d[55]),
          "=f"(d[56]), "=f"(d[57]), "=f"(d[58]), "=f"(d[59]), "=f"(d[60]), "=f"(d[61]), "=f"(d[62]), "=f"(d[63]),
          "=f"(d[64]), "=f"(d[65]), "=f"(d[66]), "=f"(d[67]), "=f"(d[68]), "=f"(d[69]), "=f"(d[70]), "=f"(d[71]),
          "=f"(d[72]), "=f"(d[73]), "=f"(d[74]), "=f"(d[75]), "=f"(d[76]), "=f"(d[77]), "=f"(d[78]), "=f"(d[79]),
          "=f"(d[80]), "=f"(d[81]), "=f"(d[82]), "=f"(d[83]), "=f"(d[84]), "=f"(d[85]), "=f"(d[86]), "=f"(d[87]),
          "=f"(d[88]), "=f"(d[89]), "=f"(d[90]), "=f"(d[91]), "=f"(d[92]), "=f"(d[93]), "=f"(d[94]), "=f"(d[95]),
          "=f"(d[96]), "=f"(d[97]), "=f"(d[98]), "=f"(d[99]), "=f"(d[100]), "=f"(d[101]), "=f"(d[102]), "=f"(d[103]),
          "=f"(d[104]), "=f"(d[105]), "=f"(d[106]), "=f"(d[107]), "=f"(d[108]), "=f"(d[109]), "=f"(d[110]), "=f"(d[111]),
          "=f"(d[112]), "=f"(d[113]), "=f"(d[114]), "=f"(d[115]), "=f"(d[116]), "=f"(d[117]), "=f"(d[118]), "=f"(d[119]),
          "=f"(d[120]), "=f"(d[121]), "=f"(d[122]), "=f"(d[123]), "=f"(d[124]), "=f"(d[125]), "=f"(d[126]), "=f"(d[127])
        : "l"(da), "l"(db));
}
__device__ __forceinline__ void wgmma_n256(float (&d)[128], uint64_t da, uint64_t db) {
    asm volatile("{\n.reg .pred p;\nsetp.eq.b32 p, 0, 0;\n"
        "wgmma.mma_async.sync.aligned.m64n256k16.f32.bf16.bf16 {"
        "%0, %1, %2, %3, %4, %5, %6, %7, %8, %9, %10, %11, %12, %13, %14, %15, "
        "%16, %17, %18, %19, %20, %21, %22, %23, %24, %25, %26, %27, %28, %29, %30, %31, "
        "%32, %33, %34, %35, %36, %37, %38, %39, %40, %41, %42, %43, %44, %45, %46, %47, "
        "%48, %49, %50, %51, %52, %53, %54, %55, %56, %57, %58, %59, %60, %61, %62, %63, "
        "%64, %65, %66, %67, %68, %69, %70, %71, %72, %73, %74, %75, %76, %77, %78, %79, "
        "%80, %81, %82, %83, %84, %85, %86, %87, %88, %89, %90, %91, %92, %93, %94, %95, "
        "%96, %97, %98, %99, %100, %101, %102, %103, %104, %105, %106, %107, %108, %109, %110, %111, "
        "%112, %113, %114, %115, %116, %117, %118, %119, %120, %121, %122, %123, %124, %125, %126, %127"
        "}, %128, %129, p, 1, 1, 0, 1;\n}\n"
        : "+f"(d[0]), "+f"(d[1]), "+f"(d[2]), "+f"(d[3]), "+f"(d[4]), "+f"(d[5]), "+f"(d[6]), "+f"(d[7]),
          "+f"(d[8]), "+f"(d[9]), "+f"(d[10]), "+f"(d[11]), "+f"(d[12]), "+f"(d[13]), "+f"(d[14]), "+f"(d[15]),
          "+f"(d[16]), "+f"(d[17]), "+f"(d[18]), "+f"(d[19]), "+f"(d[20]), "+f"(d[21]), "+f"(d[22]), "+f"(d[23]),
          "+f"(d[24]), "+f"(d[25]), "+f"(d[26]), "+f"(d[27]), "+f"(d[28]), "+f"(d[29]), "+f"(d[30]), "+f"(d[31]),
          "+f"(d[32]), "+f"(d[33]), "+f"(d[34]), "+f"(d[35]), "+f"(d[36]), "+f"(d[37]), "+f"(d[38]), "+f"(d[39]),
          "+f"(d[40]), "+f"(d[41]), "+f"(d[42]), "+f"(d[43]), "+f"(d[44]), "+f"(d[45]), "+f"(d[46]), "+f"(d[47]),
          "+f"(d[48]), "+f"(d[49]), "+f"(d[50]), "+f"(d[51]), "+f"(d[52]), "+f"(d[53]), "+f"(d[54]), "+f"(d[55]),
          "+f"(d[56]), "+f"(d[57]), "+f"(d[58]), "+f"(d[59]), "+f"(d[60]), "+f"(d[61]), "+f"(d[62]), "+f"(d[63]),
          "+f"(d[64]), "+f"(d[65]), "+f"(d[66]), "+f"(d[67]), "+f"(d[68]), "+f"(d[69]), "+f"(d[70]), "+f"(d[71]),
          "+f"(d[72]), "+f"(d[73]), "+f"(d[74]), "+f"(d[75]), "+f"(d[76]), "+f"(d[77]), "+f"(d[78]), "+f"(d[79]),
          "+f"(d[80]), "+f"(d[81]), "+f"(d[82]), "+f"(d[83]), "+f"(d[84]), "+f"(d[85]), "+f"(d[86]), "+f"(d[87]),
          "+f"(d[88]), "+f"(d[89]), "+f"(d[90]), "+f"(d[91]), "+f"(d[92]), "+f"(d[93]), "+f"(d[94]), "+f"(d[95]),
          "+f"(d[96]), "+f"(d[97]), "+f"(d[98]), "+f"(d[99]), "+f"(d[100]), "+f"(d[101]), "+f"(d[102]), "+f"(d[103]),
          "+f"(d[104]), "+f"(d[105]), "+f"(d[106]), "+f"(d[107]), "+f"(d[108]), "+f"(d[109]), "+f"(d[110]), "+f"(d[111]),
          "+f"(d[112]), "+f"(d[113]), "+f"(d[114]), "+f"(d[115]), "+f"(d[116]), "+f"(d[117]), "+f"(d[118]), "+f"(d[119]),
          "+f"(d[120]), "+f"(d[121]), "+f"(d[122]), "+f"(d[123]), "+f"(d[124]), "+f"(d[125]), "+f"(d[126]), "+f"(d[127])
        : "l"(da), "l"(db));
}

struct Idx {
    uint32_t lane, warp, w4, q4, g8, prow, pan;
    __device__ __forceinline__ Idx() {
        uint32_t t; asm volatile("mov.u32 %0, %%tid.x;" : "=r"(t));
        lane = t & 31; warp = t >> 5; w4 = warp & 3; q4 = lane & 3; g8 = lane >> 2;
        prow = w4 * 16 + ((lane >> 3) & 1) * 8 + (lane & 7);
        pan = prow * 128 + (((lane >> 4) ^ (lane & 7)) << 4);
    }
};
#define IDX() const Idx ix; const uint32_t lane = ix.lane, warp = ix.warp, w4 = ix.w4, q4 = ix.q4, g8 = ix.g8, prow = ix.prow, pan_addr = ix.pan; \
    (void)lane; (void)warp; (void)w4; (void)q4; (void)g8; (void)prow; (void)pan_addr;

__device__ __forceinline__ int kof(int t, int sh, int j) {
    const int p = t >> (sh - 1), pn = p < 2 ? p : p >= 9, q = p - 2 - 7 * pn;
    return ((p < 2 ? j : q + (q >= j)) << 7) + (pn << 6) + ((t & (sh - 1)) << 5);
}
__device__ __forceinline__ uint32_t fidx(uint32_t m, uint32_t w, uint32_t pn) {
    return m * 32 + w * 16 + pn;
}
constexpr int HC0 = 8 * 48, HC3 = HC0 + 3072;
__device__ __forceinline__ int hcol(int p, int j) { return HC0 + p * 1024 + j * 128; }
struct Ring {
    uint32_t slot, par;
    __device__ __forceinline__ void next() { if (++slot == NSLOT) { slot = 0; par ^= 1; } }
    __device__ __forceinline__ void skip(uint32_t n) { slot += n; if (slot >= NSLOT) { slot -= NSLOT; par ^= 1; } }
};
__device__ __forceinline__ uint32_t BAR_FULL(uint32_t sb, uint32_t s) { return sb + OFF_BAR + 8 * s; }
constexpr uint32_t AF_REL = 48;
__device__ __forceinline__ uint32_t BAR_EMPTY(uint32_t sb, uint32_t s) { return sb + OFF_BAR + 96 + 8 * s; }
__device__ __forceinline__ uint32_t BAR_SFULL(uint32_t sb, uint32_t i) { return sb + OFF_BAR + 152 + 8 * i; }
__device__ __forceinline__ uint32_t BAR_SREADY(uint32_t sb, uint32_t i) { return sb + OFF_BAR + 184 + 8 * i; }
__device__ __forceinline__ uint32_t BAR_ONE(uint32_t sb, uint32_t i) { return sb + OFF_BAR + 216 + 8 * i; }
enum { EV_WIN, EV_WIN1, EV_WIN2, EV_WIN3, EV_P0, EV_GA, EV_GB, EV_LN2, EV_LAG1, EV_LAG2, EV_LAG3, EV_LAG4, EV_LAG5, EV_KV, EV_PAR, EV_AGO, EV_AGO1, EV_AGO2, EV_FGO, EV_FGO1, EV_FGO2, EV_H0, EV_H1, EV_H2, EV_H3, EV_TAIL, EV_COUNT = EV_TAIL + 8 };
constexpr int NB_TAIL = 4;

struct Rel {
    uint32_t base; bool sig;
    __device__ __forceinline__ Rel(uint32_t sb, uint32_t tw) {
        uint32_t a; asm("mapa.shared::cluster.u32 %0, %1, %2;" : "=r"(a) : "r"(BAR_EMPTY(sb, 0)), "r"((tw >> 5) & 1));
        base = __shfl_sync(0xffffffffu, a, 0); sig = (tw & ~32u) == 0;
    }
    __device__ __forceinline__ void operator()(uint32_t slot) const {
        if (sig) asm volatile("mbarrier.arrive.shared::cluster.b64 _, [%0];" :: "r"(base + 8 * slot) : "memory");
    }
};
struct LnRow { float rs0, nm0, rs1, nm1; };
struct Pipe {
    Rel rel; uint32_t p1, p2;
    __device__ __forceinline__ Pipe(uint32_t sb, uint32_t tw, uint32_t first) : rel(sb, tw), p1(first), p2(NSLOT) {}
    template <bool TWO> __device__ __forceinline__ void acquire(uint32_t sb, uint32_t af, const Ring& r) {
        const uint32_t b0 = BAR_FULL(sb, r.slot), b1 = b0 + af;
        const bool ready = TWO ? mbar_test2(b0, b1, r.par) : mbar_test(b0, r.par);
        wg_wait<1>();
        rel(p2);
        if (!ready) { if (TWO) mbar_wait2(b0, b1, r.par); else mbar_wait(b0, r.par); }
    }
    __device__ __forceinline__ void issued(uint32_t slot) { p2 = p1; p1 = slot; }
    __device__ __forceinline__ void drain1() { wg_wait<1>(); rel(p2); p2 = NSLOT; }
    __device__ __forceinline__ void drain0() { wg_wait<0>(); rel(p1); p1 = NSLOT; }
    template <bool TWO, class Step> __device__ __forceinline__ void hold(int LG, uint32_t sb, uint32_t af, Ring& r, uint32_t lag_bar, Step step) {
        Ring q = r;
#pragma unroll 1
        for (int i = 0; i < LG; ++i) { if (TWO) mbar_wait2(BAR_FULL(sb, q.slot), BAR_FULL(sb, q.slot) + af, q.par); else mbar_wait(BAR_FULL(sb, q.slot), q.par); q.next(); }
        mbar_wait(lag_bar, 0);
#pragma unroll 1
        do {
            step(r.slot);
            wg_wait<2>(); rel(p2); p2 = p1; p1 = r.slot;
            if (++r.slot == NSLOT) r.slot = 0;
        } while (r.slot != q.slot);
        r.par = q.par;
    }
};
template <bool TWO, bool FIRST, int NA, int NB>
__device__ __forceinline__ void step32(float (&aa)[NA], float (&ab)[NB], uint32_t sb, uint32_t wg, uint32_t slot, int own) {
    const uint32_t st = d16(sb) + slot * (SLOT >> 4);
    const uint32_t alo = own >= 0 ? d16(sb) + OFF_STG / 16 + wg * 1024 + (own >> 1) * 512 + (own & 1) * 4 : st + wg * 256;
    const uint32_t ahi = own >= 0 ? (1024 >> 4) | (1u << 30) : (512 >> 4) | (2u << 30);
    wg_fence();
#pragma unroll
    for (int k = 0; k < 2; ++k) {
        const uint64_t da = ((uint64_t)ahi << 32) | (alo + k * 2 + 0x10000);
        if constexpr (NA == 88) {
            const uint64_t d0 = mk_desc(st, 8192 + k * 2048, 8192, 1024, 1), d1 = mk_desc(st, 12288 + k * 2048, 8192, 1024, 1);
            if (FIRST && k == 0) { wgmma_n176_z(aa, da, d0); wgmma_n176_z(ab, da, d1); }
            else { wgmma_n176(aa, da, d0); wgmma_n176(ab, da, d1); }
        } else {
            const uint64_t d0 = mk_desc(st, 8192 + k * 2048, 4096, 1024, 1), d1 = mk_desc(st, 24576 + k * 2048, 4096, 1024, 1);
            if (FIRST && k == 0) { wgmma_n256_z(aa, da, d0); if constexpr (TWO) wgmma_n128_z(ab, da, d1); }
            else { wgmma_n256(aa, da, d0); if constexpr (TWO) wgmma_n128(ab, da, d1); }
        }
    }
    wg_commit();
}
template <bool TWO, int LG, int NA, int NB, class Mid, class Tail>
__device__ __forceinline__ void mainloop32(float (&aa)[NA], float (&ab)[NB], uint32_t sb, uint32_t wg, uint32_t tw, Ring& r, uint32_t lag_ev, int g0, Mid mid, Tail tail) {
    step32<TWO, true>(aa, ab, sb, wg, r.slot, TWO ? 0 : -1);
    TS(g0, 0);
    Pipe pp(sb, tw, r.slot);
    r.next();
    const int end = wg ? 32 : 32 - LG;
#pragma unroll 1
    for (int it = 1; it < end; ++it) {
        pp.acquire<TWO>(sb, wg ? 0 : AF_REL, r);
        step32<TWO, false>(aa, ab, sb, wg, r.slot, TWO && it < 4 ? it : -1);
        pp.issued(r.slot);
        TS(g0 + it, 0);
        r.next();
        mid(it);
    }
    if (wg == 0) { pp.drain1(); pp.drain0(); pp.hold<TWO>(LG, sb, AF_REL, r, BAR_ONE(sb, lag_ev), [&](uint32_t slot) { step32<TWO, false>(aa, ab, sb, 0, slot, -1); }); }
    if (wg == 1 && tw == 0) mbar_arrive(BAR_ONE(sb, lag_ev));
    pp.drain1();
    tail();
    pp.drain0();
    TS(g0 + 31, 1);
}
template <bool FIRST>
__device__ __forceinline__ void step64(float (&acc)[64], uint32_t sb, uint32_t wg, uint32_t slot, int own) {
    const uint32_t sbb = d16(sb) + slot * (SLOT >> 4), sa = own >= 0 ? d16(sb) + OFF_STG / 16 + wg * 1024 + own * 512 : sbb + wg * 512;
    wg_fence();
#pragma unroll
    for (int k = 0; k < 4; ++k) {
        const uint64_t da = mk_desc(sa, k * 32, 16, 1024, 1), db = mk_desc(sbb, 16384 + k * 2048, 8192, 1024, 1);
        if (FIRST && k == 0) wgmma_n128_z(acc, da, db); else wgmma_n128(acc, da, db);
    }
    wg_commit();
}
template <class Put, class Mid, class Tail>
__device__ __forceinline__ void mainloop64(float (&acc)[64], bool wo, uint32_t sb, uint32_t wg, uint32_t tw, Ring& r, Put put, Mid mid, Tail tail) {
    const int g0 = wo ? 32 : 144, nst = wo ? 16 : 56, lg = wo ? LAGW : LAGD; (void)g0;
    const uint32_t lag_bar = BAR_ONE(sb, wo ? EV_LAG4 : EV_LAG5), af = wo && !wg ? AF_REL : 0;
    if (!wo) CS(28);
    step64<true>(acc, sb, wg, r.slot, wo ? 0 : -1);
    if (!wo) CS(29);
    TS(g0, 0);
    Pipe pp(sb, tw, r.slot);
    r.next();
    int it = 1;
    auto run = [&](int end, int own, bool with_put) {
#pragma unroll 1
        do {
            pp.acquire<true>(sb, af, r);
            step64<false>(acc, sb, wg, r.slot, own);
            pp.issued(r.slot);
            TS(g0 + it, 0);
            if (wo && it == 2) CS(9);
            r.next();
            if (with_put && it == (wg ? PUTD1 : PUTD0)) put();
        } while (++it < end);
    };
    const int end = wg ? nst : nst - lg;
    run(wo ? 2 : wg ? MIDD : end, wo ? 1 : -1, true);
    mid();
    if (wo) { pp.drain1(); pp.drain0(); TS(g0 + 1, 1); }
    if (it < end) run(end, -1, false);
    if (wg == 0) { pp.drain1(); pp.drain0(); pp.hold<true>(lg, sb, af, r, lag_bar, [&](uint32_t slot) { step64<false>(acc, sb, 0, slot, -1); }); }
    if (wg == 1 && tw == 0) mbar_arrive(lag_bar);
    pp.drain1();
    tail();
    pp.drain0();
    TS(g0 + nst - 1, 1);
}

struct RowAcc {
    float sm[4] = {0.f, 0.f, 0.f, 0.f}, sq[4] = {0.f, 0.f, 0.f, 0.f};
    __device__ __forceinline__ void add(int e, float x) { sm[e & 3] += x; sq[e & 3] = fmaf(x, x, sq[e & 3]); }
    __device__ __forceinline__ void publish(uint4* dst, uint32_t q4, uint32_t ep) const {
        const float s0 = sm[0] + sm[1], s1 = sm[2] + sm[3], q0 = sq[0] + sq[1], q1 = sq[2] + sq[3];
        const bool od = q4 & 1;
        float sv = (od ? s1 : s0) + __shfl_xor_sync(0xffffffffu, od ? s0 : s1, 1), qv = (od ? q1 : q0) + __shfl_xor_sync(0xffffffffu, od ? q0 : q1, 1);
        sv += __shfl_xor_sync(0xffffffffu, sv, 2); qv += __shfl_xor_sync(0xffffffffu, qv, 2);
        st_pkt16(dst + (q4 & 1) * 8, 0, __float_as_uint(sv), __float_as_uint(qv), ep);
    }
};
__device__ __forceinline__ LnRow merge_stats(const uint4* src, uint32_t q4, uint32_t ep, uint32_t sb) {
    uint4 t[4];
    uint32_t n = 0;
    while (true) {
#pragma unroll
        for (int i = 0; i < 4; ++i) t[i] = ld_pkt16(src + (q4 * 2 + (i >> 1)) * 512 + (i & 1) * 8);
        const bool ok_ = __all_sync(0xffffffffu, t[0].w == ep && t[1].w == ep && t[2].w == ep && t[3].w == ep);
        if (n < 4) CS(14 + n);
        if (ok_) break;
        SPIN_GUARD(n);
    }
    float v[4];
#pragma unroll
    for (int h = 0; h < 2; ++h) { v[h] = __uint_as_float(t[h].y) + __uint_as_float(t[2 + h].y); v[2 + h] = __uint_as_float(t[h].z) + __uint_as_float(t[2 + h].z); }
#pragma unroll
    for (int o = 1; o < 4; o <<= 1)
#pragma unroll
        for (int i = 0; i < 4; ++i) v[i] += __shfl_xor_sync(0xffffffffu, v[i], o);
    const float m0 = v[0] * (1.f / D_), m1 = v[1] * (1.f / D_);
    const float r0 = rsq(fmaxf(fmaf(-m0, m0, v[2] * (1.f / D_)), 0.f) + 1e-5f), r1 = rsq(fmaxf(fmaf(-m1, m1, v[3] * (1.f / D_)), 0.f) + 1e-5f);
    return LnRow{r0, -m0 * r0, r1, -m1 * r1};
}
struct Stg {
    uint32_t b, par;
    __device__ __forceinline__ uint32_t acquire2(uint32_t sb, uint32_t wg) {
        mbar_wait2(BAR_SREADY(sb, wg * 2), BAR_SREADY(sb, wg * 2 + 1), par);
        par ^= 1;
        return sb + OFF_STG + wg * 16384;
    }
    __device__ __forceinline__ void publish(uint32_t sb, uint32_t wg, uint32_t lane) {
        fence_async_smem();
        __syncwarp();
        if (lane == 0) mbar_arrive(BAR_SFULL(sb, wg * 2 + b));
        b ^= 1;
    }
};

struct LnPar {
    uint4 p[8];
    __device__ __forceinline__ void load(uint32_t sb, uint32_t q4) {
#pragma unroll
        for (int i = 0; i < 8; ++i) p[i] = lds128(sb + OFF_PAR + i * 64 + q4 * 16);
    }
};
__device__ __forceinline__ void ln_norm(uint32_t (&xn)[32], const float (&x)[64], const LnRow& n) {
#pragma unroll
    for (int e = 0; e < 32; ++e) {
        const float rs = (e & 1) ? n.rs1 : n.rs0, nm = (e & 1) ? n.nm1 : n.nm0;
        xn[e] = pack2(fmaf(x[2 * e], rs, nm), fmaf(x[2 * e + 1], rs, nm));
    }
}
__device__ __forceinline__ void ln_emit(const uint32_t (&xr)[32], const LnPar& lp, uint32_t sb, uint32_t wg, const Idx& ix) {
#pragma unroll
    for (int i = 0; i < 8; ++i)
        stsm4(sb + OFF_STG + wg * 16384 + (i >> 2) * 8192 + (ix.pan ^ ((i & 3) << 5)), hfma2_bf16(xr[4 * i], lp.p[i].z, lp.p[i].x), hfma2_bf16(xr[4 * i + 1], lp.p[i].z, lp.p[i].x),
              hfma2_bf16(xr[4 * i + 2], lp.p[i].w, lp.p[i].y), hfma2_bf16(xr[4 * i + 3], lp.p[i].w, lp.p[i].y));
    fence_async_smem();
    __syncwarp();
    if (ix.lane < 2) mbar_arrive(BAR_SFULL(sb, wg * 2 + ix.lane));
    bar_sync(1 + wg, 128);
}
__device__ __forceinline__ void load_slab(uint32_t (&xr)[32], uint32_t buf) {
    IDX();
#pragma unroll
    for (int i = 0; i < 8; ++i) ldsm4(buf + (i >> 2) * 8192 + (pan_addr ^ ((i & 3) << 5)), xr[4 * i], xr[4 * i + 1], xr[4 * i + 2], xr[4 * i + 3]);
}
__device__ __forceinline__ void unpack_slab(float (&x)[64], const uint32_t (&xr)[32]) {
#pragma unroll
    for (int i = 0; i < 32; ++i) unpack2(xr[i], x[2 * i], x[2 * i + 1]);
}
__device__ __forceinline__ void store_slab(const float (&x)[64], uint32_t buf, uint32_t pitch, uint32_t pan, int i0, int i1) {
#pragma unroll
    for (int i = i0; i < i1; ++i)
        stsm4(buf + (i >> 2) * pitch + (pan ^ ((i & 3) << 5)), pack2(x[8 * i], x[8 * i + 1]), pack2(x[8 * i + 2], x[8 * i + 3]), pack2(x[8 * i + 4], x[8 * i + 5]), pack2(x[8 * i + 6], x[8 * i + 7]));
}
template <int NP, class Done>
__device__ __forceinline__ void fetch_halo(uint4* src, bool first, uint32_t dst, Done done) {
    uint4 hv[4 * NP];
    uint32_t n = 0;
    while (true) {
        bool ok = true;
#pragma unroll
        for (int i = 0; i < 4 * NP; ++i) { hv[i] = first ? make_uint4(0, 0, 0, 0) : ld_pkt16(src + (i >> 2) * 256 + (i & 3) * 32); ok = ok && hv[i].x != 0; }
        if (first || __all_sync(0xffffffffu, ok)) break;
        SPIN_GUARD(n);
    }
#pragma unroll
    for (int i = 0; i < 4 * NP; ++i) stsm4(dst + (i >> 2) * 4096 + (i & 3) * 512, hv[i].x, hv[i].y, hv[i].z, hv[i].w);
    done();
    if (!first) {
#pragma unroll
        for (int i = 0; i < 4 * NP; ++i) src[(i >> 2) * 256 + (i & 3) * 32] = make_uint4(0, 0, 0, 0);
    }
}

template <int N, class G, class U>
__device__ __forceinline__ void glu(uint32_t (&h)[N], G g, U u) {
#pragma unroll
    for (int i = 0; i < N; ++i) h[i] = pack2(fmaf(tanh_(g(2 * i)), u(2 * i), u(2 * i)), fmaf(tanh_(g(2 * i + 1)), u(2 * i + 1), u(2 * i + 1)));
}
__device__ __forceinline__ void put_h(const uint32_t (&h)[32], uint32_t sb, uint32_t wg, Stg& stg) {
    IDX();
    const uint32_t buf = stg.acquire2(sb, wg);
#pragma unroll
    for (int k = 0; k < 8; ++k) stsm4(buf + (k >> 2) * 8192 + (pan_addr ^ ((k & 3) << 5)), h[4 * k], h[4 * k + 1], h[4 * k + 2], h[4 * k + 3]);
    fence_async_smem();
    __syncwarp();
    if (lane < 2) mbar_arrive(BAR_SFULL(sb, wg * 2 + lane));
}

template <int NP, bool PREV>
__device__ __forceinline__ void passes128(uint32_t (&hp)[32], uint32_t sb, uint32_t wg, uint32_t tw, Ring& r, Stg& stg) {
#pragma unroll 1
    for (int p = 0; p < NP; ++p) {
        float b256[128], none[1];
        const int put_at = !PREV && p == 0 ? -1 : wg ? PUT1 : PUT0;
        mainloop32<false, LAGS>(b256, none, sb, wg, tw, r, EV_LAG2 + p, 80 + 32 * (p & 1), [&](int it) { if (it == put_at) put_h(hp, sb, wg, stg); },
                                [&] { if (PREV || p < NP - 1) mbar_wait(BAR_FULL(sb, r.slot), r.par); });
        if (threadIdx.x == 0) { TL(29 + 2 * p); TC(114 + 2 * p); }
        if (threadIdx.x == 128) TL(53 + 2 * (p & 1));
        CS(24 + 2 * (p & 1));
        glu(hp, [&](int i) { return b256[i + (i & 32)]; }, [&](int i) { return b256[i + (i & 32) + 32]; });
        if (threadIdx.x == 0) { TL(30 + 2 * p); TC(115 + 2 * p); }
        if (threadIdx.x == 128) TL(54 + 2 * (p & 1));
        CS(25 + 2 * (p & 1));
    }
}

__global__ void __launch_bounds__(384, 1)
fused_block_kernel(const __grid_constant__ Ptrs pt, const __grid_constant__ Maps mp) {
    uint32_t* const g_flags = pt.mail->flags;
    uint2* const g_mod = pt.mail->mod;
    uint4* const g_st1 = pt.mail->st1;
    uint32_t* const g_par2 = pt.mail->par2;
    uint4* const g_halo = pt.mail->halo;
    const __nv_bfloat16* __restrict__ cvec = pt.c;
    if (threadIdx.x == 224) { prefetch_map(&mp.wm8); prefetch_map(&mp.x); }
    extern __shared__ __align__(1024) uint8_t smem[];
    const uint32_t sb = smem_u32(smem);
    const uint32_t tid = threadIdx.x, tw = tid & 127, lane = tid & 31;
    const uint32_t warp = __shfl_sync(0xffffffffu, tid >> 5, 0), wg = warp >> 2;
    uint32_t rank; asm("mov.u32 %0, %%cluster_ctarank;" : "=r"(rank));
    rank = __shfl_sync(0xffffffffu, rank, 0);
    uint32_t ep;
    uint32_t smid; asm volatile("mov.u32 %0, %%smid;" : "=r"(smid));
    const int c = __shfl_sync(0xffffffffu, smid >> 1, 0);
    const int c7 = ((c - 32) * 37) >> 8;
    int grp = c < 32 ? c & 7 : c < 60 ? c - 31 - 7 * c7 : c < 62 ? -1 : 0;
    const int j = c < 32 ? c >> 3 : c < 60 ? 4 + c7 : c < 62 ? (c - 60) * 2 + rank : c - 58;
    const bool aux = grp < 0;
    const int m = grp * 2 + rank;
    uint4* const g_st2 = g_halo + (m > 0 ? (m - 1) * 8 * 512 : 128);

    bool cluster_arrive_early = false;
    if (wg < 2) {
      if (!KDEBUG) cluster_arrive();
      ep = flag_get(g_flags + FL_DONE);
      uint16_t cw[8];
      {
          const __nv_bfloat16* cp = cvec + ((tw >> 5) * 32 + (tw & 3) * 2) * 8 + (lane >> 2);
#pragma unroll
          for (int i = 0; i < 8; ++i) asm volatile("ld.global.nc.u16 %0, [%1];" : "=h"(cw[i]) : "l"(cp + (i >> 1) * 64 + (i & 1) * 8));
      }
      asm volatile("setmaxnreg.inc.sync.aligned.u32 224;");
      if (tid == 0) TL(58);
      if (KDEBUG) cluster_arrive();
      Ring r{0, 0};
      Stg stg{0, 0};
      if (aux) {
        if (wg == 0) {
            const uint4 cv = *(const uint4*)(cvec + tw * 8);
            sts128(sb + OFF_STG + (tw >> 3) * 1024 + (tw & 7) * 16, pack2(silu_(bf_lo(cv.x)), silu_(bf_hi(cv.x))), pack2(silu_(bf_lo(cv.y)), silu_(bf_hi(cv.y))),
                   pack2(silu_(bf_lo(cv.z)), silu_(bf_hi(cv.z))), pack2(silu_(bf_lo(cv.w)), silu_(bf_hi(cv.w))));
            fence_async_smem();
        }
        cluster_wait();
        ep = __shfl_sync(0xffffffffu, ep, 0) / NCTA + 1;
        if (wg == 0) {
            bar_sync(1, 128);
#pragma unroll 1
            for (int p = 0; p < 4; ++p) {
                float acc[128];
#pragma unroll
                for (int i = 0; i < 128; ++i) acc[i] = 0.f;
                uint32_t prev = 0;
#pragma unroll 1
                for (int kc = 0; kc < 16; ++kc) {
                    mbar_wait(BAR_FULL(sb, r.slot), r.par);
                    wg_fence();
#pragma unroll
                    for (int k = 0; k < 4; ++k)
                        wgmma_n256(acc, mk_desc(d16(sb) + kc * 64, OFF_STG + k * 32, 16, 0, 1), mk_desc(d16(sb) + r.slot * (SLOT >> 4), k * 2048, 8192, 1024, 1));
                    wg_commit();
                    wg_wait<1>();
                    if (kc > 0 && tw < 4) mbar_arrive(BAR_EMPTY(sb, prev));
                    prev = r.slot;
                    r.next();
                }
                wg_wait<0>();
                if (tw < 4) mbar_arrive(BAR_EMPTY(sb, prev));
                if (tw < 4) {
#pragma unroll
                    for (int jn = 0; jn < 32; ++jn) sts32(sb + OFF_TAB + (jn * 4 + tw) * 4, pack2(acc[jn * 4], acc[jn * 4 + 1]));
                }
                bar_sync(1, 128);
                const int vec = 2 + p, blk = p * 4 + j;
                const uint32_t val = lds32(sb + OFF_TAB + tw * 4);
                if (vec == 2 || vec == 5) st_pkt(g_mod + (8 + blk) * 128 + tw, val, ep);
                else {
                    const float one = vec == 4 ? 1.f : 0.f;
                    g_par2[((blk & 3) * 16 + (tw >> 3)) * 16 + (tw & 3) * 4 + (vec - 3) * 2 + ((tw >> 2) & 1)] =
                        pack2(0.5f * bf_round(one + bf_lo(val)), 0.5f * bf_round(one + bf_hi(val)));
                }
                bar_sync(1, 128);
                if (tw == 0) {
                    if (vec == 3 || vec == 4) asm volatile("red.release.gpu.global.add.u32 [%0], 1;" :: "l"(&g_flags[FL_LN2]) : "memory");
                    TL(1 + p);
                }
            }
            if (lane < 2) mbar_arrive_cta(BAR_ONE(sb, EV_P0), lane);
        }
        r = Ring{64 % NSLOT, (64 / NSLOT) & 1};
        mbar_wait(BAR_ONE(sb, EV_P0), 0);
        mbar_wait(BAR_FULL(sb, r.slot), r.par);
        uint32_t hp[32] = {};
        passes128<4, false>(hp, sb, wg, tw, r, stg);
        put_h(hp, sb, wg, stg);
      } else {
        float xs[64];
        uint32_t xp[32];
        {
            sts128(sb + tid * 16, pack2(silu_(bf_lo(cw[0])), silu_(bf_lo(cw[1]))), pack2(silu_(bf_lo(cw[2])), silu_(bf_lo(cw[3]))),
                   pack2(silu_(bf_lo(cw[4])), silu_(bf_lo(cw[5]))), pack2(silu_(bf_lo(cw[6])), silu_(bf_lo(cw[7]))));
            cluster_wait();
            ep = __shfl_sync(0xffffffffu, ep, 0) / NCTA + 1;
            load_slab(xp, stg.acquire2(sb, wg));
            unpack_slab(xs, xp);
            if (tid == 0) TL(24);
            if (tid == 128) TL(27);
        }
#pragma unroll 1
        for (int blk = 0; ; ++blk) {
        {
            IDX();
            uint4* const st = (blk ? g_st2 : g_st1 + m * 8 * 512) + wg * 64 + w4 * 16 + g8;
            RowAcc ra;
#pragma unroll
            for (int e = 0; e < 64; ++e) ra.add(e, xs[e]);
            ra.publish(st + j * 512, q4, ep);
            uint32_t t_pub = 0; if (PDLY) asm volatile("mov.u32 %0, %%clock;" : "=r"(t_pub));
            if (tid == 0) TL(blk ? 9 : 26);
            if (tid == 128 && blk) TL(34);
            if (blk) CS(11);
            LnPar lp;
            if (blk == 0) {
            uint4* const mod_out = pt.mail->mod1 + g8 * 512 + (m * 8 + j) * 4 + q4;
            if (wg == 0) {
                uint4 af[8];
#pragma unroll
                for (int i = 0; i < 8; ++i) af[i] = lds128(sb + w4 * 512 + i * 64 + q4 * 16);
                float c[4][4] = {};
#pragma unroll
                for (int i = 0; i < 8; ++i) {
                    if (!(i & 1)) mbar_wait(BAR_ONE(sb, EV_WIN + (i >> 1)), 0);
                    if (i == 6 && tid == 0) TL(25);
#pragma unroll
                    for (int h = 0; h < 2; ++h) {
                        uint32_t b0, b1, b2, b3;
                        ldsm4t(sb + 5 * SLOT + i * 4096 + w4 * 1024 + h * 512 + (lane & 15) * 32 + (lane >> 4) * 16, b0, b1, b2, b3);
                        mma16816(c[2 * h], h ? af[i].z : af[i].x, 0u, h ? af[i].w : af[i].y, 0u, b0, b1);
                        mma16816(c[2 * h + 1], h ? af[i].z : af[i].x, 0u, h ? af[i].w : af[i].y, 0u, b2, b3);
                    }
                }
                if (lane < 4) sts128(sb + OFF_TAB + w4 * 64 + lane * 16, __float_as_uint(c[0][0] + c[2][0]), __float_as_uint(c[0][1] + c[2][1]),
                                     __float_as_uint(c[1][0] + c[3][0]), __float_as_uint(c[1][1] + c[3][1]));
                if (lane < 2) mbar_arrive_cta(BAR_ONE(sb, EV_P0), lane);
                bar_sync(1, 128);
                if (w4 == 0) {
                    float a[4] = {0.f, 0.f, 0.f, 0.f};
#pragma unroll
                    for (int i = 0; i < 4; ++i) {
                        const uint4 t = lds128(sb + OFF_TAB + i * 64 + q4 * 16);
                        a[0] += __uint_as_float(t.x); a[1] += __uint_as_float(t.y); a[2] += __uint_as_float(t.z); a[3] += __uint_as_float(t.w);
                    }
                    const float add = m >= 8 ? 1.f : 0.f;
                    st_pkt16(mod_out, pack2(bf_round(a[0]) + add, bf_round(a[1]) + add), pack2(bf_round(a[2]) + add, bf_round(a[3]) + add), ep, 0);
                    if (tid == 0) TL(3);
                }
            } else if (LWAIT >= 0) mbar_wait(BAR_ONE(sb, EV_WIN + LWAIT), 0);
            } else {
                mbar_wait2(BAR_ONE(sb, EV_LN2), BAR_FULL(sb, 0), 0);
            }
            lp.load(sb, q4);
#pragma unroll
            for (int e = 0; e < 32; ++e) xp[e] = pack2(xs[2 * e], xs[2 * e + 1]);
            if (PDLY && blk) { uint32_t t1; do { asm volatile("mov.u32 %0, %%clock;" : "=r"(t1)); } while (t1 - t_pub < PDLY); }
            if (blk) CS(13);
            const LnRow n = merge_stats(st, q4, ep, sb);
            if (tid == 0) TL(blk ? 49 : 48);
            if (tid == 128) TL(blk ? 45 : 28);
            if (blk) CS(18);
            uint32_t xn[32];
            ln_norm(xn, xs, n);
            if (blk == 0) {
                mbar_wait2(BAR_FULL(sb, 0), BAR_ONE(sb, EV_PAR), 0);
                if (FD0 && wg == 0) { uint32_t t0, t1; asm volatile("mov.u32 %0, %%clock;" : "=r"(t0)); do { asm volatile("mov.u32 %0, %%clock;" : "=r"(t1)); } while (t1 - t0 < FD0); }
                lp.load(sb, q4);
            }
            ln_emit(xn, lp, sb, wg, ix);
            if (tid == 0) { TL(blk ? 36 : 8); TC(blk ? 109 : 103); }
            if (tid == 128) TL(blk ? 43 : 22);
            if (blk) CS(21);
        }
        uint32_t hp[32];
        if (blk == 0) {
        {
            float big[128], sml[64];
            step32<true, true>(big, sml, sb, wg, r.slot, 0);
            TS(0, 0);
            Pipe pp(sb, tw, r.slot);
            r.next();
#pragma unroll 1
            for (int it = 1; it < 32 - LAGQ; ++it) {
                pp.acquire<true>(sb, wg ? 0 : AF_REL, r);
                step32<true, false>(big, sml, sb, wg, r.slot, it < 4 ? it : -1);
                pp.issued(r.slot);
                TS(it, 0);
                r.next();
            }
            auto half = [&](uint32_t slot, bool rest) {
                const uint32_t st = d16(sb) + slot * (SLOT >> 4);
#pragma unroll
                for (int k = 0; k < 2; ++k) {
                    const uint64_t da = mk_desc(st + wg * 256, k * 32, 16, 512, 2);
                    if (rest) wgmma_n256(big, da, mk_desc(st, 8192 + k * 2048, 4096, 1024, 1)); else wgmma_n128(sml, da, mk_desc(st, 24576 + k * 2048, 4096, 1024, 1));
                }
            };
            auto rest = [&](bool each) {
                wg_fence();
#pragma unroll
                for (int it = 32 - LAGQ; it < 32; ++it) { if (each && it > 32 - LAGQ) wg_fence(); half(it % NSLOT, true); if (each || it == 31) wg_commit(); }
            };
            stg.acquire2(sb, wg); mbar_wait2(BAR_SREADY(sb, 2), BAR_SREADY(sb, 3), 1);
#pragma unroll 1
            for (int it = 32 - LAGQ; it < 32; ++it) {
                pp.acquire<true>(sb, wg ? 0 : AF_REL, r);
                wg_fence(); half(r.slot, false); wg_commit();
                pp.issued(NSLOT);
                TS(it, 0);
                r.next();
            }
            if (wg) { rest(false); wg_wait<1>(); } else wg_wait<0>();
            CS(8);
            IDX();
            uint32_t k0[8], k1[8], k2[8], v0[8], v1[8], v2[8];
            const uint32_t nxt = warp + ((warp & 1) ? 3 : 1), mine = sb + OFF_STG + wg * 16384 + w4 * 2048;
            auto tails = [&](const float* kv, uint32_t (&kt)[8], uint32_t (&vt)[8]) {
#pragma unroll
                for (int t = 0; t < 8; ++t) { kt[t] = pack2(kv[4 * t + 2], kv[4 * t + 3]); vt[t] = pack2(kv[32 + 4 * t + 2], kv[32 + 4 * t + 3]); }
            };
            auto post = [&](int pn, uint32_t (&kt)[8], uint32_t (&vt)[8]) {
                uint4* dst = g_halo + (m * 8 + j) * 512 + (w4 >> 1) * 256 + pn * 128 + lane;
#pragma unroll
                for (int h = 0; h < 2; ++h) { if (!kt[4 * h]) kt[4 * h] = 0x8000u; if (!vt[4 * h]) vt[4 * h] = 0x8000u; }
#pragma unroll
                for (int h = 0; h < 2; ++h) { st_pkt16(dst + h * 32, kt[4 * h], kt[4 * h + 1], kt[4 * h + 2], kt[4 * h + 3]); st_pkt16(dst + 64 + h * 32, vt[4 * h], vt[4 * h + 1], vt[4 * h + 2], vt[4 * h + 3]); }
            };
            auto prepare = [&](int pn, const float* kv) {
                tails(kv, k2, v2);
                if (nxt < 8) {
                    const uint32_t dst = sb + OFF_STG + (nxt >> 2) * 16384 + (nxt & 3) * 2048 + pn * 8192 + lane * 16;
#pragma unroll
                    for (int h = 0; h < 2; ++h) { stsm4(dst + h * 512, k2[4 * h], k2[4 * h + 1], k2[4 * h + 2], k2[4 * h + 3]); stsm4(dst + 1024 + h * 512, v2[4 * h], v2[4 * h + 1], v2[4 * h + 2], v2[4 * h + 3]); }
                    if (pn == 0) bar_arrive(NB_TAIL + nxt, 64);
                    else { __syncwarp(); if (lane == 0) mbar_arrive(BAR_ONE(sb, EV_TAIL + nxt)); }
                } else if (pn == 0 && m < 15) post(0, k2, v2);
#pragma unroll
                for (int t = 0; t < 8; ++t) { k1[t] = pack2(kv[4 * t], kv[4 * t + 1]); v1[t] = movm(pack2(kv[32 + 4 * t], kv[32 + 4 * t + 1])); v2[t] = movm(v2[t]); }
                if (pn == 0) { CS(2); if (wg == 0) { rest(true); wg_wait<3>(); pp.rel(28 % NSLOT); wg_wait<2>(); pp.rel(29 % NSLOT); wg_wait<1>(); pp.rel(30 % NSLOT); } bar_sync(NB_TAIL + warp, 64); CS(4); }
                else mbar_wait(BAR_ONE(sb, EV_TAIL + __shfl_sync(0xffffffffu, warp, 0)), 0);
#pragma unroll
                for (int h = 0; h < 2; ++h) {
                    ldsm4(mine + pn * 8192 + lane * 16 + h * 512, k0[4 * h], k0[4 * h + 1], k0[4 * h + 2], k0[4 * h + 3]);
                    ldsm4t(mine + pn * 8192 + lane * 16 + 1024 + h * 512, v0[4 * h], v0[4 * h + 1], v0[4 * h + 2], v0[4 * h + 3]);
                }
            };
#pragma unroll
            for (int i = 0; i < 64; ++i) asm volatile("" : "+f"(sml[i]) :: "memory");
            prepare(0, sml);
            static_assert(LAGQ == 4, "");
            wg_wait<0>();
            if (wg) { pp.rel(28 % NSLOT); pp.rel(29 % NSLOT); pp.rel(30 % NSLOT); }
            pp.rel(31 % NSLOT);
            TS(31, 1);
            if (tid == 0) { TL(4); TC(104); }
            if (tid == 128) TL(50);
            CS(1);
#pragma unroll
            for (int i = 0; i < 128; ++i) asm volatile("" : "+f"(big[i]) :: "memory");
            if (nxt >= 8 && m < 15) { uint32_t kt[8], vt[8]; tails(big, kt, vt); post(1, kt, vt); }
            const bool lo0 = q4 * 2 > g8, lo1 = q4 * 2 + 1 > g8;
            const bool nopast = m == 0 && (warp & 5) == 0;
            const uint32_t lomask = (lo0 ? 0xFFFFu : 0u) | (lo1 ? 0xFFFF0000u : 0u);
            const uint32_t orow = mine + (lane & 7) * 128 + (((lane >> 3) ^ (lane & 7)) << 4);
            const float sl2 = 0.17677669529663687f * 1.4426950408889634f;
#pragma unroll
            for (int pn = 0; pn < 2; ++pn) {
                float e0[4], e1[4], mx[4], sum[4];
#pragma unroll
                for (int hh = 0; hh < 2; ++hh) {
                    uint32_t qf[8];
#pragma unroll
                    for (int i = 0; i < 8; ++i) qf[i] = pack2(big[64 + 32 * pn + 16 * hh + 2 * i], big[64 + 32 * pn + 16 * hh + 2 * i + 1]);
                    float s[3][4];
#pragma unroll
                    for (int t = 0; t < 3; ++t) {
                        const uint32_t* k = (t == 0 ? k0 : t == 1 ? k1 : k2) + 4 * hh;
                        s[t][0] = s[t][1] = s[t][2] = s[t][3] = 0.f;
                        mma16816(s[t], qf[0], qf[1], qf[2], qf[3], k[0], k[1]);
                        mma16816(s[t], qf[4], qf[5], qf[6], qf[7], k[2], k[3]);
                    }
#pragma unroll
                    for (int hf = 0; hf < 2; ++hf) {
                        const int u = hh * 2 + hf;
                        e0[u] = lo0 ? ((hf == 0 && nopast) ? -INFINITY : s[hf][hf * 2]) : s[hf + 1][hf * 2];
                        e1[u] = lo1 ? ((hf == 0 && nopast) ? -INFINITY : s[hf][hf * 2 + 1]) : s[hf + 1][hf * 2 + 1];
                        mx[u] = fmaxf(e0[u], e1[u]);
                    }
                }
#pragma unroll
                for (int o = 1; o < 4; o <<= 1)
#pragma unroll
                    for (int u = 0; u < 4; ++u) mx[u] = fmaxf(mx[u], __shfl_xor_sync(0xffffffffu, mx[u], o));
#pragma unroll
                for (int u = 0; u < 4; ++u) {
                    const float c = -mx[u] * sl2;
                    e0[u] = ex2(fmaf(e0[u], sl2, c)); e1[u] = ex2(fmaf(e1[u], sl2, c));
                    sum[u] = e0[u] + e1[u];
                }
#pragma unroll
                for (int o = 1; o < 4; o <<= 1)
#pragma unroll
                    for (int u = 0; u < 4; ++u) sum[u] += __shfl_xor_sync(0xffffffffu, sum[u], o);
#pragma unroll
                for (int u = 0; u < 4; ++u) {
                    const int h = u >> 1;
                    const float inv = rcp(sum[u]);
                    const uint32_t p = pack2(e0[u] * inv, e1[u] * inv);
                    const uint32_t* va = ((u & 1) ? v1 : v0) + 4 * h;
                    const uint32_t* vb = ((u & 1) ? v2 : v1) + 4 * h;
                    float o[2][4] = {};
#pragma unroll
                    for (int d = 0; d < 2; ++d) mma16816(o[d], va[2 * d], va[2 * d + 1], vb[2 * d], vb[2 * d + 1], p & lomask, p & ~lomask);
                    stsm4t((orow ^ ((u >> 1) << 6)) + pn * 8192 + (u & 1) * 1024, pack2(o[0][0], o[0][1]), pack2(o[0][2], o[0][3]), pack2(o[1][0], o[1][1]), pack2(o[1][2], o[1][3]));
                }
                fence_async_smem();
                __syncwarp();
                if (lane == 0) mbar_arrive(BAR_SFULL(sb, wg * 2 + pn));
                if (pn == 0) { CS(5); block_end(sb, 0); prepare(1, big); CS(3); }
            }
            CS(6);
            if (tid == 32) TL(41);
            mbar_wait2(BAR_FULL(sb, 32 % NSLOT), BAR_FULL(sb, 33 % NSLOT), (32 / NSLOT) & 1);
            load_slab(xp, sb + (32 % NSLOT + wg) * SLOT);
#pragma unroll
            for (int e = 0; e < 32; ++e) hp[e] = __float_as_uint(big[e]);
            bar_sync(1 + wg, 128);
            if (tid == 0) { TL(6); TC(106); }
            if (tid == 128) TL(44);
            CS(7);
        }
        } else {
        {
            float ag[88], au[88];
            mainloop32<true, LAG>(ag, au, sb, wg, tw, r, EV_LAG1, 48, [](int) {}, [&] {
                Ring q = r; if (!wg) q.next();
                mbar_wait(BAR_EMPTY(sb, q.slot), q.par ^ 1);
                mbar_wait(BAR_FULL(sb, r.slot), r.par);
            });
            if (tid == 0) { TL(10); TC(110); }
            if (tid == 128) TL(51);
            CS(22);
            {
                IDX();
                uint32_t h3[12];
                glu(h3, [&](int i) { return ag[64 + i]; }, [&](int i) { return au[64 + i]; });
#pragma unroll
                for (int k = 0; k < 3; ++k) stsm4(sb + (wg ? P3_SLOT1 : P3_SLOT0) * SLOT + 24576 + (pan_addr ^ (k << 5)), h3[4 * k], h3[4 * k + 1], h3[4 * k + 2], h3[4 * k + 3]);
            }
            glu(hp, [&](int i) { return ag[i]; }, [&](int i) { return au[i]; });
            if (tid == 0) { TL(11); TC(111); }
            if (tid == 128) TL(52);
            CS(23);
        }
        passes128<2, true>(hp, sb, wg, tw, r, stg);
        if (tid == 0) { TL(12); TC(112); }
        }
        {
            float acc[64], gf[32];
            mainloop64(acc, blk == 0, sb, wg, tw, r, [&] { put_h(hp, sb, wg, stg); }, [&] {
                mbar_wait(BAR_ONE(sb, EV_GA + blk), 0);
                unpack_slab(xs, xp);
                uint32_t gt[16];
#pragma unroll
                for (int cg = 0; cg < 16; ++cg) gt[cg] = lds32(sb + OFF_TAB + blk * 256 + cg * 16 + (tw & 3) * 4);
#pragma unroll
                for (int i = 0; i < 16; ++i) unpack2(gt[i], gf[2 * i], gf[2 * i + 1]);
            }, [&] { stg.acquire2(sb, wg); });
            if (tid == 0) { TL(blk ? 13 : 7); TC(blk ? 113 : 107); }
            if (tid == 128) TL(blk ? 57 : 42);
            CS(blk ? 30 : 10);
#pragma unroll
            for (int e = 0; e < 64; ++e) xs[e] = fmaf(gf[(e >> 2) * 2 + (e & 1)], acc[e], xs[e]);
        }
        if (blk) break;
        }
        {
            IDX();
#pragma unroll
            for (int p = 0; p < 2; ++p) {
                store_slab(xs, sb + OFF_STG + wg * 16384, 8192, pan_addr, 4 * p, 4 * p + 4);
                stg.publish(sb, wg, lane);
            }
            cluster_arrive();
            if (tid == 0) TL(14);
            CS(31);
        }
      }
    } else {
        if (warp == 8 && !aux && elect_one()) {
#pragma unroll
            for (int i = 0; i < 4; ++i) mbar_init(BAR_SREADY(sb, i), 1);
#pragma unroll
            for (int i = 0; i < 4; ++i) mbar_init(BAR_ONE(sb, EV_WIN + i), 1);
#pragma unroll
            for (int i = 0; i < 4; ++i) {
                mbar_expect_tx(BAR_SREADY(sb, i), 8192);
                tma_load3(sb + OFF_STG + i * 8192, &mp.x, j * 128 + (i & 1) * 64, m * 64 + (i >> 1) * 32, BAR_SREADY(sb, i));
            }
#pragma unroll 1
            for (int i = 0; i < 4; ++i) {
                mbar_expect_tx(BAR_ONE(sb, EV_WIN + i), 8192);
                tma_load(sb + 5 * SLOT + i * 8192, &mp.wm8, 2 * i * 6144 + (m * 8 + j) * 16, 0, BAR_ONE(sb, EV_WIN + i));
                tma_load(sb + 5 * SLOT + i * 8192 + 4096, &mp.wm8, (2 * i + 1) * 6144 + (m * 8 + j) * 16, 0, BAR_ONE(sb, EV_WIN + i));
            }
        }
        __syncwarp();
        asm volatile("setmaxnreg.dec.sync.aligned.u32 56;");
        if (elect_one()) {
            if (warp == 8) {
                prefetch_map(&mp.wqkv); prefetch_map(&mp.wmod);
            } else if (warp < 11) {
                mbar_init(BAR_EMPTY(sb, NSLOT), 1);
#pragma unroll
                for (int i = 0; i < 2; ++i) { mbar_init(BAR_SFULL(sb, (warp - 9) * 2 + i), 4); if (aux) mbar_init(BAR_SREADY(sb, (warp - 9) * 2 + i), 1); }
#pragma unroll
                for (int i = 0; i < 3; ++i) {
                    mbar_init(BAR_EMPTY(sb, (warp - 9) * 3 + i), 4);
                    mbar_init(BAR_FULL(sb, (warp - 9) * 3 + i), 1); mbar_init(BAR_FULL(sb, (warp - 9) * 3 + i) + AF_REL, 1);
                }
            } else {
#pragma unroll
                for (int i = EV_P0; i < EV_COUNT; ++i) mbar_init(BAR_ONE(sb, i), i == EV_P0 ? 8 : 1);
            }
            asm volatile("fence.mbarrier_init.release.cluster;" ::: "memory");
        }
        __syncwarp();
        cluster_arrive();
        ep = 0;
        if (warp != 8 || aux) ep = flag_get(g_flags + FL_DONE);
        cluster_wait();
        ep = __shfl_sync(0xffffffffu, ep, 0) / NCTA + 1;
        if (warp == 8) {
            const bool el = elect_one();
            Ring r{0, 1};
            if (aux) {
                {
                    uint32_t n = 0;
                    while (!__all_sync(0xffffffffu, ld_pkt16(pt.mail->mod1 + 256).z == ep)) { SPIN_GUARD(n); __nanosleep(200); }
                }
#pragma unroll 1
                for (int it = 0; it < 64; ++it) {
                    const int col = 2048 + (it >> 4) * 1024 + j * 256;
                    mbar_wait(BAR_EMPTY(sb, r.slot), r.par);
                    const uint32_t st = sb + r.slot * SLOT, fb = BAR_FULL(sb, r.slot);
                    if (el) {
                        mbar_expect_tx(fb, 32768);
#pragma unroll
                        for (int b = 0; b < 4; ++b) tma_load(st + b * 8192, &mp.wmod, col + b * 64, (it & 15) * 64, fb);
                    }
                    r.next();
                }
                mbar_wait(BAR_ONE(sb, EV_P0), 0);
                const CUtensorMap* wm = rank ? &mp.wu : &mp.wg;
#pragma unroll 1
                for (int g = 0; g < 128; ++g) {
                    const int mx = (j >> 1) * 8 + (g >> 5) * 2 + rank, k0 = ((g & 14) << 6) + ((g & 16) << 2) + ((g & 1) << 5);
                    if (!(g & 15) && g <= 32) mbar_wait(BAR_ONE(sb, EV_H0 + (g >> 4)), 0);
                    mbar_wait(BAR_EMPTY(sb, r.slot), r.par);
                    const uint32_t st = sb + r.slot * SLOT, fb = BAR_FULL(sb, r.slot);
                    if (el) {
                        mbar_expect_tx(fb, 24576);
                        tma_load_mc(st + 8192 + rank * 4096, wm, HC3, k0, fb);
                        tma_load_mc(st + 16384 + rank * 4096, wm, HC3 + 64, k0, fb);
                        tma_load(st, &mp.h2l, k0, mx * 128, fb);
                    }
                    r.next();
                }
            } else {
#pragma unroll 1
                for (int it = 0; it < 32; ++it) {
                    const int cb = j * 128 + rank * 64, k0 = kof(it, 2, j);
                    if (it == BW0) mbar_wait(BAR_ONE(sb, BWEV), 0);
                    if (it == BW1) mbar_wait(BAR_ONE(sb, EV_PAR), 0);
                    if (it == 5) mbar_wait(BAR_ONE(sb, EV_P0), 0);
                    if (it == AG0) mbar_wait(BAR_ONE(sb, (AGW & 1) ? EV_AGO : EV_FGO), 0);
                    mbar_wait(BAR_EMPTY(sb, r.slot), r.par);
                    const uint32_t st = sb + r.slot * SLOT, fb = BAR_FULL(sb, r.slot);
                    if (el) {
                        mbar_expect_tx(fb, it < 4 ? 24576 : 28672);
                        tma_load_mc(st + 24576 - rank * 16384, &mp.wqkv, 1024 + cb, k0, fb);
                        tma_load_mc(st + 28672 - rank * 16384, &mp.wqkv, 2048 + cb, k0, fb);
                        tma_load_mc(st + 16384 + rank * 4096, &mp.wqkv, cb, k0, fb);
                        if (it < 4) mbar_arrive(fb + AF_REL);
                        if (it == PFWO + (m >> 1)) { tma_prefetch(&mp.wo, j * 128, m * 64); tma_prefetch(&mp.wo, j * 128 + 64, m * 64); }
                        if (it >= PFG && it < PFG + PFN && (it & 7) == grp) {
                            const int kp = kof(it - PFG + PFO, 2, j);
                            tma_prefetch(rank ? &mp.wu : &mp.wg, hcol(0, j), kp); tma_prefetch(rank ? &mp.wu : &mp.wg, hcol(0, j) + 64, kp);
                            asm volatile("cp.async.bulk.prefetch.tensor.3d.L2.global [%0, {%1, %2, %3}];" :: "l"(rank ? &mp.wu3 : &mp.wg3), "r"(0), "r"(j), "r"(kp) : "memory");
                        }
                    }
                    r.next();
                }
                if (el) mbar_arrive(BAR_ONE(sb, EV_KV));
#pragma unroll 1
                for (int it = 0; it < 16; ++it) {
                    const int k0 = kof(it, 1, j);
                    if (it == AG1) mbar_wait(BAR_ONE(sb, (AGW & 2) ? EV_AGO1 : EV_FGO1), 0);
                    mbar_wait(BAR_EMPTY(sb, r.slot), r.par);
                    const uint32_t st = sb + r.slot * SLOT, fb = BAR_FULL(sb, r.slot);
                    if (el) {
                        mbar_expect_tx(fb, it < 2 ? 32768 : 24576);
                        tma_load_mc(st + 16384 + rank * 8192, &mp.wo, j * 128 + rank * 64, k0, fb);
                        if (it < 2) {
                            tma_load3(st, &mp.x, j * 128, m * 64 + it * 32, fb); tma_load3(st + 8192, &mp.x, j * 128 + 64, m * 64 + it * 32, fb);
                            mbar_arrive(fb + AF_REL);
                        }
                        if (it == 6) { prefetch_map(rank ? &mp.wu : &mp.wg); prefetch_map(rank ? &mp.wu3 : &mp.wg3); }
                    }
                    r.next();
                }
                const CUtensorMap* wm = rank ? &mp.wu : &mp.wg;
#pragma unroll 1
                for (int g = 0; g < 96; ++g) {
                    if (g == AG2) mbar_wait(BAR_ONE(sb, (AGW & 4) ? EV_AGO2 : EV_FGO2), 0);
                    const int p = g >> 5, cb = hcol(p, j), k0 = p == 0 ? kof(g, 2, j) : (g & 31) * 32;
                    mbar_wait(BAR_EMPTY(sb, r.slot), r.par);
                    const uint32_t st = sb + r.slot * SLOT, fb = BAR_FULL(sb, r.slot);
                    if (el) {
                        mbar_expect_tx(fb, (g < 4 || p > 0) ? 24576 : 28672);
                        tma_load_mc(st + 8192 + rank * 4096, wm, cb, k0, fb);
                        tma_load_mc(st + 16384 + rank * 4096, wm, cb + 64, k0, fb);
                        if (p == 0) tma_load3_mc(st + 24576 + rank * 4096, rank ? &mp.wu3 : &mp.wg3, j, k0, fb);
                        else tma_load(st, &mp.h2l, k0, m * 128, fb);
                        if (g < 4) mbar_arrive(fb + AF_REL);
                        if ((g & 7) == grp && g + PFC >= 96) tma_prefetch(&mp.wd, j * 128 + rank * 64, (g + PFC - 96) * 64);
                        if (g == 60) { prefetch_map(&mp.wd); prefetch_map(&mp.hb); }
                    }
                    r.next();
                }
#pragma unroll 1
                for (int g = 0; g < 56; ++g) {
                    if (g == 0 || (g & 15) == 6 && g > 6) mbar_wait(BAR_ONE(sb, EV_H0 + (g >> 4)), 0);
                    const int k0 = g * 64;
                    mbar_wait(BAR_EMPTY(sb, r.slot), r.par);
                    const uint32_t st = sb + r.slot * SLOT, fb = BAR_FULL(sb, r.slot);
                    if (el) {
                        mbar_expect_tx(fb, 32768);
                        tma_load_mc(st + 16384 + rank * 8192, &mp.wd, j * 128 + rank * 64, k0, fb);
                        tma_load(st, &mp.hb, k0, m * 128, fb); tma_load(st + 8192, &mp.hb, k0, m * 128 + 64, fb);
                        if ((g & 7) == grp && g + PFC < 56) tma_prefetch(&mp.wd, j * 128 + rank * 64, k0 + PFC * 64);
                    }
                    r.next();
                }
            }
        } else if (aux) {
            if (warp < 11) {
                const uint32_t w = warp - 9;
                const bool el = elect_one();
#pragma unroll 1
                for (int p = 0; p < 4; ++p) {
                    const int mx = (j >> 1) * 8 + p * 2 + rank;
                    if (el) { mbar_arrive(BAR_SREADY(sb, w * 2)); mbar_arrive(BAR_SREADY(sb, w * 2 + 1)); }
                    mbar_wait2(BAR_SFULL(sb, w * 2), BAR_SFULL(sb, w * 2 + 1), p & 1);
                    if (p < 3) pause(w ? HD1 : HD0);
                    if (el) tma_store(&mp.hb, HC3, mx * 128 + w * 64, sb + OFF_STG + w * 16384);
                    if (p < 3) pause(HP);
                    if (el) {
                        tma_store(&mp.hb, HC3 + 64, mx * 128 + w * 64, sb + OFF_STG + w * 16384 + 8192);
                        bulk_commit(); bulk_wait_fence(); flag_set(g_flags + FL_AUX + mx * 2 + w, ep * 8 + ST_H + 3);
                    }
                }
            } else {
                mbar_wait(BAR_ONE(sb, EV_P0), 0);
#pragma unroll 1
                for (int i = 0; i < 5; ++i) {
                    const uint32_t* f = g_flags + FL_PROG + fidx((j >> 1) * 8 + (i ? i - 1 : 0) * 2 + rank, lane >> 4, lane & (i ? 15 : 14));
                    uint32_t n = 0;
                    while (!__all_sync(0xffffffffu, (int32_t)(flag_get(f) - (ep * 8 + ST_H2)) >= 0)) { SPIN_GUARD(n); __nanosleep(200); }
                    if (i < 2) pause(AUXD);
                    if (lane == 0 && (i < 2 || i == 4)) mbar_arrive(BAR_ONE(sb, EV_H0 + (i < 2 ? i : 2)));
                }
            }
        } else if (warp == 11) {
            const bool el = elect_one();
            const int row0 = m * 128;
            const uint32_t* const fl = g_flags + FL_PROG + fidx(m, lane >> 4, kof(lane & 15, 1, j) >> 6);
            if (el) { prefetch_map(&mp.h1h); prefetch_map(&mp.h2h); prefetch_map(&mp.h2l); }
            auto gate = [&](int vec, int ev) {
                uint4 v; uint32_t n = 0;
                while (true) {
                    v = ld_pkt2(g_mod + vec * 512 + j * 64 + lane * 2);
                    if (__all_sync(0xffffffffu, v.y == ep && v.w == ep)) break;
                    SPIN_GUARD(n); __nanosleep(300);
                }
                asm volatile("st.shared.v2.u32 [%0], {%1, %2};" :: "r"(sb + OFF_TAB + (ev - EV_GA) * 256 + lane * 8), "r"(v.x), "r"(v.z) : "memory");
                __syncwarp();
                if (lane == 0) mbar_arrive(BAR_ONE(sb, ev));
            };
            {
                const uint4* pk = pt.mail->mod1 + grp * 512 + j * 32 + lane;
                uint4 a, b; uint32_t n = 0;
                mbar_wait(BAR_ONE(sb, EV_WIN3), 0);
                while (true) {
                    a = ld_pkt16(pk); b = ld_pkt16(pk + 256);
                    if (__all_sync(0xffffffffu, a.z == ep && b.z == ep)) break;
                    SPIN_GUARD(n);
                }
                sts128(sb + OFF_PAR + lane * 16, a.x, a.y, b.x, b.y);
                __syncwarp();
                if (lane == 0) { mbar_arrive(BAR_ONE(sb, EV_PAR)); TL(46); }
            }
            mbar_wait(BAR_ONE(sb, EV_P0), 0);
            Ring r{0, 1};
#pragma unroll 1
            for (int ph = 0; ph < 3; ++ph) {
                const int sh = ph == 1 ? 1 : 2, nst = 8 << sh;
                const uint32_t half = 16384 >> sh, target = ep * 8 + ST_H1 + ph;
                const CUtensorMap* tm = ph == 0 ? &mp.h1h : ph == 1 ? &mp.o : &mp.h2h;
                if (ph == 1) {
                    gate(2, EV_GA);
                    mbar_wait(BAR_SREADY(sb, 1), 1);
#pragma unroll 1
                    for (int i = 0; i < 2; ++i)
                        fetch_halo<1>(g_halo + ((m - 1) * 8 + j) * 512 + i * 256 + 128 + lane, m == 0, sb + OFF_STG + 8192 + i * 4096 + lane * 16,
                                      [&] { __syncwarp(); if (el) mbar_arrive(BAR_ONE(sb, EV_TAIL + 2 * i)); });
                    CS(32);
                }
                if (ph == 2) {
                    uint32_t n = 0;
                    while ((int32_t)(flag_get(g_flags + FL_LN2) - ep * 8) < 0) { SPIN_GUARD(n); __nanosleep(200); }
                    const uint4 v = __ldcg((const uint4*)(g_par2 + j * 128) + lane);
                    sts128(sb + OFF_PAR + lane * 16, v.x, v.y, v.z, v.w);
                    __syncwarp();
                    if (lane == 0) mbar_arrive(BAR_ONE(sb, EV_LN2));
                }
                const uint32_t lw = ~lane & 1, lt = lane >> 1, ls = (r.slot + lt) % NSLOT, lk = kof(lt, sh, j), lb = BAR_FULL(sb, ls) + (lw ? 0 : AF_REL);
                const uint32_t* const lf = g_flags + FL_PROG + fidx(m, lw, lk >> 6);
                int fr = 1 << sh;
                uint32_t todo = 0x3ffffu >> (2 * fr) << (2 * fr), have = ~todo, n = 0, v = 0;
                r.skip(fr);
#pragma unroll 1
                for (; fr < NSLOT; ++fr) { mbar_wait(BAR_EMPTY(sb, r.slot), r.par); r.next(); }
                if (ph == XST - 1) CS(33);
                v = flag_get(lf);
                do {
                    while (ph == 2 && fr < FRCAP && mbar_test(BAR_EMPTY(sb, r.slot), r.par)) { ++fr; r.next(); }
                    SPIN_GUARD(n);
                    const bool ok = (int32_t)(v - target) >= 0;
                    v = flag_get(lf);
                    have |= __ballot_sync(0xffffffffu, ok);
                    const uint32_t go = have & todo & ((1u << (2 * fr)) - 1);
                    if ((go >> lane) & 1) {
                        if (!lw) mbar_expect_tx(lb, half);
                        tma_load(sb + ls * SLOT + lw * half, tm, lk, row0 + lw * 64, lb);
                    }
                    __syncwarp();
                    if (lane < 2 && (todo & (0x555u << lane)) && !(todo & ~go & (0x555u << lane))) mbar_arrive(BAR_ONE(sb, (lane ? EV_FGO : EV_AGO) + ph));
                    if (ph == XST - 1) { if (go & (1u << (2 << sh))) CS(34); if (go & (2u << (2 << sh))) CS(35); if (todo & 0x555u) CS(36); if (todo & 0xaaau) CS(37); }
                    todo &= ~go;
                } while (~have);
                if (ph == XST - 1) CS(38);
                int k = kof(fr, sh, j);
#pragma unroll 1
                for (; fr < nst; ++fr) {
                    if (fr == 9 || fr == 18) {
                        const uint32_t skip = fr == 9 << (sh - 1) ? 0 : ~0x01fc01fcu;
                        while (~(__ballot_sync(0xffffffffu, (int32_t)(flag_get(fl) - target) >= 0) | skip)) SPIN_GUARD(n);
                    }
                    const uint32_t st = sb + r.slot * SLOT, fb = BAR_FULL(sb, r.slot);
                    mbar_wait(BAR_EMPTY(sb, r.slot), r.par);
                    if (el) {
                        tma_load(st + half, tm, k, row0 + 64, fb);
                        mbar_expect_tx(fb + AF_REL, half);
                        tma_load(st, tm, k, row0, fb + AF_REL);
                    }
                    if (ph == XST - 1 && fr == 9) CS(39);
                    r.next();
                    k = kof(fr + 1, sh, j);
                }
            }
#pragma unroll 1
            for (int p = 0; p < 4; ++p) {
                const uint32_t* f = p < 3 ? fl : g_flags + FL_AUX + m * 2 + (lane & 1);
                uint32_t n = 0;
                while (!__all_sync(0xffffffffu, (int32_t)(flag_get(f) - (ep * 8 + ST_H + p)) >= 0)) { SPIN_GUARD(n); __nanosleep(300); }
                if (el) mbar_arrive(BAR_ONE(sb, EV_H0 + p));
                if (p == 0) gate(5, EV_GB);
            }
        } else {
            const uint32_t w = warp - 9;
            const int row0 = m * 128 + w * 64;
            const uint32_t stg = sb + OFF_STG + w * 16384;
            uint32_t* const fl = g_flags + FL_PROG + fidx(m, w, 2 * j);
            uint32_t b = 0, par = 0;
            const bool el = elect_one();
            auto store = [&](const CUtensorMap* tm, int col, bool nat = false) {
                mbar_wait(BAR_SFULL(sb, w * 2 + b), (par >> b) & 1);
                par ^= 1u << b;
                if (el) {
                    if (nat) tma_store3(tm, col, row0 >> 1, 0, stg + b * 8192); else tma_store(tm, col, row0, stg + b * 8192);
                    bulk_commit();
                }
                b ^= 1;
            };
            auto send2 = [&](const CUtensorMap* tm, const uint32_t* buf, int step) {
                const uint32_t* const q = buf + (size_t)((row0 + lane) * (D_ / 2) + j * 64 + 31);
                store(tm, j * 128);
                if (step == XST) CS(33);
                uint32_t z = landed(el, q, D_ / 2, pt.zero);
                if (el) flag_set(fl, ep * 8 + step + z);
                if (step == XST) CS(34);
                if (step != ST_O) { mbar_wait(BAR_ONE(sb, EV_FGO + step - ST_H1), 0); pause(step == ST_H1 ? (w ? P1H : P1H + 1000) : w ? P2L : P2F); }
                store(tm, j * 128 + 64);
                if (step == XST) CS(35);
                z = landed(el, q + 32, D_ / 2, pt.zero);
                if (el) flag_set(fl + 1, ep * 8 + step + z);
                if (step == XST) CS(36);
            };
            auto free2 = [&]() { if (el) { mbar_arrive(BAR_SREADY(sb, w * 2)); mbar_arrive(BAR_SREADY(sb, w * 2 + 1)); } };
            if (el) { prefetch_map(&mp.h1s); prefetch_map(&mp.o); prefetch_map(&mp.out); prefetch_map(&mp.wo); }
            send2(&mp.h1s, pt.h1, ST_H1);
            if (w == 0) TL(47);
            free2();
            mbar_wait(BAR_ONE(sb, EV_KV), 0);
            mbar_wait(BAR_SREADY(sb, 0), 1);
            fetch_halo<1>(g_halo + ((m - 1) * 8 + j) * 512 + w * 256 + lane, m == 0, sb + OFF_STG + w * 4096 + lane * 16, [&] { bar_arrive(NB_TAIL + 2 * w, 64); CS(38); });
            send2(&mp.o, pt.o, ST_O);
            if (w == 0) TL(40); else TL(38);
            free2();
            send2(&mp.o, pt.o, ST_H2);
            if (el) { prefetch_map(&mp.hbs); prefetch_map(&mp.hb3); }
            if (w == 0) TL(37);
            free2();
#pragma unroll 1
            for (int p = 0; p < 3; ++p) {
                const int col = hcol(p, j);
                mbar_wait2(BAR_SFULL(sb, w * 2), BAR_SFULL(sb, w * 2 + 1), par & 1);
                par ^= 3;
#pragma unroll 1
                for (int i = 0; i < (p ? 2 : 3) * NSPL; ++i) {
                    pause(i ? HP / NSPL : p == 2 ? (w ? HE1 : HE0) : w ? HD1 : HD0);
                    const int pn = i / NSPL, ro = (i % NSPL) * (64 / NSPL);
                    if (el) {
                        if (pn < 2) tma_store(&mp.hbs, col + pn * 64, row0 + ro, stg + i * (8192 / NSPL));
                        else tma_store3(&mp.hb3, 0, j, row0 + ro, sb + (w ? P3_SLOT1 : P3_SLOT0) * SLOT + 24576 + ro * 128);
                        bulk_commit();
                    }
                }
                if (el) bulk_wait_read();
                free2();
                if (el) { bulk_wait_fence(); flag_set(fl, ep * 8 + ST_H + p); flag_set(fl + 1, ep * 8 + ST_H + p); }
            }
            cluster_arrive_early = true;
            cluster_arrive();
            store(&mp.out, j * 128, true); store(&mp.out, j * 128 + 64, true);
            if (el) bulk_wait_read();
        }
        __syncwarp();
    }
    if (aux || (wg == 2 && !cluster_arrive_early)) cluster_arrive();
    cluster_wait();
    if (KDEBUG == 5) __syncthreads();
    if (tid == 0) {
        TL(15);
        flag_add(pt.mail->flags + FL_DONE);
    }
}

typedef CUresult (*EncodeFn)(CUtensorMap*, CUtensorMapDataType, cuuint32_t, void*, const cuuint64_t*, const cuuint64_t*, const cuuint32_t*,
                             const cuuint32_t*, CUtensorMapInterleave, CUtensorMapSwizzle, CUtensorMapL2promotion, CUtensorMapFloatOOBfill);

void make_map(EncodeFn fn, CUtensorMap* m, const void* ptr, uint64_t rows, uint64_t cols, uint32_t brows, uint32_t bcols) {
    cuuint64_t dims[2] = {cols, rows}, strides[1] = {cols * 2};
    cuuint32_t box[2] = {bcols, brows}, es[2] = {1, 1};
    fn(m, CU_TENSOR_MAP_DATA_TYPE_BFLOAT16, 2, (void*)ptr, dims, strides, box, es, CU_TENSOR_MAP_INTERLEAVE_NONE,
       bcols == 64 ? CU_TENSOR_MAP_SWIZZLE_128B : bcols == 32 ? CU_TENSOR_MAP_SWIZZLE_64B : CU_TENSOR_MAP_SWIZZLE_NONE, CU_TENSOR_MAP_L2_PROMOTION_L2_256B, CU_TENSOR_MAP_FLOAT_OOB_FILL_NONE);
}

void make_map3(EncodeFn fn, CUtensorMap* m, const void* ptr) {
    cuuint64_t dims[3] = {D_, S_ / 2, 2}, strides[2] = {4 * D_, 2 * D_};
    cuuint32_t box[3] = {64, 32, 2}, es[3] = {1, 1, 1};
    fn(m, CU_TENSOR_MAP_DATA_TYPE_BFLOAT16, 3, (void*)ptr, dims, strides, box, es, CU_TENSOR_MAP_INTERLEAVE_NONE,
       CU_TENSOR_MAP_SWIZZLE_128B, CU_TENSOR_MAP_L2_PROMOTION_L2_256B, CU_TENSOR_MAP_FLOAT_OOB_FILL_NONE);
}

void make_map48(EncodeFn fn, CUtensorMap* m, const void* ptr, uint64_t rows, uint32_t brows) {
    cuuint64_t dims[3] = {48, 8, rows}, strides[2] = {96, 2 * F_};
    cuuint32_t box[3] = {64, 1, brows}, es[3] = {1, 1, 1};
    fn(m, CU_TENSOR_MAP_DATA_TYPE_BFLOAT16, 3, (void*)ptr, dims, strides, box, es, CU_TENSOR_MAP_INTERLEAVE_NONE,
       CU_TENSOR_MAP_SWIZZLE_128B, CU_TENSOR_MAP_L2_PROMOTION_L2_256B, CU_TENSOR_MAP_FLOAT_OOB_FILL_NONE);
}

}

extern "C" void kernel_launch(void* const* d_in, const int* in_sizes, int n_in, void* d_out, int out_size) {
    (void)in_sizes; (void)n_in; (void)out_size;
    void* fnp = nullptr;
    cudaDriverEntryPointQueryResult qr;
    cudaGetDriverEntryPoint("cuTensorMapEncodeTiled", &fnp, cudaEnableDefault, &qr);
    EncodeFn fn = (EncodeFn)fnp;
    void *h1, *o, *h2, *hb, *mail;
    cudaGetSymbolAddress(&h1, g_h1);
    cudaGetSymbolAddress(&mail, g_mail);
    cudaGetSymbolAddress(&o, g_o);
    cudaGetSymbolAddress(&hb, g_hb);
    h2 = o;
    Maps mp;
    make_map(fn, &mp.h1h, h1, S_, D_, 64, 32);
    make_map(fn, &mp.h2h, h2, S_, D_, 64, 32);
    make_map(fn, &mp.h1s, h1, S_, D_, 64, 64);
    make_map(fn, &mp.o, o, S_, D_, 64, 64);
    make_map(fn, &mp.h2l, h2, S_, D_, 128, 32);
    make_map(fn, &mp.hb, hb, S_, F_, 64, 64);
    make_map(fn, &mp.wqkv, d_in[1], D_, 3 * D_, 32, 64);
    make_map(fn, &mp.wo, d_in[2], D_, D_, 64, 64);
    make_map(fn, &mp.wg, d_in[4], D_, F_, 32, 64);
    make_map(fn, &mp.wu, d_in[5], D_, F_, 32, 64);
    make_map(fn, &mp.wd, d_in[6], F_, D_, 64, 64);
    make_map(fn, &mp.wmod, d_in[8], D_, 6 * D_, 64, 64);
    make_map(fn, &mp.wm8, d_in[8], D_ / 8, 8 * 6 * D_, 128, 16);
    make_map3(fn, &mp.x, d_in[0]);
    make_map3(fn, &mp.out, d_out);
    make_map48(fn, &mp.wg3, d_in[4], D_, 32);
    make_map48(fn, &mp.wu3, d_in[5], D_, 32);
    make_map48(fn, &mp.hb3, hb, S_, 64 / NSPL);
    make_map(fn, &mp.hbs, hb, S_, F_, 64 / NSPL, 64);
    cudaFuncSetAttribute(fused_block_kernel, cudaFuncAttributeMaxDynamicSharedMemorySize, SMEM_BYTES);
    cudaLaunchConfig_t cfg = {};
    cfg.gridDim = dim3(NCTA); cfg.blockDim = dim3(384); cfg.dynamicSmemBytes = SMEM_BYTES; cfg.stream = cudaStreamPerThread;
    cudaLaunchAttribute at[1];
    at[0].id = cudaLaunchAttributeClusterDimension; at[0].val.clusterDim.x = 2; at[0].val.clusterDim.y = 1; at[0].val.clusterDim.z = 1;
    cfg.attrs = at; cfg.numAttrs = 1;
    const Ptrs pt{(const __nv_bfloat16*)d_in[7], (Mail*)mail, (const uint32_t*)h1, (const uint32_t*)o, 0};
    cudaLaunchKernelEx(&cfg, fused_block_kernel, pt, mp);
}
```

```cpp
#include <cuda_runtime.h>
#include <cuda_bf16.h>
#include <cuda.h>
#include <stdint.h>
#include <stddef.h>

#define LAG 4
#define LAGS 4
#define LAGW 2
#define LAGD 4
#define LAGQ 4
#define PUT1 5
#define PUT0 10
#define PUTD1 6
#define PUTD0 10
#define MIDD 40
#define HD1 3000
#define HD0 1500
#define NSPL 2
#define HE1 2000
#define HE0 HD0
#define HP 2600
#define P1H 3000
#define P2L 2000
#define P2F 3000
#define AUXD 4000
#define PDLY 500
#define FD0 200
#define AG0 6
#define AG1 6
#define AG2 8
#define AGW 2
#define FRCAP 8
#define BW0 0
#define BWEV EV_WIN
#define BW1 3
#define LWAIT 3
#define PFWO 12
#define PFG 8
#define PFN 24
#define PFC 10
#define PFO 0
#define KDEBUG 0
#define CSW 0
#define XST ST_O

namespace {

constexpr int S_ = 2048, D_ = 1024, F_ = 3584;
constexpr int NCTA = 132;
constexpr int NSLOT = 6;
constexpr uint32_t SLOT = 32768;
constexpr uint32_t OFF_STG = NSLOT * SLOT;
constexpr uint32_t OFF_BAR = OFF_STG + 32768;
constexpr uint32_t OFF_PAR = OFF_BAR + 512;
constexpr uint32_t OFF_TAB = OFF_PAR + 768;
constexpr uint32_t OFF_TL = OFF_PAR + 2048;
constexpr uint32_t SMEM_BYTES = OFF_TL + (KDEBUG ? 512 : 0);
constexpr uint32_t P3_SLOT1 = (32 + 16 + 32) % NSLOT, P3_SLOT0 = (P3_SLOT1 + 1) % NSLOT;

constexpr int ST_H1 = 1, ST_O = 2, ST_H2 = 3, ST_H = 4, FL_DONE = 0, FL_LN2 = 1, FL_AUX = 32, FL_PROG = 64;

struct Maps {
    CUtensorMap h1h, h1s, o, h2h, h2l, hb, wqkv, wo, wg, wu, wd, wmod, wm8, x, out, wg3, wu3, hb3, hbs;
};

struct Mail {
    uint32_t flags[16 * 32 + 64];
    uint2 mod[6 * D_ / 2];
    uint4 mod1[8 * 512];
    uint4 st1[128 * 512];
    uint32_t par2[D_];
    uint4 halo[128 * 512];
};
struct Ptrs { const __nv_bfloat16* c; Mail* mail; const uint32_t *h1, *o; uint32_t zero; };

__device__ __align__(128) Mail g_mail;
__device__ __align__(128) __nv_bfloat16 g_h1[S_ * D_];
__device__ __align__(128) __nv_bfloat16 g_o[S_ * D_];
__device__ __align__(128) __nv_bfloat16 g_hb[S_ * F_];
#define TL(i) do {} while (0)
#define TC(i) do {} while (0)
#define TS(g, which) do {} while (0)
#define CS(i) do {} while (0)

__device__ __forceinline__ uint32_t smem_u32(const void* p) { return (uint32_t)__cvta_generic_to_shared(p); }
__device__ __forceinline__ void mbar_init(uint32_t bar, uint32_t cnt) { asm volatile("mbarrier.init.shared::cta.b64 [%0], %1;" :: "r"(bar), "r"(cnt) : "memory"); }
__device__ __forceinline__ void mbar_expect_tx(uint32_t bar, uint32_t bytes) { asm volatile("mbarrier.arrive.expect_tx.shared::cta.b64 _, [%0], %1;" :: "r"(bar), "r"(bytes) : "memory"); }
__device__ __forceinline__ void mbar_arrive(uint32_t bar) { asm volatile("mbarrier.arrive.shared::cta.b64 _, [%0];" :: "r"(bar) : "memory"); }
__device__ __forceinline__ void mbar_arrive_cta(uint32_t bar, uint32_t cta) {
    asm volatile("{\n.reg .b32 r;\nmapa.shared::cluster.u32 r, %0, %1;\nmbarrier.arrive.shared::cluster.b64 _, [r];\n}" :: "r"(bar), "r"(cta) : "memory");
}
__device__ __forceinline__ void mbar_wait(uint32_t bar, uint32_t parity) {
    asm volatile("{\n.reg .pred p;\n.reg .u32 n;\nmov.u32 n, 0;\n"
        "W_LOOP:\nmbarrier.try_wait.parity.shared::cta.b64 p, [%0], %1;\n@p bra W_DONE;\n"
        "add.u32 n, n, 1;\nsetp.lt.u32 p, n, 0x400000;\n@p bra W_LOOP;\ntrap;\nW_DONE:\n}" :: "r"(bar), "r"(parity) : "memory");
}
__device__ __forceinline__ void mbar_wait2(uint32_t b0, uint32_t b1, uint32_t parity) {
    asm volatile("{\n.reg .pred p, q;\n.reg .u32 n;\nmov.u32 n, 0;\n"
        "W_LOOP:\nmbarrier.try_wait.parity.shared::cta.b64 p, [%0], %2;\nmbarrier.try_wait.parity.shared::cta.b64 q, [%1], %2;\nand.pred p, p, q;\n@p bra W_DONE;\n"
        "add.u32 n, n, 1;\nsetp.lt.u32 p, n, 0x400000;\n@p bra W_LOOP;\ntrap;\nW_DONE:\n}" :: "r"(b0), "r"(b1), "r"(parity) : "memory");
}
__device__ __forceinline__ bool mbar_test(uint32_t bar, uint32_t parity) {
    uint32_t r; asm volatile("{\n.reg .pred p;\nmbarrier.test_wait.parity.shared::cta.b64 p, [%1], %2;\nselp.u32 %0, 1, 0, p;\n}" : "=r"(r) : "r"(bar), "r"(parity) : "memory"); return r;
}
__device__ __forceinline__ bool mbar_test2(uint32_t b0, uint32_t b1, uint32_t parity) {
    uint32_t r;
    asm volatile("{\n.reg .pred p, q;\nmbarrier.test_wait.parity.shared::cta.b64 p, [%1], %3;\nmbarrier.test_wait.parity.shared::cta.b64 q, [%2], %3;\n"
        "and.pred p, p, q;\nselp.u32 %0, 1, 0, p;\n}" : "=r"(r) : "r"(b0), "r"(b1), "r"(parity) : "memory");
    return r;
}
__device__ __forceinline__ void tma_load3(uint32_t dst, const CUtensorMap* m, int c0, int c1, uint32_t bar) {
    asm volatile("cp.async.bulk.tensor.3d.shared::cluster.global.mbarrier::complete_tx::bytes [%0], [%1, {%3, %4, %5}], [%2];"
        :: "r"(dst), "l"(m), "r"(bar), "r"(c0), "r"(c1), "r"(0) : "memory");
}
__device__ __forceinline__ void tma_store3(const CUtensorMap* m, int c0, int c1, int c2, uint32_t src) {
    asm volatile("cp.async.bulk.tensor.3d.global.shared::cta.bulk_group [%0, {%2, %3, %4}], [%1];" :: "l"(m), "r"(src), "r"(c0), "r"(c1), "r"(c2) : "memory");
}
__device__ __forceinline__ void tma_load3_mc(uint32_t dst, const CUtensorMap* m, int c1, int c2, uint32_t bar) {
    asm volatile("cp.async.bulk.tensor.3d.shared::cluster.global.mbarrier::complete_tx::bytes.multicast::cluster.L2::cache_hint [%0], [%1, {%3, %4, %5}], [%2], %6, %7;"
        :: "r"(dst), "l"(m), "r"(bar), "r"(0), "r"(c1), "r"(c2), "h"((uint16_t)3), "l"(0x12F0000000000000ull) : "memory");
}
__device__ __forceinline__ void tma_load(uint32_t dst, const CUtensorMap* m, int c0, int c1, uint32_t bar) {
    asm volatile("cp.async.bulk.tensor.2d.shared::cluster.global.mbarrier::complete_tx::bytes [%0], [%1, {%3, %4}], [%2];"
        :: "r"(dst), "l"(m), "r"(bar), "r"(c0), "r"(c1) : "memory");
}
__device__ __forceinline__ void tma_load_ef(uint32_t dst, const CUtensorMap* m, int c0, int c1, uint32_t bar) {
    asm volatile("cp.async.bulk.tensor.2d.shared::cluster.global.mbarrier::complete_tx::bytes.L2::cache_hint [%0], [%1, {%3, %4}], [%2], %5;"
        :: "r"(dst), "l"(m), "r"(bar), "r"(c0), "r"(c1), "l"(0x12F0000000000000ull) : "memory");
}
__device__ __forceinline__ void tma_load_mc(uint32_t dst, const CUtensorMap* m, int c0, int c1, uint32_t bar) {
    asm volatile("cp.async.bulk.tensor.2d.shared::cluster.global.mbarrier::complete_tx::bytes.multicast::cluster.L2::cache_hint [%0], [%1, {%3, %4}], [%2], %5, %6;"
        :: "r"(dst), "l"(m), "r"(bar), "r"(c0), "r"(c1), "h"((uint16_t)3), "l"(0x12F0000000000000ull) : "memory");
}
__device__ __forceinline__ void tma_prefetch(const CUtensorMap* m, int c0, int c1) {
    asm volatile("cp.async.bulk.prefetch.tensor.2d.L2.global [%0, {%1, %2}];" :: "l"(m), "r"(c0), "r"(c1) : "memory");
}
__device__ __forceinline__ void tma_store(const CUtensorMap* m, int c0, int c1, uint32_t src) {
    asm volatile("cp.async.bulk.tensor.2d.global.shared::cta.bulk_group [%0, {%2, %3}], [%1];" :: "l"(m), "r"(src), "r"(c0), "r"(c1) : "memory");
}
__device__ __forceinline__ void bulk_commit() { asm volatile("cp.async.bulk.commit_group;" ::: "memory"); }
__device__ __forceinline__ void bulk_wait_read() { asm volatile("cp.async.bulk.wait_group.read 0;" ::: "memory"); }
__device__ __forceinline__ void fence_async_smem() { asm volatile("fence.proxy.async.shared::cta;" ::: "memory"); }
__device__ __forceinline__ void prefetch_map(const CUtensorMap* m) { asm volatile("prefetch.tensormap [%0];" :: "l"(m) : "memory"); }
__device__ __forceinline__ void wg_fence() { asm volatile("wgmma.fence.sync.aligned;" ::: "memory"); }
__device__ __forceinline__ void wg_commit() { asm volatile("wgmma.commit_group.sync.aligned;" ::: "memory"); }
template <int N> __device__ __forceinline__ void wg_wait() { asm volatile("wgmma.wait_group.sync.aligned %0;" :: "n"(N) : "memory"); }
__device__ __forceinline__ void bar_sync(int id, int n) { asm volatile("bar.sync %0, %1;" :: "r"(id), "r"(n) : "memory"); }
__device__ __forceinline__ void bar_arrive(int id, int n) { asm volatile("bar.arrive %0, %1;" :: "r"(id), "r"(n) : "memory"); }
__device__ __forceinline__ void flag_add(uint32_t* f) { asm volatile("red.relaxed.gpu.global.add.u32 [%0], 1;" :: "l"(f) : "memory"); }
__device__ __forceinline__ void flag_set(uint32_t* f, uint32_t v) { asm volatile("red.relaxed.gpu.global.max.u32 [%0], %1;" :: "l"(f), "r"(v) : "memory"); }
__device__ __forceinline__ uint32_t flag_get(const uint32_t* f) { uint32_t v; asm volatile("ld.relaxed.gpu.global.u32 %0, [%1];" : "=r"(v) : "l"(f) : "memory"); return v; }
__device__ __forceinline__ void bulk_wait_fence() { asm volatile("cp.async.bulk.wait_group 0;\nfence.proxy.async.global;\nfence.acq_rel.gpu;" ::: "memory"); }
__device__ __forceinline__ uint32_t landed(bool el, const uint32_t* p, uint32_t pitch, uint32_t zero) {
    if (el) asm volatile("cp.async.bulk.wait_group 0;" ::: "memory");
    __syncwarp();
    const uint32_t a = flag_get(p), b = flag_get(p + 32 * pitch);
    return __reduce_or_sync(0xffffffffu, (a | b) & zero);
}
__device__ __forceinline__ uint32_t d16(uint32_t addr) { return (addr & 0x3FFFF) >> 4; }
__device__ __forceinline__ uint64_t mk_desc(uint32_t a16, uint32_t off, uint32_t lbo, uint32_t sbo, uint32_t swz) {
    const uint32_t lo = a16 + (off >> 4) + ((lbo >> 4) << 16), hi = (sbo >> 4) | (swz << 30);
    return ((uint64_t)hi << 32) | lo;
}
__device__ __forceinline__ uint32_t pack2(float lo, float hi) {
    uint32_t r; asm("cvt.rn.bf16x2.f32 %0, %1, %2;" : "=r"(r) : "f"(hi), "f"(lo)); return r;
}
__device__ __forceinline__ uint32_t hfma2_bf16(uint32_t a, uint32_t b, uint32_t c) {
    uint32_t r; asm("fma.rn.bf16x2 %0, %1, %2, %3;" : "=r"(r) : "r"(a), "r"(b), "r"(c)); return r;
}
__device__ __forceinline__ float bf_lo(uint32_t v) { return __uint_as_float(v << 16); }
__device__ __forceinline__ float bf_hi(uint32_t v) { return __uint_as_float(v & 0xFFFF0000u); }
__device__ __forceinline__ void unpack2(uint32_t v, float& lo, float& hi) {
    asm volatile("shl.b32 %0, %2, 16;\nand.b32 %1, %2, 0xffff0000;" : "=f"(lo), "=f"(hi) : "r"(v));
}
__device__ __forceinline__ float bf_round(float x) { return __bfloat162float(__float2bfloat16_rn(x)); }
__device__ __forceinline__ void stsm4(uint32_t addr, uint32_t r0, uint32_t r1, uint32_t r2, uint32_t r3) {
    asm volatile("stmatrix.sync.aligned.m8n8.x4.shared.b16 [%0], {%1, %2, %3, %4};" :: "r"(addr), "r"(r0), "r"(r1), "r"(r2), "r"(r3) : "memory");
}
__device__ __forceinline__ void stsm4t(uint32_t addr, uint32_t r0, uint32_t r1, uint32_t r2, uint32_t r3) {
    asm volatile("stmatrix.sync.aligned.m8n8.x4.trans.shared.b16 [%0], {%1, %2, %3, %4};" :: "r"(addr), "r"(r0), "r"(r1), "r"(r2), "r"(r3) : "memory");
}
__device__ __forceinline__ uint32_t movm(uint32_t a) { uint32_t d; asm volatile("movmatrix.sync.aligned.m8n8.trans.b16 %0, %1;" : "=r"(d) : "r"(a)); return d; }
__device__ __forceinline__ void ldsm4(uint32_t addr, uint32_t& r0, uint32_t& r1, uint32_t& r2, uint32_t& r3) {
    asm volatile("ldmatrix.sync.aligned.m8n8.x4.shared.b16 {%0, %1, %2, %3}, [%4];" : "=r"(r0), "=r"(r1), "=r"(r2), "=r"(r3) : "r"(addr) : "memory");
}
__device__ __forceinline__ void ldsm4t(uint32_t addr, uint32_t& r0, uint32_t& r1, uint32_t& r2, uint32_t& r3) {
    asm volatile("ldmatrix.sync.aligned.m8n8.x4.trans.shared.b16 {%0, %1, %2, %3}, [%4];" : "=r"(r0), "=r"(r1), "=r"(r2), "=r"(r3) : "r"(addr) : "memory");
}
__device__ __forceinline__ void mma16816(float (&c)[4], uint32_t a0, uint32_t a1, uint32_t a2, uint32_t a3, uint32_t b0, uint32_t b1) {
    asm("mma.sync.aligned.m16n8k16.row.col.f32.bf16.bf16.f32 {%0, %1, %2, %3}, {%4, %5, %6, %7}, {%8, %9}, {%0, %1, %2, %3};"
        : "+f"(c[0]), "+f"(c[1]), "+f"(c[2]), "+f"(c[3]) : "r"(a0), "r"(a1), "r"(a2), "r"(a3), "r"(b0), "r"(b1));
}
__device__ __forceinline__ float rsq(float x) { float r; asm("rsqrt.approx.ftz.f32 %0, %1;" : "=f"(r) : "f"(x)); return r; }
__device__ __forceinline__ float rcp(float x) { float r; asm("rcp.approx.ftz.f32 %0, %1;" : "=f"(r) : "f"(x)); return r; }
__device__ __forceinline__ float ex2(float x) { float r; asm("ex2.approx.ftz.f32 %0, %1;" : "=f"(r) : "f"(x)); return r; }
__device__ __forceinline__ float tanh_(float x) { float t; asm("tanh.approx.f32 %0, %1;" : "=f"(t) : "f"(x)); return t; }
__device__ __forceinline__ void block_end(uint32_t opaque, uint32_t id) { asm volatile("{\n.reg .pred p;\nsetp.eq.u32 p, %0, %1;\n@p trap;\n}" :: "r"(opaque), "r"(0xffffff00u + id)); }
__device__ __forceinline__ float silu_(float x) { return __fdividef(x, 1.f + __expf(-x)); }
__device__ __forceinline__ void st_pkt(void* p, uint32_t a, uint32_t b) {
    asm volatile("{\n.reg .b64 t;\nmov.b64 t, {%1, %2};\nst.relaxed.gpu.global.b64 [%0], t;\n}" :: "l"(p), "r"(a), "r"(b) : "memory");
}
__device__ __forceinline__ uint4 ld_pkt2(const void* p) {
    uint4 v; asm volatile("{\n.reg .b64 t, u;\nld.relaxed.gpu.global.v2.b64 {t, u}, [%4];\nmov.b64 {%0, %1}, t;\nmov.b64 {%2, %3}, u;\n}"
        : "=r"(v.x), "=r"(v.y), "=r"(v.z), "=r"(v.w) : "l"(p) : "memory"); return v;
}
__device__ __forceinline__ void st_pkt16(void* p, uint32_t a, uint32_t b, uint32_t c, uint32_t d) {
    asm volatile("{\n.reg .b64 t, u;\n.reg .b128 w;\nmov.b64 t, {%1, %2};\nmov.b64 u, {%3, %4};\nmov.b128 w, {t, u};\nst.relaxed.gpu.global.b128 [%0], w;\n}"
        :: "l"(p), "r"(a), "r"(b), "r"(c), "r"(d) : "memory");
}
__device__ __forceinline__ uint4 ld_pkt16(const void* p) {
    uint4 v; asm volatile("{\n.reg .b64 t, u;\n.reg .b128 w;\nld.relaxed.gpu.global.b128 w, [%4];\nmov.b128 {t, u}, w;\nmov.b64 {%0, %1}, t;\nmov.b64 {%2, %3}, u;\n}"
        : "=r"(v.x), "=r"(v.y), "=r"(v.z), "=r"(v.w) : "l"(p) : "memory"); return v;
}
#define SPIN_GUARD(n) do { if (++(n) > (1u << 22)) asm volatile("trap;"); } while (0)
__device__ __forceinline__ uint4 lds128(uint32_t a) { uint4 v; asm volatile("ld.shared.v4.u32 {%0, %1, %2, %3}, [%4];" : "=r"(v.x), "=r"(v.y), "=r"(v.z), "=r"(v.w) : "r"(a) : "memory"); return v; }
__device__ __forceinline__ void sts128(uint32_t a, uint32_t x, uint32_t y, uint32_t z, uint32_t w) { asm volatile("st.shared.v4.u32 [%0], {%1, %2, %3, %4};" :: "r"(a), "r"(x), "r"(y), "r"(z), "r"(w) : "memory"); }
__device__ __forceinline__ uint32_t lds32(uint32_t a) { uint32_t v; asm volatile("ld.shared.u32 %0, [%1];" : "=r"(v) : "r"(a) : "memory"); return v; }
__device__ __forceinline__ void sts32(uint32_t a, uint32_t v) { asm volatile("st.shared.u32 [%0], %1;" :: "r"(a), "r"(v) : "memory"); }
__device__ __forceinline__ bool elect_one() {
    uint32_t p; asm volatile("{\n.reg .pred q;\nelect.sync _|q, 0xffffffff;\nselp.u32 %0, 1, 0, q;\n}" : "=r"(p)); return p;
}
__device__ __forceinline__ void pause(uint32_t cycles) {
    uint32_t t0, t; asm volatile("mov.u32 %0, %%clock;" : "=r"(t0));
    do { __nanosleep(64); asm volatile("mov.u32 %0, %%clock;" : "=r"(t)); } while (t - t0 < cycles);
}
__device__ __forceinline__ void cluster_arrive() { asm volatile("barrier.cluster.arrive.relaxed.aligned;" ::: "memory"); }
__device__ __forceinline__ void cluster_wait() { asm volatile("barrier.cluster.wait.aligned;" ::: "memory"); }

__device__ __forceinline__ void wgmma_n128_z(float (&d)[64], uint64_t da, uint64_t db) {
    asm volatile("{\n.reg .pred p;\nsetp.ne.b32 p, 0, 0;\n"
        "wgmma.mma_async.sync.aligned.m64n128k16.f32.bf16.bf16 {"
        "%0, %1, %2, %3, %4, %5, %6, %7, %8, %9, %10, %11, %12, %13, %14, %15, "
        "%16, %17, %18, %19, %20, %21, %22, %23, %24, %25, %26, %27, %28, %29, %30, %31, "
        "%32, %33, %34, %35, %36, %37, %38, %39, %40, %41, %42, %43, %44, %45, %46, %47, "
        "%48, %49, %50, %51, %52, %53, %54, %55, %56, %57, %58, %59, %60, %61, %62, %63"
        "}, %64, %65, p, 1, 1, 0, 1;\n}\n"
        : "=f"(d[0]), "=f"(d[1]), "=f"(d[2]), "=f"(d[3]), "=f"(d[4]), "=f"(d[5]), "=f"(d[6]), "=f"(d[7]),
          "=f"(d[8]), "=f"(d[9]), "=f"(d[10]), "=f"(d[11]), "=f"(d[12]), "=f"(d[13]), "=f"(d[14]), "=f"(d[15]),
          "=f"(d[16]), "=f"(d[17]), "=f"(d[18]), "=f"(d[19]), "=f"(d[20]), "=f"(d[21]), "=f"(d[22]), "=f"(d[23]),
          "=f"(d[24]), "=f"(d[25]), "=f"(d[26]), "=f"(d[27]), "=f"(d[28]), "=f"(d[29]), "=f"(d[30]), "=f"(d[31]),
          "=f"(d[32]), "=f"(d[33]), "=f"(d[34]), "=f"(d[35]), "=f"(d[36]), "=f"(d[37]), "=f"(d[38]), "=f"(d[39]),
          "=f"(d[40]), "=f"(d[41]), "=f"(d[42]), "=f"(d[43]), "=f"(d[44]), "=f"(d[45]), "=f"(d[46]), "=f"(d[47]),
          "=f"(d[48]), "=f"(d[49]), "=f"(d[50]), "=f"(d[51]), "=f"(d[52]), "=f"(d[53]), "=f"(d[54]), "=f"(d[55]),
          "=f"(d[56]), "=f"(d[57]), "=f"(d[58]), "=f"(d[59]), "=f"(d[60]), "=f"(d[61]), "=f"(d[62]), "=f"(d[63])
        : "l"(da), "l"(db));
}
__device__ __forceinline__ void wgmma_n128(float (&d)[64], uint64_t da, uint64_t db) {
    asm volatile("{\n.reg .pred p;\nsetp.eq.b32 p, 0, 0;\n"
        "wgmma.mma_async.sync.aligned.m64n128k16.f32.bf16.bf16 {"
        "%0, %1, %2, %3, %4, %5, %6, %7, %8, %9, %10, %11, %12, %13, %14, %15, "
        "%16, %17, %18, %19, %20, %21, %22, %23, %24, %25, %26, %27, %28, %29, %30, %31, "
        "%32, %33, %34, %35, %36, %37, %38, %39, %40, %41, %42, %43, %44, %45, %46, %47, "
        "%48, %49, %50, %51, %52, %53, %54, %55, %56, %57, %58, %59, %60, %61, %62, %63"
        "}, %64, %65, p, 1, 1, 0, 1;\n}\n"
        : "+f"(d[0]), "+f"(d[1]), "+f"(d[2]), "+f"(d[3]), "+f"(d[4]), "+f"(d[5]), "+f"(d[6]), "+f"(d[7]),
          "+f"(d[8]), "+f"(d[9]), "+f"(d[10]), "+f"(d[11]), "+f"(d[12]), "+f"(d[13]), "+f"(d[14]), "+f"(d[15]),
          "+f"(d[16]), "+f"(d[17]), "+f"(d[18]), "+f"(d[19]), "+f"(d[20]), "+f"(d[21]), "+f"(d[22]), "+f"(d[23]),
          "+f"(d[24]), "+f"(d[25]), "+f"(d[26]), "+f"(d[27]), "+f"(d[28]), "+f"(d[29]), "+f"(d[30]), "+f"(d[31]),
          "+f"(d[32]), "+f"(d[33]), "+f"(d[34]), "+f"(d[35]), "+f"(d[36]), "+f"(d[37]), "+f"(d[38]), "+f"(d[39]),
          "+f"(d[40]), "+f"(d[41]), "+f"(d[42]), "+f"(d[43]), "+f"(d[44]), "+f"(d[45]), "+f"(d[46]), "+f"(d[47]),
          "+f"(d[48]), "+f"(d[49]), "+f"(d[50]), "+f"(d[51]), "+f"(d[52]), "+f"(d[53]), "+f"(d[54]), "+f"(d[55]),
          "+f"(d[56]), "+f"(d[57]), "+f"(d[58]), "+f"(d[59]), "+f"(d[60]), "+f"(d[61]), "+f"(d[62]), "+f"(d[63])
        : "l"(da), "l"(db));
}
__device__ __forceinline__ void wgmma_n176_z(float (&d)[88], uint64_t da, uint64_t db) {
    asm volatile("{\n.reg .pred p;\nsetp.ne.b32 p, 0, 0;\n"
        "wgmma.mma_async.sync.aligned.m64n176k16.f32.bf16.bf16 {"
        "%0, %1, %2, %3, %4, %5, %6, %7, %8, %9, %10, %11, %12, %13, %14, %15, "
        "%16, %17, %18, %19, %20, %21, %22, %23, %24, %25, %26, %27, %28, %29, %30, %31, "
        "%32, %33, %34, %35, %36, %37, %38, %39, %40, %41, %42, %43, %44, %45, %46, %47, "
        "%48, %49, %50, %51, %52, %53, %54, %55, %56, %57, %58, %59, %60, %61, %62, %63, "
        "%64, %65, %66, %67, %68, %69, %70, %71, %72, %73, %74, %75, %76, %77, %78, %79, "
        "%80, %81, %82, %83, %84, %85, %86, %87"
        "}, %88, %89, p, 1, 1, 0, 1;\n}\n"
        : "=f"(d[0]), "=f"(d[1]), "=f"(d[2]), "=f"(d[3]), "=f"(d[4]), "=f"(d[5]), "=f"(d[6]), "=f"(d[7]),
          "=f"(d[8]), "=f"(d[9]), "=f"(d[10]), "=f"(d[11]), "=f"(d[12]), "=f"(d[13]), "=f"(d[14]), "=f"(d[15]),
          "=f"(d[16]), "=f"(d[17]), "=f"(d[18]), "=f"(d[19]), "=f"(d[20]), "=f"(d[21]), "=f"(d[22]), "=f"(d[23]),
          "=f"(d[24]), "=f"(d[25]), "=f"(d[26]), "=f"(d[27]), "=f"(d[28]), "=f"(d[29]), "=f"(d[30]), "=f"(d[31]),
          "=f"(d[32]), "=f"(d[33]), "=f"(d[34]), "=f"(d[35]), "=f"(d[36]), "=f"(d[37]), "=f"(d[38]), "=f"(d[39]),
          "=f"(d[40]), "=f"(d[41]), "=f"(d[42]), "=f"(d[43]), "=f"(d[44]), "=f"(d[45]), "=f"(d[46]), "=f"(d[47]),
          "=f"(d[48]), "=f"(d[49]), "=f"(d[50]), "=f"(d[51]), "=f"(d[52]), "=f"(d[53]), "=f"(d[54]), "=f"(d[55]),
          "=f"(d[56]), "=f"(d[57]), "=f"(d[58]), "=f"(d[59]), "=f"(d[60]), "=f"(d[61]), "=f"(d[62]), "=f"(d[63]),
          "=f"(d[64]), "=f"(d[65]), "=f"(d[66]), "=f"(d[67]), "=f"(d[68]), "=f"(d[69]), "=f"(d[70]), "=f"(d[71]),
          "=f"(d[72]), "=f"(d[73]), "=f"(d[74]), "=f"(d[75]), "=f"(d[76]), "=f"(d[77]), "=f"(d[78]), "=f"(d[79]),
          "=f"(d[80]), "=f"(d[81]), "=f"(d[82]), "=f"(d[83]), "=f"(d[84]), "=f"(d[85]), "=f"(d[86]), "=f"(d[87])
        : "l"(da), "l"(db));
}
__device__ __forceinline__ void wgmma_n176(float (&d)[88], uint64_t da, uint64_t db) {
    asm volatile("{\n.reg .pred p;\nsetp.eq.b32 p, 0, 0;\n"
        "wgmma.mma_async.sync.aligned.m64n176k16.f32.bf16.bf16 {"
        "%0, %1, %2, %3, %4, %5, %6, %7, %8, %9, %10, %11, %12, %13, %14, %15, "
        "%16, %17, %18, %19, %20, %21, %22, %23, %24, %25, %26, %27, %28, %29, %30, %31, "
        "%32, %33, %34, %35, %36, %37, %38, %39, %40, %41, %42, %43, %44, %45, %46, %47, "
        "%48, %49, %50, %51, %52, %53, %54, %55, %56, %57, %58, %59, %60, %61, %62, %63, "
        "%64, %65, %66, %67, %68, %69, %70, %71, %72, %73, %74, %75, %76, %77, %78, %79, "
        "%80, %81, %82, %83, %84, %85, %86, %87"
        "}, %88, %89, p, 1, 1, 0, 1;\n}\n"
        : "+f"(d[0]), "+f"(d[1]), "+f"(d[2]), "+f"(d[3]), "+f"(d[4]), "+f"(d[5]), "+f"(d[6]), "+f"(d[7]),
          "+f"(d[8]), "+f"(d[9]), "+f"(d[10]), "+f"(d[11]), "+f"(d[12]), "+f"(d[13]), "+f"(d[14]), "+f"(d[15]),
          "+f"(d[16]), "+f"(d[17]), "+f"(d[18]), "+f"(d[19]), "+f"(d[20]), "+f"(d[21]), "+f"(d[22]), "+f"(d[23]),
          "+f"(d[24]), "+f"(d[25]), "+f"(d[26]), "+f"(d[27]), "+f"(d[28]), "+f"(d[29]), "+f"(d[30]), "+f"(d[31]),
          "+f"(d[32]), "+f"(d[33]), "+f"(d[34]), "+f"(d[35]), "+f"(d[36]), "+f"(d[37]), "+f"(d[38]), "+f"(d[39]),
          "+f"(d[40]), "+f"(d[41]), "+f"(d[42]), "+f"(d[43]), "+f"(d[44]), "+f"(d[45]), "+f"(d[46]), "+f"(d[47]),
          "+f"(d[48]), "+f"(d[49]), "+f"(d[50]), "+f"(d[51]), "+f"(d[52]), "+f"(d[53]), "+f"(d[54]), "+f"(d[55]),
          "+f"(d[56]), "+f"(d[57]), "+f"(d[58]), "+f"(d[59]), "+f"(d[60]), "+f"(d[61]), "+f"(d[62]), "+f"(d[63]),
          "+f"(d[64]), "+f"(d[65]), "+f"(d[66]), "+f"(d[67]), "+f"(d[68]), "+f"(d[69]), "+f"(d[70]), "+f"(d[71]),
          "+f"(d[72]), "+f"(d[73]), "+f"(d[74]), "+f"(d[75]), "+f"(d[76]), "+f"(d[77]), "+f"(d[78]), "+f"(d[79]),
          "+f"(d[80]), "+f"(d[81]), "+f"(d[82]), "+f"(d[83]), "+f"(d[84]), "+f"(d[85]), "+f"(d[86]), "+f"(d[87])
        : "l"(da), "l"(db));
}
__device__ __forceinline__ void wgmma_n256_z(float (&d)[128], uint64_t da, uint64_t db) {
    asm volatile("{\n.reg .pred p;\nsetp.ne.b32 p, 0, 0;\n"
        "wgmma.mma_async.sync.aligned.m64n256k16.f32.bf16.bf16 {"
        "%0, %1, %2, %3, %4, %5, %6, %7, %8, %9, %10, %11, %12, %13, %14, %15, "
        "%16, %17, %18, %19, %20, %21, %22, %23, %24, %25, %26, %27, %28, %29, %30, %31, "
        "%32, %33, %34, %35, %36, %37, %38, %39, %40, %41, %42, %43, %44, %45, %46, %47, "
        "%48, %49, %50, %51, %52, %53, %54, %55, %56, %57, %58, %59, %60, %61, %62, %63, "
        "%64, %65, %66, %67, %68, %69, %70, %71, %72, %73, %74, %75, %76, %77, %78, %79, "
        "%80, %81, %82, %83, %84, %85, %86, %87, %88, %89, %90, %91, %92, %93, %94, %95, "
        "%96, %97, %98, %99, %100, %101, %102, %103, %104, %105, %106, %107, %108, %109, %110, %111, "
        "%112, %113, %114, %115, %116, %117, %118, %119, %120, %121, %122, %123, %124, %125, %126, %127"
        "}, %128, %129, p, 1, 1, 0, 1;\n}\n"
        : "=f"(d[0]), "=f"(d[1]), "=f"(d[2]), "=f"(d[3]), "=f"(d[4]), "=f"(d[5]), "=f"(d[6]), "=f"(d[7]),
          "=f"(d[8]), "=f"(d[9]), "=f"(d[10]), "=f"(d[11]), "=f"(d[12]), "=f"(d[13]), "=f"(d[14]), "=f"(d[15]),
          "=f"(d[16]), "=f"(d[17]), "=f"(d[18]), "=f"(d[19]), "=f"(d[20]), "=f"(d[21]), "=f"(d[22]), "=f"(d[23]),
          "=f"(d[24]), "=f"(d[25]), "=f"(d[26]), "=f"(d[27]), "=f"(d[28]), "=f"(d[29]), "=f"(d[30]), "=f"(d[31]),
          "=f"(d[32]), "=f"(d[33]), "=f"(d[34]), "=f"(d[35]), "=f"(d[36]), "=f"(d[37]), "=f"(d[38]), "=f"(d[39]),
          "=f"(d[40]), "=f"(d[41]), "=f"(d[42]), "=f"(d[43]), "=f"(d[44]), "=f"(d[45]), "=f"(d[46]), "=f"(d[47]),
          "=f"(d[48]), "=f"(d[49]), "=f"(d[50]), "=f"(d[51]), "=f"(d[52]), "=f"(d[53]), "=f"(d[54]), "=f"(d[55]),
          "=f"(d[56]), "=f"(d[57]), "=f"(d[58]), "=f"(d[59]), "=f"(d[60]), "=f"(d[61]), "=f"(d[62]), "=f"(d[63]),
          "=f"(d[64]), "=f"(d[65]), "=f"(d[66]), "=f"(d[67]), "=f"(d[68]), "=f"(d[69]), "=f"(d[70]), "=f"(d[71]),
          "=f"(d[72]), "=f"(d[73]), "=f"(d[74]), "=f"(d[75]), "=f"(d[76]), "=f"(d[77]), "=f"(d[78]), "=f"(d[79]),
          "=f"(d[80]), "=f"(d[81]), "=f"(d[82]), "=f"(d[83]), "=f"(d[84]), "=f"(d[85]), "=f"(d[86]), "=f"(d[87]),
          "=f"(d[88]), "=f"(d[89]), "=f"(d[90]), "=f"(d[91]), "=f"(d[92]), "=f"(d[93]), "=f"(d[94]), "=f"(d[95]),
          "=f"(d[96]), "=f"(d[97]), "=f"(d[98]), "=f"(d[99]), "=f"(d[100]), "=f"(d[101]), "=f"(d[102]), "=f"(d[103]),
          "=f"(d[104]), "=f"(d[105]), "=f"(d[106]), "=f"(d[107]), "=f"(d[108]), "=f"(d[109]), "=f"(d[110]), "=f"(d[111]),
          "=f"(d[112]), "=f"(d[113]), "=f"(d[114]), "=f"(d[115]), "=f"(d[116]), "=f"(d[117]), "=f"(d[118]), "=f"(d[119]),
          "=f"(d[120]), "=f"(d[121]), "=f"(d[122]), "=f"(d[123]), "=f"(d[124]), "=f"(d[125]), "=f"(d[126]), "=f"(d[127])
        : "l"(da), "l"(db));
}
__device__ __forceinline__ void wgmma_n256(float (&d)[128], uint64_t da, uint64_t db) {
    asm volatile("{\n.reg .pred p;\nsetp.eq.b32 p, 0, 0;\n"
        "wgmma.mma_async.sync.aligned.m64n256k16.f32.bf16.bf16 {"
        "%0, %1, %2, %3, %4, %5, %6, %7, %8, %9, %10, %11, %12, %13, %14, %15, "
        "%16, %17, %18, %19, %20, %21, %22, %23, %24, %25, %26, %27, %28, %29, %30, %31, "
        "%32, %33, %34, %35, %36, %37, %38, %39, %40, %41, %42, %43, %44, %45, %46, %47, "
        "%48, %49, %50, %51, %52, %53, %54, %55, %56, %57, %58, %59, %60, %61, %62, %63, "
        "%64, %65, %66, %67, %68, %69, %70, %71, %72, %73, %74, %75, %76, %77, %78, %79, "
        "%80, %81, %82, %83, %84, %85, %86, %87, %88, %89, %90, %91, %92, %93, %94, %95, "
        "%96, %97, %98, %99, %100, %101, %102, %103, %104, %105, %106, %107, %108, %109, %110, %111, "
        "%112, %113, %114, %115, %116, %117, %118, %119, %120, %121, %122, %123, %124, %125, %126, %127"
        "}, %128, %129, p, 1, 1, 0, 1;\n}\n"
        : "+f"(d[0]), "+f"(d[1]), "+f"(d[2]), "+f"(d[3]), "+f"(d[4]), "+f"(d[5]), "+f"(d[6]), "+f"(d[7]),
          "+f"(d[8]), "+f"(d[9]), "+f"(d[10]), "+f"(d[11]), "+f"(d[12]), "+f"(d[13]), "+f"(d[14]), "+f"(d[15]),
          "+f"(d[16]), "+f"(d[17]), "+f"(d[18]), "+f"(d[19]), "+f"(d[20]), "+f"(d[21]), "+f"(d[22]), "+f"(d[23]),
          "+f"(d[24]), "+f"(d[25]), "+f"(d[26]), "+f"(d[27]), "+f"(d[28]), "+f"(d[29]), "+f"(d[30]), "+f"(d[31]),
          "+f"(d[32]), "+f"(d[33]), "+f"(d[34]), "+f"(d[35]), "+f"(d[36]), "+f"(d[37]), "+f"(d[38]), "+f"(d[39]),
          "+f"(d[40]), "+f"(d[41]), "+f"(d[42]), "+f"(d[43]), "+f"(d[44]), "+f"(d[45]), "+f"(d[46]), "+f"(d[47]),
          "+f"(d[48]), "+f"(d[49]), "+f"(d[50]), "+f"(d[51]), "+f"(d[52]), "+f"(d[53]), "+f"(d[54]), "+f"(d[55]),
          "+f"(d[56]), "+f"(d[57]), "+f"(d[58]), "+f"(d[59]), "+f"(d[60]), "+f"(d[61]), "+f"(d[62]), "+f"(d[63]),
          "+f"(d[64]), "+f"(d[65]), "+f"(d[66]), "+f"(d[67]), "+f"(d[68]), "+f"(d[69]), "+f"(d[70]), "+f"(d[71]),
          "+f"(d[72]), "+f"(d[73]), "+f"(d[74]), "+f"(d[75]), "+f"(d[76]), "+f"(d[77]), "+f"(d[78]), "+f"(d[79]),
          "+f"(d[80]), "+f"(d[81]), "+f"(d[82]), "+f"(d[83]), "+f"(d[84]), "+f"(d[85]), "+f"(d[86]), "+f"(d[87]),
          "+f"(d[88]), "+f"(d[89]), "+f"(d[90]), "+f"(d[91]), "+f"(d[92]), "+f"(d[93]), "+f"(d[94]), "+f"(d[95]),
          "+f"(d[96]), "+f"(d[97]), "+f"(d[98]), "+f"(d[99]), "+f"(d[100]), "+f"(d[101]), "+f"(d[102]), "+f"(d[103]),
          "+f"(d[104]), "+f"(d[105]), "+f"(d[106]), "+f"(d[107]), "+f"(d[108]), "+f"(d[109]), "+f"(d[110]), "+f"(d[111]),
          "+f"(d[112]), "+f"(d[113]), "+f"(d[114]), "+f"(d[115]), "+f"(d[116]), "+f"(d[117]), "+f"(d[118]), "+f"(d[119]),
          "+f"(d[120]), "+f"(d[121]), "+f"(d[122]), "+f"(d[123]), "+f"(d[124]), "+f"(d[125]), "+f"(d[126]), "+f"(d[127])
        : "l"(da), "l"(db));
}

struct Idx {
    uint32_t lane, warp, w4, q4, g8, prow, pan;
    __device__ __forceinline__ Idx() {
        uint32_t t; asm volatile("mov.u32 %0, %%tid.x;" : "=r"(t));
        lane = t & 31; warp = t >> 5; w4 = warp & 3; q4 = lane & 3; g8 = lane >> 2;
        prow = w4 * 16 + ((lane >> 3) & 1) * 8 + (lane & 7);
        pan = prow * 128 + (((lane >> 4) ^ (lane & 7)) << 4);
    }
};
#define IDX() const Idx ix; const uint32_t lane = ix.lane, warp = ix.warp, w4 = ix.w4, q4 = ix.q4, g8 = ix.g8, prow = ix.prow, pan_addr = ix.pan; \
    (void)lane; (void)warp; (void)w4; (void)q4; (void)g8; (void)prow; (void)pan_addr;

__device__ __forceinline__ int kof(int t, int sh, int j) {
    const int p = t >> (sh - 1), pn = p < 2 ? p : p >= 9, q = p - 2 - 7 * pn;
    return ((p < 2 ? j : q + (q >= j)) << 7) + (pn << 6) + ((t & (sh - 1)) << 5);
}
__device__ __forceinline__ uint32_t fidx(uint32_t m, uint32_t w, uint32_t pn) {
    return m * 32 + w * 16 + pn;
}
constexpr int HC0 = 8 * 48, HC3 = HC0 + 3072;
__device__ __forceinline__ int hcol(int p, int j) { return HC0 + p * 1024 + j * 128; }
struct Ring {
    uint32_t slot, par;
    __device__ __forceinline__ void next() { if (++slot == NSLOT) { slot = 0; par ^= 1; } }
    __device__ __forceinline__ void skip(uint32_t n) { slot += n; if (slot >= NSLOT) { slot -= NSLOT; par ^= 1; } }
};
__device__ __forceinline__ uint32_t BAR_FULL(uint32_t sb, uint32_t s) { return sb + OFF_BAR + 8 * s; }
constexpr uint32_t AF_REL = 48;
__device__ __forceinline__ uint32_t BAR_EMPTY(uint32_t sb, uint32_t s) { return sb + OFF_BAR + 96 + 8 * s; }
__device__ __forceinline__ uint32_t BAR_SFULL(uint32_t sb, uint32_t i) { return sb + OFF_BAR + 152 + 8 * i; }
__device__ __forceinline__ uint32_t BAR_SREADY(uint32_t sb, uint32_t i) { return sb + OFF_BAR + 184 + 8 * i; }
__device__ __forceinline__ uint32_t BAR_ONE(uint32_t sb, uint32_t i) { return sb + OFF_BAR + 216 + 8 * i; }
enum { EV_WIN, EV_WIN1, EV_WIN2, EV_WIN3, EV_P0, EV_GA, EV_GB, EV_LN2, EV_LAG1, EV_LAG2, EV_LAG3, EV_LAG4, EV_LAG5, EV_KV, EV_PAR, EV_AGO, EV_AGO1, EV_AGO2, EV_FGO, EV_FGO1, EV_FGO2, EV_H0, EV_H1, EV_H2, EV_H3, EV_TAIL, EV_COUNT = EV_TAIL + 8 };
constexpr int NB_TAIL = 4;

struct Rel {
    uint32_t base; bool sig;
    __device__ __forceinline__ Rel(uint32_t sb, uint32_t tw) {
        uint32_t a; asm("mapa.shared::cluster.u32 %0, %1, %2;" : "=r"(a) : "r"(BAR_EMPTY(sb, 0)), "r"((tw >> 5) & 1));
        base = __shfl_sync(0xffffffffu, a, 0); sig = (tw & ~32u) == 0;
    }
    __device__ __forceinline__ void operator()(uint32_t slot) const {
        if (sig) asm volatile("mbarrier.arrive.shared::cluster.b64 _, [%0];" :: "r"(base + 8 * slot) : "memory");
    }
};
struct LnRow { float rs0, nm0, rs1, nm1; };
struct Pipe {
    Rel rel; uint32_t p1, p2;
    __device__ __forceinline__ Pipe(uint32_t sb, uint32_t tw, uint32_t first) : rel(sb, tw), p1(first), p2(NSLOT) {}
    template <bool TWO> __device__ __forceinline__ void acquire(uint32_t sb, uint32_t af, const Ring& r) {
        const uint32_t b0 = BAR_FULL(sb, r.slot), b1 = b0 + af;
        const bool ready = TWO ? mbar_test2(b0, b1, r.par) : mbar_test(b0, r.par);
        wg_wait<1>();
        rel(p2);
        if (!ready) { if (TWO) mbar_wait2(b0, b1, r.par); else mbar_wait(b0, r.par); }
    }
    __device__ __forceinline__ void issued(uint32_t slot) { p2 = p1; p1 = slot; }
    __device__ __forceinline__ void drain1() { wg_wait<1>(); rel(p2); p2 = NSLOT; }
    __device__ __forceinline__ void drain0() { wg_wait<0>(); rel(p1); p1 = NSLOT; }
    template <bool TWO, class Step> __device__ __forceinline__ void hold(int LG, uint32_t sb, uint32_t af, Ring& r, uint32_t lag_bar, Step step) {
        Ring q = r;
#pragma unroll 1
        for (int i = 0; i < LG; ++i) { if (TWO) mbar_wait2(BAR_FULL(sb, q.slot), BAR_FULL(sb, q.slot) + af, q.par); else mbar_wait(BAR_FULL(sb, q.slot), q.par); q.next(); }
        mbar_wait(lag_bar, 0);
#pragma unroll 1
        do {
            step(r.slot);
            wg_wait<2>(); rel(p2); p2 = p1; p1 = r.slot;
            if (++r.slot == NSLOT) r.slot = 0;
        } while (r.slot != q.slot);
        r.par = q.par;
    }
};
template <bool TWO, bool FIRST, int NA, int NB>
__device__ __forceinline__ void step32(float (&aa)[NA], float (&ab)[NB], uint32_t sb, uint32_t wg, uint32_t slot, int own) {
    const uint32_t st = d16(sb) + slot * (SLOT >> 4);
    const uint32_t alo = own >= 0 ? d16(sb) + OFF_STG / 16 + wg * 1024 + (own >> 1) * 512 + (own & 1) * 4 : st + wg * 256;
    const uint32_t ahi = own >= 0 ? (1024 >> 4) | (1u << 30) : (512 >> 4) | (2u << 30);
    wg_fence();
#pragma unroll
    for (int k = 0; k < 2; ++k) {
        const uint64_t da = ((uint64_t)ahi << 32) | (alo + k * 2 + 0x10000);
        if constexpr (NA == 88) {
            const uint64_t d0 = mk_desc(st, 8192 + k * 2048, 8192, 1024, 1), d1 = mk_desc(st, 12288 + k * 2048, 8192, 1024, 1);
            if (FIRST && k == 0) { wgmma_n176_z(aa, da, d0); wgmma_n176_z(ab, da, d1); }
            else { wgmma_n176(aa, da, d0); wgmma_n176(ab, da, d1); }
        } else {
            const uint64_t d0 = mk_desc(st, 8192 + k * 2048, 4096, 1024, 1), d1 = mk_desc(st, 24576 + k * 2048, 4096, 1024, 1);
            if (FIRST && k == 0) { wgmma_n256_z(aa, da, d0); if constexpr (TWO) wgmma_n128_z(ab, da, d1); }
            else { wgmma_n256(aa, da, d0); if constexpr (TWO) wgmma_n128(ab, da, d1); }
        }
    }
    wg_commit();
}
template <bool TWO, int LG, int NA, int NB, class Mid, class Tail>
__device__ __forceinline__ void mainloop32(float (&aa)[NA], float (&ab)[NB], uint32_t sb, uint32_t wg, uint32_t tw, Ring& r, uint32_t lag_ev, int g0, Mid mid, Tail tail) {
    step32<TWO, true>(aa, ab, sb, wg, r.slot, TWO ? 0 : -1);
    TS(g0, 0);
    Pipe pp(sb, tw, r.slot);
    r.next();
    const int end = wg ? 32 : 32 - LG;
#pragma unroll 1
    for (int it = 1; it < end; ++it) {
        pp.acquire<TWO>(sb, wg ? 0 : AF_REL, r);
        step32<TWO, false>(aa, ab, sb, wg, r.slot, TWO && it < 4 ? it : -1);
        pp.issued(r.slot);
        TS(g0 + it, 0);
        r.next();
        mid(it);
    }
    if (wg == 0) { pp.drain1(); pp.drain0(); pp.hold<TWO>(LG, sb, AF_REL, r, BAR_ONE(sb, lag_ev), [&](uint32_t slot) { step32<TWO, false>(aa, ab, sb, 0, slot, -1); }); }
    if (wg == 1 && tw == 0) mbar_arrive(BAR_ONE(sb, lag_ev));
    pp.drain1();
    tail();
    pp.drain0();
    TS(g0 + 31, 1);
}
template <bool FIRST>
__device__ __forceinline__ void step64(float (&acc)[64], uint32_t sb, uint32_t wg, uint32_t slot, int own) {
    const uint32_t sbb = d16(sb) + slot * (SLOT >> 4), sa = own >= 0 ? d16(sb) + OFF_STG / 16 + wg * 1024 + own * 512 : sbb + wg * 512;
    wg_fence();
#pragma unroll
    for (int k = 0; k < 4; ++k) {
        const uint64_t da = mk_desc(sa, k * 32, 16, 1024, 1), db = mk_desc(sbb, 16384 + k * 2048, 8192, 1024, 1);
        if (FIRST && k == 0) wgmma_n128_z(acc, da, db); else wgmma_n128(acc, da, db);
    }
    wg_commit();
}
template <class Put, class Mid, class Tail>
__device__ __forceinline__ void mainloop64(float (&acc)[64], bool wo, uint32_t sb, uint32_t wg, uint32_t tw, Ring& r, Put put, Mid mid, Tail tail) {
    const int g0 = wo ? 32 : 144, nst = wo ? 16 : 56, lg = wo ? LAGW : LAGD; (void)g0;
    const uint32_t lag_bar = BAR_ONE(sb, wo ? EV_LAG4 : EV_LAG5), af = wo && !wg ? AF_REL : 0;
    if (!wo) CS(28);
    step64<true>(acc, sb, wg, r.slot, wo ? 0 : -1);
    if (!wo) CS(29);
    TS(g0, 0);
    Pipe pp(sb, tw, r.slot);
    r.next();
    int it = 1;
    auto run = [&](int end, int own, bool with_put) {
#pragma unroll 1
        do {
            pp.acquire<true>(sb, af, r);
            step64<false>(acc, sb, wg, r.slot, own);
            pp.issued(r.slot);
            TS(g0 + it, 0);
            if (wo && it == 2) CS(9);
            r.next();
            if (with_put && it == (wg ? PUTD1 : PUTD0)) put();
        } while (++it < end);
    };
    const int end = wg ? nst : nst - lg;
    run(wo ? 2 : wg ? MIDD : end, wo ? 1 : -1, true);
    mid();
    if (wo) { pp.drain1(); pp.drain0(); TS(g0 + 1, 1); }
    if (it < end) run(end, -1, false);
    if (wg == 0) { pp.drain1(); pp.drain0(); pp.hold<true>(lg, sb, af, r, lag_bar, [&](uint32_t slot) { step64<false>(acc, sb, 0, slot, -1); }); }
    if (wg == 1 && tw == 0) mbar_arrive(lag_bar);
    pp.drain1();
    tail();
    pp.drain0();
    TS(g0 + nst - 1, 1);
}

struct RowAcc {
    float sm[4] = {0.f, 0.f, 0.f, 0.f}, sq[4] = {0.f, 0.f, 0.f, 0.f};
    __device__ __forceinline__ void add(int e, float x) { sm[e & 3] += x; sq[e & 3] = fmaf(x, x, sq[e & 3]); }
    __device__ __forceinline__ void publish(uint4* dst, uint32_t q4, uint32_t ep) const {
        const float s0 = sm[0] + sm[1], s1 = sm[2] + sm[3], q0 = sq[0] + sq[1], q1 = sq[2] + sq[3];
        const bool od = q4 & 1;
        float sv = (od ? s1 : s0) + __shfl_xor_sync(0xffffffffu, od ? s0 : s1, 1), qv = (od ? q1 : q0) + __shfl_xor_sync(0xffffffffu, od ? q0 : q1, 1);
        sv += __shfl_xor_sync(0xffffffffu, sv, 2); qv += __shfl_xor_sync(0xffffffffu, qv, 2);
        st_pkt16(dst + (q4 & 1) * 8, 0, __float_as_uint(sv), __float_as_uint(qv), ep);
    }
};
__device__ __forceinline__ LnRow merge_stats(const uint4* src, uint32_t q4, uint32_t ep, uint32_t sb) {
    uint4 t[4];
    uint32_t n = 0;
    while (true) {
#pragma unroll
        for (int i = 0; i < 4; ++i) t[i] = ld_pkt16(src + (q4 * 2 + (i >> 1)) * 512 + (i & 1) * 8);
        const bool ok_ = __all_sync(0xffffffffu, t[0].w == ep && t[1].w == ep && t[2].w == ep && t[3].w == ep);
        if (n < 4) CS(14 + n);
        if (ok_) break;
        SPIN_GUARD(n);
    }
    float v[4];
#pragma unroll
    for (int h = 0; h < 2; ++h) { v[h] = __uint_as_float(t[h].y) + __uint_as_float(t[2 + h].y); v[2 + h] = __uint_as_float(t[h].z) + __uint_as_float(t[2 + h].z); }
#pragma unroll
    for (int o = 1; o < 4; o <<= 1)
#pragma unroll
        for (int i = 0; i < 4; ++i) v[i] += __shfl_xor_sync(0xffffffffu, v[i], o);
    const float m0 = v[0] * (1.f / D_), m1 = v[1] * (1.f / D_);
    const float r0 = rsq(fmaxf(fmaf(-m0, m0, v[2] * (1.f / D_)), 0.f) + 1e-5f), r1 = rsq(fmaxf(fmaf(-m1, m1, v[3] * (1.f / D_)), 0.f) + 1e-5f);
    return LnRow{r0, -m0 * r0, r1, -m1 * r1};
}
struct Stg {
    uint32_t b, par;
    __device__ __forceinline__ uint32_t acquire2(uint32_t sb, uint32_t wg) {
        mbar_wait2(BAR_SREADY(sb, wg * 2), BAR_SREADY(sb, wg * 2 + 1), par);
        par ^= 1;
        return sb + OFF_STG + wg * 16384;
    }
    __device__ __forceinline__ void publish(uint32_t sb, uint32_t wg, uint32_t lane) {
        fence_async_smem();
        __syncwarp();
        if (lane == 0) mbar_arrive(BAR_SFULL(sb, wg * 2 + b));
        b ^= 1;
    }
};

struct LnPar {
    uint4 p[8];
    __device__ __forceinline__ void load(uint32_t sb, uint32_t q4) {
#pragma unroll
        for (int i = 0; i < 8; ++i) p[i] = lds128(sb + OFF_PAR + i * 64 + q4 * 16);
    }
};
__device__ __forceinline__ void ln_norm(uint32_t (&xn)[32], const float (&x)[64], const LnRow& n) {
#pragma unroll
    for (int e = 0; e < 32; ++e) {
        const float rs = (e & 1) ? n.rs1 : n.rs0, nm = (e & 1) ? n.nm1 : n.nm0;
        xn[e] = pack2(fmaf(x[2 * e], rs, nm), fmaf(x[2 * e + 1], rs, nm));
    }
}
__device__ __forceinline__ void ln_emit(const uint32_t (&xr)[32], const LnPar& lp, uint32_t sb, uint32_t wg, const Idx& ix) {
#pragma unroll
    for (int i = 0; i < 8; ++i)
        stsm4(sb + OFF_STG + wg * 16384 + (i >> 2) * 8192 + (ix.pan ^ ((i & 3) << 5)), hfma2_bf16(xr[4 * i], lp.p[i].z, lp.p[i].x), hfma2_bf16(xr[4 * i + 1], lp.p[i].z, lp.p[i].x),
              hfma2_bf16(xr[4 * i + 2], lp.p[i].w, lp.p[i].y), hfma2_bf16(xr[4 * i + 3], lp.p[i].w, lp.p[i].y));
    fence_async_smem();
    __syncwarp();
    if (ix.lane < 2) mbar_arrive(BAR_SFULL(sb, wg * 2 + ix.lane));
    bar_sync(1 + wg, 128);
}
__device__ __forceinline__ void load_slab(uint32_t (&xr)[32], uint32_t buf) {
    IDX();
#pragma unroll
    for (int i = 0; i < 8; ++i) ldsm4(buf + (i >> 2) * 8192 + (pan_addr ^ ((i & 3) << 5)), xr[4 * i], xr[4 * i + 1], xr[4 * i + 2], xr[4 * i + 3]);
}
__device__ __forceinline__ void unpack_slab(float (&x)[64], const uint32_t (&xr)[32]) {
#pragma unroll
    for (int i = 0; i < 32; ++i) unpack2(xr[i], x[2 * i], x[2 * i + 1]);
}
__device__ __forceinline__ void store_slab(const float (&x)[64], uint32_t buf, uint32_t pitch, uint32_t pan, int i0, int i1) {
#pragma unroll
    for (int i = i0; i < i1; ++i)
        stsm4(buf + (i >> 2) * pitch + (pan ^ ((i & 3) << 5)), pack2(x[8 * i], x[8 * i + 1]), pack2(x[8 * i + 2], x[8 * i + 3]), pack2(x[8 * i + 4], x[8 * i + 5]), pack2(x[8 * i + 6], x[8 * i + 7]));
}
template <int NP, class Done>
__device__ __forceinline__ void fetch_halo(uint4* src, bool first, uint32_t dst, Done done) {
    uint4 hv[4 * NP];
    uint32_t n = 0;
    while (true) {
        bool ok = true;
#pragma unroll
        for (int i = 0; i < 4 * NP; ++i) { hv[i] = first ? make_uint4(0, 0, 0, 0) : ld_pkt16(src + (i >> 2) * 256 + (i & 3) * 32); ok = ok && hv[i].x != 0; }
        if (first || __all_sync(0xffffffffu, ok)) break;
        SPIN_GUARD(n);
    }
#pragma unroll
    for (int i = 0; i < 4 * NP; ++i) stsm4(dst + (i >> 2) * 4096 + (i & 3) * 512, hv[i].x, hv[i].y, hv[i].z, hv[i].w);
    done();
    if (!first) {
#pragma unroll
        for (int i = 0; i < 4 * NP; ++i) src[(i >> 2) * 256 + (i & 3) * 32] = make_uint4(0, 0, 0, 0);
    }
}

template <int N, class G, class U>
__device__ __forceinline__ void glu(uint32_t (&h)[N], G g, U u) {
#pragma unroll
    for (int i = 0; i < N; ++i) h[i] = pack2(fmaf(tanh_(g(2 * i)), u(2 * i), u(2 * i)), fmaf(tanh_(g(2 * i + 1)), u(2 * i + 1), u(2 * i + 1)));
}
__device__ __forceinline__ void put_h(const uint32_t (&h)[32], uint32_t sb, uint32_t wg, Stg& stg) {
    IDX();
    const uint32_t buf = stg.acquire2(sb, wg);
#pragma unroll
    for (int k = 0; k < 8; ++k) stsm4(buf + (k >> 2) * 8192 + (pan_addr ^ ((k & 3) << 5)), h[4 * k], h[4 * k + 1], h[4 * k + 2], h[4 * k + 3]);
    fence_async_smem();
    __syncwarp();
    if (lane < 2) mbar_arrive(BAR_SFULL(sb, wg * 2 + lane));
}

template <int NP, bool PREV>
__device__ __forceinline__ void passes128(uint32_t (&hp)[32], uint32_t sb, uint32_t wg, uint32_t tw, Ring& r, Stg& stg) {
#pragma unroll 1
    for (int p = 0; p < NP; ++p) {
        float b256[128], none[1];
        const int put_at = !PREV && p == 0 ? -1 : wg ? PUT1 : PUT0;
        mainloop32<false, LAGS>(b256, none, sb, wg, tw, r, EV_LAG2 + p, 80 + 32 * (p & 1), [&](int it) { if (it == put_at) put_h(hp, sb, wg, stg); },
                                [&] { if (PREV || p < NP - 1) mbar_wait(BAR_FULL(sb, r.slot), r.par); });
        if (threadIdx.x == 0) { TL(29 + 2 * p); TC(114 + 2 * p); }
        if (threadIdx.x == 128) TL(53 + 2 * (p & 1));
        CS(24 + 2 * (p & 1));
        glu(hp, [&](int i) { return b256[i + (i & 32)]; }, [&](int i) { return b256[i + (i & 32) + 32]; });
        if (threadIdx.x == 0) { TL(30 + 2 * p); TC(115 + 2 * p); }
        if (threadIdx.x == 128) TL(54 + 2 * (p & 1));
        CS(25 + 2 * (p & 1));
    }
}

__global__ void __launch_bounds__(384, 1)
fused_block_kernel(const __grid_constant__ Ptrs pt, const __grid_constant__ Maps mp) {
    uint32_t* const g_flags = pt.mail->flags;
    uint2* const g_mod = pt.mail->mod;
    uint4* const g_st1 = pt.mail->st1;
    uint32_t* const g_par2 = pt.mail->par2;
    uint4* const g_halo = pt.mail->halo;
    const __nv_bfloat16* __restrict__ cvec = pt.c;
    if (threadIdx.x == 224) { prefetch_map(&mp.wm8); prefetch_map(&mp.x); }
    extern __shared__ __align__(1024) uint8_t smem[];
    const uint32_t sb = smem_u32(smem);
    const uint32_t tid = threadIdx.x, tw = tid & 127, lane = tid & 31;
    const uint32_t warp = __shfl_sync(0xffffffffu, tid >> 5, 0), wg = warp >> 2;
    uint32_t rank; asm("mov.u32 %0, %%cluster_ctarank;" : "=r"(rank));
    rank = __shfl_sync(0xffffffffu, rank, 0);
    uint32_t ep;
    uint32_t smid; asm volatile("mov.u32 %0, %%smid;" : "=r"(smid));
    const int c = __shfl_sync(0xffffffffu, smid >> 1, 0);
    const int c7 = ((c - 32) * 37) >> 8;
    int grp = c < 32 ? c & 7 : c < 60 ? c - 31 - 7 * c7 : c < 62 ? -1 : 0;
    const int j = c < 32 ? c >> 3 : c < 60 ? 4 + c7 : c < 62 ? (c - 60) * 2 + rank : c - 58;
    const bool aux = grp < 0;
    const int m = grp * 2 + rank;
    uint4* const g_st2 = g_halo + (m > 0 ? (m - 1) * 8 * 512 : 128);

    bool cluster_arrive_early = false;
    if (wg < 2) {
      if (!KDEBUG) cluster_arrive();
      ep = flag_get(g_flags + FL_DONE);
      uint16_t cw[8];
      {
          const __nv_bfloat16* cp = cvec + ((tw >> 5) * 32 + (tw & 3) * 2) * 8 + (lane >> 2);
#pragma unroll
          for (int i = 0; i < 8; ++i) asm volatile("ld.global.nc.u16 %0, [%1];" : "=h"(cw[i]) : "l"(cp + (i >> 1) * 64 + (i & 1) * 8));
      }
      asm volatile("setmaxnreg.inc.sync.aligned.u32 224;");
      if (tid == 0) TL(58);
      if (KDEBUG) cluster_arrive();
      Ring r{0, 0};
      Stg stg{0, 0};
      if (aux) {
        if (wg == 0) {
            const uint4 cv = *(const uint4*)(cvec + tw * 8);
            sts128(sb + OFF_STG + (tw >> 3) * 1024 + (tw & 7) * 16, pack2(silu_(bf_lo(cv.x)), silu_(bf_hi(cv.x))), pack2(silu_(bf_lo(cv.y)), silu_(bf_hi(cv.y))),
                   pack2(silu_(bf_lo(cv.z)), silu_(bf_hi(cv.z))), pack2(silu_(bf_lo(cv.w)), silu_(bf_hi(cv.w))));
            fence_async_smem();
        }
        cluster_wait();
        ep = __shfl_sync(0xffffffffu, ep, 0) / NCTA + 1;
        if (wg == 0) {
            bar_sync(1, 128);
#pragma unroll 1
            for (int p = 0; p < 4; ++p) {
                float acc[128];
#pragma unroll
                for (int i = 0; i < 128; ++i) acc[i] = 0.f;
                uint32_t prev = 0;
#pragma unroll 1
                for (int kc = 0; kc < 16; ++kc) {
                    mbar_wait(BAR_FULL(sb, r.slot), r.par);
                    wg_fence();
#pragma unroll
                    for (int k = 0; k < 4; ++k)
                        wgmma_n256(acc, mk_desc(d16(sb) + kc * 64, OFF_STG + k * 32, 16, 0, 1), mk_desc(d16(sb) + r.slot * (SLOT >> 4), k * 2048, 8192, 1024, 1));
                    wg_commit();
                    wg_wait<1>();
                    if (kc > 0 && tw < 4) mbar_arrive(BAR_EMPTY(sb, prev));
                    prev = r.slot;
                    r.next();
                }
                wg_wait<0>();
                if (tw < 4) mbar_arrive(BAR_EMPTY(sb, prev));
                if (tw < 4) {
#pragma unroll
                    for (int jn = 0; jn < 32; ++jn) sts32(sb + OFF_TAB + (jn * 4 + tw) * 4, pack2(acc[jn * 4], acc[jn * 4 + 1]));
                }
                bar_sync(1, 128);
                const int vec = 2 + p, blk = p * 4 + j;
                const uint32_t val = lds32(sb + OFF_TAB + tw * 4);
                if (vec == 2 || vec == 5) st_pkt(g_mod + (8 + blk) * 128 + tw, val, ep);
                else {
                    const float one = vec == 4 ? 1.f : 0.f;
                    g_par2[((blk & 3) * 16 + (tw >> 3)) * 16 + (tw & 3) * 4 + (vec - 3) * 2 + ((tw >> 2) & 1)] =
                        pack2(0.5f * bf_round(one + bf_lo(val)), 0.5f * bf_round(one + bf_hi(val)));
                }
                bar_sync(1, 128);
                if (tw == 0) {
                    if (vec == 3 || vec == 4) asm volatile("red.release.gpu.global.add.u32 [%0], 1;" :: "l"(&g_flags[FL_LN2]) : "memory");
                    TL(1 + p);
                }
            }
            if (lane < 2) mbar_arrive_cta(BAR_ONE(sb, EV_P0), lane);
        }
        r = Ring{64 % NSLOT, (64 / NSLOT) & 1};
        mbar_wait(BAR_ONE(sb, EV_P0), 0);
        mbar_wait(BAR_FULL(sb, r.slot), r.par);
        uint32_t hp[32] = {};
        passes128<4, false>(hp, sb, wg, tw, r, stg);
        put_h(hp, sb, wg, stg);
      } else {
        float xs[64];
        uint32_t xp[32];
        {
            sts128(sb + tid * 16, pack2(silu_(bf_lo(cw[0])), silu_(bf_lo(cw[1]))), pack2(silu_(bf_lo(cw[2])), silu_(bf_lo(cw[3]))),
                   pack2(silu_(bf_lo(cw[4])), silu_(bf_lo(cw[5]))), pack2(silu_(bf_lo(cw[6])), silu_(bf_lo(cw[7]))));
            cluster_wait();
            ep = __shfl_sync(0xffffffffu, ep, 0) / NCTA + 1;
            load_slab(xp, stg.acquire2(sb, wg));
            unpack_slab(xs, xp);
            if (tid == 0) TL(24);
            if (tid == 128) TL(27);
        }
#pragma unroll 1
        for (int blk = 0; ; ++blk) {
        {
            IDX();
            uint4* const st = (blk ? g_st2 : g_st1 + m * 8 * 512) + wg * 64 + w4 * 16 + g8;
            RowAcc ra;
#pragma unroll
            for (int e = 0; e < 64; ++e) ra.add(e, xs[e]);
            ra.publish(st + j * 512, q4, ep);
            uint32_t t_pub = 0; if (PDLY) asm volatile("mov.u32 %0, %%clock;" : "=r"(t_pub));
            if (tid == 0) TL(blk ? 9 : 26);
            if (tid == 128 && blk) TL(34);
            if (blk) CS(11);
            LnPar lp;
            if (blk == 0) {
            uint4* const mod_out = pt.mail->mod1 + g8 * 512 + (m * 8 + j) * 4 + q4;
            if (wg == 0) {
                uint4 af[8];
#pragma unroll
                for (int i = 0; i < 8; ++i) af[i] = lds128(sb + w4 * 512 + i * 64 + q4 * 16);
                float c[4][4] = {};
#pragma unroll
                for (int i = 0; i < 8; ++i) {
                    if (!(i & 1)) mbar_wait(BAR_ONE(sb, EV_WIN + (i >> 1)), 0);
                    if (i == 6 && tid == 0) TL(25);
#pragma unroll
                    for (int h = 0; h < 2; ++h) {
                        uint32_t b0, b1, b2, b3;
                        ldsm4t(sb + 5 * SLOT + i * 4096 + w4 * 1024 + h * 512 + (lane & 15) * 32 + (lane >> 4) * 16, b0, b1, b2, b3);
                        mma16816(c[2 * h], h ? af[i].z : af[i].x, 0u, h ? af[i].w : af[i].y, 0u, b0, b1);
                        mma16816(c[2 * h + 1], h ? af[i].z : af[i].x, 0u, h ? af[i].w : af[i].y, 0u, b2, b3);
                    }
                }
                if (lane < 4) sts128(sb + OFF_TAB + w4 * 64 + lane * 16, __float_as_uint(c[0][0] + c[2][0]), __float_as_uint(c[0][1] + c[2][1]),
                                     __float_as_uint(c[1][0] + c[3][0]), __float_as_uint(c[1][1] + c[3][1]));
                if (lane < 2) mbar_arrive_cta(BAR_ONE(sb, EV_P0), lane);
                bar_sync(1, 128);
                if (w4 == 0) {
                    float a[4] = {0.f, 0.f, 0.f, 0.f};
#pragma unroll
                    for (int i = 0; i < 4; ++i) {
                        const uint4 t = lds128(sb + OFF_TAB + i * 64 + q4 * 16);
                        a[0] += __uint_as_float(t.x); a[1] += __uint_as_float(t.y); a[2] += __uint_as_float(t.z); a[3] += __uint_as_float(t.w);
                    }
                    const float add = m >= 8 ? 1.f : 0.f;
                    st_pkt16(mod_out, pack2(bf_round(a[0]) + add, bf_round(a[1]) + add), pack2(bf_round(a[2]) + add, bf_round(a[3]) + add), ep, 0);
                    if (tid == 0) TL(3);
                }
            } else if (LWAIT >= 0) mbar_wait(BAR_ONE(sb, EV_WIN + LWAIT), 0);
            } else {
                mbar_wait2(BAR_ONE(sb, EV_LN2), BAR_FULL(sb, 0), 0);
            }
            lp.load(sb, q4);
#pragma unroll
            for (int e = 0; e < 32; ++e) xp[e] = pack2(xs[2 * e], xs[2 * e + 1]);
            if (PDLY && blk) { uint32_t t1; do { asm volatile("mov.u32 %0, %%clock;" : "=r"(t1)); } while (t1 - t_pub < PDLY); }
            if (blk) CS(13);
            const LnRow n = merge_stats(st, q4, ep, sb);
            if (tid == 0) TL(blk ? 49 : 48);
            if (tid == 128) TL(blk ? 45 : 28);
            if (blk) CS(18);
            uint32_t xn[32];
            ln_norm(xn, xs, n);
            if (blk == 0) {
                mbar_wait2(BAR_FULL(sb, 0), BAR_ONE(sb, EV_PAR), 0);
                if (FD0 && wg == 0) { uint32_t t0, t1; asm volatile("mov.u32 %0, %%clock;" : "=r"(t0)); do { asm volatile("mov.u32 %0, %%clock;" : "=r"(t1)); } while (t1 - t0 < FD0); }
                lp.load(sb, q4);
            }
            ln_emit(xn, lp, sb, wg, ix);
            if (tid == 0) { TL(blk ? 36 : 8); TC(blk ? 109 : 103); }
            if (tid == 128) TL(blk ? 43 : 22);
            if (blk) CS(21);
        }
        uint32_t hp[32];
        if (blk == 0) {
        {
            float big[128], sml[64];
            step32<true, true>(big, sml, sb, wg, r.slot, 0);
            TS(0, 0);
            Pipe pp(sb, tw, r.slot);
            r.next();
#pragma unroll 1
            for (int it = 1; it < 32 - LAGQ; ++it) {
                pp.acquire<true>(sb, wg ? 0 : AF_REL, r);
                step32<true, false>(big, sml, sb, wg, r.slot, it < 4 ? it : -1);
                pp.issued(r.slot);
                TS(it, 0);
                r.next();
            }
            auto half = [&](uint32_t slot, bool rest) {
                const uint32_t st = d16(sb) + slot * (SLOT >> 4);
#pragma unroll
                for (int k = 0; k < 2; ++k) {
                    const uint64_t da = mk_desc(st + wg * 256, k * 32, 16, 512, 2);
                    if (rest) wgmma_n256(big, da, mk_desc(st, 8192 + k * 2048, 4096, 1024, 1)); else wgmma_n128(sml, da, mk_desc(st, 24576 + k * 2048, 4096, 1024, 1));
                }
            };
            auto rest = [&](bool each) {
                wg_fence();
#pragma unroll
                for (int it = 32 - LAGQ; it < 32; ++it) { if (each && it > 32 - LAGQ) wg_fence(); half(it % NSLOT, true); if (each || it == 31) wg_commit(); }
            };
            stg.acquire2(sb, wg); mbar_wait2(BAR_SREADY(sb, 2), BAR_SREADY(sb, 3), 1);
#pragma unroll 1
            for (int it = 32 - LAGQ; it < 32; ++it) {
                pp.acquire<true>(sb, wg ? 0 : AF_REL, r);
                wg_fence(); half(r.slot, false); wg_commit();
                pp.issued(NSLOT);
                TS(it, 0);
                r.next();
            }
            if (wg) { rest(false); wg_wait<1>(); } else wg_wait<0>();
            CS(8);
            IDX();
            uint32_t k0[8], k1[8], k2[8], v0[8], v1[8], v2[8];
            const uint32_t nxt = warp + ((warp & 1) ? 3 : 1), mine = sb + OFF_STG + wg * 16384 + w4 * 2048;
            auto tails = [&](const float* kv, uint32_t (&kt)[8], uint32_t (&vt)[8]) {
#pragma unroll
                for (int t = 0; t < 8; ++t) { kt[t] = pack2(kv[4 * t + 2], kv[4 * t + 3]); vt[t] = pack2(kv[32 + 4 * t + 2], kv[32 + 4 * t + 3]); }
            };
            auto post = [&](int pn, uint32_t (&kt)[8], uint32_t (&vt)[8]) {
                uint4* dst = g_halo + (m * 8 + j) * 512 + (w4 >> 1) * 256 + pn * 128 + lane;
#pragma unroll
                for (int h = 0; h < 2; ++h) { if (!kt[4 * h]) kt[4 * h] = 0x8000u; if (!vt[4 * h]) vt[4 * h] = 0x8000u; }
#pragma unroll
                for (int h = 0; h < 2; ++h) { st_pkt16(dst + h * 32, kt[4 * h], kt[4 * h + 1], kt[4 * h + 2], kt[4 * h + 3]); st_pkt16(dst + 64 + h * 32, vt[4 * h], vt[4 * h + 1], vt[4 * h + 2], vt[4 * h + 3]); }
            };
            auto prepare = [&](int pn, const float* kv) {
                tails(kv, k2, v2);
                if (nxt < 8) {
                    const uint32_t dst = sb + OFF_STG + (nxt >> 2) * 16384 + (nxt & 3) * 2048 + pn * 8192 + lane * 16;
#pragma unroll
                    for (int h = 0; h < 2; ++h) { stsm4(dst + h * 512, k2[4 * h], k2[4 * h + 1], k2[4 * h + 2], k2[4 * h + 3]); stsm4(dst + 1024 + h * 512, v2[4 * h], v2[4 * h + 1], v2[4 * h + 2], v2[4 * h + 3]); }
                    if (pn == 0) bar_arrive(NB_TAIL + nxt, 64);
                    else { __syncwarp(); if (lane == 0) mbar_arrive(BAR_ONE(sb, EV_TAIL + nxt)); }
                } else if (pn == 0 && m < 15) post(0, k2, v2);
#pragma unroll
                for (int t = 0; t < 8; ++t) { k1[t] = pack2(kv[4 * t], kv[4 * t + 1]); v1[t] = movm(pack2(kv[32 + 4 * t], kv[32 + 4 * t + 1])); v2[t] = movm(v2[t]); }
                if (pn == 0) { CS(2); if (wg == 0) { rest(true); wg_wait<3>(); pp.rel(28 % NSLOT); wg_wait<2>(); pp.rel(29 % NSLOT); wg_wait<1>(); pp.rel(30 % NSLOT); } bar_sync(NB_TAIL + warp, 64); CS(4); }
                else mbar_wait(BAR_ONE(sb, EV_TAIL + __shfl_sync(0xffffffffu, warp, 0)), 0);
#pragma unroll
                for (int h = 0; h < 2; ++h) {
                    ldsm4(mine + pn * 8192 + lane * 16 + h * 512, k0[4 * h], k0[4 * h + 1], k0[4 * h + 2], k0[4 * h + 3]);
                    ldsm4t(mine + pn * 8192 + lane * 16 + 1024 + h * 512, v0[4 * h], v0[4 * h + 1], v0[4 * h + 2], v0[4 * h + 3]);
                }
            };
#pragma unroll
            for (int i = 0; i < 64; ++i) asm volatile("" : "+f"(sml[i]) :: "memory");
            prepare(0, sml);
            static_assert(LAGQ == 4, "");
            wg_wait<0>();
            if (wg) { pp.rel(28 % NSLOT); pp.rel(29 % NSLOT); pp.rel(30 % NSLOT); }
            pp.rel(31 % NSLOT);
            TS(31, 1);
            if (tid == 0) { TL(4); TC(104); }
            if (tid == 128) TL(50);
            CS(1);
#pragma unroll
            for (int i = 0; i < 128; ++i) asm volatile("" : "+f"(big[i]) :: "memory");
            if (nxt >= 8 && m < 15) { uint32_t kt[8], vt[8]; tails(big, kt, vt); post(1, kt, vt); }
            const bool lo0 = q4 * 2 > g8, lo1 = q4 * 2 + 1 > g8;
            const bool nopast = m == 0 && (warp & 5) == 0;
            const uint32_t lomask = (lo0 ? 0xFFFFu : 0u) | (lo1 ? 0xFFFF0000u : 0u);
            const uint32_t orow = mine + (lane & 7) * 128 + (((lane >> 3) ^ (lane & 7)) << 4);
            const float sl2 = 0.17677669529663687f * 1.4426950408889634f;
#pragma unroll
            for (int pn = 0; pn < 2; ++pn) {
                float e0[4], e1[4], mx[4], sum[4];
#pragma unroll
                for (int hh = 0; hh < 2; ++hh) {
                    uint32_t qf[8];
#pragma unroll
                    for (int i = 0; i < 8; ++i) qf[i] = pack2(big[64 + 32 * pn + 16 * hh + 2 * i], big[64 + 32 * pn + 16 * hh + 2 * i + 1]);
                    float s[3][4];
#pragma unroll
                    for (int t = 0; t < 3; ++t) {
                        const uint32_t* k = (t == 0 ? k0 : t == 1 ? k1 : k2) + 4 * hh;
                        s[t][0] = s[t][1] = s[t][2] = s[t][3] = 0.f;
                        mma16816(s[t], qf[0], qf[1], qf[2], qf[3], k[0], k[1]);
                        mma16816(s[t], qf[4], qf[5], qf[6], qf[7], k[2], k[3]);
                    }
#pragma unroll
                    for (int hf = 0; hf < 2; ++hf) {
                        const int u = hh * 2 + hf;
                        e0[u] = lo0 ? ((hf == 0 && nopast) ? -INFINITY : s[hf][hf * 2]) : s[hf + 1][hf * 2];
                        e1[u] = lo1 ? ((hf == 0 && nopast) ? -INFINITY : s[hf][hf * 2 + 1]) : s[hf + 1][hf * 2 + 1];
                        mx[u] = fmaxf(e0[u], e1[u]);
                    }
                }
#pragma unroll
                for (int o = 1; o < 4; o <<= 1)
#pragma unroll
                    for (int u = 0; u < 4; ++u) mx[u] = fmaxf(mx[u], __shfl_xor_sync(0xffffffffu, mx[u], o));
#pragma unroll
                for (int u = 0; u < 4; ++u) {
                    const float c = -mx[u] * sl2;
                    e0[u] = ex2(fmaf(e0[u], sl2, c)); e1[u] = ex2(fmaf(e1[u], sl2, c));
                    sum[u] = e0[u] + e1[u];
                }
#pragma unroll
                for (int o = 1; o < 4; o <<= 1)
#pragma unroll
                    for (int u = 0; u < 4; ++u) sum[u] += __shfl_xor_sync(0xffffffffu, sum[u], o);
#pragma unroll
                for (int u = 0; u < 4; ++u) {
                    const int h = u >> 1;
                    const float inv = rcp(sum[u]);
                    const uint32_t p = pack2(e0[u] * inv, e1[u] * inv);
                    const uint32_t* va = ((u & 1) ? v1 : v0) + 4 * h;
                    const uint32_t* vb = ((u & 1) ? v2 : v1) + 4 * h;
                    float o[2][4] = {};
#pragma unroll
                    for (int d = 0; d < 2; ++d) mma16816(o[d], va[2 * d], va[2 * d + 1], vb[2 * d], vb[2 * d + 1], p & lomask, p & ~lomask);
                    stsm4t((orow ^ ((u >> 1) << 6)) + pn * 8192 + (u & 1) * 1024, pack2(o[0][0], o[0][1]), pack2(o[0][2], o[0][3]), pack2(o[1][0], o[1][1]), pack2(o[1][2], o[1][3]));
                }
                fence_async_smem();
                __syncwarp();
                if (lane == 0) mbar_arrive(BAR_SFULL(sb, wg * 2 + pn));
                if (pn == 0) { CS(5); block_end(sb, 0); prepare(1, big); CS(3); }
            }
            CS(6);
            if (tid == 32) TL(41);
            mbar_wait2(BAR_FULL(sb, 32 % NSLOT), BAR_FULL(sb, 33 % NSLOT), (32 / NSLOT) & 1);
            load_slab(xp, sb + (32 % NSLOT + wg) * SLOT);
#pragma unroll
            for (int e = 0; e < 32; ++e) hp[e] = __float_as_uint(big[e]);
            bar_sync(1 + wg, 128);
            if (tid == 0) { TL(6); TC(106); }
            if (tid == 128) TL(44);
            CS(7);
        }
        } else {
        {
            float ag[88], au[88];
            mainloop32<true, LAG>(ag, au, sb, wg, tw, r, EV_LAG1, 48, [](int) {}, [&] {
                Ring q = r; if (!wg) q.next();
                mbar_wait(BAR_EMPTY(sb, q.slot), q.par ^ 1);
                mbar_wait(BAR_FULL(sb, r.slot), r.par);
            });
            if (tid == 0) { TL(10); TC(110); }
            if (tid == 128) TL(51);
            CS(22);
            {
                IDX();
                uint32_t h3[12];
                glu(h3, [&](int i) { return ag[64 + i]; }, [&](int i) { return au[64 + i]; });
#pragma unroll
                for (int k = 0; k < 3; ++k) stsm4(sb + (wg ? P3_SLOT1 : P3_SLOT0) * SLOT + 24576 + (pan_addr ^ (k << 5)), h3[4 * k], h3[4 * k + 1], h3[4 * k + 2], h3[4 * k + 3]);
            }
            glu(hp, [&](int i) { return ag[i]; }, [&](int i) { return au[i]; });
            if (tid == 0) { TL(11); TC(111); }
            if (tid == 128) TL(52);
            CS(23);
        }
        passes128<2, true>(hp, sb, wg, tw, r, stg);
        if (tid == 0) { TL(12); TC(112); }
        }
        {
            float acc[64], gf[32];
            mainloop64(acc, blk == 0, sb, wg, tw, r, [&] { put_h(hp, sb, wg, stg); }, [&] {
                mbar_wait(BAR_ONE(sb, EV_GA + blk), 0);
                unpack_slab(xs, xp);
                uint32_t gt[16];
#pragma unroll
                for (int cg = 0; cg < 16; ++cg) gt[cg] = lds32(sb + OFF_TAB + blk * 256 + cg * 16 + (tw & 3) * 4);
#pragma unroll
                for (int i = 0; i < 16; ++i) unpack2(gt[i], gf[2 * i], gf[2 * i + 1]);
            }, [&] { stg.acquire2(sb, wg); });
            if (tid == 0) { TL(blk ? 13 : 7); TC(blk ? 113 : 107); }
            if (tid == 128) TL(blk ? 57 : 42);
            CS(blk ? 30 : 10);
#pragma unroll
            for (int e = 0; e < 64; ++e) xs[e] = fmaf(gf[(e >> 2) * 2 + (e & 1)], acc[e], xs[e]);
        }
        if (blk) break;
        }
        {
            IDX();
#pragma unroll
            for (int p = 0; p < 2; ++p) {
                store_slab(xs, sb + OFF_STG + wg * 16384, 8192, pan_addr, 4 * p, 4 * p + 4);
                stg.publish(sb, wg, lane);
            }
            cluster_arrive();
            if (tid == 0) TL(14);
            CS(31);
        }
      }
    } else {
        if (warp == 8 && !aux && elect_one()) {
#pragma unroll
            for (int i = 0; i < 4; ++i) mbar_init(BAR_SREADY(sb, i), 1);
#pragma unroll
            for (int i = 0; i < 4; ++i) mbar_init(BAR_ONE(sb, EV_WIN + i), 1);
#pragma unroll
            for (int i = 0; i < 4; ++i) {
                mbar_expect_tx(BAR_SREADY(sb, i), 8192);
                tma_load3(sb + OFF_STG + i * 8192, &mp.x, j * 128 + (i & 1) * 64, m * 64 + (i >> 1) * 32, BAR_SREADY(sb, i));
            }
#pragma unroll 1
            for (int i = 0; i < 4; ++i) {
                mbar_expect_tx(BAR_ONE(sb, EV_WIN + i), 8192);
                tma_load(sb + 5 * SLOT + i * 8192, &mp.wm8, 2 * i * 6144 + (m * 8 + j) * 16, 0, BAR_ONE(sb, EV_WIN + i));
                tma_load(sb + 5 * SLOT + i * 8192 + 4096, &mp.wm8, (2 * i + 1) * 6144 + (m * 8 + j) * 16, 0, BAR_ONE(sb, EV_WIN + i));
            }
        }
        __syncwarp();
        asm volatile("setmaxnreg.dec.sync.aligned.u32 56;");
        if (elect_one()) {
            if (warp == 8) {
                prefetch_map(&mp.wqkv); prefetch_map(&mp.wmod);
            } else if (warp < 11) {
                mbar_init(BAR_EMPTY(sb, NSLOT), 1);
#pragma unroll
                for (int i = 0; i < 2; ++i) { mbar_init(BAR_SFULL(sb, (warp - 9) * 2 + i), 4); if (aux) mbar_init(BAR_SREADY(sb, (warp - 9) * 2 + i), 1); }
#pragma unroll
                for (int i = 0; i < 3; ++i) {
                    mbar_init(BAR_EMPTY(sb, (warp - 9) * 3 + i), 4);
                    mbar_init(BAR_FULL(sb, (warp - 9) * 3 + i), 1); mbar_init(BAR_FULL(sb, (warp - 9) * 3 + i) + AF_REL, 1);
                }
            } else {
#pragma unroll
                for (int i = EV_P0; i < EV_COUNT; ++i) mbar_init(BAR_ONE(sb, i), i == EV_P0 ? 8 : 1);
            }
            asm volatile("fence.mbarrier_init.release.cluster;" ::: "memory");
        }
        __syncwarp();
        cluster_arrive();
        ep = 0;
        if (warp != 8 || aux) ep = flag_get(g_flags + FL_DONE);
        cluster_wait();
        ep = __shfl_sync(0xffffffffu, ep, 0) / NCTA + 1;
        if (warp == 8) {
            const bool el = elect_one();
            Ring r{0, 1};
            if (aux) {
                {
                    uint32_t n = 0;
                    while (!__all_sync(0xffffffffu, ld_pkt16(pt.mail->mod1 + 256).z == ep)) { SPIN_GUARD(n); __nanosleep(200); }
                }
#pragma unroll 1
                for (int it = 0; it < 64; ++it) {
                    const int col = 2048 + (it >> 4) * 1024 + j * 256;
                    mbar_wait(BAR_EMPTY(sb, r.slot), r.par);
                    const uint32_t st = sb + r.slot * SLOT, fb = BAR_FULL(sb, r.slot);
                    if (el) {
                        mbar_expect_tx(fb, 32768);
#pragma unroll
                        for (int b = 0; b < 4; ++b) tma_load_ef(st + b * 8192, &mp.wmod, col + b * 64, (it & 15) * 64, fb);
                    }
                    r.next();
                }
                mbar_wait(BAR_ONE(sb, EV_P0), 0);
                const CUtensorMap* wm = rank ? &mp.wu : &mp.wg;
#pragma unroll 1
                for (int g = 0; g < 128; ++g) {
                    const int mx = (j >> 1) * 8 + (g >> 5) * 2 + rank, k0 = ((g & 14) << 6) + ((g & 16) << 2) + ((g & 1) << 5);
                    if (!(g & 15) && g <= 32) mbar_wait(BAR_ONE(sb, EV_H0 + (g >> 4)), 0);
                    mbar_wait(BAR_EMPTY(sb, r.slot), r.par);
                    const uint32_t st = sb + r.slot * SLOT, fb = BAR_FULL(sb, r.slot);
                    if (el) {
                        mbar_expect_tx(fb, 24576);
                        tma_load_mc(st + 8192 + rank * 4096, wm, HC3, k0, fb);
                        tma_load_mc(st + 16384 + rank * 4096, wm, HC3 + 64, k0, fb);
                        tma_load(st, &mp.h2l, k0, mx * 128, fb);
                    }
                    r.next();
                }
            } else {
#pragma unroll 1
                for (int it = 0; it < 32; ++it) {
                    const int cb = j * 128 + rank * 64, k0 = kof(it, 2, j);
                    if (it == BW0) mbar_wait(BAR_ONE(sb, BWEV), 0);
                    if (it == BW1) mbar_wait(BAR_ONE(sb, EV_PAR), 0);
                    if (it == 5) mbar_wait(BAR_ONE(sb, EV_P0), 0);
                    if (it == AG0) mbar_wait(BAR_ONE(sb, (AGW & 1) ? EV_AGO : EV_FGO), 0);
                    mbar_wait(BAR_EMPTY(sb, r.slot), r.par);
                    const uint32_t st = sb + r.slot * SLOT, fb = BAR_FULL(sb, r.slot);
                    if (el) {
                        mbar_expect_tx(fb, it < 4 ? 24576 : 28672);
                        tma_load_mc(st + 24576 - rank * 16384, &mp.wqkv, 1024 + cb, k0, fb);
                        tma_load_mc(st + 28672 - rank * 16384, &mp.wqkv, 2048 + cb, k0, fb);
                        tma_load_mc(st + 16384 + rank * 4096, &mp.wqkv, cb, k0, fb);
                        if (it < 4) mbar_arrive(fb + AF_REL);
                        if (it == PFWO + (m >> 1)) { tma_prefetch(&mp.wo, j * 128, m * 64); tma_prefetch(&mp.wo, j * 128 + 64, m * 64); }
                        if (it >= PFG && it < PFG + PFN && (it & 7) == grp) {
                            const int kp = kof(it - PFG + PFO, 2, j);
                            tma_prefetch(rank ? &mp.wu : &mp.wg, hcol(0, j), kp); tma_prefetch(rank ? &mp.wu : &mp.wg, hcol(0, j) + 64, kp);
                            asm volatile("cp.async.bulk.prefetch.tensor.3d.L2.global [%0, {%1, %2, %3}];" :: "l"(rank ? &mp.wu3 : &mp.wg3), "r"(0), "r"(j), "r"(kp) : "memory");
                        }
                    }
                    r.next();
                }
                if (el) mbar_arrive(BAR_ONE(sb, EV_KV));
#pragma unroll 1
                for (int it = 0; it < 16; ++it) {
                    const int k0 = kof(it, 1, j);
                    if (it == AG1) mbar_wait(BAR_ONE(sb, (AGW & 2) ? EV_AGO1 : EV_FGO1), 0);
                    mbar_wait(BAR_EMPTY(sb, r.slot), r.par);
                    const uint32_t st = sb + r.slot * SLOT, fb = BAR_FULL(sb, r.slot);
                    if (el) {
                        mbar_expect_tx(fb, it < 2 ? 32768 : 24576);
                        tma_load_mc(st + 16384 + rank * 8192, &mp.wo, j * 128 + rank * 64, k0, fb);
                        if (it < 2) {
                            tma_load3(st, &mp.x, j * 128, m * 64 + it * 32, fb); tma_load3(st + 8192, &mp.x, j * 128 + 64, m * 64 + it * 32, fb);
                            mbar_arrive(fb + AF_REL);
                        }
                        if (it == 6) { prefetch_map(rank ? &mp.wu : &mp.wg); prefetch_map(rank ? &mp.wu3 : &mp.wg3); }
                    }
                    r.next();
                }
                const CUtensorMap* wm = rank ? &mp.wu : &mp.wg;
#pragma unroll 1
                for (int g = 0; g < 96; ++g) {
                    if (g == AG2) mbar_wait(BAR_ONE(sb, (AGW & 4) ? EV_AGO2 : EV_FGO2), 0);
                    const int p = g >> 5, cb = hcol(p, j), k0 = p == 0 ? kof(g, 2, j) : (g & 31) * 32;
                    mbar_wait(BAR_EMPTY(sb, r.slot), r.par);
                    const uint32_t st = sb + r.slot * SLOT, fb = BAR_FULL(sb, r.slot);
                    if (el) {
                        mbar_expect_tx(fb, (g < 4 || p > 0) ? 24576 : 28672);
                        tma_load_mc(st + 8192 + rank * 4096, wm, cb, k0, fb);
                        tma_load_mc(st + 16384 + rank * 4096, wm, cb + 64, k0, fb);
                        if (p == 0) tma_load3_mc(st + 24576 + rank * 4096, rank ? &mp.wu3 : &mp.wg3, j, k0, fb);
                        else tma_load(st, &mp.h2l, k0, m * 128, fb);
                        if (g < 4) mbar_arrive(fb + AF_REL);
                        if ((g & 7) == grp && g + PFC >= 96) tma_prefetch(&mp.wd, j * 128 + rank * 64, (g + PFC - 96) * 64);
                        if (g == 60) { prefetch_map(&mp.wd); prefetch_map(&mp.hb); }
                    }
                    r.next();
                }
#pragma unroll 1
                for (int g = 0; g < 56; ++g) {
                    if (g == 0 || (g & 15) == 6 && g > 6) mbar_wait(BAR_ONE(sb, EV_H0 + (g >> 4)), 0);
                    const int k0 = g * 64;
                    mbar_wait(BAR_EMPTY(sb, r.slot), r.par);
                    const uint32_t st = sb + r.slot * SLOT, fb = BAR_FULL(sb, r.slot);
                    if (el) {
                        mbar_expect_tx(fb, 32768);
                        tma_load_mc(st + 16384 + rank * 8192, &mp.wd, j * 128 + rank * 64, k0, fb);
                        tma_load(st, &mp.hb, k0, m * 128, fb); tma_load(st + 8192, &mp.hb, k0, m * 128 + 64, fb);
                        if ((g & 7) == grp && g + PFC < 56) tma_prefetch(&mp.wd, j * 128 + rank * 64, k0 + PFC * 64);
                    }
                    r.next();
                }
            }
        } else if (aux) {
            if (warp < 11) {
                const uint32_t w = warp - 9;
                const bool el = elect_one();
#pragma unroll 1
                for (int p = 0; p < 4; ++p) {
                    const int mx = (j >> 1) * 8 + p * 2 + rank;
                    if (el) { mbar_arrive(BAR_SREADY(sb, w * 2)); mbar_arrive(BAR_SREADY(sb, w * 2 + 1)); }
                    mbar_wait2(BAR_SFULL(sb, w * 2), BAR_SFULL(sb, w * 2 + 1), p & 1);
                    if (p < 3) pause(w ? HD1 : HD0);
                    if (el) tma_store(&mp.hb, HC3, mx * 128 + w * 64, sb + OFF_STG + w * 16384);
                    if (p < 3) pause(HP);
                    if (el) {
                        tma_store(&mp.hb, HC3 + 64, mx * 128 + w * 64, sb + OFF_STG + w * 16384 + 8192);
                        bulk_commit(); bulk_wait_fence(); flag_set(g_flags + FL_AUX + mx * 2 + w, ep * 8 + ST_H + 3);
                    }
                }
            } else {
                mbar_wait(BAR_ONE(sb, EV_P0), 0);
#pragma unroll 1
                for (int i = 0; i < 5; ++i) {
                    const uint32_t* f = g_flags + FL_PROG + fidx((j >> 1) * 8 + (i ? i - 1 : 0) * 2 + rank, lane >> 4, lane & (i ? 15 : 14));
                    uint32_t n = 0;
                    while (!__all_sync(0xffffffffu, (int32_t)(flag_get(f) - (ep * 8 + ST_H2)) >= 0)) { SPIN_GUARD(n); __nanosleep(200); }
                    if (i < 2) pause(AUXD);
                    if (lane == 0 && (i < 2 || i == 4)) mbar_arrive(BAR_ONE(sb, EV_H0 + (i < 2 ? i : 2)));
                }
            }
        } else if (warp == 11) {
            const bool el = elect_one();
            const int row0 = m * 128;
            const uint32_t* const fl = g_flags + FL_PROG + fidx(m, lane >> 4, kof(lane & 15, 1, j) >> 6);
            if (el) { prefetch_map(&mp.h1h); prefetch_map(&mp.h2h); prefetch_map(&mp.h2l); }
            auto gate = [&](int vec, int ev) {
                uint4 v; uint32_t n = 0;
                while (true) {
                    v = ld_pkt2(g_mod + vec * 512 + j * 64 + lane * 2);
                    if (__all_sync(0xffffffffu, v.y == ep && v.w == ep)) break;
                    SPIN_GUARD(n); __nanosleep(300);
                }
                asm volatile("st.shared.v2.u32 [%0], {%1, %2};" :: "r"(sb + OFF_TAB + (ev - EV_GA) * 256 + lane * 8), "r"(v.x), "r"(v.z) : "memory");
                __syncwarp();
                if (lane == 0) mbar_arrive(BAR_ONE(sb, ev));
            };
            {
                const uint4* pk = pt.mail->mod1 + grp * 512 + j * 32 + lane;
                uint4 a, b; uint32_t n = 0;
                mbar_wait(BAR_ONE(sb, EV_WIN3), 0);
                while (true) {
                    a = ld_pkt16(pk); b = ld_pkt16(pk + 256);
                    if (__all_sync(0xffffffffu, a.z == ep && b.z == ep)) break;
                    SPIN_GUARD(n);
                }
                sts128(sb + OFF_PAR + lane * 16, a.x, a.y, b.x, b.y);
                __syncwarp();
                if (lane == 0) { mbar_arrive(BAR_ONE(sb, EV_PAR)); TL(46); }
            }
            mbar_wait(BAR_ONE(sb, EV_P0), 0);
            Ring r{0, 1};
#pragma unroll 1
            for (int ph = 0; ph < 3; ++ph) {
                const int sh = ph == 1 ? 1 : 2, nst = 8 << sh;
                const uint32_t half = 16384 >> sh, target = ep * 8 + ST_H1 + ph;
                const CUtensorMap* tm = ph == 0 ? &mp.h1h : ph == 1 ? &mp.o : &mp.h2h;
                if (ph == 1) {
                    gate(2, EV_GA);
                    mbar_wait(BAR_SREADY(sb, 1), 1);
#pragma unroll 1
                    for (int i = 0; i < 2; ++i)
                        fetch_halo<1>(g_halo + ((m - 1) * 8 + j) * 512 + i * 256 + 128 + lane, m == 0, sb + OFF_STG + 8192 + i * 4096 + lane * 16,
                                      [&] { __syncwarp(); if (el) mbar_arrive(BAR_ONE(sb, EV_TAIL + 2 * i)); });
                    CS(32);
                }
                if (ph == 2) {
                    uint32_t n = 0;
                    while ((int32_t)(flag_get(g_flags + FL_LN2) - ep * 8) < 0) { SPIN_GUARD(n); __nanosleep(200); }
                    const uint4 v = __ldcg((const uint4*)(g_par2 + j * 128) + lane);
                    sts128(sb + OFF_PAR + lane * 16, v.x, v.y, v.z, v.w);
                    __syncwarp();
                    if (lane == 0) mbar_arrive(BAR_ONE(sb, EV_LN2));
                }
                const uint32_t lw = ~lane & 1, lt = lane >> 1, ls = (r.slot + lt) % NSLOT, lk = kof(lt, sh, j), lb = BAR_FULL(sb, ls) + (lw ? 0 : AF_REL);
                const uint32_t* const lf = g_flags + FL_PROG + fidx(m, lw, lk >> 6);
                int fr = 1 << sh;
                uint32_t todo = 0x3ffffu >> (2 * fr) << (2 * fr), have = ~todo, n = 0, v = 0;
                r.skip(fr);
#pragma unroll 1
                for (; fr < NSLOT; ++fr) { mbar_wait(BAR_EMPTY(sb, r.slot), r.par); r.next(); }
                if (ph == XST - 1) CS(33);
                v = flag_get(lf);
                do {
                    while (ph == 2 && fr < FRCAP && mbar_test(BAR_EMPTY(sb, r.slot), r.par)) { ++fr; r.next(); }
                    SPIN_GUARD(n);
                    const bool ok = (int32_t)(v - target) >= 0;
                    v = flag_get(lf);
                    have |= __ballot_sync(0xffffffffu, ok);
                    const uint32_t go = have & todo & ((1u << (2 * fr)) - 1);
                    if ((go >> lane) & 1) {
                        if (!lw) mbar_expect_tx(lb, half);
                        tma_load(sb + ls * SLOT + lw * half, tm, lk, row0 + lw * 64, lb);
                    }
                    __syncwarp();
                    if (lane < 2 && (todo & (0x555u << lane)) && !(todo & ~go & (0x555u << lane))) mbar_arrive(BAR_ONE(sb, (lane ? EV_FGO : EV_AGO) + ph));
                    if (ph == XST - 1) { if (go & (1u << (2 << sh))) CS(34); if (go & (2u << (2 << sh))) CS(35); if (todo & 0x555u) CS(36); if (todo & 0xaaau) CS(37); }
                    todo &= ~go;
                } while (~have);
                if (ph == XST - 1) CS(38);
                int k = kof(fr, sh, j);
#pragma unroll 1
                for (; fr < nst; ++fr) {
                    if (fr == 9 || fr == 18) {
                        const uint32_t skip = fr == 9 << (sh - 1) ? 0 : ~0x01fc01fcu;
                        while (~(__ballot_sync(0xffffffffu, (int32_t)(flag_get(fl) - target) >= 0) | skip)) SPIN_GUARD(n);
                    }
                    const uint32_t st = sb + r.slot * SLOT, fb = BAR_FULL(sb, r.slot);
                    mbar_wait(BAR_EMPTY(sb, r.slot), r.par);
                    if (el) {
                        tma_load(st + half, tm, k, row0 + 64, fb);
                        mbar_expect_tx(fb + AF_REL, half);
                        tma_load(st, tm, k, row0, fb + AF_REL);
                    }
                    if (ph == XST - 1 && fr == 9) CS(39);
                    r.next();
                    k = kof(fr + 1, sh, j);
                }
            }
#pragma unroll 1
            for (int p = 0; p < 4; ++p) {
                const uint32_t* f = p < 3 ? fl : g_flags + FL_AUX + m * 2 + (lane & 1);
                uint32_t n = 0;
                while (!__all_sync(0xffffffffu, (int32_t)(flag_get(f) - (ep * 8 + ST_H + p)) >= 0)) { SPIN_GUARD(n); __nanosleep(300); }
                if (el) mbar_arrive(BAR_ONE(sb, EV_H0 + p));
                if (p == 0) gate(5, EV_GB);
            }
        } else {
            const uint32_t w = warp - 9;
            const int row0 = m * 128 + w * 64;
            const uint32_t stg = sb + OFF_STG + w * 16384;
            uint32_t* const fl = g_flags + FL_PROG + fidx(m, w, 2 * j);
            uint32_t b = 0, par = 0;
            const bool el = elect_one();
            auto store = [&](const CUtensorMap* tm, int col, bool nat = false) {
                mbar_wait(BAR_SFULL(sb, w * 2 + b), (par >> b) & 1);
                par ^= 1u << b;
                if (el) {
                    if (nat) tma_store3(tm, col, row0 >> 1, 0, stg + b * 8192); else tma_store(tm, col, row0, stg + b * 8192);
                    bulk_commit();
                }
                b ^= 1;
            };
            auto send2 = [&](const CUtensorMap* tm, const uint32_t* buf, int step) {
                const uint32_t* const q = buf + (size_t)((row0 + lane) * (D_ / 2) + j * 64 + 31);
                store(tm, j * 128);
                if (step == XST) CS(33);
                uint32_t z = landed(el, q, D_ / 2, pt.zero);
                if (el) flag_set(fl, ep * 8 + step + z);
                if (step == XST) CS(34);
                if (step != ST_O) { mbar_wait(BAR_ONE(sb, EV_FGO + step - ST_H1), 0); pause(step == ST_H1 ? (w ? P1H : P1H + 1000) : w ? P2L : P2F); }
                store(tm, j * 128 + 64);
                if (step == XST) CS(35);
                z = landed(el, q + 32, D_ / 2, pt.zero);
                if (el) flag_set(fl + 1, ep * 8 + step + z);
                if (step == XST) CS(36);
            };
            auto free2 = [&]() { if (el) { mbar_arrive(BAR_SREADY(sb, w * 2)); mbar_arrive(BAR_SREADY(sb, w * 2 + 1)); } };
            if (el) { prefetch_map(&mp.h1s); prefetch_map(&mp.o); prefetch_map(&mp.out); prefetch_map(&mp.wo); }
            send2(&mp.h1s, pt.h1, ST_H1);
            if (w == 0) TL(47);
            free2();
            mbar_wait(BAR_ONE(sb, EV_KV), 0);
            mbar_wait(BAR_SREADY(sb, 0), 1);
            fetch_halo<1>(g_halo + ((m - 1) * 8 + j) * 512 + w * 256 + lane, m == 0, sb + OFF_STG + w * 4096 + lane * 16, [&] { bar_arrive(NB_TAIL + 2 * w, 64); CS(38); });
            send2(&mp.o, pt.o, ST_O);
            if (w == 0) TL(40); else TL(38);
            free2();
            send2(&mp.o, pt.o, ST_H2);
            if (el) { prefetch_map(&mp.hbs); prefetch_map(&mp.hb3); }
            if (w == 0) TL(37);
            free2();
#pragma unroll 1
            for (int p = 0; p < 3; ++p) {
                const int col = hcol(p, j);
                mbar_wait2(BAR_SFULL(sb, w * 2), BAR_SFULL(sb, w * 2 + 1), par & 1);
                par ^= 3;
#pragma unroll 1
                for (int i = 0; i < (p ? 2 : 3) * NSPL; ++i) {
                    pause(i ? HP / NSPL : p == 2 ? (w ? HE1 : HE0) : w ? HD1 : HD0);
                    const int pn = i / NSPL, ro = (i % NSPL) * (64 / NSPL);
                    if (el) {
                        if (pn < 2) tma_store(&mp.hbs, col + pn * 64, row0 + ro, stg + i * (8192 / NSPL));
                        else tma_store3(&mp.hb3, 0, j, row0 + ro, sb + (w ? P3_SLOT1 : P3_SLOT0) * SLOT + 24576 + ro * 128);
                        bulk_commit();
                    }
                }
                if (el) bulk_wait_read();
                free2();
                if (el) { bulk_wait_fence(); flag_set(fl, ep * 8 + ST_H + p); flag_set(fl + 1, ep * 8 + ST_H + p); }
            }
            cluster_arrive_early = true;
            cluster_arrive();
            store(&mp.out, j * 128, true); store(&mp.out, j * 128 + 64, true);
            if (el) bulk_wait_read();
        }
        __syncwarp();
    }
    if (aux || (wg == 2 && !cluster_arrive_early)) cluster_arrive();
    cluster_wait();
    if (KDEBUG == 5) __syncthreads();
    if (tid == 0) {
        TL(15);
        flag_add(pt.mail->flags + FL_DONE);
    }
}

typedef CUresult (*EncodeFn)(CUtensorMap*, CUtensorMapDataType, cuuint32_t, void*, const cuuint64_t*, const cuuint64_t*, const cuuint32_t*,
                             const cuuint32_t*, CUtensorMapInterleave, CUtensorMapSwizzle, CUtensorMapL2promotion, CUtensorMapFloatOOBfill);

void make_map(EncodeFn fn, CUtensorMap* m, const void* ptr, uint64_t rows, uint64_t cols, uint32_t brows, uint32_t bcols) {
    cuuint64_t dims[2] = {cols, rows}, strides[1] = {cols * 2};
    cuuint32_t box[2] = {bcols, brows}, es[2] = {1, 1};
    fn(m, CU_TENSOR_MAP_DATA_TYPE_BFLOAT16, 2, (void*)ptr, dims, strides, box, es, CU_TENSOR_MAP_INTERLEAVE_NONE,
       bcols == 64 ? CU_TENSOR_MAP_SWIZZLE_128B : bcols == 32 ? CU_TENSOR_MAP_SWIZZLE_64B : CU_TENSOR_MAP_SWIZZLE_NONE, CU_TENSOR_MAP_L2_PROMOTION_L2_256B, CU_TENSOR_MAP_FLOAT_OOB_FILL_NONE);
}

void make_map3(EncodeFn fn, CUtensorMap* m, const void* ptr) {
    cuuint64_t dims[3] = {D_, S_ / 2, 2}, strides[2] = {4 * D_, 2 * D_};
    cuuint32_t box[3] = {64, 32, 2}, es[3] = {1, 1, 1};
    fn(m, CU_TENSOR_MAP_DATA_TYPE_BFLOAT16, 3, (void*)ptr, dims, strides, box, es, CU_TENSOR_MAP_INTERLEAVE_NONE,
       CU_TENSOR_MAP_SWIZZLE_128B, CU_TENSOR_MAP_L2_PROMOTION_L2_256B, CU_TENSOR_MAP_FLOAT_OOB_FILL_NONE);
}

void make_map48(EncodeFn fn, CUtensorMap* m, const void* ptr, uint64_t rows, uint32_t brows) {
    cuuint64_t dims[3] = {48, 8, rows}, strides[2] = {96, 2 * F_};
    cuuint32_t box[3] = {64, 1, brows}, es[3] = {1, 1, 1};
    fn(m, CU_TENSOR_MAP_DATA_TYPE_BFLOAT16, 3, (void*)ptr, dims, strides, box, es, CU_TENSOR_MAP_INTERLEAVE_NONE,
       CU_TENSOR_MAP_SWIZZLE_128B, CU_TENSOR_MAP_L2_PROMOTION_L2_256B, CU_TENSOR_MAP_FLOAT_OOB_FILL_NONE);
}

}

extern "C" void kernel_launch(void* const* d_in, const int* in_sizes, int n_in, void* d_out, int out_size) {
    (void)in_sizes; (void)n_in; (void)out_size;
    void* fnp = nullptr;
    cudaDriverEntryPointQueryResult qr;
    cudaGetDriverEntryPoint("cuTensorMapEncodeTiled", &fnp, cudaEnableDefault, &qr);
    EncodeFn fn = (EncodeFn)fnp;
    void *h1, *o, *h2, *hb, *mail;
    cudaGetSymbolAddress(&h1, g_h1);
    cudaGetSymbolAddress(&mail, g_mail);
    cudaGetSymbolAddress(&o, g_o);
    cudaGetSymbolAddress(&hb, g_hb);
    h2 = o;
    Maps mp;
    make_map(fn, &mp.h1h, h1, S_, D_, 64, 32);
    make_map(fn, &mp.h2h, h2, S_, D_, 64, 32);
    make_map(fn, &mp.h1s, h1, S_, D_, 64, 64);
    make_map(fn, &mp.o, o, S_, D_, 64, 64);
    make_map(fn, &mp.h2l, h2, S_, D_, 128, 32);
    make_map(fn, &mp.hb, hb, S_, F_, 64, 64);
    make_map(fn, &mp.wqkv, d_in[1], D_, 3 * D_, 32, 64);
    make_map(fn, &mp.wo, d_in[2], D_, D_, 64, 64);
    make_map(fn, &mp.wg, d_in[4], D_, F_, 32, 64);
    make_map(fn, &mp.wu, d_in[5], D_, F_, 32, 64);
    make_map(fn, &mp.wd, d_in[6], F_, D_, 64, 64);
    make_map(fn, &mp.wmod, d_in[8], D_, 6 * D_, 64, 64);
    make_map(fn, &mp.wm8, d_in[8], D_ / 8, 8 * 6 * D_, 128, 16);
    make_map3(fn, &mp.x, d_in[0]);
    make_map3(fn, &mp.out, d_out);
    make_map48(fn, &mp.wg3, d_in[4], D_, 32);
    make_map48(fn, &mp.wu3, d_in[5], D_, 32);
    make_map48(fn, &mp.hb3, hb, S_, 64 / NSPL);
    make_map(fn, &mp.hbs, hb, S_, F_, 64 / NSPL, 64);
    cudaFuncSetAttribute(fused_block_kernel, cudaFuncAttributeMaxDynamicSharedMemorySize, SMEM_BYTES);
    cudaLaunchConfig_t cfg = {};
    cfg.gridDim = dim3(NCTA); cfg.blockDim = dim3(384); cfg.dynamicSmemBytes = SMEM_BYTES; cfg.stream = cudaStreamPerThread;
    cudaLaunchAttribute at[1];
    at[0].id = cudaLaunchAttributeClusterDimension; at[0].val.clusterDim.x = 2; at[0].val.clusterDim.y = 1; at[0].val.clusterDim.z = 1;
    cfg.attrs = at; cfg.numAttrs = 1;
    const Ptrs pt{(const __nv_bfloat16*)d_in[7], (Mail*)mail, (const uint32_t*)h1, (const uint32_t*)o, 0};
    cudaLaunchKernelEx(&cfg, fused_block_kernel, pt, mp);
}
```

```cpp
#include <cuda_runtime.h>
#include <cuda_bf16.h>
#include <cuda.h>
#include <stdint.h>
#include <stddef.h>

#define LAG 4
#define LAGS 4
#define LAGW 2
#define LAGD 4
#define LAGQ 4
#define PUT1 5
#define PUT0 10
#define PUTD1 6
#define PUTD0 10
#define MIDD 40
#define HD1 3000
#define HD0 1500
#define NSPL 2
#define HE1 2000
#define HE0 HD0
#define HP 2600
#define P1H 3000
#define P2L 2000
#define P2F 3000
#define AUXD 4000
#define PDLY 500
#define FD0 200
#define AG0 6
#define AG1 6
#define AG2 8
#define AGW 2
#define FRCAP 8
#define BW0 0
#define BWEV EV_WIN
#define BW1 3
#define LWAIT 3
#define PFWO 12
#define PFG 8
#define PFN 24
#define PFC 10
#define PFO 0
#define KDEBUG 0
#define CSW 0
#define XST ST_O

namespace {

constexpr int S_ = 2048, D_ = 1024, F_ = 3584;
constexpr int NCTA = 132;
constexpr int NSLOT = 6;
constexpr uint32_t SLOT = 32768;
constexpr uint32_t OFF_STG = NSLOT * SLOT;
constexpr uint32_t OFF_BAR = OFF_STG + 32768;
constexpr uint32_t OFF_PAR = OFF_BAR + 512;
constexpr uint32_t OFF_TAB = OFF_PAR + 768;
constexpr uint32_t OFF_TL = OFF_PAR + 2048;
constexpr uint32_t SMEM_BYTES = OFF_TL + (KDEBUG ? 512 : 0);
constexpr uint32_t P3_SLOT1 = (32 + 16 + 32) % NSLOT, P3_SLOT0 = (P3_SLOT1 + 1) % NSLOT;

constexpr int ST_H1 = 1, ST_O = 2, ST_H2 = 3, ST_H = 4, FL_DONE = 0, FL_LN2 = 1, FL_AUX = 32, FL_PROG = 64;

struct Maps {
    CUtensorMap h1h, h1s, o, h2h, h2l, hb, wqkv, wo, wg, wu, wd, wmod, wm8, x, out, wg3, wu3, hb3, hbs;
};

struct Mail {
    uint32_t flags[16 * 32 + 64];
    uint2 mod[6 * D_ / 2];
    uint4 mod1[8 * 512];
    uint4 st1[128 * 512];
    uint32_t par2[D_];
    uint4 halo[128 * 512];
};
struct Ptrs { const __nv_bfloat16* c; Mail* mail; const uint32_t *h1, *o; uint32_t zero; };

__device__ __align__(128) Mail g_mail;
__device__ __align__(128) __nv_bfloat16 g_h1[S_ * D_];
__device__ __align__(128) __nv_bfloat16 g_o[S_ * D_];
__device__ __align__(128) __nv_bfloat16 g_hb[S_ * F_];
#define TL(i) do {} while (0)
#define TC(i) do {} while (0)
#define TS(g, which) do {} while (0)
#define CS(i) do {} while (0)

__device__ __forceinline__ uint32_t smem_u32(const void* p) { return (uint32_t)__cvta_generic_to_shared(p); }
__device__ __forceinline__ void mbar_init(uint32_t bar, uint32_t cnt) { asm volatile("mbarrier.init.shared::cta.b64 [%0], %1;" :: "r"(bar), "r"(cnt) : "memory"); }
__device__ __forceinline__ void mbar_expect_tx(uint32_t bar, uint32_t bytes) { asm volatile("mbarrier.arrive.expect_tx.shared::cta.b64 _, [%0], %1;" :: "r"(bar), "r"(bytes) : "memory"); }
__device__ __forceinline__ void mbar_arrive(uint32_t bar) { asm volatile("mbarrier.arrive.shared::cta.b64 _, [%0];" :: "r"(bar) : "memory"); }
__device__ __forceinline__ void mbar_arrive_cta(uint32_t bar, uint32_t cta) {
    asm volatile("{\n.reg .b32 r;\nmapa.shared::cluster.u32 r, %0, %1;\nmbarrier.arrive.shared::cluster.b64 _, [r];\n}" :: "r"(bar), "r"(cta) : "memory");
}
__device__ __forceinline__ void mbar_wait(uint32_t bar, uint32_t parity) {
    asm volatile("{\n.reg .pred p;\n.reg .u32 n;\nmov.u32 n, 0;\n"
        "W_LOOP:\nmbarrier.try_wait.parity.shared::cta.b64 p, [%0], %1;\n@p bra W_DONE;\n"
        "add.u32 n, n, 1;\nsetp.lt.u32 p, n, 0x400000;\n@p bra W_LOOP;\ntrap;\nW_DONE:\n}" :: "r"(bar), "r"(parity) : "memory");
}
__device__ __forceinline__ void mbar_wait2(uint32_t b0, uint32_t b1, uint32_t parity) {
    asm volatile("{\n.reg .pred p, q;\n.reg .u32 n;\nmov.u32 n, 0;\n"
        "W_LOOP:\nmbarrier.try_wait.parity.shared::cta.b64 p, [%0], %2;\nmbarrier.try_wait.parity.shared::cta.b64 q, [%1], %2;\nand.pred p, p, q;\n@p bra W_DONE;\n"
        "add.u32 n, n, 1;\nsetp.lt.u32 p, n, 0x400000;\n@p bra W_LOOP;\ntrap;\nW_DONE:\n}" :: "r"(b0), "r"(b1), "r"(parity) : "memory");
}
__device__ __forceinline__ bool mbar_test(uint32_t bar, uint32_t parity) {
    uint32_t r; asm volatile("{\n.reg .pred p;\nmbarrier.test_wait.parity.shared::cta.b64 p, [%1], %2;\nselp.u32 %0, 1, 0, p;\n}" : "=r"(r) : "r"(bar), "r"(parity) : "memory"); return r;
}
__device__ __forceinline__ bool mbar_test2(uint32_t b0, uint32_t b1, uint32_t parity) {
    uint32_t r;
    asm volatile("{\n.reg .pred p, q;\nmbarrier.test_wait.parity.shared::cta.b64 p, [%1], %3;\nmbarrier.test_wait.parity.shared::cta.b64 q, [%2], %3;\n"
        "and.pred p, p, q;\nselp.u32 %0, 1, 0, p;\n}" : "=r"(r) : "r"(b0), "r"(b1), "r"(parity) : "memory");
    return r;
}
__device__ __forceinline__ void tma_load3(uint32_t dst, const CUtensorMap* m, int c0, int c1, uint32_t bar) {
    asm volatile("cp.async.bulk.tensor.3d.shared::cluster.global.mbarrier::complete_tx::bytes [%0], [%1, {%3, %4, %5}], [%2];"
        :: "r"(dst), "l"(m), "r"(bar), "r"(c0), "r"(c1), "r"(0) : "memory");
}
__device__ __forceinline__ void tma_store3(const CUtensorMap* m, int c0, int c1, int c2, uint32_t src) {
    asm volatile("cp.async.bulk.tensor.3d.global.shared::cta.bulk_group [%0, {%2, %3, %4}], [%1];" :: "l"(m), "r"(src), "r"(c0), "r"(c1), "r"(c2) : "memory");
}
__device__ __forceinline__ void tma_load3_mc(uint32_t dst, const CUtensorMap* m, int c1, int c2, uint32_t bar) {
    asm volatile("cp.async.bulk.tensor.3d.shared::cluster.global.mbarrier::complete_tx::bytes.multicast::cluster.L2::cache_hint [%0], [%1, {%3, %4, %5}], [%2], %6, %7;"
        :: "r"(dst), "l"(m), "r"(bar), "r"(0), "r"(c1), "r"(c2), "h"((uint16_t)3), "l"(0x12F0000000000000ull) : "memory");
}
__device__ __forceinline__ void tma_load(uint32_t dst, const CUtensorMap* m, int c0, int c1, uint32_t bar) {
    asm volatile("cp.async.bulk.tensor.2d.shared::cluster.global.mbarrier::complete_tx::bytes [%0], [%1, {%3, %4}], [%2];"
        :: "r"(dst), "l"(m), "r"(bar), "r"(c0), "r"(c1) : "memory");
}
__device__ __forceinline__ void tma_load_ef(uint32_t dst, const CUtensorMap* m, int c0, int c1, uint32_t bar) {
    asm volatile("cp.async.bulk.tensor.2d.shared::cluster.global.mbarrier::complete_tx::bytes.L2::cache_hint [%0], [%1, {%3, %4}], [%2], %5;"
        :: "r"(dst), "l"(m), "r"(bar), "r"(c0), "r"(c1), "l"(0x12F0000000000000ull) : "memory");
}
__device__ __forceinline__ void tma_load_mc(uint32_t dst, const CUtensorMap* m, int c0, int c1, uint32_t bar) {
    asm volatile("cp.async.bulk.tensor.2d.shared::cluster.global.mbarrier::complete_tx::bytes.multicast::cluster.L2::cache_hint [%0], [%1, {%3, %4}], [%2], %5, %6;"
        :: "r"(dst), "l"(m), "r"(bar), "r"(c0), "r"(c1), "h"((uint16_t)3), "l"(0x12F0000000000000ull) : "memory");
}
__device__ __forceinline__ void tma_prefetch(const CUtensorMap* m, int c0, int c1) {
    asm volatile("cp.async.bulk.prefetch.tensor.2d.L2.global [%0, {%1, %2}];" :: "l"(m), "r"(c0), "r"(c1) : "memory");
}
__device__ __forceinline__ void tma_store(const CUtensorMap* m, int c0, int c1, uint32_t src) {
    asm volatile("cp.async.bulk.tensor.2d.global.shared::cta.bulk_group [%0, {%2, %3}], [%1];" :: "l"(m), "r"(src), "r"(c0), "r"(c1) : "memory");
}
__device__ __forceinline__ void bulk_commit() { asm volatile("cp.async.bulk.commit_group;" ::: "memory"); }
__device__ __forceinline__ void bulk_wait_read() { asm volatile("cp.async.bulk.wait_group.read 0;" ::: "memory"); }
__device__ __forceinline__ void fence_async_smem() { asm volatile("fence.proxy.async.shared::cta;" ::: "memory"); }
__device__ __forceinline__ void prefetch_map(const CUtensorMap* m) { asm volatile("prefetch.tensormap [%0];" :: "l"(m) : "memory"); }
__device__ __forceinline__ void wg_fence() { asm volatile("wgmma.fence.sync.aligned;" ::: "memory"); }
__device__ __forceinline__ void wg_commit() { asm volatile("wgmma.commit_group.sync.aligned;" ::: "memory"); }
template <int N> __device__ __forceinline__ void wg_wait() { asm volatile("wgmma.wait_group.sync.aligned %0;" :: "n"(N) : "memory"); }
__device__ __forceinline__ void bar_sync(int id, int n) { asm volatile("bar.sync %0, %1;" :: "r"(id), "r"(n) : "memory"); }
__device__ __forceinline__ void bar_arrive(int id, int n) { asm volatile("bar.arrive %0, %1;" :: "r"(id), "r"(n) : "memory"); }
__device__ __forceinline__ void flag_add(uint32_t* f) { asm volatile("red.relaxed.gpu.global.add.u32 [%0], 1;" :: "l"(f) : "memory"); }
__device__ __forceinline__ void flag_set(uint32_t* f, uint32_t v) { asm volatile("red.relaxed.gpu.global.max.u32 [%0], %1;" :: "l"(f), "r"(v) : "memory"); }
__device__ __forceinline__ uint32_t flag_get(const uint32_t* f) { uint32_t v; asm volatile("ld.relaxed.gpu.global.u32 %0, [%1];" : "=r"(v) : "l"(f) : "memory"); return v; }
__device__ __forceinline__ void bulk_wait_fence() { asm volatile("cp.async.bulk.wait_group 0;\nfence.proxy.async.global;\nfence.acq_rel.gpu;" ::: "memory"); }
__device__ __forceinline__ uint32_t landed(bool el, const uint32_t* p, uint32_t pitch, uint32_t zero) {
    if (el) asm volatile("cp.async.bulk.wait_group 0;" ::: "memory");
    __syncwarp();
    const uint32_t a = flag_get(p), b = flag_get(p + 32 * pitch);
    return __reduce_or_sync(0xffffffffu, (a | b) & zero);
}
__device__ __forceinline__ uint32_t d16(uint32_t addr) { return (addr & 0x3FFFF) >> 4; }
__device__ __forceinline__ uint64_t mk_desc(uint32_t a16, uint32_t off, uint32_t lbo, uint32_t sbo, uint32_t swz) {
    const uint32_t lo = a16 + (off >> 4) + ((lbo >> 4) << 16), hi = (sbo >> 4) | (swz << 30);
    return ((uint64_t)hi << 32) | lo;
}
__device__ __forceinline__ uint32_t pack2(float lo, float hi) {
    uint32_t r; asm("cvt.rn.bf16x2.f32 %0, %1, %2;" : "=r"(r) : "f"(hi), "f"(lo)); return r;
}
__device__ __forceinline__ uint32_t hfma2_bf16(uint32_t a, uint32_t b, uint32_t c) {
    uint32_t r; asm("fma.rn.bf16x2 %0, %1, %2, %3;" : "=r"(r) : "r"(a), "r"(b), "r"(c)); return r;
}
__device__ __forceinline__ float bf_lo(uint32_t v) { return __uint_as_float(v << 16); }
__device__ __forceinline__ float bf_hi(uint32_t v) { return __uint_as_float(v & 0xFFFF0000u); }
__device__ __forceinline__ void unpack2(uint32_t v, float& lo, float& hi) {
    asm volatile("shl.b32 %0, %2, 16;\nand.b32 %1, %2, 0xffff0000;" : "=f"(lo), "=f"(hi) : "r"(v));
}
__device__ __forceinline__ float bf_round(float x) { return __bfloat162float(__float2bfloat16_rn(x)); }
__device__ __forceinline__ void stsm4(uint32_t addr, uint32_t r0, uint32_t r1, uint32_t r2, uint32_t r3) {
    asm volatile("stmatrix.sync.aligned.m8n8.x4.shared.b16 [%0], {%1, %2, %3, %4};" :: "r"(addr), "r"(r0), "r"(r1), "r"(r2), "r"(r3) : "memory");
}
__device__ __forceinline__ void stsm4t(uint32_t addr, uint32_t r0, uint32_t r1, uint32_t r2, uint32_t r3) {
    asm volatile("stmatrix.sync.aligned.m8n8.x4.trans.shared.b16 [%0], {%1, %2, %3, %4};" :: "r"(addr), "r"(r0), "r"(r1), "r"(r2), "r"(r3) : "memory");
}
__device__ __forceinline__ uint32_t movm(uint32_t a) { uint32_t d; asm volatile("movmatrix.sync.aligned.m8n8.trans.b16 %0, %1;" : "=r"(d) : "r"(a)); return d; }
__device__ __forceinline__ void ldsm4(uint32_t addr, uint32_t& r0, uint32_t& r1, uint32_t& r2, uint32_t& r3) {
    asm volatile("ldmatrix.sync.aligned.m8n8.x4.shared.b16 {%0, %1, %2, %3}, [%4];" : "=r"(r0), "=r"(r1), "=r"(r2), "=r"(r3) : "r"(addr) : "memory");
}
__device__ __forceinline__ void ldsm4t(uint32_t addr, uint32_t& r0, uint32_t& r1, uint32_t& r2, uint32_t& r3) {
    asm volatile("ldmatrix.sync.aligned.m8n8.x4.trans.shared.b16 {%0, %1, %2, %3}, [%4];" : "=r"(r0), "=r"(r1), "=r"(r2), "=r"(r3) : "r"(addr) : "memory");
}
__device__ __forceinline__ void mma16816(float (&c)[4], uint32_t a0, uint32_t a1, uint32_t a2, uint32_t a3, uint32_t b0, uint32_t b1) {
    asm("mma.sync.aligned.m16n8k16.row.col.f32.bf16.bf16.f32 {%0, %1, %2, %3}, {%4, %5, %6, %7}, {%8, %9}, {%0, %1, %2, %3};"
        : "+f"(c[0]), "+f"(c[1]), "+f"(c[2]), "+f"(c[3]) : "r"(a0), "r"(a1), "r"(a2), "r"(a3), "r"(b0), "r"(b1));
}
__device__ __forceinline__ float rsq(float x) { float r; asm("rsqrt.approx.ftz.f32 %0, %1;" : "=f"(r) : "f"(x)); return r; }
__device__ __forceinline__ float rcp(float x) { float r; asm("rcp.approx.ftz.f32 %0, %1;" : "=f"(r) : "f"(x)); return r; }
__device__ __forceinline__ float ex2(float x) { float r; asm("ex2.approx.ftz.f32 %0, %1;" : "=f"(r) : "f"(x)); return r; }
__device__ __forceinline__ float tanh_(float x) { float t; asm("tanh.approx.f32 %0, %1;" : "=f"(t) : "f"(x)); return t; }
__device__ __forceinline__ void block_end(uint32_t opaque, uint32_t id) { asm volatile("{\n.reg .pred p;\nsetp.eq.u32 p, %0, %1;\n@p trap;\n}" :: "r"(opaque), "r"(0xffffff00u + id)); }
__device__ __forceinline__ float silu_(float x) { return __fdividef(x, 1.f + __expf(-x)); }
__device__ __forceinline__ void st_pkt(void* p, uint32_t a, uint32_t b) {
    asm volatile("{\n.reg .b64 t;\nmov.b64 t, {%1, %2};\nst.relaxed.gpu.global.b64 [%0], t;\n}" :: "l"(p), "r"(a), "r"(b) : "memory");
}
__device__ __forceinline__ uint4 ld_pkt2(const void* p) {
    uint4 v; asm volatile("{\n.reg .b64 t, u;\nld.relaxed.gpu.global.v2.b64 {t, u}, [%4];\nmov.b64 {%0, %1}, t;\nmov.b64 {%2, %3}, u;\n}"
        : "=r"(v.x), "=r"(v.y), "=r"(v.z), "=r"(v.w) : "l"(p) : "memory"); return v;
}
__device__ __forceinline__ void st_pkt16(void* p, uint32_t a, uint32_t b, uint32_t c, uint32_t d) {
    asm volatile("{\n.reg .b64 t, u;\n.reg .b128 w;\nmov.b64 t, {%1, %2};\nmov.b64 u, {%3, %4};\nmov.b128 w, {t, u};\nst.relaxed.gpu.global.b128 [%0], w;\n}"
        :: "l"(p), "r"(a), "r"(b), "r"(c), "r"(d) : "memory");
}
__device__ __forceinline__ uint4 ld_pkt16(const void* p) {
    uint4 v; asm volatile("{\n.reg .b64 t, u;\n.reg .b128 w;\nld.relaxed.gpu.global.b128 w, [%4];\nmov.b128 {t, u}, w;\nmov.b64 {%0, %1}, t;\nmov.b64 {%2, %3}, u;\n}"
        : "=r"(v.x), "=r"(v.y), "=r"(v.z), "=r"(v.w) : "l"(p) : "memory"); return v;
}
#define SPIN_GUARD(n) do { if (++(n) > (1u << 22)) asm volatile("trap;"); } while (0)
__device__ __forceinline__ uint4 lds128(uint32_t a) { uint4 v; asm volatile("ld.shared.v4.u32 {%0, %1, %2, %3}, [%4];" : "=r"(v.x), "=r"(v.y), "=r"(v.z), "=r"(v.w) : "r"(a) : "memory"); return v; }
__device__ __forceinline__ void sts128(uint32_t a, uint32_t x, uint32_t y, uint32_t z, uint32_t w) { asm volatile("st.shared.v4.u32 [%0], {%1, %2, %3, %4};" :: "r"(a), "r"(x), "r"(y), "r"(z), "r"(w) : "memory"); }
__device__ __forceinline__ uint32_t lds32(uint32_t a) { uint32_t v; asm volatile("ld.shared.u32 %0, [%1];" : "=r"(v) : "r"(a) : "memory"); return v; }
__device__ __forceinline__ void sts32(uint32_t a, uint32_t v) { asm volatile("st.shared.u32 [%0], %1;" :: "r"(a), "r"(v) : "memory"); }
__device__ __forceinline__ bool elect_one() {
    uint32_t p; asm volatile("{\n.reg .pred q;\nelect.sync _|q, 0xffffffff;\nselp.u32 %0, 1, 0, q;\n}" : "=r"(p)); return p;
}
__device__ __forceinline__ void pause(uint32_t cycles) {
    uint32_t t0, t; asm volatile("mov.u32 %0, %%clock;" : "=r"(t0));
    do { __nanosleep(64); asm volatile("mov.u32 %0, %%clock;" : "=r"(t)); } while (t - t0 < cycles);
}
__device__ __forceinline__ void cluster_arrive() { asm volatile("barrier.cluster.arrive.relaxed.aligned;" ::: "memory"); }
__device__ __forceinline__ void cluster_wait() { asm volatile("barrier.cluster.wait.aligned;" ::: "memory"); }

__device__ __forceinline__ void wgmma_n128_z(float (&d)[64], uint64_t da, uint64_t db) {
    asm volatile("{\n.reg .pred p;\nsetp.ne.b32 p, 0, 0;\n"
        "wgmma.mma_async.sync.aligned.m64n128k16.f32.bf16.bf16 {"
        "%0, %1, %2, %3, %4, %5, %6, %7, %8, %9, %10, %11, %12, %13, %14, %15, "
        "%16, %17, %18, %19, %20, %21, %22, %23, %24, %25, %26, %27, %28, %29, %30, %31, "
        "%32, %33, %34, %35, %36, %37, %38, %39, %40, %41, %42, %43, %44, %45, %46, %47, "
        "%48, %49, %50, %51, %52, %53, %54, %55, %56, %57, %58, %59, %60, %61, %62, %63"
        "}, %64, %65, p, 1, 1, 0, 1;\n}\n"
        : "=f"(d[0]), "=f"(d[1]), "=f"(d[2]), "=f"(d[3]), "=f"(d[4]), "=f"(d[5]), "=f"(d[6]), "=f"(d[7]),
          "=f"(d[8]), "=f"(d[9]), "=f"(d[10]), "=f"(d[11]), "=f"(d[12]), "=f"(d[13]), "=f"(d[14]), "=f"(d[15]),
          "=f"(d[16]), "=f"(d[17]), "=f"(d[18]), "=f"(d[19]), "=f"(d[20]), "=f"(d[21]), "=f"(d[22]), "=f"(d[23]),
          "=f"(d[24]), "=f"(d[25]), "=f"(d[26]), "=f"(d[27]), "=f"(d[28]), "=f"(d[29]), "=f"(d[30]), "=f"(d[31]),
          "=f"(d[32]), "=f"(d[33]), "=f"(d[34]), "=f"(d[35]), "=f"(d[36]), "=f"(d[37]), "=f"(d[38]), "=f"(d[39]),
          "=f"(d[40]), "=f"(d[41]), "=f"(d[42]), "=f"(d[43]), "=f"(d[44]), "=f"(d[45]), "=f"(d[46]), "=f"(d[47]),
          "=f"(d[48]), "=f"(d[49]), "=f"(d[50]), "=f"(d[51]), "=f"(d[52]), "=f"(d[53]), "=f"(d[54]), "=f"(d[55]),
          "=f"(d[56]), "=f"(d[57]), "=f"(d[58]), "=f"(d[59]), "=f"(d[60]), "=f"(d[61]), "=f"(d[62]), "=f"(d[63])
        : "l"(da), "l"(db));
}
__device__ __forceinline__ void wgmma_n128(float (&d)[64], uint64_t da, uint64_t db) {
    asm volatile("{\n.reg .pred p;\nsetp.eq.b32 p, 0, 0;\n"
        "wgmma.mma_async.sync.aligned.m64n128k16.f32.bf16.bf16 {"
        "%0, %1, %2, %3, %4, %5, %6, %7, %8, %9, %10, %11, %12, %13, %14, %15, "
        "%16, %17, %18, %19, %20, %21, %22, %23, %24, %25, %26, %27, %28, %29, %30, %31, "
        "%32, %33, %34, %35, %36, %37, %38, %39, %40, %41, %42, %43, %44, %45, %46, %47, "
        "%48, %49, %50, %51, %52, %53, %54, %55, %56, %57, %58, %59, %60, %61, %62, %63"
        "}, %64, %65, p, 1, 1, 0, 1;\n}\n"
        : "+f"(d[0]), "+f"(d[1]), "+f"(d[2]), "+f"(d[3]), "+f"(d[4]), "+f"(d[5]), "+f"(d[6]), "+f"(d[7]),
          "+f"(d[8]), "+f"(d[9]), "+f"(d[10]), "+f"(d[11]), "+f"(d[12]), "+f"(d[13]), "+f"(d[14]), "+f"(d[15]),
          "+f"(d[16]), "+f"(d[17]), "+f"(d[18]), "+f"(d[19]), "+f"(d[20]), "+f"(d[21]), "+f"(d[22]), "+f"(d[23]),
          "+f"(d[24]), "+f"(d[25]), "+f"(d[26]), "+f"(d[27]), "+f"(d[28]), "+f"(d[29]), "+f"(d[30]), "+f"(d[31]),
          "+f"(d[32]), "+f"(d[33]), "+f"(d[34]), "+f"(d[35]), "+f"(d[36]), "+f"(d[37]), "+f"(d[38]), "+f"(d[39]),
          "+f"(d[40]), "+f"(d[41]), "+f"(d[42]), "+f"(d[43]), "+f"(d[44]), "+f"(d[45]), "+f"(d[46]), "+f"(d[47]),
          "+f"(d[48]), "+f"(d[49]), "+f"(d[50]), "+f"(d[51]), "+f"(d[52]), "+f"(d[53]), "+f"(d[54]), "+f"(d[55]),
          "+f"(d[56]), "+f"(d[57]), "+f"(d[58]), "+f"(d[59]), "+f"(d[60]), "+f"(d[61]), "+f"(d[62]), "+f"(d[63])
        : "l"(da), "l"(db));
}
__device__ __forceinline__ void wgmma_n176_z(float (&d)[88], uint64_t da, uint64_t db) {
    asm volatile("{\n.reg .pred p;\nsetp.ne.b32 p, 0, 0;\n"
        "wgmma.mma_async.sync.aligned.m64n176k16.f32.bf16.bf16 {"
        "%0, %1, %2, %3, %4, %5, %6, %7, %8, %9, %10, %11, %12, %13, %14, %15, "
        "%16, %17, %18, %19, %20, %21, %22, %23, %24, %25, %26, %27, %28, %29, %30, %31, "
        "%32, %33, %34, %35, %36, %37, %38, %39, %40, %41, %42, %43, %44, %45, %46, %47, "
        "%48, %49, %50, %51, %52, %53, %54, %55, %56, %57, %58, %59, %60, %61, %62, %63, "
        "%64, %65, %66, %67, %68, %69, %70, %71, %72, %73, %74, %75, %76, %77, %78, %79, "
        "%80, %81, %82, %83, %84, %85, %86, %87"
        "}, %88, %89, p, 1, 1, 0, 1;\n}\n"
        : "=f"(d[0]), "=f"(d[1]), "=f"(d[2]), "=f"(d[3]), "=f"(d[4]), "=f"(d[5]), "=f"(d[6]), "=f"(d[7]),
          "=f"(d[8]), "=f"(d[9]), "=f"(d[10]), "=f"(d[11]), "=f"(d[12]), "=f"(d[13]), "=f"(d[14]), "=f"(d[15]),
          "=f"(d[16]), "=f"(d[17]), "=f"(d[18]), "=f"(d[19]), "=f"(d[20]), "=f"(d[21]), "=f"(d[22]), "=f"(d[23]),
          "=f"(d[24]), "=f"(d[25]), "=f"(d[26]), "=f"(d[27]), "=f"(d[28]), "=f"(d[29]), "=f"(d[30]), "=f"(d[31]),
          "=f"(d[32]), "=f"(d[33]), "=f"(d[34]), "=f"(d[35]), "=f"(d[36]), "=f"(d[37]), "=f"(d[38]), "=f"(d[39]),
          "=f"(d[40]), "=f"(d[41]), "=f"(d[42]), "=f"(d[43]), "=f"(d[44]), "=f"(d[45]), "=f"(d[46]), "=f"(d[47]),
          "=f"(d[48]), "=f"(d[49]), "=f"(d[50]), "=f"(d[51]), "=f"(d[52]), "=f"(d[53]), "=f"(d[54]), "=f"(d[55]),
          "=f"(d[56]), "=f"(d[57]), "=f"(d[58]), "=f"(d[59]), "=f"(d[60]), "=f"(d[61]), "=f"(d[62]), "=f"(d[63]),
          "=f"(d[64]), "=f"(d[65]), "=f"(d[66]), "=f"(d[67]), "=f"(d[68]), "=f"(d[69]), "=f"(d[70]), "=f"(d[71]),
          "=f"(d[72]), "=f"(d[73]), "=f"(d[74]), "=f"(d[75]), "=f"(d[76]), "=f"(d[77]), "=f"(d[78]), "=f"(d[79]),
          "=f"(d[80]), "=f"(d[81]), "=f"(d[82]), "=f"(d[83]), "=f"(d[84]), "=f"(d[85]), "=f"(d[86]), "=f"(d[87])
        : "l"(da), "l"(db));
}
__device__ __forceinline__ void wgmma_n176(float (&d)[88], uint64_t da, uint64_t db) {
    asm volatile("{\n.reg .pred p;\nsetp.eq.b32 p, 0, 0;\n"
        "wgmma.mma_async.sync.aligned.m64n176k16.f32.bf16.bf16 {"
        "%0, %1, %2, %3, %4, %5, %6, %7, %8, %9, %10, %11, %12, %13, %14, %15, "
        "%16, %17, %18, %19, %20, %21, %22, %23, %24, %25, %26, %27, %28, %29, %30, %31, "
        "%32, %33, %34, %35, %36, %37, %38, %39, %40, %41, %42, %43, %44, %45, %46, %47, "
        "%48, %49, %50, %51, %52, %53, %54, %55, %56, %57, %58, %59, %60, %61, %62, %63, "
        "%64, %65, %66, %67, %68, %69, %70, %71, %72, %73, %74, %75, %76, %77, %78, %79, "
        "%80, %81, %82, %83, %84, %85, %86, %87"
        "}, %88, %89, p, 1, 1, 0, 1;\n}\n"
        : "+f"(d[0]), "+f"(d[1]), "+f"(d[2]), "+f"(d[3]), "+f"(d[4]), "+f"(d[5]), "+f"(d[6]), "+f"(d[7]),
          "+f"(d[8]), "+f"(d[9]), "+f"(d[10]), "+f"(d[11]), "+f"(d[12]), "+f"(d[13]), "+f"(d[14]), "+f"(d[15]),
          "+f"(d[16]), "+f"(d[17]), "+f"(d[18]), "+f"(d[19]), "+f"(d[20]), "+f"(d[21]), "+f"(d[22]), "+f"(d[23]),
          "+f"(d[24]), "+f"(d[25]), "+f"(d[26]), "+f"(d[27]), "+f"(d[28]), "+f"(d[29]), "+f"(d[30]), "+f"(d[31]),
          "+f"(d[32]), "+f"(d[33]), "+f"(d[34]), "+f"(d[35]), "+f"(d[36]), "+f"(d[37]), "+f"(d[38]), "+f"(d[39]),
          "+f"(d[40]), "+f"(d[41]), "+f"(d[42]), "+f"(d[43]), "+f"(d[44]), "+f"(d[45]), "+f"(d[46]), "+f"(d[47]),
          "+f"(d[48]), "+f"(d[49]), "+f"(d[50]), "+f"(d[51]), "+f"(d[52]), "+f"(d[53]), "+f"(d[54]), "+f"(d[55]),
          "+f"(d[56]), "+f"(d[57]), "+f"(d[58]), "+f"(d[59]), "+f"(d[60]), "+f"(d[61]), "+f"(d[62]), "+f"(d[63]),
          "+f"(d[64]), "+f"(d[65]), "+f"(d[66]), "+f"(d[67]), "+f"(d[68]), "+f"(d[69]), "+f"(d[70]), "+f"(d[71]),
          "+f"(d[72]), "+f"(d[73]), "+f"(d[74]), "+f"(d[75]), "+f"(d[76]), "+f"(d[77]), "+f"(d[78]), "+f"(d[79]),
          "+f"(d[80]), "+f"(d[81]), "+f"(d[82]), "+f"(d[83]), "+f"(d[84]), "+f"(d[85]), "+f"(d[86]), "+f"(d[87])
        : "l"(da), "l"(db));
}
__device__ __forceinline__ void wgmma_n256_z(float (&d)[128], uint64_t da, uint64_t db) {
    asm volatile("{\n.reg .pred p;\nsetp.ne.b32 p, 0, 0;\n"
        "wgmma.mma_async.sync.aligned.m64n256k16.f32.bf16.bf16 {"
        "%0, %1, %2, %3, %4, %5, %6, %7, %8, %9, %10, %11, %12, %13, %14, %15, "
        "%16, %17, %18, %19, %20, %21, %22, %23, %24, %25, %26, %27, %28, %29, %30, %31, "
        "%32, %33, %34, %35, %36, %37, %38, %39, %40, %41, %42, %43, %44, %45, %46, %47, "
        "%48, %49, %50, %51, %52, %53, %54, %55, %56, %57, %58, %59, %60, %61, %62, %63, "
        "%64, %65, %66, %67, %68, %69, %70, %71, %72, %73, %74, %75, %76, %77, %78, %79, "
        "%80, %81, %82, %83, %84, %85, %86, %87, %88, %89, %90, %91, %92, %93, %94, %95, "
        "%96, %97, %98, %99, %100, %101, %102, %103, %104, %105, %106, %107, %108, %109, %110, %111, "
        "%112, %113, %114, %115, %116, %117, %118, %119, %120, %121, %122, %123, %124, %125, %126, %127"
        "}, %128, %129, p, 1, 1, 0, 1;\n}\n"
        : "=f"(d[0]), "=f"(d[1]), "=f"(d[2]), "=f"(d[3]), "=f"(d[4]), "=f"(d[5]), "=f"(d[6]), "=f"(d[7]),
          "=f"(d[8]), "=f"(d[9]), "=f"(d[10]), "=f"(d[11]), "=f"(d[12]), "=f"(d[13]), "=f"(d[14]), "=f"(d[15]),
          "=f"(d[16]), "=f"(d[17]), "=f"(d[18]), "=f"(d[19]), "=f"(d[20]), "=f"(d[21]), "=f"(d[22]), "=f"(d[23]),
          "=f"(d[24]), "=f"(d[25]), "=f"(d[26]), "=f"(d[27]), "=f"(d[28]), "=f"(d[29]), "=f"(d[30]), "=f"(d[31]),
          "=f"(d[32]), "=f"(d[33]), "=f"(d[34]), "=f"(d[35]), "=f"(d[36]), "=f"(d[37]), "=f"(d[38]), "=f"(d[39]),
          "=f"(d[40]), "=f"(d[41]), "=f"(d[42]), "=f"(d[43]), "=f"(d[44]), "=f"(d[45]), "=f"(d[46]), "=f"(d[47]),
          "=f"(d[48]), "=f"(d[49]), "=f"(d[50]), "=f"(d[51]), "=f"(d[52]), "=f"(d[53]), "=f"(d[54]), "=f"(d[55]),
          "=f"(d[56]), "=f"(d[57]), "=f"(d[58]), "=f"(d[59]), "=f"(d[60]), "=f"(d[61]), "=f"(d[62]), "=f"(d[63]),
          "=f"(d[64]), "=f"(d[65]), "=f"(d[66]), "=f"(d[67]), "=f"(d[68]), "=f"(d[69]), "=f"(d[70]), "=f"(d[71]),
          "=f"(d[72]), "=f"(d[73]), "=f"(d[74]), "=f"(d[75]), "=f"(d[76]), "=f"(d[77]), "=f"(d[78]), "=f"(d[79]),
          "=f"(d[80]), "=f"(d[81]), "=f"(d[82]), "=f"(d[83]), "=f"(d[84]), "=f"(d[85]), "=f"(d[86]), "=f"(d[87]),
          "=f"(d[88]), "=f"(d[89]), "=f"(d[90]), "=f"(d[91]), "=f"(d[92]), "=f"(d[93]), "=f"(d[94]), "=f"(d[95]),
          "=f"(d[96]), "=f"(d[97]), "=f"(d[98]), "=f"(d[99]), "=f"(d[100]), "=f"(d[101]), "=f"(d[102]), "=f"(d[103]),
          "=f"(d[104]), "=f"(d[105]), "=f"(d[106]), "=f"(d[107]), "=f"(d[108]), "=f"(d[109]), "=f"(d[110]), "=f"(d[111]),
          "=f"(d[112]), "=f"(d[113]), "=f"(d[114]), "=f"(d[115]), "=f"(d[116]), "=f"(d[117]), "=f"(d[118]), "=f"(d[119]),
          "=f"(d[120]), "=f"(d[121]), "=f"(d[122]), "=f"(d[123]), "=f"(d[124]), "=f"(d[125]), "=f"(d[126]), "=f"(d[127])
        : "l"(da), "l"(db));
}
__device__ __forceinline__ void wgmma_n256(float (&d)[128], uint64_t da, uint64_t db) {
    asm volatile("{\n.reg .pred p;\nsetp.eq.b32 p, 0, 0;\n"
        "wgmma.mma_async.sync.aligned.m64n256k16.f32.bf16.bf16 {"
        "%0, %1, %2, %3, %4, %5, %6, %7, %8, %9, %10, %11, %12, %13, %14, %15, "
        "%16, %17, %18, %19, %20, %21, %22, %23, %24, %25, %26, %27, %28, %29, %30, %31, "
        "%32, %33, %34, %35, %36, %37, %38, %39, %40, %41, %42, %43, %44, %45, %46, %47, "
        "%48, %49, %50, %51, %52, %53, %54, %55, %56, %57, %58, %59, %60, %61, %62, %63, "
        "%64, %65, %66, %67, %68, %69, %70, %71, %72, %73, %74, %75, %76, %77, %78, %79, "
        "%80, %81, %82, %83, %84, %85, %86, %87, %88, %89, %90, %91, %92, %93, %94, %95, "
        "%96, %97, %98, %99, %100, %101, %102, %103, %104, %105, %106, %107, %108, %109, %110, %111, "
        "%112, %113, %114, %115, %116, %117, %118, %119, %120, %121, %122, %123, %124, %125, %126, %127"
        "}, %128, %129, p, 1, 1, 0, 1;\n}\n"
        : "+f"(d[0]), "+f"(d[1]), "+f"(d[2]), "+f"(d[3]), "+f"(d[4]), "+f"(d[5]), "+f"(d[6]), "+f"(d[7]),
          "+f"(d[8]), "+f"(d[9]), "+f"(d[10]), "+f"(d[11]), "+f"(d[12]), "+f"(d[13]), "+f"(d[14]), "+f"(d[15]),
          "+f"(d[16]), "+f"(d[17]), "+f"(d[18]), "+f"(d[19]), "+f"(d[20]), "+f"(d[21]), "+f"(d[22]), "+f"(d[23]),
          "+f"(d[24]), "+f"(d[25]), "+f"(d[26]), "+f"(d[27]), "+f"(d[28]), "+f"(d[29]), "+f"(d[30]), "+f"(d[31]),
          "+f"(d[32]), "+f"(d[33]), "+f"(d[34]), "+f"(d[35]), "+f"(d[36]), "+f"(d[37]), "+f"(d[38]), "+f"(d[39]),
          "+f"(d[40]), "+f"(d[41]), "+f"(d[42]), "+f"(d[43]), "+f"(d[44]), "+f"(d[45]), "+f"(d[46]), "+f"(d[47]),
          "+f"(d[48]), "+f"(d[49]), "+f"(d[50]), "+f"(d[51]), "+f"(d[52]), "+f"(d[53]), "+f"(d[54]), "+f"(d[55]),
          "+f"(d[56]), "+f"(d[57]), "+f"(d[58]), "+f"(d[59]), "+f"(d[60]), "+f"(d[61]), "+f"(d[62]), "+f"(d[63]),
          "+f"(d[64]), "+f"(d[65]), "+f"(d[66]), "+f"(d[67]), "+f"(d[68]), "+f"(d[69]), "+f"(d[70]), "+f"(d[71]),
          "+f"(d[72]), "+f"(d[73]), "+f"(d[74]), "+f"(d[75]), "+f"(d[76]), "+f"(d[77]), "+f"(d[78]), "+f"(d[79]),
          "+f"(d[80]), "+f"(d[81]), "+f"(d[82]), "+f"(d[83]), "+f"(d[84]), "+f"(d[85]), "+f"(d[86]), "+f"(d[87]),
          "+f"(d[88]), "+f"(d[89]), "+f"(d[90]), "+f"(d[91]), "+f"(d[92]), "+f"(d[93]), "+f"(d[94]), "+f"(d[95]),
          "+f"(d[96]), "+f"(d[97]), "+f"(d[98]), "+f"(d[99]), "+f"(d[100]), "+f"(d[101]), "+f"(d[102]), "+f"(d[103]),
          "+f"(d[104]), "+f"(d[105]), "+f"(d[106]), "+f"(d[107]), "+f"(d[108]), "+f"(d[109]), "+f"(d[110]), "+f"(d[111]),
          "+f"(d[112]), "+f"(d[113]), "+f"(d[114]), "+f"(d[115]), "+f"(d[116]), "+f"(d[117]), "+f"(d[118]), "+f"(d[119]),
          "+f"(d[120]), "+f"(d[121]), "+f"(d[122]), "+f"(d[123]), "+f"(d[124]), "+f"(d[125]), "+f"(d[126]), "+f"(d[127])
        : "l"(da), "l"(db));
}

__device__ __forceinline__ void wgmma_n8_ta(float (&d)[4], uint64_t da, uint64_t db) {
    asm volatile("{\n.reg .pred p;\nsetp.eq.b32 p, 0, 0;\nwgmma.mma_async.sync.aligned.m64n8k16.f32.bf16.bf16 {%0, %1, %2, %3}, %4, %5, p, 1, 1, 1, 0;\n}"
        : "+f"(d[0]), "+f"(d[1]), "+f"(d[2]), "+f"(d[3]) : "l"(da), "l"(db));
}

struct Idx {
    uint32_t lane, warp, w4, q4, g8, prow, pan;
    __device__ __forceinline__ Idx() {
        uint32_t t; asm volatile("mov.u32 %0, %%tid.x;" : "=r"(t));
        lane = t & 31; warp = t >> 5; w4 = warp & 3; q4 = lane & 3; g8 = lane >> 2;
        prow = w4 * 16 + ((lane >> 3) & 1) * 8 + (lane & 7);
        pan = prow * 128 + (((lane >> 4) ^ (lane & 7)) << 4);
    }
};
#define IDX() const Idx ix; const uint32_t lane = ix.lane, warp = ix.warp, w4 = ix.w4, q4 = ix.q4, g8 = ix.g8, prow = ix.prow, pan_addr = ix.pan; \
    (void)lane; (void)warp; (void)w4; (void)q4; (void)g8; (void)prow; (void)pan_addr;

__device__ __forceinline__ int kof(int t, int sh, int j) {
    const int p = t >> (sh - 1), pn = p < 2 ? p : p >= 9, q = p - 2 - 7 * pn;
    return ((p < 2 ? j : q + (q >= j)) << 7) + (pn << 6) + ((t & (sh - 1)) << 5);
}
__device__ __forceinline__ uint32_t fidx(uint32_t m, uint32_t w, uint32_t pn) {
    return m * 32 + w * 16 + pn;
}
constexpr int HC0 = 8 * 48, HC3 = HC0 + 3072;
__device__ __forceinline__ int hcol(int p, int j) { return HC0 + p * 1024 + j * 128; }
struct Ring {
    uint32_t slot, par;
    __device__ __forceinline__ void next() { if (++slot == NSLOT) { slot = 0; par ^= 1; } }
    __device__ __forceinline__ void skip(uint32_t n) { slot += n; if (slot >= NSLOT) { slot -= NSLOT; par ^= 1; } }
};
__device__ __forceinline__ uint32_t BAR_FULL(uint32_t sb, uint32_t s) { return sb + OFF_BAR + 8 * s; }
constexpr uint32_t AF_REL = 48;
__device__ __forceinline__ uint32_t BAR_EMPTY(uint32_t sb, uint32_t s) { return sb + OFF_BAR + 96 + 8 * s; }
__device__ __forceinline__ uint32_t BAR_SFULL(uint32_t sb, uint32_t i) { return sb + OFF_BAR + 152 + 8 * i; }
__device__ __forceinline__ uint32_t BAR_SREADY(uint32_t sb, uint32_t i) { return sb + OFF_BAR + 184 + 8 * i; }
__device__ __forceinline__ uint32_t BAR_ONE(uint32_t sb, uint32_t i) { return sb + OFF_BAR + 216 + 8 * i; }
enum { EV_WIN, EV_WIN1, EV_WIN2, EV_WIN3, EV_P0, EV_GA, EV_GB, EV_LN2, EV_LAG1, EV_LAG2, EV_LAG3, EV_LAG4, EV_LAG5, EV_KV, EV_PAR, EV_AGO, EV_AGO1, EV_AGO2, EV_FGO, EV_FGO1, EV_FGO2, EV_H0, EV_H1, EV_H2, EV_H3, EV_TAIL, EV_COUNT = EV_TAIL + 8 };
constexpr int NB_TAIL = 4;

struct Rel {
    uint32_t base; bool sig;
    __device__ __forceinline__ Rel(uint32_t sb, uint32_t tw) {
        uint32_t a; asm("mapa.shared::cluster.u32 %0, %1, %2;" : "=r"(a) : "r"(BAR_EMPTY(sb, 0)), "r"((tw >> 5) & 1));
        base = __shfl_sync(0xffffffffu, a, 0); sig = (tw & ~32u) == 0;
    }
    __device__ __forceinline__ void operator()(uint32_t slot) const {
        if (sig) asm volatile("mbarrier.arrive.shared::cluster.b64 _, [%0];" :: "r"(base + 8 * slot) : "memory");
    }
};
struct LnRow { float rs0, nm0, rs1, nm1; };
struct Pipe {
    Rel rel; uint32_t p1, p2;
    __device__ __forceinline__ Pipe(uint32_t sb, uint32_t tw, uint32_t first) : rel(sb, tw), p1(first), p2(NSLOT) {}
    template <bool TWO> __device__ __forceinline__ void acquire(uint32_t sb, uint32_t af, const Ring& r) {
        const uint32_t b0 = BAR_FULL(sb, r.slot), b1 = b0 + af;
        const bool ready = TWO ? mbar_test2(b0, b1, r.par) : mbar_test(b0, r.par);
        wg_wait<1>();
        rel(p2);
        if (!ready) { if (TWO) mbar_wait2(b0, b1, r.par); else mbar_wait(b0, r.par); }
    }
    __device__ __forceinline__ void issued(uint32_t slot) { p2 = p1; p1 = slot; }
    __device__ __forceinline__ void drain1() { wg_wait<1>(); rel(p2); p2 = NSLOT; }
    __device__ __forceinline__ void drain0() { wg_wait<0>(); rel(p1); p1 = NSLOT; }
    template <bool TWO, class Step> __device__ __forceinline__ void hold(int LG, uint32_t sb, uint32_t af, Ring& r, uint32_t lag_bar, Step step) {
        Ring q = r;
#pragma unroll 1
        for (int i = 0; i < LG; ++i) { if (TWO) mbar_wait2(BAR_FULL(sb, q.slot), BAR_FULL(sb, q.slot) + af, q.par); else mbar_wait(BAR_FULL(sb, q.slot), q.par); q.next(); }
        mbar_wait(lag_bar, 0);
#pragma unroll 1
        do {
            step(r.slot);
            wg_wait<2>(); rel(p2); p2 = p1; p1 = r.slot;
            if (++r.slot == NSLOT) r.slot = 0;
        } while (r.slot != q.slot);
        r.par = q.par;
    }
};
template <bool TWO, bool FIRST, int NA, int NB>
__device__ __forceinline__ void step32(float (&aa)[NA], float (&ab)[NB], uint32_t sb, uint32_t wg, uint32_t slot, int own) {
    const uint32_t st = d16(sb) + slot * (SLOT >> 4);
    const uint32_t alo = own >= 0 ? d16(sb) + OFF_STG / 16 + wg * 1024 + (own >> 1) * 512 + (own & 1) * 4 : st + wg * 256;
    const uint32_t ahi = own >= 0 ? (1024 >> 4) | (1u << 30) : (512 >> 4) | (2u << 30);
    wg_fence();
#pragma unroll
    for (int k = 0; k < 2; ++k) {
        const uint64_t da = ((uint64_t)ahi << 32) | (alo + k * 2 + 0x10000);
        if constexpr (NA == 88) {
            const uint64_t d0 = mk_desc(st, 8192 + k * 2048, 8192, 1024, 1), d1 = mk_desc(st, 12288 + k * 2048, 8192, 1024, 1);
            if (FIRST && k == 0) { wgmma_n176_z(aa, da, d0); wgmma_n176_z(ab, da, d1); }
            else { wgmma_n176(aa, da, d0); wgmma_n176(ab, da, d1); }
        } else {
            const uint64_t d0 = mk_desc(st, 8192 + k * 2048, 4096, 1024, 1), d1 = mk_desc(st, 24576 + k * 2048, 4096, 1024, 1);
            if (FIRST && k == 0) { wgmma_n256_z(aa, da, d0); if constexpr (TWO) wgmma_n128_z(ab, da, d1); }
            else { wgmma_n256(aa, da, d0); if constexpr (TWO) wgmma_n128(ab, da, d1); }
        }
    }
    wg_commit();
}
template <bool TWO, int LG, int NA, int NB, class Mid, class Tail>
__device__ __forceinline__ void mainloop32(float (&aa)[NA], float (&ab)[NB], uint32_t sb, uint32_t wg, uint32_t tw, Ring& r, uint32_t lag_ev, int g0, Mid mid, Tail tail) {
    step32<TWO, true>(aa, ab, sb, wg, r.slot, TWO ? 0 : -1);
    TS(g0, 0);
    Pipe pp(sb, tw, r.slot);
    r.next();
    const int end = wg ? 32 : 32 - LG;
#pragma unroll 1
    for (int it = 1; it < end; ++it) {
        pp.acquire<TWO>(sb, wg ? 0 : AF_REL, r);
        step32<TWO, false>(aa, ab, sb, wg, r.slot, TWO && it < 4 ? it : -1);
        pp.issued(r.slot);
        TS(g0 + it, 0);
        r.next();
        mid(it);
    }
    if (wg == 0) { pp.drain1(); pp.drain0(); pp.hold<TWO>(LG, sb, AF_REL, r, BAR_ONE(sb, lag_ev), [&](uint32_t slot) { step32<TWO, false>(aa, ab, sb, 0, slot, -1); }); }
    if (wg == 1 && tw == 0) mbar_arrive(BAR_ONE(sb, lag_ev));
    pp.drain1();
    tail();
    pp.drain0();
    TS(g0 + 31, 1);
}
template <bool FIRST>
__device__ __forceinline__ void step64(float (&acc)[64], uint32_t sb, uint32_t wg, uint32_t slot, int own) {
    const uint32_t sbb = d16(sb) + slot * (SLOT >> 4), sa = own >= 0 ? d16(sb) + OFF_STG / 16 + wg * 1024 + own * 512 : sbb + wg * 512;
    wg_fence();
#pragma unroll
    for (int k = 0; k < 4; ++k) {
        const uint64_t da = mk_desc(sa, k * 32, 16, 1024, 1), db = mk_desc(sbb, 16384 + k * 2048, 8192, 1024, 1);
        if (FIRST && k == 0) wgmma_n128_z(acc, da, db); else wgmma_n128(acc, da, db);
    }
    wg_commit();
}
template <class Put, class Mid, class Tail>
__device__ __forceinline__ void mainloop64(float (&acc)[64], bool wo, uint32_t sb, uint32_t wg, uint32_t tw, Ring& r, Put put, Mid mid, Tail tail) {
    const int g0 = wo ? 32 : 144, nst = wo ? 16 : 56, lg = wo ? LAGW : LAGD; (void)g0;
    const uint32_t lag_bar = BAR_ONE(sb, wo ? EV_LAG4 : EV_LAG5), af = wo && !wg ? AF_REL : 0;
    if (!wo) CS(28);
    step64<true>(acc, sb, wg, r.slot, wo ? 0 : -1);
    if (!wo) CS(29);
    TS(g0, 0);
    Pipe pp(sb, tw, r.slot);
    r.next();
    int it = 1;
    auto run = [&](int end, int own, bool with_put) {
#pragma unroll 1
        do {
            pp.acquire<true>(sb, af, r);
            step64<false>(acc, sb, wg, r.slot, own);
            pp.issued(r.slot);
            TS(g0 + it, 0);
            if (wo && it == 2) CS(9);
            r.next();
            if (with_put && it == (wg ? PUTD1 : PUTD0)) put();
        } while (++it < end);
    };
    const int end = wg ? nst : nst - lg;
    run(wo ? 2 : wg ? MIDD : end, wo ? 1 : -1, true);
    mid();
    if (wo) { pp.drain1(); pp.drain0(); TS(g0 + 1, 1); }
    if (it < end) run(end, -1, false);
    if (wg == 0) { pp.drain1(); pp.drain0(); pp.hold<true>(lg, sb, af, r, lag_bar, [&](uint32_t slot) { step64<false>(acc, sb, 0, slot, -1); }); }
    if (wg == 1 && tw == 0) mbar_arrive(lag_bar);
    pp.drain1();
    tail();
    pp.drain0();
    TS(g0 + nst - 1, 1);
}

struct RowAcc {
    float sm[4] = {0.f, 0.f, 0.f, 0.f}, sq[4] = {0.f, 0.f, 0.f, 0.f};
    __device__ __forceinline__ void add(int e, float x) { sm[e & 3] += x; sq[e & 3] = fmaf(x, x, sq[e & 3]); }
    __device__ __forceinline__ void publish(uint4* dst, uint32_t q4, uint32_t ep) const {
        const float s0 = sm[0] + sm[1], s1 = sm[2] + sm[3], q0 = sq[0] + sq[1], q1 = sq[2] + sq[3];
        const bool od = q4 & 1;
        float sv = (od ? s1 : s0) + __shfl_xor_sync(0xffffffffu, od ? s0 : s1, 1), qv = (od ? q1 : q0) + __shfl_xor_sync(0xffffffffu, od ? q0 : q1, 1);
        sv += __shfl_xor_sync(0xffffffffu, sv, 2); qv += __shfl_xor_sync(0xffffffffu, qv, 2);
        st_pkt16(dst + (q4 & 1) * 8, 0, __float_as_uint(sv), __float_as_uint(qv), ep);
    }
};
__device__ __forceinline__ LnRow merge_stats(const uint4* src, uint32_t q4, uint32_t ep, uint32_t sb) {
    uint4 t[4];
    uint32_t n = 0;
    while (true) {
#pragma unroll
        for (int i = 0; i < 4; ++i) t[i] = ld_pkt16(src + (q4 * 2 + (i >> 1)) * 512 + (i & 1) * 8);
        const bool ok_ = __all_sync(0xffffffffu, t[0].w == ep && t[1].w == ep && t[2].w == ep && t[3].w == ep);
        if (n < 4) CS(14 + n);
        if (ok_) break;
        SPIN_GUARD(n);
    }
    float v[4];
#pragma unroll
    for (int h = 0; h < 2; ++h) { v[h] = __uint_as_float(t[h].y) + __uint_as_float(t[2 + h].y); v[2 + h] = __uint_as_float(t[h].z) + __uint_as_float(t[2 + h].z); }
#pragma unroll
    for (int o = 1; o < 4; o <<= 1)
#pragma unroll
        for (int i = 0; i < 4; ++i) v[i] += __shfl_xor_sync(0xffffffffu, v[i], o);
    const float m0 = v[0] * (1.f / D_), m1 = v[1] * (1.f / D_);
    const float r0 = rsq(fmaxf(fmaf(-m0, m0, v[2] * (1.f / D_)), 0.f) + 1e-5f), r1 = rsq(fmaxf(fmaf(-m1, m1, v[3] * (1.f / D_)), 0.f) + 1e-5f);
    return LnRow{r0, -m0 * r0, r1, -m1 * r1};
}
struct Stg {
    uint32_t b, par;
    __device__ __forceinline__ uint32_t acquire2(uint32_t sb, uint32_t wg) {
        mbar_wait2(BAR_SREADY(sb, wg * 2), BAR_SREADY(sb, wg * 2 + 1), par);
        par ^= 1;
        return sb + OFF_STG + wg * 16384;
    }
    __device__ __forceinline__ void publish(uint32_t sb, uint32_t wg, uint32_t lane) {
        fence_async_smem();
        __syncwarp();
        if (lane == 0) mbar_arrive(BAR_SFULL(sb, wg * 2 + b));
        b ^= 1;
    }
};

struct LnPar {
    uint4 p[8];
    __device__ __forceinline__ void load(uint32_t sb, uint32_t q4) {
#pragma unroll
        for (int i = 0; i < 8; ++i) p[i] = lds128(sb + OFF_PAR + i * 64 + q4 * 16);
    }
};
__device__ __forceinline__ void ln_norm(uint32_t (&xn)[32], const float (&x)[64], const LnRow& n) {
#pragma unroll
    for (int e = 0; e < 32; ++e) {
        const float rs = (e & 1) ? n.rs1 : n.rs0, nm = (e & 1) ? n.nm1 : n.nm0;
        xn[e] = pack2(fmaf(x[2 * e], rs, nm), fmaf(x[2 * e + 1], rs, nm));
    }
}
__device__ __forceinline__ void ln_emit(const uint32_t (&xr)[32], const LnPar& lp, uint32_t sb, uint32_t wg, const Idx& ix) {
#pragma unroll
    for (int i = 0; i < 8; ++i)
        stsm4(sb + OFF_STG + wg * 16384 + (i >> 2) * 8192 + (ix.pan ^ ((i & 3) << 5)), hfma2_bf16(xr[4 * i], lp.p[i].z, lp.p[i].x), hfma2_bf16(xr[4 * i + 1], lp.p[i].z, lp.p[i].x),
              hfma2_bf16(xr[4 * i + 2], lp.p[i].w, lp.p[i].y), hfma2_bf16(xr[4 * i + 3], lp.p[i].w, lp.p[i].y));
    fence_async_smem();
    __syncwarp();
    if (ix.lane < 2) mbar_arrive(BAR_SFULL(sb, wg * 2 + ix.lane));
    bar_sync(1 + wg, 128);
}
__device__ __forceinline__ void load_slab(uint32_t (&xr)[32], uint32_t buf) {
    IDX();
#pragma unroll
    for (int i = 0; i < 8; ++i) ldsm4(buf + (i >> 2) * 8192 + (pan_addr ^ ((i & 3) << 5)), xr[4 * i], xr[4 * i + 1], xr[4 * i + 2], xr[4 * i + 3]);
}
__device__ __forceinline__ void unpack_slab(float (&x)[64], const uint32_t (&xr)[32]) {
#pragma unroll
    for (int i = 0; i < 32; ++i) unpack2(xr[i], x[2 * i], x[2 * i + 1]);
}
__device__ __forceinline__ void store_slab(const float (&x)[64], uint32_t buf, uint32_t pitch, uint32_t pan, int i0, int i1) {
#pragma unroll
    for (int i = i0; i < i1; ++i)
        stsm4(buf + (i >> 2) * pitch + (pan ^ ((i & 3) << 5)), pack2(x[8 * i], x[8 * i + 1]), pack2(x[8 * i + 2], x[8 * i + 3]), pack2(x[8 * i + 4], x[8 * i + 5]), pack2(x[8 * i + 6], x[8 * i + 7]));
}
template <int NP, class Done>
__device__ __forceinline__ void fetch_halo(uint4* src, bool first, uint32_t dst, Done done) {
    uint4 hv[4 * NP];
    uint32_t n = 0;
    while (true) {
        bool ok = true;
#pragma unroll
        for (int i = 0; i < 4 * NP; ++i) { hv[i] = first ? make_uint4(0, 0, 0, 0) : ld_pkt16(src + (i >> 2) * 256 + (i & 3) * 32); ok = ok && hv[i].x != 0; }
        if (first || __all_sync(0xffffffffu, ok)) break;
        SPIN_GUARD(n);
    }
#pragma unroll
    for (int i = 0; i < 4 * NP; ++i) stsm4(dst + (i >> 2) * 4096 + (i & 3) * 512, hv[i].x, hv[i].y, hv[i].z, hv[i].w);
    done();
    if (!first) {
#pragma unroll
        for (int i = 0; i < 4 * NP; ++i) src[(i >> 2) * 256 + (i & 3) * 32] = make_uint4(0, 0, 0, 0);
    }
}

template <int N, class G, class U>
__device__ __forceinline__ void glu(uint32_t (&h)[N], G g, U u) {
#pragma unroll
    for (int i = 0; i < N; ++i) h[i] = pack2(fmaf(tanh_(g(2 * i)), u(2 * i), u(2 * i)), fmaf(tanh_(g(2 * i + 1)), u(2 * i + 1), u(2 * i + 1)));
}
__device__ __forceinline__ void put_h(const uint32_t (&h)[32], uint32_t sb, uint32_t wg, Stg& stg) {
    IDX();
    const uint32_t buf = stg.acquire2(sb, wg);
#pragma unroll
    for (int k = 0; k < 8; ++k) stsm4(buf + (k >> 2) * 8192 + (pan_addr ^ ((k & 3) << 5)), h[4 * k], h[4 * k + 1], h[4 * k + 2], h[4 * k + 3]);
    fence_async_smem();
    __syncwarp();
    if (lane < 2) mbar_arrive(BAR_SFULL(sb, wg * 2 + lane));
}

template <int NP, bool PREV>
__device__ __forceinline__ void passes128(uint32_t (&hp)[32], uint32_t sb, uint32_t wg, uint32_t tw, Ring& r, Stg& stg) {
#pragma unroll 1
    for (int p = 0; p < NP; ++p) {
        float b256[128], none[1];
        const int put_at = !PREV && p == 0 ? -1 : wg ? PUT1 : PUT0;
        mainloop32<false, LAGS>(b256, none, sb, wg, tw, r, EV_LAG2 + p, 80 + 32 * (p & 1), [&](int it) { if (it == put_at) put_h(hp, sb, wg, stg); },
                                [&] { if (PREV || p < NP - 1) mbar_wait(BAR_FULL(sb, r.slot), r.par); });
        if (threadIdx.x == 0) { TL(29 + 2 * p); TC(114 + 2 * p); }
        if (threadIdx.x == 128) TL(53 + 2 * (p & 1));
        CS(24 + 2 * (p & 1));
        glu(hp, [&](int i) { return b256[i + (i & 32)]; }, [&](int i) { return b256[i + (i & 32) + 32]; });
        if (threadIdx.x == 0) { TL(30 + 2 * p); TC(115 + 2 * p); }
        if (threadIdx.x == 128) TL(54 + 2 * (p & 1));
        CS(25 + 2 * (p & 1));
    }
}

__global__ void __launch_bounds__(384, 1)
fused_block_kernel(const __grid_constant__ Ptrs pt, const __grid_constant__ Maps mp) {
    uint32_t* const g_flags = pt.mail->flags;
    uint2* const g_mod = pt.mail->mod;
    uint4* const g_st1 = pt.mail->st1;
    uint32_t* const g_par2 = pt.mail->par2;
    uint4* const g_halo = pt.mail->halo;
    const __nv_bfloat16* __restrict__ cvec = pt.c;
    if (threadIdx.x == 224) { prefetch_map(&mp.wm8); prefetch_map(&mp.x); }
    extern __shared__ __align__(1024) uint8_t smem[];
    const uint32_t sb = smem_u32(smem);
    const uint32_t tid = threadIdx.x, tw = tid & 127, lane = tid & 31;
    const uint32_t warp = __shfl_sync(0xffffffffu, tid >> 5, 0), wg = warp >> 2;
    uint32_t rank; asm("mov.u32 %0, %%cluster_ctarank;" : "=r"(rank));
    rank = __shfl_sync(0xffffffffu, rank, 0);
    uint32_t ep;
    uint32_t smid; asm volatile("mov.u32 %0, %%smid;" : "=r"(smid));
    const int c = __shfl_sync(0xffffffffu, smid >> 1, 0);
    const int c7 = ((c - 32) * 37) >> 8;
    int grp = c < 32 ? c & 7 : c < 60 ? c - 31 - 7 * c7 : c < 62 ? -1 : 0;
    const int j = c < 32 ? c >> 3 : c < 60 ? 4 + c7 : c < 62 ? (c - 60) * 2 + rank : c - 58;
    const bool aux = grp < 0;
    const int m = grp * 2 + rank;
    uint4* const g_st2 = g_halo + (m > 0 ? (m - 1) * 8 * 512 : 128);

    bool cluster_arrive_early = false;
    if (wg < 2) {
      if (!KDEBUG) cluster_arrive();
      ep = flag_get(g_flags + FL_DONE);
      uint16_t cw[8];
      {
          const __nv_bfloat16* cp = cvec + ((tw >> 5) * 32 + (tw & 3) * 2) * 8 + (lane >> 2);
#pragma unroll
          for (int i = 0; i < 8; ++i) asm volatile("ld.global.nc.u16 %0, [%1];" : "=h"(cw[i]) : "l"(cp + (i >> 1) * 64 + (i & 1) * 8));
      }
      asm volatile("setmaxnreg.inc.sync.aligned.u32 224;");
      if (tid == 0) TL(58);
      if (KDEBUG) cluster_arrive();
      Ring r{0, 0};
      Stg stg{0, 0};
      if (aux) {
        if (wg == 0) {
            const uint4 cv = *(const uint4*)(cvec + tw * 8);
            sts128(sb + OFF_STG + (tw >> 3) * 1024 + (tw & 7) * 16, pack2(silu_(bf_lo(cv.x)), silu_(bf_hi(cv.x))), pack2(silu_(bf_lo(cv.y)), silu_(bf_hi(cv.y))),
                   pack2(silu_(bf_lo(cv.z)), silu_(bf_hi(cv.z))), pack2(silu_(bf_lo(cv.w)), silu_(bf_hi(cv.w))));
            fence_async_smem();
        }
        cluster_wait();
        ep = __shfl_sync(0xffffffffu, ep, 0) / NCTA + 1;
        if (wg == 0) {
            bar_sync(1, 128);
#pragma unroll 1
            for (int p = 0; p < 4; ++p) {
                float acc[4][4] = {};
                uint32_t prev = 0;
#pragma unroll 1
                for (int kc = 0; kc < 16; ++kc) {
                    mbar_wait(BAR_FULL(sb, r.slot), r.par);
                    wg_fence();
#pragma unroll
                    for (int k = 0; k < 16; ++k)
                        wgmma_n8_ta(acc[k & 3], mk_desc(d16(sb) + r.slot * (SLOT >> 4), (k & 3) * 8192 + (k >> 2) * 2048, 8192, 1024, 1), mk_desc(d16(sb) + kc * 64, OFF_STG + (k >> 2) * 32, 16, 1024, 1));
                    wg_commit();
                    wg_wait<1>();
                    if (kc > 0 && tw < 4) mbar_arrive(BAR_EMPTY(sb, prev));
                    prev = r.slot;
                    r.next();
                }
                wg_wait<0>();
                if (tw < 4) mbar_arrive(BAR_EMPTY(sb, prev));
                if (!(tw & 3)) {
#pragma unroll
                    for (int i = 0; i < 8; ++i) {
                        asm volatile("" : "+f"(acc[i >> 1][(i & 1) * 2]) :: "memory");
                        asm volatile("st.shared.u16 [%0], %1;" :: "r"(sb + OFF_TAB + ((i >> 1) * 64 + (tw >> 5) * 16 + (i & 1) * 8 + (lane >> 2)) * 2), "h"((uint16_t)pack2(acc[i >> 1][(i & 1) * 2], 0.f)) : "memory");
                    }
                }
                bar_sync(1, 128);
                const int vec = p ? 6 - p : 2, blk = (vec - 2) * 4 + j;
                const uint32_t val = lds32(sb + OFF_TAB + tw * 4);
                if (vec == 2 || vec == 5) st_pkt(g_mod + (8 + blk) * 128 + tw, val, ep);
                else {
                    const float one = vec == 4 ? 1.f : 0.f;
                    g_par2[((blk & 3) * 16 + (tw >> 3)) * 16 + (tw & 3) * 4 + (vec - 3) * 2 + ((tw >> 2) & 1)] =
                        pack2(0.5f * bf_round(one + bf_lo(val)), 0.5f * bf_round(one + bf_hi(val)));
                }
                bar_sync(1, 128);
                if (tw == 0) {
                    if (p == 3) asm volatile("red.release.gpu.global.add.u32 [%0], 1;" :: "l"(&g_flags[FL_LN2]) : "memory");
                    TL(1 + p);
                }
            }
            if (lane < 2) mbar_arrive_cta(BAR_ONE(sb, EV_P0), lane);
        }
        r = Ring{64 % NSLOT, (64 / NSLOT) & 1};
        mbar_wait(BAR_ONE(sb, EV_P0), 0);
        mbar_wait(BAR_FULL(sb, r.slot), r.par);
        uint32_t hp[32] = {};
        passes128<4, false>(hp, sb, wg, tw, r, stg);
        put_h(hp, sb, wg, stg);
      } else {
        float xs[64];
        uint32_t xp[32];
        {
            sts128(sb + tid * 16, pack2(silu_(bf_lo(cw[0])), silu_(bf_lo(cw[1]))), pack2(silu_(bf_lo(cw[2])), silu_(bf_lo(cw[3]))),
                   pack2(silu_(bf_lo(cw[4])), silu_(bf_lo(cw[5]))), pack2(silu_(bf_lo(cw[6])), silu_(bf_lo(cw[7]))));
            cluster_wait();
            ep = __shfl_sync(0xffffffffu, ep, 0) / NCTA + 1;
            load_slab(xp, stg.acquire2(sb, wg));
            unpack_slab(xs, xp);
            if (tid == 0) TL(24);
            if (tid == 128) TL(27);
        }
#pragma unroll 1
        for (int blk = 0; ; ++blk) {
        {
            IDX();
            uint4* const st = (blk ? g_st2 : g_st1 + m * 8 * 512) + wg * 64 + w4 * 16 + g8;
            RowAcc ra;
#pragma unroll
            for (int e = 0; e < 64; ++e) ra.add(e, xs[e]);
            ra.publish(st + j * 512, q4, ep);
            uint32_t t_pub = 0; if (PDLY) asm volatile("mov.u32 %0, %%clock;" : "=r"(t_pub));
            if (tid == 0) TL(blk ? 9 : 26);
            if (tid == 128 && blk) TL(34);
            if (blk) CS(11);
            LnPar lp;
            if (blk == 0) {
            uint4* const mod_out = pt.mail->mod1 + g8 * 512 + (m * 8 + j) * 4 + q4;
            if (wg == 0) {
                uint4 af[8];
#pragma unroll
                for (int i = 0; i < 8; ++i) af[i] = lds128(sb + w4 * 512 + i * 64 + q4 * 16);
                float c[4][4] = {};
#pragma unroll
                for (int i = 0; i < 8; ++i) {
                    if (!(i & 1)) mbar_wait(BAR_ONE(sb, EV_WIN + (i >> 1)), 0);
                    if (i == 6 && tid == 0) TL(25);
#pragma unroll
                    for (int h = 0; h < 2; ++h) {
                        uint32_t b0, b1, b2, b3;
                        ldsm4t(sb + 5 * SLOT + i * 4096 + w4 * 1024 + h * 512 + (lane & 15) * 32 + (lane >> 4) * 16, b0, b1, b2, b3);
                        mma16816(c[2 * h], h ? af[i].z : af[i].x, 0u, h ? af[i].w : af[i].y, 0u, b0, b1);
                        mma16816(c[2 * h + 1], h ? af[i].z : af[i].x, 0u, h ? af[i].w : af[i].y, 0u, b2, b3);
                    }
                }
                if (lane < 4) sts128(sb + OFF_TAB + w4 * 64 + lane * 16, __float_as_uint(c[0][0] + c[2][0]), __float_as_uint(c[0][1] + c[2][1]),
                                     __float_as_uint(c[1][0] + c[3][0]), __float_as_uint(c[1][1] + c[3][1]));
                if (lane < 2) mbar_arrive_cta(BAR_ONE(sb, EV_P0), lane);
                bar_sync(1, 128);
                if (w4 == 0) {
                    float a[4] = {0.f, 0.f, 0.f, 0.f};
#pragma unroll
                    for (int i = 0; i < 4; ++i) {
                        const uint4 t = lds128(sb + OFF_TAB + i * 64 + q4 * 16);
                        a[0] += __uint_as_float(t.x); a[1] += __uint_as_float(t.y); a[2] += __uint_as_float(t.z); a[3] += __uint_as_float(t.w);
                    }
                    const float add = m >= 8 ? 1.f : 0.f;
                    st_pkt16(mod_out, pack2(bf_round(a[0]) + add, bf_round(a[1]) + add), pack2(bf_round(a[2]) + add, bf_round(a[3]) + add), ep, 0);
                    if (tid == 0) TL(3);
                }
            } else if (LWAIT >= 0) mbar_wait(BAR_ONE(sb, EV_WIN + LWAIT), 0);
            } else {
                mbar_wait2(BAR_ONE(sb, EV_LN2), BAR_FULL(sb, 0), 0);
            }
            lp.load(sb, q4);
#pragma unroll
            for (int e = 0; e < 32; ++e) xp[e] = pack2(xs[2 * e], xs[2 * e + 1]);
            if (PDLY && blk) { uint32_t t1; do { asm volatile("mov.u32 %0, %%clock;" : "=r"(t1)); } while (t1 - t_pub < PDLY); }
            if (blk) CS(13);
            const LnRow n = merge_stats(st, q4, ep, sb);
            if (tid == 0) TL(blk ? 49 : 48);
            if (tid == 128) TL(blk ? 45 : 28);
            if (blk) CS(18);
            uint32_t xn[32];
            ln_norm(xn, xs, n);
            if (blk == 0) {
                mbar_wait2(BAR_FULL(sb, 0), BAR_ONE(sb, EV_PAR), 0);
                if (FD0 && wg == 0) { uint32_t t0, t1; asm volatile("mov.u32 %0, %%clock;" : "=r"(t0)); do { asm volatile("mov.u32 %0, %%clock;" : "=r"(t1)); } while (t1 - t0 < FD0); }
                lp.load(sb, q4);
            }
            ln_emit(xn, lp, sb, wg, ix);
            if (tid == 0) { TL(blk ? 36 : 8); TC(blk ? 109 : 103); }
            if (tid == 128) TL(blk ? 43 : 22);
            if (blk) CS(21);
        }
        uint32_t hp[32];
        if (blk == 0) {
        {
            float big[128], sml[64];
            step32<true, true>(big, sml, sb, wg, r.slot, 0);
            TS(0, 0);
            Pipe pp(sb, tw, r.slot);
            r.next();
#pragma unroll 1
            for (int it = 1; it < 32 - LAGQ; ++it) {
                pp.acquire<true>(sb, wg ? 0 : AF_REL, r);
                step32<true, false>(big, sml, sb, wg, r.slot, it < 4 ? it : -1);
                pp.issued(r.slot);
                TS(it, 0);
                r.next();
            }
            auto half = [&](uint32_t slot, bool rest) {
                const uint32_t st = d16(sb) + slot * (SLOT >> 4);
#pragma unroll
                for (int k = 0; k < 2; ++k) {
                    const uint64_t da = mk_desc(st + wg * 256, k * 32, 16, 512, 2);
                    if (rest) wgmma_n256(big, da, mk_desc(st, 8192 + k * 2048, 4096, 1024, 1)); else wgmma_n128(sml, da, mk_desc(st, 24576 + k * 2048, 4096, 1024, 1));
                }
            };
            auto rest = [&](bool each) {
                wg_fence();
#pragma unroll
                for (int it = 32 - LAGQ; it < 32; ++it) { if (each && it > 32 - LAGQ) wg_fence(); half(it % NSLOT, true); if (each || it == 31) wg_commit(); }
            };
            stg.acquire2(sb, wg); mbar_wait2(BAR_SREADY(sb, 2), BAR_SREADY(sb, 3), 1);
#pragma unroll 1
            for (int it = 32 - LAGQ; it < 32; ++it) {
                pp.acquire<true>(sb, wg ? 0 : AF_REL, r);
                wg_fence(); half(r.slot, false); wg_commit();
                pp.issued(NSLOT);
                TS(it, 0);
                r.next();
            }
            if (wg) { rest(false); wg_wait<1>(); } else wg_wait<0>();
            CS(8);
            IDX();
            uint32_t k0[8], k1[8], k2[8], v0[8], v1[8], v2[8];
            const uint32_t nxt = warp + ((warp & 1) ? 3 : 1), mine = sb + OFF_STG + wg * 16384 + w4 * 2048;
            auto tails = [&](const float* kv, uint32_t (&kt)[8], uint32_t (&vt)[8]) {
#pragma unroll
                for (int t = 0; t < 8; ++t) { kt[t] = pack2(kv[4 * t + 2], kv[4 * t + 3]); vt[t] = pack2(kv[32 + 4 * t + 2], kv[32 + 4 * t + 3]); }
            };
            auto post = [&](int pn, uint32_t (&kt)[8], uint32_t (&vt)[8]) {
                uint4* dst = g_halo + (m * 8 + j) * 512 + (w4 >> 1) * 256 + pn * 128 + lane;
#pragma unroll
                for (int h = 0; h < 2; ++h) { if (!kt[4 * h]) kt[4 * h] = 0x8000u; if (!vt[4 * h]) vt[4 * h] = 0x8000u; }
#pragma unroll
                for (int h = 0; h < 2; ++h) { st_pkt16(dst + h * 32, kt[4 * h], kt[4 * h + 1], kt[4 * h + 2], kt[4 * h + 3]); st_pkt16(dst + 64 + h * 32, vt[4 * h], vt[4 * h + 1], vt[4 * h + 2], vt[4 * h + 3]); }
            };
            auto prepare = [&](int pn, const float* kv) {
                tails(kv, k2, v2);
                if (nxt < 8) {
                    const uint32_t dst = sb + OFF_STG + (nxt >> 2) * 16384 + (nxt & 3) * 2048 + pn * 8192 + lane * 16;
#pragma unroll
                    for (int h = 0; h < 2; ++h) { stsm4(dst + h * 512, k2[4 * h], k2[4 * h + 1], k2[4 * h + 2], k2[4 * h + 3]); stsm4(dst + 1024 + h * 512, v2[4 * h], v2[4 * h + 1], v2[4 * h + 2], v2[4 * h + 3]); }
                    if (pn == 0) bar_arrive(NB_TAIL + nxt, 64);
                    else { __syncwarp(); if (lane == 0) mbar_arrive(BAR_ONE(sb, EV_TAIL + nxt)); }
                } else if (pn == 0 && m < 15) post(0, k2, v2);
#pragma unroll
                for (int t = 0; t < 8; ++t) { k1[t] = pack2(kv[4 * t], kv[4 * t + 1]); v1[t] = movm(pack2(kv[32 + 4 * t], kv[32 + 4 * t + 1])); v2[t] = movm(v2[t]); }
                if (pn == 0) { CS(2); if (wg == 0) { rest(true); wg_wait<3>(); pp.rel(28 % NSLOT); wg_wait<2>(); pp.rel(29 % NSLOT); wg_wait<1>(); pp.rel(30 % NSLOT); } bar_sync(NB_TAIL + warp, 64); CS(4); }
                else mbar_wait(BAR_ONE(sb, EV_TAIL + __shfl_sync(0xffffffffu, warp, 0)), 0);
#pragma unroll
                for (int h = 0; h < 2; ++h) {
                    ldsm4(mine + pn * 8192 + lane * 16 + h * 512, k0[4 * h], k0[4 * h + 1], k0[4 * h + 2], k0[4 * h + 3]);
                    ldsm4t(mine + pn * 8192 + lane * 16 + 1024 + h * 512, v0[4 * h], v0[4 * h + 1], v0[4 * h + 2], v0[4 * h + 3]);
                }
            };
#pragma unroll
            for (int i = 0; i < 64; ++i) asm volatile("" : "+f"(sml[i]) :: "memory");
            prepare(0, sml);
            static_assert(LAGQ == 4, "");
            wg_wait<0>();
            if (wg) { pp.rel(28 % NSLOT); pp.rel(29 % NSLOT); pp.rel(30 % NSLOT); }
            pp.rel(31 % NSLOT);
            TS(31, 1);
            if (tid == 0) { TL(4); TC(104); }
            if (tid == 128) TL(50);
            CS(1);
#pragma unroll
            for (int i = 0; i < 128; ++i) asm volatile("" : "+f"(big[i]) :: "memory");
            if (nxt >= 8 && m < 15) { uint32_t kt[8], vt[8]; tails(big, kt, vt); post(1, kt, vt); }
            const bool lo0 = q4 * 2 > g8, lo1 = q4 * 2 + 1 > g8;
            const bool nopast = m == 0 && (warp & 5) == 0;
            const uint32_t lomask = (lo0 ? 0xFFFFu : 0u) | (lo1 ? 0xFFFF0000u : 0u);
            const uint32_t orow = mine + (lane & 7) * 128 + (((lane >> 3) ^ (lane & 7)) << 4);
            const float sl2 = 0.17677669529663687f * 1.4426950408889634f;
#pragma unroll
            for (int pn = 0; pn < 2; ++pn) {
                float e0[4], e1[4], mx[4], sum[4];
#pragma unroll
                for (int hh = 0; hh < 2; ++hh) {
                    uint32_t qf[8];
#pragma unroll
                    for (int i = 0; i < 8; ++i) qf[i] = pack2(big[64 + 32 * pn + 16 * hh + 2 * i], big[64 + 32 * pn + 16 * hh + 2 * i + 1]);
                    float s[3][4];
#pragma unroll
                    for (int t = 0; t < 3; ++t) {
                        const uint32_t* k = (t == 0 ? k0 : t == 1 ? k1 : k2) + 4 * hh;
                        s[t][0] = s[t][1] = s[t][2] = s[t][3] = 0.f;
                        mma16816(s[t], qf[0], qf[1], qf[2], qf[3], k[0], k[1]);
                        mma16816(s[t], qf[4], qf[5], qf[6], qf[7], k[2], k[3]);
                    }
#pragma unroll
                    for (int hf = 0; hf < 2; ++hf) {
                        const int u = hh * 2 + hf;
                        e0[u] = lo0 ? ((hf == 0 && nopast) ? -INFINITY : s[hf][hf * 2]) : s[hf + 1][hf * 2];
                        e1[u] = lo1 ? ((hf == 0 && nopast) ? -INFINITY : s[hf][hf * 2 + 1]) : s[hf + 1][hf * 2 + 1];
                        mx[u] = fmaxf(e0[u], e1[u]);
                    }
                }
#pragma unroll
                for (int o = 1; o < 4; o <<= 1)
#pragma unroll
                    for (int u = 0; u < 4; ++u) mx[u] = fmaxf(mx[u], __shfl_xor_sync(0xffffffffu, mx[u], o));
#pragma unroll
                for (int u = 0; u < 4; ++u) {
                    const float c = -mx[u] * sl2;
                    e0[u] = ex2(fmaf(e0[u], sl2, c)); e1[u] = ex2(fmaf(e1[u], sl2, c));
                    sum[u] = e0[u] + e1[u];
                }
#pragma unroll
                for (int o = 1; o < 4; o <<= 1)
#pragma unroll
                    for (int u = 0; u < 4; ++u) sum[u] += __shfl_xor_sync(0xffffffffu, sum[u], o);
#pragma unroll
                for (int u = 0; u < 4; ++u) {
                    const int h = u >> 1;
                    const float inv = rcp(sum[u]);
                    const uint32_t p = pack2(e0[u] * inv, e1[u] * inv);
                    const uint32_t* va = ((u & 1) ? v1 : v0) + 4 * h;
                    const uint32_t* vb = ((u & 1) ? v2 : v1) + 4 * h;
                    float o[2][4] = {};
#pragma unroll
                    for (int d = 0; d < 2; ++d) mma16816(o[d], va[2 * d], va[2 * d + 1], vb[2 * d], vb[2 * d + 1], p & lomask, p & ~lomask);
                    stsm4t((orow ^ ((u >> 1) << 6)) + pn * 8192 + (u & 1) * 1024, pack2(o[0][0], o[0][1]), pack2(o[0][2], o[0][3]), pack2(o[1][0], o[1][1]), pack2(o[1][2], o[1][3]));
                }
                fence_async_smem();
                __syncwarp();
                if (lane == 0) mbar_arrive(BAR_SFULL(sb, wg * 2 + pn));
                if (pn == 0) { CS(5); block_end(sb, 0); prepare(1, big); CS(3); }
            }
            CS(6);
            if (tid == 32) TL(41);
            mbar_wait2(BAR_FULL(sb, 32 % NSLOT), BAR_FULL(sb, 33 % NSLOT), (32 / NSLOT) & 1);
            load_slab(xp, sb + (32 % NSLOT + wg) * SLOT);
#pragma unroll
            for (int e = 0; e < 32; ++e) hp[e] = __float_as_uint(big[e]);
            bar_sync(1 + wg, 128);
            if (tid == 0) { TL(6); TC(106); }
            if (tid == 128) TL(44);
            CS(7);
        }
        } else {
        {
            float ag[88], au[88];
            mainloop32<true, LAG>(ag, au, sb, wg, tw, r, EV_LAG1, 48, [](int) {}, [&] {
                Ring q = r; if (!wg) q.next();
                mbar_wait(BAR_EMPTY(sb, q.slot), q.par ^ 1);
                mbar_wait(BAR_FULL(sb, r.slot), r.par);
            });
            if (tid == 0) { TL(10); TC(110); }
            if (tid == 128) TL(51);
            CS(22);
            {
                IDX();
                uint32_t h3[12];
                glu(h3, [&](int i) { return ag[64 + i]; }, [&](int i) { return au[64 + i]; });
#pragma unroll
                for (int k = 0; k < 3; ++k) stsm4(sb + (wg ? P3_SLOT1 : P3_SLOT0) * SLOT + 24576 + (pan_addr ^ (k << 5)), h3[4 * k], h3[4 * k + 1], h3[4 * k + 2], h3[4 * k + 3]);
            }
            glu(hp, [&](int i) { return ag[i]; }, [&](int i) { return au[i]; });
            if (tid == 0) { TL(11); TC(111); }
            if (tid == 128) TL(52);
            CS(23);
        }
        passes128<2, true>(hp, sb, wg, tw, r, stg);
        if (tid == 0) { TL(12); TC(112); }
        }
        {
            float acc[64], gf[32];
            mainloop64(acc, blk == 0, sb, wg, tw, r, [&] { put_h(hp, sb, wg, stg); }, [&] {
                mbar_wait(BAR_ONE(sb, EV_GA + blk), 0);
                unpack_slab(xs, xp);
                uint32_t gt[16];
#pragma unroll
                for (int cg = 0; cg < 16; ++cg) gt[cg] = lds32(sb + OFF_TAB + blk * 256 + cg * 16 + (tw & 3) * 4);
#pragma unroll
                for (int i = 0; i < 16; ++i) unpack2(gt[i], gf[2 * i], gf[2 * i + 1]);
            }, [&] { stg.acquire2(sb, wg); });
            if (tid == 0) { TL(blk ? 13 : 7); TC(blk ? 113 : 107); }
            if (tid == 128) TL(blk ? 57 : 42);
            CS(blk ? 30 : 10);
#pragma unroll
            for (int e = 0; e < 64; ++e) xs[e] = fmaf(gf[(e >> 2) * 2 + (e & 1)], acc[e], xs[e]);
        }
        if (blk) break;
        }
        {
            IDX();
#pragma unroll
            for (int p = 0; p < 2; ++p) {
                store_slab(xs, sb + OFF_STG + wg * 16384, 8192, pan_addr, 4 * p, 4 * p + 4);
                stg.publish(sb, wg, lane);
            }
            cluster_arrive();
            if (tid == 0) TL(14);
            CS(31);
        }
      }
    } else {
        if (warp == 8 && !aux && elect_one()) {
#pragma unroll
            for (int i = 0; i < 4; ++i) mbar_init(BAR_SREADY(sb, i), 1);
#pragma unroll
            for (int i = 0; i < 4; ++i) mbar_init(BAR_ONE(sb, EV_WIN + i), 1);
#pragma unroll
            for (int i = 0; i < 4; ++i) {
                mbar_expect_tx(BAR_SREADY(sb, i), 8192);
                tma_load3(sb + OFF_STG + i * 8192, &mp.x, j * 128 + (i & 1) * 64, m * 64 + (i >> 1) * 32, BAR_SREADY(sb, i));
            }
#pragma unroll 1
            for (int i = 0; i < 4; ++i) {
                mbar_expect_tx(BAR_ONE(sb, EV_WIN + i), 8192);
                tma_load(sb + 5 * SLOT + i * 8192, &mp.wm8, 2 * i * 6144 + (m * 8 + j) * 16, 0, BAR_ONE(sb, EV_WIN + i));
                tma_load(sb + 5 * SLOT + i * 8192 + 4096, &mp.wm8, (2 * i + 1) * 6144 + (m * 8 + j) * 16, 0, BAR_ONE(sb, EV_WIN + i));
            }
        }
        __syncwarp();
        asm volatile("setmaxnreg.dec.sync.aligned.u32 56;");
        if (elect_one()) {
            if (warp == 8) {
                prefetch_map(&mp.wqkv); prefetch_map(&mp.wmod);
            } else if (warp < 11) {
                mbar_init(BAR_EMPTY(sb, NSLOT), 1);
#pragma unroll
                for (int i = 0; i < 2; ++i) { mbar_init(BAR_SFULL(sb, (warp - 9) * 2 + i), 4); if (aux) mbar_init(BAR_SREADY(sb, (warp - 9) * 2 + i), 1); }
#pragma unroll
                for (int i = 0; i < 3; ++i) {
                    mbar_init(BAR_EMPTY(sb, (warp - 9) * 3 + i), 4);
                    mbar_init(BAR_FULL(sb, (warp - 9) * 3 + i), 1); mbar_init(BAR_FULL(sb, (warp - 9) * 3 + i) + AF_REL, 1);
                }
            } else {
#pragma unroll
                for (int i = EV_P0; i < EV_COUNT; ++i) mbar_init(BAR_ONE(sb, i), i == EV_P0 ? 8 : 1);
            }
            asm volatile("fence.mbarrier_init.release.cluster;" ::: "memory");
        }
        __syncwarp();
        cluster_arrive();
        ep = 0;
        if (warp != 8 || aux) ep = flag_get(g_flags + FL_DONE);
        cluster_wait();
        ep = __shfl_sync(0xffffffffu, ep, 0) / NCTA + 1;
        if (warp == 8) {
            const bool el = elect_one();
            Ring r{0, 1};
            if (aux) {
                {
                    uint32_t n = 0;
                    while (!__all_sync(0xffffffffu, ld_pkt16(pt.mail->mod1 + 256).z == ep)) { SPIN_GUARD(n); __nanosleep(200); }
                }
#pragma unroll 1
                for (int it = 0; it < 64; ++it) {
                    const int col = (it < 16 ? 2048 : 6144 - (it >> 4) * 1024) + j * 256;
                    mbar_wait(BAR_EMPTY(sb, r.slot), r.par);
                    const uint32_t st = sb + r.slot * SLOT, fb = BAR_FULL(sb, r.slot);
                    if (el) {
                        mbar_expect_tx(fb, 32768);
#pragma unroll
                        for (int b = 0; b < 4; ++b) tma_load_ef(st + b * 8192, &mp.wmod, col + b * 64, (it & 15) * 64, fb);
                    }
                    r.next();
                }
                mbar_wait(BAR_ONE(sb, EV_P0), 0);
                const CUtensorMap* wm = rank ? &mp.wu : &mp.wg;
#pragma unroll 1
                for (int g = 0; g < 128; ++g) {
                    const int mx = (j >> 1) * 8 + (g >> 5) * 2 + rank, k0 = ((g & 14) << 6) + ((g & 16) << 2) + ((g & 1) << 5);
                    if (!(g & 15) && g <= 32) mbar_wait(BAR_ONE(sb, EV_H0 + (g >> 4)), 0);
                    mbar_wait(BAR_EMPTY(sb, r.slot), r.par);
                    const uint32_t st = sb + r.slot * SLOT, fb = BAR_FULL(sb, r.slot);
                    if (el) {
                        mbar_expect_tx(fb, 24576);
                        tma_load_mc(st + 8192 + rank * 4096, wm, HC3, k0, fb);
                        tma_load_mc(st + 16384 + rank * 4096, wm, HC3 + 64, k0, fb);
                        tma_load(st, &mp.h2l, k0, mx * 128, fb);
                    }
                    r.next();
                }
            } else {
#pragma unroll 1
                for (int it = 0; it < 32; ++it) {
                    const int cb = j * 128 + rank * 64, k0 = kof(it, 2, j);
                    if (it == BW0) mbar_wait(BAR_ONE(sb, BWEV), 0);
                    if (it == BW1) mbar_wait(BAR_ONE(sb, EV_PAR), 0);
                    if (it == 5) mbar_wait(BAR_ONE(sb, EV_P0), 0);
                    if (it == AG0) mbar_wait(BAR_ONE(sb, (AGW & 1) ? EV_AGO : EV_FGO), 0);
                    mbar_wait(BAR_EMPTY(sb, r.slot), r.par);
                    const uint32_t st = sb + r.slot * SLOT, fb = BAR_FULL(sb, r.slot);
                    if (el) {
                        mbar_expect_tx(fb, it < 4 ? 24576 : 28672);
                        tma_load_mc(st + 24576 - rank * 16384, &mp.wqkv, 1024 + cb, k0, fb);
                        tma_load_mc(st + 28672 - rank * 16384, &mp.wqkv, 2048 + cb, k0, fb);
                        tma_load_mc(st + 16384 + rank * 4096, &mp.wqkv, cb, k0, fb);
                        if (it < 4) mbar_arrive(fb + AF_REL);
                        if (it == PFWO + (m >> 1)) { tma_prefetch(&mp.wo, j * 128, m * 64); tma_prefetch(&mp.wo, j * 128 + 64, m * 64); }
                        if (it >= PFG && it < PFG + PFN && (it & 7) == grp) {
                            const int kp = kof(it - PFG + PFO, 2, j);
                            tma_prefetch(rank ? &mp.wu : &mp.wg, hcol(0, j), kp); tma_prefetch(rank ? &mp.wu : &mp.wg, hcol(0, j) + 64, kp);
                            asm volatile("cp.async.bulk.prefetch.tensor.3d.L2.global [%0, {%1, %2, %3}];" :: "l"(rank ? &mp.wu3 : &mp.wg3), "r"(0), "r"(j), "r"(kp) : "memory");
                        }
                    }
                    r.next();
                }
                if (el) mbar_arrive(BAR_ONE(sb, EV_KV));
#pragma unroll 1
                for (int it = 0; it < 16; ++it) {
                    const int k0 = kof(it, 1, j);
                    if (it == AG1) mbar_wait(BAR_ONE(sb, (AGW & 2) ? EV_AGO1 : EV_FGO1), 0);
                    mbar_wait(BAR_EMPTY(sb, r.slot), r.par);
                    const uint32_t st = sb + r.slot * SLOT, fb = BAR_FULL(sb, r.slot);
                    if (el) {
                        mbar_expect_tx(fb, it < 2 ? 32768 : 24576);
                        tma_load_mc(st + 16384 + rank * 8192, &mp.wo, j * 128 + rank * 64, k0, fb);
                        if (it < 2) {
                            tma_load3(st, &mp.x, j * 128, m * 64 + it * 32, fb); tma_load3(st + 8192, &mp.x, j * 128 + 64, m * 64 + it * 32, fb);
                            mbar_arrive(fb + AF_REL);
                        }
                        if (it == 6) { prefetch_map(rank ? &mp.wu : &mp.wg); prefetch_map(rank ? &mp.wu3 : &mp.wg3); }
                    }
                    r.next();
                }
                const CUtensorMap* wm = rank ? &mp.wu : &mp.wg;
#pragma unroll 1
                for (int g = 0; g < 96; ++g) {
                    if (g == AG2) mbar_wait(BAR_ONE(sb, (AGW & 4) ? EV_AGO2 : EV_FGO2), 0);
                    const int p = g >> 5, cb = hcol(p, j), k0 = p == 0 ? kof(g, 2, j) : (g & 31) * 32;
                    mbar_wait(BAR_EMPTY(sb, r.slot), r.par);
                    const uint32_t st = sb + r.slot * SLOT, fb = BAR_FULL(sb, r.slot);
                    if (el) {
                        mbar_expect_tx(fb, (g < 4 || p > 0) ? 24576 : 28672);
                        tma_load_mc(st + 8192 + rank * 4096, wm, cb, k0, fb);
                        tma_load_mc(st + 16384 + rank * 4096, wm, cb + 64, k0, fb);
                        if (p == 0) tma_load3_mc(st + 24576 + rank * 4096, rank ? &mp.wu3 : &mp.wg3, j, k0, fb);
                        else tma_load(st, &mp.h2l, k0, m * 128, fb);
                        if (g < 4) mbar_arrive(fb + AF_REL);
                        if ((g & 7) == grp && g + PFC >= 96) tma_prefetch(&mp.wd, j * 128 + rank * 64, (g + PFC - 96) * 64);
                        if (g == 60) { prefetch_map(&mp.wd); prefetch_map(&mp.hb); }
                    }
                    r.next();
                }
#pragma unroll 1
                for (int g = 0; g < 56; ++g) {
                    if (g == 0 || (g & 15) == 6 && g > 6) mbar_wait(BAR_ONE(sb, EV_H0 + (g >> 4)), 0);
                    const int k0 = g * 64;
                    mbar_wait(BAR_EMPTY(sb, r.slot), r.par);
                    const uint32_t st = sb + r.slot * SLOT, fb = BAR_FULL(sb, r.slot);
                    if (el) {
                        mbar_expect_tx(fb, 32768);
                        tma_load_mc(st + 16384 + rank * 8192, &mp.wd, j * 128 + rank * 64, k0, fb);
                        tma_load(st, &mp.hb, k0, m * 128, fb); tma_load(st + 8192, &mp.hb, k0, m * 128 + 64, fb);
                        if ((g & 7) == grp && g + PFC < 56) tma_prefetch(&mp.wd, j * 128 + rank * 64, k0 + PFC * 64);
                    }
                    r.next();
                }
            }
        } else if (aux) {
            if (warp < 11) {
                const uint32_t w = warp - 9;
                const bool el = elect_one();
#pragma unroll 1
                for (int p = 0; p < 4; ++p) {
                    const int mx = (j >> 1) * 8 + p * 2 + rank;
                    if (el) { mbar_arrive(BAR_SREADY(sb, w * 2)); mbar_arrive(BAR_SREADY(sb, w * 2 + 1)); }
                    mbar_wait2(BAR_SFULL(sb, w * 2), BAR_SFULL(sb, w * 2 + 1), p & 1);
                    if (p < 3) pause(w ? HD1 : HD0);
                    if (el) tma_store(&mp.hb, HC3, mx * 128 + w * 64, sb + OFF_STG + w * 16384);
                    if (p < 3) pause(HP);
                    if (el) {
                        tma_store(&mp.hb, HC3 + 64, mx * 128 + w * 64, sb + OFF_STG + w * 16384 + 8192);
                        bulk_commit(); bulk_wait_fence(); flag_set(g_flags + FL_AUX + mx * 2 + w, ep * 8 + ST_H + 3);
                    }
                }
            } else {
                mbar_wait(BAR_ONE(sb, EV_P0), 0);
#pragma unroll 1
                for (int i = 0; i < 5; ++i) {
                    const uint32_t* f = g_flags + FL_PROG + fidx((j >> 1) * 8 + (i ? i - 1 : 0) * 2 + rank, lane >> 4, lane & (i ? 15 : 14));
                    uint32_t n = 0;
                    while (!__all_sync(0xffffffffu, (int32_t)(flag_get(f) - (ep * 8 + ST_H2)) >= 0)) { SPIN_GUARD(n); __nanosleep(200); }
                    if (i < 2) pause(AUXD);
                    if (lane == 0 && (i < 2 || i == 4)) mbar_arrive(BAR_ONE(sb, EV_H0 + (i < 2 ? i : 2)));
                }
            }
        } else if (warp == 11) {
            const bool el = elect_one();
            const int row0 = m * 128;
            const uint32_t* const fl = g_flags + FL_PROG + fidx(m, lane >> 4, kof(lane & 15, 1, j) >> 6);
            if (el) { prefetch_map(&mp.h1h); prefetch_map(&mp.h2h); prefetch_map(&mp.h2l); }
            auto gate = [&](int vec, int ev) {
                uint4 v; uint32_t n = 0;
                while (true) {
                    v = ld_pkt2(g_mod + vec * 512 + j * 64 + lane * 2);
                    if (__all_sync(0xffffffffu, v.y == ep && v.w == ep)) break;
                    SPIN_GUARD(n); __nanosleep(300);
                }
                asm volatile("st.shared.v2.u32 [%0], {%1, %2};" :: "r"(sb + OFF_TAB + (ev - EV_GA) * 256 + lane * 8), "r"(v.x), "r"(v.z) : "memory");
                __syncwarp();
                if (lane == 0) mbar_arrive(BAR_ONE(sb, ev));
            };
            {
                const uint4* pk = pt.mail->mod1 + grp * 512 + j * 32 + lane;
                uint4 a, b; uint32_t n = 0;
                mbar_wait(BAR_ONE(sb, EV_WIN3), 0);
                while (true) {
                    a = ld_pkt16(pk); b = ld_pkt16(pk + 256);
                    if (__all_sync(0xffffffffu, a.z == ep && b.z == ep)) break;
                    SPIN_GUARD(n);
                }
                sts128(sb + OFF_PAR + lane * 16, a.x, a.y, b.x, b.y);
                __syncwarp();
                if (lane == 0) { mbar_arrive(BAR_ONE(sb, EV_PAR)); TL(46); }
            }
            mbar_wait(BAR_ONE(sb, EV_P0), 0);
            Ring r{0, 1};
#pragma unroll 1
            for (int ph = 0; ph < 3; ++ph) {
                const int sh = ph == 1 ? 1 : 2, nst = 8 << sh;
                const uint32_t half = 16384 >> sh, target = ep * 8 + ST_H1 + ph;
                const CUtensorMap* tm = ph == 0 ? &mp.h1h : ph == 1 ? &mp.o : &mp.h2h;
                if (ph == 1) {
                    gate(2, EV_GA);
                    mbar_wait(BAR_SREADY(sb, 1), 1);
#pragma unroll 1
                    for (int i = 0; i < 2; ++i)
                        fetch_halo<1>(g_halo + ((m - 1) * 8 + j) * 512 + i * 256 + 128 + lane, m == 0, sb + OFF_STG + 8192 + i * 4096 + lane * 16,
                                      [&] { __syncwarp(); if (el) mbar_arrive(BAR_ONE(sb, EV_TAIL + 2 * i)); });
                    CS(32);
                }
                if (ph == 2) {
                    uint32_t n = 0;
                    while ((int32_t)(flag_get(g_flags + FL_LN2) - ep * 4) < 0) { SPIN_GUARD(n); __nanosleep(200); }
                    const uint4 v = __ldcg((const uint4*)(g_par2 + j * 128) + lane);
                    sts128(sb + OFF_PAR + lane * 16, v.x, v.y, v.z, v.w);
                    __syncwarp();
                    if (lane == 0) mbar_arrive(BAR_ONE(sb, EV_LN2));
                }
                const uint32_t lw = ~lane & 1, lt = lane >> 1, ls = (r.slot + lt) % NSLOT, lk = kof(lt, sh, j), lb = BAR_FULL(sb, ls) + (lw ? 0 : AF_REL);
                const uint32_t* const lf = g_flags + FL_PROG + fidx(m, lw, lk >> 6);
                int fr = 1 << sh;
                uint32_t todo = 0x3ffffu >> (2 * fr) << (2 * fr), have = ~todo, n = 0, v = 0;
                r.skip(fr);
#pragma unroll 1
                for (; fr < NSLOT; ++fr) { mbar_wait(BAR_EMPTY(sb, r.slot), r.par); r.next(); }
                if (ph == XST - 1) CS(33);
                v = flag_get(lf);
                do {
                    while (ph == 2 && fr < FRCAP && mbar_test(BAR_EMPTY(sb, r.slot), r.par)) { ++fr; r.next(); }
                    SPIN_GUARD(n);
                    const bool ok = (int32_t)(v - target) >= 0;
                    v = flag_get(lf);
                    have |= __ballot_sync(0xffffffffu, ok);
                    const uint32_t go = have & todo & ((1u << (2 * fr)) - 1);
                    if ((go >> lane) & 1) {
                        if (!lw) mbar_expect_tx(lb, half);
                        tma_load(sb + ls * SLOT + lw * half, tm, lk, row0 + lw * 64, lb);
                    }
                    __syncwarp();
                    if (lane < 2 && (todo & (0x555u << lane)) && !(todo & ~go & (0x555u << lane))) mbar_arrive(BAR_ONE(sb, (lane ? EV_FGO : EV_AGO) + ph));
                    if (ph == XST - 1) { if (go & (1u << (2 << sh))) CS(34); if (go & (2u << (2 << sh))) CS(35); if (todo & 0x555u) CS(36); if (todo & 0xaaau) CS(37); }
                    todo &= ~go;
                } while (~have);
                if (ph == XST - 1) CS(38);
                int k = kof(fr, sh, j);
#pragma unroll 1
                for (; fr < nst; ++fr) {
                    if (fr == 9 || fr == 18) {
                        const uint32_t skip = fr == 9 << (sh - 1) ? 0 : ~0x01fc01fcu;
                        while (~(__ballot_sync(0xffffffffu, (int32_t)(flag_get(fl) - target) >= 0) | skip)) SPIN_GUARD(n);
                    }
                    const uint32_t st = sb + r.slot * SLOT, fb = BAR_FULL(sb, r.slot);
                    mbar_wait(BAR_EMPTY(sb, r.slot), r.par);
                    if (el) {
                        tma_load(st + half, tm, k, row0 + 64, fb);
                        mbar_expect_tx(fb + AF_REL, half);
                        tma_load(st, tm, k, row0, fb + AF_REL);
                    }
                    if (ph == XST - 1 && fr == 9) CS(39);
                    r.next();
                    k = kof(fr + 1, sh, j);
                }
            }
#pragma unroll 1
            for (int p = 0; p < 4; ++p) {
                const uint32_t* f = p < 3 ? fl : g_flags + FL_AUX + m * 2 + (lane & 1);
                uint32_t n = 0;
                while (!__all_sync(0xffffffffu, (int32_t)(flag_get(f) - (ep * 8 + ST_H + p)) >= 0)) { SPIN_GUARD(n); __nanosleep(300); }
                if (el) mbar_arrive(BAR_ONE(sb, EV_H0 + p));
                if (p == 0) gate(5, EV_GB);
            }
        } else {
            const uint32_t w = warp - 9;
            const int row0 = m * 128 + w * 64;
            const uint32_t stg = sb + OFF_STG + w * 16384;
            uint32_t* const fl = g_flags + FL_PROG + fidx(m, w, 2 * j);
            uint32_t b = 0, par = 0;
            const bool el = elect_one();
            auto store = [&](const CUtensorMap* tm, int col, bool nat = false) {
                mbar_wait(BAR_SFULL(sb, w * 2 + b), (par >> b) & 1);
                par ^= 1u << b;
                if (el) {
                    if (nat) tma_store3(tm, col, row0 >> 1, 0, stg + b * 8192); else tma_store(tm, col, row0, stg + b * 8192);
                    bulk_commit();
                }
                b ^= 1;
            };
            auto send2 = [&](const CUtensorMap* tm, const uint32_t* buf, int step) {
                const uint32_t* const q = buf + (size_t)((row0 + lane) * (D_ / 2) + j * 64 + 31);
                store(tm, j * 128);
                if (step == XST) CS(33);
                uint32_t z = landed(el, q, D_ / 2, pt.zero);
                if (el) flag_set(fl, ep * 8 + step + z);
                if (step == XST) CS(34);
                if (step != ST_O) { mbar_wait(BAR_ONE(sb, EV_FGO + step - ST_H1), 0); pause(step == ST_H1 ? (w ? P1H : P1H + 1000) : w ? P2L : P2F); }
                store(tm, j * 128 + 64);
                if (step == XST) CS(35);
                z = landed(el, q + 32, D_ / 2, pt.zero);
                if (el) flag_set(fl + 1, ep * 8 + step + z);
                if (step == XST) CS(36);
            };
            auto free2 = [&]() { if (el) { mbar_arrive(BAR_SREADY(sb, w * 2)); mbar_arrive(BAR_SREADY(sb, w * 2 + 1)); } };
            if (el) { prefetch_map(&mp.h1s); prefetch_map(&mp.o); prefetch_map(&mp.out); prefetch_map(&mp.wo); }
            send2(&mp.h1s, pt.h1, ST_H1);
            if (w == 0) TL(47);
            free2();
            mbar_wait(BAR_ONE(sb, EV_KV), 0);
            mbar_wait(BAR_SREADY(sb, 0), 1);
            fetch_halo<1>(g_halo + ((m - 1) * 8 + j) * 512 + w * 256 + lane, m == 0, sb + OFF_STG + w * 4096 + lane * 16, [&] { bar_arrive(NB_TAIL + 2 * w, 64); CS(38); });
            send2(&mp.o, pt.o, ST_O);
            if (w == 0) TL(40); else TL(38);
            free2();
            send2(&mp.o, pt.o, ST_H2);
            if (el) { prefetch_map(&mp.hbs); prefetch_map(&mp.hb3); }
            if (w == 0) TL(37);
            free2();
#pragma unroll 1
            for (int p = 0; p < 3; ++p) {
                const int col = hcol(p, j);
                mbar_wait2(BAR_SFULL(sb, w * 2), BAR_SFULL(sb, w * 2 + 1), par & 1);
                par ^= 3;
#pragma unroll 1
                for (int i = 0; i < (p ? 2 : 3) * NSPL; ++i) {
                    pause(i ? HP / NSPL : p == 2 ? (w ? HE1 : HE0) : w ? HD1 : HD0);
                    const int pn = i / NSPL, ro = (i % NSPL) * (64 / NSPL);
                    if (el) {
                        if (pn < 2) tma_store(&mp.hbs, col + pn * 64, row0 + ro, stg + i * (8192 / NSPL));
                        else tma_store3(&mp.hb3, 0, j, row0 + ro, sb + (w ? P3_SLOT1 : P3_SLOT0) * SLOT + 24576 + ro * 128);
                        bulk_commit();
                    }
                }
                if (el) bulk_wait_read();
                free2();
                if (el) { bulk_wait_fence(); flag_set(fl, ep * 8 + ST_H + p); flag_set(fl + 1, ep * 8 + ST_H + p); }
            }
            cluster_arrive_early = true;
            cluster_arrive();
            store(&mp.out, j * 128, true); store(&mp.out, j * 128 + 64, true);
            if (el) bulk_wait_read();
        }
        __syncwarp();
    }
    if (aux || (wg == 2 && !cluster_arrive_early)) cluster_arrive();
    cluster_wait();
    if (KDEBUG == 5) __syncthreads();
    if (tid == 0) {
        TL(15);
        flag_add(pt.mail->flags + FL_DONE);
    }
}

typedef CUresult (*EncodeFn)(CUtensorMap*, CUtensorMapDataType, cuuint32_t, void*, const cuuint64_t*, const cuuint64_t*, const cuuint32_t*,
                             const cuuint32_t*, CUtensorMapInterleave, CUtensorMapSwizzle, CUtensorMapL2promotion, CUtensorMapFloatOOBfill);

void make_map(EncodeFn fn, CUtensorMap* m, const void* ptr, uint64_t rows, uint64_t cols, uint32_t brows, uint32_t bcols) {
    cuuint64_t dims[2] = {cols, rows}, strides[1] = {cols * 2};
    cuuint32_t box[2] = {bcols, brows}, es[2] = {1, 1};
    fn(m, CU_TENSOR_MAP_DATA_TYPE_BFLOAT16, 2, (void*)ptr, dims, strides, box, es, CU_TENSOR_MAP_INTERLEAVE_NONE,
       bcols == 64 ? CU_TENSOR_MAP_SWIZZLE_128B : bcols == 32 ? CU_TENSOR_MAP_SWIZZLE_64B : CU_TENSOR_MAP_SWIZZLE_NONE, CU_TENSOR_MAP_L2_PROMOTION_L2_256B, CU_TENSOR_MAP_FLOAT_OOB_FILL_NONE);
}

void make_map3(EncodeFn fn, CUtensorMap* m, const void* ptr) {
    cuuint64_t dims[3] = {D_, S_ / 2, 2}, strides[2] = {4 * D_, 2 * D_};
    cuuint32_t box[3] = {64, 32, 2}, es[3] = {1, 1, 1};
    fn(m, CU_TENSOR_MAP_DATA_TYPE_BFLOAT16, 3, (void*)ptr, dims, strides, box, es, CU_TENSOR_MAP_INTERLEAVE_NONE,
       CU_TENSOR_MAP_SWIZZLE_128B, CU_TENSOR_MAP_L2_PROMOTION_L2_256B, CU_TENSOR_MAP_FLOAT_OOB_FILL_NONE);
}

void make_map48(EncodeFn fn, CUtensorMap* m, const void* ptr, uint64_t rows, uint32_t brows) {
    cuuint64_t dims[3] = {48, 8, rows}, strides[2] = {96, 2 * F_};
    cuuint32_t box[3] = {64, 1, brows}, es[3] = {1, 1, 1};
    fn(m, CU_TENSOR_MAP_DATA_TYPE_BFLOAT16, 3, (void*)ptr, dims, strides, box, es, CU_TENSOR_MAP_INTERLEAVE_NONE,
       CU_TENSOR_MAP_SWIZZLE_128B, CU_TENSOR_MAP_L2_PROMOTION_L2_256B, CU_TENSOR_MAP_FLOAT_OOB_FILL_NONE);
}

}

extern "C" void kernel_launch(void* const* d_in, const int* in_sizes, int n_in, void* d_out, int out_size) {
    (void)in_sizes; (void)n_in; (void)out_size;
    void* fnp = nullptr;
    cudaDriverEntryPointQueryResult qr;
    cudaGetDriverEntryPoint("cuTensorMapEncodeTiled", &fnp, cudaEnableDefault, &qr);
    EncodeFn fn = (EncodeFn)fnp;
    void *h1, *o, *h2, *hb, *mail;
    cudaGetSymbolAddress(&h1, g_h1);
    cudaGetSymbolAddress(&mail, g_mail);
    cudaGetSymbolAddress(&o, g_o);
    cudaGetSymbolAddress(&hb, g_hb);
    h2 = o;
    Maps mp;
    make_map(fn, &mp.h1h, h1, S_, D_, 64, 32);
    make_map(fn, &mp.h2h, h2, S_, D_, 64, 32);
    make_map(fn, &mp.h1s, h1, S_, D_, 64, 64);
    make_map(fn, &mp.o, o, S_, D_, 64, 64);
    make_map(fn, &mp.h2l, h2, S_, D_, 128, 32);
    make_map(fn, &mp.hb, hb, S_, F_, 64, 64);
    make_map(fn, &mp.wqkv, d_in[1], D_, 3 * D_, 32, 64);
    make_map(fn, &mp.wo, d_in[2], D_, D_, 64, 64);
    make_map(fn, &mp.wg, d_in[4], D_, F_, 32, 64);
    make_map(fn, &mp.wu, d_in[5], D_, F_, 32, 64);
    make_map(fn, &mp.wd, d_in[6], F_, D_, 64, 64);
    make_map(fn, &mp.wmod, d_in[8], D_, 6 * D_, 64, 64);
    make_map(fn, &mp.wm8, d_in[8], D_ / 8, 8 * 6 * D_, 128, 16);
    make_map3(fn, &mp.x, d_in[0]);
    make_map3(fn, &mp.out, d_out);
    make_map48(fn, &mp.wg3, d_in[4], D_, 32);
    make_map48(fn, &mp.wu3, d_in[5], D_, 32);
    make_map48(fn, &mp.hb3, hb, S_, 64 / NSPL);
    make_map(fn, &mp.hbs, hb, S_, F_, 64 / NSPL, 64);
    cudaFuncSetAttribute(fused_block_kernel, cudaFuncAttributeMaxDynamicSharedMemorySize, SMEM_BYTES);
    cudaLaunchConfig_t cfg = {};
    cfg.gridDim = dim3(NCTA); cfg.blockDim = dim3(384); cfg.dynamicSmemBytes = SMEM_BYTES; cfg.stream = cudaStreamPerThread;
    cudaLaunchAttribute at[1];
    at[0].id = cudaLaunchAttributeClusterDimension; at[0].val.clusterDim.x = 2; at[0].val.clusterDim.y = 1; at[0].val.clusterDim.z = 1;
    cfg.attrs = at; cfg.numAttrs = 1;
    const Ptrs pt{(const __nv_bfloat16*)d_in[7], (Mail*)mail, (const uint32_t*)h1, (const uint32_t*)o, 0};
    cudaLaunchKernelEx(&cfg, fused_block_kernel, pt, mp);
}
```

```cpp
#include <cuda_runtime.h>
#include <cuda_bf16.h>
#include <cuda.h>
#include <stdint.h>
#include <stddef.h>

#define LAG 4
#define LAGS 4
#define LAGW 2
#define LAGD 4
#define LAGQ 4
#define PUT1 5
#define PUT0 10
#define PUTD1 6
#define PUTD0 10
#define MIDD 40
#define HD1 3000
#define HD0 1500
#define NSPL 2
#define HE1 2000
#define HE0 HD0
#define HP 2600
#define P1H 3000
#define P2L 2000
#define P2F 3000
#define AUXD 4000
#define PDLY 500
#define FD0 200
#define AG0 6
#define AG1 6
#define AG2 8
#define AGW 2
#define FRCAP 7
#define BW0 0
#define BWEV EV_WIN
#define BW1 3
#define LWAIT 3
#define PFWO 12
#define PFG 8
#define PFN 24
#define PFC 10
#define PFO 0
#define KDEBUG 0
#define CSW 0
#define XST ST_O

namespace {

constexpr int S_ = 2048, D_ = 1024, F_ = 3584;
constexpr int NCTA = 132;
constexpr int NSLOT = 6;
constexpr uint32_t SLOT = 32768;
constexpr uint32_t OFF_STG = NSLOT * SLOT;
constexpr uint32_t OFF_BAR = OFF_STG + 32768;
constexpr uint32_t OFF_PAR = OFF_BAR + 512;
constexpr uint32_t OFF_TAB = OFF_PAR + 768;
constexpr uint32_t OFF_TL = OFF_PAR + 2048;
constexpr uint32_t SMEM_BYTES = OFF_TL + (KDEBUG ? 512 : 0);
constexpr uint32_t P3_SLOT1 = (32 + 16 + 32) % NSLOT, P3_SLOT0 = (P3_SLOT1 + 1) % NSLOT;

constexpr int ST_H1 = 1, ST_O = 2, ST_H2 = 3, ST_H = 4, FL_DONE = 0, FL_LN2 = 1, FL_AUX = 32, FL_PROG = 64;

struct Maps {
    CUtensorMap h1h, h1s, o, h2h, h2l, hb, wqkv, wo, wg, wu, wd, wmod, wm8, x, out, wg3, wu3, hb3, hbs;
};

struct Mail {
    uint32_t flags[16 * 32 + 64];
    uint2 mod[6 * D_ / 2];
    uint4 mod1[8 * 512];
    uint4 st1[128 * 512];
    uint32_t par2[D_];
    uint4 halo[128 * 512];
};
struct Ptrs { const __nv_bfloat16* c; Mail* mail; const uint32_t *h1, *o; uint32_t zero; };

__device__ __align__(128) Mail g_mail;
__device__ __align__(128) __nv_bfloat16 g_h1[S_ * D_];
__device__ __align__(128) __nv_bfloat16 g_o[S_ * D_];
__device__ __align__(128) __nv_bfloat16 g_hb[S_ * F_];
#define TL(i) do {} while (0)
#define TC(i) do {} while (0)
#define TS(g, which) do {} while (0)
#define CS(i) do {} while (0)

__device__ __forceinline__ uint32_t smem_u32(const void* p) { return (uint32_t)__cvta_generic_to_shared(p); }
__device__ __forceinline__ void mbar_init(uint32_t bar, uint32_t cnt) { asm volatile("mbarrier.init.shared::cta.b64 [%0], %1;" :: "r"(bar), "r"(cnt) : "memory"); }
__device__ __forceinline__ void mbar_expect_tx(uint32_t bar, uint32_t bytes) { asm volatile("mbarrier.arrive.expect_tx.shared::cta.b64 _, [%0], %1;" :: "r"(bar), "r"(bytes) : "memory"); }
__device__ __forceinline__ void mbar_arrive(uint32_t bar) { asm volatile("mbarrier.arrive.shared::cta.b64 _, [%0];" :: "r"(bar) : "memory"); }
__device__ __forceinline__ void mbar_arrive_cta(uint32_t bar, uint32_t cta) {
    asm volatile("{\n.reg .b32 r;\nmapa.shared::cluster.u32 r, %0, %1;\nmbarrier.arrive.shared::cluster.b64 _, [r];\n}" :: "r"(bar), "r"(cta) : "memory");
}
__device__ __forceinline__ void mbar_wait(uint32_t bar, uint32_t parity) {
    asm volatile("{\n.reg .pred p;\n.reg .u32 n;\nmov.u32 n, 0;\n"
        "W_LOOP:\nmbarrier.try_wait.parity.shared::cta.b64 p, [%0], %1;\n@p bra W_DONE;\n"
        "add.u32 n, n, 1;\nsetp.lt.u32 p, n, 0x400000;\n@p bra W_LOOP;\ntrap;\nW_DONE:\n}" :: "r"(bar), "r"(parity) : "memory");
}
__device__ __forceinline__ void mbar_wait2(uint32_t b0, uint32_t b1, uint32_t parity) {
    asm volatile("{\n.reg .pred p, q;\n.reg .u32 n;\nmov.u32 n, 0;\n"
        "W_LOOP:\nmbarrier.try_wait.parity.shared::cta.b64 p, [%0], %2;\nmbarrier.try_wait.parity.shared::cta.b64 q, [%1], %2;\nand.pred p, p, q;\n@p bra W_DONE;\n"
        "add.u32 n, n, 1;\nsetp.lt.u32 p, n, 0x400000;\n@p bra W_LOOP;\ntrap;\nW_DONE:\n}" :: "r"(b0), "r"(b1), "r"(parity) : "memory");
}
__device__ __forceinline__ bool mbar_test(uint32_t bar, uint32_t parity) {
    uint32_t r; asm volatile("{\n.reg .pred p;\nmbarrier.test_wait.parity.shared::cta.b64 p, [%1], %2;\nselp.u32 %0, 1, 0, p;\n}" : "=r"(r) : "r"(bar), "r"(parity) : "memory"); return r;
}
__device__ __forceinline__ bool mbar_test2(uint32_t b0, uint32_t b1, uint32_t parity) {
    uint32_t r;
    asm volatile("{\n.reg .pred p, q;\nmbarrier.test_wait.parity.shared::cta.b64 p, [%1], %3;\nmbarrier.test_wait.parity.shared::cta.b64 q, [%2], %3;\n"
        "and.pred p, p, q;\nselp.u32 %0, 1, 0, p;\n}" : "=r"(r) : "r"(b0), "r"(b1), "r"(parity) : "memory");
    return r;
}
__device__ __forceinline__ void tma_load3(uint32_t dst, const CUtensorMap* m, int c0, int c1, uint32_t bar) {
    asm volatile("cp.async.bulk.tensor.3d.shared::cluster.global.mbarrier::complete_tx::bytes [%0], [%1, {%3, %4, %5}], [%2];"
        :: "r"(dst), "l"(m), "r"(bar), "r"(c0), "r"(c1), "r"(0) : "memory");
}
__device__ __forceinline__ void tma_store3(const CUtensorMap* m, int c0, int c1, int c2, uint32_t src) {
    asm volatile("cp.async.bulk.tensor.3d.global.shared::cta.bulk_group [%0, {%2, %3, %4}], [%1];" :: "l"(m), "r"(src), "r"(c0), "r"(c1), "r"(c2) : "memory");
}
__device__ __forceinline__ void tma_load3_mc(uint32_t dst, const CUtensorMap* m, int c1, int c2, uint32_t bar) {
    asm volatile("cp.async.bulk.tensor.3d.shared::cluster.global.mbarrier::complete_tx::bytes.multicast::cluster.L2::cache_hint [%0], [%1, {%3, %4, %5}], [%2], %6, %7;"
        :: "r"(dst), "l"(m), "r"(bar), "r"(0), "r"(c1), "r"(c2), "h"((uint16_t)3), "l"(0x12F0000000000000ull) : "memory");
}
__device__ __forceinline__ void tma_load(uint32_t dst, const CUtensorMap* m, int c0, int c1, uint32_t bar) {
    asm volatile("cp.async.bulk.tensor.2d.shared::cluster.global.mbarrier::complete_tx::bytes [%0], [%1, {%3, %4}], [%2];"
        :: "r"(dst), "l"(m), "r"(bar), "r"(c0), "r"(c1) : "memory");
}
__device__ __forceinline__ void tma_load_ef(uint32_t dst, const CUtensorMap* m, int c0, int c1, uint32_t bar) {
    asm volatile("cp.async.bulk.tensor.2d.shared::cluster.global.mbarrier::complete_tx::bytes.L2::cache_hint [%0], [%1, {%3, %4}], [%2], %5;"
        :: "r"(dst), "l"(m), "r"(bar), "r"(c0), "r"(c1), "l"(0x12F0000000000000ull) : "memory");
}
__device__ __forceinline__ void tma_load_mc(uint32_t dst, const CUtensorMap* m, int c0, int c1, uint32_t bar) {
    asm volatile("cp.async.bulk.tensor.2d.shared::cluster.global.mbarrier::complete_tx::bytes.multicast::cluster.L2::cache_hint [%0], [%1, {%3, %4}], [%2], %5, %6;"
        :: "r"(dst), "l"(m), "r"(bar), "r"(c0), "r"(c1), "h"((uint16_t)3), "l"(0x12F0000000000000ull) : "memory");
}
__device__ __forceinline__ void tma_prefetch(const CUtensorMap* m, int c0, int c1) {
    asm volatile("cp.async.bulk.prefetch.tensor.2d.L2.global [%0, {%1, %2}];" :: "l"(m), "r"(c0), "r"(c1) : "memory");
}
__device__ __forceinline__ void tma_store(const CUtensorMap* m, int c0, int c1, uint32_t src) {
    asm volatile("cp.async.bulk.tensor.2d.global.shared::cta.bulk_group [%0, {%2, %3}], [%1];" :: "l"(m), "r"(src), "r"(c0), "r"(c1) : "memory");
}
__device__ __forceinline__ void bulk_commit() { asm volatile("cp.async.bulk.commit_group;" ::: "memory"); }
__device__ __forceinline__ void bulk_wait_read() { asm volatile("cp.async.bulk.wait_group.read 0;" ::: "memory"); }
__device__ __forceinline__ void fence_async_smem() { asm volatile("fence.proxy.async.shared::cta;" ::: "memory"); }
__device__ __forceinline__ void prefetch_map(const CUtensorMap* m) { asm volatile("prefetch.tensormap [%0];" :: "l"(m) : "memory"); }
__device__ __forceinline__ void wg_fence() { asm volatile("wgmma.fence.sync.aligned;" ::: "memory"); }
__device__ __forceinline__ void wg_commit() { asm volatile("wgmma.commit_group.sync.aligned;" ::: "memory"); }
template <int N> __device__ __forceinline__ void wg_wait() { asm volatile("wgmma.wait_group.sync.aligned %0;" :: "n"(N) : "memory"); }
__device__ __forceinline__ void bar_sync(int id, int n) { asm volatile("bar.sync %0, %1;" :: "r"(id), "r"(n) : "memory"); }
__device__ __forceinline__ void bar_arrive(int id, int n) { asm volatile("bar.arrive %0, %1;" :: "r"(id), "r"(n) : "memory"); }
__device__ __forceinline__ void flag_add(uint32_t* f) { asm volatile("red.relaxed.gpu.global.add.u32 [%0], 1;" :: "l"(f) : "memory"); }
__device__ __forceinline__ void flag_set(uint32_t* f, uint32_t v) { asm volatile("red.relaxed.gpu.global.max.u32 [%0], %1;" :: "l"(f), "r"(v) : "memory"); }
__device__ __forceinline__ uint32_t flag_get(const uint32_t* f) { uint32_t v; asm volatile("ld.relaxed.gpu.global.u32 %0, [%1];" : "=r"(v) : "l"(f) : "memory"); return v; }
__device__ __forceinline__ void bulk_wait_fence() { asm volatile("cp.async.bulk.wait_group 0;\nfence.proxy.async.global;\nfence.acq_rel.gpu;" ::: "memory"); }
__device__ __forceinline__ uint32_t landed(bool el, const uint32_t* p, uint32_t pitch, uint32_t zero) {
    if (el) asm volatile("cp.async.bulk.wait_group 0;" ::: "memory");
    __syncwarp();
    const uint32_t a = flag_get(p), b = flag_get(p + 32 * pitch);
    return __reduce_or_sync(0xffffffffu, (a | b) & zero);
}
__device__ __forceinline__ uint32_t d16(uint32_t addr) { return (addr & 0x3FFFF) >> 4; }
__device__ __forceinline__ uint64_t mk_desc(uint32_t a16, uint32_t off, uint32_t lbo, uint32_t sbo, uint32_t swz) {
    const uint32_t lo = a16 + (off >> 4) + ((lbo >> 4) << 16), hi = (sbo >> 4) | (swz << 30);
    return ((uint64_t)hi << 32) | lo;
}
__device__ __forceinline__ uint32_t pack2(float lo, float hi) {
    uint32_t r; asm("cvt.rn.bf16x2.f32 %0, %1, %2;" : "=r"(r) : "f"(hi), "f"(lo)); return r;
}
__device__ __forceinline__ uint32_t hfma2_bf16(uint32_t a, uint32_t b, uint32_t c) {
    uint32_t r; asm("fma.rn.bf16x2 %0, %1, %2, %3;" : "=r"(r) : "r"(a), "r"(b), "r"(c)); return r;
}
__device__ __forceinline__ float bf_lo(uint32_t v) { return __uint_as_float(v << 16); }
__device__ __forceinline__ float bf_hi(uint32_t v) { return __uint_as_float(v & 0xFFFF0000u); }
__device__ __forceinline__ void unpack2(uint32_t v, float& lo, float& hi) {
    asm volatile("shl.b32 %0, %2, 16;\nand.b32 %1, %2, 0xffff0000;" : "=f"(lo), "=f"(hi) : "r"(v));
}
__device__ __forceinline__ float bf_round(float x) { return __bfloat162float(__float2bfloat16_rn(x)); }
__device__ __forceinline__ void stsm4(uint32_t addr, uint32_t r0, uint32_t r1, uint32_t r2, uint32_t r3) {
    asm volatile("stmatrix.sync.aligned.m8n8.x4.shared.b16 [%0], {%1, %2, %3, %4};" :: "r"(addr), "r"(r0), "r"(r1), "r"(r2), "r"(r3) : "memory");
}
__device__ __forceinline__ void stsm4t(uint32_t addr, uint32_t r0, uint32_t r1, uint32_t r2, uint32_t r3) {
    asm volatile("stmatrix.sync.aligned.m8n8.x4.trans.shared.b16 [%0], {%1, %2, %3, %4};" :: "r"(addr), "r"(r0), "r"(r1), "r"(r2), "r"(r3) : "memory");
}
__device__ __forceinline__ uint32_t movm(uint32_t a) { uint32_t d; asm volatile("movmatrix.sync.aligned.m8n8.trans.b16 %0, %1;" : "=r"(d) : "r"(a)); return d; }
__device__ __forceinline__ void ldsm4(uint32_t addr, uint32_t& r0, uint32_t& r1, uint32_t& r2, uint32_t& r3) {
    asm volatile("ldmatrix.sync.aligned.m8n8.x4.shared.b16 {%0, %1, %2, %3}, [%4];" : "=r"(r0), "=r"(r1), "=r"(r2), "=r"(r3) : "r"(addr) : "memory");
}
__device__ __forceinline__ void ldsm4t(uint32_t addr, uint32_t& r0, uint32_t& r1, uint32_t& r2, uint32_t& r3) {
    asm volatile("ldmatrix.sync.aligned.m8n8.x4.trans.shared.b16 {%0, %1, %2, %3}, [%4];" : "=r"(r0), "=r"(r1), "=r"(r2), "=r"(r3) : "r"(addr) : "memory");
}
__device__ __forceinline__ void mma16816(float (&c)[4], uint32_t a0, uint32_t a1, uint32_t a2, uint32_t a3, uint32_t b0, uint32_t b1) {
    asm("mma.sync.aligned.m16n8k16.row.col.f32.bf16.bf16.f32 {%0, %1, %2, %3}, {%4, %5, %6, %7}, {%8, %9}, {%0, %1, %2, %3};"
        : "+f"(c[0]), "+f"(c[1]), "+f"(c[2]), "+f"(c[3]) : "r"(a0), "r"(a1), "r"(a2), "r"(a3), "r"(b0), "r"(b1));
}
__device__ __forceinline__ float rsq(float x) { float r; asm("rsqrt.approx.ftz.f32 %0, %1;" : "=f"(r) : "f"(x)); return r; }
__device__ __forceinline__ float rcp(float x) { float r; asm("rcp.approx.ftz.f32 %0, %1;" : "=f"(r) : "f"(x)); return r; }
__device__ __forceinline__ float ex2(float x) { float r; asm("ex2.approx.ftz.f32 %0, %1;" : "=f"(r) : "f"(x)); return r; }
__device__ __forceinline__ float tanh_(float x) { float t; asm("tanh.approx.f32 %0, %1;" : "=f"(t) : "f"(x)); return t; }
__device__ __forceinline__ void block_end(uint32_t opaque, uint32_t id) { asm volatile("{\n.reg .pred p;\nsetp.eq.u32 p, %0, %1;\n@p trap;\n}" :: "r"(opaque), "r"(0xffffff00u + id)); }
__device__ __forceinline__ float silu_(float x) { return __fdividef(x, 1.f + __expf(-x)); }
__device__ __forceinline__ void st_pkt(void* p, uint32_t a, uint32_t b) {
    asm volatile("{\n.reg .b64 t;\nmov.b64 t, {%1, %2};\nst.relaxed.gpu.global.b64 [%0], t;\n}" :: "l"(p), "r"(a), "r"(b) : "memory");
}
__device__ __forceinline__ uint4 ld_pkt2(const void* p) {
    uint4 v; asm volatile("{\n.reg .b64 t, u;\nld.relaxed.gpu.global.v2.b64 {t, u}, [%4];\nmov.b64 {%0, %1}, t;\nmov.b64 {%2, %3}, u;\n}"
        : "=r"(v.x), "=r"(v.y), "=r"(v.z), "=r"(v.w) : "l"(p) : "memory"); return v;
}
__device__ __forceinline__ void st_pkt16(void* p, uint32_t a, uint32_t b, uint32_t c, uint32_t d) {
    asm volatile("{\n.reg .b64 t, u;\n.reg .b128 w;\nmov.b64 t, {%1, %2};\nmov.b64 u, {%3, %4};\nmov.b128 w, {t, u};\nst.relaxed.gpu.global.b128 [%0], w;\n}"
        :: "l"(p), "r"(a), "r"(b), "r"(c), "r"(d) : "memory");
}
__device__ __forceinline__ uint4 ld_pkt16(const void* p) {
    uint4 v; asm volatile("{\n.reg .b64 t, u;\n.reg .b128 w;\nld.relaxed.gpu.global.b128 w, [%4];\nmov.b128 {t, u}, w;\nmov.b64 {%0, %1}, t;\nmov.b64 {%2, %3}, u;\n}"
        : "=r"(v.x), "=r"(v.y), "=r"(v.z), "=r"(v.w) : "l"(p) : "memory"); return v;
}
#define SPIN_GUARD(n) do { if (++(n) > (1u << 22)) asm volatile("trap;"); } while (0)
__device__ __forceinline__ uint4 lds128(uint32_t a) { uint4 v; asm volatile("ld.shared.v4.u32 {%0, %1, %2, %3}, [%4];" : "=r"(v.x), "=r"(v.y), "=r"(v.z), "=r"(v.w) : "r"(a) : "memory"); return v; }
__device__ __forceinline__ void sts128(uint32_t a, uint32_t x, uint32_t y, uint32_t z, uint32_t w) { asm volatile("st.shared.v4.u32 [%0], {%1, %2, %3, %4};" :: "r"(a), "r"(x), "r"(y), "r"(z), "r"(w) : "memory"); }
__device__ __forceinline__ uint32_t lds32(uint32_t a) { uint32_t v; asm volatile("ld.shared.u32 %0, [%1];" : "=r"(v) : "r"(a) : "memory"); return v; }
__device__ __forceinline__ void sts32(uint32_t a, uint32_t v) { asm volatile("st.shared.u32 [%0], %1;" :: "r"(a), "r"(v) : "memory"); }
__device__ __forceinline__ bool elect_one() {
    uint32_t p; asm volatile("{\n.reg .pred q;\nelect.sync _|q, 0xffffffff;\nselp.u32 %0, 1, 0, q;\n}" : "=r"(p)); return p;
}
__device__ __forceinline__ void pause(uint32_t cycles) {
    uint32_t t0, t; asm volatile("mov.u32 %0, %%clock;" : "=r"(t0));
    do { __nanosleep(64); asm volatile("mov.u32 %0, %%clock;" : "=r"(t)); } while (t - t0 < cycles);
}
__device__ __forceinline__ void cluster_arrive() { asm volatile("barrier.cluster.arrive.relaxed.aligned;" ::: "memory"); }
__device__ __forceinline__ void cluster_wait() { asm volatile("barrier.cluster.wait.aligned;" ::: "memory"); }

__device__ __forceinline__ void wgmma_n128_z(float (&d)[64], uint64_t da, uint64_t db) {
    asm volatile("{\n.reg .pred p;\nsetp.ne.b32 p, 0, 0;\n"
        "wgmma.mma_async.sync.aligned.m64n128k16.f32.bf16.bf16 {"
        "%0, %1, %2, %3, %4, %5, %6, %7, %8, %9, %10, %11, %12, %13, %14, %15, "
        "%16, %17, %18, %19, %20, %21, %22, %23, %24, %25, %26, %27, %28, %29, %30, %31, "
        "%32, %33, %34, %35, %36, %37, %38, %39, %40, %41, %42, %43, %44, %45, %46, %47, "
        "%48, %49, %50, %51, %52, %53, %54, %55, %56, %57, %58, %59, %60, %61, %62, %63"
        "}, %64, %65, p, 1, 1, 0, 1;\n}\n"
        : "=f"(d[0]), "=f"(d[1]), "=f"(d[2]), "=f"(d[3]), "=f"(d[4]), "=f"(d[5]), "=f"(d[6]), "=f"(d[7]),
          "=f"(d[8]), "=f"(d[9]), "=f"(d[10]), "=f"(d[11]), "=f"(d[12]), "=f"(d[13]), "=f"(d[14]), "=f"(d[15]),
          "=f"(d[16]), "=f"(d[17]), "=f"(d[18]), "=f"(d[19]), "=f"(d[20]), "=f"(d[21]), "=f"(d[22]), "=f"(d[23]),
          "=f"(d[24]), "=f"(d[25]), "=f"(d[26]), "=f"(d[27]), "=f"(d[28]), "=f"(d[29]), "=f"(d[30]), "=f"(d[31]),
          "=f"(d[32]), "=f"(d[33]), "=f"(d[34]), "=f"(d[35]), "=f"(d[36]), "=f"(d[37]), "=f"(d[38]), "=f"(d[39]),
          "=f"(d[40]), "=f"(d[41]), "=f"(d[42]), "=f"(d[43]), "=f"(d[44]), "=f"(d[45]), "=f"(d[46]), "=f"(d[47]),
          "=f"(d[48]), "=f"(d[49]), "=f"(d[50]), "=f"(d[51]), "=f"(d[52]), "=f"(d[53]), "=f"(d[54]), "=f"(d[55]),
          "=f"(d[56]), "=f"(d[57]), "=f"(d[58]), "=f"(d[59]), "=f"(d[60]), "=f"(d[61]), "=f"(d[62]), "=f"(d[63])
        : "l"(da), "l"(db));
}
__device__ __forceinline__ void wgmma_n128(float (&d)[64], uint64_t da, uint64_t db) {
    asm volatile("{\n.reg .pred p;\nsetp.eq.b32 p, 0, 0;\n"
        "wgmma.mma_async.sync.aligned.m64n128k16.f32.bf16.bf16 {"
        "%0, %1, %2, %3, %4, %5, %6, %7, %8, %9, %10, %11, %12, %13, %14, %15, "
        "%16, %17, %18, %19, %20, %21, %22, %23, %24, %25, %26, %27, %28, %29, %30, %31, "
        "%32, %33, %34, %35, %36, %37, %38, %39, %40, %41, %42, %43, %44, %45, %46, %47, "
        "%48, %49, %50, %51, %52, %53, %54, %55, %56, %57, %58, %59, %60, %61, %62, %63"
        "}, %64, %65, p, 1, 1, 0, 1;\n}\n"
        : "+f"(d[0]), "+f"(d[1]), "+f"(d[2]), "+f"(d[3]), "+f"(d[4]), "+f"(d[5]), "+f"(d[6]), "+f"(d[7]),
          "+f"(d[8]), "+f"(d[9]), "+f"(d[10]), "+f"(d[11]), "+f"(d[12]), "+f"(d[13]), "+f"(d[14]), "+f"(d[15]),
          "+f"(d[16]), "+f"(d[17]), "+f"(d[18]), "+f"(d[19]), "+f"(d[20]), "+f"(d[21]), "+f"(d[22]), "+f"(d[23]),
          "+f"(d[24]), "+f"(d[25]), "+f"(d[26]), "+f"(d[27]), "+f"(d[28]), "+f"(d[29]), "+f"(d[30]), "+f"(d[31]),
          "+f"(d[32]), "+f"(d[33]), "+f"(d[34]), "+f"(d[35]), "+f"(d[36]), "+f"(d[37]), "+f"(d[38]), "+f"(d[39]),
          "+f"(d[40]), "+f"(d[41]), "+f"(d[42]), "+f"(d[43]), "+f"(d[44]), "+f"(d[45]), "+f"(d[46]), "+f"(d[47]),
          "+f"(d[48]), "+f"(d[49]), "+f"(d[50]), "+f"(d[51]), "+f"(d[52]), "+f"(d[53]), "+f"(d[54]), "+f"(d[55]),
          "+f"(d[56]), "+f"(d[57]), "+f"(d[58]), "+f"(d[59]), "+f"(d[60]), "+f"(d[61]), "+f"(d[62]), "+f"(d[63])
        : "l"(da), "l"(db));
}
__device__ __forceinline__ void wgmma_n176_z(float (&d)[88], uint64_t da, uint64_t db) {
    asm volatile("{\n.reg .pred p;\nsetp.ne.b32 p, 0, 0;\n"
        "wgmma.mma_async.sync.aligned.m64n176k16.f32.bf16.bf16 {"
        "%0, %1, %2, %3, %4, %5, %6, %7, %8, %9, %10, %11, %12, %13, %14, %15, "
        "%16, %17, %18, %19, %20, %21, %22, %23, %24, %25, %26, %27, %28, %29, %30, %31, "
        "%32, %33, %34, %35, %36, %37, %38, %39, %40, %41, %42, %43, %44, %45, %46, %47, "
        "%48, %49, %50, %51, %52, %53, %54, %55, %56, %57, %58, %59, %60, %61, %62, %63, "
        "%64, %65, %66, %67, %68, %69, %70, %71, %72, %73, %74, %75, %76, %77, %78, %79, "
        "%80, %81, %82, %83, %84, %85, %86, %87"
        "}, %88, %89, p, 1, 1, 0, 1;\n}\n"
        : "=f"(d[0]), "=f"(d[1]), "=f"(d[2]), "=f"(d[3]), "=f"(d[4]), "=f"(d[5]), "=f"(d[6]), "=f"(d[7]),
          "=f"(d[8]), "=f"(d[9]), "=f"(d[10]), "=f"(d[11]), "=f"(d[12]), "=f"(d[13]), "=f"(d[14]), "=f"(d[15]),
          "=f"(d[16]), "=f"(d[17]), "=f"(d[18]), "=f"(d[19]), "=f"(d[20]), "=f"(d[21]), "=f"(d[22]), "=f"(d[23]),
          "=f"(d[24]), "=f"(d[25]), "=f"(d[26]), "=f"(d[27]), "=f"(d[28]), "=f"(d[29]), "=f"(d[30]), "=f"(d[31]),
          "=f"(d[32]), "=f"(d[33]), "=f"(d[34]), "=f"(d[35]), "=f"(d[36]), "=f"(d[37]), "=f"(d[38]), "=f"(d[39]),
          "=f"(d[40]), "=f"(d[41]), "=f"(d[42]), "=f"(d[43]), "=f"(d[44]), "=f"(d[45]), "=f"(d[46]), "=f"(d[47]),
          "=f"(d[48]), "=f"(d[49]), "=f"(d[50]), "=f"(d[51]), "=f"(d[52]), "=f"(d[53]), "=f"(d[54]), "=f"(d[55]),
          "=f"(d[56]), "=f"(d[57]), "=f"(d[58]), "=f"(d[59]), "=f"(d[60]), "=f"(d[61]), "=f"(d[62]), "=f"(d[63]),
          "=f"(d[64]), "=f"(d[65]), "=f"(d[66]), "=f"(d[67]), "=f"(d[68]), "=f"(d[69]), "=f"(d[70]), "=f"(d[71]),
          "=f"(d[72]), "=f"(d[73]), "=f"(d[74]), "=f"(d[75]), "=f"(d[76]), "=f"(d[77]), "=f"(d[78]), "=f"(d[79]),
          "=f"(d[80]), "=f"(d[81]), "=f"(d[82]), "=f"(d[83]), "=f"(d[84]), "=f"(d[85]), "=f"(d[86]), "=f"(d[87])
        : "l"(da), "l"(db));
}
__device__ __forceinline__ void wgmma_n176(float (&d)[88], uint64_t da, uint64_t db) {
    asm volatile("{\n.reg .pred p;\nsetp.eq.b32 p, 0, 0;\n"
        "wgmma.mma_async.sync.aligned.m64n176k16.f32.bf16.bf16 {"
        "%0, %1, %2, %3, %4, %5, %6, %7, %8, %9, %10, %11, %12, %13, %14, %15, "
        "%16, %17, %18, %19, %20, %21, %22, %23, %24, %25, %26, %27, %28, %29, %30, %31, "
        "%32, %33, %34, %35, %36, %37, %38, %39, %40, %41, %42, %43, %44, %45, %46, %47, "
        "%48, %49, %50, %51, %52, %53, %54, %55, %56, %57, %58, %59, %60, %61, %62, %63, "
        "%64, %65, %66, %67, %68, %69, %70, %71, %72, %73, %74, %75, %76, %77, %78, %79, "
        "%80, %81, %82, %83, %84, %85, %86, %87"
        "}, %88, %89, p, 1, 1, 0, 1;\n}\n"
        : "+f"(d[0]), "+f"(d[1]), "+f"(d[2]), "+f"(d[3]), "+f"(d[4]), "+f"(d[5]), "+f"(d[6]), "+f"(d[7]),
          "+f"(d[8]), "+f"(d[9]), "+f"(d[10]), "+f"(d[11]), "+f"(d[12]), "+f"(d[13]), "+f"(d[14]), "+f"(d[15]),
          "+f"(d[16]), "+f"(d[17]), "+f"(d[18]), "+f"(d[19]), "+f"(d[20]), "+f"(d[21]), "+f"(d[22]), "+f"(d[23]),
          "+f"(d[24]), "+f"(d[25]), "+f"(d[26]), "+f"(d[27]), "+f"(d[28]), "+f"(d[29]), "+f"(d[30]), "+f"(d[31]),
          "+f"(d[32]), "+f"(d[33]), "+f"(d[34]), "+f"(d[35]), "+f"(d[36]), "+f"(d[37]), "+f"(d[38]), "+f"(d[39]),
          "+f"(d[40]), "+f"(d[41]), "+f"(d[42]), "+f"(d[43]), "+f"(d[44]), "+f"(d[45]), "+f"(d[46]), "+f"(d[47]),
          "+f"(d[48]), "+f"(d[49]), "+f"(d[50]), "+f"(d[51]), "+f"(d[52]), "+f"(d[53]), "+f"(d[54]), "+f"(d[55]),
          "+f"(d[56]), "+f"(d[57]), "+f"(d[58]), "+f"(d[59]), "+f"(d[60]), "+f"(d[61]), "+f"(d[62]), "+f"(d[63]),
          "+f"(d[64]), "+f"(d[65]), "+f"(d[66]), "+f"(d[67]), "+f"(d[68]), "+f"(d[69]), "+f"(d[70]), "+f"(d[71]),
          "+f"(d[72]), "+f"(d[73]), "+f"(d[74]), "+f"(d[75]), "+f"(d[76]), "+f"(d[77]), "+f"(d[78]), "+f"(d[79]),
          "+f"(d[80]), "+f"(d[81]), "+f"(d[82]), "+f"(d[83]), "+f"(d[84]), "+f"(d[85]), "+f"(d[86]), "+f"(d[87])
        : "l"(da), "l"(db));
}
__device__ __forceinline__ void wgmma_n256_z(float (&d)[128], uint64_t da, uint64_t db) {
    asm volatile("{\n.reg .pred p;\nsetp.ne.b32 p, 0, 0;\n"
        "wgmma.mma_async.sync.aligned.m64n256k16.f32.bf16.bf16 {"
        "%0, %1, %2, %3, %4, %5, %6, %7, %8, %9, %10, %11, %12, %13, %14, %15, "
        "%16, %17, %18, %19, %20, %21, %22, %23, %24, %25, %26, %27, %28, %29, %30, %31, "
        "%32, %33, %34, %35, %36, %37, %38, %39, %40, %41, %42, %43, %44, %45, %46, %47, "
        "%48, %49, %50, %51, %52, %53, %54, %55, %56, %57, %58, %59, %60, %61, %62, %63, "
        "%64, %65, %66, %67, %68, %69, %70, %71, %72, %73, %74, %75, %76, %77, %78, %79, "
        "%80, %81, %82, %83, %84, %85, %86, %87, %88, %89, %90, %91, %92, %93, %94, %95, "
        "%96, %97, %98, %99, %100, %101, %102, %103, %104, %105, %106, %107, %108, %109, %110, %111, "
        "%112, %113, %114, %115, %116, %117, %118, %119, %120, %121, %122, %123, %124, %125, %126, %127"
        "}, %128, %129, p, 1, 1, 0, 1;\n}\n"
        : "=f"(d[0]), "=f"(d[1]), "=f"(d[2]), "=f"(d[3]), "=f"(d[4]), "=f"(d[5]), "=f"(d[6]), "=f"(d[7]),
          "=f"(d[8]), "=f"(d[9]), "=f"(d[10]), "=f"(d[11]), "=f"(d[12]), "=f"(d[13]), "=f"(d[14]), "=f"(d[15]),
          "=f"(d[16]), "=f"(d[17]), "=f"(d[18]), "=f"(d[19]), "=f"(d[20]), "=f"(d[21]), "=f"(d[22]), "=f"(d[23]),
          "=f"(d[24]), "=f"(d[25]), "=f"(d[26]), "=f"(d[27]), "=f"(d[28]), "=f"(d[29]), "=f"(d[30]), "=f"(d[31]),
          "=f"(d[32]), "=f"(d[33]), "=f"(d[34]), "=f"(d[35]), "=f"(d[36]), "=f"(d[37]), "=f"(d[38]), "=f"(d[39]),
          "=f"(d[40]), "=f"(d[41]), "=f"(d[42]), "=f"(d[43]), "=f"(d[44]), "=f"(d[45]), "=f"(d[46]), "=f"(d[47]),
          "=f"(d[48]), "=f"(d[49]), "=f"(d[50]), "=f"(d[51]), "=f"(d[52]), "=f"(d[53]), "=f"(d[54]), "=f"(d[55]),
          "=f"(d[56]), "=f"(d[57]), "=f"(d[58]), "=f"(d[59]), "=f"(d[60]), "=f"(d[61]), "=f"(d[62]), "=f"(d[63]),
          "=f"(d[64]), "=f"(d[65]), "=f"(d[66]), "=f"(d[67]), "=f"(d[68]), "=f"(d[69]), "=f"(d[70]), "=f"(d[71]),
          "=f"(d[72]), "=f"(d[73]), "=f"(d[74]), "=f"(d[75]), "=f"(d[76]), "=f"(d[77]), "=f"(d[78]), "=f"(d[79]),
          "=f"(d[80]), "=f"(d[81]), "=f"(d[82]), "=f"(d[83]), "=f"(d[84]), "=f"(d[85]), "=f"(d[86]), "=f"(d[87]),
          "=f"(d[88]), "=f"(d[89]), "=f"(d[90]), "=f"(d[91]), "=f"(d[92]), "=f"(d[93]), "=f"(d[94]), "=f"(d[95]),
          "=f"(d[96]), "=f"(d[97]), "=f"(d[98]), "=f"(d[99]), "=f"(d[100]), "=f"(d[101]), "=f"(d[102]), "=f"(d[103]),
          "=f"(d[104]), "=f"(d[105]), "=f"(d[106]), "=f"(d[107]), "=f"(d[108]), "=f"(d[109]), "=f"(d[110]), "=f"(d[111]),
          "=f"(d[112]), "=f"(d[113]), "=f"(d[114]), "=f"(d[115]), "=f"(d[116]), "=f"(d[117]), "=f"(d[118]), "=f"(d[119]),
          "=f"(d[120]), "=f"(d[121]), "=f"(d[122]), "=f"(d[123]), "=f"(d[124]), "=f"(d[125]), "=f"(d[126]), "=f"(d[127])
        : "l"(da), "l"(db));
}
__device__ __forceinline__ void wgmma_n256(float (&d)[128], uint64_t da, uint64_t db) {
    asm volatile("{\n.reg .pred p;\nsetp.eq.b32 p, 0, 0;\n"
        "wgmma.mma_async.sync.aligned.m64n256k16.f32.bf16.bf16 {"
        "%0, %1, %2, %3, %4, %5, %6, %7, %8, %9, %10, %11, %12, %13, %14, %15, "
        "%16, %17, %18, %19, %20, %21, %22, %23, %24, %25, %26, %27, %28, %29, %30, %31, "
        "%32, %33, %34, %35, %36, %37, %38, %39, %40, %41, %42, %43, %44, %45, %46, %47, "
        "%48, %49, %50, %51, %52, %53, %54, %55, %56, %57, %58, %59, %60, %61, %62, %63, "
        "%64, %65, %66, %67, %68, %69, %70, %71, %72, %73, %74, %75, %76, %77, %78, %79, "
        "%80, %81, %82, %83, %84, %85, %86, %87, %88, %89, %90, %91, %92, %93, %94, %95, "
        "%96, %97, %98, %99, %100, %101, %102, %103, %104, %105, %106, %107, %108, %109, %110, %111, "
        "%112, %113, %114, %115, %116, %117, %118, %119, %120, %121, %122, %123, %124, %125, %126, %127"
        "}, %128, %129, p, 1, 1, 0, 1;\n}\n"
        : "+f"(d[0]), "+f"(d[1]), "+f"(d[2]), "+f"(d[3]), "+f"(d[4]), "+f"(d[5]), "+f"(d[6]), "+f"(d[7]),
          "+f"(d[8]), "+f"(d[9]), "+f"(d[10]), "+f"(d[11]), "+f"(d[12]), "+f"(d[13]), "+f"(d[14]), "+f"(d[15]),
          "+f"(d[16]), "+f"(d[17]), "+f"(d[18]), "+f"(d[19]), "+f"(d[20]), "+f"(d[21]), "+f"(d[22]), "+f"(d[23]),
          "+f"(d[24]), "+f"(d[25]), "+f"(d[26]), "+f"(d[27]), "+f"(d[28]), "+f"(d[29]), "+f"(d[30]), "+f"(d[31]),
          "+f"(d[32]), "+f"(d[33]), "+f"(d[34]), "+f"(d[35]), "+f"(d[36]), "+f"(d[37]), "+f"(d[38]), "+f"(d[39]),
          "+f"(d[40]), "+f"(d[41]), "+f"(d[42]), "+f"(d[43]), "+f"(d[44]), "+f"(d[45]), "+f"(d[46]), "+f"(d[47]),
          "+f"(d[48]), "+f"(d[49]), "+f"(d[50]), "+f"(d[51]), "+f"(d[52]), "+f"(d[53]), "+f"(d[54]), "+f"(d[55]),
          "+f"(d[56]), "+f"(d[57]), "+f"(d[58]), "+f"(d[59]), "+f"(d[60]), "+f"(d[61]), "+f"(d[62]), "+f"(d[63]),
          "+f"(d[64]), "+f"(d[65]), "+f"(d[66]), "+f"(d[67]), "+f"(d[68]), "+f"(d[69]), "+f"(d[70]), "+f"(d[71]),
          "+f"(d[72]), "+f"(d[73]), "+f"(d[74]), "+f"(d[75]), "+f"(d[76]), "+f"(d[77]), "+f"(d[78]), "+f"(d[79]),
          "+f"(d[80]), "+f"(d[81]), "+f"(d[82]), "+f"(d[83]), "+f"(d[84]), "+f"(d[85]), "+f"(d[86]), "+f"(d[87]),
          "+f"(d[88]), "+f"(d[89]), "+f"(d[90]), "+f"(d[91]), "+f"(d[92]), "+f"(d[93]), "+f"(d[94]), "+f"(d[95]),
          "+f"(d[96]), "+f"(d[97]), "+f"(d[98]), "+f"(d[99]), "+f"(d[100]), "+f"(d[101]), "+f"(d[102]), "+f"(d[103]),
          "+f"(d[104]), "+f"(d[105]), "+f"(d[106]), "+f"(d[107]), "+f"(d[108]), "+f"(d[109]), "+f"(d[110]), "+f"(d[111]),
          "+f"(d[112]), "+f"(d[113]), "+f"(d[114]), "+f"(d[115]), "+f"(d[116]), "+f"(d[117]), "+f"(d[118]), "+f"(d[119]),
          "+f"(d[120]), "+f"(d[121]), "+f"(d[122]), "+f"(d[123]), "+f"(d[124]), "+f"(d[125]), "+f"(d[126]), "+f"(d[127])
        : "l"(da), "l"(db));
}

__device__ __forceinline__ void wgmma_n8_ta(float (&d)[4], uint64_t da, uint64_t db) {
    asm volatile("{\n.reg .pred p;\nsetp.eq.b32 p, 0, 0;\nwgmma.mma_async.sync.aligned.m64n8k16.f32.bf16.bf16 {%0, %1, %2, %3}, %4, %5, p, 1, 1, 1, 0;\n}"
        : "+f"(d[0]), "+f"(d[1]), "+f"(d[2]), "+f"(d[3]) : "l"(da), "l"(db));
}

struct Idx {
    uint32_t lane, warp, w4, q4, g8, prow, pan;
    __device__ __forceinline__ Idx() {
        uint32_t t; asm volatile("mov.u32 %0, %%tid.x;" : "=r"(t));
        lane = t & 31; warp = t >> 5; w4 = warp & 3; q4 = lane & 3; g8 = lane >> 2;
        prow = w4 * 16 + ((lane >> 3) & 1) * 8 + (lane & 7);
        pan = prow * 128 + (((lane >> 4) ^ (lane & 7)) << 4);
    }
};
#define IDX() const Idx ix; const uint32_t lane = ix.lane, warp = ix.warp, w4 = ix.w4, q4 = ix.q4, g8 = ix.g8, prow = ix.prow, pan_addr = ix.pan; \
    (void)lane; (void)warp; (void)w4; (void)q4; (void)g8; (void)prow; (void)pan_addr;

__device__ __forceinline__ int kof(int t, int sh, int j) {
    const int p = t >> (sh - 1), pn = p < 2 ? p : p >= 9, q = p - 2 - 7 * pn;
    return ((p < 2 ? j : q + (q >= j)) << 7) + (pn << 6) + ((t & (sh - 1)) << 5);
}
__device__ __forceinline__ uint32_t fidx(uint32_t m, uint32_t w, uint32_t pn) {
    return m * 32 + w * 16 + pn;
}
constexpr int HC0 = 8 * 48, HC3 = HC0 + 3072;
__device__ __forceinline__ int hcol(int p, int j) { return HC0 + p * 1024 + j * 128; }
struct Ring {
    uint32_t slot, par;
    __device__ __forceinline__ void next() { if (++slot == NSLOT) { slot = 0; par ^= 1; } }
    __device__ __forceinline__ void skip(uint32_t n) { slot += n; if (slot >= NSLOT) { slot -= NSLOT; par ^= 1; } }
};
__device__ __forceinline__ uint32_t BAR_FULL(uint32_t sb, uint32_t s) { return sb + OFF_BAR + 8 * s; }
constexpr uint32_t AF_REL = 48;
__device__ __forceinline__ uint32_t BAR_EMPTY(uint32_t sb, uint32_t s) { return sb + OFF_BAR + 96 + 8 * s; }
__device__ __forceinline__ uint32_t BAR_SFULL(uint32_t sb, uint32_t i) { return sb + OFF_BAR + 152 + 8 * i; }
__device__ __forceinline__ uint32_t BAR_SREADY(uint32_t sb, uint32_t i) { return sb + OFF_BAR + 184 + 8 * i; }
__device__ __forceinline__ uint32_t BAR_ONE(uint32_t sb, uint32_t i) { return sb + OFF_BAR + 216 + 8 * i; }
enum { EV_WIN, EV_WIN1, EV_WIN2, EV_WIN3, EV_P0, EV_GA, EV_GB, EV_LN2, EV_LAG1, EV_LAG2, EV_LAG3, EV_LAG4, EV_LAG5, EV_KV, EV_PAR, EV_AGO, EV_AGO1, EV_AGO2, EV_FGO, EV_FGO1, EV_FGO2, EV_H0, EV_H1, EV_H2, EV_H3, EV_TAIL, EV_COUNT = EV_TAIL + 8 };
constexpr int NB_TAIL = 4;

struct Rel {
    uint32_t base; bool sig;
    __device__ __forceinline__ Rel(uint32_t sb, uint32_t tw) {
        uint32_t a; asm("mapa.shared::cluster.u32 %0, %1, %2;" : "=r"(a) : "r"(BAR_EMPTY(sb, 0)), "r"((tw >> 5) & 1));
        base = __shfl_sync(0xffffffffu, a, 0); sig = (tw & ~32u) == 0;
    }
    __device__ __forceinline__ void operator()(uint32_t slot) const {
        if (sig) asm volatile("mbarrier.arrive.shared::cluster.b64 _, [%0];" :: "r"(base + 8 * slot) : "memory");
    }
};
struct LnRow { float rs0, nm0, rs1, nm1; };
struct Pipe {
    Rel rel; uint32_t p1, p2;
    __device__ __forceinline__ Pipe(uint32_t sb, uint32_t tw, uint32_t first) : rel(sb, tw), p1(first), p2(NSLOT) {}
    template <bool TWO> __device__ __forceinline__ void acquire(uint32_t sb, uint32_t af, const Ring& r) {
        const uint32_t b0 = BAR_FULL(sb, r.slot), b1 = b0 + af;
        const bool ready = TWO ? mbar_test2(b0, b1, r.par) : mbar_test(b0, r.par);
        wg_wait<1>();
        rel(p2);
        if (!ready) { if (TWO) mbar_wait2(b0, b1, r.par); else mbar_wait(b0, r.par); }
    }
    __device__ __forceinline__ void issued(uint32_t slot) { p2 = p1; p1 = slot; }
    __device__ __forceinline__ void drain1() { wg_wait<1>(); rel(p2); p2 = NSLOT; }
    __device__ __forceinline__ void drain0() { wg_wait<0>(); rel(p1); p1 = NSLOT; }
    template <bool TWO, class Step> __device__ __forceinline__ void hold(int LG, uint32_t sb, uint32_t af, Ring& r, uint32_t lag_bar, Step step) {
        Ring q = r;
#pragma unroll 1
        for (int i = 0; i < LG; ++i) { if (TWO) mbar_wait2(BAR_FULL(sb, q.slot), BAR_FULL(sb, q.slot) + af, q.par); else mbar_wait(BAR_FULL(sb, q.slot), q.par); q.next(); }
        mbar_wait(lag_bar, 0);
#pragma unroll 1
        do {
            step(r.slot);
            wg_wait<2>(); rel(p2); p2 = p1; p1 = r.slot;
            if (++r.slot == NSLOT) r.slot = 0;
        } while (r.slot != q.slot);
        r.par = q.par;
    }
};
template <bool TWO, bool FIRST, int NA, int NB>
__device__ __forceinline__ void step32(float (&aa)[NA], float (&ab)[NB], uint32_t sb, uint32_t wg, uint32_t slot, int own) {
    const uint32_t st = d16(sb) + slot * (SLOT >> 4);
    const uint32_t alo = own >= 0 ? d16(sb) + OFF_STG / 16 + wg * 1024 + (own >> 1) * 512 + (own & 1) * 4 : st + wg * 256;
    const uint32_t ahi = own >= 0 ? (1024 >> 4) | (1u << 30) : (512 >> 4) | (2u << 30);
    wg_fence();
#pragma unroll
    for (int k = 0; k < 2; ++k) {
        const uint64_t da = ((uint64_t)ahi << 32) | (alo + k * 2 + 0x10000);
        if constexpr (NA == 88) {
            const uint64_t d0 = mk_desc(st, 8192 + k * 2048, 8192, 1024, 1), d1 = mk_desc(st, 12288 + k * 2048, 8192, 1024, 1);
            if (FIRST && k == 0) { wgmma_n176_z(aa, da, d0); wgmma_n176_z(ab, da, d1); }
            else { wgmma_n176(aa, da, d0); wgmma_n176(ab, da, d1); }
        } else {
            const uint64_t d0 = mk_desc(st, 8192 + k * 2048, 4096, 1024, 1), d1 = mk_desc(st, 24576 + k * 2048, 4096, 1024, 1);
            if (FIRST && k == 0) { wgmma_n256_z(aa, da, d0); if constexpr (TWO) wgmma_n128_z(ab, da, d1); }
            else { wgmma_n256(aa, da, d0); if constexpr (TWO) wgmma_n128(ab, da, d1); }
        }
    }
    wg_commit();
}
template <bool TWO, int LG, int NA, int NB, class Mid, class Tail>
__device__ __forceinline__ void mainloop32(float (&aa)[NA], float (&ab)[NB], uint32_t sb, uint32_t wg, uint32_t tw, Ring& r, uint32_t lag_ev, int g0, Mid mid, Tail tail) {
    step32<TWO, true>(aa, ab, sb, wg, r.slot, TWO ? 0 : -1);
    TS(g0, 0);
    Pipe pp(sb, tw, r.slot);
    r.next();
    const int end = wg ? 32 : 32 - LG;
#pragma unroll 1
    for (int it = 1; it < end; ++it) {
        pp.acquire<TWO>(sb, wg ? 0 : AF_REL, r);
        step32<TWO, false>(aa, ab, sb, wg, r.slot, TWO && it < 4 ? it : -1);
        pp.issued(r.slot);
        TS(g0 + it, 0);
        r.next();
        mid(it);
    }
    if (wg == 0) { pp.drain1(); pp.drain0(); pp.hold<TWO>(LG, sb, AF_REL, r, BAR_ONE(sb, lag_ev), [&](uint32_t slot) { step32<TWO, false>(aa, ab, sb, 0, slot, -1); }); }
    if (wg == 1 && tw == 0) mbar_arrive(BAR_ONE(sb, lag_ev));
    pp.drain1();
    tail();
    pp.drain0();
    TS(g0 + 31, 1);
}
template <bool FIRST>
__device__ __forceinline__ void step64(float (&acc)[64], uint32_t sb, uint32_t wg, uint32_t slot, int own) {
    const uint32_t sbb = d16(sb) + slot * (SLOT >> 4), sa = own >= 0 ? d16(sb) + OFF_STG / 16 + wg * 1024 + own * 512 : sbb + wg * 512;
    wg_fence();
#pragma unroll
    for (int k = 0; k < 4; ++k) {
        const uint64_t da = mk_desc(sa, k * 32, 16, 1024, 1), db = mk_desc(sbb, 16384 + k * 2048, 8192, 1024, 1);
        if (FIRST && k == 0) wgmma_n128_z(acc, da, db); else wgmma_n128(acc, da, db);
    }
    wg_commit();
}
template <class Put, class Mid, class Tail>
__device__ __forceinline__ void mainloop64(float (&acc)[64], bool wo, uint32_t sb, uint32_t wg, uint32_t tw, Ring& r, Put put, Mid mid, Tail tail) {
    const int g0 = wo ? 32 : 144, nst = wo ? 16 : 56, lg = wo ? LAGW : LAGD; (void)g0;
    const uint32_t lag_bar = BAR_ONE(sb, wo ? EV_LAG4 : EV_LAG5), af = wo && !wg ? AF_REL : 0;
    if (!wo) CS(28);
    step64<true>(acc, sb, wg, r.slot, wo ? 0 : -1);
    if (!wo) CS(29);
    TS(g0, 0);
    Pipe pp(sb, tw, r.slot);
    r.next();
    int it = 1;
    auto run = [&](int end, int own, bool with_put) {
#pragma unroll 1
        do {
            pp.acquire<true>(sb, af, r);
            step64<false>(acc, sb, wg, r.slot, own);
            pp.issued(r.slot);
            TS(g0 + it, 0);
            if (wo && it == 2) CS(9);
            r.next();
            if (with_put && it == (wg ? PUTD1 : PUTD0)) put();
        } while (++it < end);
    };
    const int end = wg ? nst : nst - lg;
    run(wo ? 2 : wg ? MIDD : end, wo ? 1 : -1, true);
    mid();
    if (wo) { pp.drain1(); pp.drain0(); TS(g0 + 1, 1); }
    if (it < end) run(end, -1, false);
    if (wg == 0 && lg) { pp.drain1(); pp.drain0(); pp.hold<true>(lg, sb, af, r, lag_bar, [&](uint32_t slot) { step64<false>(acc, sb, 0, slot, -1); }); }
    if (wg == 1 && tw == 0) mbar_arrive(lag_bar);
    pp.drain1();
    tail();
    pp.drain0();
    TS(g0 + nst - 1, 1);
}

struct RowAcc {
    float sm[4] = {0.f, 0.f, 0.f, 0.f}, sq[4] = {0.f, 0.f, 0.f, 0.f};
    __device__ __forceinline__ void add(int e, float x) { sm[e & 3] += x; sq[e & 3] = fmaf(x, x, sq[e & 3]); }
    __device__ __forceinline__ void publish(uint4* dst, uint32_t q4, uint32_t ep) const {
        const float s0 = sm[0] + sm[1], s1 = sm[2] + sm[3], q0 = sq[0] + sq[1], q1 = sq[2] + sq[3];
        const bool od = q4 & 1;
        float sv = (od ? s1 : s0) + __shfl_xor_sync(0xffffffffu, od ? s0 : s1, 1), qv = (od ? q1 : q0) + __shfl_xor_sync(0xffffffffu, od ? q0 : q1, 1);
        sv += __shfl_xor_sync(0xffffffffu, sv, 2); qv += __shfl_xor_sync(0xffffffffu, qv, 2);
        st_pkt16(dst + (q4 & 1) * 8, 0, __float_as_uint(sv), __float_as_uint(qv), ep);
    }
};
__device__ __forceinline__ LnRow merge_stats(const uint4* src, uint32_t q4, uint32_t ep, uint32_t sb) {
    uint4 t[4];
    uint32_t n = 0;
    while (true) {
#pragma unroll
        for (int i = 0; i < 4; ++i) t[i] = ld_pkt16(src + (q4 * 2 + (i >> 1)) * 512 + (i & 1) * 8);
        const bool ok_ = __all_sync(0xffffffffu, t[0].w == ep && t[1].w == ep && t[2].w == ep && t[3].w == ep);
        if (n < 4) CS(14 + n);
        if (ok_) break;
        SPIN_GUARD(n);
    }
    float v[4];
#pragma unroll
    for (int h = 0; h < 2; ++h) { v[h] = __uint_as_float(t[h].y) + __uint_as_float(t[2 + h].y); v[2 + h] = __uint_as_float(t[h].z) + __uint_as_float(t[2 + h].z); }
#pragma unroll
    for (int o = 1; o < 4; o <<= 1)
#pragma unroll
        for (int i = 0; i < 4; ++i) v[i] += __shfl_xor_sync(0xffffffffu, v[i], o);
    const float m0 = v[0] * (1.f / D_), m1 = v[1] * (1.f / D_);
    const float r0 = rsq(fmaxf(fmaf(-m0, m0, v[2] * (1.f / D_)), 0.f) + 1e-5f), r1 = rsq(fmaxf(fmaf(-m1, m1, v[3] * (1.f / D_)), 0.f) + 1e-5f);
    return LnRow{r0, -m0 * r0, r1, -m1 * r1};
}
struct Stg {
    uint32_t b, par;
    __device__ __forceinline__ uint32_t acquire2(uint32_t sb, uint32_t wg) {
        mbar_wait2(BAR_SREADY(sb, wg * 2), BAR_SREADY(sb, wg * 2 + 1), par);
        par ^= 1;
        return sb + OFF_STG + wg * 16384;
    }
    __device__ __forceinline__ void publish(uint32_t sb, uint32_t wg, uint32_t lane) {
        fence_async_smem();
        __syncwarp();
        if (lane == 0) mbar_arrive(BAR_SFULL(sb, wg * 2 + b));
        b ^= 1;
    }
};

struct LnPar {
    uint4 p[8];
    __device__ __forceinline__ void load(uint32_t sb, uint32_t q4) {
#pragma unroll
        for (int i = 0; i < 8; ++i) p[i] = lds128(sb + OFF_PAR + i * 64 + q4 * 16);
    }
};
__device__ __forceinline__ void ln_norm(uint32_t (&xn)[32], const float (&x)[64], const LnRow& n) {
#pragma unroll
    for (int e = 0; e < 32; ++e) {
        const float rs = (e & 1) ? n.rs1 : n.rs0, nm = (e & 1) ? n.nm1 : n.nm0;
        xn[e] = pack2(fmaf(x[2 * e], rs, nm), fmaf(x[2 * e + 1], rs, nm));
    }
}
__device__ __forceinline__ void ln_emit(const uint32_t (&xr)[32], const LnPar& lp, uint32_t sb, uint32_t wg, const Idx& ix) {
#pragma unroll
    for (int i = 0; i < 8; ++i)
        stsm4(sb + OFF_STG + wg * 16384 + (i >> 2) * 8192 + (ix.pan ^ ((i & 3) << 5)), hfma2_bf16(xr[4 * i], lp.p[i].z, lp.p[i].x), hfma2_bf16(xr[4 * i + 1], lp.p[i].z, lp.p[i].x),
              hfma2_bf16(xr[4 * i + 2], lp.p[i].w, lp.p[i].y), hfma2_bf16(xr[4 * i + 3], lp.p[i].w, lp.p[i].y));
    fence_async_smem();
    __syncwarp();
    if (ix.lane < 2) mbar_arrive(BAR_SFULL(sb, wg * 2 + ix.lane));
    bar_sync(1 + wg, 128);
}
__device__ __forceinline__ void load_slab(uint32_t (&xr)[32], uint32_t buf) {
    IDX();
#pragma unroll
    for (int i = 0; i < 8; ++i) ldsm4(buf + (i >> 2) * 8192 + (pan_addr ^ ((i & 3) << 5)), xr[4 * i], xr[4 * i + 1], xr[4 * i + 2], xr[4 * i + 3]);
}
__device__ __forceinline__ void unpack_slab(float (&x)[64], const uint32_t (&xr)[32]) {
#pragma unroll
    for (int i = 0; i < 32; ++i) unpack2(xr[i], x[2 * i], x[2 * i + 1]);
}
__device__ __forceinline__ void store_slab(const float (&x)[64], uint32_t buf, uint32_t pitch, uint32_t pan, int i0, int i1) {
#pragma unroll
    for (int i = i0; i < i1; ++i)
        stsm4(buf + (i >> 2) * pitch + (pan ^ ((i & 3) << 5)), pack2(x[8 * i], x[8 * i + 1]), pack2(x[8 * i + 2], x[8 * i + 3]), pack2(x[8 * i + 4], x[8 * i + 5]), pack2(x[8 * i + 6], x[8 * i + 7]));
}
template <int NP, class Done>
__device__ __forceinline__ void fetch_halo(uint4* src, bool first, uint32_t dst, Done done) {
    uint4 hv[4 * NP];
    uint32_t n = 0;
    while (true) {
        bool ok = true;
#pragma unroll
        for (int i = 0; i < 4 * NP; ++i) { hv[i] = first ? make_uint4(0, 0, 0, 0) : ld_pkt16(src + (i >> 2) * 256 + (i & 3) * 32); ok = ok && hv[i].x != 0; }
        if (first || __all_sync(0xffffffffu, ok)) break;
        SPIN_GUARD(n);
    }
#pragma unroll
    for (int i = 0; i < 4 * NP; ++i) stsm4(dst + (i >> 2) * 4096 + (i & 3) * 512, hv[i].x, hv[i].y, hv[i].z, hv[i].w);
    done();
    if (!first) {
#pragma unroll
        for (int i = 0; i < 4 * NP; ++i) src[(i >> 2) * 256 + (i & 3) * 32] = make_uint4(0, 0, 0, 0);
    }
}

template <int N, class G, class U>
__device__ __forceinline__ void glu(uint32_t (&h)[N], G g, U u) {
#pragma unroll
    for (int i = 0; i < N; ++i) h[i] = pack2(fmaf(tanh_(g(2 * i)), u(2 * i), u(2 * i)), fmaf(tanh_(g(2 * i + 1)), u(2 * i + 1), u(2 * i + 1)));
}
__device__ __forceinline__ void put_h(const uint32_t (&h)[32], uint32_t sb, uint32_t wg, Stg& stg) {
    IDX();
    const uint32_t buf = stg.acquire2(sb, wg);
#pragma unroll
    for (int k = 0; k < 8; ++k) stsm4(buf + (k >> 2) * 8192 + (pan_addr ^ ((k & 3) << 5)), h[4 * k], h[4 * k + 1], h[4 * k + 2], h[4 * k + 3]);
    fence_async_smem();
    __syncwarp();
    if (lane < 2) mbar_arrive(BAR_SFULL(sb, wg * 2 + lane));
}

template <int NP, bool PREV>
__device__ __forceinline__ void passes128(uint32_t (&hp)[32], uint32_t sb, uint32_t wg, uint32_t tw, Ring& r, Stg& stg) {
#pragma unroll 1
    for (int p = 0; p < NP; ++p) {
        float b256[128], none[1];
        const int put_at = !PREV && p == 0 ? -1 : wg ? PUT1 : PUT0;
        mainloop32<false, LAGS>(b256, none, sb, wg, tw, r, EV_LAG2 + p, 80 + 32 * (p & 1), [&](int it) { if (it == put_at) put_h(hp, sb, wg, stg); },
                                [&] { if (PREV || p < NP - 1) mbar_wait(BAR_FULL(sb, r.slot), r.par); });
        if (threadIdx.x == 0) { TL(29 + 2 * p); TC(114 + 2 * p); }
        if (threadIdx.x == 128) TL(53 + 2 * (p & 1));
        CS(24 + 2 * (p & 1));
        glu(hp, [&](int i) { return b256[i + (i & 32)]; }, [&](int i) { return b256[i + (i & 32) + 32]; });
        if (threadIdx.x == 0) { TL(30 + 2 * p); TC(115 + 2 * p); }
        if (threadIdx.x == 128) TL(54 + 2 * (p & 1));
        CS(25 + 2 * (p & 1));
    }
}

__global__ void __launch_bounds__(384, 1)
fused_block_kernel(const __grid_constant__ Ptrs pt, const __grid_constant__ Maps mp) {
    uint32_t* const g_flags = pt.mail->flags;
    uint2* const g_mod = pt.mail->mod;
    uint4* const g_st1 = pt.mail->st1;
    uint32_t* const g_par2 = pt.mail->par2;
    uint4* const g_halo = pt.mail->halo;
    const __nv_bfloat16* __restrict__ cvec = pt.c;
    if (threadIdx.x == 224) { prefetch_map(&mp.wm8); prefetch_map(&mp.x); }
    extern __shared__ __align__(1024) uint8_t smem[];
    const uint32_t sb = smem_u32(smem);
    const uint32_t tid = threadIdx.x, tw = tid & 127, lane = tid & 31;
    const uint32_t warp = __shfl_sync(0xffffffffu, tid >> 5, 0), wg = warp >> 2;
    uint32_t rank; asm("mov.u32 %0, %%cluster_ctarank;" : "=r"(rank));
    rank = __shfl_sync(0xffffffffu, rank, 0);
    uint32_t ep;
    uint32_t smid; asm volatile("mov.u32 %0, %%smid;" : "=r"(smid));
    const int c = __shfl_sync(0xffffffffu, smid >> 1, 0);
    const int c7 = ((c - 32) * 37) >> 8;
    int grp = c < 32 ? c & 7 : c < 60 ? c - 31 - 7 * c7 : c < 62 ? -1 : 0;
    const int j = c < 32 ? c >> 3 : c < 60 ? 4 + c7 : c < 62 ? (c - 60) * 2 + rank : c - 58;
    const bool aux = grp < 0;
    const int m = grp * 2 + rank;
    uint4* const g_st2 = g_halo + (m > 0 ? (m - 1) * 8 * 512 : 128);

    bool cluster_arrive_early = false;
    if (wg < 2) {
      if (!KDEBUG) cluster_arrive();
      ep = flag_get(g_flags + FL_DONE);
      uint16_t cw[8];
      {
          const __nv_bfloat16* cp = cvec + ((tw >> 5) * 32 + (tw & 3) * 2) * 8 + (lane >> 2);
#pragma unroll
          for (int i = 0; i < 8; ++i) asm volatile("ld.global.nc.u16 %0, [%1];" : "=h"(cw[i]) : "l"(cp + (i >> 1) * 64 + (i & 1) * 8));
      }
      asm volatile("setmaxnreg.inc.sync.aligned.u32 224;");
      if (tid == 0) TL(58);
      if (KDEBUG) cluster_arrive();
      Ring r{0, 0};
      Stg stg{0, 0};
      if (aux) {
        if (wg == 0) {
            const uint4 cv = *(const uint4*)(cvec + tw * 8);
            sts128(sb + OFF_STG + (tw >> 3) * 1024 + (tw & 7) * 16, pack2(silu_(bf_lo(cv.x)), silu_(bf_hi(cv.x))), pack2(silu_(bf_lo(cv.y)), silu_(bf_hi(cv.y))),
                   pack2(silu_(bf_lo(cv.z)), silu_(bf_hi(cv.z))), pack2(silu_(bf_lo(cv.w)), silu_(bf_hi(cv.w))));
            fence_async_smem();
        }
        cluster_wait();
        ep = __shfl_sync(0xffffffffu, ep, 0) / NCTA + 1;
        if (wg == 0) {
            bar_sync(1, 128);
#pragma unroll 1
            for (int p = 0; p < 4; ++p) {
                float acc[4][4] = {};
                uint32_t prev = 0;
#pragma unroll 1
                for (int kc = 0; kc < 16; ++kc) {
                    mbar_wait(BAR_FULL(sb, r.slot), r.par);
                    wg_fence();
#pragma unroll
                    for (int k = 0; k < 16; ++k)
                        wgmma_n8_ta(acc[k & 3], mk_desc(d16(sb) + r.slot * (SLOT >> 4), (k & 3) * 8192 + (k >> 2) * 2048, 8192, 1024, 1), mk_desc(d16(sb) + kc * 64, OFF_STG + (k >> 2) * 32, 16, 1024, 1));
                    wg_commit();
                    wg_wait<1>();
                    if (kc > 0 && tw < 4) mbar_arrive(BAR_EMPTY(sb, prev));
                    prev = r.slot;
                    r.next();
                }
                wg_wait<0>();
                if (tw < 4) mbar_arrive(BAR_EMPTY(sb, prev));
                if (!(tw & 3)) {
#pragma unroll
                    for (int i = 0; i < 8; ++i) {
                        asm volatile("" : "+f"(acc[i >> 1][(i & 1) * 2]) :: "memory");
                        asm volatile("st.shared.u16 [%0], %1;" :: "r"(sb + OFF_TAB + ((i >> 1) * 64 + (tw >> 5) * 16 + (i & 1) * 8 + (lane >> 2)) * 2), "h"((uint16_t)pack2(acc[i >> 1][(i & 1) * 2], 0.f)) : "memory");
                    }
                }
                bar_sync(1, 128);
                const int vec = p ? 6 - p : 2, blk = (vec - 2) * 4 + j;
                const uint32_t val = lds32(sb + OFF_TAB + tw * 4);
                if (vec == 2 || vec == 5) st_pkt(g_mod + (8 + blk) * 128 + tw, val, ep);
                else {
                    const float one = vec == 4 ? 1.f : 0.f;
                    g_par2[((blk & 3) * 16 + (tw >> 3)) * 16 + (tw & 3) * 4 + (vec - 3) * 2 + ((tw >> 2) & 1)] =
                        pack2(0.5f * bf_round(one + bf_lo(val)), 0.5f * bf_round(one + bf_hi(val)));
                }
                bar_sync(1, 128);
                if (tw == 0) {
                    if (p == 3) asm volatile("red.release.gpu.global.add.u32 [%0], 1;" :: "l"(&g_flags[FL_LN2]) : "memory");
                    TL(1 + p);
                }
            }
            if (lane < 2) mbar_arrive_cta(BAR_ONE(sb, EV_P0), lane);
        }
        r = Ring{64 % NSLOT, (64 / NSLOT) & 1};
        mbar_wait(BAR_ONE(sb, EV_P0), 0);
        mbar_wait(BAR_FULL(sb, r.slot), r.par);
        uint32_t hp[32] = {};
        passes128<4, false>(hp, sb, wg, tw, r, stg);
        put_h(hp, sb, wg, stg);
      } else {
        float xs[64];
        uint32_t xp[32];
        {
            sts128(sb + tid * 16, pack2(silu_(bf_lo(cw[0])), silu_(bf_lo(cw[1]))), pack2(silu_(bf_lo(cw[2])), silu_(bf_lo(cw[3]))),
                   pack2(silu_(bf_lo(cw[4])), silu_(bf_lo(cw[5]))), pack2(silu_(bf_lo(cw[6])), silu_(bf_lo(cw[7]))));
            cluster_wait();
            ep = __shfl_sync(0xffffffffu, ep, 0) / NCTA + 1;
            load_slab(xp, stg.acquire2(sb, wg));
            unpack_slab(xs, xp);
            if (tid == 0) TL(24);
            if (tid == 128) TL(27);
        }
#pragma unroll 1
        for (int blk = 0; ; ++blk) {
        {
            IDX();
            uint4* const st = (blk ? g_st2 : g_st1 + m * 8 * 512) + wg * 64 + w4 * 16 + g8;
            RowAcc ra;
#pragma unroll
            for (int e = 0; e < 64; ++e) ra.add(e, xs[e]);
            ra.publish(st + j * 512, q4, ep);
            uint32_t t_pub = 0; if (PDLY) asm volatile("mov.u32 %0, %%clock;" : "=r"(t_pub));
            if (tid == 0) TL(blk ? 9 : 26);
            if (tid == 128 && blk) TL(34);
            if (blk) CS(11);
            LnPar lp;
            if (blk == 0) {
            uint4* const mod_out = pt.mail->mod1 + g8 * 512 + (m * 8 + j) * 4 + q4;
            if (wg == 0) {
                uint4 af[8];
#pragma unroll
                for (int i = 0; i < 8; ++i) af[i] = lds128(sb + w4 * 512 + i * 64 + q4 * 16);
                float c[4][4] = {};
#pragma unroll
                for (int i = 0; i < 8; ++i) {
                    if (!(i & 1)) mbar_wait(BAR_ONE(sb, EV_WIN + (i >> 1)), 0);
                    if (i == 6 && tid == 0) TL(25);
#pragma unroll
                    for (int h = 0; h < 2; ++h) {
                        uint32_t b0, b1, b2, b3;
                        ldsm4t(sb + 5 * SLOT + i * 4096 + w4 * 1024 + h * 512 + (lane & 15) * 32 + (lane >> 4) * 16, b0, b1, b2, b3);
                        mma16816(c[2 * h], h ? af[i].z : af[i].x, 0u, h ? af[i].w : af[i].y, 0u, b0, b1);
                        mma16816(c[2 * h + 1], h ? af[i].z : af[i].x, 0u, h ? af[i].w : af[i].y, 0u, b2, b3);
                    }
                }
                if (lane < 4) sts128(sb + OFF_TAB + w4 * 64 + lane * 16, __float_as_uint(c[0][0] + c[2][0]), __float_as_uint(c[0][1] + c[2][1]),
                                     __float_as_uint(c[1][0] + c[3][0]), __float_as_uint(c[1][1] + c[3][1]));
                if (lane < 2) mbar_arrive_cta(BAR_ONE(sb, EV_P0), lane);
                bar_sync(1, 128);
                if (w4 == 0) {
                    float a[4] = {0.f, 0.f, 0.f, 0.f};
#pragma unroll
                    for (int i = 0; i < 4; ++i) {
                        const uint4 t = lds128(sb + OFF_TAB + i * 64 + q4 * 16);
                        a[0] += __uint_as_float(t.x); a[1] += __uint_as_float(t.y); a[2] += __uint_as_float(t.z); a[3] += __uint_as_float(t.w);
                    }
                    const float add = m >= 8 ? 1.f : 0.f;
                    st_pkt16(mod_out, pack2(bf_round(a[0]) + add, bf_round(a[1]) + add), pack2(bf_round(a[2]) + add, bf_round(a[3]) + add), ep, 0);
                    if (tid == 0) TL(3);
                }
            } else if (LWAIT >= 0) mbar_wait(BAR_ONE(sb, EV_WIN + LWAIT), 0);
            } else {
                mbar_wait2(BAR_ONE(sb, EV_LN2), BAR_FULL(sb, 0), 0);
            }
            lp.load(sb, q4);
#pragma unroll
            for (int e = 0; e < 32; ++e) xp[e] = pack2(xs[2 * e], xs[2 * e + 1]);
            if (PDLY && blk) { uint32_t t1; do { asm volatile("mov.u32 %0, %%clock;" : "=r"(t1)); } while (t1 - t_pub < PDLY); }
            if (blk) CS(13);
            const LnRow n = merge_stats(st, q4, ep, sb);
            if (tid == 0) TL(blk ? 49 : 48);
            if (tid == 128) TL(blk ? 45 : 28);
            if (blk) CS(18);
            uint32_t xn[32];
            ln_norm(xn, xs, n);
            if (blk == 0) {
                mbar_wait2(BAR_FULL(sb, 0), BAR_ONE(sb, EV_PAR), 0);
                if (FD0 && wg == 0) { uint32_t t0, t1; asm volatile("mov.u32 %0, %%clock;" : "=r"(t0)); do { asm volatile("mov.u32 %0, %%clock;" : "=r"(t1)); } while (t1 - t0 < FD0); }
                lp.load(sb, q4);
            }
            ln_emit(xn, lp, sb, wg, ix);
            if (tid == 0) { TL(blk ? 36 : 8); TC(blk ? 109 : 103); }
            if (tid == 128) TL(blk ? 43 : 22);
            if (blk) CS(21);
        }
        uint32_t hp[32];
        if (blk == 0) {
        {
            float big[128], sml[64];
            step32<true, true>(big, sml, sb, wg, r.slot, 0);
            TS(0, 0);
            Pipe pp(sb, tw, r.slot);
            r.next();
#pragma unroll 1
            for (int it = 1; it < 32 - LAGQ; ++it) {
                pp.acquire<true>(sb, wg ? 0 : AF_REL, r);
                step32<true, false>(big, sml, sb, wg, r.slot, it < 4 ? it : -1);
                pp.issued(r.slot);
                TS(it, 0);
                r.next();
            }
            auto half = [&](uint32_t slot, bool rest) {
                const uint32_t st = d16(sb) + slot * (SLOT >> 4);
#pragma unroll
                for (int k = 0; k < 2; ++k) {
                    const uint64_t da = mk_desc(st + wg * 256, k * 32, 16, 512, 2);
                    if (rest) wgmma_n256(big, da, mk_desc(st, 8192 + k * 2048, 4096, 1024, 1)); else wgmma_n128(sml, da, mk_desc(st, 24576 + k * 2048, 4096, 1024, 1));
                }
            };
            auto rest = [&](bool each) {
                wg_fence();
#pragma unroll
                for (int it = 32 - LAGQ; it < 32; ++it) { if (each && it > 32 - LAGQ) wg_fence(); half(it % NSLOT, true); if (each || it == 31) wg_commit(); }
            };
            stg.acquire2(sb, wg); mbar_wait2(BAR_SREADY(sb, 2), BAR_SREADY(sb, 3), 1);
#pragma unroll 1
            for (int it = 32 - LAGQ; it < 32; ++it) {
                pp.acquire<true>(sb, wg ? 0 : AF_REL, r);
                wg_fence(); half(r.slot, false); wg_commit();
                pp.issued(NSLOT);
                TS(it, 0);
                r.next();
            }
            if (wg) { rest(false); wg_wait<1>(); } else wg_wait<0>();
            CS(8);
            IDX();
            uint32_t k0[8], k1[8], k2[8], v0[8], v1[8], v2[8];
            const uint32_t nxt = warp + ((warp & 1) ? 3 : 1), mine = sb + OFF_STG + wg * 16384 + w4 * 2048;
            auto tails = [&](const float* kv, uint32_t (&kt)[8], uint32_t (&vt)[8]) {
#pragma unroll
                for (int t = 0; t < 8; ++t) { kt[t] = pack2(kv[4 * t + 2], kv[4 * t + 3]); vt[t] = pack2(kv[32 + 4 * t + 2], kv[32 + 4 * t + 3]); }
            };
            auto post = [&](int pn, uint32_t (&kt)[8], uint32_t (&vt)[8]) {
                uint4* dst = g_halo + (m * 8 + j) * 512 + (w4 >> 1) * 256 + pn * 128 + lane;
#pragma unroll
                for (int h = 0; h < 2; ++h) { if (!kt[4 * h]) kt[4 * h] = 0x8000u; if (!vt[4 * h]) vt[4 * h] = 0x8000u; }
#pragma unroll
                for (int h = 0; h < 2; ++h) { st_pkt16(dst + h * 32, kt[4 * h], kt[4 * h + 1], kt[4 * h + 2], kt[4 * h + 3]); st_pkt16(dst + 64 + h * 32, vt[4 * h], vt[4 * h + 1], vt[4 * h + 2], vt[4 * h + 3]); }
            };
            auto prepare = [&](int pn, const float* kv) {
                tails(kv, k2, v2);
                if (nxt < 8) {
                    const uint32_t dst = sb + OFF_STG + (nxt >> 2) * 16384 + (nxt & 3) * 2048 + pn * 8192 + lane * 16;
#pragma unroll
                    for (int h = 0; h < 2; ++h) { stsm4(dst + h * 512, k2[4 * h], k2[4 * h + 1], k2[4 * h + 2], k2[4 * h + 3]); stsm4(dst + 1024 + h * 512, v2[4 * h], v2[4 * h + 1], v2[4 * h + 2], v2[4 * h + 3]); }
                    if (pn == 0) bar_arrive(NB_TAIL + nxt, 64);
                    else { __syncwarp(); if (lane == 0) mbar_arrive(BAR_ONE(sb, EV_TAIL + nxt)); }
                } else if (pn == 0 && m < 15) post(0, k2, v2);
#pragma unroll
                for (int t = 0; t < 8; ++t) { k1[t] = pack2(kv[4 * t], kv[4 * t + 1]); v1[t] = pack2(kv[32 + 4 * t], kv[32 + 4 * t + 1]); }
                auto turn = [&] {
#pragma unroll
                    for (int t = 0; t < 8; ++t) { v1[t] = movm(v1[t]); v2[t] = movm(v2[t]); }
                };
                if (pn) turn();
                if (pn == 0) {
                    CS(2);
                    if (wg == 0) { rest(true); turn(); wg_wait<3>(); pp.rel(28 % NSLOT); wg_wait<2>(); pp.rel(29 % NSLOT); wg_wait<1>(); pp.rel(30 % NSLOT); }
                    else turn();
                    bar_sync(NB_TAIL + warp, 64); CS(4);
                }
                else mbar_wait(BAR_ONE(sb, EV_TAIL + __shfl_sync(0xffffffffu, warp, 0)), 0);
#pragma unroll
                for (int h = 0; h < 2; ++h) {
                    ldsm4(mine + pn * 8192 + lane * 16 + h * 512, k0[4 * h], k0[4 * h + 1], k0[4 * h + 2], k0[4 * h + 3]);
                    ldsm4t(mine + pn * 8192 + lane * 16 + 1024 + h * 512, v0[4 * h], v0[4 * h + 1], v0[4 * h + 2], v0[4 * h + 3]);
                }
            };
#pragma unroll
            for (int i = 0; i < 64; ++i) asm volatile("" : "+f"(sml[i]) :: "memory");
            prepare(0, sml);
            static_assert(LAGQ == 4, "");
            wg_wait<0>();
            if (wg) { pp.rel(28 % NSLOT); pp.rel(29 % NSLOT); pp.rel(30 % NSLOT); }
            pp.rel(31 % NSLOT);
            TS(31, 1);
            if (tid == 0) { TL(4); TC(104); }
            if (tid == 128) TL(50);
            CS(1);
#pragma unroll
            for (int i = 0; i < 128; ++i) asm volatile("" : "+f"(big[i]) :: "memory");
            if (nxt >= 8 && m < 15) { uint32_t kt[8], vt[8]; tails(big, kt, vt); post(1, kt, vt); }
            const bool lo0 = q4 * 2 > g8, lo1 = q4 * 2 + 1 > g8;
            const bool nopast = m == 0 && (warp & 5) == 0;
            const uint32_t lomask = (lo0 ? 0xFFFFu : 0u) | (lo1 ? 0xFFFF0000u : 0u);
            const uint32_t orow = mine + (lane & 7) * 128 + (((lane >> 3) ^ (lane & 7)) << 4);
            const float sl2 = 0.17677669529663687f * 1.4426950408889634f;
#pragma unroll
            for (int pn = 0; pn < 2; ++pn) {
                float e0[4], e1[4], mx[4], sum[4];
#pragma unroll
                for (int hh = 0; hh < 2; ++hh) {
                    uint32_t qf[8];
#pragma unroll
                    for (int i = 0; i < 8; ++i) qf[i] = pack2(big[64 + 32 * pn + 16 * hh + 2 * i], big[64 + 32 * pn + 16 * hh + 2 * i + 1]);
                    float s[3][4];
#pragma unroll
                    for (int t = 0; t < 3; ++t) {
                        const uint32_t* k = (t == 0 ? k0 : t == 1 ? k1 : k2) + 4 * hh;
                        s[t][0] = s[t][1] = s[t][2] = s[t][3] = 0.f;
                        mma16816(s[t], qf[0], qf[1], qf[2], qf[3], k[0], k[1]);
                        mma16816(s[t], qf[4], qf[5], qf[6], qf[7], k[2], k[3]);
                    }
#pragma unroll
                    for (int hf = 0; hf < 2; ++hf) {
                        const int u = hh * 2 + hf;
                        e0[u] = lo0 ? ((hf == 0 && nopast) ? -INFINITY : s[hf][hf * 2]) : s[hf + 1][hf * 2];
                        e1[u] = lo1 ? ((hf == 0 && nopast) ? -INFINITY : s[hf][hf * 2 + 1]) : s[hf + 1][hf * 2 + 1];
                        mx[u] = fmaxf(e0[u], e1[u]);
                    }
                }
#pragma unroll
                for (int o = 1; o < 4; o <<= 1)
#pragma unroll
                    for (int u = 0; u < 4; ++u) mx[u] = fmaxf(mx[u], __shfl_xor_sync(0xffffffffu, mx[u], o));
#pragma unroll
                for (int u = 0; u < 4; ++u) {
                    const float c = -mx[u] * sl2;
                    e0[u] = ex2(fmaf(e0[u], sl2, c)); e1[u] = ex2(fmaf(e1[u], sl2, c));
                    sum[u] = e0[u] + e1[u];
                }
#pragma unroll
                for (int o = 1; o < 4; o <<= 1)
#pragma unroll
                    for (int u = 0; u < 4; ++u) sum[u] += __shfl_xor_sync(0xffffffffu, sum[u], o);
#pragma unroll
                for (int u = 0; u < 4; ++u) {
                    const int h = u >> 1;
                    const float inv = rcp(sum[u]);
                    const uint32_t p = pack2(e0[u] * inv, e1[u] * inv);
                    const uint32_t* va = ((u & 1) ? v1 : v0) + 4 * h;
                    const uint32_t* vb = ((u & 1) ? v2 : v1) + 4 * h;
                    float o[2][4] = {};
#pragma unroll
                    for (int d = 0; d < 2; ++d) mma16816(o[d], va[2 * d], va[2 * d + 1], vb[2 * d], vb[2 * d + 1], p & lomask, p & ~lomask);
                    stsm4t((orow ^ ((u >> 1) << 6)) + pn * 8192 + (u & 1) * 1024, pack2(o[0][0], o[0][1]), pack2(o[0][2], o[0][3]), pack2(o[1][0], o[1][1]), pack2(o[1][2], o[1][3]));
                }
                fence_async_smem();
                __syncwarp();
                if (lane == 0) mbar_arrive(BAR_SFULL(sb, wg * 2 + pn));
                if (pn == 0) { CS(5); block_end(sb, 0); prepare(1, big); CS(3); }
            }
            CS(6);
            if (tid == 32) TL(41);
            mbar_wait2(BAR_FULL(sb, 32 % NSLOT), BAR_FULL(sb, 33 % NSLOT), (32 / NSLOT) & 1);
            load_slab(xp, sb + (32 % NSLOT + wg) * SLOT);
#pragma unroll
            for (int e = 0; e < 32; ++e) hp[e] = __float_as_uint(big[e]);
            bar_sync(1 + wg, 128);
            if (tid == 0) { TL(6); TC(106); }
            if (tid == 128) TL(44);
            CS(7);
        }
        } else {
        {
            float ag[88], au[88];
            mainloop32<true, LAG>(ag, au, sb, wg, tw, r, EV_LAG1, 48, [](int) {}, [&] {
                Ring q = r; if (!wg) q.next();
                mbar_wait(BAR_EMPTY(sb, q.slot), q.par ^ 1);
                mbar_wait(BAR_FULL(sb, r.slot), r.par);
            });
            if (tid == 0) { TL(10); TC(110); }
            if (tid == 128) TL(51);
            CS(22);
            {
                IDX();
                uint32_t h3[12];
                glu(h3, [&](int i) { return ag[64 + i]; }, [&](int i) { return au[64 + i]; });
#pragma unroll
                for (int k = 0; k < 3; ++k) stsm4(sb + (wg ? P3_SLOT1 : P3_SLOT0) * SLOT + 24576 + (pan_addr ^ (k << 5)), h3[4 * k], h3[4 * k + 1], h3[4 * k + 2], h3[4 * k + 3]);
            }
            glu(hp, [&](int i) { return ag[i]; }, [&](int i) { return au[i]; });
            if (tid == 0) { TL(11); TC(111); }
            if (tid == 128) TL(52);
            CS(23);
        }
        passes128<2, true>(hp, sb, wg, tw, r, stg);
        if (tid == 0) { TL(12); TC(112); }
        }
        {
            float acc[64], gf[32];
            mainloop64(acc, blk == 0, sb, wg, tw, r, [&] { put_h(hp, sb, wg, stg); }, [&] {
                mbar_wait(BAR_ONE(sb, EV_GA + blk), 0);
                unpack_slab(xs, xp);
                uint32_t gt[16];
#pragma unroll
                for (int cg = 0; cg < 16; ++cg) gt[cg] = lds32(sb + OFF_TAB + blk * 256 + cg * 16 + (tw & 3) * 4);
#pragma unroll
                for (int i = 0; i < 16; ++i) unpack2(gt[i], gf[2 * i], gf[2 * i + 1]);
            }, [&] { stg.acquire2(sb, wg); });
            if (tid == 0) { TL(blk ? 13 : 7); TC(blk ? 113 : 107); }
            if (tid == 128) TL(blk ? 57 : 42);
            CS(blk ? 30 : 10);
#pragma unroll
            for (int e = 0; e < 64; ++e) xs[e] = fmaf(gf[(e >> 2) * 2 + (e & 1)], acc[e], xs[e]);
        }
        if (blk) break;
        }
        {
            IDX();
#pragma unroll
            for (int p = 0; p < 2; ++p) {
                store_slab(xs, sb + OFF_STG + wg * 16384, 8192, pan_addr, 4 * p, 4 * p + 4);
                stg.publish(sb, wg, lane);
            }
            cluster_arrive();
            if (tid == 0) TL(14);
            CS(31);
        }
      }
    } else {
        if (warp == 8 && !aux && elect_one()) {
#pragma unroll
            for (int i = 0; i < 4; ++i) mbar_init(BAR_SREADY(sb, i), 1);
#pragma unroll
            for (int i = 0; i < 4; ++i) mbar_init(BAR_ONE(sb, EV_WIN + i), 1);
#pragma unroll
            for (int i = 0; i < 4; ++i) {
                mbar_expect_tx(BAR_SREADY(sb, i), 8192);
                tma_load3(sb + OFF_STG + i * 8192, &mp.x, j * 128 + (i & 1) * 64, m * 64 + (i >> 1) * 32, BAR_SREADY(sb, i));
            }
#pragma unroll 1
            for (int i = 0; i < 4; ++i) {
                mbar_expect_tx(BAR_ONE(sb, EV_WIN + i), 8192);
                tma_load(sb + 5 * SLOT + i * 8192, &mp.wm8, 2 * i * 6144 + (m * 8 + j) * 16, 0, BAR_ONE(sb, EV_WIN + i));
                tma_load(sb + 5 * SLOT + i * 8192 + 4096, &mp.wm8, (2 * i + 1) * 6144 + (m * 8 + j) * 16, 0, BAR_ONE(sb, EV_WIN + i));
            }
        }
        __syncwarp();
        asm volatile("setmaxnreg.dec.sync.aligned.u32 56;");
        if (elect_one()) {
            if (warp == 8) {
                prefetch_map(&mp.wqkv); prefetch_map(&mp.wmod);
            } else if (warp < 11) {
                mbar_init(BAR_EMPTY(sb, NSLOT), 1);
#pragma unroll
                for (int i = 0; i < 2; ++i) { mbar_init(BAR_SFULL(sb, (warp - 9) * 2 + i), 4); if (aux) mbar_init(BAR_SREADY(sb, (warp - 9) * 2 + i), 1); }
#pragma unroll
                for (int i = 0; i < 3; ++i) {
                    mbar_init(BAR_EMPTY(sb, (warp - 9) * 3 + i), 4);
                    mbar_init(BAR_FULL(sb, (warp - 9) * 3 + i), 1); mbar_init(BAR_FULL(sb, (warp - 9) * 3 + i) + AF_REL, 1);
                }
            } else {
#pragma unroll
                for (int i = EV_P0; i < EV_COUNT; ++i) mbar_init(BAR_ONE(sb, i), i == EV_P0 ? 8 : 1);
            }
            asm volatile("fence.mbarrier_init.release.cluster;" ::: "memory");
        }
        __syncwarp();
        cluster_arrive();
        ep = 0;
        if (warp != 8 || aux) ep = flag_get(g_flags + FL_DONE);
        cluster_wait();
        ep = __shfl_sync(0xffffffffu, ep, 0) / NCTA + 1;
        if (warp == 8) {
            const bool el = elect_one();
            Ring r{0, 1};
            if (aux) {
                {
                    uint32_t n = 0;
                    while (!__all_sync(0xffffffffu, ld_pkt16(pt.mail->mod1 + 256).z == ep)) { SPIN_GUARD(n); __nanosleep(200); }
                }
#pragma unroll 1
                for (int it = 0; it < 64; ++it) {
                    const int col = (it < 16 ? 2048 : 6144 - (it >> 4) * 1024) + j * 256;
                    mbar_wait(BAR_EMPTY(sb, r.slot), r.par);
                    const uint32_t st = sb + r.slot * SLOT, fb = BAR_FULL(sb, r.slot);
                    if (el) {
                        mbar_expect_tx(fb, 32768);
#pragma unroll
                        for (int b = 0; b < 4; ++b) tma_load_ef(st + b * 8192, &mp.wmod, col + b * 64, (it & 15) * 64, fb);
                    }
                    r.next();
                }
                mbar_wait(BAR_ONE(sb, EV_P0), 0);
                const CUtensorMap* wm = rank ? &mp.wu : &mp.wg;
#pragma unroll 1
                for (int g = 0; g < 128; ++g) {
                    const int mx = (j >> 1) * 8 + (g >> 5) * 2 + rank, k0 = ((g & 14) << 6) + ((g & 16) << 2) + ((g & 1) << 5);
                    if (!(g & 15) && g <= 32) mbar_wait(BAR_ONE(sb, EV_H0 + (g >> 4)), 0);
                    mbar_wait(BAR_EMPTY(sb, r.slot), r.par);
                    const uint32_t st = sb + r.slot * SLOT, fb = BAR_FULL(sb, r.slot);
                    if (el) {
                        mbar_expect_tx(fb, 24576);
                        tma_load_mc(st + 8192 + rank * 4096, wm, HC3, k0, fb);
                        tma_load_mc(st + 16384 + rank * 4096, wm, HC3 + 64, k0, fb);
                        tma_load(st, &mp.h2l, k0, mx * 128, fb);
                    }
                    r.next();
                }
            } else {
#pragma unroll 1
                for (int it = 0; it < 32; ++it) {
                    const int cb = j * 128 + rank * 64, k0 = kof(it, 2, j);
                    if (it == BW0) mbar_wait(BAR_ONE(sb, BWEV), 0);
                    if (it == BW1) mbar_wait(BAR_ONE(sb, EV_PAR), 0);
                    if (it == 5) mbar_wait(BAR_ONE(sb, EV_P0), 0);
                    if (it == AG0) mbar_wait(BAR_ONE(sb, (AGW & 1) ? EV_AGO : EV_FGO), 0);
                    mbar_wait(BAR_EMPTY(sb, r.slot), r.par);
                    const uint32_t st = sb + r.slot * SLOT, fb = BAR_FULL(sb, r.slot);
                    if (el) {
                        mbar_expect_tx(fb, it < 4 ? 24576 : 28672);
                        tma_load_mc(st + 24576 - rank * 16384, &mp.wqkv, 1024 + cb, k0, fb);
                        tma_load_mc(st + 28672 - rank * 16384, &mp.wqkv, 2048 + cb, k0, fb);
                        tma_load_mc(st + 16384 + rank * 4096, &mp.wqkv, cb, k0, fb);
                        if (it < 4) mbar_arrive(fb + AF_REL);
                        if (it == PFWO + (m >> 1)) { tma_prefetch(&mp.wo, j * 128, m * 64); tma_prefetch(&mp.wo, j * 128 + 64, m * 64); }
                        if (it >= PFG && it < PFG + PFN && (it & 7) == grp) {
                            const int kp = kof(it - PFG + PFO, 2, j);
                            tma_prefetch(rank ? &mp.wu : &mp.wg, hcol(0, j), kp); tma_prefetch(rank ? &mp.wu : &mp.wg, hcol(0, j) + 64, kp);
                            asm volatile("cp.async.bulk.prefetch.tensor.3d.L2.global [%0, {%1, %2, %3}];" :: "l"(rank ? &mp.wu3 : &mp.wg3), "r"(0), "r"(j), "r"(kp) : "memory");
                        }
                    }
                    r.next();
                }
                if (el) mbar_arrive(BAR_ONE(sb, EV_KV));
#pragma unroll 1
                for (int it = 0; it < 16; ++it) {
                    const int k0 = kof(it, 1, j);
                    if (it == AG1) mbar_wait(BAR_ONE(sb, (AGW & 2) ? EV_AGO1 : EV_FGO1), 0);
                    mbar_wait(BAR_EMPTY(sb, r.slot), r.par);
                    const uint32_t st = sb + r.slot * SLOT, fb = BAR_FULL(sb, r.slot);
                    if (el) {
                        mbar_expect_tx(fb, it < 2 ? 32768 : 24576);
                        tma_load_mc(st + 16384 + rank * 8192, &mp.wo, j * 128 + rank * 64, k0, fb);
                        if (it < 2) {
                            tma_load3(st, &mp.x, j * 128, m * 64 + it * 32, fb); tma_load3(st + 8192, &mp.x, j * 128 + 64, m * 64 + it * 32, fb);
                            mbar_arrive(fb + AF_REL);
                        }
                        if (it == 6) { prefetch_map(rank ? &mp.wu : &mp.wg); prefetch_map(rank ? &mp.wu3 : &mp.wg3); }
                    }
                    r.next();
                }
                const CUtensorMap* wm = rank ? &mp.wu : &mp.wg;
#pragma unroll 1
                for (int g = 0; g < 96; ++g) {
                    if (g == AG2) mbar_wait(BAR_ONE(sb, (AGW & 4) ? EV_AGO2 : EV_FGO2), 0);
                    const int p = g >> 5, cb = hcol(p, j), k0 = p == 0 ? kof(g, 2, j) : (g & 31) * 32;
                    mbar_wait(BAR_EMPTY(sb, r.slot), r.par);
                    const uint32_t st = sb + r.slot * SLOT, fb = BAR_FULL(sb, r.slot);
                    if (el) {
                        mbar_expect_tx(fb, (g < 4 || p > 0) ? 24576 : 28672);
                        tma_load_mc(st + 8192 + rank * 4096, wm, cb, k0, fb);
                        tma_load_mc(st + 16384 + rank * 4096, wm, cb + 64, k0, fb);
                        if (p == 0) tma_load3_mc(st + 24576 + rank * 4096, rank ? &mp.wu3 : &mp.wg3, j, k0, fb);
                        else tma_load(st, &mp.h2l, k0, m * 128, fb);
                        if (g < 4) mbar_arrive(fb + AF_REL);
                        if ((g & 7) == grp && g + PFC >= 96) tma_prefetch(&mp.wd, j * 128 + rank * 64, (g + PFC - 96) * 64);
                        if (g == 60) { prefetch_map(&mp.wd); prefetch_map(&mp.hb); }
                    }
                    r.next();
                }
#pragma unroll 1
                for (int g = 0; g < 56; ++g) {
                    if (g == 0 || (g & 15) == 6 && g > 6) mbar_wait(BAR_ONE(sb, EV_H0 + (g >> 4)), 0);
                    const int k0 = g * 64;
                    mbar_wait(BAR_EMPTY(sb, r.slot), r.par);
                    const uint32_t st = sb + r.slot * SLOT, fb = BAR_FULL(sb, r.slot);
                    if (el) {
                        mbar_expect_tx(fb, 32768);
                        tma_load_mc(st + 16384 + rank * 8192, &mp.wd, j * 128 + rank * 64, k0, fb);
                        tma_load(st, &mp.hb, k0, m * 128, fb); tma_load(st + 8192, &mp.hb, k0, m * 128 + 64, fb);
                        if ((g & 7) == grp && g + PFC < 56) tma_prefetch(&mp.wd, j * 128 + rank * 64, k0 + PFC * 64);
                    }
                    r.next();
                }
            }
        } else if (aux) {
            if (warp < 11) {
                const uint32_t w = warp - 9;
                const bool el = elect_one();
#pragma unroll 1
                for (int p = 0; p < 4; ++p) {
                    const int mx = (j >> 1) * 8 + p * 2 + rank;
                    if (el) { mbar_arrive(BAR_SREADY(sb, w * 2)); mbar_arrive(BAR_SREADY(sb, w * 2 + 1)); }
                    mbar_wait2(BAR_SFULL(sb, w * 2), BAR_SFULL(sb, w * 2 + 1), p & 1);
                    if (p < 3) pause(w ? HD1 : HD0);
                    if (el) tma_store(&mp.hb, HC3, mx * 128 + w * 64, sb + OFF_STG + w * 16384);
                    if (p < 3) pause(HP);
                    if (el) {
                        tma_store(&mp.hb, HC3 + 64, mx * 128 + w * 64, sb + OFF_STG + w * 16384 + 8192);
                        bulk_commit(); bulk_wait_fence(); flag_set(g_flags + FL_AUX + mx * 2 + w, ep * 8 + ST_H + 3);
                    }
                }
            } else {
                mbar_wait(BAR_ONE(sb, EV_P0), 0);
#pragma unroll 1
                for (int i = 0; i < 5; ++i) {
                    const uint32_t* f = g_flags + FL_PROG + fidx((j >> 1) * 8 + (i ? i - 1 : 0) * 2 + rank, lane >> 4, lane & (i ? 15 : 14));
                    uint32_t n = 0;
                    while (!__all_sync(0xffffffffu, (int32_t)(flag_get(f) - (ep * 8 + ST_H2)) >= 0)) { SPIN_GUARD(n); __nanosleep(200); }
                    if (i < 2) pause(AUXD);
                    if (lane == 0 && (i < 2 || i == 4)) mbar_arrive(BAR_ONE(sb, EV_H0 + (i < 2 ? i : 2)));
                }
            }
        } else if (warp == 11) {
            const bool el = elect_one();
            const int row0 = m * 128;
            if (el) { prefetch_map(&mp.h1h); prefetch_map(&mp.h2h); prefetch_map(&mp.h2l); }
            auto gate = [&](int vec, int ev) {
                const uint32_t lane = Idx().lane;
                uint4 v; uint32_t n = 0;
                while (true) {
                    v = ld_pkt2(g_mod + vec * 512 + j * 64 + lane * 2);
                    if (__all_sync(0xffffffffu, v.y == ep && v.w == ep)) break;
                    SPIN_GUARD(n); __nanosleep(300);
                }
                asm volatile("st.shared.v2.u32 [%0], {%1, %2};" :: "r"(sb + OFF_TAB + (ev - EV_GA) * 256 + lane * 8), "r"(v.x), "r"(v.z) : "memory");
                __syncwarp();
                if (lane == 0) mbar_arrive(BAR_ONE(sb, ev));
            };
            {
                const uint4* pk = pt.mail->mod1 + grp * 512 + j * 32 + lane;
                uint4 a, b; uint32_t n = 0;
                mbar_wait(BAR_ONE(sb, EV_WIN3), 0);
                while (true) {
                    a = ld_pkt16(pk); b = ld_pkt16(pk + 256);
                    if (__all_sync(0xffffffffu, a.z == ep && b.z == ep)) break;
                    SPIN_GUARD(n);
                }
                sts128(sb + OFF_PAR + lane * 16, a.x, a.y, b.x, b.y);
                __syncwarp();
                if (lane == 0) { mbar_arrive(BAR_ONE(sb, EV_PAR)); TL(46); }
            }
            mbar_wait(BAR_ONE(sb, EV_P0), 0);
            Ring r{0, 1};
#pragma unroll 1
            for (int ph = 0; ph < 3; ++ph) {
                const uint32_t lane = Idx().lane;
                const int sh = ph == 1 ? 1 : 2, nst = 8 << sh;
                const uint32_t half = 16384 >> sh, target = ep * 8 + ST_H1 + ph;
                const CUtensorMap* tm = ph == 0 ? &mp.h1h : ph == 1 ? &mp.o : &mp.h2h;
                if (ph == 1) {
                    gate(2, EV_GA);
                    mbar_wait(BAR_SREADY(sb, 1), 1);
                    fetch_halo<2>(g_halo + ((m - 1) * 8 + j) * 512 + 128 + lane, m == 0, sb + OFF_STG + 8192 + lane * 16,
                                  [&] { __syncwarp(); if (lane < 2) mbar_arrive(BAR_ONE(sb, EV_TAIL + 2 * lane)); });
                    CS(32);
                }
                if (ph == 2) {
                    uint32_t n = 0;
                    while ((int32_t)(flag_get(g_flags + FL_LN2) - ep * 4) < 0) { SPIN_GUARD(n); __nanosleep(200); }
                    const uint4 v = __ldcg((const uint4*)(g_par2 + j * 128) + lane);
                    sts128(sb + OFF_PAR + lane * 16, v.x, v.y, v.z, v.w);
                    __syncwarp();
                    if (lane == 0) mbar_arrive(BAR_ONE(sb, EV_LN2));
                }
                const uint32_t* const fl = g_flags + FL_PROG + fidx(m, lane >> 4, kof(lane & 15, 1, j) >> 6);
                const uint32_t lw = ~lane & 1, lt = lane >> 1, ls = (r.slot + lt) % NSLOT, lk = kof(lt, sh, j), lb = BAR_FULL(sb, ls) + (lw ? 0 : AF_REL);
                const uint32_t* const lf = g_flags + FL_PROG + fidx(m, lw, lk >> 6);
                int fr = 1 << sh;
                uint32_t todo = 0x3ffffu >> (2 * fr) << (2 * fr), have = ~todo, n = 0, v = 0;
                r.skip(fr);
#pragma unroll 1
                for (; fr < NSLOT; ++fr) { mbar_wait(BAR_EMPTY(sb, r.slot), r.par); r.next(); }
                if (ph == XST - 1) CS(33);
                v = flag_get(lf);
                do {
                    while (ph == 2 && fr < FRCAP && mbar_test(BAR_EMPTY(sb, r.slot), r.par)) { ++fr; r.next(); }
                    SPIN_GUARD(n);
                    const bool ok = (int32_t)(v - target) >= 0;
                    v = flag_get(lf);
                    have |= __ballot_sync(0xffffffffu, ok);
                    const uint32_t go = have & todo & ((1u << (2 * fr)) - 1);
                    if ((go >> lane) & 1) {
                        if (!lw) mbar_expect_tx(lb, half);
                        tma_load(sb + ls * SLOT + lw * half, tm, lk, row0 + lw * 64, lb);
                    }
                    __syncwarp();
                    if (lane < 2 && (todo & (0x555u << lane)) && !(todo & ~go & (0x555u << lane))) mbar_arrive(BAR_ONE(sb, (lane ? EV_FGO : EV_AGO) + ph));
                    if (ph == XST - 1) { if (go & (1u << (2 << sh))) CS(34); if (go & (2u << (2 << sh))) CS(35); if (todo & 0x555u) CS(36); if (todo & 0xaaau) CS(37); }
                    todo &= ~go;
                } while (~have);
                if (ph == XST - 1) CS(38);
                int k = kof(fr, sh, j);
#pragma unroll 1
                for (; fr < nst; ++fr) {
                    if (fr == 9 || fr == 18) {
                        const uint32_t skip = fr == 9 << (sh - 1) ? 0 : ~0x01fc01fcu;
                        while (~(__ballot_sync(0xffffffffu, (int32_t)(flag_get(fl) - target) >= 0) | skip)) SPIN_GUARD(n);
                    }
                    const uint32_t st = sb + r.slot * SLOT, fb = BAR_FULL(sb, r.slot);
                    mbar_wait(BAR_EMPTY(sb, r.slot), r.par);
                    if (el) {
                        tma_load(st + half, tm, k, row0 + 64, fb);
                        mbar_expect_tx(fb + AF_REL, half);
                        tma_load(st, tm, k, row0, fb + AF_REL);
                    }
                    if (ph == XST - 1 && fr == 9) CS(39);
                    r.next();
                    k = kof(fr + 1, sh, j);
                }
            }
#pragma unroll 1
            for (int p = 0; p < 4; ++p) {
                const uint32_t* f = g_flags + (p < 3 ? FL_PROG + m * 32 + lane : FL_AUX + m * 2 + (lane & 1));
                uint32_t n = 0;
                while (!__all_sync(0xffffffffu, (int32_t)(flag_get(f) - (ep * 8 + ST_H + p)) >= 0)) { SPIN_GUARD(n); __nanosleep(300); }
                if (el) mbar_arrive(BAR_ONE(sb, EV_H0 + p));
                if (p == 0) gate(5, EV_GB);
            }
        } else {
            const uint32_t w = warp - 9;
            const int row0 = m * 128 + w * 64;
            const uint32_t stg = sb + OFF_STG + w * 16384;
            uint32_t* const fl = g_flags + FL_PROG + fidx(m, w, 2 * j);
            uint32_t b = 0, par = 0;
            const bool el = elect_one();
            auto store = [&](const CUtensorMap* tm, int col, bool nat = false) {
                mbar_wait(BAR_SFULL(sb, w * 2 + b), (par >> b) & 1);
                par ^= 1u << b;
                if (el) {
                    if (nat) tma_store3(tm, col, row0 >> 1, 0, stg + b * 8192); else tma_store(tm, col, row0, stg + b * 8192);
                    bulk_commit();
                }
                b ^= 1;
            };
            auto send2 = [&](const CUtensorMap* tm, const uint32_t* buf, int step) {
                const uint32_t* const q = buf + (size_t)((row0 + lane) * (D_ / 2) + j * 64 + 31);
                store(tm, j * 128);
                if (step == XST) CS(33);
                uint32_t z = landed(el, q, D_ / 2, pt.zero);
                if (el) flag_set(fl, ep * 8 + step + z);
                if (step == XST) CS(34);
                if (step != ST_O) { mbar_wait(BAR_ONE(sb, EV_FGO + step - ST_H1), 0); pause(step == ST_H1 ? (w ? P1H : P1H + 1000) : w ? P2L : P2F); }
                store(tm, j * 128 + 64);
                if (step == XST) CS(35);
                z = landed(el, q + 32, D_ / 2, pt.zero);
                if (el) flag_set(fl + 1, ep * 8 + step + z);
                if (step == XST) CS(36);
            };
            auto free2 = [&]() { if (el) { mbar_arrive(BAR_SREADY(sb, w * 2)); mbar_arrive(BAR_SREADY(sb, w * 2 + 1)); } };
            if (el) { prefetch_map(&mp.h1s); prefetch_map(&mp.o); prefetch_map(&mp.out); prefetch_map(&mp.wo); }
            send2(&mp.h1s, pt.h1, ST_H1);
            if (w == 0) TL(47);
            free2();
            mbar_wait(BAR_ONE(sb, EV_KV), 0);
            mbar_wait(BAR_SREADY(sb, 0), 1);
            fetch_halo<1>(g_halo + ((m - 1) * 8 + j) * 512 + w * 256 + lane, m == 0, sb + OFF_STG + w * 4096 + lane * 16, [&] { bar_arrive(NB_TAIL + 2 * w, 64); CS(38); });
            send2(&mp.o, pt.o, ST_O);
            if (w == 0) TL(40); else TL(38);
            free2();
            send2(&mp.o, pt.o, ST_H2);
            if (el) { prefetch_map(&mp.hbs); prefetch_map(&mp.hb3); }
            if (w == 0) TL(37);
            free2();
#pragma unroll 1
            for (int p = 0; p < 3; ++p) {
                const int col = hcol(p, j);
                mbar_wait2(BAR_SFULL(sb, w * 2), BAR_SFULL(sb, w * 2 + 1), par & 1);
                par ^= 3;
#pragma unroll 1
                for (int i = 0; i < (p ? 2 : 3) * NSPL; ++i) {
                    pause(i ? HP / NSPL : p == 2 ? (w ? HE1 : HE0) : w ? HD1 : HD0);
                    const int pn = i / NSPL, ro = (i % NSPL) * (64 / NSPL);
                    if (el) {
                        if (pn < 2) tma_store(&mp.hbs, col + pn * 64, row0 + ro, stg + i * (8192 / NSPL));
                        else tma_store3(&mp.hb3, 0, j, row0 + ro, sb + (w ? P3_SLOT1 : P3_SLOT0) * SLOT + 24576 + ro * 128);
                        bulk_commit();
                    }
                }
                if (el) bulk_wait_read();
                free2();
                if (el) { bulk_wait_fence(); flag_set(fl, ep * 8 + ST_H + p); flag_set(fl + 1, ep * 8 + ST_H + p); }
            }
            cluster_arrive_early = true;
            cluster_arrive();
            store(&mp.out, j * 128, true); store(&mp.out, j * 128 + 64, true);
            if (el) bulk_wait_read();
        }
        __syncwarp();
    }
    if (aux || (wg == 2 && !cluster_arrive_early)) cluster_arrive();
    cluster_wait();
    if (KDEBUG == 5) __syncthreads();
    if (tid == 0) {
        TL(15);
        flag_add(pt.mail->flags + FL_DONE);
    }
}

typedef CUresult (*EncodeFn)(CUtensorMap*, CUtensorMapDataType, cuuint32_t, void*, const cuuint64_t*, const cuuint64_t*, const cuuint32_t*,
                             const cuuint32_t*, CUtensorMapInterleave, CUtensorMapSwizzle, CUtensorMapL2promotion, CUtensorMapFloatOOBfill);

void make_map(EncodeFn fn, CUtensorMap* m, const void* ptr, uint64_t rows, uint64_t cols, uint32_t brows, uint32_t bcols) {
    cuuint64_t dims[2] = {cols, rows}, strides[1] = {cols * 2};
    cuuint32_t box[2] = {bcols, brows}, es[2] = {1, 1};
    fn(m, CU_TENSOR_MAP_DATA_TYPE_BFLOAT16, 2, (void*)ptr, dims, strides, box, es, CU_TENSOR_MAP_INTERLEAVE_NONE,
       bcols == 64 ? CU_TENSOR_MAP_SWIZZLE_128B : bcols == 32 ? CU_TENSOR_MAP_SWIZZLE_64B : CU_TENSOR_MAP_SWIZZLE_NONE, CU_TENSOR_MAP_L2_PROMOTION_L2_256B, CU_TENSOR_MAP_FLOAT_OOB_FILL_NONE);
}

void make_map3(EncodeFn fn, CUtensorMap* m, const void* ptr) {
    cuuint64_t dims[3] = {D_, S_ / 2, 2}, strides[2] = {4 * D_, 2 * D_};
    cuuint32_t box[3] = {64, 32, 2}, es[3] = {1, 1, 1};
    fn(m, CU_TENSOR_MAP_DATA_TYPE_BFLOAT16, 3, (void*)ptr, dims, strides, box, es, CU_TENSOR_MAP_INTERLEAVE_NONE,
       CU_TENSOR_MAP_SWIZZLE_128B, CU_TENSOR_MAP_L2_PROMOTION_L2_256B, CU_TENSOR_MAP_FLOAT_OOB_FILL_NONE);
}

void make_map48(EncodeFn fn, CUtensorMap* m, const void* ptr, uint64_t rows, uint32_t brows) {
    cuuint64_t dims[3] = {48, 8, rows}, strides[2] = {96, 2 * F_};
    cuuint32_t box[3] = {64, 1, brows}, es[3] = {1, 1, 1};
    fn(m, CU_TENSOR_MAP_DATA_TYPE_BFLOAT16, 3, (void*)ptr, dims, strides, box, es, CU_TENSOR_MAP_INTERLEAVE_NONE,
       CU_TENSOR_MAP_SWIZZLE_128B, CU_TENSOR_MAP_L2_PROMOTION_L2_256B, CU_TENSOR_MAP_FLOAT_OOB_FILL_NONE);
}

}

extern "C" void kernel_launch(void* const* d_in, const int* in_sizes, int n_in, void* d_out, int out_size) {
    (void)in_sizes; (void)n_in; (void)out_size;
    void* fnp = nullptr;
    cudaDriverEntryPointQueryResult qr;
    cudaGetDriverEntryPoint("cuTensorMapEncodeTiled", &fnp, cudaEnableDefault, &qr);
    EncodeFn fn = (EncodeFn)fnp;
    void *h1, *o, *h2, *hb, *mail;
    cudaGetSymbolAddress(&h1, g_h1);
    cudaGetSymbolAddress(&mail, g_mail);
    cudaGetSymbolAddress(&o, g_o);
    cudaGetSymbolAddress(&hb, g_hb);
    h2 = o;
    Maps mp;
    make_map(fn, &mp.h1h, h1, S_, D_, 64, 32);
    make_map(fn, &mp.h2h, h2, S_, D_, 64, 32);
    make_map(fn, &mp.h1s, h1, S_, D_, 64, 64);
    make_map(fn, &mp.o, o, S_, D_, 64, 64);
    make_map(fn, &mp.h2l, h2, S_, D_, 128, 32);
    make_map(fn, &mp.hb, hb, S_, F_, 64, 64);
    make_map(fn, &mp.wqkv, d_in[1], D_, 3 * D_, 32, 64);
    make_map(fn, &mp.wo, d_in[2], D_, D_, 64, 64);
    make_map(fn, &mp.wg, d_in[4], D_, F_, 32, 64);
    make_map(fn, &mp.wu, d_in[5], D_, F_, 32, 64);
    make_map(fn, &mp.wd, d_in[6], F_, D_, 64, 64);
    make_map(fn, &mp.wmod, d_in[8], D_, 6 * D_, 64, 64);
    make_map(fn, &mp.wm8, d_in[8], D_ / 8, 8 * 6 * D_, 128, 16);
    make_map3(fn, &mp.x, d_in[0]);
    make_map3(fn, &mp.out, d_out);
    make_map48(fn, &mp.wg3, d_in[4], D_, 32);
    make_map48(fn, &mp.wu3, d_in[5], D_, 32);
    make_map48(fn, &mp.hb3, hb, S_, 64 / NSPL);
    make_map(fn, &mp.hbs, hb, S_, F_, 64 / NSPL, 64);
    cudaFuncSetAttribute(fused_block_kernel, cudaFuncAttributeMaxDynamicSharedMemorySize, SMEM_BYTES);
    cudaLaunchConfig_t cfg = {};
    cfg.gridDim = dim3(NCTA); cfg.blockDim = dim3(384); cfg.dynamicSmemBytes = SMEM_BYTES; cfg.stream = cudaStreamPerThread;
    cudaLaunchAttribute at[1];
    at[0].id = cudaLaunchAttributeClusterDimension; at[0].val.clusterDim.x = 2; at[0].val.clusterDim.y = 1; at[0].val.clusterDim.z = 1;
    cfg.attrs = at; cfg.numAttrs = 1;
    const Ptrs pt{(const __nv_bfloat16*)d_in[7], (Mail*)mail, (const uint32_t*)h1, (const uint32_t*)o, 0};
    cudaLaunchKernelEx(&cfg, fused_block_kernel, pt, mp);
}
```

```cpp
#include <cuda_runtime.h>
#include <cuda_bf16.h>
#include <cuda.h>
#include <stdint.h>
#include <stddef.h>

#define LAG 4
#define LAGS 4
#define LAGW 2
#define LAGD 4
#define LAGQ 4
#define PUT1 5
#define PUT0 10
#define PUTD1 6
#define PUTD0 10
#define MIDD 40
#define HD1 3000
#define HD0 1500
#define NSPL 2
#define HE1 2000
#define HE0 HD0
#define HP 2600
#define P1H 3000
#define P2L 2000
#define P2F 3000
#define AUXD 4000
#define FD0 200
#define AG0 6
#define AG1 6
#define AG2 8
#define AGW 2
#define FRCAP 7
#define BW0 0
#define BWEV EV_WIN
#define BW1 3
#define LWAIT 3
#define PFWO 12
#define PFG 8
#define PFN 24
#define PFC 10
#define PFO 0
#define RACC 1
#define KDEBUG 0
#define CSW 0
#define XST ST_O

namespace {

constexpr int S_ = 2048, D_ = 1024, F_ = 3584;
constexpr int NCTA = 132;
constexpr int NSLOT = 6;
constexpr uint32_t SLOT = 32768;
constexpr uint32_t OFF_STG = NSLOT * SLOT;
constexpr uint32_t OFF_BAR = OFF_STG + 32768;
constexpr uint32_t OFF_PAR = OFF_BAR + 512;
constexpr uint32_t OFF_TAB = OFF_PAR + 768;
constexpr uint32_t OFF_TL = OFF_PAR + 2048;
constexpr uint32_t SMEM_BYTES = OFF_TL + (KDEBUG ? 512 : 0);
constexpr uint32_t P3_SLOT1 = (32 + 16 + 32) % NSLOT, P3_SLOT0 = (P3_SLOT1 + 1) % NSLOT;

constexpr int ST_H1 = 1, ST_O = 2, ST_H2 = 3, ST_H = 4, FL_DONE = 0, FL_LN2 = 1, FL_AUX = 32, FL_PROG = 64;

struct Maps {
    CUtensorMap h1h, h1s, o, h2h, h2l, hb, wqkv, wo, wg, wu, wd, wmod, wm8, x, out, wg3, wu3, hb3, hbs;
};

struct Mail {
    uint32_t flags[16 * 32 + 64];
    uint2 mod[6 * D_ / 2];
    uint4 mod1[8 * 512];
    uint4 st1[128 * 512];
    uint32_t par2[D_];
    uint4 halo[128 * 512];
};
struct Ptrs { const __nv_bfloat16* c; Mail* mail; const uint32_t *h1, *o; uint32_t zero; };

__device__ __align__(128) Mail g_mail;
__device__ __align__(128) __nv_bfloat16 g_h1[S_ * D_];
__device__ __align__(128) __nv_bfloat16 g_o[S_ * D_];
__device__ __align__(128) __nv_bfloat16 g_hb[S_ * F_];
#define TL(i) do {} while (0)
#define TC(i) do {} while (0)
#define TS(g, which) do {} while (0)
#define CS(i) do {} while (0)

__device__ __forceinline__ uint32_t smem_u32(const void* p) { return (uint32_t)__cvta_generic_to_shared(p); }
__device__ __forceinline__ void mbar_init(uint32_t bar, uint32_t cnt) { asm volatile("mbarrier.init.shared::cta.b64 [%0], %1;" :: "r"(bar), "r"(cnt) : "memory"); }
__device__ __forceinline__ void mbar_expect_tx(uint32_t bar, uint32_t bytes) { asm volatile("mbarrier.arrive.expect_tx.shared::cta.b64 _, [%0], %1;" :: "r"(bar), "r"(bytes) : "memory"); }
__device__ __forceinline__ void mbar_arrive(uint32_t bar) { asm volatile("mbarrier.arrive.shared::cta.b64 _, [%0];" :: "r"(bar) : "memory"); }
__device__ __forceinline__ void mbar_arrive_cta(uint32_t bar, uint32_t cta) {
    asm volatile("{\n.reg .b32 r;\nmapa.shared::cluster.u32 r, %0, %1;\nmbarrier.arrive.shared::cluster.b64 _, [r];\n}" :: "r"(bar), "r"(cta) : "memory");
}
__device__ __forceinline__ void mbar_wait(uint32_t bar, uint32_t parity) {
    asm volatile("{\n.reg .pred p;\n.reg .u32 n;\nmov.u32 n, 0;\n"
        "W_LOOP:\nmbarrier.try_wait.parity.shared::cta.b64 p, [%0], %1;\n@p bra W_DONE;\n"
        "add.u32 n, n, 1;\nsetp.lt.u32 p, n, 0x400000;\n@p bra W_LOOP;\ntrap;\nW_DONE:\n}" :: "r"(bar), "r"(parity) : "memory");
}
__device__ __forceinline__ void mbar_wait2(uint32_t b0, uint32_t b1, uint32_t parity) {
    asm volatile("{\n.reg .pred p, q;\n.reg .u32 n;\nmov.u32 n, 0;\n"
        "W_LOOP:\nmbarrier.try_wait.parity.shared::cta.b64 p, [%0], %2;\nmbarrier.try_wait.parity.shared::cta.b64 q, [%1], %2;\nand.pred p, p, q;\n@p bra W_DONE;\n"
        "add.u32 n, n, 1;\nsetp.lt.u32 p, n, 0x400000;\n@p bra W_LOOP;\ntrap;\nW_DONE:\n}" :: "r"(b0), "r"(b1), "r"(parity) : "memory");
}
__device__ __forceinline__ bool mbar_test(uint32_t bar, uint32_t parity) {
    uint32_t r; asm volatile("{\n.reg .pred p;\nmbarrier.test_wait.parity.shared::cta.b64 p, [%1], %2;\nselp.u32 %0, 1, 0, p;\n}" : "=r"(r) : "r"(bar), "r"(parity) : "memory"); return r;
}
__device__ __forceinline__ bool mbar_test2(uint32_t b0, uint32_t b1, uint32_t parity) {
    uint32_t r;
    asm volatile("{\n.reg .pred p, q;\nmbarrier.test_wait.parity.shared::cta.b64 p, [%1], %3;\nmbarrier.test_wait.parity.shared::cta.b64 q, [%2], %3;\n"
        "and.pred p, p, q;\nselp.u32 %0, 1, 0, p;\n}" : "=r"(r) : "r"(b0), "r"(b1), "r"(parity) : "memory");
    return r;
}
__device__ __forceinline__ void tma_load3(uint32_t dst, const CUtensorMap* m, int c0, int c1, uint32_t bar) {
    asm volatile("cp.async.bulk.tensor.3d.shared::cluster.global.mbarrier::complete_tx::bytes [%0], [%1, {%3, %4, %5}], [%2];"
        :: "r"(dst), "l"(m), "r"(bar), "r"(c0), "r"(c1), "r"(0) : "memory");
}
__device__ __forceinline__ void tma_store3(const CUtensorMap* m, int c0, int c1, int c2, uint32_t src) {
    asm volatile("cp.async.bulk.tensor.3d.global.shared::cta.bulk_group [%0, {%2, %3, %4}], [%1];" :: "l"(m), "r"(src), "r"(c0), "r"(c1), "r"(c2) : "memory");
}
__device__ __forceinline__ void tma_load3_mc(uint32_t dst, const CUtensorMap* m, int c1, int c2, uint32_t bar) {
    asm volatile("cp.async.bulk.tensor.3d.shared::cluster.global.mbarrier::complete_tx::bytes.multicast::cluster.L2::cache_hint [%0], [%1, {%3, %4, %5}], [%2], %6, %7;"
        :: "r"(dst), "l"(m), "r"(bar), "r"(0), "r"(c1), "r"(c2), "h"((uint16_t)3), "l"(0x12F0000000000000ull) : "memory");
}
__device__ __forceinline__ void tma_load(uint32_t dst, const CUtensorMap* m, int c0, int c1, uint32_t bar) {
    asm volatile("cp.async.bulk.tensor.2d.shared::cluster.global.mbarrier::complete_tx::bytes [%0], [%1, {%3, %4}], [%2];"
        :: "r"(dst), "l"(m), "r"(bar), "r"(c0), "r"(c1) : "memory");
}
__device__ __forceinline__ void tma_load_ef(uint32_t dst, const CUtensorMap* m, int c0, int c1, uint32_t bar) {
    asm volatile("cp.async.bulk.tensor.2d.shared::cluster.global.mbarrier::complete_tx::bytes.L2::cache_hint [%0], [%1, {%3, %4}], [%2], %5;"
        :: "r"(dst), "l"(m), "r"(bar), "r"(c0), "r"(c1), "l"(0x12F0000000000000ull) : "memory");
}
__device__ __forceinline__ void tma_load_mc(uint32_t dst, const CUtensorMap* m, int c0, int c1, uint32_t bar) {
    asm volatile("cp.async.bulk.tensor.2d.shared::cluster.global.mbarrier::complete_tx::bytes.multicast::cluster.L2::cache_hint [%0], [%1, {%3, %4}], [%2], %5, %6;"
        :: "r"(dst), "l"(m), "r"(bar), "r"(c0), "r"(c1), "h"((uint16_t)3), "l"(0x12F0000000000000ull) : "memory");
}
__device__ __forceinline__ void tma_prefetch(const CUtensorMap* m, int c0, int c1) {
    asm volatile("cp.async.bulk.prefetch.tensor.2d.L2.global [%0, {%1, %2}];" :: "l"(m), "r"(c0), "r"(c1) : "memory");
}
__device__ __forceinline__ void tma_store(const CUtensorMap* m, int c0, int c1, uint32_t src) {
    asm volatile("cp.async.bulk.tensor.2d.global.shared::cta.bulk_group [%0, {%2, %3}], [%1];" :: "l"(m), "r"(src), "r"(c0), "r"(c1) : "memory");
}
__device__ __forceinline__ void bulk_commit() { asm volatile("cp.async.bulk.commit_group;" ::: "memory"); }
__device__ __forceinline__ void bulk_wait_read() { asm volatile("cp.async.bulk.wait_group.read 0;" ::: "memory"); }
__device__ __forceinline__ void fence_async_smem() { asm volatile("fence.proxy.async.shared::cta;" ::: "memory"); }
__device__ __forceinline__ void prefetch_map(const CUtensorMap* m) { asm volatile("prefetch.tensormap [%0];" :: "l"(m) : "memory"); }
__device__ __forceinline__ void wg_fence() { asm volatile("wgmma.fence.sync.aligned;" ::: "memory"); }
__device__ __forceinline__ void wg_commit() { asm volatile("wgmma.commit_group.sync.aligned;" ::: "memory"); }
template <int N> __device__ __forceinline__ void wg_wait() { asm volatile("wgmma.wait_group.sync.aligned %0;" :: "n"(N) : "memory"); }
__device__ __forceinline__ void bar_sync(int id, int n) { asm volatile("bar.sync %0, %1;" :: "r"(id), "r"(n) : "memory"); }
__device__ __forceinline__ void bar_arrive(int id, int n) { asm volatile("bar.arrive %0, %1;" :: "r"(id), "r"(n) : "memory"); }
__device__ __forceinline__ void flag_add(uint32_t* f) { asm volatile("red.relaxed.gpu.global.add.u32 [%0], 1;" :: "l"(f) : "memory"); }
__device__ __forceinline__ void flag_set(uint32_t* f, uint32_t v) { asm volatile("red.relaxed.gpu.global.max.u32 [%0], %1;" :: "l"(f), "r"(v) : "memory"); }
__device__ __forceinline__ uint32_t flag_get(const uint32_t* f) { uint32_t v; asm volatile("ld.relaxed.gpu.global.u32 %0, [%1];" : "=r"(v) : "l"(f) : "memory"); return v; }
__device__ __forceinline__ void bulk_wait_fence() { asm volatile("cp.async.bulk.wait_group 0;\nfence.proxy.async.global;\nfence.acq_rel.gpu;" ::: "memory"); }
__device__ __forceinline__ uint32_t landed(bool el, const uint32_t* p, uint32_t pitch, uint32_t zero) {
    if (el) asm volatile("cp.async.bulk.wait_group 0;" ::: "memory");
    __syncwarp();
    const uint32_t a = flag_get(p), b = flag_get(p + 32 * pitch);
    return __reduce_or_sync(0xffffffffu, (a | b) & zero);
}
__device__ __forceinline__ uint32_t d16(uint32_t addr) { return (addr & 0x3FFFF) >> 4; }
__device__ __forceinline__ uint64_t mk_desc(uint32_t a16, uint32_t off, uint32_t lbo, uint32_t sbo, uint32_t swz) {
    const uint32_t lo = a16 + (off >> 4) + ((lbo >> 4) << 16), hi = (sbo >> 4) | (swz << 30);
    return ((uint64_t)hi << 32) | lo;
}
__device__ __forceinline__ uint32_t pack2(float lo, float hi) {
    uint32_t r; asm("cvt.rn.bf16x2.f32 %0, %1, %2;" : "=r"(r) : "f"(hi), "f"(lo)); return r;
}
__device__ __forceinline__ uint32_t hfma2_bf16(uint32_t a, uint32_t b, uint32_t c) {
    uint32_t r; asm("fma.rn.bf16x2 %0, %1, %2, %3;" : "=r"(r) : "r"(a), "r"(b), "r"(c)); return r;
}
__device__ __forceinline__ float bf_lo(uint32_t v) { return __uint_as_float(v << 16); }
__device__ __forceinline__ float bf_hi(uint32_t v) { return __uint_as_float(v & 0xFFFF0000u); }
__device__ __forceinline__ void unpack2(uint32_t v, float& lo, float& hi) {
    asm volatile("shl.b32 %0, %2, 16;\nand.b32 %1, %2, 0xffff0000;" : "=f"(lo), "=f"(hi) : "r"(v));
}
__device__ __forceinline__ float bf_round(float x) { return __bfloat162float(__float2bfloat16_rn(x)); }
__device__ __forceinline__ void stsm4(uint32_t addr, uint32_t r0, uint32_t r1, uint32_t r2, uint32_t r3) {
    asm volatile("stmatrix.sync.aligned.m8n8.x4.shared.b16 [%0], {%1, %2, %3, %4};" :: "r"(addr), "r"(r0), "r"(r1), "r"(r2), "r"(r3) : "memory");
}
__device__ __forceinline__ void stsm4t(uint32_t addr, uint32_t r0, uint32_t r1, uint32_t r2, uint32_t r3) {
    asm volatile("stmatrix.sync.aligned.m8n8.x4.trans.shared.b16 [%0], {%1, %2, %3, %4};" :: "r"(addr), "r"(r0), "r"(r1), "r"(r2), "r"(r3) : "memory");
}
__device__ __forceinline__ uint32_t movm(uint32_t a) { uint32_t d; asm volatile("movmatrix.sync.aligned.m8n8.trans.b16 %0, %1;" : "=r"(d) : "r"(a)); return d; }
__device__ __forceinline__ void ldsm4(uint32_t addr, uint32_t& r0, uint32_t& r1, uint32_t& r2, uint32_t& r3) {
    asm volatile("ldmatrix.sync.aligned.m8n8.x4.shared.b16 {%0, %1, %2, %3}, [%4];" : "=r"(r0), "=r"(r1), "=r"(r2), "=r"(r3) : "r"(addr) : "memory");
}
__device__ __forceinline__ void ldsm4t(uint32_t addr, uint32_t& r0, uint32_t& r1, uint32_t& r2, uint32_t& r3) {
    asm volatile("ldmatrix.sync.aligned.m8n8.x4.trans.shared.b16 {%0, %1, %2, %3}, [%4];" : "=r"(r0), "=r"(r1), "=r"(r2), "=r"(r3) : "r"(addr) : "memory");
}
__device__ __forceinline__ void mma16816(float (&c)[4], uint32_t a0, uint32_t a1, uint32_t a2, uint32_t a3, uint32_t b0, uint32_t b1) {
    asm("mma.sync.aligned.m16n8k16.row.col.f32.bf16.bf16.f32 {%0, %1, %2, %3}, {%4, %5, %6, %7}, {%8, %9}, {%0, %1, %2, %3};"
        : "+f"(c[0]), "+f"(c[1]), "+f"(c[2]), "+f"(c[3]) : "r"(a0), "r"(a1), "r"(a2), "r"(a3), "r"(b0), "r"(b1));
}
__device__ __forceinline__ float rsq(float x) { float r; asm("rsqrt.approx.ftz.f32 %0, %1;" : "=f"(r) : "f"(x)); return r; }
__device__ __forceinline__ float rcp(float x) { float r; asm("rcp.approx.ftz.f32 %0, %1;" : "=f"(r) : "f"(x)); return r; }
__device__ __forceinline__ float ex2(float x) { float r; asm("ex2.approx.ftz.f32 %0, %1;" : "=f"(r) : "f"(x)); return r; }
__device__ __forceinline__ float tanh_(float x) { float t; asm("tanh.approx.f32 %0, %1;" : "=f"(t) : "f"(x)); return t; }
__device__ __forceinline__ void block_end(uint32_t opaque, uint32_t id) { asm volatile("{\n.reg .pred p;\nsetp.eq.u32 p, %0, %1;\n@p trap;\n}" :: "r"(opaque), "r"(0xffffff00u + id)); }
__device__ __forceinline__ float silu_(float x) { return __fdividef(x, 1.f + __expf(-x)); }
__device__ __forceinline__ void st_pkt(void* p, uint32_t a, uint32_t b) {
    asm volatile("{\n.reg .b64 t;\nmov.b64 t, {%1, %2};\nst.relaxed.gpu.global.b64 [%0], t;\n}" :: "l"(p), "r"(a), "r"(b) : "memory");
}
__device__ __forceinline__ uint4 ld_pkt2(const void* p) {
    uint4 v; asm volatile("{\n.reg .b64 t, u;\nld.relaxed.gpu.global.v2.b64 {t, u}, [%4];\nmov.b64 {%0, %1}, t;\nmov.b64 {%2, %3}, u;\n}"
        : "=r"(v.x), "=r"(v.y), "=r"(v.z), "=r"(v.w) : "l"(p) : "memory"); return v;
}
__device__ __forceinline__ void st_pkt16(void* p, uint32_t a, uint32_t b, uint32_t c, uint32_t d) {
    asm volatile("{\n.reg .b64 t, u;\n.reg .b128 w;\nmov.b64 t, {%1, %2};\nmov.b64 u, {%3, %4};\nmov.b128 w, {t, u};\nst.relaxed.gpu.global.b128 [%0], w;\n}"
        :: "l"(p), "r"(a), "r"(b), "r"(c), "r"(d) : "memory");
}
__device__ __forceinline__ uint4 ld_pkt16(const void* p) {
    uint4 v; asm volatile("{\n.reg .b64 t, u;\n.reg .b128 w;\nld.relaxed.gpu.global.b128 w, [%4];\nmov.b128 {t, u}, w;\nmov.b64 {%0, %1}, t;\nmov.b64 {%2, %3}, u;\n}"
        : "=r"(v.x), "=r"(v.y), "=r"(v.z), "=r"(v.w) : "l"(p) : "memory"); return v;
}
#define SPIN_GUARD(n) do { if (++(n) > (1u << 22)) asm volatile("trap;"); } while (0)
__device__ __forceinline__ uint4 lds128(uint32_t a) { uint4 v; asm volatile("ld.shared.v4.u32 {%0, %1, %2, %3}, [%4];" : "=r"(v.x), "=r"(v.y), "=r"(v.z), "=r"(v.w) : "r"(a) : "memory"); return v; }
__device__ __forceinline__ void sts128(uint32_t a, uint32_t x, uint32_t y, uint32_t z, uint32_t w) { asm volatile("st.shared.v4.u32 [%0], {%1, %2, %3, %4};" :: "r"(a), "r"(x), "r"(y), "r"(z), "r"(w) : "memory"); }
__device__ __forceinline__ uint32_t lds32(uint32_t a) { uint32_t v; asm volatile("ld.shared.u32 %0, [%1];" : "=r"(v) : "r"(a) : "memory"); return v; }
__device__ __forceinline__ void sts32(uint32_t a, uint32_t v) { asm volatile("st.shared.u32 [%0], %1;" :: "r"(a), "r"(v) : "memory"); }
__device__ __forceinline__ bool elect_one() {
    uint32_t p; asm volatile("{\n.reg .pred q;\nelect.sync _|q, 0xffffffff;\nselp.u32 %0, 1, 0, q;\n}" : "=r"(p)); return p;
}
__device__ __forceinline__ void pause(uint32_t cycles) {
    uint32_t t0, t; asm volatile("mov.u32 %0, %%clock;" : "=r"(t0));
    do { __nanosleep(64); asm volatile("mov.u32 %0, %%clock;" : "=r"(t)); } while (t - t0 < cycles);
}
__device__ __forceinline__ void cluster_arrive() { asm volatile("barrier.cluster.arrive.relaxed.aligned;" ::: "memory"); }
__device__ __forceinline__ void cluster_wait() { asm volatile("barrier.cluster.wait.aligned;" ::: "memory"); }

__device__ __forceinline__ void wgmma_n128_z(float (&d)[64], uint64_t da, uint64_t db) {
    asm volatile("{\n.reg .pred p;\nsetp.ne.b32 p, 0, 0;\n"
        "wgmma.mma_async.sync.aligned.m64n128k16.f32.bf16.bf16 {"
        "%0, %1, %2, %3, %4, %5, %6, %7, %8, %9, %10, %11, %12, %13, %14, %15, "
        "%16, %17, %18, %19, %20, %21, %22, %23, %24, %25, %26, %27, %28, %29, %30, %31, "
        "%32, %33, %34, %35, %36, %37, %38, %39, %40, %41, %42, %43, %44, %45, %46, %47, "
        "%48, %49, %50, %51, %52, %53, %54, %55, %56, %57, %58, %59, %60, %61, %62, %63"
        "}, %64, %65, p, 1, 1, 0, 1;\n}\n"
        : "=f"(d[0]), "=f"(d[1]), "=f"(d[2]), "=f"(d[3]), "=f"(d[4]), "=f"(d[5]), "=f"(d[6]), "=f"(d[7]),
          "=f"(d[8]), "=f"(d[9]), "=f"(d[10]), "=f"(d[11]), "=f"(d[12]), "=f"(d[13]), "=f"(d[14]), "=f"(d[15]),
          "=f"(d[16]), "=f"(d[17]), "=f"(d[18]), "=f"(d[19]), "=f"(d[20]), "=f"(d[21]), "=f"(d[22]), "=f"(d[23]),
          "=f"(d[24]), "=f"(d[25]), "=f"(d[26]), "=f"(d[27]), "=f"(d[28]), "=f"(d[29]), "=f"(d[30]), "=f"(d[31]),
          "=f"(d[32]), "=f"(d[33]), "=f"(d[34]), "=f"(d[35]), "=f"(d[36]), "=f"(d[37]), "=f"(d[38]), "=f"(d[39]),
          "=f"(d[40]), "=f"(d[41]), "=f"(d[42]), "=f"(d[43]), "=f"(d[44]), "=f"(d[45]), "=f"(d[46]), "=f"(d[47]),
          "=f"(d[48]), "=f"(d[49]), "=f"(d[50]), "=f"(d[51]), "=f"(d[52]), "=f"(d[53]), "=f"(d[54]), "=f"(d[55]),
          "=f"(d[56]), "=f"(d[57]), "=f"(d[58]), "=f"(d[59]), "=f"(d[60]), "=f"(d[61]), "=f"(d[62]), "=f"(d[63])
        : "l"(da), "l"(db));
}
__device__ __forceinline__ void wgmma_n128(float (&d)[64], uint64_t da, uint64_t db) {
    asm volatile("{\n.reg .pred p;\nsetp.eq.b32 p, 0, 0;\n"
        "wgmma.mma_async.sync.aligned.m64n128k16.f32.bf16.bf16 {"
        "%0, %1, %2, %3, %4, %5, %6, %7, %8, %9, %10, %11, %12, %13, %14, %15, "
        "%16, %17, %18, %19, %20, %21, %22, %23, %24, %25, %26, %27, %28, %29, %30, %31, "
        "%32, %33, %34, %35, %36, %37, %38, %39, %40, %41, %42, %43, %44, %45, %46, %47, "
        "%48, %49, %50, %51, %52, %53, %54, %55, %56, %57, %58, %59, %60, %61, %62, %63"
        "}, %64, %65, p, 1, 1, 0, 1;\n}\n"
        : "+f"(d[0]), "+f"(d[1]), "+f"(d[2]), "+f"(d[3]), "+f"(d[4]), "+f"(d[5]), "+f"(d[6]), "+f"(d[7]),
          "+f"(d[8]), "+f"(d[9]), "+f"(d[10]), "+f"(d[11]), "+f"(d[12]), "+f"(d[13]), "+f"(d[14]), "+f"(d[15]),
          "+f"(d[16]), "+f"(d[17]), "+f"(d[18]), "+f"(d[19]), "+f"(d[20]), "+f"(d[21]), "+f"(d[22]), "+f"(d[23]),
          "+f"(d[24]), "+f"(d[25]), "+f"(d[26]), "+f"(d[27]), "+f"(d[28]), "+f"(d[29]), "+f"(d[30]), "+f"(d[31]),
          "+f"(d[32]), "+f"(d[33]), "+f"(d[34]), "+f"(d[35]), "+f"(d[36]), "+f"(d[37]), "+f"(d[38]), "+f"(d[39]),
          "+f"(d[40]), "+f"(d[41]), "+f"(d[42]), "+f"(d[43]), "+f"(d[44]), "+f"(d[45]), "+f"(d[46]), "+f"(d[47]),
          "+f"(d[48]), "+f"(d[49]), "+f"(d[50]), "+f"(d[51]), "+f"(d[52]), "+f"(d[53]), "+f"(d[54]), "+f"(d[55]),
          "+f"(d[56]), "+f"(d[57]), "+f"(d[58]), "+f"(d[59]), "+f"(d[60]), "+f"(d[61]), "+f"(d[62]), "+f"(d[63])
        : "l"(da), "l"(db));
}
__device__ __forceinline__ void wgmma_n176_z(float (&d)[88], uint64_t da, uint64_t db) {
    asm volatile("{\n.reg .pred p;\nsetp.ne.b32 p, 0, 0;\n"
        "wgmma.mma_async.sync.aligned.m64n176k16.f32.bf16.bf16 {"
        "%0, %1, %2, %3, %4, %5, %6, %7, %8, %9, %10, %11, %12, %13, %14, %15, "
        "%16, %17, %18, %19, %20, %21, %22, %23, %24, %25, %26, %27, %28, %29, %30, %31, "
        "%32, %33, %34, %35, %36, %37, %38, %39, %40, %41, %42, %43, %44, %45, %46, %47, "
        "%48, %49, %50, %51, %52, %53, %54, %55, %56, %57, %58, %59, %60, %61, %62, %63, "
        "%64, %65, %66, %67, %68, %69, %70, %71, %72, %73, %74, %75, %76, %77, %78, %79, "
        "%80, %81, %82, %83, %84, %85, %86, %87"
        "}, %88, %89, p, 1, 1, 0, 1;\n}\n"
        : "=f"(d[0]), "=f"(d[1]), "=f"(d[2]), "=f"(d[3]), "=f"(d[4]), "=f"(d[5]), "=f"(d[6]), "=f"(d[7]),
          "=f"(d[8]), "=f"(d[9]), "=f"(d[10]), "=f"(d[11]), "=f"(d[12]), "=f"(d[13]), "=f"(d[14]), "=f"(d[15]),
          "=f"(d[16]), "=f"(d[17]), "=f"(d[18]), "=f"(d[19]), "=f"(d[20]), "=f"(d[21]), "=f"(d[22]), "=f"(d[23]),
          "=f"(d[24]), "=f"(d[25]), "=f"(d[26]), "=f"(d[27]), "=f"(d[28]), "=f"(d[29]), "=f"(d[30]), "=f"(d[31]),
          "=f"(d[32]), "=f"(d[33]), "=f"(d[34]), "=f"(d[35]), "=f"(d[36]), "=f"(d[37]), "=f"(d[38]), "=f"(d[39]),
          "=f"(d[40]), "=f"(d[41]), "=f"(d[42]), "=f"(d[43]), "=f"(d[44]), "=f"(d[45]), "=f"(d[46]), "=f"(d[47]),
          "=f"(d[48]), "=f"(d[49]), "=f"(d[50]), "=f"(d[51]), "=f"(d[52]), "=f"(d[53]), "=f"(d[54]), "=f"(d[55]),
          "=f"(d[56]), "=f"(d[57]), "=f"(d[58]), "=f"(d[59]), "=f"(d[60]), "=f"(d[61]), "=f"(d[62]), "=f"(d[63]),
          "=f"(d[64]), "=f"(d[65]), "=f"(d[66]), "=f"(d[67]), "=f"(d[68]), "=f"(d[69]), "=f"(d[70]), "=f"(d[71]),
          "=f"(d[72]), "=f"(d[73]), "=f"(d[74]), "=f"(d[75]), "=f"(d[76]), "=f"(d[77]), "=f"(d[78]), "=f"(d[79]),
          "=f"(d[80]), "=f"(d[81]), "=f"(d[82]), "=f"(d[83]), "=f"(d[84]), "=f"(d[85]), "=f"(d[86]), "=f"(d[87])
        : "l"(da), "l"(db));
}
__device__ __forceinline__ void wgmma_n176(float (&d)[88], uint64_t da, uint64_t db) {
    asm volatile("{\n.reg .pred p;\nsetp.eq.b32 p, 0, 0;\n"
        "wgmma.mma_async.sync.aligned.m64n176k16.f32.bf16.bf16 {"
        "%0, %1, %2, %3, %4, %5, %6, %7, %8, %9, %10, %11, %12, %13, %14, %15, "
        "%16, %17, %18, %19, %20, %21, %22, %23, %24, %25, %26, %27, %28, %29, %30, %31, "
        "%32, %33, %34, %35, %36, %37, %38, %39, %40, %41, %42, %43, %44, %45, %46, %47, "
        "%48, %49, %50, %51, %52, %53, %54, %55, %56, %57, %58, %59, %60, %61, %62, %63, "
        "%64, %65, %66, %67, %68, %69, %70, %71, %72, %73, %74, %75, %76, %77, %78, %79, "
        "%80, %81, %82, %83, %84, %85, %86, %87"
        "}, %88, %89, p, 1, 1, 0, 1;\n}\n"
        : "+f"(d[0]), "+f"(d[1]), "+f"(d[2]), "+f"(d[3]), "+f"(d[4]), "+f"(d[5]), "+f"(d[6]), "+f"(d[7]),
          "+f"(d[8]), "+f"(d[9]), "+f"(d[10]), "+f"(d[11]), "+f"(d[12]), "+f"(d[13]), "+f"(d[14]), "+f"(d[15]),
          "+f"(d[16]), "+f"(d[17]), "+f"(d[18]), "+f"(d[19]), "+f"(d[20]), "+f"(d[21]), "+f"(d[22]), "+f"(d[23]),
          "+f"(d[24]), "+f"(d[25]), "+f"(d[26]), "+f"(d[27]), "+f"(d[28]), "+f"(d[29]), "+f"(d[30]), "+f"(d[31]),
          "+f"(d[32]), "+f"(d[33]), "+f"(d[34]), "+f"(d[35]), "+f"(d[36]), "+f"(d[37]), "+f"(d[38]), "+f"(d[39]),
          "+f"(d[40]), "+f"(d[41]), "+f"(d[42]), "+f"(d[43]), "+f"(d[44]), "+f"(d[45]), "+f"(d[46]), "+f"(d[47]),
          "+f"(d[48]), "+f"(d[49]), "+f"(d[50]), "+f"(d[51]), "+f"(d[52]), "+f"(d[53]), "+f"(d[54]), "+f"(d[55]),
          "+f"(d[56]), "+f"(d[57]), "+f"(d[58]), "+f"(d[59]), "+f"(d[60]), "+f"(d[61]), "+f"(d[62]), "+f"(d[63]),
          "+f"(d[64]), "+f"(d[65]), "+f"(d[66]), "+f"(d[67]), "+f"(d[68]), "+f"(d[69]), "+f"(d[70]), "+f"(d[71]),
          "+f"(d[72]), "+f"(d[73]), "+f"(d[74]), "+f"(d[75]), "+f"(d[76]), "+f"(d[77]), "+f"(d[78]), "+f"(d[79]),
          "+f"(d[80]), "+f"(d[81]), "+f"(d[82]), "+f"(d[83]), "+f"(d[84]), "+f"(d[85]), "+f"(d[86]), "+f"(d[87])
        : "l"(da), "l"(db));
}
__device__ __forceinline__ void wgmma_n256_z(float (&d)[128], uint64_t da, uint64_t db) {
    asm volatile("{\n.reg .pred p;\nsetp.ne.b32 p, 0, 0;\n"
        "wgmma.mma_async.sync.aligned.m64n256k16.f32.bf16.bf16 {"
        "%0, %1, %2, %3, %4, %5, %6, %7, %8, %9, %10, %11, %12, %13, %14, %15, "
        "%16, %17, %18, %19, %20, %21, %22, %23, %24, %25, %26, %27, %28, %29, %30, %31, "
        "%32, %33, %34, %35, %36, %37, %38, %39, %40, %41, %42, %43, %44, %45, %46, %47, "
        "%48, %49, %50, %51, %52, %53, %54, %55, %56, %57, %58, %59, %60, %61, %62, %63, "
        "%64, %65, %66, %67, %68, %69, %70, %71, %72, %73, %74, %75, %76, %77, %78, %79, "
        "%80, %81, %82, %83, %84, %85, %86, %87, %88, %89, %90, %91, %92, %93, %94, %95, "
        "%96, %97, %98, %99, %100, %101, %102, %103, %104, %105, %106, %107, %108, %109, %110, %111, "
        "%112, %113, %114, %115, %116, %117, %118, %119, %120, %121, %122, %123, %124, %125, %126, %127"
        "}, %128, %129, p, 1, 1, 0, 1;\n}\n"
        : "=f"(d[0]), "=f"(d[1]), "=f"(d[2]), "=f"(d[3]), "=f"(d[4]), "=f"(d[5]), "=f"(d[6]), "=f"(d[7]),
          "=f"(d[8]), "=f"(d[9]), "=f"(d[10]), "=f"(d[11]), "=f"(d[12]), "=f"(d[13]), "=f"(d[14]), "=f"(d[15]),
          "=f"(d[16]), "=f"(d[17]), "=f"(d[18]), "=f"(d[19]), "=f"(d[20]), "=f"(d[21]), "=f"(d[22]), "=f"(d[23]),
          "=f"(d[24]), "=f"(d[25]), "=f"(d[26]), "=f"(d[27]), "=f"(d[28]), "=f"(d[29]), "=f"(d[30]), "=f"(d[31]),
          "=f"(d[32]), "=f"(d[33]), "=f"(d[34]), "=f"(d[35]), "=f"(d[36]), "=f"(d[37]), "=f"(d[38]), "=f"(d[39]),
          "=f"(d[40]), "=f"(d[41]), "=f"(d[42]), "=f"(d[43]), "=f"(d[44]), "=f"(d[45]), "=f"(d[46]), "=f"(d[47]),
          "=f"(d[48]), "=f"(d[49]), "=f"(d[50]), "=f"(d[51]), "=f"(d[52]), "=f"(d[53]), "=f"(d[54]), "=f"(d[55]),
          "=f"(d[56]), "=f"(d[57]), "=f"(d[58]), "=f"(d[59]), "=f"(d[60]), "=f"(d[61]), "=f"(d[62]), "=f"(d[63]),
          "=f"(d[64]), "=f"(d[65]), "=f"(d[66]), "=f"(d[67]), "=f"(d[68]), "=f"(d[69]), "=f"(d[70]), "=f"(d[71]),
          "=f"(d[72]), "=f"(d[73]), "=f"(d[74]), "=f"(d[75]), "=f"(d[76]), "=f"(d[77]), "=f"(d[78]), "=f"(d[79]),
          "=f"(d[80]), "=f"(d[81]), "=f"(d[82]), "=f"(d[83]), "=f"(d[84]), "=f"(d[85]), "=f"(d[86]), "=f"(d[87]),
          "=f"(d[88]), "=f"(d[89]), "=f"(d[90]), "=f"(d[91]), "=f"(d[92]), "=f"(d[93]), "=f"(d[94]), "=f"(d[95]),
          "=f"(d[96]), "=f"(d[97]), "=f"(d[98]), "=f"(d[99]), "=f"(d[100]), "=f"(d[101]), "=f"(d[102]), "=f"(d[103]),
          "=f"(d[104]), "=f"(d[105]), "=f"(d[106]), "=f"(d[107]), "=f"(d[108]), "=f"(d[109]), "=f"(d[110]), "=f"(d[111]),
          "=f"(d[112]), "=f"(d[113]), "=f"(d[114]), "=f"(d[115]), "=f"(d[116]), "=f"(d[117]), "=f"(d[118]), "=f"(d[119]),
          "=f"(d[120]), "=f"(d[121]), "=f"(d[122]), "=f"(d[123]), "=f"(d[124]), "=f"(d[125]), "=f"(d[126]), "=f"(d[127])
        : "l"(da), "l"(db));
}
__device__ __forceinline__ void wgmma_n256(float (&d)[128], uint64_t da, uint64_t db) {
    asm volatile("{\n.reg .pred p;\nsetp.eq.b32 p, 0, 0;\n"
        "wgmma.mma_async.sync.aligned.m64n256k16.f32.bf16.bf16 {"
        "%0, %1, %2, %3, %4, %5, %6, %7, %8, %9, %10, %11, %12, %13, %14, %15, "
        "%16, %17, %18, %19, %20, %21, %22, %23, %24, %25, %26, %27, %28, %29, %30, %31, "
        "%32, %33, %34, %35, %36, %37, %38, %39, %40, %41, %42, %43, %44, %45, %46, %47, "
        "%48, %49, %50, %51, %52, %53, %54, %55, %56, %57, %58, %59, %60, %61, %62, %63, "
        "%64, %65, %66, %67, %68, %69, %70, %71, %72, %73, %74, %75, %76, %77, %78, %79, "
        "%80, %81, %82, %83, %84, %85, %86, %87, %88, %89, %90, %91, %92, %93, %94, %95, "
        "%96, %97, %98, %99, %100, %101, %102, %103, %104, %105, %106, %107, %108, %109, %110, %111, "
        "%112, %113, %114, %115, %116, %117, %118, %119, %120, %121, %122, %123, %124, %125, %126, %127"
        "}, %128, %129, p, 1, 1, 0, 1;\n}\n"
        : "+f"(d[0]), "+f"(d[1]), "+f"(d[2]), "+f"(d[3]), "+f"(d[4]), "+f"(d[5]), "+f"(d[6]), "+f"(d[7]),
          "+f"(d[8]), "+f"(d[9]), "+f"(d[10]), "+f"(d[11]), "+f"(d[12]), "+f"(d[13]), "+f"(d[14]), "+f"(d[15]),
          "+f"(d[16]), "+f"(d[17]), "+f"(d[18]), "+f"(d[19]), "+f"(d[20]), "+f"(d[21]), "+f"(d[22]), "+f"(d[23]),
          "+f"(d[24]), "+f"(d[25]), "+f"(d[26]), "+f"(d[27]), "+f"(d[28]), "+f"(d[29]), "+f"(d[30]), "+f"(d[31]),
          "+f"(d[32]), "+f"(d[33]), "+f"(d[34]), "+f"(d[35]), "+f"(d[36]), "+f"(d[37]), "+f"(d[38]), "+f"(d[39]),
          "+f"(d[40]), "+f"(d[41]), "+f"(d[42]), "+f"(d[43]), "+f"(d[44]), "+f"(d[45]), "+f"(d[46]), "+f"(d[47]),
          "+f"(d[48]), "+f"(d[49]), "+f"(d[50]), "+f"(d[51]), "+f"(d[52]), "+f"(d[53]), "+f"(d[54]), "+f"(d[55]),
          "+f"(d[56]), "+f"(d[57]), "+f"(d[58]), "+f"(d[59]), "+f"(d[60]), "+f"(d[61]), "+f"(d[62]), "+f"(d[63]),
          "+f"(d[64]), "+f"(d[65]), "+f"(d[66]), "+f"(d[67]), "+f"(d[68]), "+f"(d[69]), "+f"(d[70]), "+f"(d[71]),
          "+f"(d[72]), "+f"(d[73]), "+f"(d[74]), "+f"(d[75]), "+f"(d[76]), "+f"(d[77]), "+f"(d[78]), "+f"(d[79]),
          "+f"(d[80]), "+f"(d[81]), "+f"(d[82]), "+f"(d[83]), "+f"(d[84]), "+f"(d[85]), "+f"(d[86]), "+f"(d[87]),
          "+f"(d[88]), "+f"(d[89]), "+f"(d[90]), "+f"(d[91]), "+f"(d[92]), "+f"(d[93]), "+f"(d[94]), "+f"(d[95]),
          "+f"(d[96]), "+f"(d[97]), "+f"(d[98]), "+f"(d[99]), "+f"(d[100]), "+f"(d[101]), "+f"(d[102]), "+f"(d[103]),
          "+f"(d[104]), "+f"(d[105]), "+f"(d[106]), "+f"(d[107]), "+f"(d[108]), "+f"(d[109]), "+f"(d[110]), "+f"(d[111]),
          "+f"(d[112]), "+f"(d[113]), "+f"(d[114]), "+f"(d[115]), "+f"(d[116]), "+f"(d[117]), "+f"(d[118]), "+f"(d[119]),
          "+f"(d[120]), "+f"(d[121]), "+f"(d[122]), "+f"(d[123]), "+f"(d[124]), "+f"(d[125]), "+f"(d[126]), "+f"(d[127])
        : "l"(da), "l"(db));
}

__device__ __forceinline__ void wgmma_n8_ta(float (&d)[4], uint64_t da, uint64_t db) {
    asm volatile("{\n.reg .pred p;\nsetp.eq.b32 p, 0, 0;\nwgmma.mma_async.sync.aligned.m64n8k16.f32.bf16.bf16 {%0, %1, %2, %3}, %4, %5, p, 1, 1, 1, 0;\n}"
        : "+f"(d[0]), "+f"(d[1]), "+f"(d[2]), "+f"(d[3]) : "l"(da), "l"(db));
}

struct Idx {
    uint32_t lane, warp, w4, q4, g8, prow, pan;
    __device__ __forceinline__ Idx() {
        uint32_t t; asm volatile("mov.u32 %0, %%tid.x;" : "=r"(t));
        lane = t & 31; warp = t >> 5; w4 = warp & 3; q4 = lane & 3; g8 = lane >> 2;
        prow = w4 * 16 + ((lane >> 3) & 1) * 8 + (lane & 7);
        pan = prow * 128 + (((lane >> 4) ^ (lane & 7)) << 4);
    }
};
#define IDX() const Idx ix; const uint32_t lane = ix.lane, warp = ix.warp, w4 = ix.w4, q4 = ix.q4, g8 = ix.g8, prow = ix.prow, pan_addr = ix.pan; \
    (void)lane; (void)warp; (void)w4; (void)q4; (void)g8; (void)prow; (void)pan_addr;

__device__ __forceinline__ int kof(int t, int sh, int j) {
    const int p = t >> (sh - 1), pn = p < 2 ? p : p >= 9, q = p - 2 - 7 * pn;
    return ((p < 2 ? j : q + (q >= j)) << 7) + (pn << 6) + ((t & (sh - 1)) << 5);
}
__device__ __forceinline__ uint32_t fidx(uint32_t m, uint32_t w, uint32_t pn) {
    return m * 32 + w * 16 + pn;
}
constexpr int HC0 = 8 * 48, HC3 = HC0 + 3072;
__device__ __forceinline__ int hcol(int p, int j) { return HC0 + p * 1024 + j * 128; }
struct Ring {
    uint32_t slot, par;
    __device__ __forceinline__ void next() { if (++slot == NSLOT) { slot = 0; par ^= 1; } }
    __device__ __forceinline__ void skip(uint32_t n) { slot += n; if (slot >= NSLOT) { slot -= NSLOT; par ^= 1; } }
};
__device__ __forceinline__ uint32_t BAR_FULL(uint32_t sb, uint32_t s) { return sb + OFF_BAR + 8 * s; }
constexpr uint32_t AF_REL = 48;
__device__ __forceinline__ uint32_t BAR_EMPTY(uint32_t sb, uint32_t s) { return sb + OFF_BAR + 96 + 8 * s; }
__device__ __forceinline__ uint32_t BAR_SFULL(uint32_t sb, uint32_t i) { return sb + OFF_BAR + 152 + 8 * i; }
__device__ __forceinline__ uint32_t BAR_SREADY(uint32_t sb, uint32_t i) { return sb + OFF_BAR + 184 + 8 * i; }
__device__ __forceinline__ uint32_t BAR_ONE(uint32_t sb, uint32_t i) { return sb + OFF_BAR + 216 + 8 * i; }
enum { EV_WIN, EV_WIN1, EV_WIN2, EV_WIN3, EV_P0, EV_GA, EV_GB, EV_LN2, EV_LAG1, EV_LAG2, EV_LAG3, EV_LAG4, EV_LAG5, EV_KV, EV_PAR, EV_AGO, EV_AGO1, EV_AGO2, EV_FGO, EV_FGO1, EV_FGO2, EV_H0, EV_H1, EV_H2, EV_H3, EV_TAIL, EV_COUNT = EV_TAIL + 8 };
constexpr int NB_TAIL = 4;

struct Rel {
    uint32_t base; bool sig;
    __device__ __forceinline__ Rel(uint32_t sb, uint32_t tw) {
        uint32_t a; asm("mapa.shared::cluster.u32 %0, %1, %2;" : "=r"(a) : "r"(BAR_EMPTY(sb, 0)), "r"((tw >> 5) & 1));
        base = __shfl_sync(0xffffffffu, a, 0); sig = (tw & ~32u) == 0;
    }
    __device__ __forceinline__ void operator()(uint32_t slot) const {
        if (sig) asm volatile("mbarrier.arrive.shared::cluster.b64 _, [%0];" :: "r"(base + 8 * slot) : "memory");
    }
};
struct LnRow { float rs0, nm0, rs1, nm1; };
struct Pipe {
    Rel rel; uint32_t p1, p2;
    __device__ __forceinline__ Pipe(uint32_t sb, uint32_t tw, uint32_t first) : rel(sb, tw), p1(first), p2(NSLOT) {}
    template <bool TWO> __device__ __forceinline__ void acquire(uint32_t sb, uint32_t af, const Ring& r) {
        const uint32_t b0 = BAR_FULL(sb, r.slot), b1 = b0 + af;
        const bool ready = TWO ? mbar_test2(b0, b1, r.par) : mbar_test(b0, r.par);
        wg_wait<1>();
        rel(p2);
        if (!ready) { if (TWO) mbar_wait2(b0, b1, r.par); else mbar_wait(b0, r.par); }
    }
    __device__ __forceinline__ void issued(uint32_t slot) { p2 = p1; p1 = slot; }
    __device__ __forceinline__ void drain1() { wg_wait<1>(); rel(p2); p2 = NSLOT; }
    __device__ __forceinline__ void drain0() { wg_wait<0>(); rel(p1); p1 = NSLOT; }
    template <bool TWO, class Step> __device__ __forceinline__ void hold(int LG, uint32_t sb, uint32_t af, Ring& r, uint32_t lag_bar, Step step) {
        Ring q = r;
#pragma unroll 1
        for (int i = 0; i < LG; ++i) { if (TWO) mbar_wait2(BAR_FULL(sb, q.slot), BAR_FULL(sb, q.slot) + af, q.par); else mbar_wait(BAR_FULL(sb, q.slot), q.par); q.next(); }
        mbar_wait(lag_bar, 0);
#pragma unroll 1
        do {
            step(r.slot);
            wg_wait<2>(); rel(p2); p2 = p1; p1 = r.slot;
            if (++r.slot == NSLOT) r.slot = 0;
        } while (r.slot != q.slot);
        r.par = q.par;
    }
};
template <bool TWO, bool FIRST, int NA, int NB>
__device__ __forceinline__ void step32(float (&aa)[NA], float (&ab)[NB], uint32_t sb, uint32_t wg, uint32_t slot, int own) {
    const uint32_t st = d16(sb) + slot * (SLOT >> 4);
    const uint32_t alo = own >= 0 ? d16(sb) + OFF_STG / 16 + wg * 1024 + (own >> 1) * 512 + (own & 1) * 4 : st + wg * 256;
    const uint32_t ahi = own >= 0 ? (1024 >> 4) | (1u << 30) : (512 >> 4) | (2u << 30);
    wg_fence();
#pragma unroll
    for (int k = 0; k < 2; ++k) {
        const uint64_t da = ((uint64_t)ahi << 32) | (alo + k * 2 + 0x10000);
        if constexpr (NA == 88) {
            const uint64_t d0 = mk_desc(st, 8192 + k * 2048, 8192, 1024, 1), d1 = mk_desc(st, 12288 + k * 2048, 8192, 1024, 1);
            if (FIRST && k == 0) { wgmma_n176_z(aa, da, d0); wgmma_n176_z(ab, da, d1); }
            else { wgmma_n176(aa, da, d0); wgmma_n176(ab, da, d1); }
        } else {
            const uint64_t d0 = mk_desc(st, 8192 + k * 2048, 4096, 1024, 1), d1 = mk_desc(st, 24576 + k * 2048, 4096, 1024, 1);
            if (FIRST && k == 0) { wgmma_n256_z(aa, da, d0); if constexpr (TWO) wgmma_n128_z(ab, da, d1); }
            else { wgmma_n256(aa, da, d0); if constexpr (TWO) wgmma_n128(ab, da, d1); }
        }
    }
    wg_commit();
}
template <bool TWO, int LG, int NA, int NB, class Mid, class Tail>
__device__ __forceinline__ void mainloop32(float (&aa)[NA], float (&ab)[NB], uint32_t sb, uint32_t wg, uint32_t tw, Ring& r, uint32_t lag_ev, int g0, Mid mid, Tail tail) {
    step32<TWO, true>(aa, ab, sb, wg, r.slot, TWO ? 0 : -1);
    TS(g0, 0);
    Pipe pp(sb, tw, r.slot);
    r.next();
    const int end = wg ? 32 : 32 - LG;
#pragma unroll 1
    for (int it = 1; it < end; ++it) {
        pp.acquire<TWO>(sb, wg ? 0 : AF_REL, r);
        step32<TWO, false>(aa, ab, sb, wg, r.slot, TWO && it < 4 ? it : -1);
        pp.issued(r.slot);
        TS(g0 + it, 0);
        r.next();
        mid(it);
    }
    if (wg == 0) { pp.drain1(); pp.drain0(); pp.hold<TWO>(LG, sb, AF_REL, r, BAR_ONE(sb, lag_ev), [&](uint32_t slot) { step32<TWO, false>(aa, ab, sb, 0, slot, -1); }); }
    if (wg == 1 && tw == 0) mbar_arrive(BAR_ONE(sb, lag_ev));
    pp.drain1();
    tail();
    pp.drain0();
    TS(g0 + 31, 1);
}
template <bool FIRST>
__device__ __forceinline__ void step64(float (&acc)[64], uint32_t sb, uint32_t wg, uint32_t slot, int own) {
    const uint32_t sbb = d16(sb) + slot * (SLOT >> 4), sa = own >= 0 ? d16(sb) + OFF_STG / 16 + wg * 1024 + own * 512 : sbb + wg * 512;
    wg_fence();
#pragma unroll
    for (int k = 0; k < 4; ++k) {
        const uint64_t da = mk_desc(sa, k * 32, 16, 1024, 1), db = mk_desc(sbb, 16384 + k * 2048, 8192, 1024, 1);
        if (FIRST && k == 0) wgmma_n128_z(acc, da, db); else wgmma_n128(acc, da, db);
    }
    wg_commit();
}
template <class Put, class Mid, class Tail>
__device__ __forceinline__ void mainloop64(float (&acc)[64], bool wo, uint32_t sb, uint32_t wg, uint32_t tw, Ring& r, Put put, Mid mid, Tail tail) {
    const int g0 = wo ? 32 : 144, nst = wo ? 16 : 56, lg = wo ? LAGW : LAGD; (void)g0;
    const uint32_t lag_bar = BAR_ONE(sb, wo ? EV_LAG4 : EV_LAG5), af = wo && !wg ? AF_REL : 0;
    if (!wo) CS(28);
    step64<true>(acc, sb, wg, r.slot, wo ? 0 : -1);
    if (!wo) CS(29);
    TS(g0, 0);
    Pipe pp(sb, tw, r.slot);
    r.next();
    int it = 1;
    auto run = [&](int end, int own, bool with_put) {
#pragma unroll 1
        do {
            pp.acquire<true>(sb, af, r);
            step64<false>(acc, sb, wg, r.slot, own);
            pp.issued(r.slot);
            TS(g0 + it, 0);
            if (wo && it == 2) CS(9);
            r.next();
            if (with_put && it == (wg ? PUTD1 : PUTD0)) put();
        } while (++it < end);
    };
    const int end = wg ? nst : nst - lg;
    run(wo ? 2 : wg ? MIDD : end, wo ? 1 : -1, true);
    mid();
    if (wo) { pp.drain1(); pp.drain0(); TS(g0 + 1, 1); }
    if (it < end) run(end, -1, false);
    if (wg == 0 && lg) { pp.drain1(); pp.drain0(); pp.hold<true>(lg, sb, af, r, lag_bar, [&](uint32_t slot) { step64<false>(acc, sb, 0, slot, -1); }); }
    if (wg == 1 && tw == 0) mbar_arrive(lag_bar);
    pp.drain1();
    tail();
    pp.drain0();
    TS(g0 + nst - 1, 1);
}

struct RowAcc {
    float sm[4] = {0.f, 0.f, 0.f, 0.f}, sq[4] = {0.f, 0.f, 0.f, 0.f};
    __device__ __forceinline__ void add(int e, float x) { sm[e & 3] += x; sq[e & 3] = fmaf(x, x, sq[e & 3]); }
    __device__ __forceinline__ void publish(uint4* dst, uint32_t q4, uint32_t ep, bool acc) const {
        const float s0 = sm[0] + sm[1], s1 = sm[2] + sm[3], q0 = sq[0] + sq[1], q1 = sq[2] + sq[3];
        const bool od = q4 & 1;
        float sv = (od ? s1 : s0) + __shfl_xor_sync(0xffffffffu, od ? s0 : s1, 1), qv = (od ? q1 : q0) + __shfl_xor_sync(0xffffffffu, od ? q0 : q1, 1);
        sv += __shfl_xor_sync(0xffffffffu, sv, 2); qv += __shfl_xor_sync(0xffffffffu, qv, 2);
        if (acc) { if (q4 < 2) asm volatile("red.relaxed.gpu.global.add.v4.f32 [%0], {%1, %2, %3, %4};" :: "l"(dst + q4 * 8), "f"(0.f), "f"(sv), "f"(qv), "f"(1.f) : "memory"); }
        else st_pkt16(dst + (q4 & 1) * 8, 0, __float_as_uint(sv), __float_as_uint(qv), ep);
    }
};
__device__ __forceinline__ LnRow merge_stats(const uint4* src, uint32_t q4, uint32_t ep, uint32_t sb, bool acc) {
    float v[4];
    uint32_t n = 0;
    if (acc) {
        uint4 a, b;
        while (true) {
            a = ld_pkt16(src); b = ld_pkt16(src + 8);
            const bool ok = __all_sync(0xffffffffu, a.w == __float_as_uint(8.f) && b.w == __float_as_uint(8.f));
            if (n < 4) CS(14 + n);
            if (ok) break;
            SPIN_GUARD(n);
        }
        v[0] = __uint_as_float(a.y); v[1] = __uint_as_float(b.y); v[2] = __uint_as_float(a.z); v[3] = __uint_as_float(b.z);
    } else {
        uint4 t[4];
        while (true) {
#pragma unroll
            for (int i = 0; i < 4; ++i) t[i] = ld_pkt16(src + (q4 * 2 + (i >> 1)) * 512 + (i & 1) * 8);
            if (__all_sync(0xffffffffu, t[0].w == ep && t[1].w == ep && t[2].w == ep && t[3].w == ep)) break;
            SPIN_GUARD(n);
        }
#pragma unroll
        for (int h = 0; h < 2; ++h) { v[h] = __uint_as_float(t[h].y) + __uint_as_float(t[2 + h].y); v[2 + h] = __uint_as_float(t[h].z) + __uint_as_float(t[2 + h].z); }
#pragma unroll
        for (int o = 1; o < 4; o <<= 1)
#pragma unroll
            for (int i = 0; i < 4; ++i) v[i] += __shfl_xor_sync(0xffffffffu, v[i], o);
    }
    const float m0 = v[0] * (1.f / D_), m1 = v[1] * (1.f / D_);
    const float r0 = rsq(fmaxf(fmaf(-m0, m0, v[2] * (1.f / D_)), 0.f) + 1e-5f), r1 = rsq(fmaxf(fmaf(-m1, m1, v[3] * (1.f / D_)), 0.f) + 1e-5f);
    return LnRow{r0, -m0 * r0, r1, -m1 * r1};
}
struct Stg {
    uint32_t b, par;
    __device__ __forceinline__ uint32_t acquire2(uint32_t sb, uint32_t wg) {
        mbar_wait2(BAR_SREADY(sb, wg * 2), BAR_SREADY(sb, wg * 2 + 1), par);
        par ^= 1;
        return sb + OFF_STG + wg * 16384;
    }
    __device__ __forceinline__ void publish(uint32_t sb, uint32_t wg, uint32_t lane) {
        fence_async_smem();
        __syncwarp();
        if (lane == 0) mbar_arrive(BAR_SFULL(sb, wg * 2 + b));
        b ^= 1;
    }
};

struct LnPar {
    uint4 p[8];
    __device__ __forceinline__ void load(uint32_t sb, uint32_t q4) {
#pragma unroll
        for (int i = 0; i < 8; ++i) p[i] = lds128(sb + OFF_PAR + i * 64 + q4 * 16);
    }
};
__device__ __forceinline__ void ln_norm(uint32_t (&xn)[32], const float (&x)[64], const LnRow& n) {
#pragma unroll
    for (int e = 0; e < 32; ++e) {
        const float rs = (e & 1) ? n.rs1 : n.rs0, nm = (e & 1) ? n.nm1 : n.nm0;
        xn[e] = pack2(fmaf(x[2 * e], rs, nm), fmaf(x[2 * e + 1], rs, nm));
    }
}
__device__ __forceinline__ void ln_emit(const uint32_t (&xr)[32], const LnPar& lp, uint32_t sb, uint32_t wg, const Idx& ix) {
#pragma unroll
    for (int i = 0; i < 8; ++i)
        stsm4(sb + OFF_STG + wg * 16384 + (i >> 2) * 8192 + (ix.pan ^ ((i & 3) << 5)), hfma2_bf16(xr[4 * i], lp.p[i].z, lp.p[i].x), hfma2_bf16(xr[4 * i + 1], lp.p[i].z, lp.p[i].x),
              hfma2_bf16(xr[4 * i + 2], lp.p[i].w, lp.p[i].y), hfma2_bf16(xr[4 * i + 3], lp.p[i].w, lp.p[i].y));
    fence_async_smem();
    __syncwarp();
    if (ix.lane < 2) mbar_arrive(BAR_SFULL(sb, wg * 2 + ix.lane));
    bar_sync(1 + wg, 128);
}
__device__ __forceinline__ void load_slab(uint32_t (&xr)[32], uint32_t buf) {
    IDX();
#pragma unroll
    for (int i = 0; i < 8; ++i) ldsm4(buf + (i >> 2) * 8192 + (pan_addr ^ ((i & 3) << 5)), xr[4 * i], xr[4 * i + 1], xr[4 * i + 2], xr[4 * i + 3]);
}
__device__ __forceinline__ void unpack_slab(float (&x)[64], const uint32_t (&xr)[32]) {
#pragma unroll
    for (int i = 0; i < 32; ++i) unpack2(xr[i], x[2 * i], x[2 * i + 1]);
}
__device__ __forceinline__ void store_slab(const float (&x)[64], uint32_t buf, uint32_t pitch, uint32_t pan, int i0, int i1) {
#pragma unroll
    for (int i = i0; i < i1; ++i)
        stsm4(buf + (i >> 2) * pitch + (pan ^ ((i & 3) << 5)), pack2(x[8 * i], x[8 * i + 1]), pack2(x[8 * i + 2], x[8 * i + 3]), pack2(x[8 * i + 4], x[8 * i + 5]), pack2(x[8 * i + 6], x[8 * i + 7]));
}
template <int NP, class Done>
__device__ __forceinline__ void fetch_halo(uint4* src, bool first, uint32_t dst, Done done) {
    uint4 hv[4 * NP];
    uint32_t n = 0;
    while (true) {
        bool ok = true;
#pragma unroll
        for (int i = 0; i < 4 * NP; ++i) { hv[i] = first ? make_uint4(0, 0, 0, 0) : ld_pkt16(src + (i >> 2) * 256 + (i & 3) * 32); ok = ok && hv[i].x != 0; }
        if (first || __all_sync(0xffffffffu, ok)) break;
        SPIN_GUARD(n);
    }
#pragma unroll
    for (int i = 0; i < 4 * NP; ++i) stsm4(dst + (i >> 2) * 4096 + (i & 3) * 512, hv[i].x, hv[i].y, hv[i].z, hv[i].w);
    done();
    if (!first) {
#pragma unroll
        for (int i = 0; i < 4 * NP; ++i) src[(i >> 2) * 256 + (i & 3) * 32] = make_uint4(0, 0, 0, 0);
    }
}

template <int N, class G, class U>
__device__ __forceinline__ void glu(uint32_t (&h)[N], G g, U u) {
#pragma unroll
    for (int i = 0; i < N; ++i) h[i] = pack2(fmaf(tanh_(g(2 * i)), u(2 * i), u(2 * i)), fmaf(tanh_(g(2 * i + 1)), u(2 * i + 1), u(2 * i + 1)));
}
__device__ __forceinline__ void put_h(const uint32_t (&h)[32], uint32_t sb, uint32_t wg, Stg& stg) {
    IDX();
    const uint32_t buf = stg.acquire2(sb, wg);
#pragma unroll
    for (int k = 0; k < 8; ++k) stsm4(buf + (k >> 2) * 8192 + (pan_addr ^ ((k & 3) << 5)), h[4 * k], h[4 * k + 1], h[4 * k + 2], h[4 * k + 3]);
    fence_async_smem();
    __syncwarp();
    if (lane < 2) mbar_arrive(BAR_SFULL(sb, wg * 2 + lane));
}

template <int NP, bool PREV>
__device__ __forceinline__ void passes128(uint32_t (&hp)[32], uint32_t sb, uint32_t wg, uint32_t tw, Ring& r, Stg& stg) {
#pragma unroll 1
    for (int p = 0; p < NP; ++p) {
        float b256[128], none[1];
        const int put_at = !PREV && p == 0 ? -1 : wg ? PUT1 : PUT0;
        mainloop32<false, LAGS>(b256, none, sb, wg, tw, r, EV_LAG2 + p, 80 + 32 * (p & 1), [&](int it) { if (it == put_at) put_h(hp, sb, wg, stg); },
                                [&] { if (PREV || p < NP - 1) mbar_wait(BAR_FULL(sb, r.slot), r.par); });
        if (threadIdx.x == 0) { TL(29 + 2 * p); TC(114 + 2 * p); }
        if (threadIdx.x == 128) TL(53 + 2 * (p & 1));
        CS(24 + 2 * (p & 1));
        glu(hp, [&](int i) { return b256[i + (i & 32)]; }, [&](int i) { return b256[i + (i & 32) + 32]; });
        if (threadIdx.x == 0) { TL(30 + 2 * p); TC(115 + 2 * p); }
        if (threadIdx.x == 128) TL(54 + 2 * (p & 1));
        CS(25 + 2 * (p & 1));
    }
}

__global__ void __launch_bounds__(384, 1)
fused_block_kernel(const __grid_constant__ Ptrs pt, const __grid_constant__ Maps mp) {
    uint32_t* const g_flags = pt.mail->flags;
    uint2* const g_mod = pt.mail->mod;
    uint4* const g_st1 = pt.mail->st1;
    uint32_t* const g_par2 = pt.mail->par2;
    uint4* const g_halo = pt.mail->halo;
    const __nv_bfloat16* __restrict__ cvec = pt.c;
    if (threadIdx.x == 224) { prefetch_map(&mp.wm8); prefetch_map(&mp.x); }
    extern __shared__ __align__(1024) uint8_t smem[];
    const uint32_t sb = smem_u32(smem);
    const uint32_t tid = threadIdx.x, tw = tid & 127, lane = tid & 31;
    const uint32_t warp = __shfl_sync(0xffffffffu, tid >> 5, 0), wg = warp >> 2;
    uint32_t rank; asm("mov.u32 %0, %%cluster_ctarank;" : "=r"(rank));
    rank = __shfl_sync(0xffffffffu, rank, 0);
    uint32_t ep;
    uint32_t smid; asm volatile("mov.u32 %0, %%smid;" : "=r"(smid));
    const int c = __shfl_sync(0xffffffffu, smid >> 1, 0);
    const int c7 = ((c - 32) * 37) >> 8;
    int grp = c < 32 ? c & 7 : c < 60 ? c - 31 - 7 * c7 : c < 62 ? -1 : 0;
    const int j = c < 32 ? c >> 3 : c < 60 ? 4 + c7 : c < 62 ? (c - 60) * 2 + rank : c - 58;
    const bool aux = grp < 0;
    const int m = grp * 2 + rank;
    uint4* const g_st2 = g_halo + (m > 0 ? (m - 1) * 8 * 512 : 128);

    bool cluster_arrive_early = false;
    if (wg < 2) {
      if (!KDEBUG) cluster_arrive();
      ep = flag_get(g_flags + FL_DONE);
      uint16_t cw[8];
      {
          const __nv_bfloat16* cp = cvec + ((tw >> 5) * 32 + (tw & 3) * 2) * 8 + (lane >> 2);
#pragma unroll
          for (int i = 0; i < 8; ++i) asm volatile("ld.global.nc.u16 %0, [%1];" : "=h"(cw[i]) : "l"(cp + (i >> 1) * 64 + (i & 1) * 8));
      }
      asm volatile("setmaxnreg.inc.sync.aligned.u32 224;");
      if (tid == 0) TL(58);
      if (KDEBUG) cluster_arrive();
      Ring r{0, 0};
      Stg stg{0, 0};
      if (aux) {
        if (wg == 0) {
            const uint4 cv = *(const uint4*)(cvec + tw * 8);
            sts128(sb + OFF_STG + (tw >> 3) * 1024 + (tw & 7) * 16, pack2(silu_(bf_lo(cv.x)), silu_(bf_hi(cv.x))), pack2(silu_(bf_lo(cv.y)), silu_(bf_hi(cv.y))),
                   pack2(silu_(bf_lo(cv.z)), silu_(bf_hi(cv.z))), pack2(silu_(bf_lo(cv.w)), silu_(bf_hi(cv.w))));
            fence_async_smem();
        }
        cluster_wait();
        ep = __shfl_sync(0xffffffffu, ep, 0) / NCTA + 1;
        if (wg == 0) {
            bar_sync(1, 128);
#pragma unroll 1
            for (int p = 0; p < 4; ++p) {
                float acc[4][4] = {};
                uint32_t prev = 0;
#pragma unroll 1
                for (int kc = 0; kc < 16; ++kc) {
                    mbar_wait(BAR_FULL(sb, r.slot), r.par);
                    wg_fence();
#pragma unroll
                    for (int k = 0; k < 16; ++k)
                        wgmma_n8_ta(acc[k & 3], mk_desc(d16(sb) + r.slot * (SLOT >> 4), (k & 3) * 8192 + (k >> 2) * 2048, 8192, 1024, 1), mk_desc(d16(sb) + kc * 64, OFF_STG + (k >> 2) * 32, 16, 1024, 1));
                    wg_commit();
                    wg_wait<1>();
                    if (kc > 0 && tw < 4) mbar_arrive(BAR_EMPTY(sb, prev));
                    prev = r.slot;
                    r.next();
                }
                wg_wait<0>();
                if (tw < 4) mbar_arrive(BAR_EMPTY(sb, prev));
                if (!(tw & 3)) {
#pragma unroll
                    for (int i = 0; i < 8; ++i) {
                        asm volatile("" : "+f"(acc[i >> 1][(i & 1) * 2]) :: "memory");
                        asm volatile("st.shared.u16 [%0], %1;" :: "r"(sb + OFF_TAB + ((i >> 1) * 64 + (tw >> 5) * 16 + (i & 1) * 8 + (lane >> 2)) * 2), "h"((uint16_t)pack2(acc[i >> 1][(i & 1) * 2], 0.f)) : "memory");
                    }
                }
                bar_sync(1, 128);
                const int vec = p ? 6 - p : 2, blk = (vec - 2) * 4 + j;
                const uint32_t val = lds32(sb + OFF_TAB + tw * 4);
                if (vec == 2 || vec == 5) st_pkt(g_mod + (8 + blk) * 128 + tw, val, ep);
                else {
                    const float one = vec == 4 ? 1.f : 0.f;
                    g_par2[((blk & 3) * 16 + (tw >> 3)) * 16 + (tw & 3) * 4 + (vec - 3) * 2 + ((tw >> 2) & 1)] =
                        pack2(0.5f * bf_round(one + bf_lo(val)), 0.5f * bf_round(one + bf_hi(val)));
                }
                bar_sync(1, 128);
                if (tw == 0) {
                    if (p == 3) asm volatile("red.release.gpu.global.add.u32 [%0], 1;" :: "l"(&g_flags[FL_LN2]) : "memory");
                    TL(1 + p);
                }
            }
            if (lane < 2) mbar_arrive_cta(BAR_ONE(sb, EV_P0), lane);
        }
        r = Ring{64 % NSLOT, (64 / NSLOT) & 1};
        mbar_wait(BAR_ONE(sb, EV_P0), 0);
        mbar_wait(BAR_FULL(sb, r.slot), r.par);
        uint32_t hp[32] = {};
        passes128<4, false>(hp, sb, wg, tw, r, stg);
        put_h(hp, sb, wg, stg);
      } else {
        float xs[64];
        uint32_t xp[32];
        {
            sts128(sb + tid * 16, pack2(silu_(bf_lo(cw[0])), silu_(bf_lo(cw[1]))), pack2(silu_(bf_lo(cw[2])), silu_(bf_lo(cw[3]))),
                   pack2(silu_(bf_lo(cw[4])), silu_(bf_lo(cw[5]))), pack2(silu_(bf_lo(cw[6])), silu_(bf_lo(cw[7]))));
            cluster_wait();
            ep = __shfl_sync(0xffffffffu, ep, 0) / NCTA + 1;
            load_slab(xp, stg.acquire2(sb, wg));
            unpack_slab(xs, xp);
            if (tid == 0) TL(24);
            if (tid == 128) TL(27);
        }
#pragma unroll 1
        for (int blk = 0; ; ++blk) {
        {
            IDX();
            uint4* const st = (blk ? g_st2 : g_st1 + m * 8 * 512) + wg * 64 + w4 * 16 + g8;
            const bool acc = RACC && blk;
            RowAcc ra;
#pragma unroll
            for (int e = 0; e < 64; ++e) ra.add(e, xs[e]);
            ra.publish(st + (acc ? 0 : j * 512), q4, ep, acc);
            if (tid == 0) TL(blk ? 9 : 26);
            if (tid == 128 && blk) TL(34);
            if (blk) CS(11);
            LnPar lp;
            if (blk == 0) {
            uint4* const mod_out = pt.mail->mod1 + g8 * 512 + (m * 8 + j) * 4 + q4;
            if (wg == 0) {
                uint4 af[8];
#pragma unroll
                for (int i = 0; i < 8; ++i) af[i] = lds128(sb + w4 * 512 + i * 64 + q4 * 16);
                float c[4][4] = {};
#pragma unroll
                for (int i = 0; i < 8; ++i) {
                    if (!(i & 1)) mbar_wait(BAR_ONE(sb, EV_WIN + (i >> 1)), 0);
                    if (i == 6 && tid == 0) TL(25);
#pragma unroll
                    for (int h = 0; h < 2; ++h) {
                        uint32_t b0, b1, b2, b3;
                        ldsm4t(sb + 5 * SLOT + i * 4096 + w4 * 1024 + h * 512 + (lane & 15) * 32 + (lane >> 4) * 16, b0, b1, b2, b3);
                        mma16816(c[2 * h], h ? af[i].z : af[i].x, 0u, h ? af[i].w : af[i].y, 0u, b0, b1);
                        mma16816(c[2 * h + 1], h ? af[i].z : af[i].x, 0u, h ? af[i].w : af[i].y, 0u, b2, b3);
                    }
                }
                if (lane < 4) sts128(sb + OFF_TAB + w4 * 64 + lane * 16, __float_as_uint(c[0][0] + c[2][0]), __float_as_uint(c[0][1] + c[2][1]),
                                     __float_as_uint(c[1][0] + c[3][0]), __float_as_uint(c[1][1] + c[3][1]));
                if (lane < 2) mbar_arrive_cta(BAR_ONE(sb, EV_P0), lane);
                bar_sync(1, 128);
                if (w4 == 0) {
                    float a[4] = {0.f, 0.f, 0.f, 0.f};
#pragma unroll
                    for (int i = 0; i < 4; ++i) {
                        const uint4 t = lds128(sb + OFF_TAB + i * 64 + q4 * 16);
                        a[0] += __uint_as_float(t.x); a[1] += __uint_as_float(t.y); a[2] += __uint_as_float(t.z); a[3] += __uint_as_float(t.w);
                    }
                    const float add = m >= 8 ? 1.f : 0.f;
                    st_pkt16(mod_out, pack2(bf_round(a[0]) + add, bf_round(a[1]) + add), pack2(bf_round(a[2]) + add, bf_round(a[3]) + add), ep, 0);
                    if (tid == 0) TL(3);
                }
            } else if (LWAIT >= 0) mbar_wait(BAR_ONE(sb, EV_WIN + LWAIT), 0);
            } else {
                mbar_wait2(BAR_ONE(sb, EV_LN2), BAR_FULL(sb, 0), 0);
            }
            lp.load(sb, q4);
#pragma unroll
            for (int e = 0; e < 32; ++e) xp[e] = pack2(xs[2 * e], xs[2 * e + 1]);
            if (blk) CS(13);
            const LnRow n = merge_stats(st, q4, ep, sb, acc);
            if (tid == 0) TL(blk ? 49 : 48);
            if (tid == 128) TL(blk ? 45 : 28);
            if (blk) CS(18);
            uint32_t xn[32];
            ln_norm(xn, xs, n);
            if (blk == 0) {
                mbar_wait2(BAR_FULL(sb, 0), BAR_ONE(sb, EV_PAR), 0);
                if (FD0 && wg == 0) { uint32_t t0, t1; asm volatile("mov.u32 %0, %%clock;" : "=r"(t0)); do { asm volatile("mov.u32 %0, %%clock;" : "=r"(t1)); } while (t1 - t0 < FD0); }
                lp.load(sb, q4);
            }
            ln_emit(xn, lp, sb, wg, ix);
            if (tid == 0) { TL(blk ? 36 : 8); TC(blk ? 109 : 103); }
            if (tid == 128) TL(blk ? 43 : 22);
            if (blk) CS(21);
        }
        uint32_t hp[32];
        if (blk == 0) {
        {
            float big[128], sml[64];
            step32<true, true>(big, sml, sb, wg, r.slot, 0);
            TS(0, 0);
            Pipe pp(sb, tw, r.slot);
            r.next();
#pragma unroll 1
            for (int it = 1; it < 32 - LAGQ; ++it) {
                pp.acquire<true>(sb, wg ? 0 : AF_REL, r);
                step32<true, false>(big, sml, sb, wg, r.slot, it < 4 ? it : -1);
                pp.issued(r.slot);
                TS(it, 0);
                r.next();
            }
            auto half = [&](uint32_t slot, bool rest) {
                const uint32_t st = d16(sb) + slot * (SLOT >> 4);
#pragma unroll
                for (int k = 0; k < 2; ++k) {
                    const uint64_t da = mk_desc(st + wg * 256, k * 32, 16, 512, 2);
                    if (rest) wgmma_n256(big, da, mk_desc(st, 8192 + k * 2048, 4096, 1024, 1)); else wgmma_n128(sml, da, mk_desc(st, 24576 + k * 2048, 4096, 1024, 1));
                }
            };
            auto rest = [&](bool each) {
                wg_fence();
#pragma unroll
                for (int it = 32 - LAGQ; it < 32; ++it) { if (each && it > 32 - LAGQ) wg_fence(); half(it % NSLOT, true); if (each || it == 31) wg_commit(); }
            };
            stg.acquire2(sb, wg); mbar_wait2(BAR_SREADY(sb, 2), BAR_SREADY(sb, 3), 1);
#pragma unroll 1
            for (int it = 32 - LAGQ; it < 32; ++it) {
                pp.acquire<true>(sb, wg ? 0 : AF_REL, r);
                wg_fence(); half(r.slot, false); wg_commit();
                pp.issued(NSLOT);
                TS(it, 0);
                r.next();
            }
            if (wg) { rest(false); wg_wait<1>(); } else wg_wait<0>();
            CS(8);
            IDX();
            uint32_t k0[8], k1[8], k2[8], v0[8], v1[8], v2[8];
            const uint32_t nxt = warp + ((warp & 1) ? 3 : 1), mine = sb + OFF_STG + wg * 16384 + w4 * 2048;
            auto tails = [&](const float* kv, uint32_t (&kt)[8], uint32_t (&vt)[8]) {
#pragma unroll
                for (int t = 0; t < 8; ++t) { kt[t] = pack2(kv[4 * t + 2], kv[4 * t + 3]); vt[t] = pack2(kv[32 + 4 * t + 2], kv[32 + 4 * t + 3]); }
            };
            auto post = [&](int pn, uint32_t (&kt)[8], uint32_t (&vt)[8]) {
                uint4* dst = g_halo + (m * 8 + j) * 512 + (w4 >> 1) * 256 + pn * 128 + lane;
#pragma unroll
                for (int h = 0; h < 2; ++h) { if (!kt[4 * h]) kt[4 * h] = 0x8000u; if (!vt[4 * h]) vt[4 * h] = 0x8000u; }
#pragma unroll
                for (int h = 0; h < 2; ++h) { st_pkt16(dst + h * 32, kt[4 * h], kt[4 * h + 1], kt[4 * h + 2], kt[4 * h + 3]); st_pkt16(dst + 64 + h * 32, vt[4 * h], vt[4 * h + 1], vt[4 * h + 2], vt[4 * h + 3]); }
            };
            auto prepare = [&](int pn, const float* kv) {
                tails(kv, k2, v2);
                if (nxt < 8) {
                    const uint32_t dst = sb + OFF_STG + (nxt >> 2) * 16384 + (nxt & 3) * 2048 + pn * 8192 + lane * 16;
#pragma unroll
                    for (int h = 0; h < 2; ++h) { stsm4(dst + h * 512, k2[4 * h], k2[4 * h + 1], k2[4 * h + 2], k2[4 * h + 3]); stsm4(dst + 1024 + h * 512, v2[4 * h], v2[4 * h + 1], v2[4 * h + 2], v2[4 * h + 3]); }
                    if (pn == 0) bar_arrive(NB_TAIL + nxt, 64);
                    else { __syncwarp(); if (lane == 0) mbar_arrive(BAR_ONE(sb, EV_TAIL + nxt)); }
                } else if (pn == 0 && m < 15) post(0, k2, v2);
#pragma unroll
                for (int t = 0; t < 8; ++t) { k1[t] = pack2(kv[4 * t], kv[4 * t + 1]); v1[t] = pack2(kv[32 + 4 * t], kv[32 + 4 * t + 1]); }
                auto turn = [&] {
#pragma unroll
                    for (int t = 0; t < 8; ++t) { v1[t] = movm(v1[t]); v2[t] = movm(v2[t]); }
                };
                if (pn) turn();
                if (pn == 0) {
                    CS(2);
                    if (wg == 0) { rest(true); turn(); wg_wait<3>(); pp.rel(28 % NSLOT); wg_wait<2>(); pp.rel(29 % NSLOT); wg_wait<1>(); pp.rel(30 % NSLOT); }
                    else turn();
                    bar_sync(NB_TAIL + warp, 64); CS(4);
                }
                else mbar_wait(BAR_ONE(sb, EV_TAIL + __shfl_sync(0xffffffffu, warp, 0)), 0);
#pragma unroll
                for (int h = 0; h < 2; ++h) {
                    ldsm4(mine + pn * 8192 + lane * 16 + h * 512, k0[4 * h], k0[4 * h + 1], k0[4 * h + 2], k0[4 * h + 3]);
                    ldsm4t(mine + pn * 8192 + lane * 16 + 1024 + h * 512, v0[4 * h], v0[4 * h + 1], v0[4 * h + 2], v0[4 * h + 3]);
                }
            };
#pragma unroll
            for (int i = 0; i < 64; ++i) asm volatile("" : "+f"(sml[i]) :: "memory");
            prepare(0, sml);
            static_assert(LAGQ == 4, "");
            wg_wait<0>();
            if (wg) { pp.rel(28 % NSLOT); pp.rel(29 % NSLOT); pp.rel(30 % NSLOT); }
            pp.rel(31 % NSLOT);
            TS(31, 1);
            if (tid == 0) { TL(4); TC(104); }
            if (tid == 128) TL(50);
            CS(1);
#pragma unroll
            for (int i = 0; i < 128; ++i) asm volatile("" : "+f"(big[i]) :: "memory");
            if (nxt >= 8 && m < 15) { uint32_t kt[8], vt[8]; tails(big, kt, vt); post(1, kt, vt); }
            const bool lo0 = q4 * 2 > g8, lo1 = q4 * 2 + 1 > g8;
            const bool nopast = m == 0 && (warp & 5) == 0;
            const uint32_t lomask = (lo0 ? 0xFFFFu : 0u) | (lo1 ? 0xFFFF0000u : 0u);
            const uint32_t orow = mine + (lane & 7) * 128 + (((lane >> 3) ^ (lane & 7)) << 4);
            const float sl2 = 0.17677669529663687f * 1.4426950408889634f;
#pragma unroll
            for (int pn = 0; pn < 2; ++pn) {
                float e0[4], e1[4], mx[4], sum[4];
#pragma unroll
                for (int hh = 0; hh < 2; ++hh) {
                    uint32_t qf[8];
#pragma unroll
                    for (int i = 0; i < 8; ++i) qf[i] = pack2(big[64 + 32 * pn + 16 * hh + 2 * i], big[64 + 32 * pn + 16 * hh + 2 * i + 1]);
                    float s[3][4];
#pragma unroll
                    for (int t = 0; t < 3; ++t) {
                        const uint32_t* k = (t == 0 ? k0 : t == 1 ? k1 : k2) + 4 * hh;
                        s[t][0] = s[t][1] = s[t][2] = s[t][3] = 0.f;
                        mma16816(s[t], qf[0], qf[1], qf[2], qf[3], k[0], k[1]);
                        mma16816(s[t], qf[4], qf[5], qf[6], qf[7], k[2], k[3]);
                    }
#pragma unroll
                    for (int hf = 0; hf < 2; ++hf) {
                        const int u = hh * 2 + hf;
                        e0[u] = lo0 ? ((hf == 0 && nopast) ? -INFINITY : s[hf][hf * 2]) : s[hf + 1][hf * 2];
                        e1[u] = lo1 ? ((hf == 0 && nopast) ? -INFINITY : s[hf][hf * 2 + 1]) : s[hf + 1][hf * 2 + 1];
                        mx[u] = fmaxf(e0[u], e1[u]);
                    }
                }
#pragma unroll
                for (int o = 1; o < 4; o <<= 1)
#pragma unroll
                    for (int u = 0; u < 4; ++u) mx[u] = fmaxf(mx[u], __shfl_xor_sync(0xffffffffu, mx[u], o));
#pragma unroll
                for (int u = 0; u < 4; ++u) {
                    const float c = -mx[u] * sl2;
                    e0[u] = ex2(fmaf(e0[u], sl2, c)); e1[u] = ex2(fmaf(e1[u], sl2, c));
                    sum[u] = e0[u] + e1[u];
                }
#pragma unroll
                for (int o = 1; o < 4; o <<= 1)
#pragma unroll
                    for (int u = 0; u < 4; ++u) sum[u] += __shfl_xor_sync(0xffffffffu, sum[u], o);
#pragma unroll
                for (int u = 0; u < 4; ++u) {
                    const int h = u >> 1;
                    const float inv = rcp(sum[u]);
                    const uint32_t p = pack2(e0[u] * inv, e1[u] * inv);
                    const uint32_t* va = ((u & 1) ? v1 : v0) + 4 * h;
                    const uint32_t* vb = ((u & 1) ? v2 : v1) + 4 * h;
                    float o[2][4] = {};
#pragma unroll
                    for (int d = 0; d < 2; ++d) mma16816(o[d], va[2 * d], va[2 * d + 1], vb[2 * d], vb[2 * d + 1], p & lomask, p & ~lomask);
                    stsm4t((orow ^ ((u >> 1) << 6)) + pn * 8192 + (u & 1) * 1024, pack2(o[0][0], o[0][1]), pack2(o[0][2], o[0][3]), pack2(o[1][0], o[1][1]), pack2(o[1][2], o[1][3]));
                }
                fence_async_smem();
                __syncwarp();
                if (lane == 0) mbar_arrive(BAR_SFULL(sb, wg * 2 + pn));
                if (pn == 0) { CS(5); block_end(sb, 0); prepare(1, big); CS(3); }
            }
            CS(6);
            if (tid == 32) TL(41);
            mbar_wait2(BAR_FULL(sb, 32 % NSLOT), BAR_FULL(sb, 33 % NSLOT), (32 / NSLOT) & 1);
            load_slab(xp, sb + (32 % NSLOT + wg) * SLOT);
#pragma unroll
            for (int e = 0; e < 32; ++e) hp[e] = __float_as_uint(big[e]);
            bar_sync(1 + wg, 128);
            if (tid == 0) { TL(6); TC(106); }
            if (tid == 128) TL(44);
            CS(7);
        }
        } else {
        {
            float ag[88], au[88];
            mainloop32<true, LAG>(ag, au, sb, wg, tw, r, EV_LAG1, 48, [](int) {}, [&] {
                Ring q = r; if (!wg) q.next();
                mbar_wait(BAR_EMPTY(sb, q.slot), q.par ^ 1);
                mbar_wait(BAR_FULL(sb, r.slot), r.par);
            });
            if (tid == 0) { TL(10); TC(110); }
            if (tid == 128) TL(51);
            CS(22);
            {
                IDX();
                uint32_t h3[12];
                glu(h3, [&](int i) { return ag[64 + i]; }, [&](int i) { return au[64 + i]; });
#pragma unroll
                for (int k = 0; k < 3; ++k) stsm4(sb + (wg ? P3_SLOT1 : P3_SLOT0) * SLOT + 24576 + (pan_addr ^ (k << 5)), h3[4 * k], h3[4 * k + 1], h3[4 * k + 2], h3[4 * k + 3]);
            }
            glu(hp, [&](int i) { return ag[i]; }, [&](int i) { return au[i]; });
            if (tid == 0) { TL(11); TC(111); }
            if (tid == 128) TL(52);
            CS(23);
        }
        passes128<2, true>(hp, sb, wg, tw, r, stg);
        if (tid == 0) { TL(12); TC(112); }
        }
        {
            float acc[64], gf[32];
            mainloop64(acc, blk == 0, sb, wg, tw, r, [&] { put_h(hp, sb, wg, stg); }, [&] {
                mbar_wait(BAR_ONE(sb, EV_GA + blk), 0);
                unpack_slab(xs, xp);
                uint32_t gt[16];
#pragma unroll
                for (int cg = 0; cg < 16; ++cg) gt[cg] = lds32(sb + OFF_TAB + blk * 256 + cg * 16 + (tw & 3) * 4);
#pragma unroll
                for (int i = 0; i < 16; ++i) unpack2(gt[i], gf[2 * i], gf[2 * i + 1]);
            }, [&] { stg.acquire2(sb, wg); });
            if (tid == 0) { TL(blk ? 13 : 7); TC(blk ? 113 : 107); }
            if (tid == 128) TL(blk ? 57 : 42);
            CS(blk ? 30 : 10);
#pragma unroll
            for (int e = 0; e < 64; ++e) xs[e] = fmaf(gf[(e >> 2) * 2 + (e & 1)], acc[e], xs[e]);
        }
        if (blk) break;
        }
        {
            IDX();
#pragma unroll
            for (int p = 0; p < 2; ++p) {
                store_slab(xs, sb + OFF_STG + wg * 16384, 8192, pan_addr, 4 * p, 4 * p + 4);
                stg.publish(sb, wg, lane);
            }
            cluster_arrive();
            if (tid == 0) TL(14);
            CS(31);
        }
      }
    } else {
        if (warp == 8 && !aux && elect_one()) {
#pragma unroll
            for (int i = 0; i < 4; ++i) mbar_init(BAR_SREADY(sb, i), 1);
#pragma unroll
            for (int i = 0; i < 4; ++i) mbar_init(BAR_ONE(sb, EV_WIN + i), 1);
#pragma unroll
            for (int i = 0; i < 4; ++i) {
                mbar_expect_tx(BAR_SREADY(sb, i), 8192);
                tma_load3(sb + OFF_STG + i * 8192, &mp.x, j * 128 + (i & 1) * 64, m * 64 + (i >> 1) * 32, BAR_SREADY(sb, i));
            }
#pragma unroll 1
            for (int i = 0; i < 4; ++i) {
                mbar_expect_tx(BAR_ONE(sb, EV_WIN + i), 8192);
                tma_load(sb + 5 * SLOT + i * 8192, &mp.wm8, 2 * i * 6144 + (m * 8 + j) * 16, 0, BAR_ONE(sb, EV_WIN + i));
                tma_load(sb + 5 * SLOT + i * 8192 + 4096, &mp.wm8, (2 * i + 1) * 6144 + (m * 8 + j) * 16, 0, BAR_ONE(sb, EV_WIN + i));
            }
        }
        __syncwarp();
        asm volatile("setmaxnreg.dec.sync.aligned.u32 56;");
        if (elect_one()) {
            if (warp == 8) {
                prefetch_map(&mp.wqkv); prefetch_map(&mp.wmod);
            } else if (warp < 11) {
                mbar_init(BAR_EMPTY(sb, NSLOT), 1);
#pragma unroll
                for (int i = 0; i < 2; ++i) { mbar_init(BAR_SFULL(sb, (warp - 9) * 2 + i), 4); if (aux) mbar_init(BAR_SREADY(sb, (warp - 9) * 2 + i), 1); }
#pragma unroll
                for (int i = 0; i < 3; ++i) {
                    mbar_init(BAR_EMPTY(sb, (warp - 9) * 3 + i), 4);
                    mbar_init(BAR_FULL(sb, (warp - 9) * 3 + i), 1); mbar_init(BAR_FULL(sb, (warp - 9) * 3 + i) + AF_REL, 1);
                }
            } else {
#pragma unroll
                for (int i = EV_P0; i < EV_COUNT; ++i) mbar_init(BAR_ONE(sb, i), i == EV_P0 ? 8 : 1);
            }
            asm volatile("fence.mbarrier_init.release.cluster;" ::: "memory");
        }
        __syncwarp();
        cluster_arrive();
        ep = 0;
        if (warp != 8 || aux) ep = flag_get(g_flags + FL_DONE);
        cluster_wait();
        ep = __shfl_sync(0xffffffffu, ep, 0) / NCTA + 1;
        if (warp == 8) {
            const bool el = elect_one();
            Ring r{0, 1};
            if (aux) {
                {
                    uint32_t n = 0;
                    while (!__all_sync(0xffffffffu, ld_pkt16(pt.mail->mod1 + 256).z == ep)) { SPIN_GUARD(n); __nanosleep(200); }
                }
#pragma unroll 1
                for (int it = 0; it < 64; ++it) {
                    const int col = (it < 16 ? 2048 : 6144 - (it >> 4) * 1024) + j * 256;
                    mbar_wait(BAR_EMPTY(sb, r.slot), r.par);
                    const uint32_t st = sb + r.slot * SLOT, fb = BAR_FULL(sb, r.slot);
                    if (el) {
                        mbar_expect_tx(fb, 32768);
#pragma unroll
                        for (int b = 0; b < 4; ++b) tma_load_ef(st + b * 8192, &mp.wmod, col + b * 64, (it & 15) * 64, fb);
                    }
                    r.next();
                }
                mbar_wait(BAR_ONE(sb, EV_P0), 0);
                const CUtensorMap* wm = rank ? &mp.wu : &mp.wg;
#pragma unroll 1
                for (int g = 0; g < 128; ++g) {
                    const int mx = (j >> 1) * 8 + (g >> 5) * 2 + rank, k0 = ((g & 14) << 6) + ((g & 16) << 2) + ((g & 1) << 5);
                    if (!(g & 15) && g <= 32) mbar_wait(BAR_ONE(sb, EV_H0 + (g >> 4)), 0);
                    mbar_wait(BAR_EMPTY(sb, r.slot), r.par);
                    const uint32_t st = sb + r.slot * SLOT, fb = BAR_FULL(sb, r.slot);
                    if (el) {
                        mbar_expect_tx(fb, 24576);
                        tma_load_mc(st + 8192 + rank * 4096, wm, HC3, k0, fb);
                        tma_load_mc(st + 16384 + rank * 4096, wm, HC3 + 64, k0, fb);
                        tma_load(st, &mp.h2l, k0, mx * 128, fb);
                    }
                    r.next();
                }
            } else {
#pragma unroll 1
                for (int it = 0; it < 32; ++it) {
                    const int cb = j * 128 + rank * 64, k0 = kof(it, 2, j);
                    if (it == BW0) mbar_wait(BAR_ONE(sb, BWEV), 0);
                    if (it == BW1) mbar_wait(BAR_ONE(sb, EV_PAR), 0);
                    if (it == 5) mbar_wait(BAR_ONE(sb, EV_P0), 0);
                    if (it == AG0) mbar_wait(BAR_ONE(sb, (AGW & 1) ? EV_AGO : EV_FGO), 0);
                    mbar_wait(BAR_EMPTY(sb, r.slot), r.par);
                    const uint32_t st = sb + r.slot * SLOT, fb = BAR_FULL(sb, r.slot);
                    if (el) {
                        mbar_expect_tx(fb, it < 4 ? 24576 : 28672);
                        tma_load_mc(st + 24576 - rank * 16384, &mp.wqkv, 1024 + cb, k0, fb);
                        tma_load_mc(st + 28672 - rank * 16384, &mp.wqkv, 2048 + cb, k0, fb);
                        tma_load_mc(st + 16384 + rank * 4096, &mp.wqkv, cb, k0, fb);
                        if (it < 4) mbar_arrive(fb + AF_REL);
                        if (it == PFWO + (m >> 1)) { tma_prefetch(&mp.wo, j * 128, m * 64); tma_prefetch(&mp.wo, j * 128 + 64, m * 64); }
                        if (it >= PFG && it < PFG + PFN && (it & 7) == grp) {
                            const int kp = kof(it - PFG + PFO, 2, j);
                            tma_prefetch(rank ? &mp.wu : &mp.wg, hcol(0, j), kp); tma_prefetch(rank ? &mp.wu : &mp.wg, hcol(0, j) + 64, kp);
                            asm volatile("cp.async.bulk.prefetch.tensor.3d.L2.global [%0, {%1, %2, %3}];" :: "l"(rank ? &mp.wu3 : &mp.wg3), "r"(0), "r"(j), "r"(kp) : "memory");
                        }
                    }
                    r.next();
                }
                if (el) mbar_arrive(BAR_ONE(sb, EV_KV));
#pragma unroll 1
                for (int it = 0; it < 16; ++it) {
                    const int k0 = kof(it, 1, j);
                    if (it == AG1) mbar_wait(BAR_ONE(sb, (AGW & 2) ? EV_AGO1 : EV_FGO1), 0);
                    mbar_wait(BAR_EMPTY(sb, r.slot), r.par);
                    const uint32_t st = sb + r.slot * SLOT, fb = BAR_FULL(sb, r.slot);
                    if (el) {
                        mbar_expect_tx(fb, it < 2 ? 32768 : 24576);
                        tma_load_mc(st + 16384 + rank * 8192, &mp.wo, j * 128 + rank * 64, k0, fb);
                        if (it < 2) {
                            tma_load3(st, &mp.x, j * 128, m * 64 + it * 32, fb); tma_load3(st + 8192, &mp.x, j * 128 + 64, m * 64 + it * 32, fb);
                            mbar_arrive(fb + AF_REL);
                        }
                        if (it == 6) { prefetch_map(rank ? &mp.wu : &mp.wg); prefetch_map(rank ? &mp.wu3 : &mp.wg3); }
                    }
                    r.next();
                }
                const CUtensorMap* wm = rank ? &mp.wu : &mp.wg;
#pragma unroll 1
                for (int g = 0; g < 96; ++g) {
                    if (g == AG2) mbar_wait(BAR_ONE(sb, (AGW & 4) ? EV_AGO2 : EV_FGO2), 0);
                    const int p = g >> 5, cb = hcol(p, j), k0 = p == 0 ? kof(g, 2, j) : (g & 31) * 32;
                    mbar_wait(BAR_EMPTY(sb, r.slot), r.par);
                    const uint32_t st = sb + r.slot * SLOT, fb = BAR_FULL(sb, r.slot);
                    if (el) {
                        mbar_expect_tx(fb, (g < 4 || p > 0) ? 24576 : 28672);
                        tma_load_mc(st + 8192 + rank * 4096, wm, cb, k0, fb);
                        tma_load_mc(st + 16384 + rank * 4096, wm, cb + 64, k0, fb);
                        if (p == 0) tma_load3_mc(st + 24576 + rank * 4096, rank ? &mp.wu3 : &mp.wg3, j, k0, fb);
                        else tma_load(st, &mp.h2l, k0, m * 128, fb);
                        if (g < 4) mbar_arrive(fb + AF_REL);
                        if ((g & 7) == grp && g + PFC >= 96) tma_prefetch(&mp.wd, j * 128 + rank * 64, (g + PFC - 96) * 64);
                        if (g == 60) { prefetch_map(&mp.wd); prefetch_map(&mp.hb); }
                    }
                    r.next();
                }
#pragma unroll 1
                for (int g = 0; g < 56; ++g) {
                    if (g == 0 || (g & 15) == 6 && g > 6) mbar_wait(BAR_ONE(sb, EV_H0 + (g >> 4)), 0);
                    const int k0 = g * 64;
                    mbar_wait(BAR_EMPTY(sb, r.slot), r.par);
                    const uint32_t st = sb + r.slot * SLOT, fb = BAR_FULL(sb, r.slot);
                    if (el) {
                        mbar_expect_tx(fb, 32768);
                        tma_load_mc(st + 16384 + rank * 8192, &mp.wd, j * 128 + rank * 64, k0, fb);
                        tma_load(st, &mp.hb, k0, m * 128, fb); tma_load(st + 8192, &mp.hb, k0, m * 128 + 64, fb);
                        if ((g & 7) == grp && g + PFC < 56) tma_prefetch(&mp.wd, j * 128 + rank * 64, k0 + PFC * 64);
                    }
                    r.next();
                }
            }
        } else if (aux) {
            if (warp < 11) {
                const uint32_t w = warp - 9;
                const bool el = elect_one();
#pragma unroll 1
                for (int p = 0; p < 4; ++p) {
                    const int mx = (j >> 1) * 8 + p * 2 + rank;
                    if (el) { mbar_arrive(BAR_SREADY(sb, w * 2)); mbar_arrive(BAR_SREADY(sb, w * 2 + 1)); }
                    mbar_wait2(BAR_SFULL(sb, w * 2), BAR_SFULL(sb, w * 2 + 1), p & 1);
                    if (p < 3) pause(w ? HD1 : HD0);
                    if (el) tma_store(&mp.hb, HC3, mx * 128 + w * 64, sb + OFF_STG + w * 16384);
                    if (p < 3) pause(HP);
                    if (el) {
                        tma_store(&mp.hb, HC3 + 64, mx * 128 + w * 64, sb + OFF_STG + w * 16384 + 8192);
                        bulk_commit(); bulk_wait_fence(); flag_set(g_flags + FL_AUX + mx * 2 + w, ep * 8 + ST_H + 3);
                    }
                }
            } else {
                mbar_wait(BAR_ONE(sb, EV_P0), 0);
#pragma unroll 1
                for (int i = 0; i < 5; ++i) {
                    const uint32_t* f = g_flags + FL_PROG + fidx((j >> 1) * 8 + (i ? i - 1 : 0) * 2 + rank, lane >> 4, lane & (i ? 15 : 14));
                    uint32_t n = 0;
                    while (!__all_sync(0xffffffffu, (int32_t)(flag_get(f) - (ep * 8 + ST_H2)) >= 0)) { SPIN_GUARD(n); __nanosleep(200); }
                    if (i < 2) pause(AUXD);
                    if (lane == 0 && (i < 2 || i == 4)) mbar_arrive(BAR_ONE(sb, EV_H0 + (i < 2 ? i : 2)));
                }
            }
        } else if (warp == 11) {
            const bool el = elect_one();
            const int row0 = m * 128;
            if (el) { prefetch_map(&mp.h1h); prefetch_map(&mp.h2h); prefetch_map(&mp.h2l); }
            auto gate = [&](int vec, int ev) {
                const uint32_t lane = Idx().lane;
                uint4 v; uint32_t n = 0;
                while (true) {
                    v = ld_pkt2(g_mod + vec * 512 + j * 64 + lane * 2);
                    if (__all_sync(0xffffffffu, v.y == ep && v.w == ep)) break;
                    SPIN_GUARD(n); __nanosleep(300);
                }
                asm volatile("st.shared.v2.u32 [%0], {%1, %2};" :: "r"(sb + OFF_TAB + (ev - EV_GA) * 256 + lane * 8), "r"(v.x), "r"(v.z) : "memory");
                __syncwarp();
                if (lane == 0) mbar_arrive(BAR_ONE(sb, ev));
            };
            {
                const uint4* pk = pt.mail->mod1 + grp * 512 + j * 32 + lane;
                uint4 a, b; uint32_t n = 0;
                mbar_wait(BAR_ONE(sb, EV_WIN3), 0);
                while (true) {
                    a = ld_pkt16(pk); b = ld_pkt16(pk + 256);
                    if (__all_sync(0xffffffffu, a.z == ep && b.z == ep)) break;
                    SPIN_GUARD(n);
                }
                sts128(sb + OFF_PAR + lane * 16, a.x, a.y, b.x, b.y);
                __syncwarp();
                if (lane == 0) { mbar_arrive(BAR_ONE(sb, EV_PAR)); TL(46); }
            }
            mbar_wait(BAR_ONE(sb, EV_P0), 0);
            Ring r{0, 1};
#pragma unroll 1
            for (int ph = 0; ph < 3; ++ph) {
                const uint32_t lane = Idx().lane;
                const int sh = ph == 1 ? 1 : 2, nst = 8 << sh;
                const uint32_t half = 16384 >> sh, target = ep * 8 + ST_H1 + ph;
                const CUtensorMap* tm = ph == 0 ? &mp.h1h : ph == 1 ? &mp.o : &mp.h2h;
                if (ph == 1) {
                    gate(2, EV_GA);
                    mbar_wait(BAR_SREADY(sb, 1), 1);
                    fetch_halo<2>(g_halo + ((m - 1) * 8 + j) * 512 + 128 + lane, m == 0, sb + OFF_STG + 8192 + lane * 16,
                                  [&] { __syncwarp(); if (lane < 2) mbar_arrive(BAR_ONE(sb, EV_TAIL + 2 * lane)); });
                    CS(32);
                }
                if (ph == 2) {
                    uint32_t n = 0;
                    while ((int32_t)(flag_get(g_flags + FL_LN2) - ep * 4) < 0) { SPIN_GUARD(n); __nanosleep(200); }
                    const uint4 v = __ldcg((const uint4*)(g_par2 + j * 128) + lane);
                    sts128(sb + OFF_PAR + lane * 16, v.x, v.y, v.z, v.w);
                    __syncwarp();
                    if (lane == 0) mbar_arrive(BAR_ONE(sb, EV_LN2));
                }
                const uint32_t* const fl = g_flags + FL_PROG + fidx(m, lane >> 4, kof(lane & 15, 1, j) >> 6);
                const uint32_t lw = ~lane & 1, lt = lane >> 1, ls = (r.slot + lt) % NSLOT, lk = kof(lt, sh, j), lb = BAR_FULL(sb, ls) + (lw ? 0 : AF_REL);
                const uint32_t* const lf = g_flags + FL_PROG + fidx(m, lw, lk >> 6);
                int fr = 1 << sh;
                uint32_t todo = 0x3ffffu >> (2 * fr) << (2 * fr), have = ~todo, n = 0, v = 0;
                r.skip(fr);
#pragma unroll 1
                for (; fr < NSLOT; ++fr) { mbar_wait(BAR_EMPTY(sb, r.slot), r.par); r.next(); }
                if (ph == XST - 1) CS(33);
                v = flag_get(lf);
                do {
                    while (ph == 2 && fr < FRCAP && mbar_test(BAR_EMPTY(sb, r.slot), r.par)) { ++fr; r.next(); }
                    SPIN_GUARD(n);
                    const bool ok = (int32_t)(v - target) >= 0;
                    v = flag_get(lf);
                    have |= __ballot_sync(0xffffffffu, ok);
                    const uint32_t go = have & todo & ((1u << (2 * fr)) - 1);
                    if ((go >> lane) & 1) {
                        if (!lw) mbar_expect_tx(lb, half);
                        tma_load(sb + ls * SLOT + lw * half, tm, lk, row0 + lw * 64, lb);
                    }
                    __syncwarp();
                    if (lane < 2 && (todo & (0x555u << lane)) && !(todo & ~go & (0x555u << lane))) mbar_arrive(BAR_ONE(sb, (lane ? EV_FGO : EV_AGO) + ph));
                    if (ph == XST - 1) { if (go & (1u << (2 << sh))) CS(34); if (go & (2u << (2 << sh))) CS(35); if (todo & 0x555u) CS(36); if (todo & 0xaaau) CS(37); }
                    todo &= ~go;
                } while (~have);
                if (ph == XST - 1) CS(38);
                int k = kof(fr, sh, j);
#pragma unroll 1
                for (; fr < nst; ++fr) {
                    if (fr == 9 || fr == 18) {
                        const uint32_t skip = fr == 9 << (sh - 1) ? 0 : ~0x01fc01fcu;
                        while (~(__ballot_sync(0xffffffffu, (int32_t)(flag_get(fl) - target) >= 0) | skip)) SPIN_GUARD(n);
                    }
                    const uint32_t st = sb + r.slot * SLOT, fb = BAR_FULL(sb, r.slot);
                    mbar_wait(BAR_EMPTY(sb, r.slot), r.par);
                    if (el) {
                        tma_load(st + half, tm, k, row0 + 64, fb);
                        mbar_expect_tx(fb + AF_REL, half);
                        tma_load(st, tm, k, row0, fb + AF_REL);
                    }
                    if (ph == XST - 1 && fr == 9) CS(39);
                    r.next();
                    k = kof(fr + 1, sh, j);
                }
            }
#pragma unroll 1
            for (int p = 0; p < 4; ++p) {
                const uint32_t* f = g_flags + (p < 3 ? FL_PROG + m * 32 + lane : FL_AUX + m * 2 + (lane & 1));
                uint32_t n = 0;
                while (!__all_sync(0xffffffffu, (int32_t)(flag_get(f) - (ep * 8 + ST_H + p)) >= 0)) { SPIN_GUARD(n); __nanosleep(300); }
                if (el) mbar_arrive(BAR_ONE(sb, EV_H0 + p));
                if (p == 0) gate(5, EV_GB);
            }
        } else {
            const uint32_t w = warp - 9;
            const int row0 = m * 128 + w * 64;
            const uint32_t stg = sb + OFF_STG + w * 16384;
            uint32_t* const fl = g_flags + FL_PROG + fidx(m, w, 2 * j);
            uint32_t b = 0, par = 0;
            const bool el = elect_one();
            auto store = [&](const CUtensorMap* tm, int col, bool nat = false) {
                mbar_wait(BAR_SFULL(sb, w * 2 + b), (par >> b) & 1);
                par ^= 1u << b;
                if (el) {
                    if (nat) tma_store3(tm, col, row0 >> 1, 0, stg + b * 8192); else tma_store(tm, col, row0, stg + b * 8192);
                    bulk_commit();
                }
                b ^= 1;
            };
            auto send2 = [&](const CUtensorMap* tm, const uint32_t* buf, int step) {
                const uint32_t* const q = buf + (size_t)((row0 + lane) * (D_ / 2) + j * 64 + 31);
                store(tm, j * 128);
                if (step == XST) CS(33);
                uint32_t z = landed(el, q, D_ / 2, pt.zero);
                if (el) flag_set(fl, ep * 8 + step + z);
                if (step == XST) CS(34);
                if (step != ST_O) { mbar_wait(BAR_ONE(sb, EV_FGO + step - ST_H1), 0); pause(step == ST_H1 ? (w ? P1H : P1H + 1000) : w ? P2L : P2F); }
                store(tm, j * 128 + 64);
                if (step == XST) CS(35);
                z = landed(el, q + 32, D_ / 2, pt.zero);
                if (el) flag_set(fl + 1, ep * 8 + step + z);
                if (step == XST) CS(36);
            };
            auto free2 = [&]() { if (el) { mbar_arrive(BAR_SREADY(sb, w * 2)); mbar_arrive(BAR_SREADY(sb, w * 2 + 1)); } };
            if (el) { prefetch_map(&mp.h1s); prefetch_map(&mp.o); prefetch_map(&mp.out); prefetch_map(&mp.wo); }
            send2(&mp.h1s, pt.h1, ST_H1);
            if (w == 0) TL(47);
            free2();
            mbar_wait(BAR_ONE(sb, EV_KV), 0);
            mbar_wait(BAR_SREADY(sb, 0), 1);
            fetch_halo<1>(g_halo + ((m - 1) * 8 + j) * 512 + w * 256 + lane, m == 0, sb + OFF_STG + w * 4096 + lane * 16, [&] { bar_arrive(NB_TAIL + 2 * w, 64); CS(38); });
            send2(&mp.o, pt.o, ST_O);
            if (w == 0) TL(40); else TL(38);
            free2();
            send2(&mp.o, pt.o, ST_H2);
            if (el) { prefetch_map(&mp.hbs); prefetch_map(&mp.hb3); }
            if (w == 0) TL(37);
            free2();
#pragma unroll 1
            for (int p = 0; p < 3; ++p) {
                const int col = hcol(p, j);
                mbar_wait2(BAR_SFULL(sb, w * 2), BAR_SFULL(sb, w * 2 + 1), par & 1);
                par ^= 3;
#pragma unroll 1
                for (int i = 0; i < (p ? 2 : 3) * NSPL; ++i) {
                    pause(i ? HP / NSPL : p == 2 ? (w ? HE1 : HE0) : w ? HD1 : HD0);
                    const int pn = i / NSPL, ro = (i % NSPL) * (64 / NSPL);
                    if (el) {
                        if (pn < 2) tma_store(&mp.hbs, col + pn * 64, row0 + ro, stg + i * (8192 / NSPL));
                        else tma_store3(&mp.hb3, 0, j, row0 + ro, sb + (w ? P3_SLOT1 : P3_SLOT0) * SLOT + 24576 + ro * 128);
                        bulk_commit();
                    }
                }
                if (el) bulk_wait_read();
                free2();
                if (el) { bulk_wait_fence(); flag_set(fl, ep * 8 + ST_H + p); flag_set(fl + 1, ep * 8 + ST_H + p); }
            }
            cluster_arrive_early = true;
            cluster_arrive();
            store(&mp.out, j * 128, true); store(&mp.out, j * 128 + 64, true);
            if (el) bulk_wait_read();
        }
        __syncwarp();
    }
    if (aux || (wg == 2 && !cluster_arrive_early)) cluster_arrive();
    cluster_wait();
    if (KDEBUG == 5) __syncthreads();
    if (tid == 0) {
        TL(15);
        flag_add(pt.mail->flags + FL_DONE);
    }
}

typedef CUresult (*EncodeFn)(CUtensorMap*, CUtensorMapDataType, cuuint32_t, void*, const cuuint64_t*, const cuuint64_t*, const cuuint32_t*,
                             const cuuint32_t*, CUtensorMapInterleave, CUtensorMapSwizzle, CUtensorMapL2promotion, CUtensorMapFloatOOBfill);

void make_map(EncodeFn fn, CUtensorMap* m, const void* ptr, uint64_t rows, uint64_t cols, uint32_t brows, uint32_t bcols) {
    cuuint64_t dims[2] = {cols, rows}, strides[1] = {cols * 2};
    cuuint32_t box[2] = {bcols, brows}, es[2] = {1, 1};
    fn(m, CU_TENSOR_MAP_DATA_TYPE_BFLOAT16, 2, (void*)ptr, dims, strides, box, es, CU_TENSOR_MAP_INTERLEAVE_NONE,
       bcols == 64 ? CU_TENSOR_MAP_SWIZZLE_128B : bcols == 32 ? CU_TENSOR_MAP_SWIZZLE_64B : CU_TENSOR_MAP_SWIZZLE_NONE, CU_TENSOR_MAP_L2_PROMOTION_L2_256B, CU_TENSOR_MAP_FLOAT_OOB_FILL_NONE);
}

void make_map3(EncodeFn fn, CUtensorMap* m, const void* ptr) {
    cuuint64_t dims[3] = {D_, S_ / 2, 2}, strides[2] = {4 * D_, 2 * D_};
    cuuint32_t box[3] = {64, 32, 2}, es[3] = {1, 1, 1};
    fn(m, CU_TENSOR_MAP_DATA_TYPE_BFLOAT16, 3, (void*)ptr, dims, strides, box, es, CU_TENSOR_MAP_INTERLEAVE_NONE,
       CU_TENSOR_MAP_SWIZZLE_128B, CU_TENSOR_MAP_L2_PROMOTION_L2_256B, CU_TENSOR_MAP_FLOAT_OOB_FILL_NONE);
}

void make_map48(EncodeFn fn, CUtensorMap* m, const void* ptr, uint64_t rows, uint32_t brows) {
    cuuint64_t dims[3] = {48, 8, rows}, strides[2] = {96, 2 * F_};
    cuuint32_t box[3] = {64, 1, brows}, es[3] = {1, 1, 1};
    fn(m, CU_TENSOR_MAP_DATA_TYPE_BFLOAT16, 3, (void*)ptr, dims, strides, box, es, CU_TENSOR_MAP_INTERLEAVE_NONE,
       CU_TENSOR_MAP_SWIZZLE_128B, CU_TENSOR_MAP_L2_PROMOTION_L2_256B, CU_TENSOR_MAP_FLOAT_OOB_FILL_NONE);
}

}

extern "C" void kernel_launch(void* const* d_in, const int* in_sizes, int n_in, void* d_out, int out_size) {
    (void)in_sizes; (void)n_in; (void)out_size;
    void* fnp = nullptr;
    cudaDriverEntryPointQueryResult qr;
    cudaGetDriverEntryPoint("cuTensorMapEncodeTiled", &fnp, cudaEnableDefault, &qr);
    EncodeFn fn = (EncodeFn)fnp;
    void *h1, *o, *h2, *hb, *mail;
    cudaGetSymbolAddress(&h1, g_h1);
    cudaGetSymbolAddress(&mail, g_mail);
    cudaGetSymbolAddress(&o, g_o);
    cudaGetSymbolAddress(&hb, g_hb);
    h2 = o;
    Maps mp;
    make_map(fn, &mp.h1h, h1, S_, D_, 64, 32);
    make_map(fn, &mp.h2h, h2, S_, D_, 64, 32);
    make_map(fn, &mp.h1s, h1, S_, D_, 64, 64);
    make_map(fn, &mp.o, o, S_, D_, 64, 64);
    make_map(fn, &mp.h2l, h2, S_, D_, 128, 32);
    make_map(fn, &mp.hb, hb, S_, F_, 64, 64);
    make_map(fn, &mp.wqkv, d_in[1], D_, 3 * D_, 32, 64);
    make_map(fn, &mp.wo, d_in[2], D_, D_, 64, 64);
    make_map(fn, &mp.wg, d_in[4], D_, F_, 32, 64);
    make_map(fn, &mp.wu, d_in[5], D_, F_, 32, 64);
    make_map(fn, &mp.wd, d_in[6], F_, D_, 64, 64);
    make_map(fn, &mp.wmod, d_in[8], D_, 6 * D_, 64, 64);
    make_map(fn, &mp.wm8, d_in[8], D_ / 8, 8 * 6 * D_, 128, 16);
    make_map3(fn, &mp.x, d_in[0]);
    make_map3(fn, &mp.out, d_out);
    make_map48(fn, &mp.wg3, d_in[4], D_, 32);
    make_map48(fn, &mp.wu3, d_in[5], D_, 32);
    make_map48(fn, &mp.hb3, hb, S_, 64 / NSPL);
    make_map(fn, &mp.hbs, hb, S_, F_, 64 / NSPL, 64);
    cudaFuncSetAttribute(fused_block_kernel, cudaFuncAttributeMaxDynamicSharedMemorySize, SMEM_BYTES);
    cudaLaunchConfig_t cfg = {};
    cfg.gridDim = dim3(NCTA); cfg.blockDim = dim3(384); cfg.dynamicSmemBytes = SMEM_BYTES; cfg.stream = cudaStreamPerThread;
    cudaLaunchAttribute at[1];
    at[0].id = cudaLaunchAttributeClusterDimension; at[0].val.clusterDim.x = 2; at[0].val.clusterDim.y = 1; at[0].val.clusterDim.z = 1;
    cfg.attrs = at; cfg.numAttrs = 1;
    const Ptrs pt{(const __nv_bfloat16*)d_in[7], (Mail*)mail, (const uint32_t*)h1, (const uint32_t*)o, 0};
    cudaLaunchKernelEx(&cfg, fused_block_kernel, pt, mp);
}
```

```cpp
#include <cuda_runtime.h>
#include <cuda_bf16.h>
#include <cuda.h>
#include <stdint.h>
#include <stddef.h>

#define LAG 4
#define LAGS 4
#define LAGW 2
#define LAGD 4
#define LAGQ 4
#define PUT1 5
#define PUT0 10
#define PUTD1 6
#define PUTD0 10
#define MIDD 40
#define HD1 3000
#define HD0 1500
#define NSPL 2
#define HE1 2000
#define HE0 HD0
#define HP 2600
#define P1H 3000
#define P2L 2000
#define P2F 3000
#define AUXD 4000
#define FD0 200
#define AG0 6
#define AG1 6
#define AG2 8
#define AGW 2
#define FRCAP 7
#define BW0 0
#define BWEV EV_WIN
#define BW1 3
#define LWAIT 3
#define PFWO 12
#define PFG 8
#define PFN 24
#define PFC 10
#define PFO 0
#define RACC 1
#define PADA 0
#define KDEBUG 0
#define CSW 0
#define XST ST_O

namespace {

constexpr int S_ = 2048, D_ = 1024, F_ = 3584;
constexpr int NCTA = 132;
constexpr int NSLOT = 6;
constexpr uint32_t SLOT = 32768;
constexpr uint32_t OFF_STG = NSLOT * SLOT;
constexpr uint32_t OFF_BAR = OFF_STG + 32768;
constexpr uint32_t OFF_PAR = OFF_BAR + 512;
constexpr uint32_t OFF_TAB = OFF_PAR + 768;
constexpr uint32_t OFF_TL = OFF_PAR + 2048;
constexpr uint32_t SMEM_BYTES = OFF_TL + (KDEBUG ? 512 : 0);
constexpr uint32_t P3_SLOT1 = (32 + 16 + 32) % NSLOT, P3_SLOT0 = (P3_SLOT1 + 1) % NSLOT;

constexpr int ST_H1 = 1, ST_O = 2, ST_H2 = 3, ST_H = 4, FL_DONE = 0, FL_LN2 = 1, FL_AUX = 32, FL_PROG = 64;

struct Maps {
    CUtensorMap h1h, h1s, o, h2h, h2l, hb, wqkv, wo, wg, wu, wd, wmod, wm8, x, out, wg3, wu3, hb3, hbs;
};

struct Mail {
    uint32_t flags[16 * 32 + 64];
    uint2 mod[6 * D_ / 2];
    uint4 mod1[8 * 512];
    uint4 st1[128 * 512];
    uint32_t par2[D_];
    uint4 halo[128 * 512];
};
struct Ptrs { const __nv_bfloat16* c; Mail* mail; const uint32_t *h1, *o; uint32_t zero; };

__device__ __align__(128) Mail g_mail;
__device__ __align__(128) __nv_bfloat16 g_h1[S_ * D_];
__device__ __align__(128) __nv_bfloat16 g_o[S_ * D_];
__device__ __align__(128) __nv_bfloat16 g_hb[S_ * F_];
#define TL(i) do {} while (0)
#define TC(i) do {} while (0)
#define TS(g, which) do {} while (0)
#define CS(i) do {} while (0)

__device__ __forceinline__ uint32_t smem_u32(const void* p) { return (uint32_t)__cvta_generic_to_shared(p); }
__device__ __forceinline__ void mbar_init(uint32_t bar, uint32_t cnt) { asm volatile("mbarrier.init.shared::cta.b64 [%0], %1;" :: "r"(bar), "r"(cnt) : "memory"); }
__device__ __forceinline__ void mbar_expect_tx(uint32_t bar, uint32_t bytes) { asm volatile("mbarrier.arrive.expect_tx.shared::cta.b64 _, [%0], %1;" :: "r"(bar), "r"(bytes) : "memory"); }
__device__ __forceinline__ void mbar_arrive(uint32_t bar) { asm volatile("mbarrier.arrive.shared::cta.b64 _, [%0];" :: "r"(bar) : "memory"); }
__device__ __forceinline__ void mbar_arrive_cta(uint32_t bar, uint32_t cta) {
    asm volatile("{\n.reg .b32 r;\nmapa.shared::cluster.u32 r, %0, %1;\nmbarrier.arrive.shared::cluster.b64 _, [r];\n}" :: "r"(bar), "r"(cta) : "memory");
}
__device__ __forceinline__ void mbar_wait(uint32_t bar, uint32_t parity) {
    asm volatile("{\n.reg .pred p;\n.reg .u32 n;\nmov.u32 n, 0;\n"
        "W_LOOP:\nmbarrier.try_wait.parity.shared::cta.b64 p, [%0], %1;\n@p bra W_DONE;\n"
        "add.u32 n, n, 1;\nsetp.lt.u32 p, n, 0x400000;\n@p bra W_LOOP;\ntrap;\nW_DONE:\n}" :: "r"(bar), "r"(parity) : "memory");
}
__device__ __forceinline__ void mbar_wait2(uint32_t b0, uint32_t b1, uint32_t parity) {
    asm volatile("{\n.reg .pred p, q;\n.reg .u32 n;\nmov.u32 n, 0;\n"
        "W_LOOP:\nmbarrier.try_wait.parity.shared::cta.b64 p, [%0], %2;\nmbarrier.try_wait.parity.shared::cta.b64 q, [%1], %2;\nand.pred p, p, q;\n@p bra W_DONE;\n"
        "add.u32 n, n, 1;\nsetp.lt.u32 p, n, 0x400000;\n@p bra W_LOOP;\ntrap;\nW_DONE:\n}" :: "r"(b0), "r"(b1), "r"(parity) : "memory");
}
__device__ __forceinline__ bool mbar_test(uint32_t bar, uint32_t parity) {
    uint32_t r; asm volatile("{\n.reg .pred p;\nmbarrier.test_wait.parity.shared::cta.b64 p, [%1], %2;\nselp.u32 %0, 1, 0, p;\n}" : "=r"(r) : "r"(bar), "r"(parity) : "memory"); return r;
}
__device__ __forceinline__ bool mbar_test2(uint32_t b0, uint32_t b1, uint32_t parity) {
    uint32_t r;
    asm volatile("{\n.reg .pred p, q;\nmbarrier.test_wait.parity.shared::cta.b64 p, [%1], %3;\nmbarrier.test_wait.parity.shared::cta.b64 q, [%2], %3;\n"
        "and.pred p, p, q;\nselp.u32 %0, 1, 0, p;\n}" : "=r"(r) : "r"(b0), "r"(b1), "r"(parity) : "memory");
    return r;
}
__device__ __forceinline__ void tma_load3(uint32_t dst, const CUtensorMap* m, int c0, int c1, uint32_t bar) {
    asm volatile("cp.async.bulk.tensor.3d.shared::cluster.global.mbarrier::complete_tx::bytes [%0], [%1, {%3, %4, %5}], [%2];"
        :: "r"(dst), "l"(m), "r"(bar), "r"(c0), "r"(c1), "r"(0) : "memory");
}
__device__ __forceinline__ void tma_store3(const CUtensorMap* m, int c0, int c1, int c2, uint32_t src) {
    asm volatile("cp.async.bulk.tensor.3d.global.shared::cta.bulk_group [%0, {%2, %3, %4}], [%1];" :: "l"(m), "r"(src), "r"(c0), "r"(c1), "r"(c2) : "memory");
}
__device__ __forceinline__ void tma_load3_mc(uint32_t dst, const CUtensorMap* m, int c1, int c2, uint32_t bar) {
    asm volatile("cp.async.bulk.tensor.3d.shared::cluster.global.mbarrier::complete_tx::bytes.multicast::cluster.L2::cache_hint [%0], [%1, {%3, %4, %5}], [%2], %6, %7;"
        :: "r"(dst), "l"(m), "r"(bar), "r"(0), "r"(c1), "r"(c2), "h"((uint16_t)3), "l"(0x12F0000000000000ull) : "memory");
}
__device__ __forceinline__ void tma_load(uint32_t dst, const CUtensorMap* m, int c0, int c1, uint32_t bar) {
    asm volatile("cp.async.bulk.tensor.2d.shared::cluster.global.mbarrier::complete_tx::bytes [%0], [%1, {%3, %4}], [%2];"
        :: "r"(dst), "l"(m), "r"(bar), "r"(c0), "r"(c1) : "memory");
}
__device__ __forceinline__ void tma_load_ef(uint32_t dst, const CUtensorMap* m, int c0, int c1, uint32_t bar) {
    asm volatile("cp.async.bulk.tensor.2d.shared::cluster.global.mbarrier::complete_tx::bytes.L2::cache_hint [%0], [%1, {%3, %4}], [%2], %5;"
        :: "r"(dst), "l"(m), "r"(bar), "r"(c0), "r"(c1), "l"(0x12F0000000000000ull) : "memory");
}
__device__ __forceinline__ void tma_load_mc(uint32_t dst, const CUtensorMap* m, int c0, int c1, uint32_t bar) {
    asm volatile("cp.async.bulk.tensor.2d.shared::cluster.global.mbarrier::complete_tx::bytes.multicast::cluster.L2::cache_hint [%0], [%1, {%3, %4}], [%2], %5, %6;"
        :: "r"(dst), "l"(m), "r"(bar), "r"(c0), "r"(c1), "h"((uint16_t)3), "l"(0x12F0000000000000ull) : "memory");
}
__device__ __forceinline__ void tma_prefetch(const CUtensorMap* m, int c0, int c1) {
    asm volatile("cp.async.bulk.prefetch.tensor.2d.L2.global [%0, {%1, %2}];" :: "l"(m), "r"(c0), "r"(c1) : "memory");
}
__device__ __forceinline__ void tma_store(const CUtensorMap* m, int c0, int c1, uint32_t src) {
    asm volatile("cp.async.bulk.tensor.2d.global.shared::cta.bulk_group [%0, {%2, %3}], [%1];" :: "l"(m), "r"(src), "r"(c0), "r"(c1) : "memory");
}
__device__ __forceinline__ void bulk_commit() { asm volatile("cp.async.bulk.commit_group;" ::: "memory"); }
__device__ __forceinline__ void bulk_wait_read() { asm volatile("cp.async.bulk.wait_group.read 0;" ::: "memory"); }
__device__ __forceinline__ void fence_async_smem() { asm volatile("fence.proxy.async.shared::cta;" ::: "memory"); }
__device__ __forceinline__ void prefetch_map(const CUtensorMap* m) { asm volatile("prefetch.tensormap [%0];" :: "l"(m) : "memory"); }
__device__ __forceinline__ void wg_fence() { asm volatile("wgmma.fence.sync.aligned;" ::: "memory"); }
__device__ __forceinline__ void wg_commit() { asm volatile("wgmma.commit_group.sync.aligned;" ::: "memory"); }
template <int N> __device__ __forceinline__ void wg_wait() { asm volatile("wgmma.wait_group.sync.aligned %0;" :: "n"(N) : "memory"); }
__device__ __forceinline__ void bar_sync(int id, int n) { asm volatile("bar.sync %0, %1;" :: "r"(id), "r"(n) : "memory"); }
__device__ __forceinline__ void bar_arrive(int id, int n) { asm volatile("bar.arrive %0, %1;" :: "r"(id), "r"(n) : "memory"); }
__device__ __forceinline__ void flag_add(uint32_t* f) { asm volatile("red.relaxed.gpu.global.add.u32 [%0], 1;" :: "l"(f) : "memory"); }
__device__ __forceinline__ void flag_set(uint32_t* f, uint32_t v) { asm volatile("red.relaxed.gpu.global.max.u32 [%0], %1;" :: "l"(f), "r"(v) : "memory"); }
__device__ __forceinline__ uint32_t flag_get(const uint32_t* f) { uint32_t v; asm volatile("ld.relaxed.gpu.global.u32 %0, [%1];" : "=r"(v) : "l"(f) : "memory"); return v; }
__device__ __forceinline__ void bulk_wait_fence() { asm volatile("cp.async.bulk.wait_group 0;\nfence.proxy.async.global;\nfence.acq_rel.gpu;" ::: "memory"); }
__device__ __forceinline__ uint32_t landed(bool el, const uint32_t* p, uint32_t pitch, uint32_t zero) {
    if (el) asm volatile("cp.async.bulk.wait_group 0;" ::: "memory");
    __syncwarp();
    const uint32_t a = flag_get(p), b = flag_get(p + 32 * pitch);
    return __reduce_or_sync(0xffffffffu, (a | b) & zero);
}
__device__ __forceinline__ uint32_t d16(uint32_t addr) { return (addr & 0x3FFFF) >> 4; }
__device__ __forceinline__ uint64_t mk_desc(uint32_t a16, uint32_t off, uint32_t lbo, uint32_t sbo, uint32_t swz) {
    const uint32_t lo = a16 + (off >> 4) + ((lbo >> 4) << 16), hi = (sbo >> 4) | (swz << 30);
    return ((uint64_t)hi << 32) | lo;
}
__device__ __forceinline__ uint32_t pack2(float lo, float hi) {
    uint32_t r; asm("cvt.rn.bf16x2.f32 %0, %1, %2;" : "=r"(r) : "f"(hi), "f"(lo)); return r;
}
__device__ __forceinline__ uint32_t hfma2_bf16(uint32_t a, uint32_t b, uint32_t c) {
    uint32_t r; asm("fma.rn.bf16x2 %0, %1, %2, %3;" : "=r"(r) : "r"(a), "r"(b), "r"(c)); return r;
}
__device__ __forceinline__ float bf_lo(uint32_t v) { return __uint_as_float(v << 16); }
__device__ __forceinline__ float bf_hi(uint32_t v) { return __uint_as_float(v & 0xFFFF0000u); }
__device__ __forceinline__ void unpack2(uint32_t v, float& lo, float& hi) {
    asm volatile("shl.b32 %0, %2, 16;\nand.b32 %1, %2, 0xffff0000;" : "=f"(lo), "=f"(hi) : "r"(v));
}
__device__ __forceinline__ float bf_round(float x) { return __bfloat162float(__float2bfloat16_rn(x)); }
__device__ __forceinline__ void stsm4(uint32_t addr, uint32_t r0, uint32_t r1, uint32_t r2, uint32_t r3) {
    asm volatile("stmatrix.sync.aligned.m8n8.x4.shared.b16 [%0], {%1, %2, %3, %4};" :: "r"(addr), "r"(r0), "r"(r1), "r"(r2), "r"(r3) : "memory");
}
__device__ __forceinline__ void stsm4t(uint32_t addr, uint32_t r0, uint32_t r1, uint32_t r2, uint32_t r3) {
    asm volatile("stmatrix.sync.aligned.m8n8.x4.trans.shared.b16 [%0], {%1, %2, %3, %4};" :: "r"(addr), "r"(r0), "r"(r1), "r"(r2), "r"(r3) : "memory");
}
__device__ __forceinline__ uint32_t movm(uint32_t a) { uint32_t d; asm volatile("movmatrix.sync.aligned.m8n8.trans.b16 %0, %1;" : "=r"(d) : "r"(a)); return d; }
__device__ __forceinline__ void ldsm4(uint32_t addr, uint32_t& r0, uint32_t& r1, uint32_t& r2, uint32_t& r3) {
    asm volatile("ldmatrix.sync.aligned.m8n8.x4.shared.b16 {%0, %1, %2, %3}, [%4];" : "=r"(r0), "=r"(r1), "=r"(r2), "=r"(r3) : "r"(addr) : "memory");
}
__device__ __forceinline__ void ldsm4t(uint32_t addr, uint32_t& r0, uint32_t& r1, uint32_t& r2, uint32_t& r3) {
    asm volatile("ldmatrix.sync.aligned.m8n8.x4.trans.shared.b16 {%0, %1, %2, %3}, [%4];" : "=r"(r0), "=r"(r1), "=r"(r2), "=r"(r3) : "r"(addr) : "memory");
}
__device__ __forceinline__ void mma16816(float (&c)[4], uint32_t a0, uint32_t a1, uint32_t a2, uint32_t a3, uint32_t b0, uint32_t b1) {
    asm("mma.sync.aligned.m16n8k16.row.col.f32.bf16.bf16.f32 {%0, %1, %2, %3}, {%4, %5, %6, %7}, {%8, %9}, {%0, %1, %2, %3};"
        : "+f"(c[0]), "+f"(c[1]), "+f"(c[2]), "+f"(c[3]) : "r"(a0), "r"(a1), "r"(a2), "r"(a3), "r"(b0), "r"(b1));
}
__device__ __forceinline__ float rsq(float x) { float r; asm("rsqrt.approx.ftz.f32 %0, %1;" : "=f"(r) : "f"(x)); return r; }
__device__ __forceinline__ float rcp(float x) { float r; asm("rcp.approx.ftz.f32 %0, %1;" : "=f"(r) : "f"(x)); return r; }
__device__ __forceinline__ float ex2(float x) { float r; asm("ex2.approx.ftz.f32 %0, %1;" : "=f"(r) : "f"(x)); return r; }
__device__ __forceinline__ float tanh_(float x) { float t; asm("tanh.approx.f32 %0, %1;" : "=f"(t) : "f"(x)); return t; }
__device__ __forceinline__ void block_end(uint32_t opaque, uint32_t id) { asm volatile("{\n.reg .pred p;\nsetp.eq.u32 p, %0, %1;\n@p trap;\n}" :: "r"(opaque), "r"(0xffffff00u + id)); }
__device__ __forceinline__ float silu_(float x) { return __fdividef(x, 1.f + __expf(-x)); }
__device__ __forceinline__ void st_pkt(void* p, uint32_t a, uint32_t b) {
    asm volatile("{\n.reg .b64 t;\nmov.b64 t, {%1, %2};\nst.relaxed.gpu.global.b64 [%0], t;\n}" :: "l"(p), "r"(a), "r"(b) : "memory");
}
__device__ __forceinline__ uint4 ld_pkt2(const void* p) {
    uint4 v; asm volatile("{\n.reg .b64 t, u;\nld.relaxed.gpu.global.v2.b64 {t, u}, [%4];\nmov.b64 {%0, %1}, t;\nmov.b64 {%2, %3}, u;\n}"
        : "=r"(v.x), "=r"(v.y), "=r"(v.z), "=r"(v.w) : "l"(p) : "memory"); return v;
}
__device__ __forceinline__ void st_pkt16(void* p, uint32_t a, uint32_t b, uint32_t c, uint32_t d) {
    asm volatile("{\n.reg .b64 t, u;\n.reg .b128 w;\nmov.b64 t, {%1, %2};\nmov.b64 u, {%3, %4};\nmov.b128 w, {t, u};\nst.relaxed.gpu.global.b128 [%0], w;\n}"
        :: "l"(p), "r"(a), "r"(b), "r"(c), "r"(d) : "memory");
}
__device__ __forceinline__ uint4 ld_pkt16(const void* p) {
    uint4 v; asm volatile("{\n.reg .b64 t, u;\n.reg .b128 w;\nld.relaxed.gpu.global.b128 w, [%4];\nmov.b128 {t, u}, w;\nmov.b64 {%0, %1}, t;\nmov.b64 {%2, %3}, u;\n}"
        : "=r"(v.x), "=r"(v.y), "=r"(v.z), "=r"(v.w) : "l"(p) : "memory"); return v;
}
#define SPIN_GUARD(n) do { if (++(n) > (1u << 22)) asm volatile("trap;"); } while (0)
__device__ __forceinline__ uint4 lds128(uint32_t a) { uint4 v; asm volatile("ld.shared.v4.u32 {%0, %1, %2, %3}, [%4];" : "=r"(v.x), "=r"(v.y), "=r"(v.z), "=r"(v.w) : "r"(a) : "memory"); return v; }
__device__ __forceinline__ void sts128(uint32_t a, uint32_t x, uint32_t y, uint32_t z, uint32_t w) { asm volatile("st.shared.v4.u32 [%0], {%1, %2, %3, %4};" :: "r"(a), "r"(x), "r"(y), "r"(z), "r"(w) : "memory"); }
__device__ __forceinline__ uint32_t lds32(uint32_t a) { uint32_t v; asm volatile("ld.shared.u32 %0, [%1];" : "=r"(v) : "r"(a) : "memory"); return v; }
__device__ __forceinline__ void sts32(uint32_t a, uint32_t v) { asm volatile("st.shared.u32 [%0], %1;" :: "r"(a), "r"(v) : "memory"); }
__device__ __forceinline__ bool elect_one() {
    uint32_t p; asm volatile("{\n.reg .pred q;\nelect.sync _|q, 0xffffffff;\nselp.u32 %0, 1, 0, q;\n}" : "=r"(p)); return p;
}
__device__ __forceinline__ void pause(uint32_t cycles) {
    uint32_t t0, t; asm volatile("mov.u32 %0, %%clock;" : "=r"(t0));
    do { __nanosleep(64); asm volatile("mov.u32 %0, %%clock;" : "=r"(t)); } while (t - t0 < cycles);
}
__device__ __forceinline__ void cluster_arrive() { asm volatile("barrier.cluster.arrive.relaxed.aligned;" ::: "memory"); }
__device__ __forceinline__ void cluster_wait() { asm volatile("barrier.cluster.wait.aligned;" ::: "memory"); }

__device__ __forceinline__ void wgmma_n128_z(float (&d)[64], uint64_t da, uint64_t db) {
    asm volatile("{\n.reg .pred p;\nsetp.ne.b32 p, 0, 0;\n"
        "wgmma.mma_async.sync.aligned.m64n128k16.f32.bf16.bf16 {"
        "%0, %1, %2, %3, %4, %5, %6, %7, %8, %9, %10, %11, %12, %13, %14, %15, "
        "%16, %17, %18, %19, %20, %21, %22, %23, %24, %25, %26, %27, %28, %29, %30, %31, "
        "%32, %33, %34, %35, %36, %37, %38, %39, %40, %41, %42, %43, %44, %45, %46, %47, "
        "%48, %49, %50, %51, %52, %53, %54, %55, %56, %57, %58, %59, %60, %61, %62, %63"
        "}, %64, %65, p, 1, 1, 0, 1;\n}\n"
        : "=f"(d[0]), "=f"(d[1]), "=f"(d[2]), "=f"(d[3]), "=f"(d[4]), "=f"(d[5]), "=f"(d[6]), "=f"(d[7]),
          "=f"(d[8]), "=f"(d[9]), "=f"(d[10]), "=f"(d[11]), "=f"(d[12]), "=f"(d[13]), "=f"(d[14]), "=f"(d[15]),
          "=f"(d[16]), "=f"(d[17]), "=f"(d[18]), "=f"(d[19]), "=f"(d[20]), "=f"(d[21]), "=f"(d[22]), "=f"(d[23]),
          "=f"(d[24]), "=f"(d[25]), "=f"(d[26]), "=f"(d[27]), "=f"(d[28]), "=f"(d[29]), "=f"(d[30]), "=f"(d[31]),
          "=f"(d[32]), "=f"(d[33]), "=f"(d[34]), "=f"(d[35]), "=f"(d[36]), "=f"(d[37]), "=f"(d[38]), "=f"(d[39]),
          "=f"(d[40]), "=f"(d[41]), "=f"(d[42]), "=f"(d[43]), "=f"(d[44]), "=f"(d[45]), "=f"(d[46]), "=f"(d[47]),
          "=f"(d[48]), "=f"(d[49]), "=f"(d[50]), "=f"(d[51]), "=f"(d[52]), "=f"(d[53]), "=f"(d[54]), "=f"(d[55]),
          "=f"(d[56]), "=f"(d[57]), "=f"(d[58]), "=f"(d[59]), "=f"(d[60]), "=f"(d[61]), "=f"(d[62]), "=f"(d[63])
        : "l"(da), "l"(db));
}
__device__ __forceinline__ void wgmma_n128(float (&d)[64], uint64_t da, uint64_t db) {
    asm volatile("{\n.reg .pred p;\nsetp.eq.b32 p, 0, 0;\n"
        "wgmma.mma_async.sync.aligned.m64n128k16.f32.bf16.bf16 {"
        "%0, %1, %2, %3, %4, %5, %6, %7, %8, %9, %10, %11, %12, %13, %14, %15, "
        "%16, %17, %18, %19, %20, %21, %22, %23, %24, %25, %26, %27, %28, %29, %30, %31, "
        "%32, %33, %34, %35, %36, %37, %38, %39, %40, %41, %42, %43, %44, %45, %46, %47, "
        "%48, %49, %50, %51, %52, %53, %54, %55, %56, %57, %58, %59, %60, %61, %62, %63"
        "}, %64, %65, p, 1, 1, 0, 1;\n}\n"
        : "+f"(d[0]), "+f"(d[1]), "+f"(d[2]), "+f"(d[3]), "+f"(d[4]), "+f"(d[5]), "+f"(d[6]), "+f"(d[7]),
          "+f"(d[8]), "+f"(d[9]), "+f"(d[10]), "+f"(d[11]), "+f"(d[12]), "+f"(d[13]), "+f"(d[14]), "+f"(d[15]),
          "+f"(d[16]), "+f"(d[17]), "+f"(d[18]), "+f"(d[19]), "+f"(d[20]), "+f"(d[21]), "+f"(d[22]), "+f"(d[23]),
          "+f"(d[24]), "+f"(d[25]), "+f"(d[26]), "+f"(d[27]), "+f"(d[28]), "+f"(d[29]), "+f"(d[30]), "+f"(d[31]),
          "+f"(d[32]), "+f"(d[33]), "+f"(d[34]), "+f"(d[35]), "+f"(d[36]), "+f"(d[37]), "+f"(d[38]), "+f"(d[39]),
          "+f"(d[40]), "+f"(d[41]), "+f"(d[42]), "+f"(d[43]), "+f"(d[44]), "+f"(d[45]), "+f"(d[46]), "+f"(d[47]),
          "+f"(d[48]), "+f"(d[49]), "+f"(d[50]), "+f"(d[51]), "+f"(d[52]), "+f"(d[53]), "+f"(d[54]), "+f"(d[55]),
          "+f"(d[56]), "+f"(d[57]), "+f"(d[58]), "+f"(d[59]), "+f"(d[60]), "+f"(d[61]), "+f"(d[62]), "+f"(d[63])
        : "l"(da), "l"(db));
}
__device__ __forceinline__ void wgmma_n176_z(float (&d)[88], uint64_t da, uint64_t db) {
    asm volatile("{\n.reg .pred p;\nsetp.ne.b32 p, 0, 0;\n"
        "wgmma.mma_async.sync.aligned.m64n176k16.f32.bf16.bf16 {"
        "%0, %1, %2, %3, %4, %5, %6, %7, %8, %9, %10, %11, %12, %13, %14, %15, "
        "%16, %17, %18, %19, %20, %21, %22, %23, %24, %25, %26, %27, %28, %29, %30, %31, "
        "%32, %33, %34, %35, %36, %37, %38, %39, %40, %41, %42, %43, %44, %45, %46, %47, "
        "%48, %49, %50, %51, %52, %53, %54, %55, %56, %57, %58, %59, %60, %61, %62, %63, "
        "%64, %65, %66, %67, %68, %69, %70, %71, %72, %73, %74, %75, %76, %77, %78, %79, "
        "%80, %81, %82, %83, %84, %85, %86, %87"
        "}, %88, %89, p, 1, 1, 0, 1;\n}\n"
        : "=f"(d[0]), "=f"(d[1]), "=f"(d[2]), "=f"(d[3]), "=f"(d[4]), "=f"(d[5]), "=f"(d[6]), "=f"(d[7]),
          "=f"(d[8]), "=f"(d[9]), "=f"(d[10]), "=f"(d[11]), "=f"(d[12]), "=f"(d[13]), "=f"(d[14]), "=f"(d[15]),
          "=f"(d[16]), "=f"(d[17]), "=f"(d[18]), "=f"(d[19]), "=f"(d[20]), "=f"(d[21]), "=f"(d[22]), "=f"(d[23]),
          "=f"(d[24]), "=f"(d[25]), "=f"(d[26]), "=f"(d[27]), "=f"(d[28]), "=f"(d[29]), "=f"(d[30]), "=f"(d[31]),
          "=f"(d[32]), "=f"(d[33]), "=f"(d[34]), "=f"(d[35]), "=f"(d[36]), "=f"(d[37]), "=f"(d[38]), "=f"(d[39]),
          "=f"(d[40]), "=f"(d[41]), "=f"(d[42]), "=f"(d[43]), "=f"(d[44]), "=f"(d[45]), "=f"(d[46]), "=f"(d[47]),
          "=f"(d[48]), "=f"(d[49]), "=f"(d[50]), "=f"(d[51]), "=f"(d[52]), "=f"(d[53]), "=f"(d[54]), "=f"(d[55]),
          "=f"(d[56]), "=f"(d[57]), "=f"(d[58]), "=f"(d[59]), "=f"(d[60]), "=f"(d[61]), "=f"(d[62]), "=f"(d[63]),
          "=f"(d[64]), "=f"(d[65]), "=f"(d[66]), "=f"(d[67]), "=f"(d[68]), "=f"(d[69]), "=f"(d[70]), "=f"(d[71]),
          "=f"(d[72]), "=f"(d[73]), "=f"(d[74]), "=f"(d[75]), "=f"(d[76]), "=f"(d[77]), "=f"(d[78]), "=f"(d[79]),
          "=f"(d[80]), "=f"(d[81]), "=f"(d[82]), "=f"(d[83]), "=f"(d[84]), "=f"(d[85]), "=f"(d[86]), "=f"(d[87])
        : "l"(da), "l"(db));
}
__device__ __forceinline__ void wgmma_n176(float (&d)[88], uint64_t da, uint64_t db) {
    asm volatile("{\n.reg .pred p;\nsetp.eq.b32 p, 0, 0;\n"
        "wgmma.mma_async.sync.aligned.m64n176k16.f32.bf16.bf16 {"
        "%0, %1, %2, %3, %4, %5, %6, %7, %8, %9, %10, %11, %12, %13, %14, %15, "
        "%16, %17, %18, %19, %20, %21, %22, %23, %24, %25, %26, %27, %28, %29, %30, %31, "
        "%32, %33, %34, %35, %36, %37, %38, %39, %40, %41, %42, %43, %44, %45, %46, %47, "
        "%48, %49, %50, %51, %52, %53, %54, %55, %56, %57, %58, %59, %60, %61, %62, %63, "
        "%64, %65, %66, %67, %68, %69, %70, %71, %72, %73, %74, %75, %76, %77, %78, %79, "
        "%80, %81, %82, %83, %84, %85, %86, %87"
        "}, %88, %89, p, 1, 1, 0, 1;\n}\n"
        : "+f"(d[0]), "+f"(d[1]), "+f"(d[2]), "+f"(d[3]), "+f"(d[4]), "+f"(d[5]), "+f"(d[6]), "+f"(d[7]),
          "+f"(d[8]), "+f"(d[9]), "+f"(d[10]), "+f"(d[11]), "+f"(d[12]), "+f"(d[13]), "+f"(d[14]), "+f"(d[15]),
          "+f"(d[16]), "+f"(d[17]), "+f"(d[18]), "+f"(d[19]), "+f"(d[20]), "+f"(d[21]), "+f"(d[22]), "+f"(d[23]),
          "+f"(d[24]), "+f"(d[25]), "+f"(d[26]), "+f"(d[27]), "+f"(d[28]), "+f"(d[29]), "+f"(d[30]), "+f"(d[31]),
          "+f"(d[32]), "+f"(d[33]), "+f"(d[34]), "+f"(d[35]), "+f"(d[36]), "+f"(d[37]), "+f"(d[38]), "+f"(d[39]),
          "+f"(d[40]), "+f"(d[41]), "+f"(d[42]), "+f"(d[43]), "+f"(d[44]), "+f"(d[45]), "+f"(d[46]), "+f"(d[47]),
          "+f"(d[48]), "+f"(d[49]), "+f"(d[50]), "+f"(d[51]), "+f"(d[52]), "+f"(d[53]), "+f"(d[54]), "+f"(d[55]),
          "+f"(d[56]), "+f"(d[57]), "+f"(d[58]), "+f"(d[59]), "+f"(d[60]), "+f"(d[61]), "+f"(d[62]), "+f"(d[63]),
          "+f"(d[64]), "+f"(d[65]), "+f"(d[66]), "+f"(d[67]), "+f"(d[68]), "+f"(d[69]), "+f"(d[70]), "+f"(d[71]),
          "+f"(d[72]), "+f"(d[73]), "+f"(d[74]), "+f"(d[75]), "+f"(d[76]), "+f"(d[77]), "+f"(d[78]), "+f"(d[79]),
          "+f"(d[80]), "+f"(d[81]), "+f"(d[82]), "+f"(d[83]), "+f"(d[84]), "+f"(d[85]), "+f"(d[86]), "+f"(d[87])
        : "l"(da), "l"(db));
}
__device__ __forceinline__ void wgmma_n256_z(float (&d)[128], uint64_t da, uint64_t db) {
    asm volatile("{\n.reg .pred p;\nsetp.ne.b32 p, 0, 0;\n"
        "wgmma.mma_async.sync.aligned.m64n256k16.f32.bf16.bf16 {"
        "%0, %1, %2, %3, %4, %5, %6, %7, %8, %9, %10, %11, %12, %13, %14, %15, "
        "%16, %17, %18, %19, %20, %21, %22, %23, %24, %25, %26, %27, %28, %29, %30, %31, "
        "%32, %33, %34, %35, %36, %37, %38, %39, %40, %41, %42, %43, %44, %45, %46, %47, "
        "%48, %49, %50, %51, %52, %53, %54, %55, %56, %57, %58, %59, %60, %61, %62, %63, "
        "%64, %65, %66, %67, %68, %69, %70, %71, %72, %73, %74, %75, %76, %77, %78, %79, "
        "%80, %81, %82, %83, %84, %85, %86, %87, %88, %89, %90, %91, %92, %93, %94, %95, "
        "%96, %97, %98, %99, %100, %101, %102, %103, %104, %105, %106, %107, %108, %109, %110, %111, "
        "%112, %113, %114, %115, %116, %117, %118, %119, %120, %121, %122, %123, %124, %125, %126, %127"
        "}, %128, %129, p, 1, 1, 0, 1;\n}\n"
        : "=f"(d[0]), "=f"(d[1]), "=f"(d[2]), "=f"(d[3]), "=f"(d[4]), "=f"(d[5]), "=f"(d[6]), "=f"(d[7]),
          "=f"(d[8]), "=f"(d[9]), "=f"(d[10]), "=f"(d[11]), "=f"(d[12]), "=f"(d[13]), "=f"(d[14]), "=f"(d[15]),
          "=f"(d[16]), "=f"(d[17]), "=f"(d[18]), "=f"(d[19]), "=f"(d[20]), "=f"(d[21]), "=f"(d[22]), "=f"(d[23]),
          "=f"(d[24]), "=f"(d[25]), "=f"(d[26]), "=f"(d[27]), "=f"(d[28]), "=f"(d[29]), "=f"(d[30]), "=f"(d[31]),
          "=f"(d[32]), "=f"(d[33]), "=f"(d[34]), "=f"(d[35]), "=f"(d[36]), "=f"(d[37]), "=f"(d[38]), "=f"(d[39]),
          "=f"(d[40]), "=f"(d[41]), "=f"(d[42]), "=f"(d[43]), "=f"(d[44]), "=f"(d[45]), "=f"(d[46]), "=f"(d[47]),
          "=f"(d[48]), "=f"(d[49]), "=f"(d[50]), "=f"(d[51]), "=f"(d[52]), "=f"(d[53]), "=f"(d[54]), "=f"(d[55]),
          "=f"(d[56]), "=f"(d[57]), "=f"(d[58]), "=f"(d[59]), "=f"(d[60]), "=f"(d[61]), "=f"(d[62]), "=f"(d[63]),
          "=f"(d[64]), "=f"(d[65]), "=f"(d[66]), "=f"(d[67]), "=f"(d[68]), "=f"(d[69]), "=f"(d[70]), "=f"(d[71]),
          "=f"(d[72]), "=f"(d[73]), "=f"(d[74]), "=f"(d[75]), "=f"(d[76]), "=f"(d[77]), "=f"(d[78]), "=f"(d[79]),
          "=f"(d[80]), "=f"(d[81]), "=f"(d[82]), "=f"(d[83]), "=f"(d[84]), "=f"(d[85]), "=f"(d[86]), "=f"(d[87]),
          "=f"(d[88]), "=f"(d[89]), "=f"(d[90]), "=f"(d[91]), "=f"(d[92]), "=f"(d[93]), "=f"(d[94]), "=f"(d[95]),
          "=f"(d[96]), "=f"(d[97]), "=f"(d[98]), "=f"(d[99]), "=f"(d[100]), "=f"(d[101]), "=f"(d[102]), "=f"(d[103]),
          "=f"(d[104]), "=f"(d[105]), "=f"(d[106]), "=f"(d[107]), "=f"(d[108]), "=f"(d[109]), "=f"(d[110]), "=f"(d[111]),
          "=f"(d[112]), "=f"(d[113]), "=f"(d[114]), "=f"(d[115]), "=f"(d[116]), "=f"(d[117]), "=f"(d[118]), "=f"(d[119]),
          "=f"(d[120]), "=f"(d[121]), "=f"(d[122]), "=f"(d[123]), "=f"(d[124]), "=f"(d[125]), "=f"(d[126]), "=f"(d[127])
        : "l"(da), "l"(db));
}
__device__ __forceinline__ void wgmma_n256(float (&d)[128], uint64_t da, uint64_t db) {
    asm volatile("{\n.reg .pred p;\nsetp.eq.b32 p, 0, 0;\n"
        "wgmma.mma_async.sync.aligned.m64n256k16.f32.bf16.bf16 {"
        "%0, %1, %2, %3, %4, %5, %6, %7, %8, %9, %10, %11, %12, %13, %14, %15, "
        "%16, %17, %18, %19, %20, %21, %22, %23, %24, %25, %26, %27, %28, %29, %30, %31, "
        "%32, %33, %34, %35, %36, %37, %38, %39, %40, %41, %42, %43, %44, %45, %46, %47, "
        "%48, %49, %50, %51, %52, %53, %54, %55, %56, %57, %58, %59, %60, %61, %62, %63, "
        "%64, %65, %66, %67, %68, %69, %70, %71, %72, %73, %74, %75, %76, %77, %78, %79, "
        "%80, %81, %82, %83, %84, %85, %86, %87, %88, %89, %90, %91, %92, %93, %94, %95, "
        "%96, %97, %98, %99, %100, %101, %102, %103, %104, %105, %106, %107, %108, %109, %110, %111, "
        "%112, %113, %114, %115, %116, %117, %118, %119, %120, %121, %122, %123, %124, %125, %126, %127"
        "}, %128, %129, p, 1, 1, 0, 1;\n}\n"
        : "+f"(d[0]), "+f"(d[1]), "+f"(d[2]), "+f"(d[3]), "+f"(d[4]), "+f"(d[5]), "+f"(d[6]), "+f"(d[7]),
          "+f"(d[8]), "+f"(d[9]), "+f"(d[10]), "+f"(d[11]), "+f"(d[12]), "+f"(d[13]), "+f"(d[14]), "+f"(d[15]),
          "+f"(d[16]), "+f"(d[17]), "+f"(d[18]), "+f"(d[19]), "+f"(d[20]), "+f"(d[21]), "+f"(d[22]), "+f"(d[23]),
          "+f"(d[24]), "+f"(d[25]), "+f"(d[26]), "+f"(d[27]), "+f"(d[28]), "+f"(d[29]), "+f"(d[30]), "+f"(d[31]),
          "+f"(d[32]), "+f"(d[33]), "+f"(d[34]), "+f"(d[35]), "+f"(d[36]), "+f"(d[37]), "+f"(d[38]), "+f"(d[39]),
          "+f"(d[40]), "+f"(d[41]), "+f"(d[42]), "+f"(d[43]), "+f"(d[44]), "+f"(d[45]), "+f"(d[46]), "+f"(d[47]),
          "+f"(d[48]), "+f"(d[49]), "+f"(d[50]), "+f"(d[51]), "+f"(d[52]), "+f"(d[53]), "+f"(d[54]), "+f"(d[55]),
          "+f"(d[56]), "+f"(d[57]), "+f"(d[58]), "+f"(d[59]), "+f"(d[60]), "+f"(d[61]), "+f"(d[62]), "+f"(d[63]),
          "+f"(d[64]), "+f"(d[65]), "+f"(d[66]), "+f"(d[67]), "+f"(d[68]), "+f"(d[69]), "+f"(d[70]), "+f"(d[71]),
          "+f"(d[72]), "+f"(d[73]), "+f"(d[74]), "+f"(d[75]), "+f"(d[76]), "+f"(d[77]), "+f"(d[78]), "+f"(d[79]),
          "+f"(d[80]), "+f"(d[81]), "+f"(d[82]), "+f"(d[83]), "+f"(d[84]), "+f"(d[85]), "+f"(d[86]), "+f"(d[87]),
          "+f"(d[88]), "+f"(d[89]), "+f"(d[90]), "+f"(d[91]), "+f"(d[92]), "+f"(d[93]), "+f"(d[94]), "+f"(d[95]),
          "+f"(d[96]), "+f"(d[97]), "+f"(d[98]), "+f"(d[99]), "+f"(d[100]), "+f"(d[101]), "+f"(d[102]), "+f"(d[103]),
          "+f"(d[104]), "+f"(d[105]), "+f"(d[106]), "+f"(d[107]), "+f"(d[108]), "+f"(d[109]), "+f"(d[110]), "+f"(d[111]),
          "+f"(d[112]), "+f"(d[113]), "+f"(d[114]), "+f"(d[115]), "+f"(d[116]), "+f"(d[117]), "+f"(d[118]), "+f"(d[119]),
          "+f"(d[120]), "+f"(d[121]), "+f"(d[122]), "+f"(d[123]), "+f"(d[124]), "+f"(d[125]), "+f"(d[126]), "+f"(d[127])
        : "l"(da), "l"(db));
}

__device__ __forceinline__ void wgmma_n8_ta(float (&d)[4], uint64_t da, uint64_t db) {
    asm volatile("{\n.reg .pred p;\nsetp.eq.b32 p, 0, 0;\nwgmma.mma_async.sync.aligned.m64n8k16.f32.bf16.bf16 {%0, %1, %2, %3}, %4, %5, p, 1, 1, 1, 0;\n}"
        : "+f"(d[0]), "+f"(d[1]), "+f"(d[2]), "+f"(d[3]) : "l"(da), "l"(db));
}

struct Idx {
    uint32_t lane, warp, w4, q4, g8, prow, pan;
    __device__ __forceinline__ Idx() {
        uint32_t t; asm volatile("mov.u32 %0, %%tid.x;" : "=r"(t));
        lane = t & 31; warp = t >> 5; w4 = warp & 3; q4 = lane & 3; g8 = lane >> 2;
        prow = w4 * 16 + ((lane >> 3) & 1) * 8 + (lane & 7);
        pan = prow * 128 + (((lane >> 4) ^ (lane & 7)) << 4);
    }
};
#define IDX() const Idx ix; const uint32_t lane = ix.lane, warp = ix.warp, w4 = ix.w4, q4 = ix.q4, g8 = ix.g8, prow = ix.prow, pan_addr = ix.pan; \
    (void)lane; (void)warp; (void)w4; (void)q4; (void)g8; (void)prow; (void)pan_addr;

__device__ __forceinline__ int kof(int t, int sh, int j) {
    const int p = t >> (sh - 1), pn = p < 2 ? p : p >= 9, q = p - 2 - 7 * pn;
    return ((p < 2 ? j : q + (q >= j)) << 7) + (pn << 6) + ((t & (sh - 1)) << 5);
}
__device__ __forceinline__ uint32_t fidx(uint32_t m, uint32_t w, uint32_t pn) {
    return m * 32 + w * 16 + pn;
}
constexpr int HC0 = 8 * 48, HC3 = HC0 + 3072;
__device__ __forceinline__ int hcol(int p, int j) { return HC0 + p * 1024 + j * 128; }
struct Ring {
    uint32_t slot, par;
    __device__ __forceinline__ void next() { if (++slot == NSLOT) { slot = 0; par ^= 1; } }
    __device__ __forceinline__ void skip(uint32_t n) { slot += n; if (slot >= NSLOT) { slot -= NSLOT; par ^= 1; } }
};
__device__ __forceinline__ uint32_t BAR_FULL(uint32_t sb, uint32_t s) { return sb + OFF_BAR + 8 * s; }
constexpr uint32_t AF_REL = 48;
__device__ __forceinline__ uint32_t BAR_EMPTY(uint32_t sb, uint32_t s) { return sb + OFF_BAR + 96 + 8 * s; }
__device__ __forceinline__ uint32_t BAR_SFULL(uint32_t sb, uint32_t i) { return sb + OFF_BAR + 152 + 8 * i; }
__device__ __forceinline__ uint32_t BAR_SREADY(uint32_t sb, uint32_t i) { return sb + OFF_BAR + 184 + 8 * i; }
__device__ __forceinline__ uint32_t BAR_ONE(uint32_t sb, uint32_t i) { return sb + OFF_BAR + 216 + 8 * i; }
enum { EV_WIN, EV_WIN1, EV_WIN2, EV_WIN3, EV_P0, EV_GA, EV_GB, EV_LN2, EV_LAG1, EV_LAG2, EV_LAG3, EV_LAG4, EV_LAG5, EV_KV, EV_PAR, EV_AGO, EV_AGO1, EV_AGO2, EV_FGO, EV_FGO1, EV_FGO2, EV_H0, EV_H1, EV_H2, EV_H3, EV_TAIL, EV_COUNT = EV_TAIL + 8 };
constexpr int NB_TAIL = 4;

struct Rel {
    uint32_t base; bool sig;
    __device__ __forceinline__ Rel(uint32_t sb, uint32_t tw) {
        uint32_t a; asm("mapa.shared::cluster.u32 %0, %1, %2;" : "=r"(a) : "r"(BAR_EMPTY(sb, 0)), "r"((tw >> 5) & 1));
        base = __shfl_sync(0xffffffffu, a, 0); sig = (tw & ~32u) == 0;
    }
    __device__ __forceinline__ void operator()(uint32_t slot) const {
        if (sig) asm volatile("mbarrier.arrive.shared::cluster.b64 _, [%0];" :: "r"(base + 8 * slot) : "memory");
    }
};
struct LnRow { float rs0, nm0, rs1, nm1; };
struct Pipe {
    Rel rel; uint32_t p1, p2;
    __device__ __forceinline__ Pipe(uint32_t sb, uint32_t tw, uint32_t first) : rel(sb, tw), p1(first), p2(NSLOT) {}
    template <bool TWO> __device__ __forceinline__ void acquire(uint32_t sb, uint32_t af, const Ring& r) {
        const uint32_t b0 = BAR_FULL(sb, r.slot), b1 = b0 + af;
        const bool ready = TWO ? mbar_test2(b0, b1, r.par) : mbar_test(b0, r.par);
        wg_wait<1>();
        rel(p2);
        if (!ready) { if (TWO) mbar_wait2(b0, b1, r.par); else mbar_wait(b0, r.par); }
    }
    __device__ __forceinline__ void issued(uint32_t slot) { p2 = p1; p1 = slot; }
    __device__ __forceinline__ void drain1() { wg_wait<1>(); rel(p2); p2 = NSLOT; }
    __device__ __forceinline__ void drain0() { wg_wait<0>(); rel(p1); p1 = NSLOT; }
    template <bool TWO, class Step> __device__ __forceinline__ void hold(int LG, uint32_t sb, uint32_t af, Ring& r, uint32_t lag_bar, Step step) {
        Ring q = r;
#pragma unroll 1
        for (int i = 0; i < LG; ++i) { if (TWO) mbar_wait2(BAR_FULL(sb, q.slot), BAR_FULL(sb, q.slot) + af, q.par); else mbar_wait(BAR_FULL(sb, q.slot), q.par); q.next(); }
        mbar_wait(lag_bar, 0);
#pragma unroll 1
        do {
            step(r.slot);
            wg_wait<2>(); rel(p2); p2 = p1; p1 = r.slot;
            if (++r.slot == NSLOT) r.slot = 0;
        } while (r.slot != q.slot);
        r.par = q.par;
    }
};
template <bool TWO, bool FIRST, int NA, int NB>
__device__ __forceinline__ void step32(float (&aa)[NA], float (&ab)[NB], uint32_t sb, uint32_t wg, uint32_t slot, int own) {
    const uint32_t st = d16(sb) + slot * (SLOT >> 4);
    const uint32_t alo = own >= 0 ? d16(sb) + OFF_STG / 16 + wg * 1024 + (own >> 1) * 512 + (own & 1) * 4 : st + wg * 256;
    const uint32_t ahi = own >= 0 ? (1024 >> 4) | (1u << 30) : (512 >> 4) | (2u << 30);
    wg_fence();
#pragma unroll
    for (int k = 0; k < 2; ++k) {
        const uint64_t da = ((uint64_t)ahi << 32) | (alo + k * 2 + 0x10000);
        if constexpr (NA == 88) {
            const uint64_t d0 = mk_desc(st, 8192 + k * 2048, 8192, 1024, 1), d1 = mk_desc(st, 12288 + k * 2048, 8192, 1024, 1);
            if (FIRST && k == 0) { wgmma_n176_z(aa, da, d0); wgmma_n176_z(ab, da, d1); }
            else { wgmma_n176(aa, da, d0); wgmma_n176(ab, da, d1); }
        } else {
            const uint64_t d0 = mk_desc(st, 8192 + k * 2048, 4096, 1024, 1), d1 = mk_desc(st, 24576 + k * 2048, 4096, 1024, 1);
            if (FIRST && k == 0) { wgmma_n256_z(aa, da, d0); if constexpr (TWO) wgmma_n128_z(ab, da, d1); }
            else { wgmma_n256(aa, da, d0); if constexpr (TWO) wgmma_n128(ab, da, d1); }
        }
    }
    wg_commit();
}
template <bool TWO, int LG, int NA, int NB, class Mid, class Tail>
__device__ __forceinline__ void mainloop32(float (&aa)[NA], float (&ab)[NB], uint32_t sb, uint32_t wg, uint32_t tw, Ring& r, uint32_t lag_ev, int g0, Mid mid, Tail tail) {
    step32<TWO, true>(aa, ab, sb, wg, r.slot, TWO ? 0 : -1);
    TS(g0, 0);
    Pipe pp(sb, tw, r.slot);
    r.next();
    const int end = wg ? 32 : 32 - LG;
#pragma unroll 1
    for (int it = 1; it < end; ++it) {
        pp.acquire<TWO>(sb, wg ? 0 : AF_REL, r);
        step32<TWO, false>(aa, ab, sb, wg, r.slot, TWO && it < 4 ? it : -1);
        pp.issued(r.slot);
        TS(g0 + it, 0);
        r.next();
        mid(it);
    }
    if (wg == 0) { pp.drain1(); pp.drain0(); pp.hold<TWO>(LG, sb, AF_REL, r, BAR_ONE(sb, lag_ev), [&](uint32_t slot) { step32<TWO, false>(aa, ab, sb, 0, slot, -1); }); }
    if (wg == 1 && tw == 0) mbar_arrive(BAR_ONE(sb, lag_ev));
    pp.drain1();
    tail();
    pp.drain0();
    TS(g0 + 31, 1);
}
template <bool FIRST>
__device__ __forceinline__ void step64(float (&acc)[64], uint32_t sb, uint32_t wg, uint32_t slot, int own) {
    const uint32_t sbb = d16(sb) + slot * (SLOT >> 4), sa = own >= 0 ? d16(sb) + OFF_STG / 16 + wg * 1024 + own * 512 : sbb + wg * 512;
    wg_fence();
#pragma unroll
    for (int k = 0; k < 4; ++k) {
        const uint64_t da = mk_desc(sa, k * 32, 16, 1024, 1), db = mk_desc(sbb, 16384 + k * 2048, 8192, 1024, 1);
        if (FIRST && k == 0) wgmma_n128_z(acc, da, db); else wgmma_n128(acc, da, db);
    }
    wg_commit();
}
template <class Put, class Mid, class Tail>
__device__ __forceinline__ void mainloop64(float (&acc)[64], bool wo, uint32_t sb, uint32_t wg, uint32_t tw, Ring& r, Put put, Mid mid, Tail tail) {
    const int g0 = wo ? 32 : 144, nst = wo ? 16 : 56, lg = wo ? LAGW : LAGD; (void)g0;
    const uint32_t lag_bar = BAR_ONE(sb, wo ? EV_LAG4 : EV_LAG5), af = wo && !wg ? AF_REL : 0;
    if (!wo) CS(28);
    step64<true>(acc, sb, wg, r.slot, wo ? 0 : -1);
    if (!wo) CS(29);
    TS(g0, 0);
    Pipe pp(sb, tw, r.slot);
    r.next();
    int it = 1;
    auto run = [&](int end, int own, bool with_put) {
#pragma unroll 1
        do {
            pp.acquire<true>(sb, af, r);
            step64<false>(acc, sb, wg, r.slot, own);
            pp.issued(r.slot);
            TS(g0 + it, 0);
            if (wo && it == 2) CS(9);
            r.next();
            if (with_put && it == (wg ? PUTD1 : PUTD0)) put();
        } while (++it < end);
    };
    const int end = wg ? nst : nst - lg;
    run(wo ? 2 : wg ? MIDD : end, wo ? 1 : -1, true);
    mid();
    if (wo) { pp.drain1(); pp.drain0(); TS(g0 + 1, 1); }
    if (it < end) run(end, -1, false);
    if (wg == 0 && lg) { pp.drain1(); pp.drain0(); pp.hold<true>(lg, sb, af, r, lag_bar, [&](uint32_t slot) { step64<false>(acc, sb, 0, slot, -1); }); }
    if (wg == 1 && tw == 0) mbar_arrive(lag_bar);
    pp.drain1();
    tail();
    pp.drain0();
    TS(g0 + nst - 1, 1);
}

struct RowAcc {
    float sm[4] = {0.f, 0.f, 0.f, 0.f}, sq[4] = {0.f, 0.f, 0.f, 0.f};
    __device__ __forceinline__ void add(int e, float x) { sm[e & 3] += x; sq[e & 3] = fmaf(x, x, sq[e & 3]); }
    __device__ __forceinline__ void publish(uint4* dst, uint32_t q4, uint32_t ep, bool acc) const {
        const float s0 = sm[0] + sm[1], s1 = sm[2] + sm[3], q0 = sq[0] + sq[1], q1 = sq[2] + sq[3];
        const bool od = q4 & 1;
        float sv = (od ? s1 : s0) + __shfl_xor_sync(0xffffffffu, od ? s0 : s1, 1), qv = (od ? q1 : q0) + __shfl_xor_sync(0xffffffffu, od ? q0 : q1, 1);
        sv += __shfl_xor_sync(0xffffffffu, sv, 2); qv += __shfl_xor_sync(0xffffffffu, qv, 2);
        asm volatile("{\n.reg .pred p, q;\n.reg .b64 t, u;\n.reg .b128 w;\nsetp.eq.u32 p, %4, 1;\nsetp.eq.u32 q, %4, 0;\n"
            "@p red.relaxed.gpu.global.add.v4.f32 [%0], {0f00000000, %1, %2, %3};\n"
            "mov.b64 t, {0f00000000, %1};\nmov.b64 u, {%2, %3};\nmov.b128 w, {t, u};\n@q st.relaxed.gpu.global.b128 [%0], w;\n}"
            :: "l"(dst + (q4 & 1) * 8), "f"(sv), "f"(qv), "f"(acc ? 1.f : __uint_as_float(ep)), "r"((q4 & 2) | acc) : "memory");
    }
};
__device__ __forceinline__ LnRow merge_stats(const uint4* src, uint32_t q4, uint32_t ep, uint32_t sb, bool acc) {
    float v[4];
    uint32_t n = 0;
    if (acc) {
        uint4 a, b;
        while (true) {
            a = ld_pkt16(src); b = ld_pkt16(src + 8);
            const bool ok = __all_sync(0xffffffffu, a.w == __float_as_uint(8.f) && b.w == __float_as_uint(8.f));
            if (n < 4) CS(14 + n);
            if (ok) break;
            SPIN_GUARD(n);
        }
        v[0] = __uint_as_float(a.y); v[1] = __uint_as_float(b.y); v[2] = __uint_as_float(a.z); v[3] = __uint_as_float(b.z);
    } else {
        uint4 t[4];
        while (true) {
#pragma unroll
            for (int i = 0; i < 4; ++i) t[i] = ld_pkt16(src + (q4 * 2 + (i >> 1)) * 512 + (i & 1) * 8);
            if (__all_sync(0xffffffffu, t[0].w == ep && t[1].w == ep && t[2].w == ep && t[3].w == ep)) break;
            SPIN_GUARD(n);
        }
#pragma unroll
        for (int h = 0; h < 2; ++h) { v[h] = __uint_as_float(t[h].y) + __uint_as_float(t[2 + h].y); v[2 + h] = __uint_as_float(t[h].z) + __uint_as_float(t[2 + h].z); }
#pragma unroll
        for (int o = 1; o < 4; o <<= 1)
#pragma unroll
            for (int i = 0; i < 4; ++i) v[i] += __shfl_xor_sync(0xffffffffu, v[i], o);
    }
    const float m0 = v[0] * (1.f / D_), m1 = v[1] * (1.f / D_);
    const float r0 = rsq(fmaxf(fmaf(-m0, m0, v[2] * (1.f / D_)), 0.f) + 1e-5f), r1 = rsq(fmaxf(fmaf(-m1, m1, v[3] * (1.f / D_)), 0.f) + 1e-5f);
    return LnRow{r0, -m0 * r0, r1, -m1 * r1};
}
struct Stg {
    uint32_t b, par;
    __device__ __forceinline__ uint32_t acquire2(uint32_t sb, uint32_t wg) {
        mbar_wait2(BAR_SREADY(sb, wg * 2), BAR_SREADY(sb, wg * 2 + 1), par);
        par ^= 1;
        return sb + OFF_STG + wg * 16384;
    }
    __device__ __forceinline__ void publish(uint32_t sb, uint32_t wg, uint32_t lane) {
        fence_async_smem();
        __syncwarp();
        if (lane == 0) mbar_arrive(BAR_SFULL(sb, wg * 2 + b));
        b ^= 1;
    }
};

struct LnPar {
    uint4 p[8];
    __device__ __forceinline__ void load(uint32_t sb, uint32_t q4) {
#pragma unroll
        for (int i = 0; i < 8; ++i) p[i] = lds128(sb + OFF_PAR + i * 64 + q4 * 16);
    }
};
__device__ __forceinline__ void ln_norm(uint32_t (&xn)[32], const float (&x)[64], const LnRow& n) {
#pragma unroll
    for (int e = 0; e < 32; ++e) {
        const float rs = (e & 1) ? n.rs1 : n.rs0, nm = (e & 1) ? n.nm1 : n.nm0;
        xn[e] = pack2(fmaf(x[2 * e], rs, nm), fmaf(x[2 * e + 1], rs, nm));
    }
}
__device__ __forceinline__ void ln_emit(const uint32_t (&xr)[32], const LnPar& lp, uint32_t sb, uint32_t wg, const Idx& ix) {
#pragma unroll
    for (int i = 0; i < 8; ++i)
        stsm4(sb + OFF_STG + wg * 16384 + (i >> 2) * 8192 + (ix.pan ^ ((i & 3) << 5)), hfma2_bf16(xr[4 * i], lp.p[i].z, lp.p[i].x), hfma2_bf16(xr[4 * i + 1], lp.p[i].z, lp.p[i].x),
              hfma2_bf16(xr[4 * i + 2], lp.p[i].w, lp.p[i].y), hfma2_bf16(xr[4 * i + 3], lp.p[i].w, lp.p[i].y));
    fence_async_smem();
    __syncwarp();
    if (ix.lane < 2) mbar_arrive(BAR_SFULL(sb, wg * 2 + ix.lane));
    bar_sync(1 + wg, 128);
}
__device__ __forceinline__ void load_slab(uint32_t (&xr)[32], uint32_t buf) {
    IDX();
#pragma unroll
    for (int i = 0; i < 8; ++i) ldsm4(buf + (i >> 2) * 8192 + (pan_addr ^ ((i & 3) << 5)), xr[4 * i], xr[4 * i + 1], xr[4 * i + 2], xr[4 * i + 3]);
}
__device__ __forceinline__ void unpack_slab(float (&x)[64], const uint32_t (&xr)[32]) {
#pragma unroll
    for (int i = 0; i < 32; ++i) unpack2(xr[i], x[2 * i], x[2 * i + 1]);
}
__device__ __forceinline__ void store_slab(const float (&x)[64], uint32_t buf, uint32_t pitch, uint32_t pan, int i0, int i1) {
#pragma unroll
    for (int i = i0; i < i1; ++i)
        stsm4(buf + (i >> 2) * pitch + (pan ^ ((i & 3) << 5)), pack2(x[8 * i], x[8 * i + 1]), pack2(x[8 * i + 2], x[8 * i + 3]), pack2(x[8 * i + 4], x[8 * i + 5]), pack2(x[8 * i + 6], x[8 * i + 7]));
}
template <int NP, class Done>
__device__ __forceinline__ void fetch_halo(uint4* src, bool first, uint32_t dst, Done done) {
    uint4 hv[4 * NP];
    uint32_t n = 0;
    while (true) {
        bool ok = true;
#pragma unroll
        for (int i = 0; i < 4 * NP; ++i) { hv[i] = first ? make_uint4(0, 0, 0, 0) : ld_pkt16(src + (i >> 2) * 256 + (i & 3) * 32); ok = ok && hv[i].x != 0; }
        if (first || __all_sync(0xffffffffu, ok)) break;
        SPIN_GUARD(n);
    }
#pragma unroll
    for (int i = 0; i < 4 * NP; ++i) stsm4(dst + (i >> 2) * 4096 + (i & 3) * 512, hv[i].x, hv[i].y, hv[i].z, hv[i].w);
    done();
    if (!first) {
#pragma unroll
        for (int i = 0; i < 4 * NP; ++i) src[(i >> 2) * 256 + (i & 3) * 32] = make_uint4(0, 0, 0, 0);
    }
}

template <int N, class G, class U>
__device__ __forceinline__ void glu(uint32_t (&h)[N], G g, U u) {
#pragma unroll
    for (int i = 0; i < N; ++i) h[i] = pack2(fmaf(tanh_(g(2 * i)), u(2 * i), u(2 * i)), fmaf(tanh_(g(2 * i + 1)), u(2 * i + 1), u(2 * i + 1)));
}
__device__ __forceinline__ void put_h(const uint32_t (&h)[32], uint32_t sb, uint32_t wg, Stg& stg) {
    IDX();
    const uint32_t buf = stg.acquire2(sb, wg);
#pragma unroll
    for (int k = 0; k < 8; ++k) stsm4(buf + (k >> 2) * 8192 + (pan_addr ^ ((k & 3) << 5)), h[4 * k], h[4 * k + 1], h[4 * k + 2], h[4 * k + 3]);
    fence_async_smem();
    __syncwarp();
    if (lane < 2) mbar_arrive(BAR_SFULL(sb, wg * 2 + lane));
}

template <int NP, bool PREV>
__device__ __forceinline__ void passes128(uint32_t (&hp)[32], uint32_t sb, uint32_t wg, uint32_t tw, Ring& r, Stg& stg) {
#pragma unroll 1
    for (int p = 0; p < NP; ++p) {
        float b256[128], none[1];
        const int put_at = !PREV && p == 0 ? -1 : wg ? PUT1 : PUT0;
        mainloop32<false, LAGS>(b256, none, sb, wg, tw, r, EV_LAG2 + p, 80 + 32 * (p & 1), [&](int it) { if (it == put_at) put_h(hp, sb, wg, stg); },
                                [&] { if (PREV || p < NP - 1) mbar_wait(BAR_FULL(sb, r.slot), r.par); });
        if (threadIdx.x == 0) { TL(29 + 2 * p); TC(114 + 2 * p); }
        if (threadIdx.x == 128) TL(53 + 2 * (p & 1));
        CS(24 + 2 * (p & 1));
        glu(hp, [&](int i) { return b256[i + (i & 32)]; }, [&](int i) { return b256[i + (i & 32) + 32]; });
        if (threadIdx.x == 0) { TL(30 + 2 * p); TC(115 + 2 * p); }
        if (threadIdx.x == 128) TL(54 + 2 * (p & 1));
        CS(25 + 2 * (p & 1));
    }
}

template <int N> __device__ __forceinline__ void padcode(uint32_t x) {
#pragma unroll
    for (int i = 0; i < N; ++i) asm volatile("st.volatile.shared.u32 [%0], %0;" :: "r"(x) : "memory");
}
__global__ void __launch_bounds__(384, 1)
fused_block_kernel(const __grid_constant__ Ptrs pt, const __grid_constant__ Maps mp) {
    uint32_t* const g_flags = pt.mail->flags;
    uint2* const g_mod = pt.mail->mod;
    uint4* const g_st1 = pt.mail->st1;
    uint32_t* const g_par2 = pt.mail->par2;
    uint4* const g_halo = pt.mail->halo;
    const __nv_bfloat16* __restrict__ cvec = pt.c;
    if (threadIdx.x == 224) { prefetch_map(&mp.wm8); prefetch_map(&mp.x); }
    extern __shared__ __align__(1024) uint8_t smem[];
    const uint32_t sb = smem_u32(smem);
    const uint32_t tid = threadIdx.x, tw = tid & 127, lane = tid & 31;
    const uint32_t warp = __shfl_sync(0xffffffffu, tid >> 5, 0), wg = warp >> 2;
    uint32_t rank; asm("mov.u32 %0, %%cluster_ctarank;" : "=r"(rank));
    rank = __shfl_sync(0xffffffffu, rank, 0);
    uint32_t ep;
    uint32_t smid; asm volatile("mov.u32 %0, %%smid;" : "=r"(smid));
    const int c = __shfl_sync(0xffffffffu, smid >> 1, 0);
    const int c7 = ((c - 32) * 37) >> 8;
    int grp = c < 32 ? c & 7 : c < 60 ? c - 31 - 7 * c7 : c < 62 ? -1 : 0;
    const int j = c < 32 ? c >> 3 : c < 60 ? 4 + c7 : c < 62 ? (c - 60) * 2 + rank : c - 58;
    const bool aux = grp < 0;
    const int m = grp * 2 + rank;
    uint4* const g_st2 = g_halo + (m > 0 ? (m - 1) * 8 * 512 : 128);

    bool cluster_arrive_early = false;
    if (wg < 2) {
      if (!KDEBUG) cluster_arrive();
      ep = flag_get(g_flags + FL_DONE);
      uint16_t cw[8];
      {
          const __nv_bfloat16* cp = cvec + ((tw >> 5) * 32 + (tw & 3) * 2) * 8 + (lane >> 2);
#pragma unroll
          for (int i = 0; i < 8; ++i) asm volatile("ld.global.nc.u16 %0, [%1];" : "=h"(cw[i]) : "l"(cp + (i >> 1) * 64 + (i & 1) * 8));
      }
      asm volatile("setmaxnreg.inc.sync.aligned.u32 224;");
      if (tid == 0) TL(58);
      if (KDEBUG) cluster_arrive();
      Ring r{0, 0};
      Stg stg{0, 0};
      if (!aux) {
        float xs[64];
        uint32_t xp[32];
        {
            sts128(sb + tid * 16, pack2(silu_(bf_lo(cw[0])), silu_(bf_lo(cw[1]))), pack2(silu_(bf_lo(cw[2])), silu_(bf_lo(cw[3]))),
                   pack2(silu_(bf_lo(cw[4])), silu_(bf_lo(cw[5]))), pack2(silu_(bf_lo(cw[6])), silu_(bf_lo(cw[7]))));
            cluster_wait();
            ep = __shfl_sync(0xffffffffu, ep, 0) / NCTA + 1;
            load_slab(xp, stg.acquire2(sb, wg));
            unpack_slab(xs, xp);
            if (tid == 0) TL(24);
            if (tid == 128) TL(27);
        }
#pragma unroll 1
        for (int blk = 0; ; ++blk) {
        {
            IDX();
            uint4* const st = (blk ? g_st2 : g_st1 + m * 8 * 512) + wg * 64 + w4 * 16 + g8;
            const bool acc = RACC && blk;
            RowAcc ra;
#pragma unroll
            for (int e = 0; e < 64; ++e) ra.add(e, xs[e]);
            ra.publish(st + (acc ? 0 : j * 512), q4, ep, acc);
            if (tid == 0) TL(blk ? 9 : 26);
            if (tid == 128 && blk) TL(34);
            if (blk) CS(11);
            LnPar lp;
            if (blk == 0) {
            uint4* const mod_out = pt.mail->mod1 + g8 * 512 + (m * 8 + j) * 4 + q4;
            if (wg == 0) {
                uint4 af[8];
#pragma unroll
                for (int i = 0; i < 8; ++i) af[i] = lds128(sb + w4 * 512 + i * 64 + q4 * 16);
                float c[4][4] = {};
#pragma unroll
                for (int i = 0; i < 8; ++i) {
                    if (!(i & 1)) mbar_wait(BAR_ONE(sb, EV_WIN + (i >> 1)), 0);
                    if (i == 6 && tid == 0) TL(25);
#pragma unroll
                    for (int h = 0; h < 2; ++h) {
                        uint32_t b0, b1, b2, b3;
                        ldsm4t(sb + 5 * SLOT + i * 4096 + w4 * 1024 + h * 512 + (lane & 15) * 32 + (lane >> 4) * 16, b0, b1, b2, b3);
                        mma16816(c[2 * h], h ? af[i].z : af[i].x, 0u, h ? af[i].w : af[i].y, 0u, b0, b1);
                        mma16816(c[2 * h + 1], h ? af[i].z : af[i].x, 0u, h ? af[i].w : af[i].y, 0u, b2, b3);
                    }
                }
                if (lane < 4) sts128(sb + OFF_TAB + w4 * 64 + lane * 16, __float_as_uint(c[0][0] + c[2][0]), __float_as_uint(c[0][1] + c[2][1]),
                                     __float_as_uint(c[1][0] + c[3][0]), __float_as_uint(c[1][1] + c[3][1]));
                if (lane < 2) mbar_arrive_cta(BAR_ONE(sb, EV_P0), lane);
                bar_sync(1, 128);
                if (w4 == 0) {
                    float a[4] = {0.f, 0.f, 0.f, 0.f};
#pragma unroll
                    for (int i = 0; i < 4; ++i) {
                        const uint4 t = lds128(sb + OFF_TAB + i * 64 + q4 * 16);
                        a[0] += __uint_as_float(t.x); a[1] += __uint_as_float(t.y); a[2] += __uint_as_float(t.z); a[3] += __uint_as_float(t.w);
                    }
                    const float add = m >= 8 ? 1.f : 0.f;
                    st_pkt16(mod_out, pack2(bf_round(a[0]) + add, bf_round(a[1]) + add), pack2(bf_round(a[2]) + add, bf_round(a[3]) + add), ep, 0);
                    if (tid == 0) TL(3);
                }
            } else if (LWAIT >= 0) mbar_wait(BAR_ONE(sb, EV_WIN + LWAIT), 0);
            } else {
                mbar_wait2(BAR_ONE(sb, EV_LN2), BAR_FULL(sb, 0), 0);
            }
            lp.load(sb, q4);
#pragma unroll
            for (int e = 0; e < 32; ++e) xp[e] = pack2(xs[2 * e], xs[2 * e + 1]);
            if (blk) CS(13);
            const LnRow n = merge_stats(st, q4, ep, sb, acc);
            if (tid == 0) TL(blk ? 49 : 48);
            if (tid == 128) TL(blk ? 45 : 28);
            if (blk) CS(18);
            uint32_t xn[32];
            ln_norm(xn, xs, n);
            if (blk == 0) {
                mbar_wait2(BAR_FULL(sb, 0), BAR_ONE(sb, EV_PAR), 0);
                if (FD0 && wg == 0) { uint32_t t0, t1; asm volatile("mov.u32 %0, %%clock;" : "=r"(t0)); do { asm volatile("mov.u32 %0, %%clock;" : "=r"(t1)); } while (t1 - t0 < FD0); }
                lp.load(sb, q4);
            }
            ln_emit(xn, lp, sb, wg, ix);
            if (tid == 0) { TL(blk ? 36 : 8); TC(blk ? 109 : 103); }
            if (tid == 128) TL(blk ? 43 : 22);
            if (blk) CS(21);
        }
        uint32_t hp[32];
        if (blk == 0) {
        {
            float big[128], sml[64];
            step32<true, true>(big, sml, sb, wg, r.slot, 0);
            TS(0, 0);
            Pipe pp(sb, tw, r.slot);
            r.next();
#pragma unroll 1
            for (int it = 1; it < 32 - LAGQ; ++it) {
                pp.acquire<true>(sb, wg ? 0 : AF_REL, r);
                step32<true, false>(big, sml, sb, wg, r.slot, it < 4 ? it : -1);
                pp.issued(r.slot);
                TS(it, 0);
                r.next();
            }
            auto half = [&](uint32_t slot, bool rest) {
                const uint32_t st = d16(sb) + slot * (SLOT >> 4);
#pragma unroll
                for (int k = 0; k < 2; ++k) {
                    const uint64_t da = mk_desc(st + wg * 256, k * 32, 16, 512, 2);
                    if (rest) wgmma_n256(big, da, mk_desc(st, 8192 + k * 2048, 4096, 1024, 1)); else wgmma_n128(sml, da, mk_desc(st, 24576 + k * 2048, 4096, 1024, 1));
                }
            };
            auto rest = [&](bool each) {
                wg_fence();
#pragma unroll
                for (int it = 32 - LAGQ; it < 32; ++it) { if (each && it > 32 - LAGQ) wg_fence(); half(it % NSLOT, true); if (each || it == 31) wg_commit(); }
            };
            stg.acquire2(sb, wg); mbar_wait2(BAR_SREADY(sb, 2), BAR_SREADY(sb, 3), 1);
#pragma unroll 1
            for (int it = 32 - LAGQ; it < 32; ++it) {
                pp.acquire<true>(sb, wg ? 0 : AF_REL, r);
                wg_fence(); half(r.slot, false); wg_commit();
                pp.issued(NSLOT);
                TS(it, 0);
                r.next();
            }
            if (wg) { rest(false); wg_wait<1>(); } else wg_wait<0>();
            CS(8);
            IDX();
            uint32_t k0[8], k1[8], k2[8], v0[8], v1[8], v2[8];
            const uint32_t nxt = warp + ((warp & 1) ? 3 : 1), mine = sb + OFF_STG + wg * 16384 + w4 * 2048;
            auto tails = [&](const float* kv, uint32_t (&kt)[8], uint32_t (&vt)[8]) {
#pragma unroll
                for (int t = 0; t < 8; ++t) { kt[t] = pack2(kv[4 * t + 2], kv[4 * t + 3]); vt[t] = pack2(kv[32 + 4 * t + 2], kv[32 + 4 * t + 3]); }
            };
            auto post = [&](int pn, uint32_t (&kt)[8], uint32_t (&vt)[8]) {
                uint4* dst = g_halo + (m * 8 + j) * 512 + (w4 >> 1) * 256 + pn * 128 + lane;
#pragma unroll
                for (int h = 0; h < 2; ++h) { if (!kt[4 * h]) kt[4 * h] = 0x8000u; if (!vt[4 * h]) vt[4 * h] = 0x8000u; }
#pragma unroll
                for (int h = 0; h < 2; ++h) { st_pkt16(dst + h * 32, kt[4 * h], kt[4 * h + 1], kt[4 * h + 2], kt[4 * h + 3]); st_pkt16(dst + 64 + h * 32, vt[4 * h], vt[4 * h + 1], vt[4 * h + 2], vt[4 * h + 3]); }
            };
            auto prepare = [&](int pn, const float* kv) {
                tails(kv, k2, v2);
                if (nxt < 8) {
                    const uint32_t dst = sb + OFF_STG + (nxt >> 2) * 16384 + (nxt & 3) * 2048 + pn * 8192 + lane * 16;
#pragma unroll
                    for (int h = 0; h < 2; ++h) { stsm4(dst + h * 512, k2[4 * h], k2[4 * h + 1], k2[4 * h + 2], k2[4 * h + 3]); stsm4(dst + 1024 + h * 512, v2[4 * h], v2[4 * h + 1], v2[4 * h + 2], v2[4 * h + 3]); }
                    if (pn == 0) bar_arrive(NB_TAIL + nxt, 64);
                    else { __syncwarp(); if (lane == 0) mbar_arrive(BAR_ONE(sb, EV_TAIL + nxt)); }
                } else if (pn == 0 && m < 15) post(0, k2, v2);
#pragma unroll
                for (int t = 0; t < 8; ++t) { k1[t] = pack2(kv[4 * t], kv[4 * t + 1]); v1[t] = pack2(kv[32 + 4 * t], kv[32 + 4 * t + 1]); }
                auto turn = [&] {
#pragma unroll
                    for (int t = 0; t < 8; ++t) { v1[t] = movm(v1[t]); v2[t] = movm(v2[t]); }
                };
                if (pn) turn();
                if (pn == 0) {
                    CS(2);
                    if (wg == 0) { rest(true); turn(); wg_wait<3>(); pp.rel(28 % NSLOT); wg_wait<2>(); pp.rel(29 % NSLOT); wg_wait<1>(); pp.rel(30 % NSLOT); }
                    else turn();
                    bar_sync(NB_TAIL + warp, 64); CS(4);
                }
                else mbar_wait(BAR_ONE(sb, EV_TAIL + __shfl_sync(0xffffffffu, warp, 0)), 0);
#pragma unroll
                for (int h = 0; h < 2; ++h) {
                    ldsm4(mine + pn * 8192 + lane * 16 + h * 512, k0[4 * h], k0[4 * h + 1], k0[4 * h + 2], k0[4 * h + 3]);
                    ldsm4t(mine + pn * 8192 + lane * 16 + 1024 + h * 512, v0[4 * h], v0[4 * h + 1], v0[4 * h + 2], v0[4 * h + 3]);
                }
            };
#pragma unroll
            for (int i = 0; i < 64; ++i) asm volatile("" : "+f"(sml[i]) :: "memory");
            prepare(0, sml);
            static_assert(LAGQ == 4, "");
            wg_wait<0>();
            if (wg) { pp.rel(28 % NSLOT); pp.rel(29 % NSLOT); pp.rel(30 % NSLOT); }
            pp.rel(31 % NSLOT);
            TS(31, 1);
            if (tid == 0) { TL(4); TC(104); }
            if (tid == 128) TL(50);
            CS(1);
#pragma unroll
            for (int i = 0; i < 128; ++i) asm volatile("" : "+f"(big[i]) :: "memory");
            if (nxt >= 8 && m < 15) { uint32_t kt[8], vt[8]; tails(big, kt, vt); post(1, kt, vt); }
            const bool lo0 = q4 * 2 > g8, lo1 = q4 * 2 + 1 > g8;
            const bool nopast = m == 0 && (warp & 5) == 0;
            const uint32_t lomask = (lo0 ? 0xFFFFu : 0u) | (lo1 ? 0xFFFF0000u : 0u);
            const uint32_t orow = mine + (lane & 7) * 128 + (((lane >> 3) ^ (lane & 7)) << 4);
            const float sl2 = 0.17677669529663687f * 1.4426950408889634f;
#pragma unroll
            for (int pn = 0; pn < 2; ++pn) {
                float e0[4], e1[4], mx[4], sum[4];
#pragma unroll
                for (int hh = 0; hh < 2; ++hh) {
                    uint32_t qf[8];
#pragma unroll
                    for (int i = 0; i < 8; ++i) qf[i] = pack2(big[64 + 32 * pn + 16 * hh + 2 * i], big[64 + 32 * pn + 16 * hh + 2 * i + 1]);
                    float s[3][4];
#pragma unroll
                    for (int t = 0; t < 3; ++t) {
                        const uint32_t* k = (t == 0 ? k0 : t == 1 ? k1 : k2) + 4 * hh;
                        s[t][0] = s[t][1] = s[t][2] = s[t][3] = 0.f;
                        mma16816(s[t], qf[0], qf[1], qf[2], qf[3], k[0], k[1]);
                        mma16816(s[t], qf[4], qf[5], qf[6], qf[7], k[2], k[3]);
                    }
#pragma unroll
                    for (int hf = 0; hf < 2; ++hf) {
                        const int u = hh * 2 + hf;
                        e0[u] = lo0 ? ((hf == 0 && nopast) ? -INFINITY : s[hf][hf * 2]) : s[hf + 1][hf * 2];
                        e1[u] = lo1 ? ((hf == 0 && nopast) ? -INFINITY : s[hf][hf * 2 + 1]) : s[hf + 1][hf * 2 + 1];
                        mx[u] = fmaxf(e0[u], e1[u]);
                    }
                }
#pragma unroll
                for (int o = 1; o < 4; o <<= 1)
#pragma unroll
                    for (int u = 0; u < 4; ++u) mx[u] = fmaxf(mx[u], __shfl_xor_sync(0xffffffffu, mx[u], o));
#pragma unroll
                for (int u = 0; u < 4; ++u) {
                    const float c = -mx[u] * sl2;
                    e0[u] = ex2(fmaf(e0[u], sl2, c)); e1[u] = ex2(fmaf(e1[u], sl2, c));
                    sum[u] = e0[u] + e1[u];
                }
#pragma unroll
                for (int o = 1; o < 4; o <<= 1)
#pragma unroll
                    for (int u = 0; u < 4; ++u) sum[u] += __shfl_xor_sync(0xffffffffu, sum[u], o);
#pragma unroll
                for (int u = 0; u < 4; ++u) {
                    const int h = u >> 1;
                    const float inv = rcp(sum[u]);
                    const uint32_t p = pack2(e0[u] * inv, e1[u] * inv);
                    const uint32_t* va = ((u & 1) ? v1 : v0) + 4 * h;
                    const uint32_t* vb = ((u & 1) ? v2 : v1) + 4 * h;
                    float o[2][4] = {};
#pragma unroll
                    for (int d = 0; d < 2; ++d) mma16816(o[d], va[2 * d], va[2 * d + 1], vb[2 * d], vb[2 * d + 1], p & lomask, p & ~lomask);
                    stsm4t((orow ^ ((u >> 1) << 6)) + pn * 8192 + (u & 1) * 1024, pack2(o[0][0], o[0][1]), pack2(o[0][2], o[0][3]), pack2(o[1][0], o[1][1]), pack2(o[1][2], o[1][3]));
                }
                fence_async_smem();
                __syncwarp();
                if (lane == 0) mbar_arrive(BAR_SFULL(sb, wg * 2 + pn));
                if (pn == 0) { CS(5); block_end(sb, 0); prepare(1, big); CS(3); }
            }
            CS(6);
            if (tid == 32) TL(41);
            mbar_wait2(BAR_FULL(sb, 32 % NSLOT), BAR_FULL(sb, 33 % NSLOT), (32 / NSLOT) & 1);
            load_slab(xp, sb + (32 % NSLOT + wg) * SLOT);
#pragma unroll
            for (int e = 0; e < 32; ++e) hp[e] = __float_as_uint(big[e]);
            bar_sync(1 + wg, 128);
            if (tid == 0) { TL(6); TC(106); }
            if (tid == 128) TL(44);
            CS(7);
        }
        } else {
        {
            float ag[88], au[88];
            mainloop32<true, LAG>(ag, au, sb, wg, tw, r, EV_LAG1, 48, [](int) {}, [&] {
                Ring q = r; if (!wg) q.next();
                mbar_wait(BAR_EMPTY(sb, q.slot), q.par ^ 1);
                mbar_wait(BAR_FULL(sb, r.slot), r.par);
            });
            if (tid == 0) { TL(10); TC(110); }
            if (tid == 128) TL(51);
            CS(22);
            {
                IDX();
                uint32_t h3[12];
                glu(h3, [&](int i) { return ag[64 + i]; }, [&](int i) { return au[64 + i]; });
#pragma unroll
                for (int k = 0; k < 3; ++k) stsm4(sb + (wg ? P3_SLOT1 : P3_SLOT0) * SLOT + 24576 + (pan_addr ^ (k << 5)), h3[4 * k], h3[4 * k + 1], h3[4 * k + 2], h3[4 * k + 3]);
            }
            glu(hp, [&](int i) { return ag[i]; }, [&](int i) { return au[i]; });
            if (tid == 0) { TL(11); TC(111); }
            if (tid == 128) TL(52);
            CS(23);
        }
        passes128<2, true>(hp, sb, wg, tw, r, stg);
        if (tid == 0) { TL(12); TC(112); }
        }
        {
            float acc[64], gf[32];
            mainloop64(acc, blk == 0, sb, wg, tw, r, [&] { put_h(hp, sb, wg, stg); }, [&] {
                mbar_wait(BAR_ONE(sb, EV_GA + blk), 0);
                unpack_slab(xs, xp);
                uint32_t gt[16];
#pragma unroll
                for (int cg = 0; cg < 16; ++cg) gt[cg] = lds32(sb + OFF_TAB + blk * 256 + cg * 16 + (tw & 3) * 4);
#pragma unroll
                for (int i = 0; i < 16; ++i) unpack2(gt[i], gf[2 * i], gf[2 * i + 1]);
            }, [&] { stg.acquire2(sb, wg); });
            if (tid == 0) { TL(blk ? 13 : 7); TC(blk ? 113 : 107); }
            if (tid == 128) TL(blk ? 57 : 42);
            CS(blk ? 30 : 10);
#pragma unroll
            for (int e = 0; e < 64; ++e) xs[e] = fmaf(gf[(e >> 2) * 2 + (e & 1)], acc[e], xs[e]);
        }
        if (blk) break;
        }
        {
            IDX();
#pragma unroll
            for (int p = 0; p < 2; ++p) {
                store_slab(xs, sb + OFF_STG + wg * 16384, 8192, pan_addr, 4 * p, 4 * p + 4);
                stg.publish(sb, wg, lane);
            }
            cluster_arrive();
            if (tid == 0) TL(14);
            CS(31);
        }
      } else {
        if (wg == 0) {
            const uint4 cv = *(const uint4*)(cvec + tw * 8);
            sts128(sb + OFF_STG + (tw >> 3) * 1024 + (tw & 7) * 16, pack2(silu_(bf_lo(cv.x)), silu_(bf_hi(cv.x))), pack2(silu_(bf_lo(cv.y)), silu_(bf_hi(cv.y))),
                   pack2(silu_(bf_lo(cv.z)), silu_(bf_hi(cv.z))), pack2(silu_(bf_lo(cv.w)), silu_(bf_hi(cv.w))));
            fence_async_smem();
        }
        cluster_wait();
        ep = __shfl_sync(0xffffffffu, ep, 0) / NCTA + 1;
        if (wg == 0) {
            bar_sync(1, 128);
#pragma unroll 1
            for (int p = 0; p < 4; ++p) {
                float acc[4][4] = {};
                uint32_t prev = 0;
#pragma unroll 1
                for (int kc = 0; kc < 16; ++kc) {
                    mbar_wait(BAR_FULL(sb, r.slot), r.par);
                    wg_fence();
#pragma unroll
                    for (int k = 0; k < 16; ++k)
                        wgmma_n8_ta(acc[k & 3], mk_desc(d16(sb) + r.slot * (SLOT >> 4), (k & 3) * 8192 + (k >> 2) * 2048, 8192, 1024, 1), mk_desc(d16(sb) + kc * 64, OFF_STG + (k >> 2) * 32, 16, 1024, 1));
                    wg_commit();
                    wg_wait<1>();
                    if (kc > 0 && tw < 4) mbar_arrive(BAR_EMPTY(sb, prev));
                    prev = r.slot;
                    r.next();
                }
                wg_wait<0>();
                if (tw < 4) mbar_arrive(BAR_EMPTY(sb, prev));
                if (!(tw & 3)) {
#pragma unroll
                    for (int i = 0; i < 8; ++i) {
                        asm volatile("" : "+f"(acc[i >> 1][(i & 1) * 2]) :: "memory");
                        asm volatile("st.shared.u16 [%0], %1;" :: "r"(sb + OFF_TAB + ((i >> 1) * 64 + (tw >> 5) * 16 + (i & 1) * 8 + (lane >> 2)) * 2), "h"((uint16_t)pack2(acc[i >> 1][(i & 1) * 2], 0.f)) : "memory");
                    }
                }
                bar_sync(1, 128);
                const int vec = p ? 6 - p : 2, blk = (vec - 2) * 4 + j;
                const uint32_t val = lds32(sb + OFF_TAB + tw * 4);
                if (vec == 2 || vec == 5) st_pkt(g_mod + (8 + blk) * 128 + tw, val, ep);
                else {
                    const float one = vec == 4 ? 1.f : 0.f;
                    g_par2[((blk & 3) * 16 + (tw >> 3)) * 16 + (tw & 3) * 4 + (vec - 3) * 2 + ((tw >> 2) & 1)] =
                        pack2(0.5f * bf_round(one + bf_lo(val)), 0.5f * bf_round(one + bf_hi(val)));
                }
                bar_sync(1, 128);
                if (tw == 0) {
                    if (p == 3) asm volatile("red.release.gpu.global.add.u32 [%0], 1;" :: "l"(&g_flags[FL_LN2]) : "memory");
                    TL(1 + p);
                }
            }
            if (lane < 2) mbar_arrive_cta(BAR_ONE(sb, EV_P0), lane);
        }
        r = Ring{64 % NSLOT, (64 / NSLOT) & 1};
        mbar_wait(BAR_ONE(sb, EV_P0), 0);
        mbar_wait(BAR_FULL(sb, r.slot), r.par);
        uint32_t hp[32] = {};
        passes128<4, false>(hp, sb, wg, tw, r, stg);
        put_h(hp, sb, wg, stg);
        if (PADA && sb == 0xfffffff0u) padcode<PADA + 0>(tid);
      }
    } else {
        if (warp == 8 && !aux && elect_one()) {
#pragma unroll
            for (int i = 0; i < 4; ++i) mbar_init(BAR_SREADY(sb, i), 1);
#pragma unroll
            for (int i = 0; i < 4; ++i) mbar_init(BAR_ONE(sb, EV_WIN + i), 1);
#pragma unroll
            for (int i = 0; i < 4; ++i) {
                mbar_expect_tx(BAR_SREADY(sb, i), 8192);
                tma_load3(sb + OFF_STG + i * 8192, &mp.x, j * 128 + (i & 1) * 64, m * 64 + (i >> 1) * 32, BAR_SREADY(sb, i));
            }
#pragma unroll 1
            for (int i = 0; i < 4; ++i) {
                mbar_expect_tx(BAR_ONE(sb, EV_WIN + i), 8192);
                tma_load(sb + 5 * SLOT + i * 8192, &mp.wm8, 2 * i * 6144 + (m * 8 + j) * 16, 0, BAR_ONE(sb, EV_WIN + i));
                tma_load(sb + 5 * SLOT + i * 8192 + 4096, &mp.wm8, (2 * i + 1) * 6144 + (m * 8 + j) * 16, 0, BAR_ONE(sb, EV_WIN + i));
            }
        }
        __syncwarp();
        asm volatile("setmaxnreg.dec.sync.aligned.u32 56;");
        if (elect_one()) {
            if (warp == 8) {
                prefetch_map(&mp.wqkv); prefetch_map(&mp.wmod);
            } else if (warp < 11) {
                mbar_init(BAR_EMPTY(sb, NSLOT), 1);
#pragma unroll
                for (int i = 0; i < 2; ++i) { mbar_init(BAR_SFULL(sb, (warp - 9) * 2 + i), 4); if (aux) mbar_init(BAR_SREADY(sb, (warp - 9) * 2 + i), 1); }
#pragma unroll
                for (int i = 0; i < 3; ++i) {
                    mbar_init(BAR_EMPTY(sb, (warp - 9) * 3 + i), 4);
                    mbar_init(BAR_FULL(sb, (warp - 9) * 3 + i), 1); mbar_init(BAR_FULL(sb, (warp - 9) * 3 + i) + AF_REL, 1);
                }
            } else {
#pragma unroll
                for (int i = EV_P0; i < EV_COUNT; ++i) mbar_init(BAR_ONE(sb, i), i == EV_P0 ? 8 : 1);
            }
            asm volatile("fence.mbarrier_init.release.cluster;" ::: "memory");
        }
        __syncwarp();
        cluster_arrive();
        ep = 0;
        if (warp != 8 || aux) ep = flag_get(g_flags + FL_DONE);
        cluster_wait();
        ep = __shfl_sync(0xffffffffu, ep, 0) / NCTA + 1;
        if (warp == 8) {
            const bool el = elect_one();
            Ring r{0, 1};
            if (__builtin_expect(aux, 0)) {
                {
                    uint32_t n = 0;
                    while (!__all_sync(0xffffffffu, ld_pkt16(pt.mail->mod1 + 256).z == ep)) { SPIN_GUARD(n); __nanosleep(200); }
                }
#pragma unroll 1
                for (int it = 0; it < 64; ++it) {
                    const int col = (it < 16 ? 2048 : 6144 - (it >> 4) * 1024) + j * 256;
                    mbar_wait(BAR_EMPTY(sb, r.slot), r.par);
                    const uint32_t st = sb + r.slot * SLOT, fb = BAR_FULL(sb, r.slot);
                    if (el) {
                        mbar_expect_tx(fb, 32768);
#pragma unroll
                        for (int b = 0; b < 4; ++b) tma_load_ef(st + b * 8192, &mp.wmod, col + b * 64, (it & 15) * 64, fb);
                    }
                    r.next();
                }
                mbar_wait(BAR_ONE(sb, EV_P0), 0);
                const CUtensorMap* wm = rank ? &mp.wu : &mp.wg;
#pragma unroll 1
                for (int g = 0; g < 128; ++g) {
                    const int mx = (j >> 1) * 8 + (g >> 5) * 2 + rank, k0 = ((g & 14) << 6) + ((g & 16) << 2) + ((g & 1) << 5);
                    if (!(g & 15) && g <= 32) mbar_wait(BAR_ONE(sb, EV_H0 + (g >> 4)), 0);
                    mbar_wait(BAR_EMPTY(sb, r.slot), r.par);
                    const uint32_t st = sb + r.slot * SLOT, fb = BAR_FULL(sb, r.slot);
                    if (el) {
                        mbar_expect_tx(fb, 24576);
                        tma_load_mc(st + 8192 + rank * 4096, wm, HC3, k0, fb);
                        tma_load_mc(st + 16384 + rank * 4096, wm, HC3 + 64, k0, fb);
                        tma_load(st, &mp.h2l, k0, mx * 128, fb);
                    }
                    r.next();
                }
            } else {
#pragma unroll 1
                for (int it = 0; it < 32; ++it) {
                    const int cb = j * 128 + rank * 64, k0 = kof(it, 2, j);
                    if (it == BW0) mbar_wait(BAR_ONE(sb, BWEV), 0);
                    if (it == BW1) mbar_wait(BAR_ONE(sb, EV_PAR), 0);
                    if (it == 5) mbar_wait(BAR_ONE(sb, EV_P0), 0);
                    if (it == AG0) mbar_wait(BAR_ONE(sb, (AGW & 1) ? EV_AGO : EV_FGO), 0);
                    mbar_wait(BAR_EMPTY(sb, r.slot), r.par);
                    const uint32_t st = sb + r.slot * SLOT, fb = BAR_FULL(sb, r.slot);
                    if (el) {
                        mbar_expect_tx(fb, it < 4 ? 24576 : 28672);
                        tma_load_mc(st + 24576 - rank * 16384, &mp.wqkv, 1024 + cb, k0, fb);
                        tma_load_mc(st + 28672 - rank * 16384, &mp.wqkv, 2048 + cb, k0, fb);
                        tma_load_mc(st + 16384 + rank * 4096, &mp.wqkv, cb, k0, fb);
                        if (it < 4) mbar_arrive(fb + AF_REL);
                        if (it == PFWO + (m >> 1)) { tma_prefetch(&mp.wo, j * 128, m * 64); tma_prefetch(&mp.wo, j * 128 + 64, m * 64); }
                        if (it >= PFG && it < PFG + PFN && (it & 7) == grp) {
                            const int kp = kof(it - PFG + PFO, 2, j);
                            tma_prefetch(rank ? &mp.wu : &mp.wg, hcol(0, j), kp); tma_prefetch(rank ? &mp.wu : &mp.wg, hcol(0, j) + 64, kp);
                            asm volatile("cp.async.bulk.prefetch.tensor.3d.L2.global [%0, {%1, %2, %3}];" :: "l"(rank ? &mp.wu3 : &mp.wg3), "r"(0), "r"(j), "r"(kp) : "memory");
                        }
                    }
                    r.next();
                }
                if (el) mbar_arrive(BAR_ONE(sb, EV_KV));
#pragma unroll 1
                for (int it = 0; it < 16; ++it) {
                    const int k0 = kof(it, 1, j);
                    if (it == AG1) mbar_wait(BAR_ONE(sb, (AGW & 2) ? EV_AGO1 : EV_FGO1), 0);
                    mbar_wait(BAR_EMPTY(sb, r.slot), r.par);
                    const uint32_t st = sb + r.slot * SLOT, fb = BAR_FULL(sb, r.slot);
                    if (el) {
                        mbar_expect_tx(fb, it < 2 ? 32768 : 24576);
                        tma_load_mc(st + 16384 + rank * 8192, &mp.wo, j * 128 + rank * 64, k0, fb);
                        if (it < 2) {
                            tma_load3(st, &mp.x, j * 128, m * 64 + it * 32, fb); tma_load3(st + 8192, &mp.x, j * 128 + 64, m * 64 + it * 32, fb);
                            mbar_arrive(fb + AF_REL);
                        }
                        if (it == 6) { prefetch_map(rank ? &mp.wu : &mp.wg); prefetch_map(rank ? &mp.wu3 : &mp.wg3); }
                    }
                    r.next();
                }
                const CUtensorMap* wm = rank ? &mp.wu : &mp.wg;
#pragma unroll 1
                for (int g = 0; g < 96; ++g) {
                    if (g == AG2) mbar_wait(BAR_ONE(sb, (AGW & 4) ? EV_AGO2 : EV_FGO2), 0);
                    const int p = g >> 5, cb = hcol(p, j), k0 = p == 0 ? kof(g, 2, j) : (g & 31) * 32;
                    mbar_wait(BAR_EMPTY(sb, r.slot), r.par);
                    const uint32_t st = sb + r.slot * SLOT, fb = BAR_FULL(sb, r.slot);
                    if (el) {
                        mbar_expect_tx(fb, (g < 4 || p > 0) ? 24576 : 28672);
                        tma_load_mc(st + 8192 + rank * 4096, wm, cb, k0, fb);
                        tma_load_mc(st + 16384 + rank * 4096, wm, cb + 64, k0, fb);
                        if (p == 0) tma_load3_mc(st + 24576 + rank * 4096, rank ? &mp.wu3 : &mp.wg3, j, k0, fb);
                        else tma_load(st, &mp.h2l, k0, m * 128, fb);
                        if (g < 4) mbar_arrive(fb + AF_REL);
                        if ((g & 7) == grp && g + PFC >= 96) tma_prefetch(&mp.wd, j * 128 + rank * 64, (g + PFC - 96) * 64);
                        if (g == 60) { prefetch_map(&mp.wd); prefetch_map(&mp.hb); }
                    }
                    r.next();
                }
#pragma unroll 1
                for (int g = 0; g < 56; ++g) {
                    if (g == 0 || (g & 15) == 6 && g > 6) mbar_wait(BAR_ONE(sb, EV_H0 + (g >> 4)), 0);
                    const int k0 = g * 64;
                    mbar_wait(BAR_EMPTY(sb, r.slot), r.par);
                    const uint32_t st = sb + r.slot * SLOT, fb = BAR_FULL(sb, r.slot);
                    if (el) {
                        mbar_expect_tx(fb, 32768);
                        tma_load_mc(st + 16384 + rank * 8192, &mp.wd, j * 128 + rank * 64, k0, fb);
                        tma_load(st, &mp.hb, k0, m * 128, fb); tma_load(st + 8192, &mp.hb, k0, m * 128 + 64, fb);
                        if ((g & 7) == grp && g + PFC < 56) tma_prefetch(&mp.wd, j * 128 + rank * 64, k0 + PFC * 64);
                    }
                    r.next();
                }
            }
        } else if (__builtin_expect(aux, 0)) {
            if (warp < 11) {
                const uint32_t w = warp - 9;
                const bool el = elect_one();
#pragma unroll 1
                for (int p = 0; p < 4; ++p) {
                    const int mx = (j >> 1) * 8 + p * 2 + rank;
                    if (el) { mbar_arrive(BAR_SREADY(sb, w * 2)); mbar_arrive(BAR_SREADY(sb, w * 2 + 1)); }
                    mbar_wait2(BAR_SFULL(sb, w * 2), BAR_SFULL(sb, w * 2 + 1), p & 1);
                    if (p < 3) pause(w ? HD1 : HD0);
                    if (el) tma_store(&mp.hb, HC3, mx * 128 + w * 64, sb + OFF_STG + w * 16384);
                    if (p < 3) pause(HP);
                    if (el) {
                        tma_store(&mp.hb, HC3 + 64, mx * 128 + w * 64, sb + OFF_STG + w * 16384 + 8192);
                        bulk_commit(); bulk_wait_fence(); flag_set(g_flags + FL_AUX + mx * 2 + w, ep * 8 + ST_H + 3);
                    }
                }
            } else {
                mbar_wait(BAR_ONE(sb, EV_P0), 0);
#pragma unroll 1
                for (int i = 0; i < 5; ++i) {
                    const uint32_t* f = g_flags + FL_PROG + fidx((j >> 1) * 8 + (i ? i - 1 : 0) * 2 + rank, lane >> 4, lane & (i ? 15 : 14));
                    uint32_t n = 0;
                    while (!__all_sync(0xffffffffu, (int32_t)(flag_get(f) - (ep * 8 + ST_H2)) >= 0)) { SPIN_GUARD(n); __nanosleep(200); }
                    if (i < 2) pause(AUXD);
                    if (lane == 0 && (i < 2 || i == 4)) mbar_arrive(BAR_ONE(sb, EV_H0 + (i < 2 ? i : 2)));
                }
            }
        } else if (warp == 11) {
            const bool el = elect_one();
            const int row0 = m * 128;
            if (el) { prefetch_map(&mp.h1h); prefetch_map(&mp.h2h); prefetch_map(&mp.h2l); }
            auto gate = [&](int vec, int ev) {
                const uint32_t lane = Idx().lane;
                uint4 v; uint32_t n = 0;
                while (true) {
                    v = ld_pkt2(g_mod + vec * 512 + j * 64 + lane * 2);
                    if (__all_sync(0xffffffffu, v.y == ep && v.w == ep)) break;
                    SPIN_GUARD(n); __nanosleep(300);
                }
                asm volatile("st.shared.v2.u32 [%0], {%1, %2};" :: "r"(sb + OFF_TAB + (ev - EV_GA) * 256 + lane * 8), "r"(v.x), "r"(v.z) : "memory");
                __syncwarp();
                if (lane == 0) mbar_arrive(BAR_ONE(sb, ev));
            };
            {
                const uint4* pk = pt.mail->mod1 + grp * 512 + j * 32 + lane;
                uint4 a, b; uint32_t n = 0;
                mbar_wait(BAR_ONE(sb, EV_WIN3), 0);
                while (true) {
                    a = ld_pkt16(pk); b = ld_pkt16(pk + 256);
                    if (__all_sync(0xffffffffu, a.z == ep && b.z == ep)) break;
                    SPIN_GUARD(n);
                }
                sts128(sb + OFF_PAR + lane * 16, a.x, a.y, b.x, b.y);
                __syncwarp();
                if (lane == 0) { mbar_arrive(BAR_ONE(sb, EV_PAR)); TL(46); }
            }
            mbar_wait(BAR_ONE(sb, EV_P0), 0);
            Ring r{0, 1};
#pragma unroll 1
            for (int ph = 0; ph < 3; ++ph) {
                const uint32_t lane = Idx().lane;
                const int sh = ph == 1 ? 1 : 2, nst = 8 << sh;
                const uint32_t half = 16384 >> sh, target = ep * 8 + ST_H1 + ph;
                const CUtensorMap* tm = ph == 0 ? &mp.h1h : ph == 1 ? &mp.o : &mp.h2h;
                if (ph == 1) {
                    gate(2, EV_GA);
                    mbar_wait(BAR_SREADY(sb, 1), 1);
                    fetch_halo<2>(g_halo + ((m - 1) * 8 + j) * 512 + 128 + lane, m == 0, sb + OFF_STG + 8192 + lane * 16,
                                  [&] { __syncwarp(); if (lane < 2) mbar_arrive(BAR_ONE(sb, EV_TAIL + 2 * lane)); });
                    CS(32);
                }
                if (ph == 2) {
                    uint32_t n = 0;
                    while ((int32_t)(flag_get(g_flags + FL_LN2) - ep * 4) < 0) { SPIN_GUARD(n); __nanosleep(200); }
                    const uint4 v = __ldcg((const uint4*)(g_par2 + j * 128) + lane);
                    sts128(sb + OFF_PAR + lane * 16, v.x, v.y, v.z, v.w);
                    __syncwarp();
                    if (lane == 0) mbar_arrive(BAR_ONE(sb, EV_LN2));
                }
                const uint32_t* const fl = g_flags + FL_PROG + fidx(m, lane >> 4, kof(lane & 15, 1, j) >> 6);
                const uint32_t lw = ~lane & 1, lt = lane >> 1, ls = (r.slot + lt) % NSLOT, lk = kof(lt, sh, j), lb = BAR_FULL(sb, ls) + (lw ? 0 : AF_REL);
                const uint32_t* const lf = g_flags + FL_PROG + fidx(m, lw, lk >> 6);
                int fr = 1 << sh;
                uint32_t todo = 0x3ffffu >> (2 * fr) << (2 * fr), have = ~todo, n = 0, v = 0;
                r.skip(fr);
#pragma unroll 1
                for (; fr < NSLOT; ++fr) { mbar_wait(BAR_EMPTY(sb, r.slot), r.par); r.next(); }
                if (ph == XST - 1) CS(33);
                v = flag_get(lf);
                do {
                    while (ph == 2 && fr < FRCAP && mbar_test(BAR_EMPTY(sb, r.slot), r.par)) { ++fr; r.next(); }
                    SPIN_GUARD(n);
                    const bool ok = (int32_t)(v - target) >= 0;
                    v = flag_get(lf);
                    have |= __ballot_sync(0xffffffffu, ok);
                    const uint32_t go = have & todo & ((1u << (2 * fr)) - 1);
                    if ((go >> lane) & 1) {
                        if (!lw) mbar_expect_tx(lb, half);
                        tma_load(sb + ls * SLOT + lw * half, tm, lk, row0 + lw * 64, lb);
                    }
                    __syncwarp();
                    if (lane < 2 && (todo & (0x555u << lane)) && !(todo & ~go & (0x555u << lane))) mbar_arrive(BAR_ONE(sb, (lane ? EV_FGO : EV_AGO) + ph));
                    if (ph == XST - 1) { if (go & (1u << (2 << sh))) CS(34); if (go & (2u << (2 << sh))) CS(35); if (todo & 0x555u) CS(36); if (todo & 0xaaau) CS(37); }
                    todo &= ~go;
                } while (~have);
                if (ph == XST - 1) CS(38);
                int k = kof(fr, sh, j);
#pragma unroll 1
                for (; fr < nst; ++fr) {
                    if (fr == 9 || fr == 18) {
                        const uint32_t skip = fr == 9 << (sh - 1) ? 0 : ~0x01fc01fcu;
                        while (~(__ballot_sync(0xffffffffu, (int32_t)(flag_get(fl) - target) >= 0) | skip)) SPIN_GUARD(n);
                    }
                    const uint32_t st = sb + r.slot * SLOT, fb = BAR_FULL(sb, r.slot);
                    mbar_wait(BAR_EMPTY(sb, r.slot), r.par);
                    if (el) {
                        tma_load(st + half, tm, k, row0 + 64, fb);
                        mbar_expect_tx(fb + AF_REL, half);
                        tma_load(st, tm, k, row0, fb + AF_REL);
                    }
                    if (ph == XST - 1 && fr == 9) CS(39);
                    r.next();
                    k = kof(fr + 1, sh, j);
                }
            }
#pragma unroll 1
            for (int p = 0; p < 4; ++p) {
                const uint32_t* f = g_flags + (p < 3 ? FL_PROG + m * 32 + lane : FL_AUX + m * 2 + (lane & 1));
                uint32_t n = 0;
                while (!__all_sync(0xffffffffu, (int32_t)(flag_get(f) - (ep * 8 + ST_H + p)) >= 0)) { SPIN_GUARD(n); __nanosleep(300); }
                if (el) mbar_arrive(BAR_ONE(sb, EV_H0 + p));
                if (p == 0) gate(5, EV_GB);
            }
        } else {
            const uint32_t w = warp - 9;
            const int row0 = m * 128 + w * 64;
            const uint32_t stg = sb + OFF_STG + w * 16384;
            uint32_t* const fl = g_flags + FL_PROG + fidx(m, w, 2 * j);
            uint32_t b = 0, par = 0;
            const bool el = elect_one();
            auto store = [&](const CUtensorMap* tm, int col, bool nat = false) {
                mbar_wait(BAR_SFULL(sb, w * 2 + b), (par >> b) & 1);
                par ^= 1u << b;
                if (el) {
                    if (nat) tma_store3(tm, col, row0 >> 1, 0, stg + b * 8192); else tma_store(tm, col, row0, stg + b * 8192);
                    bulk_commit();
                }
                b ^= 1;
            };
            auto send2 = [&](const CUtensorMap* tm, const uint32_t* buf, int step) {
                const uint32_t* const q = buf + (size_t)((row0 + lane) * (D_ / 2) + j * 64 + 31);
                store(tm, j * 128);
                if (step == XST) CS(33);
                uint32_t z = landed(el, q, D_ / 2, pt.zero);
                if (el) flag_set(fl, ep * 8 + step + z);
                if (step == XST) CS(34);
                if (step != ST_O) { mbar_wait(BAR_ONE(sb, EV_FGO + step - ST_H1), 0); pause(step == ST_H1 ? (w ? P1H : P1H + 1000) : w ? P2L : P2F); }
                store(tm, j * 128 + 64);
                if (step == XST) CS(35);
                z = landed(el, q + 32, D_ / 2, pt.zero);
                if (el) flag_set(fl + 1, ep * 8 + step + z);
                if (step == XST) CS(36);
            };
            auto free2 = [&]() { if (el) { mbar_arrive(BAR_SREADY(sb, w * 2)); mbar_arrive(BAR_SREADY(sb, w * 2 + 1)); } };
            if (el) { prefetch_map(&mp.h1s); prefetch_map(&mp.o); prefetch_map(&mp.out); prefetch_map(&mp.wo); }
            send2(&mp.h1s, pt.h1, ST_H1);
            if (w == 0) TL(47);
            free2();
            mbar_wait(BAR_ONE(sb, EV_KV), 0);
            mbar_wait(BAR_SREADY(sb, 0), 1);
            fetch_halo<1>(g_halo + ((m - 1) * 8 + j) * 512 + w * 256 + lane, m == 0, sb + OFF_STG + w * 4096 + lane * 16, [&] { bar_arrive(NB_TAIL + 2 * w, 64); CS(38); });
            send2(&mp.o, pt.o, ST_O);
            if (w == 0) TL(40); else TL(38);
            free2();
            send2(&mp.o, pt.o, ST_H2);
            if (el) { prefetch_map(&mp.hbs); prefetch_map(&mp.hb3); }
            if (w == 0) TL(37);
            free2();
#pragma unroll 1
            for (int p = 0; p < 3; ++p) {
                const int col = hcol(p, j);
                mbar_wait2(BAR_SFULL(sb, w * 2), BAR_SFULL(sb, w * 2 + 1), par & 1);
                par ^= 3;
#pragma unroll 1
                for (int i = 0; i < (p ? 2 : 3) * NSPL; ++i) {
                    pause(i ? HP / NSPL : p == 2 ? (w ? HE1 : HE0) : w ? HD1 : HD0);
                    const int pn = i / NSPL, ro = (i % NSPL) * (64 / NSPL);
                    if (el) {
                        if (pn < 2) tma_store(&mp.hbs, col + pn * 64, row0 + ro, stg + i * (8192 / NSPL));
                        else tma_store3(&mp.hb3, 0, j, row0 + ro, sb + (w ? P3_SLOT1 : P3_SLOT0) * SLOT + 24576 + ro * 128);
                        bulk_commit();
                    }
                }
                if (el) bulk_wait_read();
                free2();
                if (el) { bulk_wait_fence(); flag_set(fl, ep * 8 + ST_H + p); flag_set(fl + 1, ep * 8 + ST_H + p); }
            }
            cluster_arrive_early = true;
            cluster_arrive();
            store(&mp.out, j * 128, true); store(&mp.out, j * 128 + 64, true);
            if (el) bulk_wait_read();
        }
        __syncwarp();
    }
    if (aux || (wg == 2 && !cluster_arrive_early)) cluster_arrive();
    cluster_wait();
    if (KDEBUG == 5) __syncthreads();
    if (tid == 0) {
        TL(15);
        flag_add(pt.mail->flags + FL_DONE);
    }
}

typedef CUresult (*EncodeFn)(CUtensorMap*, CUtensorMapDataType, cuuint32_t, void*, const cuuint64_t*, const cuuint64_t*, const cuuint32_t*,
                             const cuuint32_t*, CUtensorMapInterleave, CUtensorMapSwizzle, CUtensorMapL2promotion, CUtensorMapFloatOOBfill);

void make_map(EncodeFn fn, CUtensorMap* m, const void* ptr, uint64_t rows, uint64_t cols, uint32_t brows, uint32_t bcols) {
    cuuint64_t dims[2] = {cols, rows}, strides[1] = {cols * 2};
    cuuint32_t box[2] = {bcols, brows}, es[2] = {1, 1};
    fn(m, CU_TENSOR_MAP_DATA_TYPE_BFLOAT16, 2, (void*)ptr, dims, strides, box, es, CU_TENSOR_MAP_INTERLEAVE_NONE,
       bcols == 64 ? CU_TENSOR_MAP_SWIZZLE_128B : bcols == 32 ? CU_TENSOR_MAP_SWIZZLE_64B : CU_TENSOR_MAP_SWIZZLE_NONE, CU_TENSOR_MAP_L2_PROMOTION_L2_256B, CU_TENSOR_MAP_FLOAT_OOB_FILL_NONE);
}

void make_map3(EncodeFn fn, CUtensorMap* m, const void* ptr) {
    cuuint64_t dims[3] = {D_, S_ / 2, 2}, strides[2] = {4 * D_, 2 * D_};
    cuuint32_t box[3] = {64, 32, 2}, es[3] = {1, 1, 1};
    fn(m, CU_TENSOR_MAP_DATA_TYPE_BFLOAT16, 3, (void*)ptr, dims, strides, box, es, CU_TENSOR_MAP_INTERLEAVE_NONE,
       CU_TENSOR_MAP_SWIZZLE_128B, CU_TENSOR_MAP_L2_PROMOTION_L2_256B, CU_TENSOR_MAP_FLOAT_OOB_FILL_NONE);
}

void make_map48(EncodeFn fn, CUtensorMap* m, const void* ptr, uint64_t rows, uint32_t brows) {
    cuuint64_t dims[3] = {48, 8, rows}, strides[2] = {96, 2 * F_};
    cuuint32_t box[3] = {64, 1, brows}, es[3] = {1, 1, 1};
    fn(m, CU_TENSOR_MAP_DATA_TYPE_BFLOAT16, 3, (void*)ptr, dims, strides, box, es, CU_TENSOR_MAP_INTERLEAVE_NONE,
       CU_TENSOR_MAP_SWIZZLE_128B, CU_TENSOR_MAP_L2_PROMOTION_L2_256B, CU_TENSOR_MAP_FLOAT_OOB_FILL_NONE);
}

}

extern "C" void kernel_launch(void* const* d_in, const int* in_sizes, int n_in, void* d_out, int out_size) {
    (void)in_sizes; (void)n_in; (void)out_size;
    void* fnp = nullptr;
    cudaDriverEntryPointQueryResult qr;
    cudaGetDriverEntryPoint("cuTensorMapEncodeTiled", &fnp, cudaEnableDefault, &qr);
    EncodeFn fn = (EncodeFn)fnp;
    void *h1, *o, *h2, *hb, *mail;
    cudaGetSymbolAddress(&h1, g_h1);
    cudaGetSymbolAddress(&mail, g_mail);
    cudaGetSymbolAddress(&o, g_o);
    cudaGetSymbolAddress(&hb, g_hb);
    h2 = o;
    Maps mp;
    make_map(fn, &mp.h1h, h1, S_, D_, 64, 32);
    make_map(fn, &mp.h2h, h2, S_, D_, 64, 32);
    make_map(fn, &mp.h1s, h1, S_, D_, 64, 64);
    make_map(fn, &mp.o, o, S_, D_, 64, 64);
    make_map(fn, &mp.h2l, h2, S_, D_, 128, 32);
    make_map(fn, &mp.hb, hb, S_, F_, 64, 64);
    make_map(fn, &mp.wqkv, d_in[1], D_, 3 * D_, 32, 64);
    make_map(fn, &mp.wo, d_in[2], D_, D_, 64, 64);
    make_map(fn, &mp.wg, d_in[4], D_, F_, 32, 64);
    make_map(fn, &mp.wu, d_in[5], D_, F_, 32, 64);
    make_map(fn, &mp.wd, d_in[6], F_, D_, 64, 64);
    make_map(fn, &mp.wmod, d_in[8], D_, 6 * D_, 64, 64);
    make_map(fn, &mp.wm8, d_in[8], D_ / 8, 8 * 6 * D_, 128, 16);
    make_map3(fn, &mp.x, d_in[0]);
    make_map3(fn, &mp.out, d_out);
    make_map48(fn, &mp.wg3, d_in[4], D_, 32);
    make_map48(fn, &mp.wu3, d_in[5], D_, 32);
    make_map48(fn, &mp.hb3, hb, S_, 64 / NSPL);
    make_map(fn, &mp.hbs, hb, S_, F_, 64 / NSPL, 64);
    cudaFuncSetAttribute(fused_block_kernel, cudaFuncAttributeMaxDynamicSharedMemorySize, SMEM_BYTES);
    cudaLaunchConfig_t cfg = {};
    cfg.gridDim = dim3(NCTA); cfg.blockDim = dim3(384); cfg.dynamicSmemBytes = SMEM_BYTES; cfg.stream = cudaStreamPerThread;
    cudaLaunchAttribute at[1];
    at[0].id = cudaLaunchAttributeClusterDimension; at[0].val.clusterDim.x = 2; at[0].val.clusterDim.y = 1; at[0].val.clusterDim.z = 1;
    cfg.attrs = at; cfg.numAttrs = 1;
    const Ptrs pt{(const __nv_bfloat16*)d_in[7], (Mail*)mail, (const uint32_t*)h1, (const uint32_t*)o, 0};
    cudaLaunchKernelEx(&cfg, fused_block_kernel, pt, mp);
}
```
